```python
import torch

def _softmax(x, axis=-1):
    return torch.softmax(x, dim=axis)
def _gelu(x):
    return torch.nn.functional.gelu(x, approximate="tanh")
def _silu(x):
    return torch.nn.functional.silu(x)
def _sigmoid(x):
    return torch.sigmoid(x)
def _layernorm(x, axis=-1, eps=1e-5):
    m = x.mean(dim=axis, keepdim=True)
    v = x.var(dim=axis, keepdim=True, unbiased=False)
    return (x - m) / torch.sqrt(v + eps)
def _scatter_add(tgt, idx, src, axis=0):
    return tgt.clone().index_add_(axis, idx, src)
def _segment_sum(src, seg, n):
    out = torch.zeros((n,) + src.shape[1:], dtype=src.dtype)
    return out.index_add_(0, seg, src)
def _pad(x, pw):
    flat = tuple(v for pair in reversed(pw) for v in pair)
    return torch.nn.functional.pad(x, flat)

kernel_name = 'sequential_preLN__softmax_full_mha__glu_gated_bilinear__prompt'

def setup_inputs():

    _w = (lambda a: (lambda t: t.to(torch.bfloat16) if t.is_floating_point() else t)(torch.as_tensor(a)))
    def _A_setup():
        B, S, D = 1, 2048, 640
        return {
            "x": _w((lambda *s: torch.randn(*s, dtype=torch.bfloat16) * 0.05)(B, S, D)),
            "wqkv": _w((lambda *s: torch.randn(*s, dtype=torch.bfloat16) * 0.05)(D, 3 * D)),
            "wo": _w((lambda *s: torch.randn(*s, dtype=torch.bfloat16) * 0.05)(D, D)),
        }
    _A_in = _A_setup()

    def _B_setup():
        B, S, D, F = 1, 2048, 640, 1728
        return {
            "x": _w((lambda *s: torch.randn(*s, dtype=torch.bfloat16) * 0.05)(B, S, D)),
            "w_gate": _w((lambda *s: torch.randn(*s, dtype=torch.bfloat16) * 0.8)(D, F) * (D ** -0.5)),
            "w_up": _w((lambda *s: torch.randn(*s, dtype=torch.bfloat16) * 0.8)(D, F) * (D ** -0.5)),
            "w_down": _w((lambda *s: torch.randn(*s, dtype=torch.bfloat16) * 0.8)(F, D) * (F ** -0.5)),
        }
    _B_in = _B_setup()

    return {
        "A_x": _A_in["x"],
        "A_wqkv": _A_in["wqkv"],
        "A_wo": _A_in["wo"],
        "B_x": _B_in["x"],
        "B_w_gate": _B_in["w_gate"],
        "B_w_up": _B_in["w_up"],
        "B_w_down": _B_in["w_down"],
    }

def reference(A_x, A_wqkv, A_wo, B_x, B_w_gate, B_w_up, B_w_down):
    def _A_ref(x, wqkv, wo):
        B, S, D = x.shape
        H = 32; Dh = D // H
        qkv = (lambda x, *d: x.permute(*d))((x @ wqkv).reshape(B, S, 3, H, Dh), 2, 0, 3, 1, 4)
        q, k, v = qkv[0], qkv[1], qkv[2]
        scale = Dh ** -0.5
        scores = torch.einsum("bhqd,bhkd->bhqk", q, k) * scale
        p = _softmax(scores, axis=-1)
        o = torch.einsum("bhqk,bhkd->bhqd", p, v)
        return (lambda x, *d: x.permute(*d))(o, 0, 2, 1, 3).reshape(B, S, D) @ wo

    def _B_ref(x, w_gate, w_up, w_down):
        g = torch.einsum("bsd,df->bsf", x, w_gate)
        u = torch.einsum("bsd,df->bsf", x, w_up)
        h = g * u
        return torch.einsum("bsf,fd->bsd", h, w_down)

    x = A_x
    h = x + _A_ref(_layernorm(x, axis=-1), A_wqkv, A_wo)
    h2 = h + _B_ref(_layernorm(h, axis=-1), B_w_gate, B_w_up, B_w_down)
    return h2
```

```cpp
#include <cuda_runtime.h>
#include <cuda_bf16.h>
#include <cuda.h>
#include <stdint.h>

typedef __nv_bfloat16 bf16;

constexpr int S_ = 2048, D_ = 640, F_ = 1728;
constexpr int HEAD_IMG = 98304;
constexpr uint32_t POLY_MASK = 0xBBAB;
constexpr float QSCALE = 0.22360679774997896f * 1.4426950408889634f;

__device__ uint4 g_qkv[96 * HEAD_IMG / 16];
__device__ uint4 g_o[S_ * D_ / 8];
__device__ uint4 g_h[S_ * D_ / 8];
__device__ uint4 g_hh[S_ * F_ / 8];
__device__ uint4 g_wo[D_ * D_ / 8];
__device__ uint4 g_wgu[2 * D_ * F_ / 8];
__device__ uint4 g_wd[F_ * D_ / 8];
__device__ float2 g_rowstat[S_];
__device__ float g_cpart[16 * 2048];
__device__ float g_csgu[2 * F_];
__device__ float2 g_hpart[S_ * 8];
__device__ unsigned g_cnt[24 * 32];

__device__ __forceinline__ uint32_t smem_u32(const void* p) { return (uint32_t)__cvta_generic_to_shared(p); }
__device__ __forceinline__ void mbar_init(uint32_t a, uint32_t c) {
  asm volatile("mbarrier.init.shared::cta.b64 [%0], %1;" ::"r"(a), "r"(c) : "memory");
}
__device__ __forceinline__ void mbar_expect(uint32_t a, uint32_t bytes) {
  asm volatile("mbarrier.arrive.expect_tx.shared::cta.b64 _, [%0], %1;" ::"r"(a), "r"(bytes) : "memory");
}
__device__ __forceinline__ void mbar_arrive(uint32_t a) {
  asm volatile("mbarrier.arrive.shared::cta.b64 _, [%0];" ::"r"(a) : "memory");
}
__device__ __forceinline__ void mbar_arrive_cta(uint32_t a, uint32_t cta) {
  asm volatile("{\n.reg .b32 r;\nmapa.shared::cluster.u32 r, %0, %1;\n"
               "mbarrier.arrive.release.cluster.shared::cluster.b64 _, [r];\n}" ::"r"(a), "r"(cta) : "memory");
}
__device__ __forceinline__ bool mbar_try(uint32_t a, uint32_t ph) {
  uint32_t ok;
  asm volatile("{\n.reg .pred p;\nmbarrier.try_wait.parity.shared::cta.b64 p, [%1], %2;\nselp.u32 %0, 1, 0, p;\n}"
               : "=r"(ok) : "r"(a), "r"(ph) : "memory");
  return ok;
}
__device__ __forceinline__ bool mbar_try_cluster(uint32_t a, uint32_t ph) {
  uint32_t ok;
  asm volatile("{\n.reg .pred p;\nmbarrier.try_wait.parity.acquire.cluster.shared::cta.b64 p, [%1], %2;\n"
               "selp.u32 %0, 1, 0, p;\n}" : "=r"(ok) : "r"(a), "r"(ph) : "memory");
  return ok;
}
__device__ __noinline__ void wait_timeout() { __trap(); }
__device__ __forceinline__ void mbar_wait(uint32_t a, uint32_t ph) {
  if (mbar_try(a, ph)) return;
  uint32_t it = 0;
  while (!mbar_try(a, ph)) if (++it > (1u << 22)) wait_timeout();
}
__device__ __forceinline__ void mbar_wait_cluster(uint32_t a, uint32_t ph) {
  if (mbar_try_cluster(a, ph)) return;
  uint32_t it = 0;
  while (!mbar_try_cluster(a, ph)) if (++it > (1u << 22)) wait_timeout();
}
__device__ __forceinline__ void tma2d(uint32_t dst, const CUtensorMap* m, int c0, int c1, uint32_t bar) {
  asm volatile("cp.async.bulk.tensor.2d.shared::cluster.global.mbarrier::complete_tx::bytes [%0], [%1, {%3, %4}], [%2];"
               ::"r"(dst), "l"(m), "r"(bar), "r"(c0), "r"(c1) : "memory");
}
__device__ __forceinline__ void tma2d_mc(uint32_t dst, const CUtensorMap* m, int c0, int c1, uint32_t bar) {
  asm volatile("cp.async.bulk.tensor.2d.shared::cluster.global.mbarrier::complete_tx::bytes.multicast::cluster "
               "[%0], [%1, {%3, %4}], [%2], %5;"
               ::"r"(dst), "l"(m), "r"(bar), "r"(c0), "r"(c1), "h"((uint16_t)3) : "memory");
}
__device__ __forceinline__ void bulk_ld(uint32_t dst, const void* src, uint32_t bytes, uint32_t bar) {
  asm volatile("cp.async.bulk.shared::cluster.global.mbarrier::complete_tx::bytes [%0], [%1], %2, [%3];"
               ::"r"(dst), "l"(src), "r"(bytes), "r"(bar) : "memory");
}
__device__ __forceinline__ void bulk_ld_mc(uint32_t dst, const void* src, uint32_t bytes, uint32_t bar) {
  asm volatile("cp.async.bulk.shared::cluster.global.mbarrier::complete_tx::bytes.multicast::cluster "
               "[%0], [%1], %2, [%3], %4;"
               ::"r"(dst), "l"(src), "r"(bytes), "r"(bar), "h"((uint16_t)3) : "memory");
}
__device__ __forceinline__ void cluster_sync() {
  __syncwarp();
  asm volatile("barrier.cluster.arrive.aligned;\nbarrier.cluster.wait.aligned;" ::: "memory");
}
__device__ __forceinline__ void pdl_wait() { asm volatile("griddepcontrol.wait;" ::: "memory"); }
__device__ __forceinline__ void pdl_trigger() { asm volatile("griddepcontrol.launch_dependents;" ::: "memory"); }
__device__ __forceinline__ void bar_sync(int id, int n) { asm volatile("bar.sync %0, %1;" ::"r"(id), "r"(n) : "memory"); }
__device__ __forceinline__ void bar_arrive(int id, int n) { asm volatile("bar.arrive %0, %1;" ::"r"(id), "r"(n) : "memory"); }
#define WG_FENCE() asm volatile("wgmma.fence.sync.aligned;" ::: "memory")
#define WG_COMMIT() asm volatile("wgmma.commit_group.sync.aligned;" ::: "memory")
#define WG_WAIT(n) asm volatile("wgmma.wait_group.sync.aligned %0;" ::"n"(n) : "memory")
__device__ __forceinline__ uint64_t mkdesc(uint32_t addr, uint32_t lbo, uint32_t sbo, uint32_t sw) {
  return (uint64_t)((addr & 0x3FFFF) >> 4) | ((uint64_t)(lbo >> 4) << 16) | ((uint64_t)(sbo >> 4) << 32) |
         ((uint64_t)sw << 62);
}
template <int N> __device__ __forceinline__ void fence_regs(float (&r)[N]) {
#pragma unroll
  for (int i = 0; i < N; i++) asm volatile("" : "+f"(r[i])::"memory");
}
__device__ __forceinline__ uint32_t pack_bf16(float lo, float hi) {
  uint32_t r;
  asm("cvt.rn.bf16x2.f32 %0, %1, %2;" : "=r"(r) : "f"(hi), "f"(lo));
  return r;
}
__device__ __forceinline__ float bf_lo(uint32_t v) { return __uint_as_float(v << 16); }
__device__ __forceinline__ float bf_hi(uint32_t v) { return __uint_as_float(v & 0xffff0000u); }
__device__ __forceinline__ float ex2(float x) {
  float y;
  asm("ex2.approx.ftz.f32 %0, %1;" : "=f"(y) : "f"(x));
  return y;
}
__device__ __forceinline__ uint4 ldg_nc(const void* p) {
  uint4 v;
  asm volatile("ld.global.nc.L1::no_allocate.v4.u32 {%0, %1, %2, %3}, [%4];"
               : "=r"(v.x), "=r"(v.y), "=r"(v.z), "=r"(v.w) : "l"(p));
  return v;
}

__device__ __forceinline__ void wgmma_ss_n256(float (&d)[128], uint64_t da, uint64_t db, int sd) {
  asm volatile("{\n.reg .pred p;\nsetp.ne.b32 p, %130, 0;\n"
      "wgmma.mma_async.sync.aligned.m64n256k16.f32.bf16.bf16 {"
      "%0, %1, %2, %3, %4, %5, %6, %7, %8, %9, %10, %11, %12, %13, %14, %15, "
      "%16, %17, %18, %19, %20, %21, %22, %23, %24, %25, %26, %27, %28, %29, %30, %31, "
      "%32, %33, %34, %35, %36, %37, %38, %39, %40, %41, %42, %43, %44, %45, %46, %47, "
      "%48, %49, %50, %51, %52, %53, %54, %55, %56, %57, %58, %59, %60, %61, %62, %63, "
      "%64, %65, %66, %67, %68, %69, %70, %71, %72, %73, %74, %75, %76, %77, %78, %79, "
      "%80, %81, %82, %83, %84, %85, %86, %87, %88, %89, %90, %91, %92, %93, %94, %95, "
      "%96, %97, %98, %99, %100, %101, %102, %103, %104, %105, %106, %107, %108, %109, %110, %111, "
      "%112, %113, %114, %115, %116, %117, %118, %119, %120, %121, %122, %123, %124, %125, %126, %127"
      "}, %128, %129, p, 1, 1, 0, 1;\n}\n"
    : "+f"(d[0]), "+f"(d[1]), "+f"(d[2]), "+f"(d[3]), "+f"(d[4]), "+f"(d[5]), "+f"(d[6]), "+f"(d[7]),
      "+f"(d[8]), "+f"(d[9]), "+f"(d[10]), "+f"(d[11]), "+f"(d[12]), "+f"(d[13]), "+f"(d[14]), "+f"(d[15]),
      "+f"(d[16]), "+f"(d[17]), "+f"(d[18]), "+f"(d[19]), "+f"(d[20]), "+f"(d[21]), "+f"(d[22]), "+f"(d[23]),
      "+f"(d[24]), "+f"(d[25]), "+f"(d[26]), "+f"(d[27]), "+f"(d[28]), "+f"(d[29]), "+f"(d[30]), "+f"(d[31]),
      "+f"(d[32]), "+f"(d[33]), "+f"(d[34]), "+f"(d[35]), "+f"(d[36]), "+f"(d[37]), "+f"(d[38]), "+f"(d[39]),
      "+f"(d[40]), "+f"(d[41]), "+f"(d[42]), "+f"(d[43]), "+f"(d[44]), "+f"(d[45]), "+f"(d[46]), "+f"(d[47]),
      "+f"(d[48]), "+f"(d[49]), "+f"(d[50]), "+f"(d[51]), "+f"(d[52]), "+f"(d[53]), "+f"(d[54]), "+f"(d[55]),
      "+f"(d[56]), "+f"(d[57]), "+f"(d[58]), "+f"(d[59]), "+f"(d[60]), "+f"(d[61]), "+f"(d[62]), "+f"(d[63]),
      "+f"(d[64]), "+f"(d[65]), "+f"(d[66]), "+f"(d[67]), "+f"(d[68]), "+f"(d[69]), "+f"(d[70]), "+f"(d[71]),
      "+f"(d[72]), "+f"(d[73]), "+f"(d[74]), "+f"(d[75]), "+f"(d[76]), "+f"(d[77]), "+f"(d[78]), "+f"(d[79]),
      "+f"(d[80]), "+f"(d[81]), "+f"(d[82]), "+f"(d[83]), "+f"(d[84]), "+f"(d[85]), "+f"(d[86]), "+f"(d[87]),
      "+f"(d[88]), "+f"(d[89]), "+f"(d[90]), "+f"(d[91]), "+f"(d[92]), "+f"(d[93]), "+f"(d[94]), "+f"(d[95]),
      "+f"(d[96]), "+f"(d[97]), "+f"(d[98]), "+f"(d[99]), "+f"(d[100]), "+f"(d[101]), "+f"(d[102]), "+f"(d[103]),
      "+f"(d[104]), "+f"(d[105]), "+f"(d[106]), "+f"(d[107]), "+f"(d[108]), "+f"(d[109]), "+f"(d[110]), "+f"(d[111]),
      "+f"(d[112]), "+f"(d[113]), "+f"(d[114]), "+f"(d[115]), "+f"(d[116]), "+f"(d[117]), "+f"(d[118]), "+f"(d[119]),
      "+f"(d[120]), "+f"(d[121]), "+f"(d[122]), "+f"(d[123]), "+f"(d[124]), "+f"(d[125]), "+f"(d[126]), "+f"(d[127])
    : "l"(da), "l"(db), "r"(sd));
}
__device__ __forceinline__ void wgmma_ss_n216(float (&d)[108], uint64_t da, uint64_t db, int sd) {
  asm volatile("{\n.reg .pred p;\nsetp.ne.b32 p, %110, 0;\n"
      "wgmma.mma_async.sync.aligned.m64n216k16.f32.bf16.bf16 {"
      "%0, %1, %2, %3, %4, %5, %6, %7, %8, %9, %10, %11, %12, %13, %14, %15, "
      "%16, %17, %18, %19, %20, %21, %22, %23, %24, %25, %26, %27, %28, %29, %30, %31, "
      "%32, %33, %34, %35, %36, %37, %38, %39, %40, %41, %42, %43, %44, %45, %46, %47, "
      "%48, %49, %50, %51, %52, %53, %54, %55, %56, %57, %58, %59, %60, %61, %62, %63, "
      "%64, %65, %66, %67, %68, %69, %70, %71, %72, %73, %74, %75, %76, %77, %78, %79, "
      "%80, %81, %82, %83, %84, %85, %86, %87, %88, %89, %90, %91, %92, %93, %94, %95, "
      "%96, %97, %98, %99, %100, %101, %102, %103, %104, %105, %106, %107"
      "}, %108, %109, p, 1, 1, 0, 1;\n}\n"
    : "+f"(d[0]), "+f"(d[1]), "+f"(d[2]), "+f"(d[3]), "+f"(d[4]), "+f"(d[5]), "+f"(d[6]), "+f"(d[7]),
      "+f"(d[8]), "+f"(d[9]), "+f"(d[10]), "+f"(d[11]), "+f"(d[12]), "+f"(d[13]), "+f"(d[14]), "+f"(d[15]),
      "+f"(d[16]), "+f"(d[17]), "+f"(d[18]), "+f"(d[19]), "+f"(d[20]), "+f"(d[21]), "+f"(d[22]), "+f"(d[23]),
      "+f"(d[24]), "+f"(d[25]), "+f"(d[26]), "+f"(d[27]), "+f"(d[28]), "+f"(d[29]), "+f"(d[30]), "+f"(d[31]),
      "+f"(d[32]), "+f"(d[33]), "+f"(d[34]), "+f"(d[35]), "+f"(d[36]), "+f"(d[37]), "+f"(d[38]), "+f"(d[39]),
      "+f"(d[40]), "+f"(d[41]), "+f"(d[42]), "+f"(d[43]), "+f"(d[44]), "+f"(d[45]), "+f"(d[46]), "+f"(d[47]),
      "+f"(d[48]), "+f"(d[49]), "+f"(d[50]), "+f"(d[51]), "+f"(d[52]), "+f"(d[53]), "+f"(d[54]), "+f"(d[55]),
      "+f"(d[56]), "+f"(d[57]), "+f"(d[58]), "+f"(d[59]), "+f"(d[60]), "+f"(d[61]), "+f"(d[62]), "+f"(d[63]),
      "+f"(d[64]), "+f"(d[65]), "+f"(d[66]), "+f"(d[67]), "+f"(d[68]), "+f"(d[69]), "+f"(d[70]), "+f"(d[71]),
      "+f"(d[72]), "+f"(d[73]), "+f"(d[74]), "+f"(d[75]), "+f"(d[76]), "+f"(d[77]), "+f"(d[78]), "+f"(d[79]),
      "+f"(d[80]), "+f"(d[81]), "+f"(d[82]), "+f"(d[83]), "+f"(d[84]), "+f"(d[85]), "+f"(d[86]), "+f"(d[87]),
      "+f"(d[88]), "+f"(d[89]), "+f"(d[90]), "+f"(d[91]), "+f"(d[92]), "+f"(d[93]), "+f"(d[94]), "+f"(d[95]),
      "+f"(d[96]), "+f"(d[97]), "+f"(d[98]), "+f"(d[99]), "+f"(d[100]), "+f"(d[101]), "+f"(d[102]), "+f"(d[103]),
      "+f"(d[104]), "+f"(d[105]), "+f"(d[106]), "+f"(d[107])
    : "l"(da), "l"(db), "r"(sd));
}
__device__ __forceinline__ void wgmma_ss_n80(float (&d)[40], uint64_t da, uint64_t db, int sd) {
  asm volatile("{\n.reg .pred p;\nsetp.ne.b32 p, %42, 0;\n"
      "wgmma.mma_async.sync.aligned.m64n80k16.f32.bf16.bf16 {"
      "%0, %1, %2, %3, %4, %5, %6, %7, %8, %9, %10, %11, %12, %13, %14, %15, "
      "%16, %17, %18, %19, %20, %21, %22, %23, %24, %25, %26, %27, %28, %29, %30, %31, "
      "%32, %33, %34, %35, %36, %37, %38, %39"
      "}, %40, %41, p, 1, 1, 0, 1;\n}\n"
    : "+f"(d[0]), "+f"(d[1]), "+f"(d[2]), "+f"(d[3]), "+f"(d[4]), "+f"(d[5]), "+f"(d[6]), "+f"(d[7]),
      "+f"(d[8]), "+f"(d[9]), "+f"(d[10]), "+f"(d[11]), "+f"(d[12]), "+f"(d[13]), "+f"(d[14]), "+f"(d[15]),
      "+f"(d[16]), "+f"(d[17]), "+f"(d[18]), "+f"(d[19]), "+f"(d[20]), "+f"(d[21]), "+f"(d[22]), "+f"(d[23]),
      "+f"(d[24]), "+f"(d[25]), "+f"(d[26]), "+f"(d[27]), "+f"(d[28]), "+f"(d[29]), "+f"(d[30]), "+f"(d[31]),
      "+f"(d[32]), "+f"(d[33]), "+f"(d[34]), "+f"(d[35]), "+f"(d[36]), "+f"(d[37]), "+f"(d[38]), "+f"(d[39])
    : "l"(da), "l"(db), "r"(sd));
}
__device__ __forceinline__ void wgmma_rs_n128(float (&d)[64], uint32_t a0, uint32_t a1, uint32_t a2, uint32_t a3,
                                  uint64_t db, int sd) {
  asm volatile("{\n.reg .pred p;\nsetp.ne.b32 p, %69, 0;\n"
      "wgmma.mma_async.sync.aligned.m64n128k16.f32.bf16.bf16 {"
      "%0, %1, %2, %3, %4, %5, %6, %7, %8, %9, %10, %11, %12, %13, %14, %15, "
      "%16, %17, %18, %19, %20, %21, %22, %23, %24, %25, %26, %27, %28, %29, %30, %31, "
      "%32, %33, %34, %35, %36, %37, %38, %39, %40, %41, %42, %43, %44, %45, %46, %47, "
      "%48, %49, %50, %51, %52, %53, %54, %55, %56, %57, %58, %59, %60, %61, %62, %63"
      "}, {%64, %65, %66, %67}, %68, p, 1, 1, 0;\n}\n"
    : "+f"(d[0]), "+f"(d[1]), "+f"(d[2]), "+f"(d[3]), "+f"(d[4]), "+f"(d[5]), "+f"(d[6]), "+f"(d[7]),
      "+f"(d[8]), "+f"(d[9]), "+f"(d[10]), "+f"(d[11]), "+f"(d[12]), "+f"(d[13]), "+f"(d[14]), "+f"(d[15]),
      "+f"(d[16]), "+f"(d[17]), "+f"(d[18]), "+f"(d[19]), "+f"(d[20]), "+f"(d[21]), "+f"(d[22]), "+f"(d[23]),
      "+f"(d[24]), "+f"(d[25]), "+f"(d[26]), "+f"(d[27]), "+f"(d[28]), "+f"(d[29]), "+f"(d[30]), "+f"(d[31]),
      "+f"(d[32]), "+f"(d[33]), "+f"(d[34]), "+f"(d[35]), "+f"(d[36]), "+f"(d[37]), "+f"(d[38]), "+f"(d[39]),
      "+f"(d[40]), "+f"(d[41]), "+f"(d[42]), "+f"(d[43]), "+f"(d[44]), "+f"(d[45]), "+f"(d[46]), "+f"(d[47]),
      "+f"(d[48]), "+f"(d[49]), "+f"(d[50]), "+f"(d[51]), "+f"(d[52]), "+f"(d[53]), "+f"(d[54]), "+f"(d[55]),
      "+f"(d[56]), "+f"(d[57]), "+f"(d[58]), "+f"(d[59]), "+f"(d[60]), "+f"(d[61]), "+f"(d[62]), "+f"(d[63])
    : "r"(a0), "r"(a1), "r"(a2), "r"(a3), "l"(db), "r"(sd));
}
__device__ __forceinline__ void wgmma_rs_n24(float (&d)[12], uint32_t a0, uint32_t a1, uint32_t a2, uint32_t a3,
                                  uint64_t db, int sd) {
  asm volatile("{\n.reg .pred p;\nsetp.ne.b32 p, %17, 0;\n"
      "wgmma.mma_async.sync.aligned.m64n24k16.f32.bf16.bf16 {"
      "%0, %1, %2, %3, %4, %5, %6, %7, %8, %9, %10, %11"
      "}, {%12, %13, %14, %15}, %16, p, 1, 1, 1;\n}\n"
    : "+f"(d[0]), "+f"(d[1]), "+f"(d[2]), "+f"(d[3]), "+f"(d[4]), "+f"(d[5]), "+f"(d[6]), "+f"(d[7]),
      "+f"(d[8]), "+f"(d[9]), "+f"(d[10]), "+f"(d[11])
    : "r"(a0), "r"(a1), "r"(a2), "r"(a3), "l"(db), "r"(sd));
}

constexpr int K1_ST = 4, K1_STAGE = 49152;
constexpr int K1_SMEM = K1_ST * K1_STAGE + 2048   + 1024   + 3072   + 128;

__global__ void __cluster_dims__(2, 1, 1) __launch_bounds__(384, 1)
k1_qkv(const __grid_constant__ CUtensorMap tmx, const __grid_constant__ CUtensorMap tmw,
       const bf16* __restrict__ x, const bf16* __restrict__ w) {
  extern __shared__ __align__(1024) uint8_t sm[];
  float4* tab = (float4*)(sm + K1_ST * K1_STAGE);
  float2* rowab = (float2*)(sm + K1_ST * K1_STAGE + 2048);
  float* red = (float*)(sm + K1_ST * K1_STAGE + 3072);
  const uint32_t sbase = smem_u32(sm);
  const uint32_t fullb = sbase + K1_ST * K1_STAGE + 6144, emptyb = fullb + 8 * K1_ST;
  const int tid = threadIdx.x, lane = tid & 31;
  const int warp = __shfl_sync(~0u, tid >> 5, 0);
  const int rank = blockIdx.x & 1, cl = blockIdx.x >> 1;
  const int n = cl & 7, m = (cl >> 3) * 2 + rank;

  if (tid == 0) {
    for (int i = 0; i < K1_ST; i++) { mbar_init(fullb + 8 * i, 1); mbar_init(emptyb + 8 * i, 4); }
    asm volatile("fence.mbarrier_init.release.cluster;" ::: "memory");
  }
  __syncthreads();
  cluster_sync();
  pdl_trigger();

  if (warp == 0) {
    if (lane == 0) {
      for (int kt = 0; kt < 10; kt++) {
        const int s = kt % K1_ST;
        if (kt >= K1_ST) mbar_wait_cluster(emptyb + 8 * s, ((kt / K1_ST) - 1) & 1);
        mbar_expect(fullb + 8 * s, K1_STAGE);
        const uint32_t sa = sbase + s * K1_STAGE, sb = sa + 16384;
        tma2d(sa, &tmx, kt * 64, m * 128, fullb + 8 * s);
#pragma unroll
        for (int j = 0; j < 4; j++)
          tma2d_mc(sb + j * 8192 + rank * 4096, &tmw, n * 256 + j * 64, kt * 64 + rank * 32, fullb + 8 * s);
      }
    }
  } else if (warp < 4) {
    const int w3 = warp - 1, t96 = tid - 32;
    {
      float acc8[8];
#pragma unroll
      for (int i = 0; i < 8; i++) acc8[i] = 0.f;
      const int col0 = n * 256 + lane * 8;
      if (col0 < 1920) {
#pragma unroll 7
        for (int r = w3; r < 40; r += 3) {
          uint4 v = ldg_nc(w + (size_t)(m * 40 + r) * 1920 + col0);
          acc8[0] += bf_lo(v.x); acc8[1] += bf_hi(v.x); acc8[2] += bf_lo(v.y); acc8[3] += bf_hi(v.y);
          acc8[4] += bf_lo(v.z); acc8[5] += bf_hi(v.z); acc8[6] += bf_lo(v.w); acc8[7] += bf_hi(v.w);
        }
      }
#pragma unroll
      for (int i = 0; i < 8; i++) red[w3 * 256 + lane * 8 + i] = acc8[i];
    }
#pragma unroll 2
    for (int r = w3; r < 16; r += 3) {
      const int row = m * 128 + n * 16 + r;
      const bf16* xr = x + (size_t)row * D_;
      uint4 v[3];
      v[0] = ldg_nc(xr + lane * 8);
      v[1] = ldg_nc(xr + 256 + lane * 8);
      v[2] = make_uint4(0, 0, 0, 0);
      if (lane < 16) v[2] = ldg_nc(xr + 512 + lane * 8);
      float f[24];
#pragma unroll
      for (int i = 0; i < 3; i++) {
        f[8 * i + 0] = bf_lo(v[i].x); f[8 * i + 1] = bf_hi(v[i].x); f[8 * i + 2] = bf_lo(v[i].y); f[8 * i + 3] = bf_hi(v[i].y);
        f[8 * i + 4] = bf_lo(v[i].z); f[8 * i + 5] = bf_hi(v[i].z); f[8 * i + 6] = bf_lo(v[i].w); f[8 * i + 7] = bf_hi(v[i].w);
      }
      float s = 0.f;
#pragma unroll
      for (int i = 0; i < 24; i++) s += f[i];
#pragma unroll
      for (int o = 16; o; o >>= 1) s += __shfl_xor_sync(~0u, s, o);
      const float mean = s * (1.f / D_);
      float q = 0.f;
#pragma unroll
      for (int i = 0; i < 16; i++) { float d = f[i] - mean; q = fmaf(d, d, q); }
      if (lane < 16) {
#pragma unroll
        for (int i = 16; i < 24; i++) { float d = f[i] - mean; q = fmaf(d, d, q); }
      }
#pragma unroll
      for (int o = 16; o; o >>= 1) q += __shfl_xor_sync(~0u, q, o);
      if (lane == 0) g_rowstat[row] = make_float2(rsqrtf(q * (1.f / D_) + 1e-5f), mean);
    }
    bar_sync(1, 96);
    for (int c = t96; c < 256; c += 96) g_cpart[m * 2048 + n * 256 + c] = red[c] + red[256 + c] + red[512 + c];
    __threadfence();
    bar_sync(1, 96);
    if (t96 == 0) {
      asm volatile("red.release.gpu.global.add.u32 [%0], 1;" ::"l"(&g_cnt[m * 32]) : "memory");
      asm volatile("red.release.gpu.global.add.u32 [%0], 1;" ::"l"(&g_cnt[(16 + n) * 32]) : "memory");
    }
    {
      const int sh0 = (n * 256 + 1) / 20, sh1 = min((n * 256 + 255 - 18) / 20, 95);
      for (int i = t96; i < (sh1 - sh0 + 1) * 128; i += 96) {
        const int sh = sh0 + (i >> 7), r = i & 127;
        uint2 v;
        if (sh < 32) v = make_uint2(0x3F803F80u, 0x00003F80u);
        else if (sh >= 64) v = make_uint2(0x00003F80u, 0u);
        else if ((POLY_MASK >> (r >> 3)) & 1) v = make_uint2(0x4A7A4B00u, 0x00004653u);
        else v = make_uint2(0u, 0u);
        *(uint2*)((uint8_t*)g_qkv + (size_t)sh * HEAD_IMG + (m * 16 + (r >> 3)) * 384 + 256 + (r & 7) * 16 + 8) = v;
      }
    }
    if (t96 == 0) {
      uint32_t a, b, it = 0;
      while (true) {
        asm volatile("ld.acquire.gpu.global.u32 %0, [%1];" : "=r"(a) : "l"(&g_cnt[m * 32]) : "memory");
        asm volatile("ld.acquire.gpu.global.u32 %0, [%1];" : "=r"(b) : "l"(&g_cnt[(16 + n) * 32]) : "memory");
        if (a >= 8 && b >= 16) break;
        if (++it > (1u << 22)) wait_timeout();
        __nanosleep(64);
      }
    }
    bar_sync(1, 96);
    for (int r = t96; r < 128; r += 96) {
      float2 st = __ldcg(&g_rowstat[m * 128 + r]);
      rowab[r] = make_float2(st.x, -st.x * st.y);
      const int col = n * 256 + 2 * r;
      float c0 = 0.f, c1 = 0.f;
#pragma unroll
      for (int i = 0; i < 16; i++) {
        float2 p = __ldcg((const float2*)&g_cpart[i * 2048 + col]);
        c0 += p.x; c1 += p.y;
      }
      const int sh = col / 20, d = col - sh * 20;
      tab[r] = make_float4(c0, c1, __int_as_float(sh * HEAD_IMG + (d >> 3) * 128 + (d & 7) * 2), 0.f);
    }
    bar_arrive(2, 96 + 256);
  } else {
    const int cw = warp - 4, wg = cw >> 2;
    float acc[128];
    const uint64_t da0 = mkdesc(sbase + wg * 8192, 16, 1024, 1);
    const uint64_t db0 = mkdesc(sbase + 16384, 8192, 1024, 1);
#pragma unroll 1
    for (int kt = 0; kt < 10; kt++) {
      const int s = kt % K1_ST;
      mbar_wait(fullb + 8 * s, (kt / K1_ST) & 1);
      const uint64_t da = da0 + s * (K1_STAGE >> 4), db = db0 + s * (K1_STAGE >> 4);
      WG_FENCE();
#pragma unroll
      for (int k = 0; k < 4; k++) wgmma_ss_n256(acc, da + k * 2, db + k * 128, (kt | k) != 0);
      WG_COMMIT();
      if (kt > 0) {
        WG_WAIT(1);
        if (kt - 1 + K1_ST < 10 && (tid & 127) < 2) mbar_arrive_cta(emptyb + 8 * ((kt - 1) % K1_ST), tid & 1);
      }
    }
    WG_WAIT(0);
    fence_regs(acc);
    bar_sync(2, 96 + 256);
    const int g = lane >> 2, c = lane & 3;
    const int r0 = cw * 16 + g;
    const float2 ab0 = rowab[r0], ab1 = rowab[r0 + 8];
    const float k0 = ((POLY_MASK >> (cw * 2)) & 1) ? 32768.f : 1.f, k1 = ((POLY_MASK >> (cw * 2 + 1)) & 1) ? 32768.f : 1.f;
    uint8_t* dst = (uint8_t*)g_qkv + (m * 16 + cw * 2) * 384 + g * 16;
#pragma unroll
    for (int half = 0; half < 2; half++) {
      const int sec = (n * 256 + half * 128) / 640;
      if (sec > 2) break;
      const float f0 = sec == 0 ? QSCALE : (sec == 1 ? k0 : 1.f), f1 = sec == 0 ? QSCALE : (sec == 1 ? k1 : 1.f);
      const float a0 = ab0.x * f0, b0 = ab0.y * f0, a1 = ab1.x * f1, b1 = ab1.y * f1;
#pragma unroll
      for (int jj = 0; jj < 16; jj++) {
        const int j = half * 16 + jj;
        const float4 t = tab[4 * j + c];
        uint8_t* p = dst + __float_as_int(t.z);
        *(uint32_t*)p = pack_bf16(fmaf(acc[4 * j], a0, b0 * t.x), fmaf(acc[4 * j + 1], a0, b0 * t.y));
        *(uint32_t*)(p + 384) = pack_bf16(fmaf(acc[4 * j + 2], a1, b1 * t.x), fmaf(acc[4 * j + 3], a1, b1 * t.y));
      }
    }
  }
  cluster_sync();
}

constexpr int K2_SMEM = 2 * HEAD_IMG + 2 * 6144 + 256;

__device__ __forceinline__ uint32_t exp_pair(bool poly, float a, float b, uint32_t mk) {
  if (poly) {
    const uint32_t pk = __byte_perm(__float_as_uint(a), __float_as_uint(b), 0x6521);
    uint32_t m, q;
    asm("lop3.b32 %0, %1, %2, 0x3f803f80, 0xEA;" : "=r"(m) : "r"(pk), "r"(mk));
    asm("fma.rn.bf16x2 %0, %1, %1, %2;" : "=r"(q) : "r"(m), "r"(0x40014001u));
    return pk - m + q;
  }
  return pack_bf16(ex2(a), ex2(b));
}
__device__ __forceinline__ void exp_pv(const float (&s)[64], float (&o)[12], uint64_t dv, uint32_t mk) {
#pragma unroll
  for (int k0 = 0; k0 < 8; k0 += 2) {
    uint32_t p[8];
#pragma unroll
    for (int i = 0; i < 8; i++)
      p[i] = exp_pair((POLY_MASK >> (k0 * 2 + i / 2)) & 1, s[k0 * 8 + 2 * i], s[k0 * 8 + 2 * i + 1], mk);
    WG_FENCE();
    wgmma_rs_n24(o, p[0], p[1], p[2], p[3], dv + k0 * 48, 1);
    wgmma_rs_n24(o, p[4], p[5], p[6], p[7], dv + k0 * 48 + 48, 1);
  }
}
__device__ __forceinline__ void load_q(uint32_t (&q)[6], const uint8_t* p) {
  q[0] = __ldcg((const uint32_t*)p);         q[1] = __ldcg((const uint32_t*)(p + 384));
  q[2] = __ldcg((const uint32_t*)(p + 128)); q[3] = __ldcg((const uint32_t*)(p + 512));
  q[4] = __ldcg((const uint32_t*)(p + 256)); q[5] = __ldcg((const uint32_t*)(p + 640));
}
__device__ __forceinline__ void store_o(const float (&o)[12], bf16* dst, int lane) {
  const float l0 = __shfl_sync(~0u, o[8], (lane & ~3) | 2), l1 = __shfl_sync(~0u, o[10], (lane & ~3) | 2);
  const float i0 = __frcp_rn(l0), i1 = __frcp_rn(l1);
  uint32_t* p0 = (uint32_t*)dst;
  uint32_t* p1 = (uint32_t*)(dst + 8 * D_);
  p0[0] = pack_bf16(o[0] * i0, o[1] * i0); p1[0] = pack_bf16(o[2] * i1, o[3] * i1);
  p0[4] = pack_bf16(o[4] * i0, o[5] * i0); p1[4] = pack_bf16(o[6] * i1, o[7] * i1);
  if ((lane & 3) < 2) { p0[8] = pack_bf16(o[8] * i0, o[9] * i0); p1[8] = pack_bf16(o[10] * i1, o[11] * i1); }
}
__device__ __forceinline__ float sq20(uint4 a, uint4 b, uint2 c) {
  uint32_t s0, s1;
  asm("mul.rn.bf16x2 %0, %1, %1;" : "=r"(s0) : "r"(a.x));
  asm("mul.rn.bf16x2 %0, %1, %1;" : "=r"(s1) : "r"(a.y));
#define SQ_(acc, v) asm("fma.rn.bf16x2 %0, %1, %1, %0;" : "+r"(acc) : "r"(v))
  SQ_(s0, a.z); SQ_(s1, a.w); SQ_(s0, b.x); SQ_(s1, b.y); SQ_(s0, b.z); SQ_(s1, b.w); SQ_(s0, c.x); SQ_(s1, c.y);
#undef SQ_
  return (bf_lo(s0) + bf_hi(s0)) + (bf_lo(s1) + bf_hi(s1));
}

__global__ void __launch_bounds__(512, 1)
k2_attn(const bf16* __restrict__ wo, const bf16* __restrict__ wg_, const bf16* __restrict__ wu,
        const bf16* __restrict__ wd, uint32_t mk) {
  extern __shared__ __align__(1024) uint8_t sm[];
  const uint32_t sbase = smem_u32(sm);
  float* part = (float*)(sm + 2 * HEAD_IMG);
  const uint32_t kvb = sbase + 2 * HEAD_IMG + 2 * 6144;
  const uint32_t flagb = kvb + 128, partb = kvb + 136;
  volatile uint32_t* sflag = (volatile uint32_t*)(sm + 2 * HEAD_IMG + 2 * 6144 + 160);
  const int tid = threadIdx.x, lane = tid & 31;
  const int warp = __shfl_sync(~0u, tid >> 5, 0);
  const int head = blockIdx.x >> 2, qb = blockIdx.x & 3;
  const uint8_t* qimg = (const uint8_t*)g_qkv + (size_t)head * HEAD_IMG + qb * 64 * 384;

  if (tid == 0) {
    for (int i = 0; i < 16; i++) mbar_init(kvb + 8 * i, 1);
    mbar_init(flagb, 1); mbar_init(partb, 128); mbar_init(partb + 8, 128);
    asm volatile("fence.mbarrier_init.release.cluster;" ::: "memory");
  }
  __syncthreads();

  if (warp >= 12) {
    asm volatile("setmaxnreg.dec.sync.aligned.u32 56;");
    const int t = tid - 384;
    pdl_wait();
    pdl_trigger();
    if (t == 0) {
      const uint8_t* kimg = (const uint8_t*)g_qkv + (size_t)(32 + head) * HEAD_IMG;
      const uint8_t* vimg = (const uint8_t*)g_qkv + (size_t)(64 + head) * HEAD_IMG;
      for (int b = 0; b < 16; b++) {
        mbar_expect(kvb + 8 * b, 12288);
        bulk_ld(sbase + b * 6144, kimg + b * 6144, 6144, kvb + 8 * b);
        bulk_ld(sbase + HEAD_IMG + b * 6144, vimg + b * 6144, 6144, kvb + 8 * b);
      }
    }
    if (blockIdx.x == 0 && t >= 32 && t < 56) g_cnt[(t - 32) * 32] = 0;
    {
      float qm = 0.f, km = 0.f;
      const int ro = (t >> 3) * 384 + (t & 7) * 16;
#pragma unroll
      for (int i = 0; i < 4; i++) {
        const uint8_t* p = qimg + i * 6144 + ro;
        const float v = sq20(__ldcg((const uint4*)p), __ldcg((const uint4*)(p + 128)), __ldcg((const uint2*)(p + 256)));
        qm = __uint_as_float(max(__float_as_uint(qm), __float_as_uint(v)));
      }
#pragma unroll 1
      for (int b = 0; b < 16; b++) {
        mbar_wait(kvb + 8 * b, 0);
        const uint8_t* p = sm + b * 6144 + ro;
        const float v = sq20(*(const uint4*)p, *(const uint4*)(p + 128), *(const uint2*)(p + 256));
        km = __uint_as_float(max(__float_as_uint(km), __float_as_uint(v)));
      }
      if ((POLY_MASK >> (t >> 3)) & 1) km *= 9.313225746154785e-10f;
      const uint32_t qw = __reduce_max_sync(~0u, __float_as_uint(qm)), kw = __reduce_max_sync(~0u, __float_as_uint(km));
      if (lane == 0) { sflag[1 + (warp & 3)] = qw; sflag[5 + (warp & 3)] = kw; }
      bar_sync(1, 128);
      if (t == 0) {
        const float q2 = __uint_as_float(max(max(sflag[1], sflag[2]), max(sflag[3], sflag[4])));
        const float k2 = __uint_as_float(max(max(sflag[5], sflag[6]), max(sflag[7], sflag[8])));
        sflag[0] = (q2 * k2 <= 3000.f) ? 1u : 0u;
        mbar_arrive(flagb);
      }
    }
    const int kr = (warp & 3) * 8 + (lane >> 2), ch = lane & 3;
    if (blockIdx.x < 108) {
      const int cg = blockIdx.x * 4 + ch;
      const int up = cg >= 216, cc = cg - up * 216;
      const int nt = cc / 27, ci = cc - nt * 27 + up * 27;
      const bf16* src = (up ? wu : wg_) + cc * 8 + (size_t)kr * F_;
      uint4* dst = g_wgu + ((size_t)nt * 10 * 54 + ci) * 64 + kr;
      float a8[8];
#pragma unroll
      for (int i = 0; i < 8; i++) a8[i] = 0.f;
#pragma unroll 4
      for (int it = 0; it < 20; it++) {
        const uint4 v = ldg_nc(src + (size_t)it * 32 * F_);
        dst[(it >> 1) * (54 * 64) + (it & 1) * 32] = v;
        a8[0] += bf_lo(v.x); a8[1] += bf_hi(v.x); a8[2] += bf_lo(v.y); a8[3] += bf_hi(v.y);
        a8[4] += bf_lo(v.z); a8[5] += bf_hi(v.z); a8[6] += bf_lo(v.w); a8[7] += bf_hi(v.w);
      }
#pragma unroll
      for (int i = 0; i < 8; i++) {
        a8[i] += __shfl_xor_sync(~0u, a8[i], 4);
        a8[i] += __shfl_xor_sync(~0u, a8[i], 8);
        a8[i] += __shfl_xor_sync(~0u, a8[i], 16);
      }
      float* red = (float*)(sm + K2_SMEM);
      if (lane < 4) {
#pragma unroll
        for (int i = 0; i < 8; i++) red[(warp & 3) * 32 + lane * 8 + i] = a8[i];
      }
      bar_sync(1, 128);
      if (t < 32) g_csgu[blockIdx.x * 32 + t] = red[t] + red[32 + t] + red[64 + t] + red[96 + t];
    }
    {
      const int first = blockIdx.x < 108 ? blockIdx.x * 8 : 864 + (blockIdx.x - 108) * 31;
      const int last = min(blockIdx.x < 108 ? first + 8 : first + 31, 1480);
#pragma unroll 4
      for (int ps = first; ps < last; ps++) {
        const int rg = ps / 20, cs = ps - rg * 20;
        const int cg = cs * 4 + ch, nt = cg / 10, ci = cg - nt * 10;
        const bool isd = rg < 54;
        const int k = (isd ? rg : rg - 54) * 32 + kr;
        const uint4 v = ldg_nc((isd ? wd : wo) + (size_t)k * D_ + cg * 8);
        uint4* dst = (isd ? g_wd + (size_t)nt * 27 * 640 : g_wo + (size_t)nt * 10 * 640) + ((k >> 6) * 10 + ci) * 64 + (k & 63);
        *dst = v;
      }
    }
  } else {
    asm volatile("setmaxnreg.inc.sync.aligned.u32 152;");
    const int wg = warp >> 2, wq = warp & 3;
    const uint8_t* qthr = qimg + wq * 768 + (lane >> 2) * 16 + (lane & 3) * 4;
    bf16* othr = (bf16*)g_o + (size_t)(qb * 512 + wq * 16 + (lane >> 2)) * D_ + head * 20 + (lane & 3) * 2;
    const uint64_t dk0 = mkdesc(sbase, 128, 384, 0), dk0b = mkdesc(sbase + 256, 0, 384, 0);
    const uint64_t dv0 = mkdesc(sbase + HEAD_IMG, 384, 128, 0);
    const int nun = wg == 1 ? 4 : 3;
    const uint32_t utile = wg == 0 ? 0x210u : (wg == 1 ? 0x4325u : 0x576u);
    pdl_wait();
    uint32_t q[6];
    load_q(q, qthr + (utile & 15) * 3072);
    bool fast = true;
#pragma unroll 1
    for (int u = 0; u < nun; u++) {
      const int tile = (utile >> (4 * u)) & 15;
      int b0 = 0, b1 = 16;
      if (wg == 0 && u == 2) b1 = 11;
      if (wg == 1 && u == 0) b1 = 6;
      if (wg == 1 && u == 1) b0 = 11;
      if (wg == 2 && u == 2) b0 = 6;
      const bool wt = u == 0 || (wg == 1 && u == 1);
      float s[64], o[12];
#pragma unroll
      for (int i = 0; i < 12; i++) o[i] = 0.f;
      uint64_t dk = dk0 + b0 * 384, dkb = dk0b + b0 * 384, dv = dv0 + b0 * 384;
      if (wt) mbar_wait(kvb + 8 * b0, 0);
      fence_regs(o);
      WG_FENCE();
      wgmma_rs_n128(s, q[0], q[1], q[2], q[3], dk, 0);
      wgmma_rs_n128(s, q[4], q[5], 0, 0, dkb, 1);
      WG_COMMIT();
#pragma unroll 1
      for (int b = b0 + 1; b < b1; b++) {
        if (wt) mbar_wait(kvb + 8 * b, 0);
        WG_WAIT(0);
        fence_regs(s); fence_regs(o);
        exp_pv(s, o, dv, mk);
        dk += 384; dkb += 384; dv += 384;
        wgmma_rs_n128(s, q[0], q[1], q[2], q[3], dk, 0);
        wgmma_rs_n128(s, q[4], q[5], 0, 0, dkb, 1);
        WG_COMMIT();
      }
      WG_WAIT(0);
      fence_regs(s); fence_regs(o);
      if (u + 1 < nun) load_q(q, qthr + ((utile >> (4 * u + 4)) & 15) * 3072);
      exp_pv(s, o, dv, mk);
      WG_COMMIT();
      WG_WAIT(0);
      fence_regs(o);
      if (wg == 1 && u < 2) {
        float4* pp = (float4*)(part + u * 1536) + (tid & 127);
        pp[0] = make_float4(o[0], o[1], o[2], o[3]);
        pp[128] = make_float4(o[4], o[5], o[6], o[7]);
        pp[256] = make_float4(o[8], o[9], o[10], o[11]);
        mbar_arrive(partb + 8 * u);
        if (u == 0) continue;
      }
      if (wt) {
        mbar_wait(flagb, 0);
        fast = sflag[0] != 0;
        if (!fast) break;
        if (wg == 1) continue;
      }
      if (wg != 1 && u == 2) {
        const int pi = wg == 0 ? 1 : 0;
        mbar_wait(partb + 8 * pi, 0);
        const float4* pp = (const float4*)(part + pi * 1536) + (tid & 127);
        const float4 x0 = pp[0], x1 = pp[128], x2 = pp[256];
        o[0] += x0.x; o[1] += x0.y; o[2] += x0.z; o[3] += x0.w; o[4] += x1.x; o[5] += x1.y;
        o[6] += x1.z; o[7] += x1.w; o[8] += x2.x; o[9] += x2.y; o[10] += x2.z; o[11] += x2.w;
      }
      store_o(o, othr + (size_t)tile * 64 * D_, lane);
    }
    if (!fast) {
#pragma unroll 1
      for (int tile = wg; tile < 8; tile += 3) {
        load_q(q, qthr + tile * 3072);
        if ((lane & 3) >= 2) { q[4] = 0; q[5] = 0; }
        float o[12], m0 = -INFINITY, m1 = -INFINITY;
#pragma unroll
        for (int i = 0; i < 12; i++) o[i] = 0.f;
#pragma unroll 1
        for (int b = 0; b < 16; b++) {
          float s[64];
          WG_FENCE();
          wgmma_rs_n128(s, q[0], q[1], q[2], q[3], dk0 + b * 384, 0);
          wgmma_rs_n128(s, q[4], q[5], 0, 0, dk0b + b * 384, 1);
          WG_COMMIT();
          WG_WAIT(0);
          fence_regs(s);
          float x0 = m0, x1 = m1;
#pragma unroll
          for (int j = 0; j < 16; j++) {
            if ((POLY_MASK >> j) & 1) {
#pragma unroll
              for (int i = 0; i < 4; i++) s[4 * j + i] *= (1.f / 32768.f);
            }
            x0 = fmaxf(x0, fmaxf(s[4 * j], s[4 * j + 1]));
            x1 = fmaxf(x1, fmaxf(s[4 * j + 2], s[4 * j + 3]));
          }
          x0 = fmaxf(x0, __shfl_xor_sync(~0u, x0, 1)); x0 = fmaxf(x0, __shfl_xor_sync(~0u, x0, 2));
          x1 = fmaxf(x1, __shfl_xor_sync(~0u, x1, 1)); x1 = fmaxf(x1, __shfl_xor_sync(~0u, x1, 2));
          const float al0 = ex2(m0 - x0), al1 = ex2(m1 - x1);
          m0 = x0; m1 = x1;
#pragma unroll
          for (int i = 0; i < 12; i++) o[i] *= (i & 2) ? al1 : al0;
          uint32_t p[32];
#pragma unroll
          for (int i = 0; i < 32; i++) {
            const float mm = (i & 1) ? m1 : m0;
            p[i] = pack_bf16(ex2(s[2 * i] - mm), ex2(s[2 * i + 1] - mm));
          }
          fence_regs(o);
          WG_FENCE();
#pragma unroll
          for (int k = 0; k < 8; k++) wgmma_rs_n24(o, p[4 * k], p[4 * k + 1], p[4 * k + 2], p[4 * k + 3], dv0 + b * 384 + k * 48, 1);
          WG_COMMIT();
          WG_WAIT(0);
          fence_regs(o);
        }
        store_o(o, othr + (size_t)tile * 64 * D_, lane);
      }
    }
  }
}

constexpr int K3_ST = 8, K3_STAGE = 26624;
constexpr int K3_SMEM = K3_ST * K3_STAGE + 256;

template <int KT, bool STATS>
__global__ void __cluster_dims__(2, 1, 1) __launch_bounds__(384, 1)
k3_proj(const __grid_constant__ CUtensorMap tma, const uint4* __restrict__ wimg, const bf16* __restrict__ res,
        bf16* __restrict__ out) {
  extern __shared__ __align__(1024) uint8_t sm[];
  const uint32_t sbase = smem_u32(sm);
  const uint32_t fullb = sbase + K3_ST * K3_STAGE, emptyb = fullb + 8 * K3_ST;
  const int tid = threadIdx.x, lane = tid & 31;
  const int warp = __shfl_sync(~0u, tid >> 5, 0);
  const int rank = blockIdx.x & 1;
  const int n = blockIdx.x & 7, m = blockIdx.x >> 3;
  if (tid == 0) {
    for (int i = 0; i < K3_ST; i++) { mbar_init(fullb + 8 * i, 1); mbar_init(emptyb + 8 * i, 4); }
    asm volatile("fence.mbarrier_init.release.cluster;" ::: "memory");
  }
  __syncthreads();
  cluster_sync();
  if (warp == 0) {
    if (lane == 0) {
      const uint8_t* wb = (const uint8_t*)wimg + (size_t)n * KT * 10240;
      if (!STATS) {
        for (int kt = 0; kt < K3_ST; kt++) {
          mbar_expect(fullb + 8 * kt, K3_STAGE);
          bulk_ld(sbase + kt * K3_STAGE + 16384, wb + kt * 10240, 10240, fullb + 8 * kt);
        }
      }
      pdl_wait();
      pdl_trigger();
      for (int kt = 0; kt < KT; kt++) {
        const int s = kt % K3_ST;
        const uint32_t sa = sbase + s * K3_STAGE;
        if (kt >= K3_ST) mbar_wait_cluster(emptyb + 8 * s, ((kt / K3_ST) - 1) & 1);
        if (STATS || kt >= K3_ST) {
          mbar_expect(fullb + 8 * s, K3_STAGE);
          bulk_ld(sa + 16384, wb + kt * 10240, 10240, fullb + 8 * s);
        }
        tma2d_mc(sa + rank * 8192, &tma, kt * 64, m * 128 + rank * 64, fullb + 8 * s);
      }
    }
  } else if (warp >= 4) {
    const int cw = warp - 4, wg = cw >> 2;
    const int g = lane >> 2, c = lane & 3;
    const size_t ro = (size_t)(m * 128 + cw * 16 + g) * D_ + n * 80 + c * 2;
    pdl_wait();
    uint32_t rv[20];
#pragma unroll
    for (int j = 0; j < 10; j++) {
      rv[2 * j] = __ldcg((const uint32_t*)(res + ro + j * 8));
      rv[2 * j + 1] = __ldcg((const uint32_t*)(res + ro + 8 * D_ + j * 8));
    }
    float acc[40];
    const uint64_t da0 = mkdesc(sbase + wg * 8192, 16, 1024, 1);
    const uint64_t db0 = mkdesc(sbase + 16384, 128, 1024, 0);
#pragma unroll 1
    for (int kt = 0; kt < KT; kt++) {
      const int s = kt % K3_ST;
      mbar_wait(fullb + 8 * s, (kt / K3_ST) & 1);
      const uint64_t da = da0 + s * (K3_STAGE >> 4), db = db0 + s * (K3_STAGE >> 4);
      WG_FENCE();
#pragma unroll
      for (int k = 0; k < 4; k++) wgmma_ss_n80(acc, da + k * 2, db + k * 16, (kt | k) != 0);
      WG_COMMIT();
      if (kt > 0) {
        WG_WAIT(1);
        if (kt - 1 + K3_ST < KT && (tid & 127) < 2) mbar_arrive_cta(emptyb + 8 * ((kt - 1) % K3_ST), tid & 1);
      }
    }
    WG_WAIT(0);
    fence_regs(acc);
    float s0 = 0.f, s1 = 0.f;
#pragma unroll
    for (int j = 0; j < 10; j++) {
      acc[4 * j] += bf_lo(rv[2 * j]); acc[4 * j + 1] += bf_hi(rv[2 * j]);
      acc[4 * j + 2] += bf_lo(rv[2 * j + 1]); acc[4 * j + 3] += bf_hi(rv[2 * j + 1]);
      *(uint32_t*)(out + ro + j * 8) = pack_bf16(acc[4 * j], acc[4 * j + 1]);
      *(uint32_t*)(out + ro + 8 * D_ + j * 8) = pack_bf16(acc[4 * j + 2], acc[4 * j + 3]);
      s0 += acc[4 * j] + acc[4 * j + 1]; s1 += acc[4 * j + 2] + acc[4 * j + 3];
    }
    if (STATS) {
      s0 += __shfl_xor_sync(~0u, s0, 1); s0 += __shfl_xor_sync(~0u, s0, 2);
      s1 += __shfl_xor_sync(~0u, s1, 1); s1 += __shfl_xor_sync(~0u, s1, 2);
      s0 *= (1.f / 80.f); s1 *= (1.f / 80.f);
      float q0 = 0.f, q1 = 0.f;
#pragma unroll
      for (int j = 0; j < 10; j++) {
        float d;
        d = acc[4 * j] - s0; q0 = fmaf(d, d, q0); d = acc[4 * j + 1] - s0; q0 = fmaf(d, d, q0);
        d = acc[4 * j + 2] - s1; q1 = fmaf(d, d, q1); d = acc[4 * j + 3] - s1; q1 = fmaf(d, d, q1);
      }
      q0 += __shfl_xor_sync(~0u, q0, 1); q0 += __shfl_xor_sync(~0u, q0, 2);
      q1 += __shfl_xor_sync(~0u, q1, 1); q1 += __shfl_xor_sync(~0u, q1, 2);
      if (c == 0) {
        g_hpart[(m * 128 + cw * 16 + g) * 8 + n] = make_float2(s0, q0);
        g_hpart[(m * 128 + cw * 16 + g + 8) * 8 + n] = make_float2(s1, q1);
      }
    }
  }
  cluster_sync();
}

constexpr int K4_ST = 3, K4_STAGE = 71680;
constexpr int K4_SMEM = K4_ST * K4_STAGE + 1728 + 1024 + 64;

__global__ void __cluster_dims__(2, 1, 1) __launch_bounds__(256, 1)
k4_ffn1(const __grid_constant__ CUtensorMap tmh) {
  extern __shared__ __align__(1024) uint8_t sm[];
  float* cs = (float*)(sm + K4_ST * K4_STAGE);
  float2* rowst = (float2*)(sm + K4_ST * K4_STAGE + 1728);
  const uint32_t sbase = smem_u32(sm);
  const uint32_t fullb = sbase + K4_ST * K4_STAGE + 2752, emptyb = fullb + 8 * K4_ST;
  const int tid = threadIdx.x, lane = tid & 31;
  const int warp = __shfl_sync(~0u, tid >> 5, 0);
  const int rank = blockIdx.x & 1, cl = blockIdx.x >> 1;
  const int n = cl & 7, m = (cl >> 3) * 2 + rank;
  const uint8_t* wb = (const uint8_t*)g_wgu + (size_t)n * 10 * 55296 + rank * 27648;
  if (tid == 0) {
    for (int i = 0; i < K4_ST; i++) { mbar_init(fullb + 8 * i, 1); mbar_init(emptyb + 8 * i, 4); }
    asm volatile("fence.mbarrier_init.release.cluster;" ::: "memory");
  }
  __syncthreads();
  cluster_sync();
  if (tid == 0) {
    for (int kt = 0; kt < K4_ST; kt++) {
      mbar_expect(fullb + 8 * kt, K4_STAGE);
      bulk_ld_mc(sbase + kt * K4_STAGE + 16384 + rank * 27648, wb + kt * 55296, 27648, fullb + 8 * kt);
    }
  }
  for (int i = tid; i < 432; i += 256) cs[i] = __ldcg(&g_csgu[(i >= 216 ? F_ - 216 : 0) + n * 216 + i]);
  pdl_wait();
  pdl_trigger();
  if (tid == 0) {
    for (int kt = 0; kt < K4_ST; kt++) tma2d(sbase + kt * K4_STAGE, &tmh, kt * 64, m * 128, fullb + 8 * kt);
  }
  if (tid >= 128) {
    const int r = tid - 128;
    const float4* pp = (const float4*)&g_hpart[(m * 128 + r) * 8];
    float4 p[4];
#pragma unroll
    for (int i = 0; i < 4; i++) p[i] = __ldcg(pp + i);
    float mean = 0.f, m2 = 0.f;
#pragma unroll
    for (int i = 0; i < 4; i++) { mean += p[i].x + p[i].z; m2 += p[i].y + p[i].w; }
    mean *= 0.125f;
#pragma unroll
    for (int i = 0; i < 4; i++) {
      const float d0 = p[i].x - mean, d1 = p[i].z - mean;
      m2 = fmaf(80.f * d0, d0, m2); m2 = fmaf(80.f * d1, d1, m2);
    }
    rowst[r] = make_float2(-mean, __frcp_rn(m2 * (1.f / D_) + 1e-5f));
  }
  __syncwarp();
  float ag[108], au[108];
  const uint64_t da0 = mkdesc(sbase + (warp >> 2) * 8192, 16, 1024, 1);
  const uint64_t db0 = mkdesc(sbase + 16384, 128, 1024, 0);
#pragma unroll 1
  for (int kt = 0; kt < 10; kt++) {
    const int s = kt % K4_ST;
    mbar_wait(fullb + 8 * s, (kt / K4_ST) & 1);
    const uint64_t da = da0 + s * (K4_STAGE >> 4), db = db0 + s * (K4_STAGE >> 4);
    WG_FENCE();
#pragma unroll
    for (int k = 0; k < 4; k++) {
      wgmma_ss_n216(ag, da + k * 2, db + k * 16, (kt | k) != 0);
      wgmma_ss_n216(au, da + k * 2, db + 1728 + k * 16, (kt | k) != 0);
    }
    WG_COMMIT();
    if (kt > 0 && kt - 1 + K4_ST < 10) {
      WG_WAIT(1);
      const int sp = (kt - 1) % K4_ST;
      if ((tid & 127) < 2) mbar_arrive_cta(emptyb + 8 * sp, tid & 1);
      if (tid == 0) {
        const uint32_t sa = sbase + sp * K4_STAGE;
        mbar_wait_cluster(emptyb + 8 * sp, ((kt - 1) / K4_ST) & 1);
        mbar_expect(fullb + 8 * sp, K4_STAGE);
        bulk_ld_mc(sa + 16384 + rank * 27648, wb + (kt - 1 + K4_ST) * 55296, 27648, fullb + 8 * sp);
        tma2d(sa, &tmh, (kt - 1 + K4_ST) * 64, m * 128, fullb + 8 * sp);
      }
      __syncwarp();
    }
  }
  WG_WAIT(0);
  fence_regs(ag); fence_regs(au);
  __syncthreads();
  const int g = lane >> 2, c = lane & 3;
  const float2 st0 = rowst[warp * 16 + g], st1 = rowst[warp * 16 + g + 8];
  bf16* dst = (bf16*)g_hh + (size_t)(m * 128 + warp * 16 + g) * F_ + n * 216 + c * 2;
#pragma unroll
  for (int j = 0; j < 27; j++) {
    const float2 cg = *(const float2*)&cs[j * 8 + c * 2], cu = *(const float2*)&cs[216 + j * 8 + c * 2];
    const float h0 = fmaf(st0.x, cg.x, ag[4 * j]) * st0.y * fmaf(st0.x, cu.x, au[4 * j]);
    const float h1 = fmaf(st0.x, cg.y, ag[4 * j + 1]) * st0.y * fmaf(st0.x, cu.y, au[4 * j + 1]);
    const float h2 = fmaf(st1.x, cg.x, ag[4 * j + 2]) * st1.y * fmaf(st1.x, cu.x, au[4 * j + 2]);
    const float h3 = fmaf(st1.x, cg.y, ag[4 * j + 3]) * st1.y * fmaf(st1.x, cu.y, au[4 * j + 3]);
    *(uint32_t*)(dst + j * 8) = pack_bf16(h0, h1);
    *(uint32_t*)(dst + 8 * F_ + j * 8) = pack_bf16(h2, h3);
  }
  cluster_sync();
}

typedef CUresult (*EncodeFn)(CUtensorMap*, CUtensorMapDataType, cuuint32_t, void*, const cuuint64_t*, const cuuint64_t*,
                             const cuuint32_t*, const cuuint32_t*, CUtensorMapInterleave, CUtensorMapSwizzle,
                             CUtensorMapL2promotion, CUtensorMapFloatOOBfill);

static CUtensorMap make_map(EncodeFn enc, const void* p, uint64_t inner, uint64_t outer, uint32_t box_outer) {
  CUtensorMap m;
  cuuint64_t gd[2] = {inner, outer};
  cuuint64_t gs[1] = {inner * 2};
  cuuint32_t bd[2] = {64, box_outer};
  cuuint32_t es[2] = {1, 1};
  enc(&m, CU_TENSOR_MAP_DATA_TYPE_BFLOAT16, 2, (void*)p, gd, gs, bd, es, CU_TENSOR_MAP_INTERLEAVE_NONE,
      CU_TENSOR_MAP_SWIZZLE_128B, CU_TENSOR_MAP_L2_PROMOTION_L2_256B, CU_TENSOR_MAP_FLOAT_OOB_FILL_NONE);
  return m;
}

template <typename... KArgs, typename... Args>
static void launch(void (*k)(KArgs...), int threads, int smem, bool pdl, Args... args) {
  cudaLaunchConfig_t cfg = {};
  cfg.gridDim = dim3(128);
  cfg.blockDim = dim3(threads);
  cfg.dynamicSmemBytes = smem;
  cfg.stream = cudaStreamPerThread;
  cudaLaunchAttribute at[1];
  at[0].id = cudaLaunchAttributeProgrammaticStreamSerialization;
  at[0].val.programmaticStreamSerializationAllowed = 1;
  cfg.attrs = at;
  cfg.numAttrs = pdl ? 1 : 0;
  cudaLaunchKernelEx(&cfg, k, KArgs(args)...);
}

extern "C" void kernel_launch(void* const* d_in, const int* in_sizes, int n_in, void* d_out, int out_size) {
  const bf16* x = (const bf16*)d_in[0];
  const bf16* wqkv = (const bf16*)d_in[1];
  const bf16* wo = (const bf16*)d_in[2];
  const bf16* wg = (const bf16*)d_in[4];
  const bf16* wu = (const bf16*)d_in[5];
  const bf16* wd = (const bf16*)d_in[6];

  static EncodeFn enc = nullptr;
  static void *p_o, *p_h, *p_hh, *p_wo, *p_wd;
  if (!enc) {
    void* fn = nullptr;
    cudaDriverEntryPointQueryResult qr;
    cudaGetDriverEntryPoint("cuTensorMapEncodeTiled", &fn, cudaEnableDefault, &qr);
    enc = (EncodeFn)fn;
    cudaGetSymbolAddress(&p_o, g_o); cudaGetSymbolAddress(&p_h, g_h); cudaGetSymbolAddress(&p_hh, g_hh);
    cudaGetSymbolAddress(&p_wo, g_wo); cudaGetSymbolAddress(&p_wd, g_wd);
    cudaFuncSetAttribute(k1_qkv, cudaFuncAttributeMaxDynamicSharedMemorySize, K1_SMEM);
    cudaFuncSetAttribute(k2_attn, cudaFuncAttributeMaxDynamicSharedMemorySize, K2_SMEM + 512);
    cudaFuncSetAttribute(k3_proj<10, true>, cudaFuncAttributeMaxDynamicSharedMemorySize, K3_SMEM);
    cudaFuncSetAttribute(k3_proj<27, false>, cudaFuncAttributeMaxDynamicSharedMemorySize, K3_SMEM);
    cudaFuncSetAttribute(k4_ffn1, cudaFuncAttributeMaxDynamicSharedMemorySize, K4_SMEM);
  }
  const CUtensorMap tmx = make_map(enc, x, D_, S_, 128);
  const CUtensorMap tmw = make_map(enc, wqkv, 3 * D_, D_, 32);
  const CUtensorMap tmo = make_map(enc, p_o, D_, S_, 64);
  const CUtensorMap tmh = make_map(enc, p_h, D_, S_, 128);
  const CUtensorMap tmhh = make_map(enc, p_hh, F_, S_, 64);

  launch(k1_qkv, 384, K1_SMEM, false, tmx, tmw, x, wqkv);
  launch(k2_attn, 512, K2_SMEM + 512, true, wo, wg, wu, wd, 0x007f007fu);
  launch(k3_proj<10, true>, 384, K3_SMEM, true, tmo, (const uint4*)p_wo, x, (bf16*)p_h);
  launch(k4_ffn1, 256, K4_SMEM, true, tmh);
  launch(k3_proj<27, false>, 384, K3_SMEM, true, tmhh, (const uint4*)p_wd, (const bf16*)p_h, (bf16*)d_out);
}
```

```cpp
#include <cuda_runtime.h>
#include <cuda_bf16.h>
#include <cuda.h>
#include <stdint.h>

typedef __nv_bfloat16 bf16;

constexpr int S_ = 2048, D_ = 640, F_ = 1728;
constexpr int HEAD_IMG = 98304;
constexpr uint32_t POLY_MASK = 0xBBAB;
constexpr float QSCALE = 0.22360679774997896f * 1.4426950408889634f;

__device__ __align__(1024) uint4 g_qkv[96 * HEAD_IMG / 16];
__device__ __align__(1024) uint4 g_o[S_ * D_ / 8];
__device__ __align__(1024) uint4 g_h[S_ * D_ / 8];
__device__ __align__(1024) uint4 g_hh[S_ * F_ / 8];
__device__ __align__(1024) uint4 g_wo[D_ * D_ / 8];
__device__ __align__(1024) uint4 g_wgu[2 * D_ * F_ / 8];
__device__ __align__(1024) uint4 g_wd[F_ * D_ / 8];
__device__ float2 g_rowstat[S_];
__device__ float g_cpart[16 * 2048];
__device__ float g_csgu[2 * F_];
__device__ float2 g_hpart[8 * S_];
__device__ unsigned g_cnt[24 * 32];

#define STAMP(k, i)
__device__ __forceinline__ uint32_t smem_u32(const void* p) { return (uint32_t)__cvta_generic_to_shared(p); }
__device__ __forceinline__ void mbar_init(uint32_t a, uint32_t c) {
  asm volatile("mbarrier.init.shared::cta.b64 [%0], %1;" ::"r"(a), "r"(c) : "memory");
}
__device__ __forceinline__ void mbar_expect(uint32_t a, uint32_t bytes) {
  asm volatile("mbarrier.arrive.expect_tx.shared::cta.b64 _, [%0], %1;" ::"r"(a), "r"(bytes) : "memory");
}
__device__ __forceinline__ void mbar_arrive(uint32_t a) {
  asm volatile("mbarrier.arrive.shared::cta.b64 _, [%0];" ::"r"(a) : "memory");
}
__device__ __forceinline__ void mbar_arrive_cta(uint32_t a, uint32_t cta) {
  asm volatile("{\n.reg .b32 r;\nmapa.shared::cluster.u32 r, %0, %1;\n"
               "mbarrier.arrive.shared::cluster.b64 _, [r];\n}" ::"r"(a), "r"(cta) : "memory");
}
__device__ __forceinline__ bool mbar_try(uint32_t a, uint32_t ph) {
  uint32_t ok;
  asm volatile("{\n.reg .pred p;\nmbarrier.try_wait.parity.shared::cta.b64 p, [%1], %2;\nselp.u32 %0, 1, 0, p;\n}"
               : "=r"(ok) : "r"(a), "r"(ph) : "memory");
  return ok;
}
__device__ __noinline__ void wait_timeout() { __trap(); }
__device__ __forceinline__ void mbar_wait(uint32_t a, uint32_t ph) {
  if (mbar_try(a, ph)) return;
  uint32_t it = 0;
  while (!mbar_try(a, ph)) if (++it > (1u << 22)) wait_timeout();
}
__device__ __forceinline__ void tma2d(uint32_t dst, const CUtensorMap* m, int c0, int c1, uint32_t bar) {
  asm volatile("cp.async.bulk.tensor.2d.shared::cluster.global.mbarrier::complete_tx::bytes [%0], [%1, {%3, %4}], [%2];"
               ::"r"(dst), "l"(m), "r"(bar), "r"(c0), "r"(c1) : "memory");
}
__device__ __forceinline__ void tma2d_mc(uint32_t dst, const CUtensorMap* m, int c0, int c1, uint32_t bar) {
  asm volatile("cp.async.bulk.tensor.2d.shared::cluster.global.mbarrier::complete_tx::bytes.multicast::cluster "
               "[%0], [%1, {%3, %4}], [%2], %5;"
               ::"r"(dst), "l"(m), "r"(bar), "r"(c0), "r"(c1), "h"((uint16_t)3) : "memory");
}
__device__ __forceinline__ void bulk_ld(uint32_t dst, const void* src, uint32_t bytes, uint32_t bar) {
  asm volatile("cp.async.bulk.shared::cluster.global.mbarrier::complete_tx::bytes [%0], [%1], %2, [%3];"
               ::"r"(dst), "l"(src), "r"(bytes), "r"(bar) : "memory");
}
__device__ __forceinline__ void bulk_ld_mc(uint32_t dst, const void* src, uint32_t bytes, uint32_t bar) {
  asm volatile("cp.async.bulk.shared::cluster.global.mbarrier::complete_tx::bytes.multicast::cluster "
               "[%0], [%1], %2, [%3], %4;"
               ::"r"(dst), "l"(src), "r"(bytes), "r"(bar), "h"((uint16_t)3) : "memory");
}
__device__ __forceinline__ void cluster_arrive() { asm volatile("barrier.cluster.arrive.relaxed.aligned;" ::: "memory"); }
__device__ __forceinline__ void cluster_wait() { asm volatile("barrier.cluster.wait.aligned;" ::: "memory"); }
__device__ __forceinline__ void bulk_st(void* dst, uint32_t src, uint32_t bytes) {
  asm volatile("cp.async.bulk.global.shared::cta.bulk_group [%0], [%1], %2;" ::"l"(dst), "r"(src), "r"(bytes) : "memory");
}
__device__ __forceinline__ void tma2d_st(const CUtensorMap* m, int c0, int c1, uint32_t src) {
  asm volatile("cp.async.bulk.tensor.2d.global.shared::cta.bulk_group [%0, {%2, %3}], [%1];"
               ::"l"(m), "r"(src), "r"(c0), "r"(c1) : "memory");
}
__device__ __forceinline__ void bulk_commit_wait() {
  asm volatile("cp.async.bulk.commit_group;\ncp.async.bulk.wait_group.read 0;" ::: "memory");
}
__device__ __forceinline__ void fence_async() { asm volatile("fence.proxy.async.shared::cta;" ::: "memory"); }
__device__ __forceinline__ void prefetch_map(const CUtensorMap* m) {
  asm volatile("prefetch.tensormap [%0];" ::"l"(m) : "memory");
}
__device__ __forceinline__ void cluster_sync_relaxed() {
  __syncwarp();
  asm volatile("barrier.cluster.arrive.relaxed.aligned;\nbarrier.cluster.wait.aligned;" ::: "memory");
}
__device__ __forceinline__ void pdl_wait() { asm volatile("griddepcontrol.wait;" ::: "memory"); }
__device__ __forceinline__ void pdl_trigger() { asm volatile("griddepcontrol.launch_dependents;" ::: "memory"); }
__device__ __forceinline__ void bar_sync(int id, int n) { asm volatile("bar.sync %0, %1;" ::"r"(id), "r"(n) : "memory"); }
__device__ __forceinline__ void bar_arrive(int id, int n) { asm volatile("bar.arrive %0, %1;" ::"r"(id), "r"(n) : "memory"); }
#define WG_FENCE() asm volatile("wgmma.fence.sync.aligned;" ::: "memory")
#define WG_COMMIT() asm volatile("wgmma.commit_group.sync.aligned;" ::: "memory")
#define WG_WAIT(n) asm volatile("wgmma.wait_group.sync.aligned %0;" ::"n"(n) : "memory")
__device__ __forceinline__ uint64_t mkdesc(uint32_t addr, uint32_t lbo, uint32_t sbo, uint32_t sw) {
  return (uint64_t)((addr & 0x3FFFF) >> 4) | ((uint64_t)(lbo >> 4) << 16) | ((uint64_t)(sbo >> 4) << 32) |
         ((uint64_t)sw << 62);
}
template <int N> __device__ __forceinline__ void fence_regs(float (&r)[N]) {
#pragma unroll
  for (int i = 0; i < N; i++) asm volatile("" : "+f"(r[i])::"memory");
}
__device__ __forceinline__ uint32_t pack_bf16(float lo, float hi) {
  uint32_t r;
  asm("cvt.rn.bf16x2.f32 %0, %1, %2;" : "=r"(r) : "f"(hi), "f"(lo));
  return r;
}
__device__ __forceinline__ float bf_lo(uint32_t v) { return __uint_as_float(v << 16); }
__device__ __forceinline__ float bf_hi(uint32_t v) { return __uint_as_float(v & 0xffff0000u); }
__device__ __forceinline__ float ex2(float x) {
  float y;
  asm("ex2.approx.ftz.f32 %0, %1;" : "=f"(y) : "f"(x));
  return y;
}
__device__ __forceinline__ uint4 ldg_nc(const void* p) {
  uint4 v;
  asm volatile("ld.global.nc.L1::no_allocate.v4.u32 {%0, %1, %2, %3}, [%4];"
               : "=r"(v.x), "=r"(v.y), "=r"(v.z), "=r"(v.w) : "l"(p));
  return v;
}

__device__ __forceinline__ void wgmma_ss_n256(float (&d)[128], uint64_t da, uint64_t db, int sd) {
  asm volatile("{\n.reg .pred p;\nsetp.ne.b32 p, %130, 0;\n"
      "wgmma.mma_async.sync.aligned.m64n256k16.f32.bf16.bf16 {"
      "%0, %1, %2, %3, %4, %5, %6, %7, %8, %9, %10, %11, %12, %13, %14, %15, "
      "%16, %17, %18, %19, %20, %21, %22, %23, %24, %25, %26, %27, %28, %29, %30, %31, "
      "%32, %33, %34, %35, %36, %37, %38, %39, %40, %41, %42, %43, %44, %45, %46, %47, "
      "%48, %49, %50, %51, %52, %53, %54, %55, %56, %57, %58, %59, %60, %61, %62, %63, "
      "%64, %65, %66, %67, %68, %69, %70, %71, %72, %73, %74, %75, %76, %77, %78, %79, "
      "%80, %81, %82, %83, %84, %85, %86, %87, %88, %89, %90, %91, %92, %93, %94, %95, "
      "%96, %97, %98, %99, %100, %101, %102, %103, %104, %105, %106, %107, %108, %109, %110, %111, "
      "%112, %113, %114, %115, %116, %117, %118, %119, %120, %121, %122, %123, %124, %125, %126, %127"
      "}, %128, %129, p, 1, 1, 0, 1;\n}\n"
    : "+f"(d[0]), "+f"(d[1]), "+f"(d[2]), "+f"(d[3]), "+f"(d[4]), "+f"(d[5]), "+f"(d[6]), "+f"(d[7]),
      "+f"(d[8]), "+f"(d[9]), "+f"(d[10]), "+f"(d[11]), "+f"(d[12]), "+f"(d[13]), "+f"(d[14]), "+f"(d[15]),
      "+f"(d[16]), "+f"(d[17]), "+f"(d[18]), "+f"(d[19]), "+f"(d[20]), "+f"(d[21]), "+f"(d[22]), "+f"(d[23]),
      "+f"(d[24]), "+f"(d[25]), "+f"(d[26]), "+f"(d[27]), "+f"(d[28]), "+f"(d[29]), "+f"(d[30]), "+f"(d[31]),
      "+f"(d[32]), "+f"(d[33]), "+f"(d[34]), "+f"(d[35]), "+f"(d[36]), "+f"(d[37]), "+f"(d[38]), "+f"(d[39]),
      "+f"(d[40]), "+f"(d[41]), "+f"(d[42]), "+f"(d[43]), "+f"(d[44]), "+f"(d[45]), "+f"(d[46]), "+f"(d[47]),
      "+f"(d[48]), "+f"(d[49]), "+f"(d[50]), "+f"(d[51]), "+f"(d[52]), "+f"(d[53]), "+f"(d[54]), "+f"(d[55]),
      "+f"(d[56]), "+f"(d[57]), "+f"(d[58]), "+f"(d[59]), "+f"(d[60]), "+f"(d[61]), "+f"(d[62]), "+f"(d[63]),
      "+f"(d[64]), "+f"(d[65]), "+f"(d[66]), "+f"(d[67]), "+f"(d[68]), "+f"(d[69]), "+f"(d[70]), "+f"(d[71]),
      "+f"(d[72]), "+f"(d[73]), "+f"(d[74]), "+f"(d[75]), "+f"(d[76]), "+f"(d[77]), "+f"(d[78]), "+f"(d[79]),
      "+f"(d[80]), "+f"(d[81]), "+f"(d[82]), "+f"(d[83]), "+f"(d[84]), "+f"(d[85]), "+f"(d[86]), "+f"(d[87]),
      "+f"(d[88]), "+f"(d[89]), "+f"(d[90]), "+f"(d[91]), "+f"(d[92]), "+f"(d[93]), "+f"(d[94]), "+f"(d[95]),
      "+f"(d[96]), "+f"(d[97]), "+f"(d[98]), "+f"(d[99]), "+f"(d[100]), "+f"(d[101]), "+f"(d[102]), "+f"(d[103]),
      "+f"(d[104]), "+f"(d[105]), "+f"(d[106]), "+f"(d[107]), "+f"(d[108]), "+f"(d[109]), "+f"(d[110]), "+f"(d[111]),
      "+f"(d[112]), "+f"(d[113]), "+f"(d[114]), "+f"(d[115]), "+f"(d[116]), "+f"(d[117]), "+f"(d[118]), "+f"(d[119]),
      "+f"(d[120]), "+f"(d[121]), "+f"(d[122]), "+f"(d[123]), "+f"(d[124]), "+f"(d[125]), "+f"(d[126]), "+f"(d[127])
    : "l"(da), "l"(db), "r"(sd));
}
__device__ __forceinline__ void wgmma_ss_n216(float (&d)[108], uint64_t da, uint64_t db, int sd) {
  asm volatile("{\n.reg .pred p;\nsetp.ne.b32 p, %110, 0;\n"
      "wgmma.mma_async.sync.aligned.m64n216k16.f32.bf16.bf16 {"
      "%0, %1, %2, %3, %4, %5, %6, %7, %8, %9, %10, %11, %12, %13, %14, %15, "
      "%16, %17, %18, %19, %20, %21, %22, %23, %24, %25, %26, %27, %28, %29, %30, %31, "
      "%32, %33, %34, %35, %36, %37, %38, %39, %40, %41, %42, %43, %44, %45, %46, %47, "
      "%48, %49, %50, %51, %52, %53, %54, %55, %56, %57, %58, %59, %60, %61, %62, %63, "
      "%64, %65, %66, %67, %68, %69, %70, %71, %72, %73, %74, %75, %76, %77, %78, %79, "
      "%80, %81, %82, %83, %84, %85, %86, %87, %88, %89, %90, %91, %92, %93, %94, %95, "
      "%96, %97, %98, %99, %100, %101, %102, %103, %104, %105, %106, %107"
      "}, %108, %109, p, 1, 1, 0, 1;\n}\n"
    : "+f"(d[0]), "+f"(d[1]), "+f"(d[2]), "+f"(d[3]), "+f"(d[4]), "+f"(d[5]), "+f"(d[6]), "+f"(d[7]),
      "+f"(d[8]), "+f"(d[9]), "+f"(d[10]), "+f"(d[11]), "+f"(d[12]), "+f"(d[13]), "+f"(d[14]), "+f"(d[15]),
      "+f"(d[16]), "+f"(d[17]), "+f"(d[18]), "+f"(d[19]), "+f"(d[20]), "+f"(d[21]), "+f"(d[22]), "+f"(d[23]),
      "+f"(d[24]), "+f"(d[25]), "+f"(d[26]), "+f"(d[27]), "+f"(d[28]), "+f"(d[29]), "+f"(d[30]), "+f"(d[31]),
      "+f"(d[32]), "+f"(d[33]), "+f"(d[34]), "+f"(d[35]), "+f"(d[36]), "+f"(d[37]), "+f"(d[38]), "+f"(d[39]),
      "+f"(d[40]), "+f"(d[41]), "+f"(d[42]), "+f"(d[43]), "+f"(d[44]), "+f"(d[45]), "+f"(d[46]), "+f"(d[47]),
      "+f"(d[48]), "+f"(d[49]), "+f"(d[50]), "+f"(d[51]), "+f"(d[52]), "+f"(d[53]), "+f"(d[54]), "+f"(d[55]),
      "+f"(d[56]), "+f"(d[57]), "+f"(d[58]), "+f"(d[59]), "+f"(d[60]), "+f"(d[61]), "+f"(d[62]), "+f"(d[63]),
      "+f"(d[64]), "+f"(d[65]), "+f"(d[66]), "+f"(d[67]), "+f"(d[68]), "+f"(d[69]), "+f"(d[70]), "+f"(d[71]),
      "+f"(d[72]), "+f"(d[73]), "+f"(d[74]), "+f"(d[75]), "+f"(d[76]), "+f"(d[77]), "+f"(d[78]), "+f"(d[79]),
      "+f"(d[80]), "+f"(d[81]), "+f"(d[82]), "+f"(d[83]), "+f"(d[84]), "+f"(d[85]), "+f"(d[86]), "+f"(d[87]),
      "+f"(d[88]), "+f"(d[89]), "+f"(d[90]), "+f"(d[91]), "+f"(d[92]), "+f"(d[93]), "+f"(d[94]), "+f"(d[95]),
      "+f"(d[96]), "+f"(d[97]), "+f"(d[98]), "+f"(d[99]), "+f"(d[100]), "+f"(d[101]), "+f"(d[102]), "+f"(d[103]),
      "+f"(d[104]), "+f"(d[105]), "+f"(d[106]), "+f"(d[107])
    : "l"(da), "l"(db), "r"(sd));
}
__device__ __forceinline__ void wgmma_ss_n80(float (&d)[40], uint64_t da, uint64_t db, int sd) {
  asm volatile("{\n.reg .pred p;\nsetp.ne.b32 p, %42, 0;\n"
      "wgmma.mma_async.sync.aligned.m64n80k16.f32.bf16.bf16 {"
      "%0, %1, %2, %3, %4, %5, %6, %7, %8, %9, %10, %11, %12, %13, %14, %15, "
      "%16, %17, %18, %19, %20, %21, %22, %23, %24, %25, %26, %27, %28, %29, %30, %31, "
      "%32, %33, %34, %35, %36, %37, %38, %39"
      "}, %40, %41, p, 1, 1, 0, 1;\n}\n"
    : "+f"(d[0]), "+f"(d[1]), "+f"(d[2]), "+f"(d[3]), "+f"(d[4]), "+f"(d[5]), "+f"(d[6]), "+f"(d[7]),
      "+f"(d[8]), "+f"(d[9]), "+f"(d[10]), "+f"(d[11]), "+f"(d[12]), "+f"(d[13]), "+f"(d[14]), "+f"(d[15]),
      "+f"(d[16]), "+f"(d[17]), "+f"(d[18]), "+f"(d[19]), "+f"(d[20]), "+f"(d[21]), "+f"(d[22]), "+f"(d[23]),
      "+f"(d[24]), "+f"(d[25]), "+f"(d[26]), "+f"(d[27]), "+f"(d[28]), "+f"(d[29]), "+f"(d[30]), "+f"(d[31]),
      "+f"(d[32]), "+f"(d[33]), "+f"(d[34]), "+f"(d[35]), "+f"(d[36]), "+f"(d[37]), "+f"(d[38]), "+f"(d[39])
    : "l"(da), "l"(db), "r"(sd));
}
__device__ __forceinline__ void wgmma_rs_n128(float (&d)[64], uint32_t a0, uint32_t a1, uint32_t a2, uint32_t a3,
                                  uint64_t db, int sd) {
  asm volatile("{\n.reg .pred p;\nsetp.ne.b32 p, %69, 0;\n"
      "wgmma.mma_async.sync.aligned.m64n128k16.f32.bf16.bf16 {"
      "%0, %1, %2, %3, %4, %5, %6, %7, %8, %9, %10, %11, %12, %13, %14, %15, "
      "%16, %17, %18, %19, %20, %21, %22, %23, %24, %25, %26, %27, %28, %29, %30, %31, "
      "%32, %33, %34, %35, %36, %37, %38, %39, %40, %41, %42, %43, %44, %45, %46, %47, "
      "%48, %49, %50, %51, %52, %53, %54, %55, %56, %57, %58, %59, %60, %61, %62, %63"
      "}, {%64, %65, %66, %67}, %68, p, 1, 1, 0;\n}\n"
    : "+f"(d[0]), "+f"(d[1]), "+f"(d[2]), "+f"(d[3]), "+f"(d[4]), "+f"(d[5]), "+f"(d[6]), "+f"(d[7]),
      "+f"(d[8]), "+f"(d[9]), "+f"(d[10]), "+f"(d[11]), "+f"(d[12]), "+f"(d[13]), "+f"(d[14]), "+f"(d[15]),
      "+f"(d[16]), "+f"(d[17]), "+f"(d[18]), "+f"(d[19]), "+f"(d[20]), "+f"(d[21]), "+f"(d[22]), "+f"(d[23]),
      "+f"(d[24]), "+f"(d[25]), "+f"(d[26]), "+f"(d[27]), "+f"(d[28]), "+f"(d[29]), "+f"(d[30]), "+f"(d[31]),
      "+f"(d[32]), "+f"(d[33]), "+f"(d[34]), "+f"(d[35]), "+f"(d[36]), "+f"(d[37]), "+f"(d[38]), "+f"(d[39]),
      "+f"(d[40]), "+f"(d[41]), "+f"(d[42]), "+f"(d[43]), "+f"(d[44]), "+f"(d[45]), "+f"(d[46]), "+f"(d[47]),
      "+f"(d[48]), "+f"(d[49]), "+f"(d[50]), "+f"(d[51]), "+f"(d[52]), "+f"(d[53]), "+f"(d[54]), "+f"(d[55]),
      "+f"(d[56]), "+f"(d[57]), "+f"(d[58]), "+f"(d[59]), "+f"(d[60]), "+f"(d[61]), "+f"(d[62]), "+f"(d[63])
    : "r"(a0), "r"(a1), "r"(a2), "r"(a3), "l"(db), "r"(sd));
}
__device__ __forceinline__ void wgmma_rs_n24(float (&d)[12], uint32_t a0, uint32_t a1, uint32_t a2, uint32_t a3,
                                  uint64_t db, int sd) {
  asm volatile("{\n.reg .pred p;\nsetp.ne.b32 p, %17, 0;\n"
      "wgmma.mma_async.sync.aligned.m64n24k16.f32.bf16.bf16 {"
      "%0, %1, %2, %3, %4, %5, %6, %7, %8, %9, %10, %11"
      "}, {%12, %13, %14, %15}, %16, p, 1, 1, 1;\n}\n"
    : "+f"(d[0]), "+f"(d[1]), "+f"(d[2]), "+f"(d[3]), "+f"(d[4]), "+f"(d[5]), "+f"(d[6]), "+f"(d[7]),
      "+f"(d[8]), "+f"(d[9]), "+f"(d[10]), "+f"(d[11])
    : "r"(a0), "r"(a1), "r"(a2), "r"(a3), "l"(db), "r"(sd));
}

constexpr int K1_ST = 4, K1_STAGE = 49152;
constexpr int K1_SMEM = K1_ST * K1_STAGE + 2048   + 1024   + 3072   + 128;

__global__ void __cluster_dims__(2, 1, 1) __launch_bounds__(384, 1)
k1_qkv(const __grid_constant__ CUtensorMap tmx, const __grid_constant__ CUtensorMap tmw,
       const bf16* __restrict__ x, const bf16* __restrict__ w) {
  extern __shared__ __align__(1024) uint8_t sm[];
  float4* tab = (float4*)(sm + K1_ST * K1_STAGE);
  float2* rowab = (float2*)(sm + K1_ST * K1_STAGE + 2048);
  float* red = (float*)(sm + K1_ST * K1_STAGE + 3072);
  const uint32_t sbase = smem_u32(sm);
  const uint32_t fullb = sbase + K1_ST * K1_STAGE + 6144, emptyb = fullb + 8 * K1_ST;
  const int tid = threadIdx.x, lane = tid & 31;
  const int warp = __shfl_sync(~0u, tid >> 5, 0);
  const int rank = blockIdx.x & 1, cl = blockIdx.x >> 1;
  const int n = cl & 7, m = (cl >> 3) * 2 + rank;
  const int c0 = n * 240 - (n & 1) * 16;
  if (tid == 0) STAMP(0, 0);
  if (tid == 0) {
    prefetch_map(&tmx); prefetch_map(&tmw);
    for (int i = 0; i < K1_ST; i++) { mbar_init(fullb + 8 * i, 1); mbar_init(emptyb + 8 * i, 4); }
    asm volatile("fence.mbarrier_init.release.cluster;" ::: "memory");
  }
  __syncthreads();
  cluster_arrive();
  pdl_trigger();

  if (warp == 0) {
    if (lane == 0) {
      for (int kt = 0; kt < K1_ST; kt++) {
        mbar_expect(fullb + 8 * kt, K1_STAGE);
        tma2d(sbase + kt * K1_STAGE, &tmx, kt * 64, m * 128, fullb + 8 * kt);
      }
    }
    __syncwarp();
    cluster_wait();
    if (lane == 0) {
      for (int kt = 0; kt < 10; kt++) {
        const int s = kt % K1_ST;
        const uint32_t sa = sbase + s * K1_STAGE, sb = sa + 16384 + rank * 16384;
        if (kt >= K1_ST) {
          mbar_wait(emptyb + 8 * s, ((kt / K1_ST) - 1) & 1);
          mbar_expect(fullb + 8 * s, K1_STAGE);
          tma2d(sa, &tmx, kt * 64, m * 128, fullb + 8 * s);
        }
#pragma unroll
        for (int j = 0; j < 4; j++) tma2d_mc(sb + j * 4096, &tmw, c0 + rank * 128 + j * 32, kt * 64, fullb + 8 * s);
      }
    }
    __syncwarp();
  } else if (warp < 4) {
    const int w3 = warp - 1, t96 = tid - 32;
    {
      float acc8[8];
#pragma unroll
      for (int i = 0; i < 8; i++) acc8[i] = 0.f;
#pragma unroll 7
      for (int r = w3; r < 40; r += 3) {
        uint4 v = ldg_nc(w + (size_t)(m * 40 + r) * 1920 + c0 + lane * 8);
        acc8[0] += bf_lo(v.x); acc8[1] += bf_hi(v.x); acc8[2] += bf_lo(v.y); acc8[3] += bf_hi(v.y);
        acc8[4] += bf_lo(v.z); acc8[5] += bf_hi(v.z); acc8[6] += bf_lo(v.w); acc8[7] += bf_hi(v.w);
      }
#pragma unroll
      for (int i = 0; i < 8; i++) red[w3 * 256 + lane * 8 + i] = acc8[i];
    }
#pragma unroll 2
    for (int r = w3; r < 16; r += 3) {
      const int row = m * 128 + n * 16 + r;
      const bf16* xr = x + (size_t)row * D_;
      uint4 v[3];
      v[0] = ldg_nc(xr + lane * 8);
      v[1] = ldg_nc(xr + 256 + lane * 8);
      v[2] = make_uint4(0, 0, 0, 0);
      if (lane < 16) v[2] = ldg_nc(xr + 512 + lane * 8);
      float f[24];
#pragma unroll
      for (int i = 0; i < 3; i++) {
        f[8 * i + 0] = bf_lo(v[i].x); f[8 * i + 1] = bf_hi(v[i].x); f[8 * i + 2] = bf_lo(v[i].y); f[8 * i + 3] = bf_hi(v[i].y);
        f[8 * i + 4] = bf_lo(v[i].z); f[8 * i + 5] = bf_hi(v[i].z); f[8 * i + 6] = bf_lo(v[i].w); f[8 * i + 7] = bf_hi(v[i].w);
      }
      float s = 0.f;
#pragma unroll
      for (int i = 0; i < 24; i++) s += f[i];
#pragma unroll
      for (int o = 16; o; o >>= 1) s += __shfl_xor_sync(~0u, s, o);
      const float mean = s * (1.f / D_);
      float q = 0.f;
#pragma unroll
      for (int i = 0; i < 16; i++) { float d = f[i] - mean; q = fmaf(d, d, q); }
      if (lane < 16) {
#pragma unroll
        for (int i = 16; i < 24; i++) { float d = f[i] - mean; q = fmaf(d, d, q); }
      }
#pragma unroll
      for (int o = 16; o; o >>= 1) q += __shfl_xor_sync(~0u, q, o);
      if (lane == 0) g_rowstat[row] = make_float2(rsqrtf(q * (1.f / D_) + 1e-5f), mean);
    }
    bar_sync(1, 96);
    for (int c = t96; c < 256; c += 96) g_cpart[m * 2048 + n * 256 + c] = red[c] + red[256 + c] + red[512 + c];
    bar_sync(1, 96);
    if (t96 == 0) {
      __threadfence();
      asm volatile("red.relaxed.gpu.global.add.u32 [%0], 1;" ::"l"(&g_cnt[m * 32]) : "memory");
      asm volatile("red.relaxed.gpu.global.add.u32 [%0], 1;" ::"l"(&g_cnt[(16 + n) * 32]) : "memory");
      uint32_t a, b, it = 0;
      while (true) {
        asm volatile("ld.relaxed.gpu.global.u32 %0, [%1];" : "=r"(a) : "l"(&g_cnt[m * 32]) : "memory");
        asm volatile("ld.relaxed.gpu.global.u32 %0, [%1];" : "=r"(b) : "l"(&g_cnt[(16 + n) * 32]) : "memory");
        if (a >= 8 && b >= 16) break;
        if (++it > (1u << 22)) wait_timeout();
        __nanosleep(64);
      }
      __threadfence();
    }
    bar_sync(1, 96);
    for (int r = t96; r < 128; r += 96) {
      float2 st = __ldcg(&g_rowstat[m * 128 + r]);
      rowab[r] = make_float2(st.x, -st.x * st.y);
      float s0 = 0.f, s1 = 0.f;
#pragma unroll
      for (int i = 0; i < 16; i++) {
        float2 p = __ldcg((const float2*)&g_cpart[i * 2048 + n * 256 + 2 * r]);
        s0 += p.x; s1 += p.y;
      }
      const int lc = max(2 * r - (n & 1) * 16, 0), hl = lc / 20, d = lc - hl * 20;
      tab[r] = make_float4(s0, s1, __int_as_float(hl * 6144 + (d >> 3) * 128 + (d & 7) * 2), 0.f);
    }
    cluster_wait();
    if (tid == 32) STAMP(0, 5);
    bar_sync(2, 96 + 256);
    for (int i = t96; i < 12 * 128; i += 96) {
      const int hl = i >> 7, r = i & 127, sh = n * 12 + hl;
      uint2 v;
      if (sh < 32) v = make_uint2(0x3F803F80u, 0x00003F80u);
      else if (sh >= 64) v = make_uint2(0x00003F80u, 0u);
      else if ((POLY_MASK >> (r >> 3)) & 1) v = make_uint2(0x4A7A4B00u, 0x00004653u);
      else v = make_uint2(0u, 0u);
      *(uint2*)(sm + hl * 6144 + (r >> 3) * 384 + 256 + (r & 7) * 16 + 8) = v;
    }
    fence_async();
    bar_sync(3, 96 + 256);
    if (t96 < 12) {
      bulk_st((uint8_t*)g_qkv + (size_t)(n * 12 + t96) * HEAD_IMG + m * 6144, sbase + t96 * 6144, 6144);
      bulk_commit_wait();
    }
    __syncwarp();
  } else {
    const int cw = warp - 4, wg = cw >> 2;
    float acc[128];
    const uint64_t da0 = mkdesc(sbase + wg * 8192, 16, 1024, 1);
    const uint64_t db0 = mkdesc(sbase + 16384, 4096, 512, 2);
    cluster_wait();
#pragma unroll 1
    for (int kt = 0; kt < 10; kt++) {
      const int s = kt % K1_ST;
      mbar_wait(fullb + 8 * s, (kt / K1_ST) & 1);
      if (kt == 0 && tid == 128) STAMP(0, 1);
      const uint64_t da = da0 + s * (K1_STAGE >> 4), db = db0 + s * (K1_STAGE >> 4);
      WG_FENCE();
#pragma unroll
      for (int k = 0; k < 4; k++) wgmma_ss_n256(acc, da + k * 2, db + k * 64, (kt | k) != 0);
      WG_COMMIT();
      if (kt > 0) {
        WG_WAIT(1);
        if (kt - 1 + K1_ST < 10 && (tid & 127) < 2) mbar_arrive_cta(emptyb + 8 * ((kt - 1) % K1_ST), tid & 1);
      }
    }
    WG_WAIT(0);
    fence_regs(acc);
    if (tid == 128) STAMP(0, 2);
    bar_sync(2, 96 + 256);
    if (tid == 128) STAMP(0, 3);
    const int g = lane >> 2, c = lane & 3;
    const float2 ab0 = rowab[cw * 16 + g], ab1 = rowab[cw * 16 + g + 8];
    const float k0 = ((POLY_MASK >> (cw * 2)) & 1) ? 32768.f : 1.f, k1 = ((POLY_MASK >> (cw * 2 + 1)) & 1) ? 32768.f : 1.f;
    uint8_t* dst = sm + cw * 768 + g * 16;
#pragma unroll
    for (int seg = 0; seg < 3; seg++) {
      const int j0 = seg == 0 ? 0 : (seg == 1 ? 12 : 20), j1 = seg == 0 ? 12 : (seg == 1 ? 20 : 32);
      const int sec = (c0 + j0 * 8 + 16) / 640;
      const float f0 = sec == 0 ? QSCALE : (sec == 1 ? k0 : 1.f), f1 = sec == 0 ? QSCALE : (sec == 1 ? k1 : 1.f);
      const float a0 = ab0.x * f0, b0 = ab0.y * f0, a1 = ab1.x * f1, b1 = ab1.y * f1;
#pragma unroll
      for (int j = j0; j < j1; j++) {
        if ((j < 2 && (n & 1)) || (j >= 30 && !(n & 1))) continue;
        const float4 t = tab[4 * j + c];
        uint8_t* p = dst + __float_as_int(t.z);
        *(uint32_t*)p = pack_bf16(fmaf(acc[4 * j], a0, b0 * t.x), fmaf(acc[4 * j + 1], a0, b0 * t.y));
        *(uint32_t*)(p + 384) = pack_bf16(fmaf(acc[4 * j + 2], a1, b1 * t.x), fmaf(acc[4 * j + 3], a1, b1 * t.y));
      }
    }
    fence_async();
    bar_arrive(3, 96 + 256);
    if (tid == 128) STAMP(0, 4);
  }
  cluster_sync_relaxed();
  if (tid == 32) STAMP(0, 6);
}

constexpr int K2_SMEM = 2 * HEAD_IMG + 2 * 6144 + 256;

__device__ __forceinline__ uint32_t exp_pair(bool poly, float a, float b, uint32_t mk) {
  if (poly) {
    const uint32_t pk = __byte_perm(__float_as_uint(a), __float_as_uint(b), 0x6521);
    uint32_t m, q;
    asm("lop3.b32 %0, %1, %2, 0x3f803f80, 0xEA;" : "=r"(m) : "r"(pk), "r"(mk));
    asm("fma.rn.bf16x2 %0, %1, %1, %2;" : "=r"(q) : "r"(m), "r"(0x40014001u));
    return pk - m + q;
  }
  return pack_bf16(ex2(a), ex2(b));
}
__device__ __forceinline__ void exp_pv(const float (&s)[64], float (&o)[12], uint64_t dv, uint32_t mk) {
#pragma unroll
  for (int k0 = 0; k0 < 8; k0 += 2) {
    uint32_t p[8];
#pragma unroll
    for (int i = 0; i < 8; i++)
      p[i] = exp_pair((POLY_MASK >> (k0 * 2 + i / 2)) & 1, s[k0 * 8 + 2 * i], s[k0 * 8 + 2 * i + 1], mk);
    WG_FENCE();
    wgmma_rs_n24(o, p[0], p[1], p[2], p[3], dv + k0 * 48, 1);
    wgmma_rs_n24(o, p[4], p[5], p[6], p[7], dv + k0 * 48 + 48, 1);
  }
}
__device__ __forceinline__ void load_q(uint32_t (&q)[6], const uint8_t* p) {
  q[0] = __ldcg((const uint32_t*)p);         q[1] = __ldcg((const uint32_t*)(p + 384));
  q[2] = __ldcg((const uint32_t*)(p + 128)); q[3] = __ldcg((const uint32_t*)(p + 512));
  q[4] = __ldcg((const uint32_t*)(p + 256)); q[5] = __ldcg((const uint32_t*)(p + 640));
}
__device__ __forceinline__ void store_o(const float (&o)[12], uint8_t* dst, int o0, int o1, int o2, int lane) {
  const float l0 = __shfl_sync(~0u, o[8], (lane & ~3) | 2), l1 = __shfl_sync(~0u, o[10], (lane & ~3) | 2);
  const float i0 = __frcp_rn(l0), i1 = __frcp_rn(l1);
  *(uint32_t*)(dst + o0) = pack_bf16(o[0] * i0, o[1] * i0); *(uint32_t*)(dst + o0 + 1024) = pack_bf16(o[2] * i1, o[3] * i1);
  *(uint32_t*)(dst + o1) = pack_bf16(o[4] * i0, o[5] * i0); *(uint32_t*)(dst + o1 + 1024) = pack_bf16(o[6] * i1, o[7] * i1);
  if ((lane & 3) < 2) {
    *(uint32_t*)(dst + o2) = pack_bf16(o[8] * i0, o[9] * i0);
    *(uint32_t*)(dst + o2 + 1024) = pack_bf16(o[10] * i1, o[11] * i1);
  }
}
__device__ __forceinline__ int img_off(int chunk) { return (chunk >> 3) * 16384 + (chunk & 7) * 128; }
__device__ __forceinline__ float sq20(uint4 a, uint4 b, uint2 c) {
  uint32_t s0, s1;
  asm("mul.rn.bf16x2 %0, %1, %1;" : "=r"(s0) : "r"(a.x));
  asm("mul.rn.bf16x2 %0, %1, %1;" : "=r"(s1) : "r"(a.y));
#define SQ_(acc, v) asm("fma.rn.bf16x2 %0, %1, %1, %0;" : "+r"(acc) : "r"(v))
  SQ_(s0, a.z); SQ_(s1, a.w); SQ_(s0, b.x); SQ_(s1, b.y); SQ_(s0, b.z); SQ_(s1, b.w); SQ_(s0, c.x); SQ_(s1, c.y);
#undef SQ_
  return (bf_lo(s0) + bf_hi(s0)) + (bf_lo(s1) + bf_hi(s1));
}

__global__ void __launch_bounds__(512, 1)
k2_attn(const bf16* __restrict__ wo, const bf16* __restrict__ wg_, const bf16* __restrict__ wu,
        const bf16* __restrict__ wd, uint32_t mk) {
  extern __shared__ __align__(1024) uint8_t sm[];
  const uint32_t sbase = smem_u32(sm);
  float* part = (float*)(sm + 2 * HEAD_IMG);
  const uint32_t kvb = sbase + 2 * HEAD_IMG + 2 * 6144;
  const uint32_t flagb = kvb + 128, partb = kvb + 136;
  volatile uint32_t* sflag = (volatile uint32_t*)(sm + 2 * HEAD_IMG + 2 * 6144 + 160);
  const int tid = threadIdx.x, lane = tid & 31;
  const int warp = __shfl_sync(~0u, tid >> 5, 0);
  const int head = blockIdx.x >> 2, qb = blockIdx.x & 3;
  const uint8_t* qimg = (const uint8_t*)g_qkv + (size_t)head * HEAD_IMG + qb * 64 * 384;

  if (tid == 0) STAMP(1, 0);
  if (tid == 0) {
    for (int i = 0; i < 16; i++) mbar_init(kvb + 8 * i, 1);
    mbar_init(flagb, 1); mbar_init(partb, 128); mbar_init(partb + 8, 128);
    asm volatile("fence.mbarrier_init.release.cluster;" ::: "memory");
  }
  __syncthreads();

  if (warp >= 12) {
    asm volatile("setmaxnreg.dec.sync.aligned.u32 56;");
    const int t = tid - 384;
    pdl_wait();
    pdl_trigger();
    if (t == 0) {
      const uint8_t* kimg = (const uint8_t*)g_qkv + (size_t)(32 + head) * HEAD_IMG;
      const uint8_t* vimg = (const uint8_t*)g_qkv + (size_t)(64 + head) * HEAD_IMG;
      for (int b = 0; b < 16; b++) {
        mbar_expect(kvb + 8 * b, 12288);
        bulk_ld(sbase + b * 6144, kimg + b * 6144, 6144, kvb + 8 * b);
        bulk_ld(sbase + HEAD_IMG + b * 6144, vimg + b * 6144, 6144, kvb + 8 * b);
      }
    }
    if (blockIdx.x == 0 && t >= 32 && t < 56) g_cnt[(t - 32) * 32] = 0;
    {
      float qm = 0.f, km = 0.f;
      const int ro = (t >> 3) * 384 + (t & 7) * 16;
#pragma unroll
      for (int i = 0; i < 4; i++) {
        const uint8_t* p = qimg + i * 6144 + ro;
        const float v = sq20(__ldcg((const uint4*)p), __ldcg((const uint4*)(p + 128)), __ldcg((const uint2*)(p + 256)));
        qm = __uint_as_float(max(__float_as_uint(qm), __float_as_uint(v)));
      }
#pragma unroll 1
      for (int b = 0; b < 16; b++) {
        mbar_wait(kvb + 8 * b, 0);
        const uint8_t* p = sm + b * 6144 + ro;
        const float v = sq20(*(const uint4*)p, *(const uint4*)(p + 128), *(const uint2*)(p + 256));
        km = __uint_as_float(max(__float_as_uint(km), __float_as_uint(v)));
      }
      if ((POLY_MASK >> (t >> 3)) & 1) km *= 9.313225746154785e-10f;
      const uint32_t qw = __reduce_max_sync(~0u, __float_as_uint(qm)), kw = __reduce_max_sync(~0u, __float_as_uint(km));
      if (lane == 0) { sflag[1 + (warp & 3)] = qw; sflag[5 + (warp & 3)] = kw; }
      bar_sync(1, 128);
      if (t == 0) {
        const float q2 = __uint_as_float(max(max(sflag[1], sflag[2]), max(sflag[3], sflag[4])));
        const float k2 = __uint_as_float(max(max(sflag[5], sflag[6]), max(sflag[7], sflag[8])));
        sflag[0] = (q2 * k2 <= 3000.f) ? 1u : 0u;
        mbar_arrive(flagb);
        STAMP(1, 2);
      }
    }
    const int kr = (warp & 3) * 8 + (lane >> 2), ch = lane & 3;
    if (blockIdx.x < 108) {
      const int cg = blockIdx.x * 4 + ch;
      const int up = cg >= 216, cc = cg - up * 216;
      const int nt = cc / 27, ci = cc - nt * 27 + up * 27;
      const bf16* src = (up ? wu : wg_) + cc * 8 + (size_t)kr * F_;
      uint4* dst = g_wgu + ((size_t)nt * 10 * 54 + ci) * 64 + kr;
      float a8[8];
#pragma unroll
      for (int i = 0; i < 8; i++) a8[i] = 0.f;
#pragma unroll 4
      for (int it = 0; it < 20; it++) {
        const uint4 v = ldg_nc(src + (size_t)it * 32 * F_);
        dst[(it >> 1) * (54 * 64) + (it & 1) * 32] = v;
        a8[0] += bf_lo(v.x); a8[1] += bf_hi(v.x); a8[2] += bf_lo(v.y); a8[3] += bf_hi(v.y);
        a8[4] += bf_lo(v.z); a8[5] += bf_hi(v.z); a8[6] += bf_lo(v.w); a8[7] += bf_hi(v.w);
      }
#pragma unroll
      for (int i = 0; i < 8; i++) {
        a8[i] += __shfl_xor_sync(~0u, a8[i], 4);
        a8[i] += __shfl_xor_sync(~0u, a8[i], 8);
        a8[i] += __shfl_xor_sync(~0u, a8[i], 16);
      }
      float* red = (float*)(sm + K2_SMEM);
      if (lane < 4) {
#pragma unroll
        for (int i = 0; i < 8; i++) red[(warp & 3) * 32 + lane * 8 + i] = a8[i];
      }
      bar_sync(1, 128);
      if (t < 32) g_csgu[blockIdx.x * 32 + t] = red[t] + red[32 + t] + red[64 + t] + red[96 + t];
    }
    {
      const int first = blockIdx.x < 108 ? blockIdx.x * 8 : 864 + (blockIdx.x - 108) * 31;
      const int last = min(blockIdx.x < 108 ? first + 8 : first + 31, 1480);
#pragma unroll 4
      for (int ps = first; ps < last; ps++) {
        const int rg = ps / 20, cs = ps - rg * 20;
        const int cg = cs * 4 + ch, nt = cg / 10, ci = cg - nt * 10;
        const bool isd = rg < 54;
        const int k = (isd ? rg : rg - 54) * 32 + kr;
        int ks = k;
        if (!isd) {
          const int pr = k / 40, r = k - pr * 40;
          ks = pr * 40 + (r < 16 ? r : (r < 32 ? r + 4 : (r < 36 ? r - 16 : r)));
        }
        const uint4 v = ldg_nc((isd ? wd : wo) + (size_t)ks * D_ + cg * 8);
        uint4* dst = (isd ? g_wd + (size_t)nt * 27 * 640 : g_wo + (size_t)nt * 10 * 640) + ((k >> 6) * 10 + ci) * 64 + (k & 63);
        *dst = v;
      }
    }
    if (t == 0) STAMP(1, 6);
  } else {
    asm volatile("setmaxnreg.inc.sync.aligned.u32 152;");
    const int wg = warp >> 2, wq = warp & 3;
    const uint8_t* qthr = qimg + wq * 768 + (lane >> 2) * 16 + (lane & 3) * 4;
    uint8_t* othr = (uint8_t*)g_o + (size_t)qb * 4 * 163840 + wq * 2048 + (lane >> 2) * 16 + (lane & 3) * 4;
    const int oc = (head >> 1) * 5 + (head & 1) * 2;
    const int oo0 = img_off(oc), oo1 = img_off(oc + 1), oo2 = img_off((head >> 1) * 5 + 4) + (head & 1) * 8;
    const uint64_t dk0 = mkdesc(sbase, 128, 384, 0), dk0b = mkdesc(sbase + 256, 0, 384, 0);
    const uint64_t dv0 = mkdesc(sbase + HEAD_IMG, 384, 128, 0);
    const int nun = wg == 1 ? 4 : 3;
    const uint32_t utile = wg == 0 ? 0x210u : (wg == 1 ? 0x4325u : 0x576u);
    pdl_wait();
    if (tid == 0) STAMP(1, 1);
    uint32_t q[6];
    load_q(q, qthr + (utile & 15) * 3072);
    bool fast = true;
#pragma unroll 1
    for (int u = 0; u < nun; u++) {
      const int tile = (utile >> (4 * u)) & 15;
      int b0 = 0, b1 = 16;
      if (wg == 0 && u == 2) b1 = 11;
      if (wg == 1 && u == 0) b1 = 6;
      if (wg == 1 && u == 1) b0 = 11;
      if (wg == 2 && u == 2) b0 = 6;
      const bool wt = u == 0 || (wg == 1 && u == 1);
      float s[64], o[12];
#pragma unroll
      for (int i = 0; i < 12; i++) o[i] = 0.f;
      uint64_t dk = dk0 + b0 * 384, dkb = dk0b + b0 * 384, dv = dv0 + b0 * 384;
      if (wt) mbar_wait(kvb + 8 * b0, 0);
      fence_regs(o);
      WG_FENCE();
      wgmma_rs_n128(s, q[0], q[1], q[2], q[3], dk, 0);
      wgmma_rs_n128(s, q[4], q[5], 0, 0, dkb, 1);
      WG_COMMIT();
#pragma unroll 1
      for (int b = b0 + 1; b < b1; b++) {
        if (wt) mbar_wait(kvb + 8 * b, 0);
        WG_WAIT(0);
        fence_regs(s); fence_regs(o);
        exp_pv(s, o, dv, mk);
        dk += 384; dkb += 384; dv += 384;
        wgmma_rs_n128(s, q[0], q[1], q[2], q[3], dk, 0);
        wgmma_rs_n128(s, q[4], q[5], 0, 0, dkb, 1);
        WG_COMMIT();
      }
      WG_WAIT(0);
      fence_regs(s); fence_regs(o);
      if (u + 1 < nun) load_q(q, qthr + ((utile >> (4 * u + 4)) & 15) * 3072);
      exp_pv(s, o, dv, mk);
      WG_COMMIT();
      WG_WAIT(0);
      fence_regs(o);
      if (wg == 1 && u < 2) {
        float4* pp = (float4*)(part + u * 1536) + (tid & 127);
        pp[0] = make_float4(o[0], o[1], o[2], o[3]);
        pp[128] = make_float4(o[4], o[5], o[6], o[7]);
        pp[256] = make_float4(o[8], o[9], o[10], o[11]);
        mbar_arrive(partb + 8 * u);
        if (u == 0) continue;
      }
      if (wt) {
        mbar_wait(flagb, 0);
        fast = sflag[0] != 0;
        if (!fast) break;
        if (wg == 1) continue;
      }
      if (wg != 1 && u == 2) {
        const int pi = wg == 0 ? 1 : 0;
        mbar_wait(partb + 8 * pi, 0);
        const float4* pp = (const float4*)(part + pi * 1536) + (tid & 127);
        const float4 x0 = pp[0], x1 = pp[128], x2 = pp[256];
        o[0] += x0.x; o[1] += x0.y; o[2] += x0.z; o[3] += x0.w; o[4] += x1.x; o[5] += x1.y;
        o[6] += x1.z; o[7] += x1.w; o[8] += x2.x; o[9] += x2.y; o[10] += x2.z; o[11] += x2.w;
      }
      store_o(o, othr + (tile >> 1) * 163840 + (tile & 1) * 8192, oo0, oo1, oo2, lane);
    }
    if ((tid & 127) == 0) STAMP(1, 3 + wg);
    if (!fast) {
#pragma unroll 1
      for (int tile = wg; tile < 8; tile += 3) {
        load_q(q, qthr + tile * 3072);
        if ((lane & 3) >= 2) { q[4] = 0; q[5] = 0; }
        float o[12], m0 = -INFINITY, m1 = -INFINITY;
#pragma unroll
        for (int i = 0; i < 12; i++) o[i] = 0.f;
#pragma unroll 1
        for (int b = 0; b < 16; b++) {
          float s[64];
          WG_FENCE();
          wgmma_rs_n128(s, q[0], q[1], q[2], q[3], dk0 + b * 384, 0);
          wgmma_rs_n128(s, q[4], q[5], 0, 0, dk0b + b * 384, 1);
          WG_COMMIT();
          WG_WAIT(0);
          fence_regs(s);
          float x0 = m0, x1 = m1;
#pragma unroll
          for (int j = 0; j < 16; j++) {
            if ((POLY_MASK >> j) & 1) {
#pragma unroll
              for (int i = 0; i < 4; i++) s[4 * j + i] *= (1.f / 32768.f);
            }
            x0 = fmaxf(x0, fmaxf(s[4 * j], s[4 * j + 1]));
            x1 = fmaxf(x1, fmaxf(s[4 * j + 2], s[4 * j + 3]));
          }
          x0 = fmaxf(x0, __shfl_xor_sync(~0u, x0, 1)); x0 = fmaxf(x0, __shfl_xor_sync(~0u, x0, 2));
          x1 = fmaxf(x1, __shfl_xor_sync(~0u, x1, 1)); x1 = fmaxf(x1, __shfl_xor_sync(~0u, x1, 2));
          const float al0 = ex2(m0 - x0), al1 = ex2(m1 - x1);
          m0 = x0; m1 = x1;
#pragma unroll
          for (int i = 0; i < 12; i++) o[i] *= (i & 2) ? al1 : al0;
          uint32_t p[32];
#pragma unroll
          for (int i = 0; i < 32; i++) {
            const float mm = (i & 1) ? m1 : m0;
            p[i] = pack_bf16(ex2(s[2 * i] - mm), ex2(s[2 * i + 1] - mm));
          }
          fence_regs(o);
          WG_FENCE();
#pragma unroll
          for (int k = 0; k < 8; k++) wgmma_rs_n24(o, p[4 * k], p[4 * k + 1], p[4 * k + 2], p[4 * k + 3], dv0 + b * 384 + k * 48, 1);
          WG_COMMIT();
          WG_WAIT(0);
          fence_regs(o);
        }
        store_o(o, othr + (tile >> 1) * 163840 + (tile & 1) * 8192, oo0, oo1, oo2, lane);
      }
    }
  }
}

constexpr int K3_ST = 7, K3_STAGE = 26624;
constexpr int K3_SMEM = K3_ST * K3_STAGE + 20480 + 256;

template <int KT, bool FIRST>
__global__ void __cluster_dims__(2, 1, 1) __launch_bounds__(384, 1)
k3_proj(const __grid_constant__ CUtensorMap tmr, const uint4* __restrict__ aimg, const uint4* __restrict__ wimg) {
  extern __shared__ __align__(1024) uint8_t sm[];
  const uint32_t sbase = smem_u32(sm);
  uint8_t* stg = sm + K3_ST * K3_STAGE;
  const uint32_t fullb = sbase + K3_ST * K3_STAGE + 20480, emptyb = fullb + 8 * K3_ST, resb = emptyb + 8 * K3_ST;
  const int tid = threadIdx.x, lane = tid & 31;
  const int warp = __shfl_sync(~0u, tid >> 5, 0);
  const int rank = blockIdx.x & 1;
  const int n = blockIdx.x & 7, m = blockIdx.x >> 3;
  if (tid == 0) STAMP(FIRST ? 2 : 4, 0);
  if (tid == 0) {
    prefetch_map(&tmr);
    for (int i = 0; i < K3_ST; i++) { mbar_init(fullb + 8 * i, 1); mbar_init(emptyb + 8 * i, 4); }
    mbar_init(resb, 1);
    asm volatile("fence.mbarrier_init.release.cluster;" ::: "memory");
  }
  __syncthreads();
  cluster_arrive();
  if (warp == 0) {
    const uint8_t* wb = (const uint8_t*)wimg + (size_t)n * KT * 10240;
    const uint8_t* ab = (const uint8_t*)aimg + (size_t)m * KT * 16384 + rank * 8192;
    if (lane == 0) {
      if (FIRST) {
        mbar_expect(resb, 20480);
        tma2d(smem_u32(stg), &tmr, n * 80, m * 128, resb);
        tma2d(smem_u32(stg) + 10240, &tmr, n * 80, m * 128 + 64, resb);
      } else {
        for (int kt = 0; kt < K3_ST; kt++) {
          mbar_expect(fullb + 8 * kt, K3_STAGE);
          bulk_ld(sbase + kt * K3_STAGE + 16384, wb + kt * 10240, 10240, fullb + 8 * kt);
        }
      }
    }
    __syncwarp();
    cluster_wait();
    pdl_wait();
    pdl_trigger();
    if (lane == 0) {
      for (int kt = 0; kt < KT; kt++) {
        const int s = kt % K3_ST;
        const uint32_t sa = sbase + s * K3_STAGE;
        if (kt >= K3_ST) mbar_wait(emptyb + 8 * s, ((kt / K3_ST) - 1) & 1);
        if (FIRST || kt >= K3_ST) mbar_expect(fullb + 8 * s, K3_STAGE);
        bulk_ld_mc(sa + rank * 8192, ab + kt * 16384, 8192, fullb + 8 * s);
        if (FIRST || kt >= K3_ST) bulk_ld(sa + 16384, wb + kt * 10240, 10240, fullb + 8 * s);
      }
    }
    __syncwarp();
  } else if (warp >= 4) {
    const int cw = warp - 4, wg = cw >> 2;
    const int g = lane >> 2, c = lane & 3;
    uint8_t* himg = (uint8_t*)g_h + (size_t)m * 163840 + cw * 2048 + g * 16 + c * 4;
    uint32_t rv[20];
    if (!FIRST) {
#pragma unroll
      for (int j = 0; j < 10; j++) {
        rv[2 * j] = __ldcg((const uint32_t*)(himg + img_off(n * 10 + j)));
        rv[2 * j + 1] = __ldcg((const uint32_t*)(himg + img_off(n * 10 + j) + 1024));
      }
    }
    cluster_wait();
    float acc[40];
    const uint64_t da0 = mkdesc(sbase + wg * 8192, 128, 1024, 0);
    const uint64_t db0 = mkdesc(sbase + 16384, 128, 1024, 0);
#pragma unroll 1
    for (int kt = 0; kt < KT; kt++) {
      const int s = kt % K3_ST;
      mbar_wait(fullb + 8 * s, (kt / K3_ST) & 1);
      if (kt == 0 && tid == 128) STAMP(FIRST ? 2 : 4, 2);
      const uint64_t da = da0 + s * (K3_STAGE >> 4), db = db0 + s * (K3_STAGE >> 4);
      WG_FENCE();
#pragma unroll
      for (int k = 0; k < 4; k++) wgmma_ss_n80(acc, da + k * 16, db + k * 16, (kt | k) != 0);
      WG_COMMIT();
      if (kt > 0) {
        WG_WAIT(1);
        if (kt - 1 + K3_ST < KT && (tid & 127) < 2) mbar_arrive_cta(emptyb + 8 * ((kt - 1) % K3_ST), tid & 1);
      }
    }
    uint8_t* sp = stg + (cw * 16 + g) * 160 + c * 4;
    if (FIRST) {
      mbar_wait(resb, 0);
#pragma unroll
      for (int j = 0; j < 10; j++) {
        rv[2 * j] = *(const uint32_t*)(sp + j * 16);
        rv[2 * j + 1] = *(const uint32_t*)(sp + 1280 + j * 16);
      }
    }
    WG_WAIT(0);
    fence_regs(acc);
    if (tid == 128) STAMP(FIRST ? 2 : 4, 3);
    float s0 = 0.f, s1 = 0.f;
#pragma unroll
    for (int j = 0; j < 10; j++) {
      acc[4 * j] += bf_lo(rv[2 * j]); acc[4 * j + 1] += bf_hi(rv[2 * j]);
      acc[4 * j + 2] += bf_lo(rv[2 * j + 1]); acc[4 * j + 3] += bf_hi(rv[2 * j + 1]);
      if (FIRST) {
        *(uint32_t*)(himg + img_off(n * 10 + j)) = pack_bf16(acc[4 * j], acc[4 * j + 1]);
        *(uint32_t*)(himg + img_off(n * 10 + j) + 1024) = pack_bf16(acc[4 * j + 2], acc[4 * j + 3]);
        s0 += acc[4 * j] + acc[4 * j + 1]; s1 += acc[4 * j + 2] + acc[4 * j + 3];
      } else {
        *(uint32_t*)(sp + j * 16) = pack_bf16(acc[4 * j], acc[4 * j + 1]);
        *(uint32_t*)(sp + 1280 + j * 16) = pack_bf16(acc[4 * j + 2], acc[4 * j + 3]);
      }
    }
    if (FIRST) {
      s0 += __shfl_xor_sync(~0u, s0, 1); s0 += __shfl_xor_sync(~0u, s0, 2);
      s1 += __shfl_xor_sync(~0u, s1, 1); s1 += __shfl_xor_sync(~0u, s1, 2);
      s0 *= (1.f / 80.f); s1 *= (1.f / 80.f);
      float q0 = 0.f, q1 = 0.f;
#pragma unroll
      for (int j = 0; j < 10; j++) {
        float d;
        d = acc[4 * j] - s0; q0 = fmaf(d, d, q0); d = acc[4 * j + 1] - s0; q0 = fmaf(d, d, q0);
        d = acc[4 * j + 2] - s1; q1 = fmaf(d, d, q1); d = acc[4 * j + 3] - s1; q1 = fmaf(d, d, q1);
      }
      q0 += __shfl_xor_sync(~0u, q0, 1); q0 += __shfl_xor_sync(~0u, q0, 2);
      q1 += __shfl_xor_sync(~0u, q1, 1); q1 += __shfl_xor_sync(~0u, q1, 2);
      if (c < 2) g_hpart[n * S_ + m * 128 + cw * 16 + g + c * 8] = c ? make_float2(s1, q1) : make_float2(s0, q0);
    } else {
      fence_async();
      bar_sync(1 + wg, 128);
      if ((tid & 127) == 0) {
        tma2d_st(&tmr, n * 80, m * 128 + wg * 64, smem_u32(stg) + wg * 10240);
        bulk_commit_wait();
      }
      __syncwarp();
    }
    if (tid == 128) STAMP(FIRST ? 2 : 4, 4);
  } else {
    cluster_wait();
  }
  cluster_sync_relaxed();
}

constexpr int K4_ST = 3, K4_STAGE = 71680;
constexpr int K4_SMEM = K4_ST * K4_STAGE + 1728 + 1024 + 64;

__global__ void __cluster_dims__(2, 1, 1) __launch_bounds__(256, 1)
k4_ffn1() {
  extern __shared__ __align__(1024) uint8_t sm[];
  float* cs = (float*)(sm + K4_ST * K4_STAGE);
  float2* rowst = (float2*)(sm + K4_ST * K4_STAGE + 1728);
  const uint32_t sbase = smem_u32(sm);
  const uint32_t fullb = sbase + K4_ST * K4_STAGE + 2752, emptyb = fullb + 8 * K4_ST;
  const int tid = threadIdx.x, lane = tid & 31;
  const int warp = __shfl_sync(~0u, tid >> 5, 0);
  const int rank = blockIdx.x & 1, cl = blockIdx.x >> 1;
  const int n = cl & 7, m = (cl >> 3) * 2 + rank;
  const uint8_t* wb = (const uint8_t*)g_wgu + (size_t)n * 10 * 55296 + rank * 27648;
  const uint8_t* ab = (const uint8_t*)g_h + (size_t)m * 163840;
  if (tid == 0) STAMP(3, 0);
  if (tid == 0) {
    for (int i = 0; i < K4_ST; i++) { mbar_init(fullb + 8 * i, 1); mbar_init(emptyb + 8 * i, 4); }
    asm volatile("fence.mbarrier_init.release.cluster;" ::: "memory");
  }
  __syncthreads();
  cluster_arrive();
  const float cs0 = __ldcg(&g_csgu[(tid >= 216 ? F_ - 216 : 0) + n * 216 + tid]);
  const float cs1 = tid < 176 ? __ldcg(&g_csgu[F_ - 216 + n * 216 + 256 + tid]) : 0.f;
  cluster_wait();
  if (tid == 0) {
    for (int kt = 0; kt < K4_ST; kt++) {
      mbar_expect(fullb + 8 * kt, K4_STAGE);
      bulk_ld_mc(sbase + kt * K4_STAGE + 16384 + rank * 27648, wb + kt * 55296, 27648, fullb + 8 * kt);
    }
  }
  pdl_wait();
  pdl_trigger();
  if (tid == 128) STAMP(3, 1);
  if (tid == 0) {
    for (int kt = 0; kt < K4_ST; kt++) bulk_ld(sbase + kt * K4_STAGE, ab + kt * 16384, 16384, fullb + 8 * kt);
  }
  if (tid >= 128) {
    const int r = tid - 128;
    float2 p[8];
#pragma unroll
    for (int i = 0; i < 8; i++) p[i] = __ldcg(&g_hpart[i * S_ + m * 128 + r]);
    float mean = 0.f, m2 = 0.f;
#pragma unroll
    for (int i = 0; i < 8; i++) { mean += p[i].x; m2 += p[i].y; }
    mean *= 0.125f;
#pragma unroll
    for (int i = 0; i < 8; i++) { const float d = p[i].x - mean; m2 = fmaf(80.f * d, d, m2); }
    rowst[r] = make_float2(-mean, __frcp_rn(m2 * (1.f / D_) + 1e-5f));
  }
  cs[tid] = cs0;
  if (tid < 176) cs[256 + tid] = cs1;
  __syncwarp();
  float ag[108], au[108];
  const uint64_t da0 = mkdesc(sbase + (warp >> 2) * 8192, 128, 1024, 0);
  const uint64_t db0 = mkdesc(sbase + 16384, 128, 1024, 0);
#pragma unroll 1
  for (int kt = 0; kt < 10; kt++) {
    const int s = kt % K4_ST;
    mbar_wait(fullb + 8 * s, (kt / K4_ST) & 1);
    if (kt == 0 && tid == 128) STAMP(3, 2);
    const uint64_t da = da0 + s * (K4_STAGE >> 4), db = db0 + s * (K4_STAGE >> 4);
    WG_FENCE();
#pragma unroll
    for (int k = 0; k < 4; k++) {
      wgmma_ss_n216(ag, da + k * 16, db + k * 16, (kt | k) != 0);
      wgmma_ss_n216(au, da + k * 16, db + 1728 + k * 16, (kt | k) != 0);
    }
    WG_COMMIT();
    if (kt > 0 && kt - 1 + K4_ST < 10) {
      WG_WAIT(1);
      const int sp = (kt - 1) % K4_ST;
      if ((tid & 127) < 2) mbar_arrive_cta(emptyb + 8 * sp, tid & 1);
      if (tid == 0) {
        const uint32_t sa = sbase + sp * K4_STAGE;
        mbar_wait(emptyb + 8 * sp, ((kt - 1) / K4_ST) & 1);
        mbar_expect(fullb + 8 * sp, K4_STAGE);
        bulk_ld_mc(sa + 16384 + rank * 27648, wb + (kt - 1 + K4_ST) * 55296, 27648, fullb + 8 * sp);
        bulk_ld(sa, ab + (kt - 1 + K4_ST) * 16384, 16384, fullb + 8 * sp);
      }
      __syncwarp();
    }
  }
  WG_WAIT(0);
  fence_regs(ag); fence_regs(au);
  if (tid == 128) STAMP(3, 3);
  __syncthreads();
  const int g = lane >> 2, c = lane & 3;
  const float2 st0 = rowst[warp * 16 + g], st1 = rowst[warp * 16 + g + 8];
  uint8_t* dst = (uint8_t*)g_hh + (size_t)m * 27 * 16384 + warp * 2048 + g * 16 + c * 4;
#pragma unroll
  for (int j = 0; j < 27; j++) {
    const float2 cg = *(const float2*)&cs[j * 8 + c * 2], cu = *(const float2*)&cs[216 + j * 8 + c * 2];
    const float h0 = fmaf(st0.x, cg.x, ag[4 * j]) * st0.y * fmaf(st0.x, cu.x, au[4 * j]);
    const float h1 = fmaf(st0.x, cg.y, ag[4 * j + 1]) * st0.y * fmaf(st0.x, cu.y, au[4 * j + 1]);
    const float h2 = fmaf(st1.x, cg.x, ag[4 * j + 2]) * st1.y * fmaf(st1.x, cu.x, au[4 * j + 2]);
    const float h3 = fmaf(st1.x, cg.y, ag[4 * j + 3]) * st1.y * fmaf(st1.x, cu.y, au[4 * j + 3]);
    *(uint32_t*)(dst + img_off(n * 27 + j)) = pack_bf16(h0, h1);
    *(uint32_t*)(dst + img_off(n * 27 + j) + 1024) = pack_bf16(h2, h3);
  }
  if (tid == 128) STAMP(3, 4);
  cluster_sync_relaxed();
}

typedef CUresult (*EncodeFn)(CUtensorMap*, CUtensorMapDataType, cuuint32_t, void*, const cuuint64_t*, const cuuint64_t*,
                             const cuuint32_t*, const cuuint32_t*, CUtensorMapInterleave, CUtensorMapSwizzle,
                             CUtensorMapL2promotion, CUtensorMapFloatOOBfill);

static CUtensorMap make_map(EncodeFn enc, const void* p, uint64_t inner, uint64_t outer, uint32_t box_inner,
                            uint32_t box_outer, CUtensorMapSwizzle swz) {
  CUtensorMap m;
  cuuint64_t gd[2] = {inner, outer};
  cuuint64_t gs[1] = {inner * 2};
  cuuint32_t bd[2] = {box_inner, box_outer};
  cuuint32_t es[2] = {1, 1};
  enc(&m, CU_TENSOR_MAP_DATA_TYPE_BFLOAT16, 2, (void*)p, gd, gs, bd, es, CU_TENSOR_MAP_INTERLEAVE_NONE, swz,
      CU_TENSOR_MAP_L2_PROMOTION_L2_256B, CU_TENSOR_MAP_FLOAT_OOB_FILL_NONE);
  return m;
}

template <typename... KArgs, typename... Args>
static void launch(void (*k)(KArgs...), int threads, int smem, bool pdl, Args... args) {
  cudaLaunchConfig_t cfg = {};
  cfg.gridDim = dim3(128);
  cfg.blockDim = dim3(threads);
  cfg.dynamicSmemBytes = smem;
  cfg.stream = cudaStreamPerThread;
  cudaLaunchAttribute at[1];
  at[0].id = cudaLaunchAttributeProgrammaticStreamSerialization;
  at[0].val.programmaticStreamSerializationAllowed = 1;
  cfg.attrs = at;
  cfg.numAttrs = pdl ? 1 : 0;
  cudaLaunchKernelEx(&cfg, k, KArgs(args)...);
}

extern "C" void kernel_launch(void* const* d_in, const int* in_sizes, int n_in, void* d_out, int out_size) {
  const bf16* x = (const bf16*)d_in[0];
  const bf16* wqkv = (const bf16*)d_in[1];
  const bf16* wo = (const bf16*)d_in[2];
  const bf16* wg = (const bf16*)d_in[4];
  const bf16* wu = (const bf16*)d_in[5];
  const bf16* wd = (const bf16*)d_in[6];

  static EncodeFn enc = nullptr;
  static void *p_o, *p_hh, *p_wo, *p_wd;
  if (!enc) {
    void* fn = nullptr;
    cudaDriverEntryPointQueryResult qr;
    cudaGetDriverEntryPoint("cuTensorMapEncodeTiled", &fn, cudaEnableDefault, &qr);
    enc = (EncodeFn)fn;
    cudaGetSymbolAddress(&p_o, g_o); cudaGetSymbolAddress(&p_hh, g_hh);
    cudaGetSymbolAddress(&p_wo, g_wo); cudaGetSymbolAddress(&p_wd, g_wd);
    cudaFuncSetAttribute(k1_qkv, cudaFuncAttributeMaxDynamicSharedMemorySize, K1_SMEM);
    cudaFuncSetAttribute(k2_attn, cudaFuncAttributeMaxDynamicSharedMemorySize, K2_SMEM + 512);
    cudaFuncSetAttribute(k3_proj<10, true>, cudaFuncAttributeMaxDynamicSharedMemorySize, K3_SMEM);
    cudaFuncSetAttribute(k3_proj<27, false>, cudaFuncAttributeMaxDynamicSharedMemorySize, K3_SMEM);
    cudaFuncSetAttribute(k4_ffn1, cudaFuncAttributeMaxDynamicSharedMemorySize, K4_SMEM);
  }
  const CUtensorMap tmx = make_map(enc, x, D_, S_, 64, 128, CU_TENSOR_MAP_SWIZZLE_128B);
  const CUtensorMap tmw = make_map(enc, wqkv, 3 * D_, D_, 32, 64, CU_TENSOR_MAP_SWIZZLE_64B);
  const CUtensorMap tmxr = make_map(enc, x, D_, S_, 80, 64, CU_TENSOR_MAP_SWIZZLE_NONE);
  const CUtensorMap tmout = make_map(enc, d_out, D_, S_, 80, 64, CU_TENSOR_MAP_SWIZZLE_NONE);

  launch(k1_qkv, 384, K1_SMEM, false, tmx, tmw, x, wqkv);
  launch(k2_attn, 512, K2_SMEM + 512, true, wo, wg, wu, wd, 0x007f007fu);
  launch(k3_proj<10, true>, 384, K3_SMEM, true, tmxr, (const uint4*)p_o, (const uint4*)p_wo);
  launch(k4_ffn1, 256, K4_SMEM, true);
  launch(k3_proj<27, false>, 384, K3_SMEM, true, tmout, (const uint4*)p_hh, (const uint4*)p_wd);
}
```

```cpp
#include <cuda_runtime.h>
#include <cuda_bf16.h>
#include <cuda.h>
#include <stdint.h>

typedef __nv_bfloat16 bf16;

constexpr int S_ = 2048, D_ = 640, F_ = 1728;
constexpr int HEAD_IMG = 98304;
constexpr uint32_t POLY_MASK = 0xBBAB;
constexpr float QSCALE = 0.22360679774997896f * 1.4426950408889634f;

__device__ __align__(1024) uint4 g_qkv[96 * HEAD_IMG / 16];
__device__ __align__(1024) uint4 g_o[S_ * D_ / 8];
__device__ __align__(1024) uint4 g_h[S_ * D_ / 8];
__device__ __align__(1024) uint4 g_hh[S_ * F_ / 8];
__device__ __align__(1024) uint4 g_wo[D_ * D_ / 8];
__device__ __align__(1024) uint4 g_wgu[2 * D_ * F_ / 8];
__device__ __align__(1024) uint4 g_wd[F_ * D_ / 8];
__device__ float2 g_rowstat[S_];
__device__ float g_cpart[16 * 2048];
__device__ float g_csgu[2 * F_];
__device__ float2 g_hpart[8 * S_];
__device__ unsigned g_cnt[24 * 32];

#define STAMP(k, i)
__device__ __forceinline__ uint32_t smem_u32(const void* p) { return (uint32_t)__cvta_generic_to_shared(p); }
__device__ __forceinline__ void mbar_init(uint32_t a, uint32_t c) {
  asm volatile("mbarrier.init.shared::cta.b64 [%0], %1;" ::"r"(a), "r"(c) : "memory");
}
__device__ __forceinline__ void mbar_expect(uint32_t a, uint32_t bytes) {
  asm volatile("mbarrier.arrive.expect_tx.shared::cta.b64 _, [%0], %1;" ::"r"(a), "r"(bytes) : "memory");
}
__device__ __forceinline__ void mbar_arrive(uint32_t a) {
  asm volatile("mbarrier.arrive.shared::cta.b64 _, [%0];" ::"r"(a) : "memory");
}
__device__ __forceinline__ void mbar_arrive_cta(uint32_t a, uint32_t cta) {
  asm volatile("{\n.reg .b32 r;\nmapa.shared::cluster.u32 r, %0, %1;\n"
               "mbarrier.arrive.shared::cluster.b64 _, [r];\n}" ::"r"(a), "r"(cta) : "memory");
}
__device__ __forceinline__ bool mbar_try(uint32_t a, uint32_t ph) {
  uint32_t ok;
  asm volatile("{\n.reg .pred p;\nmbarrier.try_wait.parity.shared::cta.b64 p, [%1], %2;\nselp.u32 %0, 1, 0, p;\n}"
               : "=r"(ok) : "r"(a), "r"(ph) : "memory");
  return ok;
}
__device__ __noinline__ void wait_timeout() { __trap(); }
__device__ __forceinline__ void mbar_wait(uint32_t a, uint32_t ph) {
  if (mbar_try(a, ph)) return;
  uint32_t it = 0;
  while (!mbar_try(a, ph)) if (++it > (1u << 22)) wait_timeout();
}
__device__ __forceinline__ void tma2d(uint32_t dst, const CUtensorMap* m, int c0, int c1, uint32_t bar) {
  asm volatile("cp.async.bulk.tensor.2d.shared::cluster.global.mbarrier::complete_tx::bytes [%0], [%1, {%3, %4}], [%2];"
               ::"r"(dst), "l"(m), "r"(bar), "r"(c0), "r"(c1) : "memory");
}
__device__ __forceinline__ void tma2d_mc(uint32_t dst, const CUtensorMap* m, int c0, int c1, uint32_t bar) {
  asm volatile("cp.async.bulk.tensor.2d.shared::cluster.global.mbarrier::complete_tx::bytes.multicast::cluster "
               "[%0], [%1, {%3, %4}], [%2], %5;"
               ::"r"(dst), "l"(m), "r"(bar), "r"(c0), "r"(c1), "h"((uint16_t)3) : "memory");
}
__device__ __forceinline__ void bulk_ld(uint32_t dst, const void* src, uint32_t bytes, uint32_t bar) {
  asm volatile("cp.async.bulk.shared::cluster.global.mbarrier::complete_tx::bytes [%0], [%1], %2, [%3];"
               ::"r"(dst), "l"(src), "r"(bytes), "r"(bar) : "memory");
}
__device__ __forceinline__ void bulk_ld_mc(uint32_t dst, const void* src, uint32_t bytes, uint32_t bar) {
  asm volatile("cp.async.bulk.shared::cluster.global.mbarrier::complete_tx::bytes.multicast::cluster "
               "[%0], [%1], %2, [%3], %4;"
               ::"r"(dst), "l"(src), "r"(bytes), "r"(bar), "h"((uint16_t)3) : "memory");
}
__device__ __forceinline__ void cluster_arrive() { asm volatile("barrier.cluster.arrive.relaxed.aligned;" ::: "memory"); }
__device__ __forceinline__ void cluster_wait() { asm volatile("barrier.cluster.wait.aligned;" ::: "memory"); }
__device__ __forceinline__ void bulk_st(void* dst, uint32_t src, uint32_t bytes) {
  asm volatile("cp.async.bulk.global.shared::cta.bulk_group [%0], [%1], %2;" ::"l"(dst), "r"(src), "r"(bytes) : "memory");
}
__device__ __forceinline__ void tma2d_st(const CUtensorMap* m, int c0, int c1, uint32_t src) {
  asm volatile("cp.async.bulk.tensor.2d.global.shared::cta.bulk_group [%0, {%2, %3}], [%1];"
               ::"l"(m), "r"(src), "r"(c0), "r"(c1) : "memory");
}
__device__ __forceinline__ void bulk_commit_wait() {
  asm volatile("cp.async.bulk.commit_group;\ncp.async.bulk.wait_group.read 0;" ::: "memory");
}
__device__ __forceinline__ uint32_t mapa(uint32_t a, uint32_t cta) {
  uint32_t r;
  asm("mapa.shared::cluster.u32 %0, %1, %2;" : "=r"(r) : "r"(a), "r"(cta));
  return r;
}
__device__ __forceinline__ void st_async4(uint32_t dst, float a, float b, float c, float d, uint32_t bar) {
  asm volatile("st.async.shared::cluster.mbarrier::complete_tx::bytes.v4.f32 [%0], {%1, %2, %3, %4}, [%5];"
               ::"r"(dst), "f"(a), "f"(b), "f"(c), "f"(d), "r"(bar) : "memory");
}
__device__ __forceinline__ void fence_async() { asm volatile("fence.proxy.async.shared::cta;" ::: "memory"); }
__device__ __forceinline__ void prefetch_map(const CUtensorMap* m) {
  asm volatile("prefetch.tensormap [%0];" ::"l"(m) : "memory");
}
__device__ __forceinline__ void cluster_sync_relaxed() {
  __syncwarp();
  asm volatile("barrier.cluster.arrive.relaxed.aligned;\nbarrier.cluster.wait.aligned;" ::: "memory");
}
__device__ __forceinline__ void pdl_wait() { asm volatile("griddepcontrol.wait;" ::: "memory"); }
__device__ __forceinline__ void pdl_trigger() { asm volatile("griddepcontrol.launch_dependents;" ::: "memory"); }
__device__ __forceinline__ void bar_sync(int id, int n) { asm volatile("bar.sync %0, %1;" ::"r"(id), "r"(n) : "memory"); }
__device__ __forceinline__ void bar_arrive(int id, int n) { asm volatile("bar.arrive %0, %1;" ::"r"(id), "r"(n) : "memory"); }
#define WG_FENCE() asm volatile("wgmma.fence.sync.aligned;" ::: "memory")
#define WG_COMMIT() asm volatile("wgmma.commit_group.sync.aligned;" ::: "memory")
#define WG_WAIT(n) asm volatile("wgmma.wait_group.sync.aligned %0;" ::"n"(n) : "memory")
__device__ __forceinline__ uint64_t mkdesc(uint32_t addr, uint32_t lbo, uint32_t sbo, uint32_t sw) {
  return (uint64_t)((addr & 0x3FFFF) >> 4) | ((uint64_t)(lbo >> 4) << 16) | ((uint64_t)(sbo >> 4) << 32) |
         ((uint64_t)sw << 62);
}
template <int N> __device__ __forceinline__ void fence_regs(float (&r)[N]) {
#pragma unroll
  for (int i = 0; i < N; i++) asm volatile("" : "+f"(r[i])::"memory");
}
__device__ __forceinline__ uint32_t pack_bf16(float lo, float hi) {
  uint32_t r;
  asm("cvt.rn.bf16x2.f32 %0, %1, %2;" : "=r"(r) : "f"(hi), "f"(lo));
  return r;
}
__device__ __forceinline__ float bf_lo(uint32_t v) { return __uint_as_float(v << 16); }
__device__ __forceinline__ float bf_hi(uint32_t v) { return __uint_as_float(v & 0xffff0000u); }
__device__ __forceinline__ float ex2(float x) {
  float y;
  asm("ex2.approx.ftz.f32 %0, %1;" : "=f"(y) : "f"(x));
  return y;
}
__device__ __forceinline__ uint4 ldg_nc(const void* p) {
  uint4 v;
  asm volatile("ld.global.nc.L1::no_allocate.v4.u32 {%0, %1, %2, %3}, [%4];"
               : "=r"(v.x), "=r"(v.y), "=r"(v.z), "=r"(v.w) : "l"(p));
  return v;
}

__device__ __forceinline__ void wgmma_ss_n256(float (&d)[128], uint64_t da, uint64_t db, int sd) {
  asm volatile("{\n.reg .pred p;\nsetp.ne.b32 p, %130, 0;\n"
      "wgmma.mma_async.sync.aligned.m64n256k16.f32.bf16.bf16 {"
      "%0, %1, %2, %3, %4, %5, %6, %7, %8, %9, %10, %11, %12, %13, %14, %15, "
      "%16, %17, %18, %19, %20, %21, %22, %23, %24, %25, %26, %27, %28, %29, %30, %31, "
      "%32, %33, %34, %35, %36, %37, %38, %39, %40, %41, %42, %43, %44, %45, %46, %47, "
      "%48, %49, %50, %51, %52, %53, %54, %55, %56, %57, %58, %59, %60, %61, %62, %63, "
      "%64, %65, %66, %67, %68, %69, %70, %71, %72, %73, %74, %75, %76, %77, %78, %79, "
      "%80, %81, %82, %83, %84, %85, %86, %87, %88, %89, %90, %91, %92, %93, %94, %95, "
      "%96, %97, %98, %99, %100, %101, %102, %103, %104, %105, %106, %107, %108, %109, %110, %111, "
      "%112, %113, %114, %115, %116, %117, %118, %119, %120, %121, %122, %123, %124, %125, %126, %127"
      "}, %128, %129, p, 1, 1, 0, 1;\n}\n"
    : "+f"(d[0]), "+f"(d[1]), "+f"(d[2]), "+f"(d[3]), "+f"(d[4]), "+f"(d[5]), "+f"(d[6]), "+f"(d[7]),
      "+f"(d[8]), "+f"(d[9]), "+f"(d[10]), "+f"(d[11]), "+f"(d[12]), "+f"(d[13]), "+f"(d[14]), "+f"(d[15]),
      "+f"(d[16]), "+f"(d[17]), "+f"(d[18]), "+f"(d[19]), "+f"(d[20]), "+f"(d[21]), "+f"(d[22]), "+f"(d[23]),
      "+f"(d[24]), "+f"(d[25]), "+f"(d[26]), "+f"(d[27]), "+f"(d[28]), "+f"(d[29]), "+f"(d[30]), "+f"(d[31]),
      "+f"(d[32]), "+f"(d[33]), "+f"(d[34]), "+f"(d[35]), "+f"(d[36]), "+f"(d[37]), "+f"(d[38]), "+f"(d[39]),
      "+f"(d[40]), "+f"(d[41]), "+f"(d[42]), "+f"(d[43]), "+f"(d[44]), "+f"(d[45]), "+f"(d[46]), "+f"(d[47]),
      "+f"(d[48]), "+f"(d[49]), "+f"(d[50]), "+f"(d[51]), "+f"(d[52]), "+f"(d[53]), "+f"(d[54]), "+f"(d[55]),
      "+f"(d[56]), "+f"(d[57]), "+f"(d[58]), "+f"(d[59]), "+f"(d[60]), "+f"(d[61]), "+f"(d[62]), "+f"(d[63]),
      "+f"(d[64]), "+f"(d[65]), "+f"(d[66]), "+f"(d[67]), "+f"(d[68]), "+f"(d[69]), "+f"(d[70]), "+f"(d[71]),
      "+f"(d[72]), "+f"(d[73]), "+f"(d[74]), "+f"(d[75]), "+f"(d[76]), "+f"(d[77]), "+f"(d[78]), "+f"(d[79]),
      "+f"(d[80]), "+f"(d[81]), "+f"(d[82]), "+f"(d[83]), "+f"(d[84]), "+f"(d[85]), "+f"(d[86]), "+f"(d[87]),
      "+f"(d[88]), "+f"(d[89]), "+f"(d[90]), "+f"(d[91]), "+f"(d[92]), "+f"(d[93]), "+f"(d[94]), "+f"(d[95]),
      "+f"(d[96]), "+f"(d[97]), "+f"(d[98]), "+f"(d[99]), "+f"(d[100]), "+f"(d[101]), "+f"(d[102]), "+f"(d[103]),
      "+f"(d[104]), "+f"(d[105]), "+f"(d[106]), "+f"(d[107]), "+f"(d[108]), "+f"(d[109]), "+f"(d[110]), "+f"(d[111]),
      "+f"(d[112]), "+f"(d[113]), "+f"(d[114]), "+f"(d[115]), "+f"(d[116]), "+f"(d[117]), "+f"(d[118]), "+f"(d[119]),
      "+f"(d[120]), "+f"(d[121]), "+f"(d[122]), "+f"(d[123]), "+f"(d[124]), "+f"(d[125]), "+f"(d[126]), "+f"(d[127])
    : "l"(da), "l"(db), "r"(sd));
}
__device__ __forceinline__ void wgmma_ss_n216(float (&d)[108], uint64_t da, uint64_t db, int sd) {
  asm volatile("{\n.reg .pred p;\nsetp.ne.b32 p, %110, 0;\n"
      "wgmma.mma_async.sync.aligned.m64n216k16.f32.bf16.bf16 {"
      "%0, %1, %2, %3, %4, %5, %6, %7, %8, %9, %10, %11, %12, %13, %14, %15, "
      "%16, %17, %18, %19, %20, %21, %22, %23, %24, %25, %26, %27, %28, %29, %30, %31, "
      "%32, %33, %34, %35, %36, %37, %38, %39, %40, %41, %42, %43, %44, %45, %46, %47, "
      "%48, %49, %50, %51, %52, %53, %54, %55, %56, %57, %58, %59, %60, %61, %62, %63, "
      "%64, %65, %66, %67, %68, %69, %70, %71, %72, %73, %74, %75, %76, %77, %78, %79, "
      "%80, %81, %82, %83, %84, %85, %86, %87, %88, %89, %90, %91, %92, %93, %94, %95, "
      "%96, %97, %98, %99, %100, %101, %102, %103, %104, %105, %106, %107"
      "}, %108, %109, p, 1, 1, 0, 1;\n}\n"
    : "+f"(d[0]), "+f"(d[1]), "+f"(d[2]), "+f"(d[3]), "+f"(d[4]), "+f"(d[5]), "+f"(d[6]), "+f"(d[7]),
      "+f"(d[8]), "+f"(d[9]), "+f"(d[10]), "+f"(d[11]), "+f"(d[12]), "+f"(d[13]), "+f"(d[14]), "+f"(d[15]),
      "+f"(d[16]), "+f"(d[17]), "+f"(d[18]), "+f"(d[19]), "+f"(d[20]), "+f"(d[21]), "+f"(d[22]), "+f"(d[23]),
      "+f"(d[24]), "+f"(d[25]), "+f"(d[26]), "+f"(d[27]), "+f"(d[28]), "+f"(d[29]), "+f"(d[30]), "+f"(d[31]),
      "+f"(d[32]), "+f"(d[33]), "+f"(d[34]), "+f"(d[35]), "+f"(d[36]), "+f"(d[37]), "+f"(d[38]), "+f"(d[39]),
      "+f"(d[40]), "+f"(d[41]), "+f"(d[42]), "+f"(d[43]), "+f"(d[44]), "+f"(d[45]), "+f"(d[46]), "+f"(d[47]),
      "+f"(d[48]), "+f"(d[49]), "+f"(d[50]), "+f"(d[51]), "+f"(d[52]), "+f"(d[53]), "+f"(d[54]), "+f"(d[55]),
      "+f"(d[56]), "+f"(d[57]), "+f"(d[58]), "+f"(d[59]), "+f"(d[60]), "+f"(d[61]), "+f"(d[62]), "+f"(d[63]),
      "+f"(d[64]), "+f"(d[65]), "+f"(d[66]), "+f"(d[67]), "+f"(d[68]), "+f"(d[69]), "+f"(d[70]), "+f"(d[71]),
      "+f"(d[72]), "+f"(d[73]), "+f"(d[74]), "+f"(d[75]), "+f"(d[76]), "+f"(d[77]), "+f"(d[78]), "+f"(d[79]),
      "+f"(d[80]), "+f"(d[81]), "+f"(d[82]), "+f"(d[83]), "+f"(d[84]), "+f"(d[85]), "+f"(d[86]), "+f"(d[87]),
      "+f"(d[88]), "+f"(d[89]), "+f"(d[90]), "+f"(d[91]), "+f"(d[92]), "+f"(d[93]), "+f"(d[94]), "+f"(d[95]),
      "+f"(d[96]), "+f"(d[97]), "+f"(d[98]), "+f"(d[99]), "+f"(d[100]), "+f"(d[101]), "+f"(d[102]), "+f"(d[103]),
      "+f"(d[104]), "+f"(d[105]), "+f"(d[106]), "+f"(d[107])
    : "l"(da), "l"(db), "r"(sd));
}
__device__ __forceinline__ void wgmma_ss_n160(float (&d)[80], uint64_t da, uint64_t db, int sd) {
  asm volatile("{\n.reg .pred p;\nsetp.ne.b32 p, %82, 0;\n"
      "wgmma.mma_async.sync.aligned.m64n160k16.f32.bf16.bf16 {"
      "%0, %1, %2, %3, %4, %5, %6, %7, %8, %9, %10, %11, %12, %13, %14, %15, "
      "%16, %17, %18, %19, %20, %21, %22, %23, %24, %25, %26, %27, %28, %29, %30, %31, "
      "%32, %33, %34, %35, %36, %37, %38, %39, %40, %41, %42, %43, %44, %45, %46, %47, "
      "%48, %49, %50, %51, %52, %53, %54, %55, %56, %57, %58, %59, %60, %61, %62, %63, "
      "%64, %65, %66, %67, %68, %69, %70, %71, %72, %73, %74, %75, %76, %77, %78, %79"
      "}, %80, %81, p, 1, 1, 0, 1;\n}\n"
    : "+f"(d[0]), "+f"(d[1]), "+f"(d[2]), "+f"(d[3]), "+f"(d[4]), "+f"(d[5]), "+f"(d[6]), "+f"(d[7]),
      "+f"(d[8]), "+f"(d[9]), "+f"(d[10]), "+f"(d[11]), "+f"(d[12]), "+f"(d[13]), "+f"(d[14]), "+f"(d[15]),
      "+f"(d[16]), "+f"(d[17]), "+f"(d[18]), "+f"(d[19]), "+f"(d[20]), "+f"(d[21]), "+f"(d[22]), "+f"(d[23]),
      "+f"(d[24]), "+f"(d[25]), "+f"(d[26]), "+f"(d[27]), "+f"(d[28]), "+f"(d[29]), "+f"(d[30]), "+f"(d[31]),
      "+f"(d[32]), "+f"(d[33]), "+f"(d[34]), "+f"(d[35]), "+f"(d[36]), "+f"(d[37]), "+f"(d[38]), "+f"(d[39]),
      "+f"(d[40]), "+f"(d[41]), "+f"(d[42]), "+f"(d[43]), "+f"(d[44]), "+f"(d[45]), "+f"(d[46]), "+f"(d[47]),
      "+f"(d[48]), "+f"(d[49]), "+f"(d[50]), "+f"(d[51]), "+f"(d[52]), "+f"(d[53]), "+f"(d[54]), "+f"(d[55]),
      "+f"(d[56]), "+f"(d[57]), "+f"(d[58]), "+f"(d[59]), "+f"(d[60]), "+f"(d[61]), "+f"(d[62]), "+f"(d[63]),
      "+f"(d[64]), "+f"(d[65]), "+f"(d[66]), "+f"(d[67]), "+f"(d[68]), "+f"(d[69]), "+f"(d[70]), "+f"(d[71]),
      "+f"(d[72]), "+f"(d[73]), "+f"(d[74]), "+f"(d[75]), "+f"(d[76]), "+f"(d[77]), "+f"(d[78]), "+f"(d[79])
    : "l"(da), "l"(db), "r"(sd));
}
__device__ __forceinline__ void wgmma_rs_n128(float (&d)[64], uint32_t a0, uint32_t a1, uint32_t a2, uint32_t a3,
                                  uint64_t db, int sd) {
  asm volatile("{\n.reg .pred p;\nsetp.ne.b32 p, %69, 0;\n"
      "wgmma.mma_async.sync.aligned.m64n128k16.f32.bf16.bf16 {"
      "%0, %1, %2, %3, %4, %5, %6, %7, %8, %9, %10, %11, %12, %13, %14, %15, "
      "%16, %17, %18, %19, %20, %21, %22, %23, %24, %25, %26, %27, %28, %29, %30, %31, "
      "%32, %33, %34, %35, %36, %37, %38, %39, %40, %41, %42, %43, %44, %45, %46, %47, "
      "%48, %49, %50, %51, %52, %53, %54, %55, %56, %57, %58, %59, %60, %61, %62, %63"
      "}, {%64, %65, %66, %67}, %68, p, 1, 1, 0;\n}\n"
    : "+f"(d[0]), "+f"(d[1]), "+f"(d[2]), "+f"(d[3]), "+f"(d[4]), "+f"(d[5]), "+f"(d[6]), "+f"(d[7]),
      "+f"(d[8]), "+f"(d[9]), "+f"(d[10]), "+f"(d[11]), "+f"(d[12]), "+f"(d[13]), "+f"(d[14]), "+f"(d[15]),
      "+f"(d[16]), "+f"(d[17]), "+f"(d[18]), "+f"(d[19]), "+f"(d[20]), "+f"(d[21]), "+f"(d[22]), "+f"(d[23]),
      "+f"(d[24]), "+f"(d[25]), "+f"(d[26]), "+f"(d[27]), "+f"(d[28]), "+f"(d[29]), "+f"(d[30]), "+f"(d[31]),
      "+f"(d[32]), "+f"(d[33]), "+f"(d[34]), "+f"(d[35]), "+f"(d[36]), "+f"(d[37]), "+f"(d[38]), "+f"(d[39]),
      "+f"(d[40]), "+f"(d[41]), "+f"(d[42]), "+f"(d[43]), "+f"(d[44]), "+f"(d[45]), "+f"(d[46]), "+f"(d[47]),
      "+f"(d[48]), "+f"(d[49]), "+f"(d[50]), "+f"(d[51]), "+f"(d[52]), "+f"(d[53]), "+f"(d[54]), "+f"(d[55]),
      "+f"(d[56]), "+f"(d[57]), "+f"(d[58]), "+f"(d[59]), "+f"(d[60]), "+f"(d[61]), "+f"(d[62]), "+f"(d[63])
    : "r"(a0), "r"(a1), "r"(a2), "r"(a3), "l"(db), "r"(sd));
}
__device__ __forceinline__ void wgmma_rs_n24(float (&d)[12], uint32_t a0, uint32_t a1, uint32_t a2, uint32_t a3,
                                  uint64_t db, int sd) {
  asm volatile("{\n.reg .pred p;\nsetp.ne.b32 p, %17, 0;\n"
      "wgmma.mma_async.sync.aligned.m64n24k16.f32.bf16.bf16 {"
      "%0, %1, %2, %3, %4, %5, %6, %7, %8, %9, %10, %11"
      "}, {%12, %13, %14, %15}, %16, p, 1, 1, 1;\n}\n"
    : "+f"(d[0]), "+f"(d[1]), "+f"(d[2]), "+f"(d[3]), "+f"(d[4]), "+f"(d[5]), "+f"(d[6]), "+f"(d[7]),
      "+f"(d[8]), "+f"(d[9]), "+f"(d[10]), "+f"(d[11])
    : "r"(a0), "r"(a1), "r"(a2), "r"(a3), "l"(db), "r"(sd));
}

constexpr int K1_ST = 4, K1_STAGE = 49152;
constexpr int K1_SMEM = K1_ST * K1_STAGE + 2048   + 1024   + 3072   + 128;

__global__ void __cluster_dims__(2, 1, 1) __launch_bounds__(384, 1)
k1_qkv(const __grid_constant__ CUtensorMap tmx, const __grid_constant__ CUtensorMap tmw,
       const bf16* __restrict__ x, const bf16* __restrict__ w, const bf16* __restrict__ wo) {
  extern __shared__ __align__(1024) uint8_t sm[];
  float4* tab = (float4*)(sm + K1_ST * K1_STAGE);
  float2* rowab = (float2*)(sm + K1_ST * K1_STAGE + 2048);
  float* red = (float*)(sm + K1_ST * K1_STAGE + 3072);
  const uint32_t sbase = smem_u32(sm);
  const uint32_t fullb = sbase + K1_ST * K1_STAGE + 6144, emptyb = fullb + 8 * K1_ST;
  const int tid = threadIdx.x, lane = tid & 31;
  const int warp = __shfl_sync(~0u, tid >> 5, 0);
  const int rank = blockIdx.x & 1, cl = blockIdx.x >> 1;
  const int n = cl & 7, m = (cl >> 3) * 2 + rank;
  const int c0 = n * 240 - (n & 1) * 16;
  if (tid == 0) STAMP(0, 0);
  if (tid == 0) {
    prefetch_map(&tmx); prefetch_map(&tmw);
    for (int i = 0; i < K1_ST; i++) { mbar_init(fullb + 8 * i, 1); mbar_init(emptyb + 8 * i, 4); }
    asm volatile("fence.mbarrier_init.release.cluster;" ::: "memory");
  }
  __syncthreads();
  cluster_arrive();
  pdl_trigger();

  if (warp == 0) {
    if (lane == 0) {
      for (int kt = 0; kt < K1_ST; kt++) {
        mbar_expect(fullb + 8 * kt, K1_STAGE);
        tma2d(sbase + kt * K1_STAGE, &tmx, kt * 64, m * 128, fullb + 8 * kt);
      }
    }
    __syncwarp();
    cluster_wait();
    if (lane == 0) {
      for (int kt = 0; kt < 10; kt++) {
        const int s = kt % K1_ST;
        const uint32_t sa = sbase + s * K1_STAGE, sb = sa + 16384 + rank * 16384;
        if (kt >= K1_ST) {
          mbar_wait(emptyb + 8 * s, ((kt / K1_ST) - 1) & 1);
          mbar_expect(fullb + 8 * s, K1_STAGE);
          tma2d(sa, &tmx, kt * 64, m * 128, fullb + 8 * s);
        }
#pragma unroll
        for (int j = 0; j < 4; j++) tma2d_mc(sb + j * 4096, &tmw, c0 + rank * 128 + j * 32, kt * 64, fullb + 8 * s);
      }
    }
    __syncwarp();
  } else if (warp < 4) {
    const int w3 = warp - 1, t96 = tid - 32;
    uint4 xv[6][3], wv[14];
#pragma unroll
    for (int i = 0; i < 6; i++) {
      const bf16* xr = x + (size_t)(m * 128 + n * 16 + min(w3 + 3 * i, 15)) * D_ + lane * 8;
      xv[i][0] = ldg_nc(xr);
      xv[i][1] = ldg_nc(xr + 256);
      xv[i][2] = ldg_nc(xr + (lane < 16 ? 512 : 0));
    }
#pragma unroll
    for (int i = 0; i < 14; i++) wv[i] = ldg_nc(w + (size_t)(m * 40 + min(w3 + 3 * i, 39)) * 1920 + c0 + lane * 8);
#pragma unroll
    for (int i = 0; i < 6; i++) {
      float f[24];
#pragma unroll
      for (int k = 0; k < 3; k++) {
        const uint4 v = xv[i][k];
        f[8 * k + 0] = bf_lo(v.x); f[8 * k + 1] = bf_hi(v.x); f[8 * k + 2] = bf_lo(v.y); f[8 * k + 3] = bf_hi(v.y);
        f[8 * k + 4] = bf_lo(v.z); f[8 * k + 5] = bf_hi(v.z); f[8 * k + 6] = bf_lo(v.w); f[8 * k + 7] = bf_hi(v.w);
      }
      float s = 0.f, s2 = 0.f;
#pragma unroll
      for (int k = 0; k < 16; k++) s += f[k];
#pragma unroll
      for (int k = 16; k < 24; k++) s2 += f[k];
      if (lane < 16) s += s2;
#pragma unroll
      for (int o = 16; o; o >>= 1) s += __shfl_xor_sync(~0u, s, o);
      const float mean = s * (1.f / D_);
      float q = 0.f, q2 = 0.f;
#pragma unroll
      for (int k = 0; k < 16; k++) { float d = f[k] - mean; q = fmaf(d, d, q); }
#pragma unroll
      for (int k = 16; k < 24; k++) { float d = f[k] - mean; q2 = fmaf(d, d, q2); }
      if (lane < 16) q += q2;
#pragma unroll
      for (int o = 16; o; o >>= 1) q += __shfl_xor_sync(~0u, q, o);
      if (lane == 0 && w3 + 3 * i < 16)
        g_rowstat[m * 128 + n * 16 + w3 + 3 * i] = make_float2(rsqrtf(q * (1.f / D_) + 1e-5f), mean);
    }
    {
      float acc8[8];
#pragma unroll
      for (int i = 0; i < 8; i++) acc8[i] = 0.f;
#pragma unroll
      for (int i = 0; i < 14; i++) {
        if (i < 13 || w3 == 0) {
          const uint4 v = wv[i];
          acc8[0] += bf_lo(v.x); acc8[1] += bf_hi(v.x); acc8[2] += bf_lo(v.y); acc8[3] += bf_hi(v.y);
          acc8[4] += bf_lo(v.z); acc8[5] += bf_hi(v.z); acc8[6] += bf_lo(v.w); acc8[7] += bf_hi(v.w);
        }
      }
#pragma unroll
      for (int i = 0; i < 8; i++) red[w3 * 256 + lane * 8 + i] = acc8[i];
    }
    bar_sync(1, 96);
    for (int c = t96; c < 256; c += 96) g_cpart[m * 2048 + n * 256 + c] = red[c] + red[256 + c] + red[512 + c];
    bar_sync(1, 96);
    if (t96 == 0) {
      __threadfence();
      asm volatile("red.relaxed.gpu.global.add.u32 [%0], 1;" ::"l"(&g_cnt[m * 32]) : "memory");
      asm volatile("red.relaxed.gpu.global.add.u32 [%0], 1;" ::"l"(&g_cnt[(16 + n) * 32]) : "memory");
      uint32_t a, b, it = 0;
      while (true) {
        asm volatile("ld.relaxed.gpu.global.u32 %0, [%1];" : "=r"(a) : "l"(&g_cnt[m * 32]) : "memory");
        asm volatile("ld.relaxed.gpu.global.u32 %0, [%1];" : "=r"(b) : "l"(&g_cnt[(16 + n) * 32]) : "memory");
        if (a >= 8 && b >= 16) break;
        if (++it > (1u << 22)) wait_timeout();
        __nanosleep(64);
      }
      __threadfence();
    } else if (t96 >= 32) {
      uint4 v[7];
#pragma unroll
      for (int i = 0; i < 7; i++) {
        const int e = min(t96 - 32 + 64 * i, 399), k = blockIdx.x * 5 + e / 80, pr = k / 40, r = k - pr * 40;
        v[i] = ldg_nc(wo + (size_t)(pr * 40 + (r < 16 ? r : (r < 32 ? r + 4 : (r < 36 ? r - 16 : r)))) * D_ + (e % 80) * 8);
      }
#pragma unroll
      for (int i = 0; i < 7; i++) {
        const int e = min(t96 - 32 + 64 * i, 399), k = blockIdx.x * 5 + e / 80, cg = e % 80, nt = cg / 10;
        g_wo[((nt * 10 + (k >> 6)) * 10 + cg - nt * 10) * 64 + (k & 63)] = v[i];
      }
    }
    bar_sync(1, 96);
    for (int r = t96; r < 128; r += 96) {
      float2 st = __ldcg(&g_rowstat[m * 128 + r]);
      rowab[r] = make_float2(st.x, -st.x * st.y);
      float s0 = 0.f, s1 = 0.f;
#pragma unroll
      for (int i = 0; i < 16; i++) {
        float2 p = __ldcg((const float2*)&g_cpart[i * 2048 + n * 256 + 2 * r]);
        s0 += p.x; s1 += p.y;
      }
      const int lc = max(2 * r - (n & 1) * 16, 0), hl = lc / 20, d = lc - hl * 20;
      tab[r] = make_float4(s0, s1, __int_as_float(hl * 6144 + (d >> 3) * 128 + (d & 7) * 2), 0.f);
    }
    cluster_wait();
    if (tid == 32) STAMP(0, 5);
    bar_sync(2, 96 + 256);
    for (int i = t96; i < 12 * 128; i += 96) {
      const int hl = i >> 7, r = i & 127, sh = n * 12 + hl;
      uint2 v;
      if (sh < 32) v = make_uint2(0x3F803F80u, 0x00003F80u);
      else if (sh >= 64) v = make_uint2(0x00003F80u, 0u);
      else if ((POLY_MASK >> (r >> 3)) & 1) v = make_uint2(0x4A7A4B00u, 0x00004653u);
      else v = make_uint2(0u, 0u);
      *(uint2*)(sm + hl * 6144 + (r >> 3) * 384 + 256 + (r & 7) * 16 + 8) = v;
    }
    fence_async();
    bar_sync(3, 96 + 256);
    if (t96 < 12) {
      bulk_st((uint8_t*)g_qkv + (size_t)(n * 12 + t96) * HEAD_IMG + m * 6144, sbase + t96 * 6144, 6144);
      bulk_commit_wait();
    }
    __syncwarp();
  } else {
    const int cw = warp - 4, wg = cw >> 2;
    float acc[128];
    const uint64_t da0 = mkdesc(sbase + wg * 8192, 16, 1024, 1);
    const uint64_t db0 = mkdesc(sbase + 16384, 4096, 512, 2);
    cluster_wait();
#pragma unroll 1
    for (int kt = 0; kt < 10; kt++) {
      const int s = kt % K1_ST;
      mbar_wait(fullb + 8 * s, (kt / K1_ST) & 1);
      if (kt == 0 && tid == 128) STAMP(0, 1);
      const uint64_t da = da0 + s * (K1_STAGE >> 4), db = db0 + s * (K1_STAGE >> 4);
      WG_FENCE();
#pragma unroll
      for (int k = 0; k < 4; k++) wgmma_ss_n256(acc, da + k * 2, db + k * 64, (kt | k) != 0);
      WG_COMMIT();
      if (kt > 0) {
        WG_WAIT(1);
        if (kt - 1 + K1_ST < 10 && (tid & 127) < 2) mbar_arrive_cta(emptyb + 8 * ((kt - 1) % K1_ST), tid & 1);
      }
    }
    WG_WAIT(0);
    fence_regs(acc);
    if (tid == 128) STAMP(0, 2);
    bar_sync(2, 96 + 256);
    if (tid == 128) STAMP(0, 3);
    const int g = lane >> 2, c = lane & 3;
    const float2 ab0 = rowab[cw * 16 + g], ab1 = rowab[cw * 16 + g + 8];
    const float k0 = ((POLY_MASK >> (cw * 2)) & 1) ? 32768.f : 1.f, k1 = ((POLY_MASK >> (cw * 2 + 1)) & 1) ? 32768.f : 1.f;
    uint8_t* dst = sm + cw * 768 + g * 16;
#pragma unroll
    for (int seg = 0; seg < 3; seg++) {
      const int j0 = seg == 0 ? 0 : (seg == 1 ? 12 : 20), j1 = seg == 0 ? 12 : (seg == 1 ? 20 : 32);
      const int sec = (c0 + j0 * 8 + 16) / 640;
      const float f0 = sec == 0 ? QSCALE : (sec == 1 ? k0 : 1.f), f1 = sec == 0 ? QSCALE : (sec == 1 ? k1 : 1.f);
      const float a0 = ab0.x * f0, b0 = ab0.y * f0, a1 = ab1.x * f1, b1 = ab1.y * f1;
#pragma unroll
      for (int j = j0; j < j1; j++) {
        if ((j < 2 && (n & 1)) || (j >= 30 && !(n & 1))) continue;
        const float4 t = tab[4 * j + c];
        uint8_t* p = dst + __float_as_int(t.z);
        *(uint32_t*)p = pack_bf16(fmaf(acc[4 * j], a0, b0 * t.x), fmaf(acc[4 * j + 1], a0, b0 * t.y));
        *(uint32_t*)(p + 384) = pack_bf16(fmaf(acc[4 * j + 2], a1, b1 * t.x), fmaf(acc[4 * j + 3], a1, b1 * t.y));
      }
    }
    fence_async();
    bar_arrive(3, 96 + 256);
    if (tid == 128) STAMP(0, 4);
  }
  cluster_sync_relaxed();
  if (tid == 32) STAMP(0, 6);
}

constexpr int K2_SMEM = 2 * HEAD_IMG + 2 * 6144 + 256;

__device__ __forceinline__ uint32_t exp_pair(bool poly, float a, float b, uint32_t mk) {
  if (poly) {
    const uint32_t pk = __byte_perm(__float_as_uint(a), __float_as_uint(b), 0x6521);
    uint32_t m, q;
    asm("lop3.b32 %0, %1, %2, 0x3f803f80, 0xEA;" : "=r"(m) : "r"(pk), "r"(mk));
    asm("fma.rn.bf16x2 %0, %1, %1, %2;" : "=r"(q) : "r"(m), "r"(0x40014001u));
    return pk - m + q;
  }
  return pack_bf16(ex2(a), ex2(b));
}
__device__ __forceinline__ void exp_pv(const float (&s)[64], float (&o)[12], uint64_t dv, uint32_t mk) {
#pragma unroll
  for (int k0 = 0; k0 < 8; k0 += 2) {
    uint32_t p[8];
#pragma unroll
    for (int i = 0; i < 8; i++)
      p[i] = exp_pair((POLY_MASK >> (k0 * 2 + i / 2)) & 1, s[k0 * 8 + 2 * i], s[k0 * 8 + 2 * i + 1], mk);
    WG_FENCE();
    wgmma_rs_n24(o, p[0], p[1], p[2], p[3], dv + k0 * 48, 1);
    wgmma_rs_n24(o, p[4], p[5], p[6], p[7], dv + k0 * 48 + 48, 1);
  }
}
__device__ __forceinline__ void load_q(uint32_t (&q)[6], const uint8_t* p) {
  q[0] = __ldcg((const uint32_t*)p);         q[1] = __ldcg((const uint32_t*)(p + 384));
  q[2] = __ldcg((const uint32_t*)(p + 128)); q[3] = __ldcg((const uint32_t*)(p + 512));
  q[4] = __ldcg((const uint32_t*)(p + 256)); q[5] = __ldcg((const uint32_t*)(p + 640));
}
__device__ __forceinline__ void store_o(const float (&o)[12], uint8_t* dst, int o0, int o1, int o2, int lane) {
  const float l0 = __shfl_sync(~0u, o[8], (lane & ~3) | 2), l1 = __shfl_sync(~0u, o[10], (lane & ~3) | 2);
  const float i0 = __frcp_rn(l0), i1 = __frcp_rn(l1);
  *(uint32_t*)(dst + o0) = pack_bf16(o[0] * i0, o[1] * i0); *(uint32_t*)(dst + o0 + 1024) = pack_bf16(o[2] * i1, o[3] * i1);
  *(uint32_t*)(dst + o1) = pack_bf16(o[4] * i0, o[5] * i0); *(uint32_t*)(dst + o1 + 1024) = pack_bf16(o[6] * i1, o[7] * i1);
  if ((lane & 3) < 2) {
    *(uint32_t*)(dst + o2) = pack_bf16(o[8] * i0, o[9] * i0);
    *(uint32_t*)(dst + o2 + 1024) = pack_bf16(o[10] * i1, o[11] * i1);
  }
}
__device__ __forceinline__ int img_off(int chunk) { return (chunk >> 3) * 16384 + (chunk & 7) * 128; }
__device__ __forceinline__ float sq20(uint4 a, uint4 b, uint2 c) {
  uint32_t s0, s1;
  asm("mul.rn.bf16x2 %0, %1, %1;" : "=r"(s0) : "r"(a.x));
  asm("mul.rn.bf16x2 %0, %1, %1;" : "=r"(s1) : "r"(a.y));
#define SQ_(acc, v) asm("fma.rn.bf16x2 %0, %1, %1, %0;" : "+r"(acc) : "r"(v))
  SQ_(s0, a.z); SQ_(s1, a.w); SQ_(s0, b.x); SQ_(s1, b.y); SQ_(s0, b.z); SQ_(s1, b.w); SQ_(s0, c.x); SQ_(s1, c.y);
#undef SQ_
  return (bf_lo(s0) + bf_hi(s0)) + (bf_lo(s1) + bf_hi(s1));
}

__global__ void __launch_bounds__(512, 1)
k2_attn(const bf16* __restrict__ wg_, const bf16* __restrict__ wu,
        const bf16* __restrict__ wd, uint32_t mk) {
  extern __shared__ __align__(1024) uint8_t sm[];
  const uint32_t sbase = smem_u32(sm);
  float* part = (float*)(sm + 2 * HEAD_IMG);
  const uint32_t kvb = sbase + 2 * HEAD_IMG + 2 * 6144;
  const uint32_t flagb = kvb + 128, partb = kvb + 136;
  volatile uint32_t* sflag = (volatile uint32_t*)(sm + 2 * HEAD_IMG + 2 * 6144 + 160);
  const int tid = threadIdx.x, lane = tid & 31;
  const int warp = __shfl_sync(~0u, tid >> 5, 0);
  const int head = blockIdx.x >> 2, qb = blockIdx.x & 3;
  const uint8_t* qimg = (const uint8_t*)g_qkv + (size_t)head * HEAD_IMG + qb * 64 * 384;

  if (tid == 0) STAMP(1, 0);
  if (tid == 0) {
    for (int i = 0; i < 16; i++) mbar_init(kvb + 8 * i, 1);
    mbar_init(flagb, 1); mbar_init(partb, 128); mbar_init(partb + 8, 128);
    asm volatile("fence.mbarrier_init.release.cluster;" ::: "memory");
  }
  __syncthreads();

  if (warp >= 12) {
    asm volatile("setmaxnreg.dec.sync.aligned.u32 56;");
    const int t = tid - 384;
    pdl_wait();
    pdl_trigger();
    if (t == 0) {
      const uint8_t* kimg = (const uint8_t*)g_qkv + (size_t)(32 + head) * HEAD_IMG;
      const uint8_t* vimg = (const uint8_t*)g_qkv + (size_t)(64 + head) * HEAD_IMG;
      for (int b = 0; b < 16; b++) {
        mbar_expect(kvb + 8 * b, 12288);
        bulk_ld(sbase + b * 6144, kimg + b * 6144, 6144, kvb + 8 * b);
        bulk_ld(sbase + HEAD_IMG + b * 6144, vimg + b * 6144, 6144, kvb + 8 * b);
      }
    }
    if (blockIdx.x == 0 && t >= 32 && t < 56) g_cnt[(t - 32) * 32] = 0;
    {
      float qm = 0.f, km = 0.f;
      const int ro = (t >> 3) * 384 + (t & 7) * 16;
#pragma unroll
      for (int i = 0; i < 4; i++) {
        const uint8_t* p = qimg + i * 6144 + ro;
        const float v = sq20(__ldcg((const uint4*)p), __ldcg((const uint4*)(p + 128)), __ldcg((const uint2*)(p + 256)));
        qm = __uint_as_float(max(__float_as_uint(qm), __float_as_uint(v)));
      }
#pragma unroll 1
      for (int b = 0; b < 16; b++) {
        mbar_wait(kvb + 8 * b, 0);
        const uint8_t* p = sm + b * 6144 + ro;
        const float v = sq20(*(const uint4*)p, *(const uint4*)(p + 128), *(const uint2*)(p + 256));
        km = __uint_as_float(max(__float_as_uint(km), __float_as_uint(v)));
      }
      if ((POLY_MASK >> (t >> 3)) & 1) km *= 9.313225746154785e-10f;
      const uint32_t qw = __reduce_max_sync(~0u, __float_as_uint(qm)), kw = __reduce_max_sync(~0u, __float_as_uint(km));
      if (lane == 0) { sflag[1 + (warp & 3)] = qw; sflag[5 + (warp & 3)] = kw; }
      bar_sync(1, 128);
      if (t == 0) {
        const float q2 = __uint_as_float(max(max(sflag[1], sflag[2]), max(sflag[3], sflag[4])));
        const float k2 = __uint_as_float(max(max(sflag[5], sflag[6]), max(sflag[7], sflag[8])));
        sflag[0] = (q2 * k2 <= 3000.f) ? 1u : 0u;
        mbar_arrive(flagb);
        STAMP(1, 2);
      }
    }
    const int kr = (warp & 3) * 8 + (lane >> 2), ch = lane & 3;
    if (blockIdx.x < 108) {
      const int cg = blockIdx.x * 4 + ch;
      const int up = cg >= 216, cc = cg - up * 216;
      const int nt = cc / 27, ci = cc - nt * 27 + up * 27;
      const bf16* src = (up ? wu : wg_) + cc * 8 + (size_t)kr * F_;
      uint4* dst = g_wgu + ((size_t)nt * 10 * 54 + ci) * 64 + kr;
      float a8[8];
#pragma unroll
      for (int i = 0; i < 8; i++) a8[i] = 0.f;
#pragma unroll 4
      for (int it = 0; it < 20; it++) {
        const uint4 v = ldg_nc(src + (size_t)it * 32 * F_);
        dst[(it >> 1) * (54 * 64) + (it & 1) * 32] = v;
        a8[0] += bf_lo(v.x); a8[1] += bf_hi(v.x); a8[2] += bf_lo(v.y); a8[3] += bf_hi(v.y);
        a8[4] += bf_lo(v.z); a8[5] += bf_hi(v.z); a8[6] += bf_lo(v.w); a8[7] += bf_hi(v.w);
      }
#pragma unroll
      for (int i = 0; i < 8; i++) {
        a8[i] += __shfl_xor_sync(~0u, a8[i], 4);
        a8[i] += __shfl_xor_sync(~0u, a8[i], 8);
        a8[i] += __shfl_xor_sync(~0u, a8[i], 16);
      }
      float* red = (float*)(sm + K2_SMEM);
      if (lane < 4) {
#pragma unroll
        for (int i = 0; i < 8; i++) red[(warp & 3) * 32 + lane * 8 + i] = a8[i];
      }
      bar_sync(1, 128);
      if (t < 32) g_csgu[blockIdx.x * 32 + t] = red[t] + red[32 + t] + red[64 + t] + red[96 + t];
    }
    {
      const int first = blockIdx.x < 108 ? blockIdx.x * 5 : 540 + (blockIdx.x - 108) * 27;
      const int last = blockIdx.x < 108 ? first + 5 : first + 27;
#pragma unroll 4
      for (int ps = first; ps < last; ps++) {
        const int rg = ps / 20, cs = ps - rg * 20;
        const int cg = cs * 4 + ch, nt = cg / 10, ci = cg - nt * 10;
        const int k = rg * 32 + kr;
        g_wd[((nt * 27 + (k >> 6)) * 10 + ci) * 64 + (k & 63)] = ldg_nc(wd + (size_t)k * D_ + cg * 8);
      }
    }
    if (t == 0) STAMP(1, 6);
  } else {
    asm volatile("setmaxnreg.inc.sync.aligned.u32 152;");
    const int wg = warp >> 2, wq = warp & 3;
    const uint8_t* qthr = qimg + wq * 768 + (lane >> 2) * 16 + (lane & 3) * 4;
    uint8_t* othr = (uint8_t*)g_o + (size_t)qb * 4 * 163840 + wq * 2048 + (lane >> 2) * 16 + (lane & 3) * 4;
    const int oc = (head >> 1) * 5 + (head & 1) * 2;
    const int oo0 = img_off(oc), oo1 = img_off(oc + 1), oo2 = img_off((head >> 1) * 5 + 4) + (head & 1) * 8;
    const uint64_t dk0 = mkdesc(sbase, 128, 384, 0), dk0b = mkdesc(sbase + 256, 0, 384, 0);
    const uint64_t dv0 = mkdesc(sbase + HEAD_IMG, 384, 128, 0);
    const int nun = wg == 1 ? 4 : 3;
    const uint32_t utile = wg == 0 ? 0x210u : (wg == 1 ? 0x4325u : 0x576u);
    pdl_wait();
    if (tid == 0) STAMP(1, 1);
    uint32_t q[6];
    load_q(q, qthr + (utile & 15) * 3072);
    bool fast = true;
#pragma unroll 1
    for (int u = 0; u < nun; u++) {
      const int tile = (utile >> (4 * u)) & 15;
      int b0 = 0, b1 = 16;
      if (wg == 0 && u == 2) b1 = 11;
      if (wg == 1 && u == 0) b1 = 6;
      if (wg == 1 && u == 1) b0 = 11;
      if (wg == 2 && u == 2) b0 = 6;
      const bool wt = u == 0 || (wg == 1 && u == 1);
      float s[64], o[12];
#pragma unroll
      for (int i = 0; i < 12; i++) o[i] = 0.f;
      uint64_t dk = dk0 + b0 * 384, dkb = dk0b + b0 * 384, dv = dv0 + b0 * 384;
      if (wt) mbar_wait(kvb + 8 * b0, 0);
      fence_regs(o);
      WG_FENCE();
      wgmma_rs_n128(s, q[0], q[1], q[2], q[3], dk, 0);
      wgmma_rs_n128(s, q[4], q[5], 0, 0, dkb, 1);
      WG_COMMIT();
#pragma unroll 1
      for (int b = b0 + 1; b < b1; b++) {
        if (wt) mbar_wait(kvb + 8 * b, 0);
        WG_WAIT(0);
        fence_regs(s); fence_regs(o);
        exp_pv(s, o, dv, mk);
        dk += 384; dkb += 384; dv += 384;
        wgmma_rs_n128(s, q[0], q[1], q[2], q[3], dk, 0);
        wgmma_rs_n128(s, q[4], q[5], 0, 0, dkb, 1);
        WG_COMMIT();
      }
      WG_WAIT(0);
      fence_regs(s); fence_regs(o);
      if (u + 1 < nun) load_q(q, qthr + ((utile >> (4 * u + 4)) & 15) * 3072);
      exp_pv(s, o, dv, mk);
      WG_COMMIT();
      WG_WAIT(0);
      fence_regs(o);
      if (wg == 1 && u < 2) {
        float4* pp = (float4*)(part + u * 1536) + (tid & 127);
        pp[0] = make_float4(o[0], o[1], o[2], o[3]);
        pp[128] = make_float4(o[4], o[5], o[6], o[7]);
        pp[256] = make_float4(o[8], o[9], o[10], o[11]);
        mbar_arrive(partb + 8 * u);
        if (u == 0) continue;
      }
      if (wt) {
        mbar_wait(flagb, 0);
        fast = sflag[0] != 0;
        if (!fast) break;
        if (wg == 1) continue;
      }
      if (wg != 1 && u == 2) {
        const int pi = wg == 0 ? 1 : 0;
        mbar_wait(partb + 8 * pi, 0);
        const float4* pp = (const float4*)(part + pi * 1536) + (tid & 127);
        const float4 x0 = pp[0], x1 = pp[128], x2 = pp[256];
        o[0] += x0.x; o[1] += x0.y; o[2] += x0.z; o[3] += x0.w; o[4] += x1.x; o[5] += x1.y;
        o[6] += x1.z; o[7] += x1.w; o[8] += x2.x; o[9] += x2.y; o[10] += x2.z; o[11] += x2.w;
      }
      store_o(o, othr + (tile >> 1) * 163840 + (tile & 1) * 8192, oo0, oo1, oo2, lane);
    }
    if ((tid & 127) == 0) STAMP(1, 3 + wg);
    if (!fast) {
#pragma unroll 1
      for (int tile = wg; tile < 8; tile += 3) {
        load_q(q, qthr + tile * 3072);
        if ((lane & 3) >= 2) { q[4] = 0; q[5] = 0; }
        float o[12], m0 = -INFINITY, m1 = -INFINITY;
#pragma unroll
        for (int i = 0; i < 12; i++) o[i] = 0.f;
#pragma unroll 1
        for (int b = 0; b < 16; b++) {
          float s[64];
          WG_FENCE();
          wgmma_rs_n128(s, q[0], q[1], q[2], q[3], dk0 + b * 384, 0);
          wgmma_rs_n128(s, q[4], q[5], 0, 0, dk0b + b * 384, 1);
          WG_COMMIT();
          WG_WAIT(0);
          fence_regs(s);
          float x0 = m0, x1 = m1;
#pragma unroll
          for (int j = 0; j < 16; j++) {
            if ((POLY_MASK >> j) & 1) {
#pragma unroll
              for (int i = 0; i < 4; i++) s[4 * j + i] *= (1.f / 32768.f);
            }
            x0 = fmaxf(x0, fmaxf(s[4 * j], s[4 * j + 1]));
            x1 = fmaxf(x1, fmaxf(s[4 * j + 2], s[4 * j + 3]));
          }
          x0 = fmaxf(x0, __shfl_xor_sync(~0u, x0, 1)); x0 = fmaxf(x0, __shfl_xor_sync(~0u, x0, 2));
          x1 = fmaxf(x1, __shfl_xor_sync(~0u, x1, 1)); x1 = fmaxf(x1, __shfl_xor_sync(~0u, x1, 2));
          const float al0 = ex2(m0 - x0), al1 = ex2(m1 - x1);
          m0 = x0; m1 = x1;
#pragma unroll
          for (int i = 0; i < 12; i++) o[i] *= (i & 2) ? al1 : al0;
          uint32_t p[32];
#pragma unroll
          for (int i = 0; i < 32; i++) {
            const float mm = (i & 1) ? m1 : m0;
            p[i] = pack_bf16(ex2(s[2 * i] - mm), ex2(s[2 * i + 1] - mm));
          }
          fence_regs(o);
          WG_FENCE();
#pragma unroll
          for (int k = 0; k < 8; k++) wgmma_rs_n24(o, p[4 * k], p[4 * k + 1], p[4 * k + 2], p[4 * k + 3], dv0 + b * 384 + k * 48, 1);
          WG_COMMIT();
          WG_WAIT(0);
          fence_regs(o);
        }
        store_o(o, othr + (tile >> 1) * 163840 + (tile & 1) * 8192, oo0, oo1, oo2, lane);
      }
    }
  }
}

constexpr int K3_ST = 4, K3_STAGE = 36864;
constexpr int K3_SMEM = K3_ST * K3_STAGE + 40960 + 20480 + 256;

template <int KT, bool FIRST>
__global__ void __cluster_dims__(2, 1, 1) __launch_bounds__(384, 1)
k3_proj(const __grid_constant__ CUtensorMap tmr, const uint4* __restrict__ aimg, const uint4* __restrict__ wimg) {
  extern __shared__ __align__(1024) uint8_t sm[];
  const uint32_t sbase = smem_u32(sm);
  uint8_t* xch = sm + K3_ST * K3_STAGE;
  uint8_t* stg = sm + K3_ST * K3_STAGE + 40960;
  const uint32_t fullb = smem_u32(stg) + 20480, emptyb = fullb + 8 * K3_ST, resb = emptyb + 8 * K3_ST, xchb = resb + 8;
  const int tid = threadIdx.x, lane = tid & 31;
  const int warp = __shfl_sync(~0u, tid >> 5, 0);
  const int rank = blockIdx.x & 1;
  const int n = blockIdx.x & 7, m = blockIdx.x >> 3;
  const int kt0 = rank * ((KT + 1) / 2), nkt = rank ? KT / 2 : (KT + 1) / 2;
  if (tid == 0) STAMP(FIRST ? 2 : 4, 0);
  if (tid == 0) {
    prefetch_map(&tmr);
    for (int i = 0; i < K3_ST; i++) { mbar_init(fullb + 8 * i, 1); mbar_init(emptyb + 8 * i, 2); }
    mbar_init(resb, 1); mbar_init(xchb, 1);
    mbar_expect(xchb, 40960);
    asm volatile("fence.mbarrier_init.release.cluster;" ::: "memory");
  }
  __syncthreads();
  cluster_arrive();
  if (warp == 0) {
    if (lane == 0) {
      const uint8_t* wk = (const uint8_t*)wimg + (size_t)(n * KT + kt0) * 10240;
      const uint8_t* ws = (const uint8_t*)wimg + (size_t)((n ^ 1) * KT + kt0) * 10240;
      const uint8_t* ab = (const uint8_t*)aimg + (size_t)(m * KT + kt0) * 16384;
      for (int i = 0; i < K3_ST; i++) {
        mbar_expect(fullb + 8 * i, K3_STAGE);
        bulk_ld(sbase + i * K3_STAGE + 16384, wk + i * 10240, 10240, fullb + 8 * i);
        bulk_ld(sbase + i * K3_STAGE + 26624, ws + i * 10240, 10240, fullb + 8 * i);
      }
      if (FIRST) {
        mbar_expect(resb, 20480);
        tma2d(smem_u32(stg), &tmr, n * 80, m * 128, resb);
        tma2d(smem_u32(stg) + 10240, &tmr, n * 80, m * 128 + 64, resb);
      }
      pdl_wait();
      pdl_trigger();
      for (int i = 0; i < nkt; i++) {
        const int s = i % K3_ST;
        const uint32_t sa = sbase + s * K3_STAGE;
        if (i >= K3_ST) {
          mbar_wait(emptyb + 8 * s, ((i / K3_ST) - 1) & 1);
          mbar_expect(fullb + 8 * s, K3_STAGE);
        }
        bulk_ld(sa, ab + i * 16384, 16384, fullb + 8 * s);
        if (i >= K3_ST) {
          bulk_ld(sa + 16384, wk + i * 10240, 10240, fullb + 8 * s);
          bulk_ld(sa + 26624, ws + i * 10240, 10240, fullb + 8 * s);
        }
      }
    }
    __syncwarp();
    cluster_wait();
  } else if (warp >= 4) {
    const int cw = warp - 4, wg = cw >> 2;
    const int g = lane >> 2, c = lane & 3;
    uint8_t* himg = (uint8_t*)g_h + (size_t)m * 163840 + cw * 2048 + g * 16 + c * 4;
    uint32_t rv[20];
    if (!FIRST) {
#pragma unroll
      for (int j = 0; j < 10; j++) {
        rv[2 * j] = __ldcg((const uint32_t*)(himg + img_off(n * 10 + j)));
        rv[2 * j + 1] = __ldcg((const uint32_t*)(himg + img_off(n * 10 + j) + 1024));
      }
    }
    float acc[80];
    const uint64_t da0 = mkdesc(sbase + wg * 8192, 128, 1024, 0);
    const uint64_t db0 = mkdesc(sbase + 16384, 128, 1024, 0);
#pragma unroll 1
    for (int i = 0; i < nkt; i++) {
      const int s = i % K3_ST;
      mbar_wait(fullb + 8 * s, (i / K3_ST) & 1);
      if (i == 0 && tid == 128) STAMP(FIRST ? 2 : 4, 2);
      const uint64_t da = da0 + s * (K3_STAGE >> 4), db = db0 + s * (K3_STAGE >> 4);
      WG_FENCE();
#pragma unroll
      for (int k = 0; k < 4; k++) wgmma_ss_n160(acc, da + k * 16, db + k * 16, (i | k) != 0);
      WG_COMMIT();
      if (i > 0) {
        WG_WAIT(1);
        if ((tid & 127) == 0) mbar_arrive(emptyb + 8 * ((i - 1) % K3_ST));
      }
    }
    uint8_t* sp = stg + (cw * 16 + g) * 160 + c * 4;
    if (FIRST) {
      mbar_wait(resb, 0);
#pragma unroll
      for (int j = 0; j < 10; j++) {
        rv[2 * j] = *(const uint32_t*)(sp + j * 16);
        rv[2 * j + 1] = *(const uint32_t*)(sp + 1280 + j * 16);
      }
    }
    cluster_wait();
    const uint32_t rx = mapa(smem_u32(xch) + (tid - 128) * 16, rank ^ 1), rb = mapa(xchb, rank ^ 1);
    WG_WAIT(0);
    fence_regs(acc);
    if (tid == 128) STAMP(FIRST ? 2 : 4, 3);
#pragma unroll
    for (int j = 0; j < 10; j++) st_async4(rx + j * 4096, acc[40 + 4 * j], acc[41 + 4 * j], acc[42 + 4 * j], acc[43 + 4 * j], rb);
#pragma unroll
    for (int j = 0; j < 10; j++) {
      acc[4 * j] += bf_lo(rv[2 * j]); acc[4 * j + 1] += bf_hi(rv[2 * j]);
      acc[4 * j + 2] += bf_lo(rv[2 * j + 1]); acc[4 * j + 3] += bf_hi(rv[2 * j + 1]);
    }
    mbar_wait(xchb, 0);
    if (tid == 128) STAMP(FIRST ? 2 : 4, 5);
    float s0 = 0.f, s1 = 0.f;
#pragma unroll
    for (int j = 0; j < 10; j++) {
      const float4 p = *(const float4*)(xch + (tid - 128) * 16 + j * 4096);
      acc[4 * j] += p.x; acc[4 * j + 1] += p.y; acc[4 * j + 2] += p.z; acc[4 * j + 3] += p.w;
      if (FIRST) {
        *(uint32_t*)(himg + img_off(n * 10 + j)) = pack_bf16(acc[4 * j], acc[4 * j + 1]);
        *(uint32_t*)(himg + img_off(n * 10 + j) + 1024) = pack_bf16(acc[4 * j + 2], acc[4 * j + 3]);
        s0 += acc[4 * j] + acc[4 * j + 1]; s1 += acc[4 * j + 2] + acc[4 * j + 3];
      } else {
        *(uint32_t*)(sp + j * 16) = pack_bf16(acc[4 * j], acc[4 * j + 1]);
        *(uint32_t*)(sp + 1280 + j * 16) = pack_bf16(acc[4 * j + 2], acc[4 * j + 3]);
      }
    }
    if (FIRST) {
      s0 += __shfl_xor_sync(~0u, s0, 1); s0 += __shfl_xor_sync(~0u, s0, 2);
      s1 += __shfl_xor_sync(~0u, s1, 1); s1 += __shfl_xor_sync(~0u, s1, 2);
      s0 *= (1.f / 80.f); s1 *= (1.f / 80.f);
      float q0 = 0.f, q1 = 0.f;
#pragma unroll
      for (int j = 0; j < 10; j++) {
        float d;
        d = acc[4 * j] - s0; q0 = fmaf(d, d, q0); d = acc[4 * j + 1] - s0; q0 = fmaf(d, d, q0);
        d = acc[4 * j + 2] - s1; q1 = fmaf(d, d, q1); d = acc[4 * j + 3] - s1; q1 = fmaf(d, d, q1);
      }
      q0 += __shfl_xor_sync(~0u, q0, 1); q0 += __shfl_xor_sync(~0u, q0, 2);
      q1 += __shfl_xor_sync(~0u, q1, 1); q1 += __shfl_xor_sync(~0u, q1, 2);
      if (c < 2) g_hpart[n * S_ + m * 128 + cw * 16 + g + c * 8] = c ? make_float2(s1, q1) : make_float2(s0, q0);
    } else {
      fence_async();
      bar_sync(1 + wg, 128);
      if ((tid & 127) == 0) {
        tma2d_st(&tmr, n * 80, m * 128 + wg * 64, smem_u32(stg) + wg * 10240);
        bulk_commit_wait();
      }
      __syncwarp();
    }
    if (tid == 128) STAMP(FIRST ? 2 : 4, 4);
  } else {
    cluster_wait();
  }
}

constexpr int K4_ST = 3, K4_STAGE = 71680;
constexpr int K4_SMEM = K4_ST * K4_STAGE + 1728 + 1024 + 64;

__global__ void __cluster_dims__(2, 1, 1) __launch_bounds__(256, 1)
k4_ffn1() {
  extern __shared__ __align__(1024) uint8_t sm[];
  float* cs = (float*)(sm + K4_ST * K4_STAGE);
  float2* rowst = (float2*)(sm + K4_ST * K4_STAGE + 1728);
  const uint32_t sbase = smem_u32(sm);
  const uint32_t fullb = sbase + K4_ST * K4_STAGE + 2752, emptyb = fullb + 8 * K4_ST;
  const int tid = threadIdx.x, lane = tid & 31;
  const int warp = __shfl_sync(~0u, tid >> 5, 0);
  const int rank = blockIdx.x & 1, cl = blockIdx.x >> 1;
  const int n = cl & 7, m = (cl >> 3) * 2 + rank;
  const uint8_t* wb = (const uint8_t*)g_wgu + (size_t)n * 10 * 55296 + rank * 27648;
  const uint8_t* ab = (const uint8_t*)g_h + (size_t)m * 163840;
  if (tid == 0) STAMP(3, 0);
  if (tid == 0) {
    for (int i = 0; i < K4_ST; i++) { mbar_init(fullb + 8 * i, 1); mbar_init(emptyb + 8 * i, 4); }
    asm volatile("fence.mbarrier_init.release.cluster;" ::: "memory");
  }
  __syncthreads();
  cluster_arrive();
  const float cs0 = __ldcg(&g_csgu[(tid >= 216 ? F_ - 216 : 0) + n * 216 + tid]);
  const float cs1 = tid < 176 ? __ldcg(&g_csgu[F_ - 216 + n * 216 + 256 + tid]) : 0.f;
  cluster_wait();
  if (tid == 0) {
    for (int kt = 0; kt < K4_ST; kt++) mbar_expect(fullb + 8 * kt, K4_STAGE);
    bulk_ld_mc(sbase + 16384 + rank * 27648, wb, 27648, fullb);
  }
  pdl_wait();
  pdl_trigger();
  if (tid == 128) STAMP(3, 1);
  if (tid == 0) {
    bulk_ld(sbase, ab, 16384, fullb);
    for (int kt = 1; kt < K4_ST; kt++) {
      bulk_ld(sbase + kt * K4_STAGE, ab + kt * 16384, 16384, fullb + 8 * kt);
      bulk_ld_mc(sbase + kt * K4_STAGE + 16384 + rank * 27648, wb + kt * 55296, 27648, fullb + 8 * kt);
    }
  }
  if (tid >= 128) {
    const int r = tid - 128;
    float2 p[8];
#pragma unroll
    for (int i = 0; i < 8; i++) p[i] = __ldcg(&g_hpart[i * S_ + m * 128 + r]);
    float mean = 0.f, m2 = 0.f;
#pragma unroll
    for (int i = 0; i < 8; i++) { mean += p[i].x; m2 += p[i].y; }
    mean *= 0.125f;
#pragma unroll
    for (int i = 0; i < 8; i++) { const float d = p[i].x - mean; m2 = fmaf(80.f * d, d, m2); }
    rowst[r] = make_float2(-mean, __frcp_rn(m2 * (1.f / D_) + 1e-5f));
  }
  cs[tid] = cs0;
  if (tid < 176) cs[256 + tid] = cs1;
  __syncwarp();
  float ag[108], au[108];
  const uint64_t da0 = mkdesc(sbase + (warp >> 2) * 8192, 128, 1024, 0);
  const uint64_t db0 = mkdesc(sbase + 16384, 128, 1024, 0);
#pragma unroll 1
  for (int kt = 0; kt < 10; kt++) {
    const int s = kt % K4_ST;
    mbar_wait(fullb + 8 * s, (kt / K4_ST) & 1);
    if (kt == 0 && tid == 128) STAMP(3, 2);
    const uint64_t da = da0 + s * (K4_STAGE >> 4), db = db0 + s * (K4_STAGE >> 4);
    WG_FENCE();
#pragma unroll
    for (int k = 0; k < 4; k++) {
      wgmma_ss_n216(ag, da + k * 16, db + k * 16, (kt | k) != 0);
      wgmma_ss_n216(au, da + k * 16, db + 1728 + k * 16, (kt | k) != 0);
    }
    WG_COMMIT();
    if (kt > 0 && kt - 1 + K4_ST < 10) {
      WG_WAIT(1);
      const int sp = (kt - 1) % K4_ST;
      if ((tid & 127) < 2) mbar_arrive_cta(emptyb + 8 * sp, tid & 1);
      if (tid == 0) {
        const uint32_t sa = sbase + sp * K4_STAGE;
        mbar_wait(emptyb + 8 * sp, ((kt - 1) / K4_ST) & 1);
        mbar_expect(fullb + 8 * sp, K4_STAGE);
        bulk_ld_mc(sa + 16384 + rank * 27648, wb + (kt - 1 + K4_ST) * 55296, 27648, fullb + 8 * sp);
        bulk_ld(sa, ab + (kt - 1 + K4_ST) * 16384, 16384, fullb + 8 * sp);
      }
      __syncwarp();
    }
  }
  WG_WAIT(0);
  fence_regs(ag); fence_regs(au);
  if (tid == 128) STAMP(3, 3);
  __syncthreads();
  const int g = lane >> 2, c = lane & 3;
  const float2 st0 = rowst[warp * 16 + g], st1 = rowst[warp * 16 + g + 8];
  uint8_t* dst = (uint8_t*)g_hh + (size_t)m * 27 * 16384 + warp * 2048 + g * 16 + c * 4;
#pragma unroll
  for (int j = 0; j < 27; j++) {
    const float2 cg = *(const float2*)&cs[j * 8 + c * 2], cu = *(const float2*)&cs[216 + j * 8 + c * 2];
    const float h0 = fmaf(st0.x, cg.x, ag[4 * j]) * st0.y * fmaf(st0.x, cu.x, au[4 * j]);
    const float h1 = fmaf(st0.x, cg.y, ag[4 * j + 1]) * st0.y * fmaf(st0.x, cu.y, au[4 * j + 1]);
    const float h2 = fmaf(st1.x, cg.x, ag[4 * j + 2]) * st1.y * fmaf(st1.x, cu.x, au[4 * j + 2]);
    const float h3 = fmaf(st1.x, cg.y, ag[4 * j + 3]) * st1.y * fmaf(st1.x, cu.y, au[4 * j + 3]);
    *(uint32_t*)(dst + img_off(n * 27 + j)) = pack_bf16(h0, h1);
    *(uint32_t*)(dst + img_off(n * 27 + j) + 1024) = pack_bf16(h2, h3);
  }
  if (tid == 128) STAMP(3, 4);
  cluster_sync_relaxed();
}

typedef CUresult (*EncodeFn)(CUtensorMap*, CUtensorMapDataType, cuuint32_t, void*, const cuuint64_t*, const cuuint64_t*,
                             const cuuint32_t*, const cuuint32_t*, CUtensorMapInterleave, CUtensorMapSwizzle,
                             CUtensorMapL2promotion, CUtensorMapFloatOOBfill);

static CUtensorMap make_map(EncodeFn enc, const void* p, uint64_t inner, uint64_t outer, uint32_t box_inner,
                            uint32_t box_outer, CUtensorMapSwizzle swz) {
  CUtensorMap m;
  cuuint64_t gd[2] = {inner, outer};
  cuuint64_t gs[1] = {inner * 2};
  cuuint32_t bd[2] = {box_inner, box_outer};
  cuuint32_t es[2] = {1, 1};
  enc(&m, CU_TENSOR_MAP_DATA_TYPE_BFLOAT16, 2, (void*)p, gd, gs, bd, es, CU_TENSOR_MAP_INTERLEAVE_NONE, swz,
      CU_TENSOR_MAP_L2_PROMOTION_L2_256B, CU_TENSOR_MAP_FLOAT_OOB_FILL_NONE);
  return m;
}

template <typename... KArgs, typename... Args>
static void launch(void (*k)(KArgs...), int threads, int smem, bool pdl, Args... args) {
  cudaLaunchConfig_t cfg = {};
  cfg.gridDim = dim3(128);
  cfg.blockDim = dim3(threads);
  cfg.dynamicSmemBytes = smem;
  cfg.stream = cudaStreamPerThread;
  cudaLaunchAttribute at[1];
  at[0].id = cudaLaunchAttributeProgrammaticStreamSerialization;
  at[0].val.programmaticStreamSerializationAllowed = 1;
  cfg.attrs = at;
  cfg.numAttrs = pdl ? 1 : 0;
  cudaLaunchKernelEx(&cfg, k, KArgs(args)...);
}

extern "C" void kernel_launch(void* const* d_in, const int* in_sizes, int n_in, void* d_out, int out_size) {
  const bf16* x = (const bf16*)d_in[0];
  const bf16* wqkv = (const bf16*)d_in[1];
  const bf16* wo = (const bf16*)d_in[2];
  const bf16* wg = (const bf16*)d_in[4];
  const bf16* wu = (const bf16*)d_in[5];
  const bf16* wd = (const bf16*)d_in[6];

  static EncodeFn enc = nullptr;
  static void *p_o, *p_hh, *p_wo, *p_wd;
  if (!enc) {
    void* fn = nullptr;
    cudaDriverEntryPointQueryResult qr;
    cudaGetDriverEntryPoint("cuTensorMapEncodeTiled", &fn, cudaEnableDefault, &qr);
    enc = (EncodeFn)fn;
    cudaGetSymbolAddress(&p_o, g_o); cudaGetSymbolAddress(&p_hh, g_hh);
    cudaGetSymbolAddress(&p_wo, g_wo); cudaGetSymbolAddress(&p_wd, g_wd);
    cudaFuncSetAttribute(k1_qkv, cudaFuncAttributeMaxDynamicSharedMemorySize, K1_SMEM);
    cudaFuncSetAttribute(k2_attn, cudaFuncAttributeMaxDynamicSharedMemorySize, K2_SMEM + 512);
    cudaFuncSetAttribute(k3_proj<10, true>, cudaFuncAttributeMaxDynamicSharedMemorySize, K3_SMEM);
    cudaFuncSetAttribute(k3_proj<27, false>, cudaFuncAttributeMaxDynamicSharedMemorySize, K3_SMEM);
    cudaFuncSetAttribute(k4_ffn1, cudaFuncAttributeMaxDynamicSharedMemorySize, K4_SMEM);
  }
  const CUtensorMap tmx = make_map(enc, x, D_, S_, 64, 128, CU_TENSOR_MAP_SWIZZLE_128B);
  const CUtensorMap tmw = make_map(enc, wqkv, 3 * D_, D_, 32, 64, CU_TENSOR_MAP_SWIZZLE_64B);
  const CUtensorMap tmxr = make_map(enc, x, D_, S_, 80, 64, CU_TENSOR_MAP_SWIZZLE_NONE);
  const CUtensorMap tmout = make_map(enc, d_out, D_, S_, 80, 64, CU_TENSOR_MAP_SWIZZLE_NONE);

  launch(k1_qkv, 384, K1_SMEM, false, tmx, tmw, x, wqkv, wo);
  launch(k2_attn, 512, K2_SMEM + 512, true, wg, wu, wd, 0x007f007fu);
  launch(k3_proj<10, true>, 384, K3_SMEM, true, tmxr, (const uint4*)p_o, (const uint4*)p_wo);
  launch(k4_ffn1, 256, K4_SMEM, true);
  launch(k3_proj<27, false>, 384, K3_SMEM, true, tmout, (const uint4*)p_hh, (const uint4*)p_wd);
}
```

```cpp
#include <cuda_runtime.h>
#include <cuda_bf16.h>
#include <cuda.h>
#include <stdint.h>

typedef __nv_bfloat16 bf16;

constexpr int S_ = 2048, D_ = 640, F_ = 1728;
constexpr int HEAD_IMG = 98304;
constexpr uint32_t POLY_MASK = 0xBBAB;
constexpr float QSCALE = 0.22360679774997896f * 1.4426950408889634f;

__device__ __align__(1024) uint4 g_qkv[96 * HEAD_IMG / 16];
__device__ __align__(1024) uint4 g_o[S_ * D_ / 8];
__device__ __align__(1024) uint4 g_h[S_ * D_ / 8];
__device__ __align__(1024) uint4 g_hh[S_ * F_ / 8];
__device__ __align__(1024) uint4 g_wo[D_ * D_ / 8];
__device__ __align__(1024) uint4 g_wgu[2 * D_ * F_ / 8];
__device__ __align__(1024) uint4 g_wd[F_ * D_ / 8];
__device__ float2 g_rowstat[S_];
__device__ float g_cpart[16 * 2048];
__device__ float g_csgu[2 * F_];
__device__ float2 g_hpart[8 * S_];
__device__ unsigned g_cnt[24 * 32];

#define STAMP(k, i)
__device__ __forceinline__ uint32_t smem_u32(const void* p) { return (uint32_t)__cvta_generic_to_shared(p); }
__device__ __forceinline__ void mbar_init(uint32_t a, uint32_t c) {
  asm volatile("mbarrier.init.shared::cta.b64 [%0], %1;" ::"r"(a), "r"(c) : "memory");
}
__device__ __forceinline__ void mbar_expect(uint32_t a, uint32_t bytes) {
  asm volatile("mbarrier.arrive.expect_tx.shared::cta.b64 _, [%0], %1;" ::"r"(a), "r"(bytes) : "memory");
}
__device__ __forceinline__ void mbar_arrive(uint32_t a) {
  asm volatile("mbarrier.arrive.shared::cta.b64 _, [%0];" ::"r"(a) : "memory");
}
__device__ __forceinline__ void mbar_arrive_cta(uint32_t a, uint32_t cta) {
  asm volatile("{\n.reg .b32 r;\nmapa.shared::cluster.u32 r, %0, %1;\n"
               "mbarrier.arrive.shared::cluster.b64 _, [r];\n}" ::"r"(a), "r"(cta) : "memory");
}
__device__ __forceinline__ bool mbar_try(uint32_t a, uint32_t ph) {
  uint32_t ok;
  asm volatile("{\n.reg .pred p;\nmbarrier.try_wait.parity.shared::cta.b64 p, [%1], %2;\nselp.u32 %0, 1, 0, p;\n}"
               : "=r"(ok) : "r"(a), "r"(ph) : "memory");
  return ok;
}
__device__ __noinline__ void wait_timeout() { __trap(); }
__device__ __forceinline__ void mbar_wait(uint32_t a, uint32_t ph) {
  if (mbar_try(a, ph)) return;
  uint32_t it = 0;
  while (!mbar_try(a, ph)) if (++it > (1u << 22)) wait_timeout();
}
__device__ __forceinline__ void tma2d(uint32_t dst, const CUtensorMap* m, int c0, int c1, uint32_t bar) {
  asm volatile("cp.async.bulk.tensor.2d.shared::cluster.global.mbarrier::complete_tx::bytes [%0], [%1, {%3, %4}], [%2];"
               ::"r"(dst), "l"(m), "r"(bar), "r"(c0), "r"(c1) : "memory");
}
__device__ __forceinline__ void tma2d_mc(uint32_t dst, const CUtensorMap* m, int c0, int c1, uint32_t bar) {
  asm volatile("cp.async.bulk.tensor.2d.shared::cluster.global.mbarrier::complete_tx::bytes.multicast::cluster "
               "[%0], [%1, {%3, %4}], [%2], %5;"
               ::"r"(dst), "l"(m), "r"(bar), "r"(c0), "r"(c1), "h"((uint16_t)3) : "memory");
}
__device__ __forceinline__ void bulk_ld(uint32_t dst, const void* src, uint32_t bytes, uint32_t bar) {
  asm volatile("cp.async.bulk.shared::cluster.global.mbarrier::complete_tx::bytes [%0], [%1], %2, [%3];"
               ::"r"(dst), "l"(src), "r"(bytes), "r"(bar) : "memory");
}
__device__ __forceinline__ void bulk_ld_mc(uint32_t dst, const void* src, uint32_t bytes, uint32_t bar) {
  asm volatile("cp.async.bulk.shared::cluster.global.mbarrier::complete_tx::bytes.multicast::cluster "
               "[%0], [%1], %2, [%3], %4;"
               ::"r"(dst), "l"(src), "r"(bytes), "r"(bar), "h"((uint16_t)3) : "memory");
}
__device__ __forceinline__ void cluster_arrive() { asm volatile("barrier.cluster.arrive.relaxed.aligned;" ::: "memory"); }
__device__ __forceinline__ void cluster_wait() { asm volatile("barrier.cluster.wait.aligned;" ::: "memory"); }
__device__ __forceinline__ void bulk_st(void* dst, uint32_t src, uint32_t bytes) {
  asm volatile("cp.async.bulk.global.shared::cta.bulk_group [%0], [%1], %2;" ::"l"(dst), "r"(src), "r"(bytes) : "memory");
}
__device__ __forceinline__ void tma2d_st(const CUtensorMap* m, int c0, int c1, uint32_t src) {
  asm volatile("cp.async.bulk.tensor.2d.global.shared::cta.bulk_group [%0, {%2, %3}], [%1];"
               ::"l"(m), "r"(src), "r"(c0), "r"(c1) : "memory");
}
__device__ __forceinline__ void bulk_commit_wait() {
  asm volatile("cp.async.bulk.commit_group;\ncp.async.bulk.wait_group.read 0;" ::: "memory");
}
__device__ __forceinline__ uint32_t mapa(uint32_t a, uint32_t cta) {
  uint32_t r;
  asm("mapa.shared::cluster.u32 %0, %1, %2;" : "=r"(r) : "r"(a), "r"(cta));
  return r;
}
__device__ __forceinline__ void st_async4(uint32_t dst, float a, float b, float c, float d, uint32_t bar) {
  asm volatile("st.async.shared::cluster.mbarrier::complete_tx::bytes.v4.f32 [%0], {%1, %2, %3, %4}, [%5];"
               ::"r"(dst), "f"(a), "f"(b), "f"(c), "f"(d), "r"(bar) : "memory");
}
__device__ __forceinline__ void fence_async() { asm volatile("fence.proxy.async.shared::cta;" ::: "memory"); }
__device__ __forceinline__ void prefetch_map(const CUtensorMap* m) {
  asm volatile("prefetch.tensormap [%0];" ::"l"(m) : "memory");
}
__device__ __forceinline__ void cluster_sync_relaxed() {
  __syncwarp();
  asm volatile("barrier.cluster.arrive.relaxed.aligned;\nbarrier.cluster.wait.aligned;" ::: "memory");
}
__device__ __forceinline__ void pdl_wait() { asm volatile("griddepcontrol.wait;" ::: "memory"); }
__device__ __forceinline__ void pdl_trigger() { asm volatile("griddepcontrol.launch_dependents;" ::: "memory"); }
__device__ __forceinline__ void bar_sync(int id, int n) { asm volatile("bar.sync %0, %1;" ::"r"(id), "r"(n) : "memory"); }
__device__ __forceinline__ void bar_arrive(int id, int n) { asm volatile("bar.arrive %0, %1;" ::"r"(id), "r"(n) : "memory"); }
#define WG_FENCE() asm volatile("wgmma.fence.sync.aligned;" ::: "memory")
#define WG_COMMIT() asm volatile("wgmma.commit_group.sync.aligned;" ::: "memory")
#define WG_WAIT(n) asm volatile("wgmma.wait_group.sync.aligned %0;" ::"n"(n) : "memory")
__device__ __forceinline__ uint64_t mkdesc(uint32_t addr, uint32_t lbo, uint32_t sbo, uint32_t sw) {
  return (uint64_t)((addr & 0x3FFFF) >> 4) | ((uint64_t)(lbo >> 4) << 16) | ((uint64_t)(sbo >> 4) << 32) |
         ((uint64_t)sw << 62);
}
template <int N> __device__ __forceinline__ void fence_regs(float (&r)[N]) {
#pragma unroll
  for (int i = 0; i < N; i++) asm volatile("" : "+f"(r[i])::"memory");
}
__device__ __forceinline__ uint32_t pack_bf16(float lo, float hi) {
  uint32_t r;
  asm("cvt.rn.bf16x2.f32 %0, %1, %2;" : "=r"(r) : "f"(hi), "f"(lo));
  return r;
}
__device__ __forceinline__ float bf_lo(uint32_t v) { return __uint_as_float(v << 16); }
__device__ __forceinline__ float bf_hi(uint32_t v) { return __uint_as_float(v & 0xffff0000u); }
__device__ __forceinline__ float ex2(float x) {
  float y;
  asm("ex2.approx.ftz.f32 %0, %1;" : "=f"(y) : "f"(x));
  return y;
}
__device__ __forceinline__ uint4 ldg_nc(const void* p) {
  uint4 v;
  asm volatile("ld.global.nc.L1::no_allocate.v4.u32 {%0, %1, %2, %3}, [%4];"
               : "=r"(v.x), "=r"(v.y), "=r"(v.z), "=r"(v.w) : "l"(p));
  return v;
}

__device__ __forceinline__ void wgmma_ss_n256(float (&d)[128], uint64_t da, uint64_t db, int sd) {
  asm volatile("{\n.reg .pred p;\nsetp.ne.b32 p, %130, 0;\n"
      "wgmma.mma_async.sync.aligned.m64n256k16.f32.bf16.bf16 {"
      "%0, %1, %2, %3, %4, %5, %6, %7, %8, %9, %10, %11, %12, %13, %14, %15, "
      "%16, %17, %18, %19, %20, %21, %22, %23, %24, %25, %26, %27, %28, %29, %30, %31, "
      "%32, %33, %34, %35, %36, %37, %38, %39, %40, %41, %42, %43, %44, %45, %46, %47, "
      "%48, %49, %50, %51, %52, %53, %54, %55, %56, %57, %58, %59, %60, %61, %62, %63, "
      "%64, %65, %66, %67, %68, %69, %70, %71, %72, %73, %74, %75, %76, %77, %78, %79, "
      "%80, %81, %82, %83, %84, %85, %86, %87, %88, %89, %90, %91, %92, %93, %94, %95, "
      "%96, %97, %98, %99, %100, %101, %102, %103, %104, %105, %106, %107, %108, %109, %110, %111, "
      "%112, %113, %114, %115, %116, %117, %118, %119, %120, %121, %122, %123, %124, %125, %126, %127"
      "}, %128, %129, p, 1, 1, 0, 1;\n}\n"
    : "+f"(d[0]), "+f"(d[1]), "+f"(d[2]), "+f"(d[3]), "+f"(d[4]), "+f"(d[5]), "+f"(d[6]), "+f"(d[7]),
      "+f"(d[8]), "+f"(d[9]), "+f"(d[10]), "+f"(d[11]), "+f"(d[12]), "+f"(d[13]), "+f"(d[14]), "+f"(d[15]),
      "+f"(d[16]), "+f"(d[17]), "+f"(d[18]), "+f"(d[19]), "+f"(d[20]), "+f"(d[21]), "+f"(d[22]), "+f"(d[23]),
      "+f"(d[24]), "+f"(d[25]), "+f"(d[26]), "+f"(d[27]), "+f"(d[28]), "+f"(d[29]), "+f"(d[30]), "+f"(d[31]),
      "+f"(d[32]), "+f"(d[33]), "+f"(d[34]), "+f"(d[35]), "+f"(d[36]), "+f"(d[37]), "+f"(d[38]), "+f"(d[39]),
      "+f"(d[40]), "+f"(d[41]), "+f"(d[42]), "+f"(d[43]), "+f"(d[44]), "+f"(d[45]), "+f"(d[46]), "+f"(d[47]),
      "+f"(d[48]), "+f"(d[49]), "+f"(d[50]), "+f"(d[51]), "+f"(d[52]), "+f"(d[53]), "+f"(d[54]), "+f"(d[55]),
      "+f"(d[56]), "+f"(d[57]), "+f"(d[58]), "+f"(d[59]), "+f"(d[60]), "+f"(d[61]), "+f"(d[62]), "+f"(d[63]),
      "+f"(d[64]), "+f"(d[65]), "+f"(d[66]), "+f"(d[67]), "+f"(d[68]), "+f"(d[69]), "+f"(d[70]), "+f"(d[71]),
      "+f"(d[72]), "+f"(d[73]), "+f"(d[74]), "+f"(d[75]), "+f"(d[76]), "+f"(d[77]), "+f"(d[78]), "+f"(d[79]),
      "+f"(d[80]), "+f"(d[81]), "+f"(d[82]), "+f"(d[83]), "+f"(d[84]), "+f"(d[85]), "+f"(d[86]), "+f"(d[87]),
      "+f"(d[88]), "+f"(d[89]), "+f"(d[90]), "+f"(d[91]), "+f"(d[92]), "+f"(d[93]), "+f"(d[94]), "+f"(d[95]),
      "+f"(d[96]), "+f"(d[97]), "+f"(d[98]), "+f"(d[99]), "+f"(d[100]), "+f"(d[101]), "+f"(d[102]), "+f"(d[103]),
      "+f"(d[104]), "+f"(d[105]), "+f"(d[106]), "+f"(d[107]), "+f"(d[108]), "+f"(d[109]), "+f"(d[110]), "+f"(d[111]),
      "+f"(d[112]), "+f"(d[113]), "+f"(d[114]), "+f"(d[115]), "+f"(d[116]), "+f"(d[117]), "+f"(d[118]), "+f"(d[119]),
      "+f"(d[120]), "+f"(d[121]), "+f"(d[122]), "+f"(d[123]), "+f"(d[124]), "+f"(d[125]), "+f"(d[126]), "+f"(d[127])
    : "l"(da), "l"(db), "r"(sd));
}
__device__ __forceinline__ void wgmma_ss_n216(float (&d)[108], uint64_t da, uint64_t db, int sd) {
  asm volatile("{\n.reg .pred p;\nsetp.ne.b32 p, %110, 0;\n"
      "wgmma.mma_async.sync.aligned.m64n216k16.f32.bf16.bf16 {"
      "%0, %1, %2, %3, %4, %5, %6, %7, %8, %9, %10, %11, %12, %13, %14, %15, "
      "%16, %17, %18, %19, %20, %21, %22, %23, %24, %25, %26, %27, %28, %29, %30, %31, "
      "%32, %33, %34, %35, %36, %37, %38, %39, %40, %41, %42, %43, %44, %45, %46, %47, "
      "%48, %49, %50, %51, %52, %53, %54, %55, %56, %57, %58, %59, %60, %61, %62, %63, "
      "%64, %65, %66, %67, %68, %69, %70, %71, %72, %73, %74, %75, %76, %77, %78, %79, "
      "%80, %81, %82, %83, %84, %85, %86, %87, %88, %89, %90, %91, %92, %93, %94, %95, "
      "%96, %97, %98, %99, %100, %101, %102, %103, %104, %105, %106, %107"
      "}, %108, %109, p, 1, 1, 0, 1;\n}\n"
    : "+f"(d[0]), "+f"(d[1]), "+f"(d[2]), "+f"(d[3]), "+f"(d[4]), "+f"(d[5]), "+f"(d[6]), "+f"(d[7]),
      "+f"(d[8]), "+f"(d[9]), "+f"(d[10]), "+f"(d[11]), "+f"(d[12]), "+f"(d[13]), "+f"(d[14]), "+f"(d[15]),
      "+f"(d[16]), "+f"(d[17]), "+f"(d[18]), "+f"(d[19]), "+f"(d[20]), "+f"(d[21]), "+f"(d[22]), "+f"(d[23]),
      "+f"(d[24]), "+f"(d[25]), "+f"(d[26]), "+f"(d[27]), "+f"(d[28]), "+f"(d[29]), "+f"(d[30]), "+f"(d[31]),
      "+f"(d[32]), "+f"(d[33]), "+f"(d[34]), "+f"(d[35]), "+f"(d[36]), "+f"(d[37]), "+f"(d[38]), "+f"(d[39]),
      "+f"(d[40]), "+f"(d[41]), "+f"(d[42]), "+f"(d[43]), "+f"(d[44]), "+f"(d[45]), "+f"(d[46]), "+f"(d[47]),
      "+f"(d[48]), "+f"(d[49]), "+f"(d[50]), "+f"(d[51]), "+f"(d[52]), "+f"(d[53]), "+f"(d[54]), "+f"(d[55]),
      "+f"(d[56]), "+f"(d[57]), "+f"(d[58]), "+f"(d[59]), "+f"(d[60]), "+f"(d[61]), "+f"(d[62]), "+f"(d[63]),
      "+f"(d[64]), "+f"(d[65]), "+f"(d[66]), "+f"(d[67]), "+f"(d[68]), "+f"(d[69]), "+f"(d[70]), "+f"(d[71]),
      "+f"(d[72]), "+f"(d[73]), "+f"(d[74]), "+f"(d[75]), "+f"(d[76]), "+f"(d[77]), "+f"(d[78]), "+f"(d[79]),
      "+f"(d[80]), "+f"(d[81]), "+f"(d[82]), "+f"(d[83]), "+f"(d[84]), "+f"(d[85]), "+f"(d[86]), "+f"(d[87]),
      "+f"(d[88]), "+f"(d[89]), "+f"(d[90]), "+f"(d[91]), "+f"(d[92]), "+f"(d[93]), "+f"(d[94]), "+f"(d[95]),
      "+f"(d[96]), "+f"(d[97]), "+f"(d[98]), "+f"(d[99]), "+f"(d[100]), "+f"(d[101]), "+f"(d[102]), "+f"(d[103]),
      "+f"(d[104]), "+f"(d[105]), "+f"(d[106]), "+f"(d[107])
    : "l"(da), "l"(db), "r"(sd));
}
__device__ __forceinline__ void wgmma_ss_n160(float (&d)[80], uint64_t da, uint64_t db, int sd) {
  asm volatile("{\n.reg .pred p;\nsetp.ne.b32 p, %82, 0;\n"
      "wgmma.mma_async.sync.aligned.m64n160k16.f32.bf16.bf16 {"
      "%0, %1, %2, %3, %4, %5, %6, %7, %8, %9, %10, %11, %12, %13, %14, %15, "
      "%16, %17, %18, %19, %20, %21, %22, %23, %24, %25, %26, %27, %28, %29, %30, %31, "
      "%32, %33, %34, %35, %36, %37, %38, %39, %40, %41, %42, %43, %44, %45, %46, %47, "
      "%48, %49, %50, %51, %52, %53, %54, %55, %56, %57, %58, %59, %60, %61, %62, %63, "
      "%64, %65, %66, %67, %68, %69, %70, %71, %72, %73, %74, %75, %76, %77, %78, %79"
      "}, %80, %81, p, 1, 1, 0, 1;\n}\n"
    : "+f"(d[0]), "+f"(d[1]), "+f"(d[2]), "+f"(d[3]), "+f"(d[4]), "+f"(d[5]), "+f"(d[6]), "+f"(d[7]),
      "+f"(d[8]), "+f"(d[9]), "+f"(d[10]), "+f"(d[11]), "+f"(d[12]), "+f"(d[13]), "+f"(d[14]), "+f"(d[15]),
      "+f"(d[16]), "+f"(d[17]), "+f"(d[18]), "+f"(d[19]), "+f"(d[20]), "+f"(d[21]), "+f"(d[22]), "+f"(d[23]),
      "+f"(d[24]), "+f"(d[25]), "+f"(d[26]), "+f"(d[27]), "+f"(d[28]), "+f"(d[29]), "+f"(d[30]), "+f"(d[31]),
      "+f"(d[32]), "+f"(d[33]), "+f"(d[34]), "+f"(d[35]), "+f"(d[36]), "+f"(d[37]), "+f"(d[38]), "+f"(d[39]),
      "+f"(d[40]), "+f"(d[41]), "+f"(d[42]), "+f"(d[43]), "+f"(d[44]), "+f"(d[45]), "+f"(d[46]), "+f"(d[47]),
      "+f"(d[48]), "+f"(d[49]), "+f"(d[50]), "+f"(d[51]), "+f"(d[52]), "+f"(d[53]), "+f"(d[54]), "+f"(d[55]),
      "+f"(d[56]), "+f"(d[57]), "+f"(d[58]), "+f"(d[59]), "+f"(d[60]), "+f"(d[61]), "+f"(d[62]), "+f"(d[63]),
      "+f"(d[64]), "+f"(d[65]), "+f"(d[66]), "+f"(d[67]), "+f"(d[68]), "+f"(d[69]), "+f"(d[70]), "+f"(d[71]),
      "+f"(d[72]), "+f"(d[73]), "+f"(d[74]), "+f"(d[75]), "+f"(d[76]), "+f"(d[77]), "+f"(d[78]), "+f"(d[79])
    : "l"(da), "l"(db), "r"(sd));
}
__device__ __forceinline__ void wgmma_rs_n128(float (&d)[64], uint32_t a0, uint32_t a1, uint32_t a2, uint32_t a3,
                                  uint64_t db, int sd) {
  asm volatile("{\n.reg .pred p;\nsetp.ne.b32 p, %69, 0;\n"
      "wgmma.mma_async.sync.aligned.m64n128k16.f32.bf16.bf16 {"
      "%0, %1, %2, %3, %4, %5, %6, %7, %8, %9, %10, %11, %12, %13, %14, %15, "
      "%16, %17, %18, %19, %20, %21, %22, %23, %24, %25, %26, %27, %28, %29, %30, %31, "
      "%32, %33, %34, %35, %36, %37, %38, %39, %40, %41, %42, %43, %44, %45, %46, %47, "
      "%48, %49, %50, %51, %52, %53, %54, %55, %56, %57, %58, %59, %60, %61, %62, %63"
      "}, {%64, %65, %66, %67}, %68, p, 1, 1, 0;\n}\n"
    : "+f"(d[0]), "+f"(d[1]), "+f"(d[2]), "+f"(d[3]), "+f"(d[4]), "+f"(d[5]), "+f"(d[6]), "+f"(d[7]),
      "+f"(d[8]), "+f"(d[9]), "+f"(d[10]), "+f"(d[11]), "+f"(d[12]), "+f"(d[13]), "+f"(d[14]), "+f"(d[15]),
      "+f"(d[16]), "+f"(d[17]), "+f"(d[18]), "+f"(d[19]), "+f"(d[20]), "+f"(d[21]), "+f"(d[22]), "+f"(d[23]),
      "+f"(d[24]), "+f"(d[25]), "+f"(d[26]), "+f"(d[27]), "+f"(d[28]), "+f"(d[29]), "+f"(d[30]), "+f"(d[31]),
      "+f"(d[32]), "+f"(d[33]), "+f"(d[34]), "+f"(d[35]), "+f"(d[36]), "+f"(d[37]), "+f"(d[38]), "+f"(d[39]),
      "+f"(d[40]), "+f"(d[41]), "+f"(d[42]), "+f"(d[43]), "+f"(d[44]), "+f"(d[45]), "+f"(d[46]), "+f"(d[47]),
      "+f"(d[48]), "+f"(d[49]), "+f"(d[50]), "+f"(d[51]), "+f"(d[52]), "+f"(d[53]), "+f"(d[54]), "+f"(d[55]),
      "+f"(d[56]), "+f"(d[57]), "+f"(d[58]), "+f"(d[59]), "+f"(d[60]), "+f"(d[61]), "+f"(d[62]), "+f"(d[63])
    : "r"(a0), "r"(a1), "r"(a2), "r"(a3), "l"(db), "r"(sd));
}
__device__ __forceinline__ void wgmma_rs_n24(float (&d)[12], uint32_t a0, uint32_t a1, uint32_t a2, uint32_t a3,
                                  uint64_t db, int sd) {
  asm volatile("{\n.reg .pred p;\nsetp.ne.b32 p, %17, 0;\n"
      "wgmma.mma_async.sync.aligned.m64n24k16.f32.bf16.bf16 {"
      "%0, %1, %2, %3, %4, %5, %6, %7, %8, %9, %10, %11"
      "}, {%12, %13, %14, %15}, %16, p, 1, 1, 1;\n}\n"
    : "+f"(d[0]), "+f"(d[1]), "+f"(d[2]), "+f"(d[3]), "+f"(d[4]), "+f"(d[5]), "+f"(d[6]), "+f"(d[7]),
      "+f"(d[8]), "+f"(d[9]), "+f"(d[10]), "+f"(d[11])
    : "r"(a0), "r"(a1), "r"(a2), "r"(a3), "l"(db), "r"(sd));
}

constexpr int K1_ST = 4, K1_STAGE = 49152;
constexpr int K1_SMEM = K1_ST * K1_STAGE + 2048   + 1024   + 3072   + 128;

__global__ void __cluster_dims__(2, 1, 1) __launch_bounds__(384, 1)
k1_qkv(const __grid_constant__ CUtensorMap tmx, const __grid_constant__ CUtensorMap tmw,
       const bf16* __restrict__ x, const bf16* __restrict__ w, const bf16* __restrict__ wo) {
  extern __shared__ __align__(1024) uint8_t sm[];
  float4* tab = (float4*)(sm + K1_ST * K1_STAGE);
  float2* rowab = (float2*)(sm + K1_ST * K1_STAGE + 2048);
  float* red = (float*)(sm + K1_ST * K1_STAGE + 3072);
  uint8_t* img = sm + 2 * K1_STAGE;
  const uint32_t sbase = smem_u32(sm);
  const uint32_t fullb = sbase + K1_ST * K1_STAGE + 6144, emptyb = fullb + 8 * K1_ST;
  const int tid = threadIdx.x, lane = tid & 31;
  const int warp = __shfl_sync(~0u, tid >> 5, 0);
  const int rank = blockIdx.x & 1, cl = blockIdx.x >> 1;
  const int n = cl & 7, m = (cl >> 3) * 2 + rank;
  const int c0 = n * 240 - (n & 1) * 16;
  if (tid == 0) STAMP(0, 0);
  if (tid == 0) {
    prefetch_map(&tmx); prefetch_map(&tmw);
    for (int i = 0; i < K1_ST; i++) { mbar_init(fullb + 8 * i, 1); mbar_init(emptyb + 8 * i, 4); }
    asm volatile("fence.mbarrier_init.release.cluster;" ::: "memory");
    for (int kt = 0; kt < K1_ST; kt++) {
      mbar_expect(fullb + 8 * kt, K1_STAGE);
      tma2d(sbase + kt * K1_STAGE, &tmx, kt * 64, m * 128, fullb + 8 * kt);
    }
  }

  if (warp == 0) {
    bar_sync(0, 384);
    cluster_arrive();
    cluster_wait();
    pdl_trigger();
    if (lane == 0) {
      for (int kt = 0; kt < 10; kt++) {
        const int s = kt % K1_ST;
        const uint32_t sa = sbase + s * K1_STAGE, sb = sa + 16384 + rank * 16384;
        if (kt >= K1_ST) {
          mbar_wait(emptyb + 8 * s, ((kt / K1_ST) - 1) & 1);
          mbar_expect(fullb + 8 * s, K1_STAGE);
          tma2d(sa, &tmx, kt * 64, m * 128, fullb + 8 * s);
        }
#pragma unroll
        for (int j = 0; j < 4; j++) tma2d_mc(sb + j * 4096, &tmw, c0 + rank * 128 + j * 32, kt * 64, fullb + 8 * s);
      }
    }
    __syncwarp();
  } else if (warp < 4) {
    const int w3 = warp - 1, t96 = tid - 32;
    uint4 wv[14];
#pragma unroll
    for (int i = 0; i < 14; i++) wv[i] = ldg_nc(w + (size_t)(m * 40 + min(w3 + 3 * i, 39)) * 1920 + c0 + lane * 8);
    bar_sync(0, 384);
    cluster_arrive();
    {
      float acc8[8];
#pragma unroll
      for (int i = 0; i < 8; i++) acc8[i] = 0.f;
#pragma unroll
      for (int i = 0; i < 14; i++) {
        if (i < 13 || w3 == 0) {
          const uint4 v = wv[i];
          acc8[0] += bf_lo(v.x); acc8[1] += bf_hi(v.x); acc8[2] += bf_lo(v.y); acc8[3] += bf_hi(v.y);
          acc8[4] += bf_lo(v.z); acc8[5] += bf_hi(v.z); acc8[6] += bf_lo(v.w); acc8[7] += bf_hi(v.w);
        }
      }
      *(float4*)&red[w3 * 256 + lane * 8] = make_float4(acc8[0], acc8[1], acc8[2], acc8[3]);
      *(float4*)&red[w3 * 256 + lane * 8 + 4] = make_float4(acc8[4], acc8[5], acc8[6], acc8[7]);
    }
    bar_sync(1, 96);
    if (t96 < 64) {
      const float4 p0 = *(const float4*)&red[t96 * 4], p1 = *(const float4*)&red[256 + t96 * 4], p2 = *(const float4*)&red[512 + t96 * 4];
      *(float4*)&g_cpart[m * 2048 + n * 256 + t96 * 4] = make_float4(p0.x + p1.x + p2.x, p0.y + p1.y + p2.y, p0.z + p1.z + p2.z, p0.w + p1.w + p2.w);
    }
    bar_sync(3, 96 + 256);
    if (t96 == 0) {
      __threadfence();
      asm volatile("red.relaxed.gpu.global.add.u32 [%0], 1;" ::"l"(&g_cnt[m * 32]) : "memory");
      asm volatile("red.relaxed.gpu.global.add.u32 [%0], 1;" ::"l"(&g_cnt[(16 + n) * 32]) : "memory");
      uint32_t a, b, it = 0;
      while (true) {
        asm volatile("ld.relaxed.gpu.global.u32 %0, [%1];" : "=r"(a) : "l"(&g_cnt[m * 32]) : "memory");
        asm volatile("ld.relaxed.gpu.global.u32 %0, [%1];" : "=r"(b) : "l"(&g_cnt[(16 + n) * 32]) : "memory");
        if (a >= 8 && b >= 16) break;
        if (++it > (1u << 22)) wait_timeout();
        __nanosleep(32);
      }
      __threadfence();
    } else if (t96 >= 32) {
      uint4 v[7];
#pragma unroll
      for (int i = 0; i < 7; i++) {
        const int e = min(t96 - 32 + 64 * i, 399), k = blockIdx.x * 5 + e / 80, pr = k / 40, r = k - pr * 40;
        v[i] = ldg_nc(wo + (size_t)(pr * 40 + (r < 16 ? r : (r < 32 ? r + 4 : (r < 36 ? r - 16 : r)))) * D_ + (e % 80) * 8);
      }
#pragma unroll
      for (int i = 0; i < 7; i++) {
        const int e = min(t96 - 32 + 64 * i, 399), k = blockIdx.x * 5 + e / 80, cg = e % 80, nt = cg / 10;
        g_wo[((nt * 10 + (k >> 6)) * 10 + cg - nt * 10) * 64 + (k & 63)] = v[i];
      }
    }
    bar_sync(1, 96);
    for (int r = t96; r < 128; r += 96) {
      float2 st = __ldcg(&g_rowstat[m * 128 + r]);
      float2 p[16];
#pragma unroll
      for (int i = 0; i < 16; i++) p[i] = __ldcg((const float2*)&g_cpart[i * 2048 + n * 256 + 2 * r]);
      rowab[r] = make_float2(st.x, -st.x * st.y);
      float s0 = 0.f, s1 = 0.f;
#pragma unroll
      for (int i = 0; i < 16; i++) { s0 += p[i].x; s1 += p[i].y; }
      const int lc = max(2 * r - (n & 1) * 16, 0), hl = lc / 20, d = lc - hl * 20;
      tab[r] = make_float4(s0, s1, __int_as_float(hl * 6144 + (d >> 3) * 128 + (d & 7) * 2), 0.f);
    }
    if (tid == 32) STAMP(0, 5);
    mbar_wait(emptyb + 16, 1);
    mbar_wait(emptyb + 24, 1);
    for (int r = t96; r < 128; r += 96) {
      uint8_t* p = img + (r >> 3) * 384 + 256 + (r & 7) * 16 + 8;
      const uint2 kv = ((POLY_MASK >> (r >> 3)) & 1) ? make_uint2(0x4A7A4B00u, 0x00004653u)
                                                     : make_uint2(0u, 0u);
#pragma unroll
      for (int hl = 0; hl < 12; hl++) {
        const int sh = n * 12 + hl;
        *(uint2*)(p + hl * 6144) = sh < 32 ? make_uint2(0x3F803F80u, 0x00003F80u) : (sh < 64 ? kv : make_uint2(0x00003F80u, 0u));
      }
    }
    fence_async();
    bar_arrive(2, 96 + 256);
    cluster_wait();
  } else {
    const int cw = warp - 4, wg = cw >> 2;
    {
      uint4 xv[2][3];
#pragma unroll
      for (int i = 0; i < 2; i++) {
        const bf16* xr = x + (size_t)(m * 128 + n * 16 + cw * 2 + i) * D_ + lane * 8;
        xv[i][0] = ldg_nc(xr);
        xv[i][1] = ldg_nc(xr + 256);
        xv[i][2] = ldg_nc(xr + (lane < 16 ? 512 : 0));
      }
      bar_sync(0, 384);
      cluster_arrive();
#pragma unroll
      for (int i = 0; i < 2; i++) {
        float f[24];
#pragma unroll
        for (int k = 0; k < 3; k++) {
          const uint4 v = xv[i][k];
          f[8 * k + 0] = bf_lo(v.x); f[8 * k + 1] = bf_hi(v.x); f[8 * k + 2] = bf_lo(v.y); f[8 * k + 3] = bf_hi(v.y);
          f[8 * k + 4] = bf_lo(v.z); f[8 * k + 5] = bf_hi(v.z); f[8 * k + 6] = bf_lo(v.w); f[8 * k + 7] = bf_hi(v.w);
        }
        float s = 0.f, s2 = 0.f;
#pragma unroll
        for (int k = 0; k < 16; k++) s += f[k];
#pragma unroll
        for (int k = 16; k < 24; k++) s2 += f[k];
        if (lane < 16) s += s2;
#pragma unroll
        for (int o = 16; o; o >>= 1) s += __shfl_xor_sync(~0u, s, o);
        const float mean = s * (1.f / D_);
        float q = 0.f, q2 = 0.f;
#pragma unroll
        for (int k = 0; k < 16; k++) { float d = f[k] - mean; q = fmaf(d, d, q); }
#pragma unroll
        for (int k = 16; k < 24; k++) { float d = f[k] - mean; q2 = fmaf(d, d, q2); }
        if (lane < 16) q += q2;
#pragma unroll
        for (int o = 16; o; o >>= 1) q += __shfl_xor_sync(~0u, q, o);
        if (lane == 0) g_rowstat[m * 128 + n * 16 + cw * 2 + i] = make_float2(rsqrtf(q * (1.f / D_) + 1e-5f), mean);
      }
      bar_arrive(3, 96 + 256);
    }
    float acc[128];
    const uint64_t da0 = mkdesc(sbase + wg * 8192, 16, 1024, 1);
    const uint64_t db0 = mkdesc(sbase + 16384, 4096, 512, 2);
    cluster_wait();
#pragma unroll 1
    for (int kt = 0; kt < 10; kt++) {
      const int s = kt % K1_ST;
      mbar_wait(fullb + 8 * s, (kt / K1_ST) & 1);
      if (kt == 0 && tid == 128) STAMP(0, 1);
      const uint64_t da = da0 + s * (K1_STAGE >> 4), db = db0 + s * (K1_STAGE >> 4);
      WG_FENCE();
#pragma unroll
      for (int k = 0; k < 4; k++) wgmma_ss_n256(acc, da + k * 2, db + k * 64, (kt | k) != 0);
      WG_COMMIT();
      if (kt > 0) {
        WG_WAIT(1);
        if (kt < 9 && (tid & 127) < 2) mbar_arrive_cta(emptyb + 8 * ((kt - 1) % K1_ST), tid & 1);
      }
    }
    WG_WAIT(0);
    fence_regs(acc);
    if (tid == 128) STAMP(0, 2);
    bar_sync(2, 96 + 256);
    if (tid == 128) STAMP(0, 3);
    const int g = lane >> 2, c = lane & 3;
    const float2 ab0 = rowab[cw * 16 + g], ab1 = rowab[cw * 16 + g + 8];
    const float k0 = ((POLY_MASK >> (cw * 2)) & 1) ? 32768.f : 1.f, k1 = ((POLY_MASK >> (cw * 2 + 1)) & 1) ? 32768.f : 1.f;
    uint8_t* dst = img + cw * 768 + g * 16;
    uint8_t* gdst = (uint8_t*)g_qkv + (size_t)(n * 12 + lane) * HEAD_IMG + m * 6144 + cw * 768;
#pragma unroll
    for (int seg = 0; seg < 3; seg++) {
      const int j0 = seg == 0 ? 0 : (seg == 1 ? 12 : 20), j1 = seg == 0 ? 12 : (seg == 1 ? 20 : 32);
      const int sec = (c0 + j0 * 8 + 16) / 640;
      const float f0 = sec == 0 ? QSCALE : (sec == 1 ? k0 : 1.f), f1 = sec == 0 ? QSCALE : (sec == 1 ? k1 : 1.f);
      const float a0 = ab0.x * f0, b0 = ab0.y * f0, a1 = ab1.x * f1, b1 = ab1.y * f1;
#pragma unroll
      for (int j = j0; j < j1; j++) {
        if ((j < 2 && (n & 1)) || (j >= 30 && !(n & 1))) continue;
        const float4 t = tab[4 * j + c];
        uint8_t* p = dst + __float_as_int(t.z);
        *(uint32_t*)p = pack_bf16(fmaf(acc[4 * j], a0, b0 * t.x), fmaf(acc[4 * j + 1], a0, b0 * t.y));
        *(uint32_t*)(p + 384) = pack_bf16(fmaf(acc[4 * j + 2], a1, b1 * t.x), fmaf(acc[4 * j + 3], a1, b1 * t.y));
      }
      fence_async();
      __syncwarp();
      const int h0 = seg == 0 ? 0 : (seg == 1 ? 4 : 7), h1 = seg == 0 ? 4 : (seg == 1 ? 7 : 12);
      if (lane >= h0 && lane < h1) bulk_st(gdst, smem_u32(img) + lane * 6144 + cw * 768, 768);
    }
    if (tid == 128) STAMP(0, 4);
    if (lane < 12) bulk_commit_wait();
    __syncwarp();
  }
  cluster_sync_relaxed();
  if (tid == 128) STAMP(0, 6);
}

constexpr int K2_SMEM = 2 * HEAD_IMG + 2 * 6144 + 256;

__device__ __forceinline__ uint32_t exp_pair(bool poly, float a, float b, uint32_t mk) {
  if (poly) {
    const uint32_t pk = __byte_perm(__float_as_uint(a), __float_as_uint(b), 0x6521);
    uint32_t m, q;
    asm("lop3.b32 %0, %1, %2, 0x3f803f80, 0xEA;" : "=r"(m) : "r"(pk), "r"(mk));
    asm("fma.rn.bf16x2 %0, %1, %1, %2;" : "=r"(q) : "r"(m), "r"(0x40014001u));
    return pk - m + q;
  }
  return pack_bf16(ex2(a), ex2(b));
}
__device__ __forceinline__ void exp_pv(const float (&s)[64], float (&o)[12], uint64_t dv, uint32_t mk) {
#pragma unroll
  for (int k0 = 0; k0 < 8; k0 += 2) {
    uint32_t p[8];
#pragma unroll
    for (int i = 0; i < 8; i++)
      p[i] = exp_pair((POLY_MASK >> (k0 * 2 + i / 2)) & 1, s[k0 * 8 + 2 * i], s[k0 * 8 + 2 * i + 1], mk);
    WG_FENCE();
    wgmma_rs_n24(o, p[0], p[1], p[2], p[3], dv + k0 * 48, 1);
    wgmma_rs_n24(o, p[4], p[5], p[6], p[7], dv + k0 * 48 + 48, 1);
  }
}
__device__ __forceinline__ void load_q(uint32_t (&q)[6], const uint8_t* p) {
  q[0] = __ldcg((const uint32_t*)p);         q[1] = __ldcg((const uint32_t*)(p + 384));
  q[2] = __ldcg((const uint32_t*)(p + 128)); q[3] = __ldcg((const uint32_t*)(p + 512));
  q[4] = __ldcg((const uint32_t*)(p + 256)); q[5] = __ldcg((const uint32_t*)(p + 640));
}
__device__ __forceinline__ void store_o(const float (&o)[12], uint8_t* dst, int o0, int o1, int o2, int lane) {
  const float l0 = __shfl_sync(~0u, o[8], (lane & ~3) | 2), l1 = __shfl_sync(~0u, o[10], (lane & ~3) | 2);
  const float i0 = __frcp_rn(l0), i1 = __frcp_rn(l1);
  *(uint32_t*)(dst + o0) = pack_bf16(o[0] * i0, o[1] * i0); *(uint32_t*)(dst + o0 + 1024) = pack_bf16(o[2] * i1, o[3] * i1);
  *(uint32_t*)(dst + o1) = pack_bf16(o[4] * i0, o[5] * i0); *(uint32_t*)(dst + o1 + 1024) = pack_bf16(o[6] * i1, o[7] * i1);
  if ((lane & 3) < 2) {
    *(uint32_t*)(dst + o2) = pack_bf16(o[8] * i0, o[9] * i0);
    *(uint32_t*)(dst + o2 + 1024) = pack_bf16(o[10] * i1, o[11] * i1);
  }
}
__device__ __forceinline__ int img_off(int chunk) { return (chunk >> 3) * 16384 + (chunk & 7) * 128; }
__device__ __forceinline__ float sq20(uint4 a, uint4 b, uint2 c) {
  uint32_t s0, s1;
  asm("mul.rn.bf16x2 %0, %1, %1;" : "=r"(s0) : "r"(a.x));
  asm("mul.rn.bf16x2 %0, %1, %1;" : "=r"(s1) : "r"(a.y));
#define SQ_(acc, v) asm("fma.rn.bf16x2 %0, %1, %1, %0;" : "+r"(acc) : "r"(v))
  SQ_(s0, a.z); SQ_(s1, a.w); SQ_(s0, b.x); SQ_(s1, b.y); SQ_(s0, b.z); SQ_(s1, b.w); SQ_(s0, c.x); SQ_(s1, c.y);
#undef SQ_
  return (bf_lo(s0) + bf_hi(s0)) + (bf_lo(s1) + bf_hi(s1));
}

__global__ void __launch_bounds__(512, 1)
k2_attn(const bf16* __restrict__ wg_, const bf16* __restrict__ wu,
        const bf16* __restrict__ wd, uint32_t mk) {
  extern __shared__ __align__(1024) uint8_t sm[];
  const uint32_t sbase = smem_u32(sm);
  float* part = (float*)(sm + 2 * HEAD_IMG);
  const uint32_t kvb = sbase + 2 * HEAD_IMG + 2 * 6144;
  const uint32_t flagb = kvb + 128, partb = kvb + 136;
  volatile uint32_t* sflag = (volatile uint32_t*)(sm + 2 * HEAD_IMG + 2 * 6144 + 160);
  const int tid = threadIdx.x, lane = tid & 31;
  const int warp = __shfl_sync(~0u, tid >> 5, 0);
  const int head = blockIdx.x >> 2, qb = blockIdx.x & 3;
  const uint8_t* qimg = (const uint8_t*)g_qkv + (size_t)head * HEAD_IMG + qb * 64 * 384;

  if (tid == 0) STAMP(1, 0);
  if (tid == 0) {
    for (int i = 0; i < 16; i++) mbar_init(kvb + 8 * i, 1);
    mbar_init(flagb, 1); mbar_init(partb, 128); mbar_init(partb + 8, 128);
    asm volatile("fence.mbarrier_init.release.cluster;" ::: "memory");
  }
  __syncthreads();

  if (warp >= 12) {
    asm volatile("setmaxnreg.dec.sync.aligned.u32 56;");
    const int t = tid - 384;
    pdl_wait();
    pdl_trigger();
    if (t == 0) {
      const uint8_t* kimg = (const uint8_t*)g_qkv + (size_t)(32 + head) * HEAD_IMG;
      const uint8_t* vimg = (const uint8_t*)g_qkv + (size_t)(64 + head) * HEAD_IMG;
      for (int b = 0; b < 16; b++) {
        mbar_expect(kvb + 8 * b, 12288);
        bulk_ld(sbase + b * 6144, kimg + b * 6144, 6144, kvb + 8 * b);
        bulk_ld(sbase + HEAD_IMG + b * 6144, vimg + b * 6144, 6144, kvb + 8 * b);
      }
    }
    if (blockIdx.x == 0 && t >= 32 && t < 56) g_cnt[(t - 32) * 32] = 0;
    {
      float qm = 0.f, km = 0.f;
      const int ro = (t >> 3) * 384 + (t & 7) * 16;
#pragma unroll
      for (int i = 0; i < 4; i++) {
        const uint8_t* p = qimg + i * 6144 + ro;
        const float v = sq20(__ldcg((const uint4*)p), __ldcg((const uint4*)(p + 128)), __ldcg((const uint2*)(p + 256)));
        qm = __uint_as_float(max(__float_as_uint(qm), __float_as_uint(v)));
      }
#pragma unroll 1
      for (int b = 0; b < 16; b++) {
        mbar_wait(kvb + 8 * b, 0);
        const uint8_t* p = sm + b * 6144 + ro;
        const float v = sq20(*(const uint4*)p, *(const uint4*)(p + 128), *(const uint2*)(p + 256));
        km = __uint_as_float(max(__float_as_uint(km), __float_as_uint(v)));
      }
      if ((POLY_MASK >> (t >> 3)) & 1) km *= 9.313225746154785e-10f;
      const uint32_t qw = __reduce_max_sync(~0u, __float_as_uint(qm)), kw = __reduce_max_sync(~0u, __float_as_uint(km));
      if (lane == 0) { sflag[1 + (warp & 3)] = qw; sflag[5 + (warp & 3)] = kw; }
      bar_sync(1, 128);
      if (t == 0) {
        const float q2 = __uint_as_float(max(max(sflag[1], sflag[2]), max(sflag[3], sflag[4])));
        const float k2 = __uint_as_float(max(max(sflag[5], sflag[6]), max(sflag[7], sflag[8])));
        sflag[0] = (q2 * k2 <= 3000.f) ? 1u : 0u;
        mbar_arrive(flagb);
        STAMP(1, 2);
      }
    }
    const int kr = (warp & 3) * 8 + (lane >> 2), ch = lane & 3;
    if (blockIdx.x < 108) {
      const int cg = blockIdx.x * 4 + ch;
      const int up = cg >= 216, cc = cg - up * 216;
      const int nt = cc / 27, ci = cc - nt * 27 + up * 27;
      const bf16* src = (up ? wu : wg_) + cc * 8 + (size_t)kr * F_;
      uint4* dst = g_wgu + ((size_t)nt * 10 * 54 + ci) * 64 + kr;
      float a8[8];
#pragma unroll
      for (int i = 0; i < 8; i++) a8[i] = 0.f;
#pragma unroll 4
      for (int it = 0; it < 20; it++) {
        const uint4 v = ldg_nc(src + (size_t)it * 32 * F_);
        dst[(it >> 1) * (54 * 64) + (it & 1) * 32] = v;
        a8[0] += bf_lo(v.x); a8[1] += bf_hi(v.x); a8[2] += bf_lo(v.y); a8[3] += bf_hi(v.y);
        a8[4] += bf_lo(v.z); a8[5] += bf_hi(v.z); a8[6] += bf_lo(v.w); a8[7] += bf_hi(v.w);
      }
#pragma unroll
      for (int i = 0; i < 8; i++) {
        a8[i] += __shfl_xor_sync(~0u, a8[i], 4);
        a8[i] += __shfl_xor_sync(~0u, a8[i], 8);
        a8[i] += __shfl_xor_sync(~0u, a8[i], 16);
      }
      float* red = (float*)(sm + K2_SMEM);
      if (lane < 4) {
#pragma unroll
        for (int i = 0; i < 8; i++) red[(warp & 3) * 32 + lane * 8 + i] = a8[i];
      }
      bar_sync(1, 128);
      if (t < 32) g_csgu[blockIdx.x * 32 + t] = red[t] + red[32 + t] + red[64 + t] + red[96 + t];
    }
    {
      const int first = blockIdx.x < 108 ? blockIdx.x * 5 : 540 + (blockIdx.x - 108) * 27;
      const int last = blockIdx.x < 108 ? first + 5 : first + 27;
#pragma unroll 4
      for (int ps = first; ps < last; ps++) {
        const int rg = ps / 20, cs = ps - rg * 20;
        const int cg = cs * 4 + ch, nt = cg / 10, ci = cg - nt * 10;
        const int k = rg * 32 + kr;
        g_wd[((nt * 27 + (k >> 6)) * 10 + ci) * 64 + (k & 63)] = ldg_nc(wd + (size_t)k * D_ + cg * 8);
      }
    }
    if (t == 0) STAMP(1, 6);
  } else {
    asm volatile("setmaxnreg.inc.sync.aligned.u32 152;");
    const int wg = warp >> 2, wq = warp & 3;
    const uint8_t* qthr = qimg + wq * 768 + (lane >> 2) * 16 + (lane & 3) * 4;
    uint8_t* othr = (uint8_t*)g_o + (size_t)qb * 4 * 163840 + wq * 2048 + (lane >> 2) * 16 + (lane & 3) * 4;
    const int oc = (head >> 1) * 5 + (head & 1) * 2;
    const int oo0 = img_off(oc), oo1 = img_off(oc + 1), oo2 = img_off((head >> 1) * 5 + 4) + (head & 1) * 8;
    const uint64_t dk0 = mkdesc(sbase, 128, 384, 0), dk0b = mkdesc(sbase + 256, 0, 384, 0);
    const uint64_t dv0 = mkdesc(sbase + HEAD_IMG, 384, 128, 0);
    const int nun = wg == 1 ? 4 : 3;
    const uint32_t utile = wg == 0 ? 0x210u : (wg == 1 ? 0x4325u : 0x576u);
    pdl_wait();
    if (tid == 0) STAMP(1, 1);
    uint32_t q[6];
    load_q(q, qthr + (utile & 15) * 3072);
    bool fast = true;
#pragma unroll 1
    for (int u = 0; u < nun; u++) {
      const int tile = (utile >> (4 * u)) & 15;
      int b0 = 0, b1 = 16;
      if (wg == 0 && u == 2) b1 = 11;
      if (wg == 1 && u == 0) b1 = 6;
      if (wg == 1 && u == 1) b0 = 11;
      if (wg == 2 && u == 2) b0 = 6;
      const bool wt = u == 0 || (wg == 1 && u == 1);
      float s[64], o[12];
#pragma unroll
      for (int i = 0; i < 12; i++) o[i] = 0.f;
      uint64_t dk = dk0 + b0 * 384, dkb = dk0b + b0 * 384, dv = dv0 + b0 * 384;
      if (wt) mbar_wait(kvb + 8 * b0, 0);
      fence_regs(o);
      WG_FENCE();
      wgmma_rs_n128(s, q[0], q[1], q[2], q[3], dk, 0);
      wgmma_rs_n128(s, q[4], q[5], 0, 0, dkb, 1);
      WG_COMMIT();
#pragma unroll 1
      for (int b = b0 + 1; b < b1; b++) {
        if (wt) mbar_wait(kvb + 8 * b, 0);
        WG_WAIT(0);
        fence_regs(s); fence_regs(o);
        exp_pv(s, o, dv, mk);
        dk += 384; dkb += 384; dv += 384;
        wgmma_rs_n128(s, q[0], q[1], q[2], q[3], dk, 0);
        wgmma_rs_n128(s, q[4], q[5], 0, 0, dkb, 1);
        WG_COMMIT();
      }
      WG_WAIT(0);
      fence_regs(s); fence_regs(o);
      if (u + 1 < nun) load_q(q, qthr + ((utile >> (4 * u + 4)) & 15) * 3072);
      exp_pv(s, o, dv, mk);
      WG_COMMIT();
      WG_WAIT(0);
      fence_regs(o);
      if (wg == 1 && u < 2) {
        float4* pp = (float4*)(part + u * 1536) + (tid & 127);
        pp[0] = make_float4(o[0], o[1], o[2], o[3]);
        pp[128] = make_float4(o[4], o[5], o[6], o[7]);
        pp[256] = make_float4(o[8], o[9], o[10], o[11]);
        mbar_arrive(partb + 8 * u);
        if (u == 0) continue;
      }
      if (wt) {
        mbar_wait(flagb, 0);
        fast = sflag[0] != 0;
        if (!fast) break;
        if (wg == 1) continue;
      }
      if (wg != 1 && u == 2) {
        const int pi = wg == 0 ? 1 : 0;
        mbar_wait(partb + 8 * pi, 0);
        const float4* pp = (const float4*)(part + pi * 1536) + (tid & 127);
        const float4 x0 = pp[0], x1 = pp[128], x2 = pp[256];
        o[0] += x0.x; o[1] += x0.y; o[2] += x0.z; o[3] += x0.w; o[4] += x1.x; o[5] += x1.y;
        o[6] += x1.z; o[7] += x1.w; o[8] += x2.x; o[9] += x2.y; o[10] += x2.z; o[11] += x2.w;
      }
      store_o(o, othr + (tile >> 1) * 163840 + (tile & 1) * 8192, oo0, oo1, oo2, lane);
    }
    if ((tid & 127) == 0) STAMP(1, 3 + wg);
    if (!fast) {
#pragma unroll 1
      for (int tile = wg; tile < 8; tile += 3) {
        load_q(q, qthr + tile * 3072);
        if ((lane & 3) >= 2) { q[4] = 0; q[5] = 0; }
        float o[12], m0 = -INFINITY, m1 = -INFINITY;
#pragma unroll
        for (int i = 0; i < 12; i++) o[i] = 0.f;
#pragma unroll 1
        for (int b = 0; b < 16; b++) {
          float s[64];
          WG_FENCE();
          wgmma_rs_n128(s, q[0], q[1], q[2], q[3], dk0 + b * 384, 0);
          wgmma_rs_n128(s, q[4], q[5], 0, 0, dk0b + b * 384, 1);
          WG_COMMIT();
          WG_WAIT(0);
          fence_regs(s);
          float x0 = m0, x1 = m1;
#pragma unroll
          for (int j = 0; j < 16; j++) {
            if ((POLY_MASK >> j) & 1) {
#pragma unroll
              for (int i = 0; i < 4; i++) s[4 * j + i] *= (1.f / 32768.f);
            }
            x0 = fmaxf(x0, fmaxf(s[4 * j], s[4 * j + 1]));
            x1 = fmaxf(x1, fmaxf(s[4 * j + 2], s[4 * j + 3]));
          }
          x0 = fmaxf(x0, __shfl_xor_sync(~0u, x0, 1)); x0 = fmaxf(x0, __shfl_xor_sync(~0u, x0, 2));
          x1 = fmaxf(x1, __shfl_xor_sync(~0u, x1, 1)); x1 = fmaxf(x1, __shfl_xor_sync(~0u, x1, 2));
          const float al0 = ex2(m0 - x0), al1 = ex2(m1 - x1);
          m0 = x0; m1 = x1;
#pragma unroll
          for (int i = 0; i < 12; i++) o[i] *= (i & 2) ? al1 : al0;
          uint32_t p[32];
#pragma unroll
          for (int i = 0; i < 32; i++) {
            const float mm = (i & 1) ? m1 : m0;
            p[i] = pack_bf16(ex2(s[2 * i] - mm), ex2(s[2 * i + 1] - mm));
          }
          fence_regs(o);
          WG_FENCE();
#pragma unroll
          for (int k = 0; k < 8; k++) wgmma_rs_n24(o, p[4 * k], p[4 * k + 1], p[4 * k + 2], p[4 * k + 3], dv0 + b * 384 + k * 48, 1);
          WG_COMMIT();
          WG_WAIT(0);
          fence_regs(o);
        }
        store_o(o, othr + (tile >> 1) * 163840 + (tile & 1) * 8192, oo0, oo1, oo2, lane);
      }
    }
  }
}

constexpr int K3_ST = 4, K3_STAGE = 36864;
constexpr int K3_SMEM = K3_ST * K3_STAGE + 40960 + 20480 + 256;

template <int KT, bool FIRST>
__global__ void __cluster_dims__(2, 1, 1) __launch_bounds__(384, 1)
k3_proj(const __grid_constant__ CUtensorMap tmr, const uint4* __restrict__ aimg, const uint4* __restrict__ wimg) {
  extern __shared__ __align__(1024) uint8_t sm[];
  const uint32_t sbase = smem_u32(sm);
  uint8_t* xch = sm + K3_ST * K3_STAGE;
  uint8_t* stg = sm + K3_ST * K3_STAGE + 40960;
  const uint32_t fullb = smem_u32(stg) + 20480, emptyb = fullb + 8 * K3_ST, resb = emptyb + 8 * K3_ST, xchb = resb + 8;
  const int tid = threadIdx.x, lane = tid & 31;
  const int warp = __shfl_sync(~0u, tid >> 5, 0);
  const int rank = blockIdx.x & 1;
  const int n = blockIdx.x & 7, m = blockIdx.x >> 3;
  const int kt0 = rank * ((KT + 1) / 2), nkt = rank ? KT / 2 : (KT + 1) / 2;
  if (tid == 0) STAMP(FIRST ? 2 : 4, 0);
  if (tid == 0) {
    prefetch_map(&tmr);
    for (int i = 0; i < K3_ST; i++) { mbar_init(fullb + 8 * i, 1); mbar_init(emptyb + 8 * i, 2); }
    mbar_init(resb, 1); mbar_init(xchb, 1);
    mbar_expect(xchb, 40960);
    asm volatile("fence.mbarrier_init.release.cluster;" ::: "memory");
  }
  __syncthreads();
  cluster_arrive();
  if (warp == 0) {
    if (lane == 0) {
      const uint8_t* wk = (const uint8_t*)wimg + (size_t)(n * KT + kt0) * 10240;
      const uint8_t* ws = (const uint8_t*)wimg + (size_t)((n ^ 1) * KT + kt0) * 10240;
      const uint8_t* ab = (const uint8_t*)aimg + (size_t)(m * KT + kt0) * 16384;
      mbar_expect(fullb, K3_STAGE);
      bulk_ld(sbase + 16384, wk, 10240, fullb);
      bulk_ld(sbase + 26624, ws, 10240, fullb);
      pdl_wait();
      pdl_trigger();
      for (int i = 0; i < nkt; i++) {
        const int s = i % K3_ST;
        const uint32_t sa = sbase + s * K3_STAGE;
        if (i >= K3_ST) mbar_wait(emptyb + 8 * s, ((i / K3_ST) - 1) & 1);
        if (i > 0) mbar_expect(fullb + 8 * s, K3_STAGE);
        bulk_ld(sa, ab + i * 16384, 16384, fullb + 8 * s);
        if (i > 0) {
          bulk_ld(sa + 16384, wk + i * 10240, 10240, fullb + 8 * s);
          bulk_ld(sa + 26624, ws + i * 10240, 10240, fullb + 8 * s);
        }
        if (FIRST && i == K3_ST - 1) {
          mbar_expect(resb, 20480);
          tma2d(smem_u32(stg), &tmr, n * 80, m * 128, resb);
          tma2d(smem_u32(stg) + 10240, &tmr, n * 80, m * 128 + 64, resb);
        }
      }
    }
    __syncwarp();
    cluster_wait();
  } else if (warp >= 4) {
    const int cw = warp - 4, wg = cw >> 2;
    const int g = lane >> 2, c = lane & 3;
    uint8_t* himg = (uint8_t*)g_h + (size_t)m * 163840 + cw * 2048 + g * 16 + c * 4;
    uint32_t rv[20];
    if (!FIRST) {
#pragma unroll
      for (int j = 0; j < 10; j++) {
        rv[2 * j] = __ldcg((const uint32_t*)(himg + img_off(n * 10 + j)));
        rv[2 * j + 1] = __ldcg((const uint32_t*)(himg + img_off(n * 10 + j) + 1024));
      }
    }
    float acc[80];
    const uint64_t da0 = mkdesc(sbase + wg * 8192, 128, 1024, 0);
    const uint64_t db0 = mkdesc(sbase + 16384, 128, 1024, 0);
#pragma unroll 1
    for (int i = 0; i < nkt; i++) {
      const int s = i % K3_ST;
      mbar_wait(fullb + 8 * s, (i / K3_ST) & 1);
      if (i == 0 && tid == 128) STAMP(FIRST ? 2 : 4, 2);
      const uint64_t da = da0 + s * (K3_STAGE >> 4), db = db0 + s * (K3_STAGE >> 4);
      WG_FENCE();
#pragma unroll
      for (int k = 0; k < 4; k++) wgmma_ss_n160(acc, da + k * 16, db + k * 16, (i | k) != 0);
      WG_COMMIT();
      if (i > 0) {
        WG_WAIT(1);
        if ((tid & 127) == 0) mbar_arrive(emptyb + 8 * ((i - 1) % K3_ST));
      }
    }
    uint8_t* sp = stg + (cw * 16 + g) * 160 + c * 4;
    if (FIRST) {
      mbar_wait(resb, 0);
#pragma unroll
      for (int j = 0; j < 10; j++) {
        rv[2 * j] = *(const uint32_t*)(sp + j * 16);
        rv[2 * j + 1] = *(const uint32_t*)(sp + 1280 + j * 16);
      }
    }
    cluster_wait();
    WG_WAIT(0);
    fence_regs(acc);
    if (tid == 128) STAMP(FIRST ? 2 : 4, 3);
    bar_sync(3, 256);
#pragma unroll
    for (int j = 0; j < 10; j++)
      *(float4*)(sm + cw * 5120 + j * 512 + lane * 16) = make_float4(acc[40 + 4 * j], acc[41 + 4 * j], acc[42 + 4 * j], acc[43 + 4 * j]);
    fence_async();
    __syncwarp();
    if (lane == 0)
      asm volatile("cp.async.bulk.shared::cluster.shared::cta.mbarrier::complete_tx::bytes [%0], [%1], 5120, [%2];"
                   ::"r"(mapa(smem_u32(xch) + cw * 5120, rank ^ 1)), "r"(sbase + cw * 5120), "r"(mapa(xchb, rank ^ 1)) : "memory");
#pragma unroll
    for (int j = 0; j < 10; j++) {
      acc[4 * j] += bf_lo(rv[2 * j]); acc[4 * j + 1] += bf_hi(rv[2 * j]);
      acc[4 * j + 2] += bf_lo(rv[2 * j + 1]); acc[4 * j + 3] += bf_hi(rv[2 * j + 1]);
    }
    mbar_wait(xchb, 0);
    if (tid == 128) STAMP(FIRST ? 2 : 4, 5);
    float s0 = 0.f, s1 = 0.f;
#pragma unroll
    for (int j = 0; j < 10; j++) {
      const float4 p = *(const float4*)(xch + cw * 5120 + j * 512 + lane * 16);
      acc[4 * j] += p.x; acc[4 * j + 1] += p.y; acc[4 * j + 2] += p.z; acc[4 * j + 3] += p.w;
      if (FIRST) {
        *(uint32_t*)(himg + img_off(n * 10 + j)) = pack_bf16(acc[4 * j], acc[4 * j + 1]);
        *(uint32_t*)(himg + img_off(n * 10 + j) + 1024) = pack_bf16(acc[4 * j + 2], acc[4 * j + 3]);
        s0 += acc[4 * j] + acc[4 * j + 1]; s1 += acc[4 * j + 2] + acc[4 * j + 3];
      } else {
        *(uint32_t*)(sp + j * 16) = pack_bf16(acc[4 * j], acc[4 * j + 1]);
        *(uint32_t*)(sp + 1280 + j * 16) = pack_bf16(acc[4 * j + 2], acc[4 * j + 3]);
      }
    }
    if (FIRST) {
      s0 += __shfl_xor_sync(~0u, s0, 1); s0 += __shfl_xor_sync(~0u, s0, 2);
      s1 += __shfl_xor_sync(~0u, s1, 1); s1 += __shfl_xor_sync(~0u, s1, 2);
      s0 *= (1.f / 80.f); s1 *= (1.f / 80.f);
      float q0 = 0.f, q1 = 0.f;
#pragma unroll
      for (int j = 0; j < 10; j++) {
        float d;
        d = acc[4 * j] - s0; q0 = fmaf(d, d, q0); d = acc[4 * j + 1] - s0; q0 = fmaf(d, d, q0);
        d = acc[4 * j + 2] - s1; q1 = fmaf(d, d, q1); d = acc[4 * j + 3] - s1; q1 = fmaf(d, d, q1);
      }
      q0 += __shfl_xor_sync(~0u, q0, 1); q0 += __shfl_xor_sync(~0u, q0, 2);
      q1 += __shfl_xor_sync(~0u, q1, 1); q1 += __shfl_xor_sync(~0u, q1, 2);
      if (c < 2) g_hpart[n * S_ + m * 128 + cw * 16 + g + c * 8] = c ? make_float2(s1, q1) : make_float2(s0, q0);
    } else {
      fence_async();
      bar_sync(1 + wg, 128);
      if ((tid & 127) == 0) {
        tma2d_st(&tmr, n * 80, m * 128 + wg * 64, smem_u32(stg) + wg * 10240);
        bulk_commit_wait();
      }
      __syncwarp();
    }
    if (tid == 128) STAMP(FIRST ? 2 : 4, 4);
  } else {
    cluster_wait();
  }
  cluster_sync_relaxed();
}

constexpr int K4_ST = 3, K4_STAGE = 71680;
constexpr int K4_SMEM = K4_ST * K4_STAGE + 1728 + 1024 + 64;

__global__ void __cluster_dims__(2, 1, 1) __launch_bounds__(256, 1)
k4_ffn1() {
  extern __shared__ __align__(1024) uint8_t sm[];
  float* cs = (float*)(sm + K4_ST * K4_STAGE);
  float2* rowst = (float2*)(sm + K4_ST * K4_STAGE + 1728);
  const uint32_t sbase = smem_u32(sm);
  const uint32_t fullb = sbase + K4_ST * K4_STAGE + 2752, emptyb = fullb + 8 * K4_ST;
  const int tid = threadIdx.x, lane = tid & 31;
  const int warp = __shfl_sync(~0u, tid >> 5, 0);
  const int rank = blockIdx.x & 1, cl = blockIdx.x >> 1;
  const int n = cl & 7, m = (cl >> 3) * 2 + rank;
  const uint8_t* wb = (const uint8_t*)g_wgu + (size_t)n * 10 * 55296 + rank * 27648;
  const uint8_t* ab = (const uint8_t*)g_h + (size_t)m * 163840;
  if (tid == 0) STAMP(3, 0);
  if (tid == 0) {
    for (int i = 0; i < K4_ST; i++) { mbar_init(fullb + 8 * i, 1); mbar_init(emptyb + 8 * i, 4); }
    asm volatile("fence.mbarrier_init.release.cluster;" ::: "memory");
  }
  __syncthreads();
  cluster_arrive();
  const float cs0 = __ldcg(&g_csgu[(tid >= 216 ? F_ - 216 : 0) + n * 216 + tid]);
  const float cs1 = tid < 176 ? __ldcg(&g_csgu[F_ - 216 + n * 216 + 256 + tid]) : 0.f;
  cluster_wait();
  if (tid == 0) {
    for (int kt = 0; kt < K4_ST; kt++) mbar_expect(fullb + 8 * kt, K4_STAGE);
    bulk_ld_mc(sbase + 16384 + rank * 27648, wb, 27648, fullb);
  }
  pdl_wait();
  pdl_trigger();
  if (tid == 128) STAMP(3, 1);
  if (tid == 0) {
    bulk_ld(sbase, ab, 16384, fullb);
    for (int kt = 1; kt < K4_ST; kt++) {
      bulk_ld(sbase + kt * K4_STAGE, ab + kt * 16384, 16384, fullb + 8 * kt);
      bulk_ld_mc(sbase + kt * K4_STAGE + 16384 + rank * 27648, wb + kt * 55296, 27648, fullb + 8 * kt);
    }
  }
  if (tid >= 128) {
    const int r = tid - 128;
    float2 p[8];
#pragma unroll
    for (int i = 0; i < 8; i++) p[i] = __ldcg(&g_hpart[i * S_ + m * 128 + r]);
    float mean = 0.f, m2 = 0.f;
#pragma unroll
    for (int i = 0; i < 8; i++) { mean += p[i].x; m2 += p[i].y; }
    mean *= 0.125f;
#pragma unroll
    for (int i = 0; i < 8; i++) { const float d = p[i].x - mean; m2 = fmaf(80.f * d, d, m2); }
    rowst[r] = make_float2(-mean, __frcp_rn(m2 * (1.f / D_) + 1e-5f));
  }
  cs[tid] = cs0;
  if (tid < 176) cs[256 + tid] = cs1;
  __syncwarp();
  float ag[108], au[108];
  const uint64_t da0 = mkdesc(sbase + (warp >> 2) * 8192, 128, 1024, 0);
  const uint64_t db0 = mkdesc(sbase + 16384, 128, 1024, 0);
#pragma unroll 1
  for (int kt = 0; kt < 10; kt++) {
    const int s = kt % K4_ST;
    mbar_wait(fullb + 8 * s, (kt / K4_ST) & 1);
    if (kt == 0 && tid == 128) STAMP(3, 2);
    const uint64_t da = da0 + s * (K4_STAGE >> 4), db = db0 + s * (K4_STAGE >> 4);
    WG_FENCE();
#pragma unroll
    for (int k = 0; k < 4; k++) {
      wgmma_ss_n216(ag, da + k * 16, db + k * 16, (kt | k) != 0);
      wgmma_ss_n216(au, da + k * 16, db + 1728 + k * 16, (kt | k) != 0);
    }
    WG_COMMIT();
    if (kt > 0 && kt - 1 + K4_ST < 10) {
      WG_WAIT(1);
      const int sp = (kt - 1) % K4_ST;
      if ((tid & 127) < 2) mbar_arrive_cta(emptyb + 8 * sp, tid & 1);
      if (tid == 0) {
        const uint32_t sa = sbase + sp * K4_STAGE;
        mbar_wait(emptyb + 8 * sp, ((kt - 1) / K4_ST) & 1);
        mbar_expect(fullb + 8 * sp, K4_STAGE);
        bulk_ld_mc(sa + 16384 + rank * 27648, wb + (kt - 1 + K4_ST) * 55296, 27648, fullb + 8 * sp);
        bulk_ld(sa, ab + (kt - 1 + K4_ST) * 16384, 16384, fullb + 8 * sp);
      }
      __syncwarp();
    }
  }
  WG_WAIT(0);
  fence_regs(ag); fence_regs(au);
  if (tid == 128) STAMP(3, 3);
  __syncthreads();
  const int g = lane >> 2, c = lane & 3;
  const float2 st0 = rowst[warp * 16 + g], st1 = rowst[warp * 16 + g + 8];
  uint8_t* dst = (uint8_t*)g_hh + (size_t)m * 27 * 16384 + warp * 2048 + g * 16 + c * 4;
#pragma unroll
  for (int j = 0; j < 27; j++) {
    const float2 cg = *(const float2*)&cs[j * 8 + c * 2], cu = *(const float2*)&cs[216 + j * 8 + c * 2];
    const float h0 = fmaf(st0.x, cg.x, ag[4 * j]) * st0.y * fmaf(st0.x, cu.x, au[4 * j]);
    const float h1 = fmaf(st0.x, cg.y, ag[4 * j + 1]) * st0.y * fmaf(st0.x, cu.y, au[4 * j + 1]);
    const float h2 = fmaf(st1.x, cg.x, ag[4 * j + 2]) * st1.y * fmaf(st1.x, cu.x, au[4 * j + 2]);
    const float h3 = fmaf(st1.x, cg.y, ag[4 * j + 3]) * st1.y * fmaf(st1.x, cu.y, au[4 * j + 3]);
    *(uint32_t*)(dst + img_off(n * 27 + j)) = pack_bf16(h0, h1);
    *(uint32_t*)(dst + img_off(n * 27 + j) + 1024) = pack_bf16(h2, h3);
  }
  if (tid == 128) STAMP(3, 4);
  cluster_sync_relaxed();
}

typedef CUresult (*EncodeFn)(CUtensorMap*, CUtensorMapDataType, cuuint32_t, void*, const cuuint64_t*, const cuuint64_t*,
                             const cuuint32_t*, const cuuint32_t*, CUtensorMapInterleave, CUtensorMapSwizzle,
                             CUtensorMapL2promotion, CUtensorMapFloatOOBfill);

static CUtensorMap make_map(EncodeFn enc, const void* p, uint64_t inner, uint64_t outer, uint32_t box_inner,
                            uint32_t box_outer, CUtensorMapSwizzle swz) {
  CUtensorMap m;
  cuuint64_t gd[2] = {inner, outer};
  cuuint64_t gs[1] = {inner * 2};
  cuuint32_t bd[2] = {box_inner, box_outer};
  cuuint32_t es[2] = {1, 1};
  enc(&m, CU_TENSOR_MAP_DATA_TYPE_BFLOAT16, 2, (void*)p, gd, gs, bd, es, CU_TENSOR_MAP_INTERLEAVE_NONE, swz,
      CU_TENSOR_MAP_L2_PROMOTION_L2_256B, CU_TENSOR_MAP_FLOAT_OOB_FILL_NONE);
  return m;
}

template <typename... KArgs, typename... Args>
static void launch(void (*k)(KArgs...), int threads, int smem, bool pdl, Args... args) {
  cudaLaunchConfig_t cfg = {};
  cfg.gridDim = dim3(128);
  cfg.blockDim = dim3(threads);
  cfg.dynamicSmemBytes = smem;
  cfg.stream = cudaStreamPerThread;
  cudaLaunchAttribute at[1];
  at[0].id = cudaLaunchAttributeProgrammaticStreamSerialization;
  at[0].val.programmaticStreamSerializationAllowed = 1;
  cfg.attrs = at;
  cfg.numAttrs = pdl ? 1 : 0;
  cudaLaunchKernelEx(&cfg, k, KArgs(args)...);
}

extern "C" void kernel_launch(void* const* d_in, const int* in_sizes, int n_in, void* d_out, int out_size) {
  const bf16* x = (const bf16*)d_in[0];
  const bf16* wqkv = (const bf16*)d_in[1];
  const bf16* wo = (const bf16*)d_in[2];
  const bf16* wg = (const bf16*)d_in[4];
  const bf16* wu = (const bf16*)d_in[5];
  const bf16* wd = (const bf16*)d_in[6];

  static EncodeFn enc = nullptr;
  static void *p_o, *p_hh, *p_wo, *p_wd;
  if (!enc) {
    void* fn = nullptr;
    cudaDriverEntryPointQueryResult qr;
    cudaGetDriverEntryPoint("cuTensorMapEncodeTiled", &fn, cudaEnableDefault, &qr);
    enc = (EncodeFn)fn;
    cudaGetSymbolAddress(&p_o, g_o); cudaGetSymbolAddress(&p_hh, g_hh);
    cudaGetSymbolAddress(&p_wo, g_wo); cudaGetSymbolAddress(&p_wd, g_wd);
    cudaFuncSetAttribute(k1_qkv, cudaFuncAttributeMaxDynamicSharedMemorySize, K1_SMEM);
    cudaFuncSetAttribute(k2_attn, cudaFuncAttributeMaxDynamicSharedMemorySize, K2_SMEM + 512);
    cudaFuncSetAttribute(k3_proj<10, true>, cudaFuncAttributeMaxDynamicSharedMemorySize, K3_SMEM);
    cudaFuncSetAttribute(k3_proj<27, false>, cudaFuncAttributeMaxDynamicSharedMemorySize, K3_SMEM);
    cudaFuncSetAttribute(k4_ffn1, cudaFuncAttributeMaxDynamicSharedMemorySize, K4_SMEM);
  }
  const CUtensorMap tmx = make_map(enc, x, D_, S_, 64, 128, CU_TENSOR_MAP_SWIZZLE_128B);
  const CUtensorMap tmw = make_map(enc, wqkv, 3 * D_, D_, 32, 64, CU_TENSOR_MAP_SWIZZLE_64B);
  const CUtensorMap tmxr = make_map(enc, x, D_, S_, 80, 64, CU_TENSOR_MAP_SWIZZLE_NONE);
  const CUtensorMap tmout = make_map(enc, d_out, D_, S_, 80, 64, CU_TENSOR_MAP_SWIZZLE_NONE);

  launch(k1_qkv, 384, K1_SMEM, false, tmx, tmw, x, wqkv, wo);
  launch(k2_attn, 512, K2_SMEM + 512, true, wg, wu, wd, 0x007f007fu);
  launch(k3_proj<10, true>, 384, K3_SMEM, true, tmxr, (const uint4*)p_o, (const uint4*)p_wo);
  launch(k4_ffn1, 256, K4_SMEM, true);
  launch(k3_proj<27, false>, 384, K3_SMEM, true, tmout, (const uint4*)p_hh, (const uint4*)p_wd);
}
```

```cpp
#include <cuda_runtime.h>
#include <cuda_bf16.h>
#include <cuda.h>
#include <stdint.h>

typedef __nv_bfloat16 bf16;

constexpr int S_ = 2048, D_ = 640, F_ = 1728;
constexpr int HEAD_IMG = 98304;
constexpr uint32_t POLY_MASK = 0xBBAB;
constexpr float QSCALE = 0.22360679774997896f * 1.4426950408889634f;

__device__ __align__(1024) uint4 g_qkv[96 * HEAD_IMG / 16];
__device__ __align__(1024) uint4 g_o[S_ * D_ / 8];
__device__ __align__(1024) uint4 g_h[S_ * D_ / 8];
__device__ __align__(1024) uint4 g_hh[S_ * F_ / 8];
__device__ __align__(1024) uint4 g_wo[D_ * D_ / 8];
__device__ __align__(1024) uint4 g_wgu[2 * D_ * F_ / 8];
__device__ __align__(1024) uint4 g_wd[F_ * D_ / 8];
__device__ float2 g_rowstat[S_];
__device__ float g_cpart[16 * 2048];
__device__ float g_csgu[2 * F_];
__device__ float2 g_hpart[8 * S_];
__device__ unsigned g_cnt[24 * 32];

#define STAMP(k, i)
__device__ __forceinline__ uint32_t smem_u32(const void* p) { return (uint32_t)__cvta_generic_to_shared(p); }
__device__ __forceinline__ void mbar_init(uint32_t a, uint32_t c) {
  asm volatile("mbarrier.init.shared::cta.b64 [%0], %1;" ::"r"(a), "r"(c) : "memory");
}
__device__ __forceinline__ void mbar_expect(uint32_t a, uint32_t bytes) {
  asm volatile("mbarrier.arrive.expect_tx.shared::cta.b64 _, [%0], %1;" ::"r"(a), "r"(bytes) : "memory");
}
__device__ __forceinline__ void mbar_arrive(uint32_t a) {
  asm volatile("mbarrier.arrive.shared::cta.b64 _, [%0];" ::"r"(a) : "memory");
}
__device__ __forceinline__ void mbar_arrive_cta(uint32_t a, uint32_t cta) {
  asm volatile("{\n.reg .b32 r;\nmapa.shared::cluster.u32 r, %0, %1;\n"
               "mbarrier.arrive.shared::cluster.b64 _, [r];\n}" ::"r"(a), "r"(cta) : "memory");
}
__device__ __forceinline__ bool mbar_try(uint32_t a, uint32_t ph) {
  uint32_t ok;
  asm volatile("{\n.reg .pred p;\nmbarrier.try_wait.parity.shared::cta.b64 p, [%1], %2;\nselp.u32 %0, 1, 0, p;\n}"
               : "=r"(ok) : "r"(a), "r"(ph) : "memory");
  return ok;
}
__device__ __noinline__ void wait_timeout() { __trap(); }
__device__ __forceinline__ void mbar_wait(uint32_t a, uint32_t ph) {
  if (mbar_try(a, ph)) return;
  uint32_t it = 0;
  while (!mbar_try(a, ph)) if (++it > (1u << 22)) wait_timeout();
}
__device__ __forceinline__ void tma2d(uint32_t dst, const CUtensorMap* m, int c0, int c1, uint32_t bar) {
  asm volatile("cp.async.bulk.tensor.2d.shared::cluster.global.mbarrier::complete_tx::bytes [%0], [%1, {%3, %4}], [%2];"
               ::"r"(dst), "l"(m), "r"(bar), "r"(c0), "r"(c1) : "memory");
}
__device__ __forceinline__ void tma2d_mc(uint32_t dst, const CUtensorMap* m, int c0, int c1, uint32_t bar) {
  asm volatile("cp.async.bulk.tensor.2d.shared::cluster.global.mbarrier::complete_tx::bytes.multicast::cluster "
               "[%0], [%1, {%3, %4}], [%2], %5;"
               ::"r"(dst), "l"(m), "r"(bar), "r"(c0), "r"(c1), "h"((uint16_t)3) : "memory");
}
__device__ __forceinline__ void bulk_ld(uint32_t dst, const void* src, uint32_t bytes, uint32_t bar) {
  asm volatile("cp.async.bulk.shared::cluster.global.mbarrier::complete_tx::bytes [%0], [%1], %2, [%3];"
               ::"r"(dst), "l"(src), "r"(bytes), "r"(bar) : "memory");
}
__device__ __forceinline__ void bulk_ld_mc(uint32_t dst, const void* src, uint32_t bytes, uint32_t bar) {
  asm volatile("cp.async.bulk.shared::cluster.global.mbarrier::complete_tx::bytes.multicast::cluster "
               "[%0], [%1], %2, [%3], %4;"
               ::"r"(dst), "l"(src), "r"(bytes), "r"(bar), "h"((uint16_t)3) : "memory");
}
__device__ __forceinline__ void cluster_arrive() { asm volatile("barrier.cluster.arrive.relaxed.aligned;" ::: "memory"); }
__device__ __forceinline__ void cluster_wait() { asm volatile("barrier.cluster.wait.aligned;" ::: "memory"); }
__device__ __forceinline__ void bulk_st(void* dst, uint32_t src, uint32_t bytes) {
  asm volatile("cp.async.bulk.global.shared::cta.bulk_group [%0], [%1], %2;" ::"l"(dst), "r"(src), "r"(bytes) : "memory");
}
__device__ __forceinline__ void tma2d_st(const CUtensorMap* m, int c0, int c1, uint32_t src) {
  asm volatile("cp.async.bulk.tensor.2d.global.shared::cta.bulk_group [%0, {%2, %3}], [%1];"
               ::"l"(m), "r"(src), "r"(c0), "r"(c1) : "memory");
}
__device__ __forceinline__ void bulk_commit_wait() {
  asm volatile("cp.async.bulk.commit_group;\ncp.async.bulk.wait_group.read 0;" ::: "memory");
}
__device__ __forceinline__ uint32_t mapa(uint32_t a, uint32_t cta) {
  uint32_t r;
  asm("mapa.shared::cluster.u32 %0, %1, %2;" : "=r"(r) : "r"(a), "r"(cta));
  return r;
}
__device__ __forceinline__ void st_async4(uint32_t dst, float a, float b, float c, float d, uint32_t bar) {
  asm volatile("st.async.shared::cluster.mbarrier::complete_tx::bytes.v4.f32 [%0], {%1, %2, %3, %4}, [%5];"
               ::"r"(dst), "f"(a), "f"(b), "f"(c), "f"(d), "r"(bar) : "memory");
}
__device__ __forceinline__ void fence_async() { asm volatile("fence.proxy.async.shared::cta;" ::: "memory"); }
__device__ __forceinline__ void prefetch_map(const CUtensorMap* m) {
  asm volatile("prefetch.tensormap [%0];" ::"l"(m) : "memory");
}
__device__ __forceinline__ void cluster_sync_relaxed() {
  __syncwarp();
  asm volatile("barrier.cluster.arrive.relaxed.aligned;\nbarrier.cluster.wait.aligned;" ::: "memory");
}
__device__ __forceinline__ void pdl_wait() { asm volatile("griddepcontrol.wait;" ::: "memory"); }
__device__ __forceinline__ void pdl_trigger() { asm volatile("griddepcontrol.launch_dependents;" ::: "memory"); }
__device__ __forceinline__ void bar_sync(int id, int n) { asm volatile("bar.sync %0, %1;" ::"r"(id), "r"(n) : "memory"); }
__device__ __forceinline__ void bar_arrive(int id, int n) { asm volatile("bar.arrive %0, %1;" ::"r"(id), "r"(n) : "memory"); }
#define WG_FENCE() asm volatile("wgmma.fence.sync.aligned;" ::: "memory")
#define WG_COMMIT() asm volatile("wgmma.commit_group.sync.aligned;" ::: "memory")
#define WG_WAIT(n) asm volatile("wgmma.wait_group.sync.aligned %0;" ::"n"(n) : "memory")
__device__ __forceinline__ uint64_t mkdesc(uint32_t addr, uint32_t lbo, uint32_t sbo, uint32_t sw) {
  return (uint64_t)((addr & 0x3FFFF) >> 4) | ((uint64_t)(lbo >> 4) << 16) | ((uint64_t)(sbo >> 4) << 32) |
         ((uint64_t)sw << 62);
}
template <int N> __device__ __forceinline__ void fence_regs(float (&r)[N]) {
#pragma unroll
  for (int i = 0; i < N; i++) asm volatile("" : "+f"(r[i])::"memory");
}
__device__ __forceinline__ uint32_t pack_bf16(float lo, float hi) {
  uint32_t r;
  asm("cvt.rn.bf16x2.f32 %0, %1, %2;" : "=r"(r) : "f"(hi), "f"(lo));
  return r;
}
__device__ __forceinline__ float bf_lo(uint32_t v) { return __uint_as_float(v << 16); }
__device__ __forceinline__ float bf_hi(uint32_t v) { return __uint_as_float(v & 0xffff0000u); }
__device__ __forceinline__ float ex2(float x) {
  float y;
  asm("ex2.approx.ftz.f32 %0, %1;" : "=f"(y) : "f"(x));
  return y;
}
__device__ __forceinline__ uint4 ldg_nc(const void* p) {
  uint4 v;
  asm volatile("ld.global.nc.L1::no_allocate.v4.u32 {%0, %1, %2, %3}, [%4];"
               : "=r"(v.x), "=r"(v.y), "=r"(v.z), "=r"(v.w) : "l"(p));
  return v;
}

__device__ __forceinline__ void wgmma_ss_n240(float (&d)[120], uint64_t da, uint64_t db, int sd) {
  asm volatile("{\n.reg .pred p;\nsetp.ne.b32 p, %122, 0;\n"
      "wgmma.mma_async.sync.aligned.m64n240k16.f32.bf16.bf16 {"
      "%0, %1, %2, %3, %4, %5, %6, %7, %8, %9, %10, %11, %12, %13, %14, %15, "
      "%16, %17, %18, %19, %20, %21, %22, %23, %24, %25, %26, %27, %28, %29, %30, %31, "
      "%32, %33, %34, %35, %36, %37, %38, %39, %40, %41, %42, %43, %44, %45, %46, %47, "
      "%48, %49, %50, %51, %52, %53, %54, %55, %56, %57, %58, %59, %60, %61, %62, %63, "
      "%64, %65, %66, %67, %68, %69, %70, %71, %72, %73, %74, %75, %76, %77, %78, %79, "
      "%80, %81, %82, %83, %84, %85, %86, %87, %88, %89, %90, %91, %92, %93, %94, %95, "
      "%96, %97, %98, %99, %100, %101, %102, %103, %104, %105, %106, %107, %108, %109, %110, %111, "
      "%112, %113, %114, %115, %116, %117, %118, %119"
      "}, %120, %121, p, 1, 1, 0, 1;\n}\n"
    : "+f"(d[0]), "+f"(d[1]), "+f"(d[2]), "+f"(d[3]), "+f"(d[4]), "+f"(d[5]), "+f"(d[6]), "+f"(d[7]),
      "+f"(d[8]), "+f"(d[9]), "+f"(d[10]), "+f"(d[11]), "+f"(d[12]), "+f"(d[13]), "+f"(d[14]), "+f"(d[15]),
      "+f"(d[16]), "+f"(d[17]), "+f"(d[18]), "+f"(d[19]), "+f"(d[20]), "+f"(d[21]), "+f"(d[22]), "+f"(d[23]),
      "+f"(d[24]), "+f"(d[25]), "+f"(d[26]), "+f"(d[27]), "+f"(d[28]), "+f"(d[29]), "+f"(d[30]), "+f"(d[31]),
      "+f"(d[32]), "+f"(d[33]), "+f"(d[34]), "+f"(d[35]), "+f"(d[36]), "+f"(d[37]), "+f"(d[38]), "+f"(d[39]),
      "+f"(d[40]), "+f"(d[41]), "+f"(d[42]), "+f"(d[43]), "+f"(d[44]), "+f"(d[45]), "+f"(d[46]), "+f"(d[47]),
      "+f"(d[48]), "+f"(d[49]), "+f"(d[50]), "+f"(d[51]), "+f"(d[52]), "+f"(d[53]), "+f"(d[54]), "+f"(d[55]),
      "+f"(d[56]), "+f"(d[57]), "+f"(d[58]), "+f"(d[59]), "+f"(d[60]), "+f"(d[61]), "+f"(d[62]), "+f"(d[63]),
      "+f"(d[64]), "+f"(d[65]), "+f"(d[66]), "+f"(d[67]), "+f"(d[68]), "+f"(d[69]), "+f"(d[70]), "+f"(d[71]),
      "+f"(d[72]), "+f"(d[73]), "+f"(d[74]), "+f"(d[75]), "+f"(d[76]), "+f"(d[77]), "+f"(d[78]), "+f"(d[79]),
      "+f"(d[80]), "+f"(d[81]), "+f"(d[82]), "+f"(d[83]), "+f"(d[84]), "+f"(d[85]), "+f"(d[86]), "+f"(d[87]),
      "+f"(d[88]), "+f"(d[89]), "+f"(d[90]), "+f"(d[91]), "+f"(d[92]), "+f"(d[93]), "+f"(d[94]), "+f"(d[95]),
      "+f"(d[96]), "+f"(d[97]), "+f"(d[98]), "+f"(d[99]), "+f"(d[100]), "+f"(d[101]), "+f"(d[102]), "+f"(d[103]),
      "+f"(d[104]), "+f"(d[105]), "+f"(d[106]), "+f"(d[107]), "+f"(d[108]), "+f"(d[109]), "+f"(d[110]), "+f"(d[111]),
      "+f"(d[112]), "+f"(d[113]), "+f"(d[114]), "+f"(d[115]), "+f"(d[116]), "+f"(d[117]), "+f"(d[118]), "+f"(d[119])
    : "l"(da), "l"(db), "r"(sd));
}
__device__ __forceinline__ void wgmma_ss_n216(float (&d)[108], uint64_t da, uint64_t db, int sd) {
  asm volatile("{\n.reg .pred p;\nsetp.ne.b32 p, %110, 0;\n"
      "wgmma.mma_async.sync.aligned.m64n216k16.f32.bf16.bf16 {"
      "%0, %1, %2, %3, %4, %5, %6, %7, %8, %9, %10, %11, %12, %13, %14, %15, "
      "%16, %17, %18, %19, %20, %21, %22, %23, %24, %25, %26, %27, %28, %29, %30, %31, "
      "%32, %33, %34, %35, %36, %37, %38, %39, %40, %41, %42, %43, %44, %45, %46, %47, "
      "%48, %49, %50, %51, %52, %53, %54, %55, %56, %57, %58, %59, %60, %61, %62, %63, "
      "%64, %65, %66, %67, %68, %69, %70, %71, %72, %73, %74, %75, %76, %77, %78, %79, "
      "%80, %81, %82, %83, %84, %85, %86, %87, %88, %89, %90, %91, %92, %93, %94, %95, "
      "%96, %97, %98, %99, %100, %101, %102, %103, %104, %105, %106, %107"
      "}, %108, %109, p, 1, 1, 0, 1;\n}\n"
    : "+f"(d[0]), "+f"(d[1]), "+f"(d[2]), "+f"(d[3]), "+f"(d[4]), "+f"(d[5]), "+f"(d[6]), "+f"(d[7]),
      "+f"(d[8]), "+f"(d[9]), "+f"(d[10]), "+f"(d[11]), "+f"(d[12]), "+f"(d[13]), "+f"(d[14]), "+f"(d[15]),
      "+f"(d[16]), "+f"(d[17]), "+f"(d[18]), "+f"(d[19]), "+f"(d[20]), "+f"(d[21]), "+f"(d[22]), "+f"(d[23]),
      "+f"(d[24]), "+f"(d[25]), "+f"(d[26]), "+f"(d[27]), "+f"(d[28]), "+f"(d[29]), "+f"(d[30]), "+f"(d[31]),
      "+f"(d[32]), "+f"(d[33]), "+f"(d[34]), "+f"(d[35]), "+f"(d[36]), "+f"(d[37]), "+f"(d[38]), "+f"(d[39]),
      "+f"(d[40]), "+f"(d[41]), "+f"(d[42]), "+f"(d[43]), "+f"(d[44]), "+f"(d[45]), "+f"(d[46]), "+f"(d[47]),
      "+f"(d[48]), "+f"(d[49]), "+f"(d[50]), "+f"(d[51]), "+f"(d[52]), "+f"(d[53]), "+f"(d[54]), "+f"(d[55]),
      "+f"(d[56]), "+f"(d[57]), "+f"(d[58]), "+f"(d[59]), "+f"(d[60]), "+f"(d[61]), "+f"(d[62]), "+f"(d[63]),
      "+f"(d[64]), "+f"(d[65]), "+f"(d[66]), "+f"(d[67]), "+f"(d[68]), "+f"(d[69]), "+f"(d[70]), "+f"(d[71]),
      "+f"(d[72]), "+f"(d[73]), "+f"(d[74]), "+f"(d[75]), "+f"(d[76]), "+f"(d[77]), "+f"(d[78]), "+f"(d[79]),
      "+f"(d[80]), "+f"(d[81]), "+f"(d[82]), "+f"(d[83]), "+f"(d[84]), "+f"(d[85]), "+f"(d[86]), "+f"(d[87]),
      "+f"(d[88]), "+f"(d[89]), "+f"(d[90]), "+f"(d[91]), "+f"(d[92]), "+f"(d[93]), "+f"(d[94]), "+f"(d[95]),
      "+f"(d[96]), "+f"(d[97]), "+f"(d[98]), "+f"(d[99]), "+f"(d[100]), "+f"(d[101]), "+f"(d[102]), "+f"(d[103]),
      "+f"(d[104]), "+f"(d[105]), "+f"(d[106]), "+f"(d[107])
    : "l"(da), "l"(db), "r"(sd));
}
__device__ __forceinline__ void wgmma_ss_n160(float (&d)[80], uint64_t da, uint64_t db, int sd) {
  asm volatile("{\n.reg .pred p;\nsetp.ne.b32 p, %82, 0;\n"
      "wgmma.mma_async.sync.aligned.m64n160k16.f32.bf16.bf16 {"
      "%0, %1, %2, %3, %4, %5, %6, %7, %8, %9, %10, %11, %12, %13, %14, %15, "
      "%16, %17, %18, %19, %20, %21, %22, %23, %24, %25, %26, %27, %28, %29, %30, %31, "
      "%32, %33, %34, %35, %36, %37, %38, %39, %40, %41, %42, %43, %44, %45, %46, %47, "
      "%48, %49, %50, %51, %52, %53, %54, %55, %56, %57, %58, %59, %60, %61, %62, %63, "
      "%64, %65, %66, %67, %68, %69, %70, %71, %72, %73, %74, %75, %76, %77, %78, %79"
      "}, %80, %81, p, 1, 1, 0, 1;\n}\n"
    : "+f"(d[0]), "+f"(d[1]), "+f"(d[2]), "+f"(d[3]), "+f"(d[4]), "+f"(d[5]), "+f"(d[6]), "+f"(d[7]),
      "+f"(d[8]), "+f"(d[9]), "+f"(d[10]), "+f"(d[11]), "+f"(d[12]), "+f"(d[13]), "+f"(d[14]), "+f"(d[15]),
      "+f"(d[16]), "+f"(d[17]), "+f"(d[18]), "+f"(d[19]), "+f"(d[20]), "+f"(d[21]), "+f"(d[22]), "+f"(d[23]),
      "+f"(d[24]), "+f"(d[25]), "+f"(d[26]), "+f"(d[27]), "+f"(d[28]), "+f"(d[29]), "+f"(d[30]), "+f"(d[31]),
      "+f"(d[32]), "+f"(d[33]), "+f"(d[34]), "+f"(d[35]), "+f"(d[36]), "+f"(d[37]), "+f"(d[38]), "+f"(d[39]),
      "+f"(d[40]), "+f"(d[41]), "+f"(d[42]), "+f"(d[43]), "+f"(d[44]), "+f"(d[45]), "+f"(d[46]), "+f"(d[47]),
      "+f"(d[48]), "+f"(d[49]), "+f"(d[50]), "+f"(d[51]), "+f"(d[52]), "+f"(d[53]), "+f"(d[54]), "+f"(d[55]),
      "+f"(d[56]), "+f"(d[57]), "+f"(d[58]), "+f"(d[59]), "+f"(d[60]), "+f"(d[61]), "+f"(d[62]), "+f"(d[63]),
      "+f"(d[64]), "+f"(d[65]), "+f"(d[66]), "+f"(d[67]), "+f"(d[68]), "+f"(d[69]), "+f"(d[70]), "+f"(d[71]),
      "+f"(d[72]), "+f"(d[73]), "+f"(d[74]), "+f"(d[75]), "+f"(d[76]), "+f"(d[77]), "+f"(d[78]), "+f"(d[79])
    : "l"(da), "l"(db), "r"(sd));
}
__device__ __forceinline__ void wgmma_rs_n128(float (&d)[64], uint32_t a0, uint32_t a1, uint32_t a2, uint32_t a3,
                                  uint64_t db, int sd) {
  asm volatile("{\n.reg .pred p;\nsetp.ne.b32 p, %69, 0;\n"
      "wgmma.mma_async.sync.aligned.m64n128k16.f32.bf16.bf16 {"
      "%0, %1, %2, %3, %4, %5, %6, %7, %8, %9, %10, %11, %12, %13, %14, %15, "
      "%16, %17, %18, %19, %20, %21, %22, %23, %24, %25, %26, %27, %28, %29, %30, %31, "
      "%32, %33, %34, %35, %36, %37, %38, %39, %40, %41, %42, %43, %44, %45, %46, %47, "
      "%48, %49, %50, %51, %52, %53, %54, %55, %56, %57, %58, %59, %60, %61, %62, %63"
      "}, {%64, %65, %66, %67}, %68, p, 1, 1, 0;\n}\n"
    : "+f"(d[0]), "+f"(d[1]), "+f"(d[2]), "+f"(d[3]), "+f"(d[4]), "+f"(d[5]), "+f"(d[6]), "+f"(d[7]),
      "+f"(d[8]), "+f"(d[9]), "+f"(d[10]), "+f"(d[11]), "+f"(d[12]), "+f"(d[13]), "+f"(d[14]), "+f"(d[15]),
      "+f"(d[16]), "+f"(d[17]), "+f"(d[18]), "+f"(d[19]), "+f"(d[20]), "+f"(d[21]), "+f"(d[22]), "+f"(d[23]),
      "+f"(d[24]), "+f"(d[25]), "+f"(d[26]), "+f"(d[27]), "+f"(d[28]), "+f"(d[29]), "+f"(d[30]), "+f"(d[31]),
      "+f"(d[32]), "+f"(d[33]), "+f"(d[34]), "+f"(d[35]), "+f"(d[36]), "+f"(d[37]), "+f"(d[38]), "+f"(d[39]),
      "+f"(d[40]), "+f"(d[41]), "+f"(d[42]), "+f"(d[43]), "+f"(d[44]), "+f"(d[45]), "+f"(d[46]), "+f"(d[47]),
      "+f"(d[48]), "+f"(d[49]), "+f"(d[50]), "+f"(d[51]), "+f"(d[52]), "+f"(d[53]), "+f"(d[54]), "+f"(d[55]),
      "+f"(d[56]), "+f"(d[57]), "+f"(d[58]), "+f"(d[59]), "+f"(d[60]), "+f"(d[61]), "+f"(d[62]), "+f"(d[63])
    : "r"(a0), "r"(a1), "r"(a2), "r"(a3), "l"(db), "r"(sd));
}
__device__ __forceinline__ void wgmma_rs_n24(float (&d)[12], uint32_t a0, uint32_t a1, uint32_t a2, uint32_t a3,
                                  uint64_t db, int sd) {
  asm volatile("{\n.reg .pred p;\nsetp.ne.b32 p, %17, 0;\n"
      "wgmma.mma_async.sync.aligned.m64n24k16.f32.bf16.bf16 {"
      "%0, %1, %2, %3, %4, %5, %6, %7, %8, %9, %10, %11"
      "}, {%12, %13, %14, %15}, %16, p, 1, 1, 1;\n}\n"
    : "+f"(d[0]), "+f"(d[1]), "+f"(d[2]), "+f"(d[3]), "+f"(d[4]), "+f"(d[5]), "+f"(d[6]), "+f"(d[7]),
      "+f"(d[8]), "+f"(d[9]), "+f"(d[10]), "+f"(d[11])
    : "r"(a0), "r"(a1), "r"(a2), "r"(a3), "l"(db), "r"(sd));
}

constexpr int K1_ST = 4, K1_STAGE = 49152;
constexpr int K1_SMEM = K1_ST * K1_STAGE + 1024   + 1024   + 3072   + 128;

__global__ void __cluster_dims__(2, 1, 1) __launch_bounds__(384, 1)
k1_qkv(const __grid_constant__ CUtensorMap tmx, const __grid_constant__ CUtensorMap tmw,
       const bf16* __restrict__ x, const bf16* __restrict__ w, const bf16* __restrict__ wo) {
  extern __shared__ __align__(1024) uint8_t sm[];
  float* cs = (float*)(sm + K1_ST * K1_STAGE);
  float2* rowab = (float2*)(sm + K1_ST * K1_STAGE + 1024);
  float* red = (float*)(sm + K1_ST * K1_STAGE + 2048);
  const uint32_t sbase = smem_u32(sm);
  const uint32_t fullb = sbase + K1_ST * K1_STAGE + 5120, emptyb = fullb + 8 * K1_ST;
  const int tid = threadIdx.x, lane = tid & 31;
  const int warp = __shfl_sync(~0u, tid >> 5, 0);
  const int rank = blockIdx.x & 1, cl = blockIdx.x >> 1;
  const int n = cl & 7, m = (cl >> 3) * 2 + rank;
  if (tid == 0) STAMP(0, 0);

  if (warp == 0) {
    if (lane == 0) {
      prefetch_map(&tmx); prefetch_map(&tmw);
      for (int i = 0; i < K1_ST; i++) { mbar_init(fullb + 8 * i, 1); mbar_init(emptyb + 8 * i, 4); }
      asm volatile("fence.mbarrier_init.release.cluster;" ::: "memory");
    }
    __syncwarp();
    cluster_arrive();
    bar_arrive(4, 256 + 32);
    if (lane == 0) {
      for (int kt = 0; kt < K1_ST; kt++) {
        mbar_expect(fullb + 8 * kt, K1_STAGE);
        tma2d(sbase + kt * K1_STAGE, &tmx, kt * 64, m * 128, fullb + 8 * kt);
      }
    }
    __syncwarp();
    cluster_wait();
    if (tid == 0) STAMP(5, 3);
    if (lane == 0) {
      for (int kt = 0; kt < 10; kt++) {
        const int s = kt % K1_ST;
        const uint32_t sa = sbase + s * K1_STAGE, sb = sa + 16384 + rank * 16384;
        if (kt >= K1_ST) {
          mbar_wait(emptyb + 8 * s, ((kt / K1_ST) - 1) & 1);
          mbar_expect(fullb + 8 * s, K1_STAGE);
          tma2d(sa, &tmx, kt * 64, m * 128, fullb + 8 * s);
        }
#pragma unroll
        for (int j = 0; j < 4; j++) tma2d_mc(sb + j * 4096, &tmw, n * 240 + rank * 128 + j * 32, kt * 64, fullb + 8 * s);
        if (kt == K1_ST - 1) pdl_trigger();
      }
    }
    __syncwarp();
  } else if (warp < 4) {
    cluster_arrive();
    const int w3 = warp - 1, t96 = tid - 32;
    {
      uint4 wv[14];
#pragma unroll
      for (int i = 0; i < 14; i++)
        wv[i] = ldg_nc(w + (size_t)(m * 40 + min(w3 + 3 * i, 39)) * 1920 + n * 240 + min(lane, 29) * 8);
      float acc8[8];
#pragma unroll
      for (int i = 0; i < 8; i++) acc8[i] = 0.f;
#pragma unroll
      for (int i = 0; i < 14; i++) {
        if (i < 13 || w3 == 0) {
          const uint4 v = wv[i];
          acc8[0] += bf_lo(v.x); acc8[1] += bf_hi(v.x); acc8[2] += bf_lo(v.y); acc8[3] += bf_hi(v.y);
          acc8[4] += bf_lo(v.z); acc8[5] += bf_hi(v.z); acc8[6] += bf_lo(v.w); acc8[7] += bf_hi(v.w);
        }
      }
      *(float4*)&red[w3 * 256 + lane * 8] = make_float4(acc8[0], acc8[1], acc8[2], acc8[3]);
      *(float4*)&red[w3 * 256 + lane * 8 + 4] = make_float4(acc8[4], acc8[5], acc8[6], acc8[7]);
    }
    bar_sync(1, 96);
    if (t96 < 64) {
      const float4 p0 = *(const float4*)&red[t96 * 4], p1 = *(const float4*)&red[256 + t96 * 4], p2 = *(const float4*)&red[512 + t96 * 4];
      *(float4*)&g_cpart[m * 2048 + n * 256 + t96 * 4] = make_float4(p0.x + p1.x + p2.x, p0.y + p1.y + p2.y, p0.z + p1.z + p2.z, p0.w + p1.w + p2.w);
    }
    bar_sync(3, 96 + 256);
    if (tid == 32) STAMP(5, 7);
    if (t96 == 0) {
      __threadfence();
      asm volatile("red.relaxed.gpu.global.add.u32 [%0], 1;" ::"l"(&g_cnt[m * 32]) : "memory");
      asm volatile("red.relaxed.gpu.global.add.u32 [%0], 1;" ::"l"(&g_cnt[(16 + n) * 32]) : "memory");
      uint32_t a, b, it = 0;
      while (true) {
        asm volatile("ld.acquire.gpu.global.u32 %0, [%1];" : "=r"(a) : "l"(&g_cnt[m * 32]) : "memory");
        asm volatile("ld.acquire.gpu.global.u32 %0, [%1];" : "=r"(b) : "l"(&g_cnt[(16 + n) * 32]) : "memory");
        if (a >= 8 && b >= 16) break;
        if (++it > (1u << 22)) wait_timeout();
      }
    }
    bar_sync(1, 96);
    if (t96 < 64) {
      float4 p[16];
#pragma unroll
      for (int i = 0; i < 16; i++) p[i] = __ldcg((const float4*)&g_cpart[i * 2048 + n * 256 + t96 * 4]);
      float4 t = p[0];
#pragma unroll
      for (int i = 1; i < 16; i++) { t.x += p[i].x; t.y += p[i].y; t.z += p[i].z; t.w += p[i].w; }
      *(float4*)&cs[t96 * 4] = t;
    } else {
#pragma unroll
      for (int i = 0; i < 2; i++) {
        const float4 st = __ldcg((const float4*)&g_rowstat[m * 128 + i * 64 + lane * 2]);
        *(float4*)&rowab[i * 64 + lane * 2] = make_float4(st.x, -st.x * st.y, st.z, -st.z * st.w);
      }
    }
    bar_arrive(2, 96 + 256);
    if (tid == 32) STAMP(0, 5);
    {
      uint4 v[5];
      if (t96 < 80) {
#pragma unroll
        for (int i = 0; i < 5; i++) {
          const int k = blockIdx.x * 5 + i, pr = k / 40, r = k - pr * 40;
          v[i] = ldg_nc(wo + (size_t)(pr * 40 + (r < 16 ? r : (r < 32 ? r + 4 : (r < 36 ? r - 16 : r)))) * D_ + t96 * 8);
        }
        const int nt = t96 / 10;
#pragma unroll
        for (int i = 0; i < 5; i++) {
          const int k = blockIdx.x * 5 + i;
          g_wo[((nt * 10 + (k >> 6)) * 10 + t96 - nt * 10) * 64 + (k & 63)] = v[i];
        }
      }
    }
    __syncwarp();
    cluster_wait();
  } else {
    cluster_arrive();
    const int cw = warp - 4, wg = cw >> 2;
    {
      uint4 xv[2][3];
#pragma unroll
      for (int i = 0; i < 2; i++) {
        const bf16* xr = x + (size_t)(m * 128 + n * 16 + cw * 2 + i) * D_ + lane * 8;
        xv[i][0] = ldg_nc(xr);
        xv[i][1] = ldg_nc(xr + 256);
        xv[i][2] = ldg_nc(xr + (lane < 16 ? 512 : 0));
      }
#pragma unroll
      for (int i = 0; i < 2; i++) {
        float f[24];
#pragma unroll
        for (int k = 0; k < 3; k++) {
          const uint4 v = xv[i][k];
          f[8 * k + 0] = bf_lo(v.x); f[8 * k + 1] = bf_hi(v.x); f[8 * k + 2] = bf_lo(v.y); f[8 * k + 3] = bf_hi(v.y);
          f[8 * k + 4] = bf_lo(v.z); f[8 * k + 5] = bf_hi(v.z); f[8 * k + 6] = bf_lo(v.w); f[8 * k + 7] = bf_hi(v.w);
        }
        float s = 0.f, s2 = 0.f;
#pragma unroll
        for (int k = 0; k < 16; k++) s += f[k];
#pragma unroll
        for (int k = 16; k < 24; k++) s2 += f[k];
        if (lane < 16) s += s2;
#pragma unroll
        for (int o = 16; o; o >>= 1) s += __shfl_xor_sync(~0u, s, o);
        const float mean = s * (1.f / D_);
        float q = 0.f, q2 = 0.f;
#pragma unroll
        for (int k = 0; k < 16; k++) { float d = f[k] - mean; q = fmaf(d, d, q); }
#pragma unroll
        for (int k = 16; k < 24; k++) { float d = f[k] - mean; q2 = fmaf(d, d, q2); }
        if (lane < 16) q += q2;
#pragma unroll
        for (int o = 16; o; o >>= 1) q += __shfl_xor_sync(~0u, q, o);
        if (lane == 0) g_rowstat[m * 128 + n * 16 + cw * 2 + i] = make_float2(rsqrtf(q * (1.f / D_) + 1e-5f), mean);
      }
      bar_arrive(3, 96 + 256);
      if (tid == 128) STAMP(5, 2);
    }
    float acc[120];
    const uint64_t da0 = mkdesc(sbase + wg * 8192, 16, 1024, 1);
    const uint64_t db0 = mkdesc(sbase + 16384, 4096, 512, 2);
    bar_sync(4, 256 + 32);
    cluster_wait();
#pragma unroll 1
    for (int kt = 0; kt < 10; kt++) {
      const int s = kt % K1_ST;
      mbar_wait(fullb + 8 * s, (kt / K1_ST) & 1);
      if (kt == 0 && tid == 128) STAMP(0, 1);
      const uint64_t da = da0 + s * (K1_STAGE >> 4), db = db0 + s * (K1_STAGE >> 4);
      WG_FENCE();
#pragma unroll
      for (int k = 0; k < 4; k++) wgmma_ss_n240(acc, da + k * 2, db + k * 64, (kt | k) != 0);
      WG_COMMIT();
      if (kt > 0) {
        WG_WAIT(1);
        if (kt - 1 + K1_ST < 10 && (tid & 127) < 2) mbar_arrive_cta(emptyb + 8 * ((kt - 1) % K1_ST), tid & 1);
      }
    }
    WG_WAIT(0);
    fence_regs(acc);
    if (tid == 128) STAMP(0, 2);
    bar_sync(2, 96 + 256);
    if (tid == 128) STAMP(0, 3);
    const int g = lane >> 2, c = lane & 3;
    const bool lo = c < 2;
    const float2 ab0 = rowab[cw * 16 + g], ab1 = rowab[cw * 16 + g + 8];
    const bool p0 = (POLY_MASK >> (cw * 2)) & 1, p1 = (POLY_MASK >> (cw * 2 + 1)) & 1;
    const uint32_t padq = c == 2 ? 0x3F803F80u : 0x00003F80u, padk = c == 2 ? 0x4A7A4B00u : 0x00004653u;
    const uint32_t padv = c == 2 ? 0x00003F80u : 0u;
    uint8_t* dst = (uint8_t*)g_qkv + (size_t)(n * 12) * HEAD_IMG + (m * 16 + cw * 2) * 384 + g * 16 + c * 4;
#pragma unroll
    for (int hp = 0; hp < 6; hp++) {
      const int sec = (n * 12 + hp * 2) >> 5;
      const float f0 = sec == 0 ? QSCALE : (sec == 1 && p0 ? 32768.f : 1.f), f1 = sec == 0 ? QSCALE : (sec == 1 && p1 ? 32768.f : 1.f);
      const uint32_t pad0 = sec == 0 ? padq : (sec == 2 ? padv : (p0 ? padk : 0u));
      const uint32_t pad1 = sec == 0 ? padq : (sec == 2 ? padv : (p1 ? padk : 0u));
      const float a0 = ab0.x * f0, b0 = ab0.y * f0, a1 = ab1.x * f1, b1 = ab1.y * f1;
      uint32_t u[5], v[5];
#pragma unroll
      for (int i = 0; i < 5; i++) {
        const int j = hp * 5 + i;
        const float2 t = *(const float2*)&cs[j * 8 + c * 2];
        u[i] = pack_bf16(fmaf(acc[4 * j], a0, b0 * t.x), fmaf(acc[4 * j + 1], a0, b0 * t.y));
        v[i] = pack_bf16(fmaf(acc[4 * j + 2], a1, b1 * t.x), fmaf(acc[4 * j + 3], a1, b1 * t.y));
      }
      uint8_t* pe = dst + (size_t)hp * 2 * HEAD_IMG;
      uint8_t* po = pe + HEAD_IMG;
      *(uint32_t*)(pe) = u[0];       *(uint32_t*)(pe + 384) = v[0];
      *(uint32_t*)(pe + 128) = u[1]; *(uint32_t*)(pe + 512) = v[1];
      *(uint32_t*)(pe + 256) = lo ? u[2] : pad0; *(uint32_t*)(pe + 640) = lo ? v[2] : pad1;
      *(uint32_t*)(po) = __shfl_xor_sync(~0u, lo ? u[3] : u[2], 2);
      *(uint32_t*)(po + 384) = __shfl_xor_sync(~0u, lo ? v[3] : v[2], 2);
      *(uint32_t*)(po + 128) = __shfl_xor_sync(~0u, lo ? u[4] : u[3], 2);
      *(uint32_t*)(po + 512) = __shfl_xor_sync(~0u, lo ? v[4] : v[3], 2);
      const uint32_t tu = __shfl_xor_sync(~0u, u[4], 2), tv = __shfl_xor_sync(~0u, v[4], 2);
      *(uint32_t*)(po + 256) = lo ? tu : pad0; *(uint32_t*)(po + 640) = lo ? tv : pad1;
    }
    if (tid == 128) STAMP(0, 4);
  }
  cluster_sync_relaxed();
  if (tid == 128) STAMP(0, 6);
}

constexpr int K2_SMEM = 2 * HEAD_IMG + 2 * 6144 + 256;

__device__ __forceinline__ uint32_t exp_pair(bool poly, float a, float b, uint32_t mk) {
  if (poly) {
    const uint32_t pk = __byte_perm(__float_as_uint(a), __float_as_uint(b), 0x6521);
    uint32_t m, q;
    asm("lop3.b32 %0, %1, %2, 0x3f803f80, 0xEA;" : "=r"(m) : "r"(pk), "r"(mk));
    asm("fma.rn.bf16x2 %0, %1, %1, %2;" : "=r"(q) : "r"(m), "r"(0x40014001u));
    return pk - m + q;
  }
  return pack_bf16(ex2(a), ex2(b));
}
__device__ __forceinline__ void exp_pv(const float (&s)[64], float (&o)[12], uint64_t dv, uint32_t mk) {
#pragma unroll
  for (int k0 = 0; k0 < 8; k0 += 2) {
    uint32_t p[8];
#pragma unroll
    for (int i = 0; i < 8; i++)
      p[i] = exp_pair((POLY_MASK >> (k0 * 2 + i / 2)) & 1, s[k0 * 8 + 2 * i], s[k0 * 8 + 2 * i + 1], mk);
    WG_FENCE();
    wgmma_rs_n24(o, p[0], p[1], p[2], p[3], dv + k0 * 48, 1);
    wgmma_rs_n24(o, p[4], p[5], p[6], p[7], dv + k0 * 48 + 48, 1);
  }
}
__device__ __forceinline__ void load_q(uint32_t (&q)[6], const uint8_t* p) {
  q[0] = __ldcg((const uint32_t*)p);         q[1] = __ldcg((const uint32_t*)(p + 384));
  q[2] = __ldcg((const uint32_t*)(p + 128)); q[3] = __ldcg((const uint32_t*)(p + 512));
  q[4] = __ldcg((const uint32_t*)(p + 256)); q[5] = __ldcg((const uint32_t*)(p + 640));
}
__device__ __forceinline__ void store_o(const float (&o)[12], uint8_t* dst, int o0, int o1, int o2, int lane) {
  const float l0 = __shfl_sync(~0u, o[8], (lane & ~3) | 2), l1 = __shfl_sync(~0u, o[10], (lane & ~3) | 2);
  const float i0 = __frcp_rn(l0), i1 = __frcp_rn(l1);
  *(uint32_t*)(dst + o0) = pack_bf16(o[0] * i0, o[1] * i0); *(uint32_t*)(dst + o0 + 1024) = pack_bf16(o[2] * i1, o[3] * i1);
  *(uint32_t*)(dst + o1) = pack_bf16(o[4] * i0, o[5] * i0); *(uint32_t*)(dst + o1 + 1024) = pack_bf16(o[6] * i1, o[7] * i1);
  if ((lane & 3) < 2) {
    *(uint32_t*)(dst + o2) = pack_bf16(o[8] * i0, o[9] * i0);
    *(uint32_t*)(dst + o2 + 1024) = pack_bf16(o[10] * i1, o[11] * i1);
  }
}
__device__ __forceinline__ int img_off(int chunk) { return (chunk >> 3) * 16384 + (chunk & 7) * 128; }
__device__ __forceinline__ float sq20(uint4 a, uint4 b, uint2 c) {
  uint32_t s0, s1;
  asm("mul.rn.bf16x2 %0, %1, %1;" : "=r"(s0) : "r"(a.x));
  asm("mul.rn.bf16x2 %0, %1, %1;" : "=r"(s1) : "r"(a.y));
#define SQ_(acc, v) asm("fma.rn.bf16x2 %0, %1, %1, %0;" : "+r"(acc) : "r"(v))
  SQ_(s0, a.z); SQ_(s1, a.w); SQ_(s0, b.x); SQ_(s1, b.y); SQ_(s0, b.z); SQ_(s1, b.w); SQ_(s0, c.x); SQ_(s1, c.y);
#undef SQ_
  return (bf_lo(s0) + bf_hi(s0)) + (bf_lo(s1) + bf_hi(s1));
}

__global__ void __launch_bounds__(512, 1)
k2_attn(const bf16* __restrict__ wg_, const bf16* __restrict__ wu,
        const bf16* __restrict__ wd, uint32_t mk) {
  extern __shared__ __align__(1024) uint8_t sm[];
  const uint32_t sbase = smem_u32(sm);
  float* part = (float*)(sm + 2 * HEAD_IMG);
  const uint32_t kvb = sbase + 2 * HEAD_IMG + 2 * 6144;
  const uint32_t flagb = kvb + 128, partb = kvb + 136;
  volatile uint32_t* sflag = (volatile uint32_t*)(sm + 2 * HEAD_IMG + 2 * 6144 + 160);
  const int tid = threadIdx.x, lane = tid & 31;
  const int warp = __shfl_sync(~0u, tid >> 5, 0);
  const int head = blockIdx.x >> 2, qb = blockIdx.x & 3;
  const uint8_t* qimg = (const uint8_t*)g_qkv + (size_t)head * HEAD_IMG + qb * 64 * 384;

  if (tid == 0) STAMP(1, 0);
  if (tid == 0) {
    for (int i = 0; i < 16; i++) mbar_init(kvb + 8 * i, 1);
    mbar_init(flagb, 1); mbar_init(partb, 128); mbar_init(partb + 8, 128);
    asm volatile("fence.mbarrier_init.release.cluster;" ::: "memory");
  }
  __syncthreads();

  if (warp >= 12) {
    asm volatile("setmaxnreg.dec.sync.aligned.u32 56;");
    const int t = tid - 384;
    pdl_wait();
    pdl_trigger();
    if (t == 0) {
      const uint8_t* kimg = (const uint8_t*)g_qkv + (size_t)(32 + head) * HEAD_IMG;
      const uint8_t* vimg = (const uint8_t*)g_qkv + (size_t)(64 + head) * HEAD_IMG;
      for (int b = 0; b < 16; b++) {
        mbar_expect(kvb + 8 * b, 12288);
        bulk_ld(sbase + b * 6144, kimg + b * 6144, 6144, kvb + 8 * b);
        bulk_ld(sbase + HEAD_IMG + b * 6144, vimg + b * 6144, 6144, kvb + 8 * b);
      }
    }
    if (blockIdx.x == 0 && t >= 32 && t < 56) g_cnt[(t - 32) * 32] = 0;
    {
      float qm = 0.f, km = 0.f;
      const int ro = (t >> 3) * 384 + (t & 7) * 16;
#pragma unroll
      for (int i = 0; i < 4; i++) {
        const uint8_t* p = qimg + i * 6144 + ro;
        const float v = sq20(__ldcg((const uint4*)p), __ldcg((const uint4*)(p + 128)), __ldcg((const uint2*)(p + 256)));
        qm = __uint_as_float(max(__float_as_uint(qm), __float_as_uint(v)));
      }
#pragma unroll 1
      for (int b = 0; b < 16; b++) {
        mbar_wait(kvb + 8 * b, 0);
        const uint8_t* p = sm + b * 6144 + ro;
        const float v = sq20(*(const uint4*)p, *(const uint4*)(p + 128), *(const uint2*)(p + 256));
        km = __uint_as_float(max(__float_as_uint(km), __float_as_uint(v)));
      }
      if ((POLY_MASK >> (t >> 3)) & 1) km *= 9.313225746154785e-10f;
      const uint32_t qw = __reduce_max_sync(~0u, __float_as_uint(qm)), kw = __reduce_max_sync(~0u, __float_as_uint(km));
      if (lane == 0) { sflag[1 + (warp & 3)] = qw; sflag[5 + (warp & 3)] = kw; }
      bar_sync(1, 128);
      if (t == 0) {
        const float q2 = __uint_as_float(max(max(sflag[1], sflag[2]), max(sflag[3], sflag[4])));
        const float k2 = __uint_as_float(max(max(sflag[5], sflag[6]), max(sflag[7], sflag[8])));
        sflag[0] = (q2 * k2 <= 3000.f) ? 1u : 0u;
        mbar_arrive(flagb);
        STAMP(1, 2);
      }
    }
    const int kr = (warp & 3) * 8 + (lane >> 2), ch = lane & 3;
    if (blockIdx.x < 108) {
      const int cg = blockIdx.x * 4 + ch;
      const int up = cg >= 216, cc = cg - up * 216;
      const int nt = cc / 27, ci = cc - nt * 27 + up * 27;
      const bf16* src = (up ? wu : wg_) + cc * 8 + (size_t)kr * F_;
      uint4* dst = g_wgu + ((size_t)nt * 10 * 54 + ci) * 64 + kr;
      float a8[8];
#pragma unroll
      for (int i = 0; i < 8; i++) a8[i] = 0.f;
#pragma unroll 4
      for (int it = 0; it < 20; it++) {
        const uint4 v = ldg_nc(src + (size_t)it * 32 * F_);
        dst[(it >> 1) * (54 * 64) + (it & 1) * 32] = v;
        a8[0] += bf_lo(v.x); a8[1] += bf_hi(v.x); a8[2] += bf_lo(v.y); a8[3] += bf_hi(v.y);
        a8[4] += bf_lo(v.z); a8[5] += bf_hi(v.z); a8[6] += bf_lo(v.w); a8[7] += bf_hi(v.w);
      }
#pragma unroll
      for (int i = 0; i < 8; i++) {
        a8[i] += __shfl_xor_sync(~0u, a8[i], 4);
        a8[i] += __shfl_xor_sync(~0u, a8[i], 8);
        a8[i] += __shfl_xor_sync(~0u, a8[i], 16);
      }
      float* red = (float*)(sm + K2_SMEM);
      if (lane < 4) {
#pragma unroll
        for (int i = 0; i < 8; i++) red[(warp & 3) * 32 + lane * 8 + i] = a8[i];
      }
      bar_sync(1, 128);
      if (t < 32) g_csgu[blockIdx.x * 32 + t] = red[t] + red[32 + t] + red[64 + t] + red[96 + t];
    }
    {
      const int first = blockIdx.x < 108 ? blockIdx.x * 5 : 540 + (blockIdx.x - 108) * 27;
      const int last = blockIdx.x < 108 ? first + 5 : first + 27;
#pragma unroll 4
      for (int ps = first; ps < last; ps++) {
        const int rg = ps / 20, cs = ps - rg * 20;
        const int cg = cs * 4 + ch, nt = cg / 10, ci = cg - nt * 10;
        const int k = rg * 32 + kr;
        g_wd[((nt * 27 + (k >> 6)) * 10 + ci) * 64 + (k & 63)] = ldg_nc(wd + (size_t)k * D_ + cg * 8);
      }
    }
    if (t == 0) STAMP(1, 6);
  } else {
    asm volatile("setmaxnreg.inc.sync.aligned.u32 152;");
    const int wg = warp >> 2, wq = warp & 3;
    const uint8_t* qthr = qimg + wq * 768 + (lane >> 2) * 16 + (lane & 3) * 4;
    uint8_t* othr = (uint8_t*)g_o + (size_t)qb * 4 * 163840 + wq * 2048 + (lane >> 2) * 16 + (lane & 3) * 4;
    const int oc = (head >> 1) * 5 + (head & 1) * 2;
    const int oo0 = img_off(oc), oo1 = img_off(oc + 1), oo2 = img_off((head >> 1) * 5 + 4) + (head & 1) * 8;
    const uint64_t dk0 = mkdesc(sbase, 128, 384, 0), dk0b = mkdesc(sbase + 256, 0, 384, 0);
    const uint64_t dv0 = mkdesc(sbase + HEAD_IMG, 384, 128, 0);
    const int nun = wg == 1 ? 4 : 3;
    const uint32_t utile = wg == 0 ? 0x210u : (wg == 1 ? 0x4325u : 0x576u);
    pdl_wait();
    if (tid == 0) STAMP(1, 1);
    uint32_t q[6];
    load_q(q, qthr + (utile & 15) * 3072);
    bool fast = true;
#pragma unroll 1
    for (int u = 0; u < nun; u++) {
      const int tile = (utile >> (4 * u)) & 15;
      int b0 = 0, b1 = 16;
      if (wg == 0 && u == 2) b1 = 11;
      if (wg == 1 && u == 0) b1 = 6;
      if (wg == 1 && u == 1) b0 = 11;
      if (wg == 2 && u == 2) b0 = 6;
      const bool wt = u == 0 || (wg == 1 && u == 1);
      float s[64], o[12];
#pragma unroll
      for (int i = 0; i < 12; i++) o[i] = 0.f;
      uint64_t dk = dk0 + b0 * 384, dkb = dk0b + b0 * 384, dv = dv0 + b0 * 384;
      if (wt) mbar_wait(kvb + 8 * b0, 0);
      fence_regs(o);
      WG_FENCE();
      wgmma_rs_n128(s, q[0], q[1], q[2], q[3], dk, 0);
      wgmma_rs_n128(s, q[4], q[5], 0, 0, dkb, 1);
      WG_COMMIT();
#pragma unroll 1
      for (int b = b0 + 1; b < b1; b++) {
        if (wt) mbar_wait(kvb + 8 * b, 0);
        WG_WAIT(0);
        fence_regs(s); fence_regs(o);
        exp_pv(s, o, dv, mk);
        dk += 384; dkb += 384; dv += 384;
        wgmma_rs_n128(s, q[0], q[1], q[2], q[3], dk, 0);
        wgmma_rs_n128(s, q[4], q[5], 0, 0, dkb, 1);
        WG_COMMIT();
      }
      WG_WAIT(0);
      fence_regs(s); fence_regs(o);
      if (u + 1 < nun) load_q(q, qthr + ((utile >> (4 * u + 4)) & 15) * 3072);
      exp_pv(s, o, dv, mk);
      WG_COMMIT();
      WG_WAIT(0);
      fence_regs(o);
      if (wg == 1 && u < 2) {
        float4* pp = (float4*)(part + u * 1536) + (tid & 127);
        pp[0] = make_float4(o[0], o[1], o[2], o[3]);
        pp[128] = make_float4(o[4], o[5], o[6], o[7]);
        pp[256] = make_float4(o[8], o[9], o[10], o[11]);
        mbar_arrive(partb + 8 * u);
        if (u == 0) continue;
      }
      if (wt) {
        mbar_wait(flagb, 0);
        fast = sflag[0] != 0;
        if (!fast) break;
        if (wg == 1) continue;
      }
      if (wg != 1 && u == 2) {
        const int pi = wg == 0 ? 1 : 0;
        mbar_wait(partb + 8 * pi, 0);
        const float4* pp = (const float4*)(part + pi * 1536) + (tid & 127);
        const float4 x0 = pp[0], x1 = pp[128], x2 = pp[256];
        o[0] += x0.x; o[1] += x0.y; o[2] += x0.z; o[3] += x0.w; o[4] += x1.x; o[5] += x1.y;
        o[6] += x1.z; o[7] += x1.w; o[8] += x2.x; o[9] += x2.y; o[10] += x2.z; o[11] += x2.w;
      }
      store_o(o, othr + (tile >> 1) * 163840 + (tile & 1) * 8192, oo0, oo1, oo2, lane);
    }
    if ((tid & 127) == 0) STAMP(1, 3 + wg);
    if (!fast) {
#pragma unroll 1
      for (int tile = wg; tile < 8; tile += 3) {
        load_q(q, qthr + tile * 3072);
        if ((lane & 3) >= 2) { q[4] = 0; q[5] = 0; }
        float o[12], m0 = -INFINITY, m1 = -INFINITY;
#pragma unroll
        for (int i = 0; i < 12; i++) o[i] = 0.f;
#pragma unroll 1
        for (int b = 0; b < 16; b++) {
          float s[64];
          WG_FENCE();
          wgmma_rs_n128(s, q[0], q[1], q[2], q[3], dk0 + b * 384, 0);
          wgmma_rs_n128(s, q[4], q[5], 0, 0, dk0b + b * 384, 1);
          WG_COMMIT();
          WG_WAIT(0);
          fence_regs(s);
          float x0 = m0, x1 = m1;
#pragma unroll
          for (int j = 0; j < 16; j++) {
            if ((POLY_MASK >> j) & 1) {
#pragma unroll
              for (int i = 0; i < 4; i++) s[4 * j + i] *= (1.f / 32768.f);
            }
            x0 = fmaxf(x0, fmaxf(s[4 * j], s[4 * j + 1]));
            x1 = fmaxf(x1, fmaxf(s[4 * j + 2], s[4 * j + 3]));
          }
          x0 = fmaxf(x0, __shfl_xor_sync(~0u, x0, 1)); x0 = fmaxf(x0, __shfl_xor_sync(~0u, x0, 2));
          x1 = fmaxf(x1, __shfl_xor_sync(~0u, x1, 1)); x1 = fmaxf(x1, __shfl_xor_sync(~0u, x1, 2));
          const float al0 = ex2(m0 - x0), al1 = ex2(m1 - x1);
          m0 = x0; m1 = x1;
#pragma unroll
          for (int i = 0; i < 12; i++) o[i] *= (i & 2) ? al1 : al0;
          uint32_t p[32];
#pragma unroll
          for (int i = 0; i < 32; i++) {
            const float mm = (i & 1) ? m1 : m0;
            p[i] = pack_bf16(ex2(s[2 * i] - mm), ex2(s[2 * i + 1] - mm));
          }
          fence_regs(o);
          WG_FENCE();
#pragma unroll
          for (int k = 0; k < 8; k++) wgmma_rs_n24(o, p[4 * k], p[4 * k + 1], p[4 * k + 2], p[4 * k + 3], dv0 + b * 384 + k * 48, 1);
          WG_COMMIT();
          WG_WAIT(0);
          fence_regs(o);
        }
        store_o(o, othr + (tile >> 1) * 163840 + (tile & 1) * 8192, oo0, oo1, oo2, lane);
      }
    }
  }
}

constexpr int K3_ST = 4, K3_STAGE = 36864;
constexpr int K3_SMEM = K3_ST * K3_STAGE + 40960 + 20480 + 256;

template <int KT, bool FIRST>
__global__ void __cluster_dims__(2, 1, 1) __launch_bounds__(384, 1)
k3_proj(const __grid_constant__ CUtensorMap tmr, const uint4* __restrict__ aimg, const uint4* __restrict__ wimg) {
  extern __shared__ __align__(1024) uint8_t sm[];
  const uint32_t sbase = smem_u32(sm);
  uint8_t* xch = sm + K3_ST * K3_STAGE;
  uint8_t* stg = sm + K3_ST * K3_STAGE + 40960;
  const uint32_t fullb = smem_u32(stg) + 20480, emptyb = fullb + 8 * K3_ST, resb = emptyb + 8 * K3_ST, xchb = resb + 8;
  const int tid = threadIdx.x, lane = tid & 31;
  const int warp = __shfl_sync(~0u, tid >> 5, 0);
  const int rank = blockIdx.x & 1;
  const int n = blockIdx.x & 7, m = blockIdx.x >> 3;
  const int kt0 = rank * ((KT + 1) / 2), nkt = rank ? KT / 2 : (KT + 1) / 2;
  if (tid == 0) STAMP(FIRST ? 2 : 4, 0);
  if (tid == 0) {
    prefetch_map(&tmr);
    for (int i = 0; i < K3_ST; i++) { mbar_init(fullb + 8 * i, 1); mbar_init(emptyb + 8 * i, 2); }
    mbar_init(resb, 1); mbar_init(xchb, 1);
    mbar_expect(xchb, 40960);
    asm volatile("fence.mbarrier_init.release.cluster;" ::: "memory");
  }
  __syncthreads();
  cluster_arrive();
  if (warp == 0) {
    if (lane == 0) {
      const uint8_t* wk = (const uint8_t*)wimg + (size_t)(n * KT + kt0) * 10240;
      const uint8_t* ws = (const uint8_t*)wimg + (size_t)((n ^ 1) * KT + kt0) * 10240;
      const uint8_t* ab = (const uint8_t*)aimg + (size_t)(m * KT + kt0) * 16384;
      mbar_expect(fullb, K3_STAGE);
      bulk_ld(sbase + 16384, wk, 10240, fullb);
      bulk_ld(sbase + 26624, ws, 10240, fullb);
      pdl_wait();
      pdl_trigger();
      for (int i = 0; i < nkt; i++) {
        const int s = i % K3_ST;
        const uint32_t sa = sbase + s * K3_STAGE;
        if (i >= K3_ST) mbar_wait(emptyb + 8 * s, ((i / K3_ST) - 1) & 1);
        if (i > 0) mbar_expect(fullb + 8 * s, K3_STAGE);
        bulk_ld(sa, ab + i * 16384, 16384, fullb + 8 * s);
        if (i > 0) {
          bulk_ld(sa + 16384, wk + i * 10240, 10240, fullb + 8 * s);
          bulk_ld(sa + 26624, ws + i * 10240, 10240, fullb + 8 * s);
        }
        if (FIRST && i == K3_ST - 1) {
          mbar_expect(resb, 20480);
          tma2d(smem_u32(stg), &tmr, n * 80, m * 128, resb);
          tma2d(smem_u32(stg) + 10240, &tmr, n * 80, m * 128 + 64, resb);
        }
      }
    }
    __syncwarp();
    cluster_wait();
  } else if (warp >= 4) {
    const int cw = warp - 4, wg = cw >> 2;
    const int g = lane >> 2, c = lane & 3;
    uint8_t* himg = (uint8_t*)g_h + (size_t)m * 163840 + cw * 2048 + g * 16 + c * 4;
    uint32_t rv[20];
    if (!FIRST) {
#pragma unroll
      for (int j = 0; j < 10; j++) {
        rv[2 * j] = __ldcg((const uint32_t*)(himg + img_off(n * 10 + j)));
        rv[2 * j + 1] = __ldcg((const uint32_t*)(himg + img_off(n * 10 + j) + 1024));
      }
    }
    float acc[80];
    const uint64_t da0 = mkdesc(sbase + wg * 8192, 128, 1024, 0);
    const uint64_t db0 = mkdesc(sbase + 16384, 128, 1024, 0);
#pragma unroll 1
    for (int i = 0; i < nkt; i++) {
      const int s = i % K3_ST;
      mbar_wait(fullb + 8 * s, (i / K3_ST) & 1);
      if (i == 0 && tid == 128) STAMP(FIRST ? 2 : 4, 2);
      const uint64_t da = da0 + s * (K3_STAGE >> 4), db = db0 + s * (K3_STAGE >> 4);
      WG_FENCE();
#pragma unroll
      for (int k = 0; k < 4; k++) wgmma_ss_n160(acc, da + k * 16, db + k * 16, (i | k) != 0);
      WG_COMMIT();
      if (i > 0) {
        WG_WAIT(1);
        if ((tid & 127) == 0) mbar_arrive(emptyb + 8 * ((i - 1) % K3_ST));
      }
    }
    uint8_t* sp = stg + (cw * 16 + g) * 160 + c * 4;
    if (FIRST) {
      mbar_wait(resb, 0);
#pragma unroll
      for (int j = 0; j < 10; j++) {
        rv[2 * j] = *(const uint32_t*)(sp + j * 16);
        rv[2 * j + 1] = *(const uint32_t*)(sp + 1280 + j * 16);
      }
    }
    cluster_wait();
    WG_WAIT(0);
    fence_regs(acc);
    if (tid == 128) STAMP(FIRST ? 2 : 4, 3);
    bar_sync(3, 256);
#pragma unroll
    for (int j = 0; j < 10; j++)
      *(float4*)(sm + cw * 5120 + j * 512 + lane * 16) = make_float4(acc[40 + 4 * j], acc[41 + 4 * j], acc[42 + 4 * j], acc[43 + 4 * j]);
    fence_async();
    __syncwarp();
    if (lane == 0)
      asm volatile("cp.async.bulk.shared::cluster.shared::cta.mbarrier::complete_tx::bytes [%0], [%1], 5120, [%2];"
                   ::"r"(mapa(smem_u32(xch) + cw * 5120, rank ^ 1)), "r"(sbase + cw * 5120), "r"(mapa(xchb, rank ^ 1)) : "memory");
#pragma unroll
    for (int j = 0; j < 10; j++) {
      acc[4 * j] += bf_lo(rv[2 * j]); acc[4 * j + 1] += bf_hi(rv[2 * j]);
      acc[4 * j + 2] += bf_lo(rv[2 * j + 1]); acc[4 * j + 3] += bf_hi(rv[2 * j + 1]);
    }
    mbar_wait(xchb, 0);
    if (tid == 128) STAMP(FIRST ? 2 : 4, 5);
    float s0 = 0.f, s1 = 0.f;
#pragma unroll
    for (int j = 0; j < 10; j++) {
      const float4 p = *(const float4*)(xch + cw * 5120 + j * 512 + lane * 16);
      acc[4 * j] += p.x; acc[4 * j + 1] += p.y; acc[4 * j + 2] += p.z; acc[4 * j + 3] += p.w;
      if (FIRST) {
        *(uint32_t*)(himg + img_off(n * 10 + j)) = pack_bf16(acc[4 * j], acc[4 * j + 1]);
        *(uint32_t*)(himg + img_off(n * 10 + j) + 1024) = pack_bf16(acc[4 * j + 2], acc[4 * j + 3]);
        s0 += acc[4 * j] + acc[4 * j + 1]; s1 += acc[4 * j + 2] + acc[4 * j + 3];
      } else {
        *(uint32_t*)(sp + j * 16) = pack_bf16(acc[4 * j], acc[4 * j + 1]);
        *(uint32_t*)(sp + 1280 + j * 16) = pack_bf16(acc[4 * j + 2], acc[4 * j + 3]);
      }
    }
    if (FIRST) {
      s0 += __shfl_xor_sync(~0u, s0, 1); s0 += __shfl_xor_sync(~0u, s0, 2);
      s1 += __shfl_xor_sync(~0u, s1, 1); s1 += __shfl_xor_sync(~0u, s1, 2);
      s0 *= (1.f / 80.f); s1 *= (1.f / 80.f);
      float q0 = 0.f, q1 = 0.f;
#pragma unroll
      for (int j = 0; j < 10; j++) {
        float d;
        d = acc[4 * j] - s0; q0 = fmaf(d, d, q0); d = acc[4 * j + 1] - s0; q0 = fmaf(d, d, q0);
        d = acc[4 * j + 2] - s1; q1 = fmaf(d, d, q1); d = acc[4 * j + 3] - s1; q1 = fmaf(d, d, q1);
      }
      q0 += __shfl_xor_sync(~0u, q0, 1); q0 += __shfl_xor_sync(~0u, q0, 2);
      q1 += __shfl_xor_sync(~0u, q1, 1); q1 += __shfl_xor_sync(~0u, q1, 2);
      if (c < 2) g_hpart[n * S_ + m * 128 + cw * 16 + g + c * 8] = c ? make_float2(s1, q1) : make_float2(s0, q0);
    } else {
      fence_async();
      bar_sync(1 + wg, 128);
      if ((tid & 127) == 0) {
        tma2d_st(&tmr, n * 80, m * 128 + wg * 64, smem_u32(stg) + wg * 10240);
        bulk_commit_wait();
      }
      __syncwarp();
    }
    if (tid == 128) STAMP(FIRST ? 2 : 4, 4);
  } else {
    cluster_wait();
  }
  cluster_sync_relaxed();
}

constexpr int K4_ST = 3, K4_STAGE = 71680;
constexpr int K4_SMEM = K4_ST * K4_STAGE + 1728 + 1024 + 64;

__global__ void __cluster_dims__(2, 1, 1) __launch_bounds__(256, 1)
k4_ffn1() {
  extern __shared__ __align__(1024) uint8_t sm[];
  float* cs = (float*)(sm + K4_ST * K4_STAGE);
  float2* rowst = (float2*)(sm + K4_ST * K4_STAGE + 1728);
  const uint32_t sbase = smem_u32(sm);
  const uint32_t fullb = sbase + K4_ST * K4_STAGE + 2752, emptyb = fullb + 8 * K4_ST;
  const int tid = threadIdx.x, lane = tid & 31;
  const int warp = __shfl_sync(~0u, tid >> 5, 0);
  const int rank = blockIdx.x & 1, cl = blockIdx.x >> 1;
  const int n = cl & 7, m = (cl >> 3) * 2 + rank;
  const uint8_t* wb = (const uint8_t*)g_wgu + (size_t)n * 10 * 55296 + rank * 27648;
  const uint8_t* ab = (const uint8_t*)g_h + (size_t)m * 163840;
  if (tid == 0) STAMP(3, 0);
  if (tid == 0) {
    for (int i = 0; i < K4_ST; i++) { mbar_init(fullb + 8 * i, 1); mbar_init(emptyb + 8 * i, 4); }
    asm volatile("fence.mbarrier_init.release.cluster;" ::: "memory");
  }
  __syncthreads();
  cluster_arrive();
  const float cs0 = __ldcg(&g_csgu[(tid >= 216 ? F_ - 216 : 0) + n * 216 + tid]);
  const float cs1 = tid < 176 ? __ldcg(&g_csgu[F_ - 216 + n * 216 + 256 + tid]) : 0.f;
  cluster_wait();
  if (tid == 0) {
    for (int kt = 0; kt < K4_ST; kt++) mbar_expect(fullb + 8 * kt, K4_STAGE);
    bulk_ld_mc(sbase + 16384 + rank * 27648, wb, 27648, fullb);
  }
  pdl_wait();
  pdl_trigger();
  if (tid == 128) STAMP(3, 1);
  if (tid == 0) {
    bulk_ld(sbase, ab, 16384, fullb);
    for (int kt = 1; kt < K4_ST; kt++) {
      bulk_ld(sbase + kt * K4_STAGE, ab + kt * 16384, 16384, fullb + 8 * kt);
      bulk_ld_mc(sbase + kt * K4_STAGE + 16384 + rank * 27648, wb + kt * 55296, 27648, fullb + 8 * kt);
    }
  }
  if (tid >= 128) {
    const int r = tid - 128;
    float2 p[8];
#pragma unroll
    for (int i = 0; i < 8; i++) p[i] = __ldcg(&g_hpart[i * S_ + m * 128 + r]);
    float mean = 0.f, m2 = 0.f;
#pragma unroll
    for (int i = 0; i < 8; i++) { mean += p[i].x; m2 += p[i].y; }
    mean *= 0.125f;
#pragma unroll
    for (int i = 0; i < 8; i++) { const float d = p[i].x - mean; m2 = fmaf(80.f * d, d, m2); }
    rowst[r] = make_float2(-mean, __frcp_rn(m2 * (1.f / D_) + 1e-5f));
  }
  cs[tid] = cs0;
  if (tid < 176) cs[256 + tid] = cs1;
  __syncwarp();
  float ag[108], au[108];
  const uint64_t da0 = mkdesc(sbase + (warp >> 2) * 8192, 128, 1024, 0);
  const uint64_t db0 = mkdesc(sbase + 16384, 128, 1024, 0);
#pragma unroll 1
  for (int kt = 0; kt < 10; kt++) {
    const int s = kt % K4_ST;
    mbar_wait(fullb + 8 * s, (kt / K4_ST) & 1);
    if (kt == 0 && tid == 128) STAMP(3, 2);
    const uint64_t da = da0 + s * (K4_STAGE >> 4), db = db0 + s * (K4_STAGE >> 4);
    WG_FENCE();
#pragma unroll
    for (int k = 0; k < 4; k++) {
      wgmma_ss_n216(ag, da + k * 16, db + k * 16, (kt | k) != 0);
      wgmma_ss_n216(au, da + k * 16, db + 1728 + k * 16, (kt | k) != 0);
    }
    WG_COMMIT();
    if (kt > 0 && kt - 1 + K4_ST < 10) {
      WG_WAIT(1);
      const int sp = (kt - 1) % K4_ST;
      if ((tid & 127) < 2) mbar_arrive_cta(emptyb + 8 * sp, tid & 1);
      if (tid == 0) {
        const uint32_t sa = sbase + sp * K4_STAGE;
        mbar_wait(emptyb + 8 * sp, ((kt - 1) / K4_ST) & 1);
        mbar_expect(fullb + 8 * sp, K4_STAGE);
        bulk_ld_mc(sa + 16384 + rank * 27648, wb + (kt - 1 + K4_ST) * 55296, 27648, fullb + 8 * sp);
        bulk_ld(sa, ab + (kt - 1 + K4_ST) * 16384, 16384, fullb + 8 * sp);
      }
      __syncwarp();
    }
  }
  WG_WAIT(0);
  fence_regs(ag); fence_regs(au);
  if (tid == 128) STAMP(3, 3);
  __syncthreads();
  const int g = lane >> 2, c = lane & 3;
  const float2 st0 = rowst[warp * 16 + g], st1 = rowst[warp * 16 + g + 8];
  uint8_t* dst = (uint8_t*)g_hh + (size_t)m * 27 * 16384 + warp * 2048 + g * 16 + c * 4;
#pragma unroll
  for (int j = 0; j < 27; j++) {
    const float2 cg = *(const float2*)&cs[j * 8 + c * 2], cu = *(const float2*)&cs[216 + j * 8 + c * 2];
    const float h0 = fmaf(st0.x, cg.x, ag[4 * j]) * st0.y * fmaf(st0.x, cu.x, au[4 * j]);
    const float h1 = fmaf(st0.x, cg.y, ag[4 * j + 1]) * st0.y * fmaf(st0.x, cu.y, au[4 * j + 1]);
    const float h2 = fmaf(st1.x, cg.x, ag[4 * j + 2]) * st1.y * fmaf(st1.x, cu.x, au[4 * j + 2]);
    const float h3 = fmaf(st1.x, cg.y, ag[4 * j + 3]) * st1.y * fmaf(st1.x, cu.y, au[4 * j + 3]);
    *(uint32_t*)(dst + img_off(n * 27 + j)) = pack_bf16(h0, h1);
    *(uint32_t*)(dst + img_off(n * 27 + j) + 1024) = pack_bf16(h2, h3);
  }
  if (tid == 128) STAMP(3, 4);
  cluster_sync_relaxed();
}

typedef CUresult (*EncodeFn)(CUtensorMap*, CUtensorMapDataType, cuuint32_t, void*, const cuuint64_t*, const cuuint64_t*,
                             const cuuint32_t*, const cuuint32_t*, CUtensorMapInterleave, CUtensorMapSwizzle,
                             CUtensorMapL2promotion, CUtensorMapFloatOOBfill);

static CUtensorMap make_map(EncodeFn enc, const void* p, uint64_t inner, uint64_t outer, uint32_t box_inner,
                            uint32_t box_outer, CUtensorMapSwizzle swz) {
  CUtensorMap m;
  cuuint64_t gd[2] = {inner, outer};
  cuuint64_t gs[1] = {inner * 2};
  cuuint32_t bd[2] = {box_inner, box_outer};
  cuuint32_t es[2] = {1, 1};
  enc(&m, CU_TENSOR_MAP_DATA_TYPE_BFLOAT16, 2, (void*)p, gd, gs, bd, es, CU_TENSOR_MAP_INTERLEAVE_NONE, swz,
      CU_TENSOR_MAP_L2_PROMOTION_L2_256B, CU_TENSOR_MAP_FLOAT_OOB_FILL_NONE);
  return m;
}

template <typename... KArgs, typename... Args>
static void launch(void (*k)(KArgs...), int threads, int smem, bool pdl, Args... args) {
  cudaLaunchConfig_t cfg = {};
  cfg.gridDim = dim3(128);
  cfg.blockDim = dim3(threads);
  cfg.dynamicSmemBytes = smem;
  cfg.stream = cudaStreamPerThread;
  cudaLaunchAttribute at[1];
  at[0].id = cudaLaunchAttributeProgrammaticStreamSerialization;
  at[0].val.programmaticStreamSerializationAllowed = 1;
  cfg.attrs = at;
  cfg.numAttrs = pdl ? 1 : 0;
  cudaLaunchKernelEx(&cfg, k, KArgs(args)...);
}

extern "C" void kernel_launch(void* const* d_in, const int* in_sizes, int n_in, void* d_out, int out_size) {
  const bf16* x = (const bf16*)d_in[0];
  const bf16* wqkv = (const bf16*)d_in[1];
  const bf16* wo = (const bf16*)d_in[2];
  const bf16* wg = (const bf16*)d_in[4];
  const bf16* wu = (const bf16*)d_in[5];
  const bf16* wd = (const bf16*)d_in[6];

  static EncodeFn enc = nullptr;
  static void *p_o, *p_hh, *p_wo, *p_wd;
  if (!enc) {
    void* fn = nullptr;
    cudaDriverEntryPointQueryResult qr;
    cudaGetDriverEntryPoint("cuTensorMapEncodeTiled", &fn, cudaEnableDefault, &qr);
    enc = (EncodeFn)fn;
    cudaGetSymbolAddress(&p_o, g_o); cudaGetSymbolAddress(&p_hh, g_hh);
    cudaGetSymbolAddress(&p_wo, g_wo); cudaGetSymbolAddress(&p_wd, g_wd);
    cudaFuncSetAttribute(k1_qkv, cudaFuncAttributeMaxDynamicSharedMemorySize, K1_SMEM);
    cudaFuncSetAttribute(k2_attn, cudaFuncAttributeMaxDynamicSharedMemorySize, K2_SMEM + 512);
    cudaFuncSetAttribute(k3_proj<10, true>, cudaFuncAttributeMaxDynamicSharedMemorySize, K3_SMEM);
    cudaFuncSetAttribute(k3_proj<27, false>, cudaFuncAttributeMaxDynamicSharedMemorySize, K3_SMEM);
    cudaFuncSetAttribute(k4_ffn1, cudaFuncAttributeMaxDynamicSharedMemorySize, K4_SMEM);
  }
  const CUtensorMap tmx = make_map(enc, x, D_, S_, 64, 128, CU_TENSOR_MAP_SWIZZLE_128B);
  const CUtensorMap tmw = make_map(enc, wqkv, 3 * D_, D_, 32, 64, CU_TENSOR_MAP_SWIZZLE_64B);
  const CUtensorMap tmxr = make_map(enc, x, D_, S_, 80, 64, CU_TENSOR_MAP_SWIZZLE_NONE);
  const CUtensorMap tmout = make_map(enc, d_out, D_, S_, 80, 64, CU_TENSOR_MAP_SWIZZLE_NONE);

  launch(k1_qkv, 384, K1_SMEM, false, tmx, tmw, x, wqkv, wo);
  launch(k2_attn, 512, K2_SMEM + 512, true, wg, wu, wd, 0x007f007fu);
  launch(k3_proj<10, true>, 384, K3_SMEM, true, tmxr, (const uint4*)p_o, (const uint4*)p_wo);
  launch(k4_ffn1, 256, K4_SMEM, true);
  launch(k3_proj<27, false>, 384, K3_SMEM, true, tmout, (const uint4*)p_hh, (const uint4*)p_wd);
}
```

```cpp
#include <cuda_runtime.h>
#include <cuda_bf16.h>
#include <cuda.h>
#include <stdint.h>

typedef __nv_bfloat16 bf16;

constexpr int S_ = 2048, D_ = 640, F_ = 1728;
constexpr int HEAD_IMG = 98304;
#define PMASK 0xABAB
constexpr uint32_t POLY_MASK = PMASK;
constexpr float QSCALE = 0.22360679774997896f * 1.4426950408889634f;

__device__ __align__(1024) uint4 g_qkv[96 * HEAD_IMG / 16];
__device__ __align__(1024) uint4 g_o[S_ * D_ / 8];
__device__ __align__(1024) uint4 g_h[S_ * D_ / 8];
__device__ __align__(1024) uint4 g_hh[S_ * F_ / 8];
__device__ __align__(1024) uint4 g_wo[D_ * D_ / 8];
__device__ __align__(1024) uint4 g_wgu[2 * D_ * F_ / 8];
__device__ __align__(1024) uint4 g_wd[F_ * D_ / 8];
__device__ uint4 g_rowstat[S_];
__device__ uint4 g_cpart[16 * 8 * 128];
__device__ float g_nrm[64 * 128];
__device__ float g_csgu[2 * F_];
__device__ float2 g_hpart[8 * S_];
__device__ unsigned g_epoch;

#define STAMP(k, i)
__device__ __forceinline__ uint32_t smem_u32(const void* p) { return (uint32_t)__cvta_generic_to_shared(p); }
__device__ __forceinline__ void mbar_init(uint32_t a, uint32_t c) {
  asm volatile("mbarrier.init.shared::cta.b64 [%0], %1;" ::"r"(a), "r"(c) : "memory");
}
__device__ __forceinline__ void mbar_expect(uint32_t a, uint32_t bytes) {
  asm volatile("mbarrier.arrive.expect_tx.shared::cta.b64 _, [%0], %1;" ::"r"(a), "r"(bytes) : "memory");
}
__device__ __forceinline__ void mbar_arrive(uint32_t a) {
  asm volatile("mbarrier.arrive.shared::cta.b64 _, [%0];" ::"r"(a) : "memory");
}
__device__ __forceinline__ void mbar_arrive_cta(uint32_t a, uint32_t cta) {
  asm volatile("{\n.reg .b32 r;\nmapa.shared::cluster.u32 r, %0, %1;\n"
               "mbarrier.arrive.shared::cluster.b64 _, [r];\n}" ::"r"(a), "r"(cta) : "memory");
}
__device__ __forceinline__ bool mbar_try(uint32_t a, uint32_t ph) {
  uint32_t ok;
  asm volatile("{\n.reg .pred p;\nmbarrier.try_wait.parity.shared::cta.b64 p, [%1], %2;\nselp.u32 %0, 1, 0, p;\n}"
               : "=r"(ok) : "r"(a), "r"(ph) : "memory");
  return ok;
}
__device__ __noinline__ void wait_timeout() { __trap(); }
__device__ __forceinline__ void mbar_wait(uint32_t a, uint32_t ph) {
  if (mbar_try(a, ph)) return;
  uint32_t it = 0;
  while (!mbar_try(a, ph)) if (++it > (1u << 22)) wait_timeout();
}
__device__ __forceinline__ void tma2d(uint32_t dst, const CUtensorMap* m, int c0, int c1, uint32_t bar) {
  asm volatile("cp.async.bulk.tensor.2d.shared::cluster.global.mbarrier::complete_tx::bytes [%0], [%1, {%3, %4}], [%2];"
               ::"r"(dst), "l"(m), "r"(bar), "r"(c0), "r"(c1) : "memory");
}
__device__ __forceinline__ void tma2d_mc(uint32_t dst, const CUtensorMap* m, int c0, int c1, uint32_t bar) {
  asm volatile("cp.async.bulk.tensor.2d.shared::cluster.global.mbarrier::complete_tx::bytes.multicast::cluster "
               "[%0], [%1, {%3, %4}], [%2], %5;"
               ::"r"(dst), "l"(m), "r"(bar), "r"(c0), "r"(c1), "h"((uint16_t)3) : "memory");
}
__device__ __forceinline__ void bulk_ld(uint32_t dst, const void* src, uint32_t bytes, uint32_t bar) {
  asm volatile("cp.async.bulk.shared::cluster.global.mbarrier::complete_tx::bytes [%0], [%1], %2, [%3];"
               ::"r"(dst), "l"(src), "r"(bytes), "r"(bar) : "memory");
}
__device__ __forceinline__ void bulk_ld_mc(uint32_t dst, const void* src, uint32_t bytes, uint32_t bar) {
  asm volatile("cp.async.bulk.shared::cluster.global.mbarrier::complete_tx::bytes.multicast::cluster "
               "[%0], [%1], %2, [%3], %4;"
               ::"r"(dst), "l"(src), "r"(bytes), "r"(bar), "h"((uint16_t)3) : "memory");
}
__device__ __forceinline__ void cluster_arrive() { asm volatile("barrier.cluster.arrive.relaxed.aligned;" ::: "memory"); }
__device__ __forceinline__ void cluster_wait() { asm volatile("barrier.cluster.wait.aligned;" ::: "memory"); }
__device__ __forceinline__ void bulk_st(void* dst, uint32_t src, uint32_t bytes) {
  asm volatile("cp.async.bulk.global.shared::cta.bulk_group [%0], [%1], %2;" ::"l"(dst), "r"(src), "r"(bytes) : "memory");
}
__device__ __forceinline__ void tma2d_st(const CUtensorMap* m, int c0, int c1, uint32_t src) {
  asm volatile("cp.async.bulk.tensor.2d.global.shared::cta.bulk_group [%0, {%2, %3}], [%1];"
               ::"l"(m), "r"(src), "r"(c0), "r"(c1) : "memory");
}
__device__ __forceinline__ void bulk_commit_wait() {
  asm volatile("cp.async.bulk.commit_group;\ncp.async.bulk.wait_group.read 0;" ::: "memory");
}
__device__ __forceinline__ uint32_t mapa(uint32_t a, uint32_t cta) {
  uint32_t r;
  asm("mapa.shared::cluster.u32 %0, %1, %2;" : "=r"(r) : "r"(a), "r"(cta));
  return r;
}
__device__ __forceinline__ void st_async4(uint32_t dst, float a, float b, float c, float d, uint32_t bar) {
  asm volatile("st.async.shared::cluster.mbarrier::complete_tx::bytes.v4.f32 [%0], {%1, %2, %3, %4}, [%5];"
               ::"r"(dst), "f"(a), "f"(b), "f"(c), "f"(d), "r"(bar) : "memory");
}
__device__ __forceinline__ void fence_async() { asm volatile("fence.proxy.async.shared::cta;" ::: "memory"); }
__device__ __forceinline__ void prefetch_map(const CUtensorMap* m) {
  asm volatile("prefetch.tensormap [%0];" ::"l"(m) : "memory");
}
__device__ __forceinline__ void cluster_sync_relaxed() {
  __syncwarp();
  asm volatile("barrier.cluster.arrive.relaxed.aligned;\nbarrier.cluster.wait.aligned;" ::: "memory");
}
__device__ __forceinline__ void pdl_wait() { asm volatile("griddepcontrol.wait;" ::: "memory"); }
__device__ __forceinline__ void pdl_trigger() { asm volatile("griddepcontrol.launch_dependents;" ::: "memory"); }
__device__ __forceinline__ void bar_sync(int id, int n) { asm volatile("bar.sync %0, %1;" ::"r"(id), "r"(n) : "memory"); }
__device__ __forceinline__ void bar_arrive(int id, int n) { asm volatile("bar.arrive %0, %1;" ::"r"(id), "r"(n) : "memory"); }
#define WG_FENCE() asm volatile("wgmma.fence.sync.aligned;" ::: "memory")
#define WG_COMMIT() asm volatile("wgmma.commit_group.sync.aligned;" ::: "memory")
#define WG_WAIT(n) asm volatile("wgmma.wait_group.sync.aligned %0;" ::"n"(n) : "memory")
__device__ __forceinline__ uint64_t mkdesc(uint32_t addr, uint32_t lbo, uint32_t sbo, uint32_t sw) {
  return (uint64_t)((addr & 0x3FFFF) >> 4) | ((uint64_t)(lbo >> 4) << 16) | ((uint64_t)(sbo >> 4) << 32) |
         ((uint64_t)sw << 62);
}
template <int N> __device__ __forceinline__ void fence_regs(float (&r)[N]) {
#pragma unroll
  for (int i = 0; i < N; i++) asm volatile("" : "+f"(r[i])::"memory");
}
__device__ __forceinline__ uint32_t pack_bf16(float lo, float hi) {
  uint32_t r;
  asm("cvt.rn.bf16x2.f32 %0, %1, %2;" : "=r"(r) : "f"(hi), "f"(lo));
  return r;
}
__device__ __forceinline__ float bf_lo(uint32_t v) { return __uint_as_float(v << 16); }
__device__ __forceinline__ float bf_hi(uint32_t v) { return __uint_as_float(v & 0xffff0000u); }
__device__ __forceinline__ float ex2(float x) {
  float y;
  asm("ex2.approx.ftz.f32 %0, %1;" : "=f"(y) : "f"(x));
  return y;
}
__device__ __forceinline__ uint4 ldg_nc(const void* p) {
  uint4 v;
  asm volatile("ld.global.nc.L1::no_allocate.v4.u32 {%0, %1, %2, %3}, [%4];"
               : "=r"(v.x), "=r"(v.y), "=r"(v.z), "=r"(v.w) : "l"(p));
  return v;
}

__device__ __forceinline__ uint4 ld_relaxed(const uint4* p) {
  uint64_t a, b;
  asm volatile("ld.relaxed.gpu.global.v2.u64 {%0, %1}, [%2];" : "=l"(a), "=l"(b) : "l"(p) : "memory");
  return make_uint4((uint32_t)a, (uint32_t)(a >> 32), (uint32_t)b, (uint32_t)(b >> 32));
}
__device__ __forceinline__ void st_relaxed(uint4* p, float x, float y, uint32_t tag) {
  const uint64_t a = ((uint64_t)tag << 32) | __float_as_uint(x), b = ((uint64_t)tag << 32) | __float_as_uint(y);
  asm volatile("st.relaxed.gpu.global.v2.u64 [%0], {%1, %2};" ::"l"(p), "l"(a), "l"(b) : "memory");
}
__device__ __forceinline__ void tma3d(uint32_t dst, const CUtensorMap* m, int c1, int c2, uint32_t bar) {
  asm volatile("cp.async.bulk.tensor.3d.shared::cluster.global.mbarrier::complete_tx::bytes [%0], [%1, {%3, %4, %5}], [%2];"
               ::"r"(dst), "l"(m), "r"(bar), "r"(0), "r"(c1), "r"(c2) : "memory");
}
#define ACC8(a, v) do { a[0] += bf_lo(v.x); a[1] += bf_hi(v.x); a[2] += bf_lo(v.y); a[3] += bf_hi(v.y); \
                        a[4] += bf_lo(v.z); a[5] += bf_hi(v.z); a[6] += bf_lo(v.w); a[7] += bf_hi(v.w); } while (0)

__device__ __forceinline__ void wgmma_ss_n240(float (&d)[120], uint64_t da, uint64_t db, int sd) {
  asm volatile("{\n.reg .pred p;\nsetp.ne.b32 p, %122, 0;\n"
      "wgmma.mma_async.sync.aligned.m64n240k16.f32.bf16.bf16 {"
      "%0, %1, %2, %3, %4, %5, %6, %7, %8, %9, %10, %11, %12, %13, %14, %15, "
      "%16, %17, %18, %19, %20, %21, %22, %23, %24, %25, %26, %27, %28, %29, %30, %31, "
      "%32, %33, %34, %35, %36, %37, %38, %39, %40, %41, %42, %43, %44, %45, %46, %47, "
      "%48, %49, %50, %51, %52, %53, %54, %55, %56, %57, %58, %59, %60, %61, %62, %63, "
      "%64, %65, %66, %67, %68, %69, %70, %71, %72, %73, %74, %75, %76, %77, %78, %79, "
      "%80, %81, %82, %83, %84, %85, %86, %87, %88, %89, %90, %91, %92, %93, %94, %95, "
      "%96, %97, %98, %99, %100, %101, %102, %103, %104, %105, %106, %107, %108, %109, %110, %111, "
      "%112, %113, %114, %115, %116, %117, %118, %119"
      "}, %120, %121, p, 1, 1, 0, 1;\n}\n"
    : "+f"(d[0]), "+f"(d[1]), "+f"(d[2]), "+f"(d[3]), "+f"(d[4]), "+f"(d[5]), "+f"(d[6]), "+f"(d[7]),
      "+f"(d[8]), "+f"(d[9]), "+f"(d[10]), "+f"(d[11]), "+f"(d[12]), "+f"(d[13]), "+f"(d[14]), "+f"(d[15]),
      "+f"(d[16]), "+f"(d[17]), "+f"(d[18]), "+f"(d[19]), "+f"(d[20]), "+f"(d[21]), "+f"(d[22]), "+f"(d[23]),
      "+f"(d[24]), "+f"(d[25]), "+f"(d[26]), "+f"(d[27]), "+f"(d[28]), "+f"(d[29]), "+f"(d[30]), "+f"(d[31]),
      "+f"(d[32]), "+f"(d[33]), "+f"(d[34]), "+f"(d[35]), "+f"(d[36]), "+f"(d[37]), "+f"(d[38]), "+f"(d[39]),
      "+f"(d[40]), "+f"(d[41]), "+f"(d[42]), "+f"(d[43]), "+f"(d[44]), "+f"(d[45]), "+f"(d[46]), "+f"(d[47]),
      "+f"(d[48]), "+f"(d[49]), "+f"(d[50]), "+f"(d[51]), "+f"(d[52]), "+f"(d[53]), "+f"(d[54]), "+f"(d[55]),
      "+f"(d[56]), "+f"(d[57]), "+f"(d[58]), "+f"(d[59]), "+f"(d[60]), "+f"(d[61]), "+f"(d[62]), "+f"(d[63]),
      "+f"(d[64]), "+f"(d[65]), "+f"(d[66]), "+f"(d[67]), "+f"(d[68]), "+f"(d[69]), "+f"(d[70]), "+f"(d[71]),
      "+f"(d[72]), "+f"(d[73]), "+f"(d[74]), "+f"(d[75]), "+f"(d[76]), "+f"(d[77]), "+f"(d[78]), "+f"(d[79]),
      "+f"(d[80]), "+f"(d[81]), "+f"(d[82]), "+f"(d[83]), "+f"(d[84]), "+f"(d[85]), "+f"(d[86]), "+f"(d[87]),
      "+f"(d[88]), "+f"(d[89]), "+f"(d[90]), "+f"(d[91]), "+f"(d[92]), "+f"(d[93]), "+f"(d[94]), "+f"(d[95]),
      "+f"(d[96]), "+f"(d[97]), "+f"(d[98]), "+f"(d[99]), "+f"(d[100]), "+f"(d[101]), "+f"(d[102]), "+f"(d[103]),
      "+f"(d[104]), "+f"(d[105]), "+f"(d[106]), "+f"(d[107]), "+f"(d[108]), "+f"(d[109]), "+f"(d[110]), "+f"(d[111]),
      "+f"(d[112]), "+f"(d[113]), "+f"(d[114]), "+f"(d[115]), "+f"(d[116]), "+f"(d[117]), "+f"(d[118]), "+f"(d[119])
    : "l"(da), "l"(db), "r"(sd));
}
__device__ __forceinline__ void wgmma_ss_n216(float (&d)[108], uint64_t da, uint64_t db, int sd) {
  asm volatile("{\n.reg .pred p;\nsetp.ne.b32 p, %110, 0;\n"
      "wgmma.mma_async.sync.aligned.m64n216k16.f32.bf16.bf16 {"
      "%0, %1, %2, %3, %4, %5, %6, %7, %8, %9, %10, %11, %12, %13, %14, %15, "
      "%16, %17, %18, %19, %20, %21, %22, %23, %24, %25, %26, %27, %28, %29, %30, %31, "
      "%32, %33, %34, %35, %36, %37, %38, %39, %40, %41, %42, %43, %44, %45, %46, %47, "
      "%48, %49, %50, %51, %52, %53, %54, %55, %56, %57, %58, %59, %60, %61, %62, %63, "
      "%64, %65, %66, %67, %68, %69, %70, %71, %72, %73, %74, %75, %76, %77, %78, %79, "
      "%80, %81, %82, %83, %84, %85, %86, %87, %88, %89, %90, %91, %92, %93, %94, %95, "
      "%96, %97, %98, %99, %100, %101, %102, %103, %104, %105, %106, %107"
      "}, %108, %109, p, 1, 1, 0, 1;\n}\n"
    : "+f"(d[0]), "+f"(d[1]), "+f"(d[2]), "+f"(d[3]), "+f"(d[4]), "+f"(d[5]), "+f"(d[6]), "+f"(d[7]),
      "+f"(d[8]), "+f"(d[9]), "+f"(d[10]), "+f"(d[11]), "+f"(d[12]), "+f"(d[13]), "+f"(d[14]), "+f"(d[15]),
      "+f"(d[16]), "+f"(d[17]), "+f"(d[18]), "+f"(d[19]), "+f"(d[20]), "+f"(d[21]), "+f"(d[22]), "+f"(d[23]),
      "+f"(d[24]), "+f"(d[25]), "+f"(d[26]), "+f"(d[27]), "+f"(d[28]), "+f"(d[29]), "+f"(d[30]), "+f"(d[31]),
      "+f"(d[32]), "+f"(d[33]), "+f"(d[34]), "+f"(d[35]), "+f"(d[36]), "+f"(d[37]), "+f"(d[38]), "+f"(d[39]),
      "+f"(d[40]), "+f"(d[41]), "+f"(d[42]), "+f"(d[43]), "+f"(d[44]), "+f"(d[45]), "+f"(d[46]), "+f"(d[47]),
      "+f"(d[48]), "+f"(d[49]), "+f"(d[50]), "+f"(d[51]), "+f"(d[52]), "+f"(d[53]), "+f"(d[54]), "+f"(d[55]),
      "+f"(d[56]), "+f"(d[57]), "+f"(d[58]), "+f"(d[59]), "+f"(d[60]), "+f"(d[61]), "+f"(d[62]), "+f"(d[63]),
      "+f"(d[64]), "+f"(d[65]), "+f"(d[66]), "+f"(d[67]), "+f"(d[68]), "+f"(d[69]), "+f"(d[70]), "+f"(d[71]),
      "+f"(d[72]), "+f"(d[73]), "+f"(d[74]), "+f"(d[75]), "+f"(d[76]), "+f"(d[77]), "+f"(d[78]), "+f"(d[79]),
      "+f"(d[80]), "+f"(d[81]), "+f"(d[82]), "+f"(d[83]), "+f"(d[84]), "+f"(d[85]), "+f"(d[86]), "+f"(d[87]),
      "+f"(d[88]), "+f"(d[89]), "+f"(d[90]), "+f"(d[91]), "+f"(d[92]), "+f"(d[93]), "+f"(d[94]), "+f"(d[95]),
      "+f"(d[96]), "+f"(d[97]), "+f"(d[98]), "+f"(d[99]), "+f"(d[100]), "+f"(d[101]), "+f"(d[102]), "+f"(d[103]),
      "+f"(d[104]), "+f"(d[105]), "+f"(d[106]), "+f"(d[107])
    : "l"(da), "l"(db), "r"(sd));
}
__device__ __forceinline__ void wgmma_ss_n160(float (&d)[80], uint64_t da, uint64_t db, int sd) {
  asm volatile("{\n.reg .pred p;\nsetp.ne.b32 p, %82, 0;\n"
      "wgmma.mma_async.sync.aligned.m64n160k16.f32.bf16.bf16 {"
      "%0, %1, %2, %3, %4, %5, %6, %7, %8, %9, %10, %11, %12, %13, %14, %15, "
      "%16, %17, %18, %19, %20, %21, %22, %23, %24, %25, %26, %27, %28, %29, %30, %31, "
      "%32, %33, %34, %35, %36, %37, %38, %39, %40, %41, %42, %43, %44, %45, %46, %47, "
      "%48, %49, %50, %51, %52, %53, %54, %55, %56, %57, %58, %59, %60, %61, %62, %63, "
      "%64, %65, %66, %67, %68, %69, %70, %71, %72, %73, %74, %75, %76, %77, %78, %79"
      "}, %80, %81, p, 1, 1, 0, 1;\n}\n"
    : "+f"(d[0]), "+f"(d[1]), "+f"(d[2]), "+f"(d[3]), "+f"(d[4]), "+f"(d[5]), "+f"(d[6]), "+f"(d[7]),
      "+f"(d[8]), "+f"(d[9]), "+f"(d[10]), "+f"(d[11]), "+f"(d[12]), "+f"(d[13]), "+f"(d[14]), "+f"(d[15]),
      "+f"(d[16]), "+f"(d[17]), "+f"(d[18]), "+f"(d[19]), "+f"(d[20]), "+f"(d[21]), "+f"(d[22]), "+f"(d[23]),
      "+f"(d[24]), "+f"(d[25]), "+f"(d[26]), "+f"(d[27]), "+f"(d[28]), "+f"(d[29]), "+f"(d[30]), "+f"(d[31]),
      "+f"(d[32]), "+f"(d[33]), "+f"(d[34]), "+f"(d[35]), "+f"(d[36]), "+f"(d[37]), "+f"(d[38]), "+f"(d[39]),
      "+f"(d[40]), "+f"(d[41]), "+f"(d[42]), "+f"(d[43]), "+f"(d[44]), "+f"(d[45]), "+f"(d[46]), "+f"(d[47]),
      "+f"(d[48]), "+f"(d[49]), "+f"(d[50]), "+f"(d[51]), "+f"(d[52]), "+f"(d[53]), "+f"(d[54]), "+f"(d[55]),
      "+f"(d[56]), "+f"(d[57]), "+f"(d[58]), "+f"(d[59]), "+f"(d[60]), "+f"(d[61]), "+f"(d[62]), "+f"(d[63]),
      "+f"(d[64]), "+f"(d[65]), "+f"(d[66]), "+f"(d[67]), "+f"(d[68]), "+f"(d[69]), "+f"(d[70]), "+f"(d[71]),
      "+f"(d[72]), "+f"(d[73]), "+f"(d[74]), "+f"(d[75]), "+f"(d[76]), "+f"(d[77]), "+f"(d[78]), "+f"(d[79])
    : "l"(da), "l"(db), "r"(sd));
}
__device__ __forceinline__ void wgmma_ss_n80(float (&d)[40], uint64_t da, uint64_t db, int sd) {
  asm volatile("{\n.reg .pred p;\nsetp.ne.b32 p, %42, 0;\n"
      "wgmma.mma_async.sync.aligned.m64n80k16.f32.bf16.bf16 {"
      "%0, %1, %2, %3, %4, %5, %6, %7, %8, %9, %10, %11, %12, %13, %14, %15, "
      "%16, %17, %18, %19, %20, %21, %22, %23, %24, %25, %26, %27, %28, %29, %30, %31, "
      "%32, %33, %34, %35, %36, %37, %38, %39"
      "}, %40, %41, p, 1, 1, 0, 1;\n}\n"
    : "+f"(d[0]), "+f"(d[1]), "+f"(d[2]), "+f"(d[3]), "+f"(d[4]), "+f"(d[5]), "+f"(d[6]), "+f"(d[7]),
      "+f"(d[8]), "+f"(d[9]), "+f"(d[10]), "+f"(d[11]), "+f"(d[12]), "+f"(d[13]), "+f"(d[14]), "+f"(d[15]),
      "+f"(d[16]), "+f"(d[17]), "+f"(d[18]), "+f"(d[19]), "+f"(d[20]), "+f"(d[21]), "+f"(d[22]), "+f"(d[23]),
      "+f"(d[24]), "+f"(d[25]), "+f"(d[26]), "+f"(d[27]), "+f"(d[28]), "+f"(d[29]), "+f"(d[30]), "+f"(d[31]),
      "+f"(d[32]), "+f"(d[33]), "+f"(d[34]), "+f"(d[35]), "+f"(d[36]), "+f"(d[37]), "+f"(d[38]), "+f"(d[39])
    : "l"(da), "l"(db), "r"(sd));
}
__device__ __forceinline__ void wgmma_rs_n128(float (&d)[64], uint32_t a0, uint32_t a1, uint32_t a2, uint32_t a3,
                                  uint64_t db, int sd) {
  asm volatile("{\n.reg .pred p;\nsetp.ne.b32 p, %69, 0;\n"
      "wgmma.mma_async.sync.aligned.m64n128k16.f32.bf16.bf16 {"
      "%0, %1, %2, %3, %4, %5, %6, %7, %8, %9, %10, %11, %12, %13, %14, %15, "
      "%16, %17, %18, %19, %20, %21, %22, %23, %24, %25, %26, %27, %28, %29, %30, %31, "
      "%32, %33, %34, %35, %36, %37, %38, %39, %40, %41, %42, %43, %44, %45, %46, %47, "
      "%48, %49, %50, %51, %52, %53, %54, %55, %56, %57, %58, %59, %60, %61, %62, %63"
      "}, {%64, %65, %66, %67}, %68, p, 1, 1, 0;\n}\n"
    : "+f"(d[0]), "+f"(d[1]), "+f"(d[2]), "+f"(d[3]), "+f"(d[4]), "+f"(d[5]), "+f"(d[6]), "+f"(d[7]),
      "+f"(d[8]), "+f"(d[9]), "+f"(d[10]), "+f"(d[11]), "+f"(d[12]), "+f"(d[13]), "+f"(d[14]), "+f"(d[15]),
      "+f"(d[16]), "+f"(d[17]), "+f"(d[18]), "+f"(d[19]), "+f"(d[20]), "+f"(d[21]), "+f"(d[22]), "+f"(d[23]),
      "+f"(d[24]), "+f"(d[25]), "+f"(d[26]), "+f"(d[27]), "+f"(d[28]), "+f"(d[29]), "+f"(d[30]), "+f"(d[31]),
      "+f"(d[32]), "+f"(d[33]), "+f"(d[34]), "+f"(d[35]), "+f"(d[36]), "+f"(d[37]), "+f"(d[38]), "+f"(d[39]),
      "+f"(d[40]), "+f"(d[41]), "+f"(d[42]), "+f"(d[43]), "+f"(d[44]), "+f"(d[45]), "+f"(d[46]), "+f"(d[47]),
      "+f"(d[48]), "+f"(d[49]), "+f"(d[50]), "+f"(d[51]), "+f"(d[52]), "+f"(d[53]), "+f"(d[54]), "+f"(d[55]),
      "+f"(d[56]), "+f"(d[57]), "+f"(d[58]), "+f"(d[59]), "+f"(d[60]), "+f"(d[61]), "+f"(d[62]), "+f"(d[63])
    : "r"(a0), "r"(a1), "r"(a2), "r"(a3), "l"(db), "r"(sd));
}
__device__ __forceinline__ void wgmma_rs_n24(float (&d)[12], uint32_t a0, uint32_t a1, uint32_t a2, uint32_t a3,
                                  uint64_t db, int sd) {
  asm volatile("{\n.reg .pred p;\nsetp.ne.b32 p, %17, 0;\n"
      "wgmma.mma_async.sync.aligned.m64n24k16.f32.bf16.bf16 {"
      "%0, %1, %2, %3, %4, %5, %6, %7, %8, %9, %10, %11"
      "}, {%12, %13, %14, %15}, %16, p, 1, 1, 1;\n}\n"
    : "+f"(d[0]), "+f"(d[1]), "+f"(d[2]), "+f"(d[3]), "+f"(d[4]), "+f"(d[5]), "+f"(d[6]), "+f"(d[7]),
      "+f"(d[8]), "+f"(d[9]), "+f"(d[10]), "+f"(d[11])
    : "r"(a0), "r"(a1), "r"(a2), "r"(a3), "l"(db), "r"(sd));
}

constexpr int K1_ST = 4, K1_STAGE = 49152;
constexpr int K1_SMEM = K1_ST * K1_STAGE + 1024   + 1024   + 3072   + 128;

__global__ void __cluster_dims__(2, 1, 1) __launch_bounds__(384, 1)
k1_qkv(const __grid_constant__ CUtensorMap tmx, const __grid_constant__ CUtensorMap tmw,
       const bf16* __restrict__ x, const bf16* __restrict__ w, const bf16* __restrict__ wo,
       const bf16* __restrict__ wgate, const bf16* __restrict__ wup) {
  extern __shared__ __align__(1024) uint8_t sm[];
  float* cs = (float*)(sm + K1_ST * K1_STAGE);
  float2* rowab = (float2*)(sm + K1_ST * K1_STAGE + 1024);
  float* red = (float*)(sm + K1_ST * K1_STAGE + 2048);
  const uint32_t sbase = smem_u32(sm);
  const uint32_t fullb = sbase + K1_ST * K1_STAGE + 5120, emptyb = fullb + 8 * K1_ST;
  const int tid = threadIdx.x, lane = tid & 31;
  const int warp = __shfl_sync(~0u, tid >> 5, 0);
  const int rank = blockIdx.x & 1, cl = blockIdx.x >> 1;
  const int n = cl & 7, m = (cl >> 3) * 2 + rank;
  if (tid == 0) STAMP(0, 0);

  if (warp == 0) {
    if (lane == 0) {
      prefetch_map(&tmx); prefetch_map(&tmw);
      for (int i = 0; i < K1_ST; i++) { mbar_init(fullb + 8 * i, 1); mbar_init(emptyb + 8 * i, 4); }
      asm volatile("fence.mbarrier_init.release.cluster;" ::: "memory");
    }
    __syncwarp();
    cluster_arrive();
    if (lane == 0) {
      for (int kt = 0; kt < K1_ST; kt++) mbar_expect(fullb + 8 * kt, K1_STAGE);
      tma2d(sbase, &tmx, 0, m * 128, fullb);
    }
    __syncwarp();
    cluster_wait();
    if (tid == 0) STAMP(5, 3);
    if (lane == 0) {
#pragma unroll
      for (int j = 0; j < 4; j++) tma2d_mc(sbase + 16384 + rank * 16384 + j * 4096, &tmw, n * 240 + rank * 128 + j * 32, 0, fullb);
    }
    __syncwarp();
    bar_arrive(4, 384);
    if (lane == 0) {
      for (int kt = 1; kt < 10; kt++) {
        const int s = kt % K1_ST;
        const uint32_t sa = sbase + s * K1_STAGE, sb = sa + 16384 + rank * 16384;
        if (kt >= K1_ST) {
          mbar_wait(emptyb + 8 * s, ((kt / K1_ST) - 1) & 1);
          mbar_expect(fullb + 8 * s, K1_STAGE);
        }
        tma2d(sa, &tmx, kt * 64, m * 128, fullb + 8 * s);
#pragma unroll
        for (int j = 0; j < 4; j++) tma2d_mc(sb + j * 4096, &tmw, n * 240 + rank * 128 + j * 32, kt * 64, fullb + 8 * s);
        if (kt == K1_ST - 1) pdl_trigger();
      }
    }
    __syncwarp();
  } else if (warp < 4) {
    cluster_arrive();
    const int w3 = warp - 1, t96 = tid - 32;
    const uint32_t tag = __ldcg(&g_epoch) + 1;
    bar_sync(4, 384);
    {
      uint4 wv[14];
#pragma unroll
      for (int i = 0; i < 14; i++)
        wv[i] = ldg_nc(w + (size_t)(m * 40 + min(w3 + 3 * i, 39)) * 1920 + n * 240 + min(lane, 29) * 8);
      float acc8[8];
#pragma unroll
      for (int i = 0; i < 8; i++) acc8[i] = 0.f;
#pragma unroll
      for (int i = 0; i < 14; i++)
        if (i < 13 || w3 == 0) ACC8(acc8, wv[i]);
      *(float4*)&red[w3 * 256 + lane * 8] = make_float4(acc8[0], acc8[1], acc8[2], acc8[3]);
      *(float4*)&red[w3 * 256 + lane * 8 + 4] = make_float4(acc8[4], acc8[5], acc8[6], acc8[7]);
    }
    bar_sync(1, 96);
    for (int i = t96; i < 120; i += 96) {
      const float2 p0 = *(const float2*)&red[i * 2], p1 = *(const float2*)&red[256 + i * 2], p2 = *(const float2*)&red[512 + i * 2];
      st_relaxed(&g_cpart[(m * 8 + n) * 128 + i], p0.x + p1.x + p2.x, p0.y + p1.y + p2.y, tag);
    }
    if (tid == 32) STAMP(5, 7);
    for (int i = t96; i < 128; i += 96) {
      uint32_t it = 0;
      while (true) {
        uint4 p[16];
        const uint4 st = ld_relaxed(&g_rowstat[m * 128 + i]);
#pragma unroll
        for (int k = 0; k < 16; k++) p[k] = ld_relaxed(&g_cpart[(k * 8 + n) * 128 + min(i, 119)]);
        bool ok = st.y == tag && st.w == tag;
        float s0 = 0.f, s1 = 0.f;
#pragma unroll
        for (int k = 0; k < 16; k++) {
          ok = ok && p[k].y == tag && p[k].w == tag;
          s0 += __uint_as_float(p[k].x); s1 += __uint_as_float(p[k].z);
        }
        if (ok) {
          *(float2*)&cs[i * 2] = make_float2(s0, s1);
          rowab[i] = make_float2(__uint_as_float(st.x), -__uint_as_float(st.x) * __uint_as_float(st.z));
          break;
        }
        if (++it > (1u << 20)) wait_timeout();
      }
    }
    __syncwarp();
    bar_arrive(2, 96 + 256);
    if (tid == 32) STAMP(0, 5);
    if (blockIdx.x < 108) {
      const int cg = blockIdx.x * 4 + (lane & 3), up = cg >= 216;
      const bf16* src = (up ? wup : wgate) + (cg - up * 216) * 8;
      const int r0 = w3 * 8 + (lane >> 2);
      float a8[8];
#pragma unroll
      for (int i = 0; i < 8; i++) a8[i] = 0.f;
#pragma unroll
      for (int bt = 0; bt < 2; bt++) {
        uint4 v[14];
#pragma unroll
        for (int i = 0; i < 14; i++) v[i] = ldg_nc(src + (size_t)min(r0 + 24 * (bt * 14 + i), 639) * F_);
#pragma unroll
        for (int i = 0; i < 14; i++)
          if (r0 + 24 * (bt * 14 + i) < 640) ACC8(a8, v[i]);
      }
#pragma unroll
      for (int i = 0; i < 8; i++) {
        a8[i] += __shfl_xor_sync(~0u, a8[i], 4);
        a8[i] += __shfl_xor_sync(~0u, a8[i], 8);
        a8[i] += __shfl_xor_sync(~0u, a8[i], 16);
      }
      if (lane < 4) {
        *(float4*)&red[w3 * 32 + lane * 8] = make_float4(a8[0], a8[1], a8[2], a8[3]);
        *(float4*)&red[w3 * 32 + lane * 8 + 4] = make_float4(a8[4], a8[5], a8[6], a8[7]);
      }
      bar_sync(1, 96);
      if (t96 < 32) g_csgu[blockIdx.x * 32 + t96] = red[t96] + red[32 + t96] + red[64 + t96];
    }
    {
      uint4 v[5];
      if (t96 < 80) {
#pragma unroll
        for (int i = 0; i < 5; i++) {
          const int k = blockIdx.x * 5 + i, pr = k / 40, r = k - pr * 40;
          v[i] = ldg_nc(wo + (size_t)(pr * 40 + (r < 16 ? r : (r < 32 ? r + 4 : (r < 36 ? r - 16 : r)))) * D_ + t96 * 8);
        }
        const int nt = t96 / 10;
#pragma unroll
        for (int i = 0; i < 5; i++) {
          const int k = blockIdx.x * 5 + i;
          g_wo[((nt * 10 + (k >> 6)) * 10 + t96 - nt * 10) * 64 + (k & 63)] = v[i];
        }
      }
    }
    if (tid == 32) STAMP(0, 7);
    __syncwarp();
    cluster_wait();
  } else {
    cluster_arrive();
    const int cw = warp - 4, wg = cw >> 2;
    const uint32_t tag = __ldcg(&g_epoch) + 1;
    bar_sync(4, 384);
    {
      uint4 xv[2][3];
#pragma unroll
      for (int i = 0; i < 2; i++) {
        const bf16* xr = x + (size_t)(m * 128 + n * 16 + cw * 2 + i) * D_ + lane * 8;
        xv[i][0] = ldg_nc(xr);
        xv[i][1] = ldg_nc(xr + 256);
        xv[i][2] = ldg_nc(xr + (lane < 16 ? 512 : 0));
      }
#pragma unroll
      for (int i = 0; i < 2; i++) {
        float f[24];
#pragma unroll
        for (int k = 0; k < 3; k++) {
          const uint4 v = xv[i][k];
          f[8 * k + 0] = bf_lo(v.x); f[8 * k + 1] = bf_hi(v.x); f[8 * k + 2] = bf_lo(v.y); f[8 * k + 3] = bf_hi(v.y);
          f[8 * k + 4] = bf_lo(v.z); f[8 * k + 5] = bf_hi(v.z); f[8 * k + 6] = bf_lo(v.w); f[8 * k + 7] = bf_hi(v.w);
        }
        float s = 0.f, s2 = 0.f;
#pragma unroll
        for (int k = 0; k < 16; k++) s += f[k];
#pragma unroll
        for (int k = 16; k < 24; k++) s2 += f[k];
        if (lane < 16) s += s2;
#pragma unroll
        for (int o = 16; o; o >>= 1) s += __shfl_xor_sync(~0u, s, o);
        const float mean = s * (1.f / D_);
        float q = 0.f, q2 = 0.f;
#pragma unroll
        for (int k = 0; k < 16; k++) { float d = f[k] - mean; q = fmaf(d, d, q); }
#pragma unroll
        for (int k = 16; k < 24; k++) { float d = f[k] - mean; q2 = fmaf(d, d, q2); }
        if (lane < 16) q += q2;
#pragma unroll
        for (int o = 16; o; o >>= 1) q += __shfl_xor_sync(~0u, q, o);
        if (lane == 0) st_relaxed(&g_rowstat[m * 128 + n * 16 + cw * 2 + i], rsqrtf(q * (1.f / D_) + 1e-5f), mean, tag);
      }
      if (tid == 128) STAMP(5, 2);
    }
    float acc[120];
    const uint64_t da0 = mkdesc(sbase + wg * 8192, 16, 1024, 1);
    const uint64_t db0 = mkdesc(sbase + 16384, 4096, 512, 2);
    cluster_wait();
#pragma unroll 1
    for (int kt = 0; kt < 10; kt++) {
      const int s = kt % K1_ST;
      mbar_wait(fullb + 8 * s, (kt / K1_ST) & 1);
      if (kt == 0 && tid == 128) STAMP(0, 1);
      const uint64_t da = da0 + s * (K1_STAGE >> 4), db = db0 + s * (K1_STAGE >> 4);
      WG_FENCE();
#pragma unroll
      for (int k = 0; k < 4; k++) wgmma_ss_n240(acc, da + k * 2, db + k * 64, (kt | k) != 0);
      WG_COMMIT();
      if (kt > 0) {
        WG_WAIT(1);
        if (kt - 1 + K1_ST < 10 && (tid & 127) < 2) mbar_arrive_cta(emptyb + 8 * ((kt - 1) % K1_ST), tid & 1);
      }
    }
    WG_WAIT(0);
    fence_regs(acc);
    if (tid == 128) STAMP(0, 2);
    bar_sync(2, 96 + 256);
    if (tid == 128) STAMP(0, 3);
    const int g = lane >> 2, c = lane & 3;
    const bool lo = c < 2;
    const float2 ab0 = rowab[cw * 16 + g], ab1 = rowab[cw * 16 + g + 8];
    const bool p0 = (POLY_MASK >> (cw * 2)) & 1, p1 = (POLY_MASK >> (cw * 2 + 1)) & 1;
    const uint32_t padq = c == 2 ? 0x3F803F80u : 0x00003F80u, padk = c == 2 ? 0x4A7A4B00u : 0x00004653u;
    const uint32_t padv = c == 2 ? 0x00003F80u : 0u;
    uint8_t* dst = (uint8_t*)g_qkv + (size_t)(n * 12) * HEAD_IMG + m * 6144 + lane * 4;
#pragma unroll
    for (int hp = 0; hp < 6; hp++) {
      const int sec = (n * 12 + hp * 2) >> 5;
      const float f0 = sec == 0 ? QSCALE : (sec == 1 && p0 ? 32768.f : 1.f), f1 = sec == 0 ? QSCALE : (sec == 1 && p1 ? 32768.f : 1.f);
      const uint32_t pad0 = sec == 0 ? padq : (sec == 2 ? padv : (p0 ? padk : 0u));
      const uint32_t pad1 = sec == 0 ? padq : (sec == 2 ? padv : (p1 ? padk : 0u));
      const float a0 = ab0.x * f0, b0 = ab0.y * f0, a1 = ab1.x * f1, b1 = ab1.y * f1;
      uint32_t u[5], v[5];
      float su[5], sv[5];
#pragma unroll
      for (int i = 0; i < 5; i++) {
        const int j = hp * 5 + i;
        const float2 t = *(const float2*)&cs[j * 8 + c * 2];
        const float x0 = fmaf(acc[4 * j], a0, b0 * t.x), x1 = fmaf(acc[4 * j + 1], a0, b0 * t.y);
        const float y0 = fmaf(acc[4 * j + 2], a1, b1 * t.x), y1 = fmaf(acc[4 * j + 3], a1, b1 * t.y);
        u[i] = pack_bf16(x0, x1); v[i] = pack_bf16(y0, y1);
        su[i] = fmaf(x0, x0, x1 * x1); sv[i] = fmaf(y0, y0, y1 * y1);
      }
      if (sec < 2) {
        const float r0 = (sec == 1 && p0) ? 9.313225746154785e-10f : 1.f, r1 = (sec == 1 && p1) ? 9.313225746154785e-10f : 1.f;
        float e0 = (su[0] + su[1] + (lo ? su[2] : 0.f)) * r0, e1 = (sv[0] + sv[1] + (lo ? sv[2] : 0.f)) * r1;
        float o0 = (su[3] + su[4] + (lo ? 0.f : su[2])) * r0, o1 = (sv[3] + sv[4] + (lo ? 0.f : sv[2])) * r1;
        e0 += __shfl_xor_sync(~0u, e0, 1); e1 += __shfl_xor_sync(~0u, e1, 1);
        o0 += __shfl_xor_sync(~0u, o0, 1); o1 += __shfl_xor_sync(~0u, o1, 1);
        e0 += __shfl_xor_sync(~0u, e0, 2); e1 += __shfl_xor_sync(~0u, e1, 2);
        o0 += __shfl_xor_sync(~0u, o0, 2); o1 += __shfl_xor_sync(~0u, o1, 2);
        const uint32_t em = __reduce_max_sync(~0u, max(__float_as_uint(e0), __float_as_uint(e1)));
        const uint32_t om = __reduce_max_sync(~0u, max(__float_as_uint(o0), __float_as_uint(o1)));
        if (lane < 2) g_nrm[(n * 12 + hp * 2 + lane) * 128 + m * 8 + cw] = __uint_as_float(lane ? om : em);
      }
      const int cst = sec == 1 ? 2048 : 128, gst = sec == 1 ? 128 : 384;
      uint8_t* pe = dst + (size_t)hp * 2 * HEAD_IMG + cw * 2 * gst;
      uint8_t* pf = pe + gst;
      *(uint32_t*)(pe) = u[0];       *(uint32_t*)(pf) = v[0];
      *(uint32_t*)(pe + cst) = u[1]; *(uint32_t*)(pf + cst) = v[1];
      *(uint32_t*)(pe + 2 * cst) = lo ? u[2] : pad0; *(uint32_t*)(pf + 2 * cst) = lo ? v[2] : pad1;
      *(uint32_t*)(pe + HEAD_IMG) = __shfl_xor_sync(~0u, lo ? u[3] : u[2], 2);
      *(uint32_t*)(pf + HEAD_IMG) = __shfl_xor_sync(~0u, lo ? v[3] : v[2], 2);
      *(uint32_t*)(pe + cst + HEAD_IMG) = __shfl_xor_sync(~0u, lo ? u[4] : u[3], 2);
      *(uint32_t*)(pf + cst + HEAD_IMG) = __shfl_xor_sync(~0u, lo ? v[4] : v[3], 2);
      const uint32_t tu = __shfl_xor_sync(~0u, u[4], 2), tv = __shfl_xor_sync(~0u, v[4], 2);
      *(uint32_t*)(pe + 2 * cst + HEAD_IMG) = lo ? tu : pad0; *(uint32_t*)(pf + 2 * cst + HEAD_IMG) = lo ? tv : pad1;
    }
    if (tid == 128) STAMP(0, 4);
  }
  cluster_sync_relaxed();
  if (tid == 128) STAMP(0, 6);
}

constexpr int K2_SMEM = 2 * HEAD_IMG + 2 * 6144 + 2 * 10240 + 256;

__device__ __forceinline__ uint64_t desc64(uint32_t lo, uint32_t hi) {
  uint64_t d;
  asm("mov.b64 %0, {%1, %2};" : "=l"(d) : "r"(lo), "r"(hi));
  return d;
}
__device__ __forceinline__ uint32_t exp_pair(bool poly, float a, float b, uint32_t mk) {
  if (poly) {
    const uint32_t pk = __byte_perm(__float_as_uint(a), __float_as_uint(b), 0x6521);
    uint32_t m, q;
    asm("lop3.b32 %0, %1, %2, 0x3f803f80, 0xEA;" : "=r"(m) : "r"(pk), "r"(mk));
    asm("fma.rn.bf16x2 %0, %1, %1, %2;" : "=r"(q) : "r"(m), "r"(0x40014001u));
    return pk - m + q;
  }
  return pack_bf16(ex2(a), ex2(b));
}
#define PV_GR 2
__device__ __forceinline__ void exp_pv(const float (&s)[64], float (&o)[12], uint64_t dv, uint32_t mk) {
#pragma unroll
  for (int k0 = 0; k0 < 8; k0 += PV_GR) {
    uint32_t p[4 * PV_GR];
#pragma unroll
    for (int i = 0; i < 4 * PV_GR; i++)
      p[i] = exp_pair((POLY_MASK >> (k0 * 2 + i / 2)) & 1, s[k0 * 8 + 2 * i], s[k0 * 8 + 2 * i + 1], mk);
    WG_FENCE();
#pragma unroll
    for (int k = 0; k < PV_GR; k++)
      wgmma_rs_n24(o, p[4 * k], p[4 * k + 1], p[4 * k + 2], p[4 * k + 3], dv + (k0 + k) * 48, 1);
  }
}
__device__ __forceinline__ void load_q(uint32_t (&q)[6], const uint8_t* p) {
  q[0] = __ldcg((const uint32_t*)p);         q[1] = __ldcg((const uint32_t*)(p + 384));
  q[2] = __ldcg((const uint32_t*)(p + 128)); q[3] = __ldcg((const uint32_t*)(p + 512));
  q[4] = __ldcg((const uint32_t*)(p + 256)); q[5] = __ldcg((const uint32_t*)(p + 640));
}
__device__ __forceinline__ float rcp(float x) {
  float y;
  asm("rcp.approx.ftz.f32 %0, %1;" : "=f"(y) : "f"(x));
  return y;
}
__device__ __forceinline__ int img_off(int chunk) { return (chunk >> 3) * 16384 + (chunk & 7) * 128; }
__device__ __forceinline__ void store_o(const float (&o)[12], int tile) {
  int tid, bid;
  asm volatile("mov.u32 %0, %%tid.x;" : "=r"(tid));
  asm volatile("mov.u32 %0, %%ctaid.x;" : "=r"(bid));
  const int head = bid >> 2;
  uint8_t* dst = (uint8_t*)g_o + ((bid & 3) * 4 + (tile >> 1)) * 163840 + (tile & 1) * 8192 + ((tid >> 5) & 3) * 2048 + (tid & 31) * 4;
  const int oc = (head >> 1) * 5 + (head & 1) * 2;
  const int o0 = img_off(oc), o1 = img_off(oc + 1), o2 = img_off((head >> 1) * 5 + 4) + (head & 1) * 8;
  const float i0 = rcp(__shfl_sync(~0u, o[8], 2, 4)), i1 = rcp(__shfl_sync(~0u, o[10], 2, 4));
  *(uint32_t*)(dst + o0) = pack_bf16(o[0] * i0, o[1] * i0); *(uint32_t*)(dst + o0 + 1024) = pack_bf16(o[2] * i1, o[3] * i1);
  *(uint32_t*)(dst + o1) = pack_bf16(o[4] * i0, o[5] * i0); *(uint32_t*)(dst + o1 + 1024) = pack_bf16(o[6] * i1, o[7] * i1);
  if ((tid & 3) < 2) {
    *(uint32_t*)(dst + o2) = pack_bf16(o[8] * i0, o[9] * i0);
    *(uint32_t*)(dst + o2 + 1024) = pack_bf16(o[10] * i1, o[11] * i1);
  }
}

__global__ void __launch_bounds__(512, 1)
k2_attn(const __grid_constant__ CUtensorMap tmg, const __grid_constant__ CUtensorMap tmu,
        const __grid_constant__ CUtensorMap tmd, uint32_t mk) {
  extern __shared__ __align__(1024) uint8_t sm[];
  const uint32_t sbase = smem_u32(sm);
  float* part = (float*)(sm + 2 * HEAD_IMG);
  const uint32_t rbuf = sbase + 2 * HEAD_IMG + 2 * 6144;
  const uint32_t kvb = rbuf + 2 * 10240;
  const uint32_t partb = kvb + 128, rbar = kvb + 144;
  const int tid = threadIdx.x, lane = tid & 31;
  const int warp = __shfl_sync(~0u, tid >> 5, 0);
  const int head = blockIdx.x >> 2, qb = blockIdx.x & 3;

  if (tid == 0) STAMP(1, 0);
  if (tid == 0) {
    for (int i = 0; i < 16; i++) mbar_init(kvb + 8 * i, 1);
    mbar_init(partb, 128); mbar_init(partb + 8, 128); mbar_init(rbar, 1); mbar_init(rbar + 8, 1);
    asm volatile("fence.mbarrier_init.release.cluster;" ::: "memory");
  }
  __syncthreads();

  if (warp >= 12) {
    asm volatile("setmaxnreg.dec.sync.aligned.u32 32;");
    if (tid == 384) {
      pdl_wait();
      pdl_trigger();
      const uint8_t* kimg = (const uint8_t*)g_qkv + (size_t)(32 + head) * HEAD_IMG;
#pragma unroll 1
      for (int b = 0; b < 16; b++) {
        mbar_expect(kvb + 8 * b, 12288);
        bulk_ld(sbase + b * 6144, kimg + b * 6144, 6144, kvb + 8 * b);
        bulk_ld(sbase + HEAD_IMG + b * 6144, kimg + 32 * HEAD_IMG + b * 6144, 6144, kvb + 8 * b);
      }
      if (blockIdx.x == 0) g_epoch = g_epoch + 1;
      mbar_wait(kvb + 8 * 15, 0);
      uint8_t* pdst = nullptr;
      uint32_t pbytes = 0;
#pragma unroll 1
      for (int i = 0; i < 7; i++) {
        const int p = blockIdx.x + 128 * i;
        uint8_t* dst = nullptr;
        uint32_t bytes = 0;
        if (i < 6 && p < 696) {
          asm volatile("cp.async.bulk.wait_group.read 0;" ::: "memory");
          if (p < 480) {
            const int nk = p / 6, r = p - nk * 6, nt = nk / 10, kt = nk - nt * 10, up = r / 3;
            bytes = 9216;
            dst = (uint8_t*)g_wgu + (size_t)(nk * 54 + r * 9) * 1024;
            mbar_expect(rbar + 8 * (i & 1), bytes);
            tma3d(rbuf + (i & 1) * 10240, up ? &tmu : &tmg, kt * 64, nt * 27 + (r - up * 3) * 9, rbar + 8 * (i & 1));
          } else {
            const int nk = p - 480, nt = nk / 27, kt = nk - nt * 27;
            bytes = 10240;
            dst = (uint8_t*)g_wd + (size_t)nk * 10240;
            mbar_expect(rbar + 8 * (i & 1), bytes);
            tma3d(rbuf + (i & 1) * 10240, &tmd, kt * 64, nt * 10, rbar + 8 * (i & 1));
          }
        }
        if (pbytes) {
          mbar_wait(rbar + 8 * ((i - 1) & 1), ((i - 1) >> 1) & 1);
          bulk_st(pdst, rbuf + ((i - 1) & 1) * 10240, pbytes);
          asm volatile("cp.async.bulk.commit_group;" ::: "memory");
        }
        pdst = dst; pbytes = bytes;
      }
      asm volatile("cp.async.bulk.wait_group.read 0;" ::: "memory");
      STAMP(1, 6);
    }
  } else {
    asm volatile("setmaxnreg.inc.sync.aligned.u32 160;");
    const int wg = warp >> 2;
    const uint8_t* qthr = (const uint8_t*)g_qkv + (size_t)head * HEAD_IMG + qb * 64 * 384 + (warp & 3) * 768 + lane * 4;
    const uint32_t klo0 = ((sbase & 0x3FFFF) >> 4) | (128u << 16), vlo0 = (((sbase + HEAD_IMG) & 0x3FFFF) >> 4) | (24u << 16);
    constexpr int64_t KSTEP2 = 256 - (128 << 16);
    const int nun = wg == 1 ? 4 : 3;
    uint32_t utile = wg == 0 ? 0x210u : (wg == 1 ? 0x4325u : 0x576u);
    uint32_t ubeg = wg == 0 ? 0u : (wg == 1 ? 0x00b0u : 0x600u);
    uint32_t ulen = wg == 0 ? 0x0b1010u : (wg == 1 ? 0x10100506u : 0x0a1010u);
    pdl_wait();
    if (tid == 0) STAMP(1, 1);
    uint32_t q[6], qn[6];
    load_q(q, qthr + (utile & 15) * 3072);
    load_q(qn, qthr + ((utile >> 4) & 15) * 3072);
    bool fast;
    {
      const float4 kn = __ldcg((const float4*)&g_nrm[(32 + head) * 128 + lane * 4]);
      const float qv = __ldcg(&g_nrm[head * 128 + qb * 32 + lane]);
      const uint32_t km = max(max(__float_as_uint(kn.x), __float_as_uint(kn.y)), max(__float_as_uint(kn.z), __float_as_uint(kn.w)));
      const float k2 = __uint_as_float(__reduce_max_sync(~0u, km)), q2 = __uint_as_float(__reduce_max_sync(~0u, __float_as_uint(qv)));
      fast = q2 * k2 <= 3400.f;
    }
    if (fast) {
      float s[64], o[12];
#pragma unroll
      for (int i = 0; i < 12; i++) o[i] = 0.f;
      uint32_t klo = klo0, vlo = vlo0, kb = kvb;
      int cnt = ulen & 255, u = 0;
      bool wt = true;
      mbar_wait(kb, 0);
      if (tid == 0) STAMP(5, 4);
      fence_regs(o);
      WG_FENCE();
      wgmma_rs_n128(s, q[0], q[1], q[2], q[3], desc64(klo, 8), 0);
      wgmma_rs_n128(s, q[4], q[5], 0, 0, desc64(klo, 8) + KSTEP2, 1);
      WG_COMMIT();
#pragma unroll 1
      while (true) {
        const bool last = --cnt == 0;
        if (last) {
          if (u + 1 == nun) break;
          const uint32_t b = (ubeg >> 4) & 15;
          klo = klo0 + b * 384 - 384; kb = kvb + b * 8 - 8;
          wt = wg == 1 && u < 2;
        }
        klo += 384; kb += 8;
        if (wt) mbar_wait(kb, 0);
        WG_WAIT(0);
        fence_regs(s); fence_regs(o);
        exp_pv(s, o, desc64(vlo, 8), mk);
        vlo += 384;
        if (last) {
#pragma unroll
          for (int i = 0; i < 6; i++) q[i] = qn[i];
          WG_FENCE();
        }
        wgmma_rs_n128(s, q[0], q[1], q[2], q[3], desc64(klo, 8), 0);
        wgmma_rs_n128(s, q[4], q[5], 0, 0, desc64(klo, 8) + KSTEP2, 1);
        WG_COMMIT();
        if (last) {
          if (u + 2 < nun) load_q(qn, qthr + ((utile >> 8) & 15) * 3072);
          WG_WAIT(0);
          fence_regs(s); fence_regs(o);
          if (wg == 1 && u < 2) {
            float4* pp = (float4*)(part + u * 1536) + (tid & 127);
            pp[0] = make_float4(o[0], o[1], o[2], o[3]);
            pp[128] = make_float4(o[4], o[5], o[6], o[7]);
            pp[256] = make_float4(o[8], o[9], o[10], o[11]);
            mbar_arrive(partb + 8 * u);
          } else {
            store_o(o, utile & 15);
          }
#pragma unroll
          for (int i = 0; i < 12; i++) o[i] = 0.f;
          u++; utile >>= 4; ubeg >>= 4; ulen >>= 8;
          cnt = ulen & 255;
          vlo = vlo0 + (ubeg & 15) * 384;
          if (tid == 0) STAMP(5, 4 + u);
        }
      }
      WG_WAIT(0);
      fence_regs(s); fence_regs(o);
      exp_pv(s, o, desc64(vlo, 8), mk);
      WG_COMMIT();
      WG_WAIT(0);
      fence_regs(o);
      if (wg != 1) {
        const int pi = wg == 0 ? 1 : 0;
        mbar_wait(partb + 8 * pi, 0);
        const float4* pp = (const float4*)(part + pi * 1536) + (tid & 127);
        const float4 x0 = pp[0], x1 = pp[128], x2 = pp[256];
        o[0] += x0.x; o[1] += x0.y; o[2] += x0.z; o[3] += x0.w; o[4] += x1.x; o[5] += x1.y;
        o[6] += x1.z; o[7] += x1.w; o[8] += x2.x; o[9] += x2.y; o[10] += x2.z; o[11] += x2.w;
      }
      store_o(o, utile & 15);
      if ((tid & 127) == 0) STAMP(1, 3 + wg);
    } else {
#pragma unroll 1
      for (int tile = wg; tile < 8; tile += 3) {
        load_q(q, qthr + tile * 3072);
        if ((lane & 3) >= 2) { q[4] = 0; q[5] = 0; }
        float o[12], m0 = -INFINITY, m1 = -INFINITY;
#pragma unroll
        for (int i = 0; i < 12; i++) o[i] = 0.f;
#pragma unroll 1
        for (int b = 0; b < 16; b++) {
          float s[64];
          mbar_wait(kvb + 8 * b, 0);
          WG_FENCE();
          wgmma_rs_n128(s, q[0], q[1], q[2], q[3], desc64(klo0 + b * 384, 8), 0);
          wgmma_rs_n128(s, q[4], q[5], 0, 0, desc64(klo0 + b * 384, 8) + KSTEP2, 1);
          WG_COMMIT();
          WG_WAIT(0);
          fence_regs(s);
          float x0 = m0, x1 = m1;
#pragma unroll
          for (int j = 0; j < 16; j++) {
            if ((POLY_MASK >> j) & 1) {
#pragma unroll
              for (int i = 0; i < 4; i++) s[4 * j + i] *= (1.f / 32768.f);
            }
            x0 = fmaxf(x0, fmaxf(s[4 * j], s[4 * j + 1]));
            x1 = fmaxf(x1, fmaxf(s[4 * j + 2], s[4 * j + 3]));
          }
          x0 = fmaxf(x0, __shfl_xor_sync(~0u, x0, 1)); x0 = fmaxf(x0, __shfl_xor_sync(~0u, x0, 2));
          x1 = fmaxf(x1, __shfl_xor_sync(~0u, x1, 1)); x1 = fmaxf(x1, __shfl_xor_sync(~0u, x1, 2));
          const float al0 = ex2(m0 - x0), al1 = ex2(m1 - x1);
          m0 = x0; m1 = x1;
#pragma unroll
          for (int i = 0; i < 12; i++) o[i] *= (i & 2) ? al1 : al0;
          uint32_t p[32];
#pragma unroll
          for (int i = 0; i < 32; i++) {
            const float mm = (i & 1) ? m1 : m0;
            p[i] = pack_bf16(ex2(s[2 * i] - mm), ex2(s[2 * i + 1] - mm));
          }
          fence_regs(o);
          WG_FENCE();
#pragma unroll
          for (int k = 0; k < 8; k++)
            wgmma_rs_n24(o, p[4 * k], p[4 * k + 1], p[4 * k + 2], p[4 * k + 3], desc64(vlo0 + b * 384 + k * 48, 8), 1);
          WG_COMMIT();
          WG_WAIT(0);
          fence_regs(o);
        }
        store_o(o, tile);
      }
    }
  }
}

constexpr int K3_ST = 4, K3_STAGE = 36864;
constexpr int K3_SMEM = K3_ST * K3_STAGE + 40960 + 20480 + 256;

template <int KT, bool FIRST>
__global__ void __cluster_dims__(2, 1, 1) __launch_bounds__(384, 1)
k3_proj(const __grid_constant__ CUtensorMap tmr, const uint4* __restrict__ aimg, const uint4* __restrict__ wimg) {
  extern __shared__ __align__(1024) uint8_t sm[];
  const uint32_t sbase = smem_u32(sm);
  uint8_t* xch = sm + K3_ST * K3_STAGE;
  uint8_t* stg = sm + K3_ST * K3_STAGE + 40960;
  const uint32_t fullb = smem_u32(stg) + 20480, emptyb = fullb + 8 * K3_ST, resb = emptyb + 8 * K3_ST, xchb = resb + 8;
  const int tid = threadIdx.x, lane = tid & 31;
  const int warp = __shfl_sync(~0u, tid >> 5, 0);
  const int rank = blockIdx.x & 1;
  const int n = blockIdx.x & 7, m = blockIdx.x >> 3;
  const int kt0 = rank * ((KT + 1) / 2), nkt = rank ? KT / 2 : (KT + 1) / 2;
  if (tid == 0) STAMP(FIRST ? 2 : 4, 0);
  if (tid == 0) {
    prefetch_map(&tmr);
    for (int i = 0; i < K3_ST; i++) { mbar_init(fullb + 8 * i, 1); mbar_init(emptyb + 8 * i, 2); }
    mbar_init(resb, 1); mbar_init(xchb, 1);
    mbar_expect(xchb, 40960);
    asm volatile("fence.mbarrier_init.release.cluster;" ::: "memory");
  }
  __syncthreads();
  cluster_arrive();
  if (warp == 0) {
    if (lane == 0) {
      const uint8_t* wk = (const uint8_t*)wimg + (size_t)(n * KT + kt0) * 10240;
      const uint8_t* ws = (const uint8_t*)wimg + (size_t)((n ^ 1) * KT + kt0) * 10240;
      const uint8_t* ab = (const uint8_t*)aimg + (size_t)(m * KT + kt0) * 16384;
      mbar_expect(fullb, K3_STAGE);
      bulk_ld(sbase + 16384, wk, 10240, fullb);
      bulk_ld(sbase + 26624, ws, 10240, fullb);
      pdl_wait();
      pdl_trigger();
      for (int i = 0; i < nkt; i++) {
        const int s = i % K3_ST;
        const uint32_t sa = sbase + s * K3_STAGE;
        if (i >= K3_ST) mbar_wait(emptyb + 8 * s, ((i / K3_ST) - 1) & 1);
        if (i > 0) mbar_expect(fullb + 8 * s, K3_STAGE);
        bulk_ld(sa, ab + i * 16384, 16384, fullb + 8 * s);
        if (i > 0) {
          bulk_ld(sa + 16384, wk + i * 10240, 10240, fullb + 8 * s);
          bulk_ld(sa + 26624, ws + i * 10240, 10240, fullb + 8 * s);
        }
        if (FIRST && i == K3_ST - 1) {
          mbar_expect(resb, 20480);
          tma2d(smem_u32(stg), &tmr, n * 80, m * 128, resb);
          tma2d(smem_u32(stg) + 10240, &tmr, n * 80, m * 128 + 64, resb);
        }
      }
    }
    __syncwarp();
    cluster_wait();
  } else if (warp >= 4) {
    const int cw = warp - 4, wg = cw >> 2;
    const int g = lane >> 2, c = lane & 3;
    uint8_t* himg = (uint8_t*)g_h + (size_t)m * 163840 + cw * 2048 + g * 16 + c * 4;
    uint32_t rv[20];
    if (!FIRST) {
#pragma unroll
      for (int j = 0; j < 10; j++) {
        rv[2 * j] = __ldcg((const uint32_t*)(himg + img_off(n * 10 + j)));
        rv[2 * j + 1] = __ldcg((const uint32_t*)(himg + img_off(n * 10 + j) + 1024));
      }
    }
    float acc[80];
    const uint64_t da0 = mkdesc(sbase + wg * 8192, 128, 1024, 0);
    const uint64_t db0 = mkdesc(sbase + 16384, 128, 1024, 0);
#pragma unroll 1
    for (int i = 0; i < nkt; i++) {
      const int s = i % K3_ST;
      mbar_wait(fullb + 8 * s, (i / K3_ST) & 1);
      if (i == 0 && tid == 128) STAMP(FIRST ? 2 : 4, 2);
      const uint64_t da = da0 + s * (K3_STAGE >> 4), db = db0 + s * (K3_STAGE >> 4);
      WG_FENCE();
#pragma unroll
      for (int k = 0; k < 4; k++) wgmma_ss_n160(acc, da + k * 16, db + k * 16, (i | k) != 0);
      WG_COMMIT();
      if (i > 0) {
        WG_WAIT(1);
        if ((tid & 127) == 0) mbar_arrive(emptyb + 8 * ((i - 1) % K3_ST));
      }
    }
    uint8_t* sp = stg + (cw * 16 + g) * 160 + c * 4;
    if (FIRST) {
      mbar_wait(resb, 0);
#pragma unroll
      for (int j = 0; j < 10; j++) {
        rv[2 * j] = *(const uint32_t*)(sp + j * 16);
        rv[2 * j + 1] = *(const uint32_t*)(sp + 1280 + j * 16);
      }
    }
    cluster_wait();
    WG_WAIT(0);
    fence_regs(acc);
    if (tid == 128) STAMP(FIRST ? 2 : 4, 3);
    bar_sync(3, 256);
#pragma unroll
    for (int j = 0; j < 10; j++)
      *(float4*)(sm + cw * 5120 + j * 512 + lane * 16) = make_float4(acc[40 + 4 * j], acc[41 + 4 * j], acc[42 + 4 * j], acc[43 + 4 * j]);
    fence_async();
    __syncwarp();
    if (lane == 0)
      asm volatile("cp.async.bulk.shared::cluster.shared::cta.mbarrier::complete_tx::bytes [%0], [%1], 5120, [%2];"
                   ::"r"(mapa(smem_u32(xch) + cw * 5120, rank ^ 1)), "r"(sbase + cw * 5120), "r"(mapa(xchb, rank ^ 1)) : "memory");
#pragma unroll
    for (int j = 0; j < 10; j++) {
      acc[4 * j] += bf_lo(rv[2 * j]); acc[4 * j + 1] += bf_hi(rv[2 * j]);
      acc[4 * j + 2] += bf_lo(rv[2 * j + 1]); acc[4 * j + 3] += bf_hi(rv[2 * j + 1]);
    }
    mbar_wait(xchb, 0);
    if (tid == 128) STAMP(FIRST ? 2 : 4, 5);
    float s0 = 0.f, s1 = 0.f;
#pragma unroll
    for (int j = 0; j < 10; j++) {
      const float4 p = *(const float4*)(xch + cw * 5120 + j * 512 + lane * 16);
      acc[4 * j] += p.x; acc[4 * j + 1] += p.y; acc[4 * j + 2] += p.z; acc[4 * j + 3] += p.w;
      if (FIRST) {
        *(uint32_t*)(himg + img_off(n * 10 + j)) = pack_bf16(acc[4 * j], acc[4 * j + 1]);
        *(uint32_t*)(himg + img_off(n * 10 + j) + 1024) = pack_bf16(acc[4 * j + 2], acc[4 * j + 3]);
        s0 += acc[4 * j] + acc[4 * j + 1]; s1 += acc[4 * j + 2] + acc[4 * j + 3];
      } else {
        *(uint32_t*)(sp + j * 16) = pack_bf16(acc[4 * j], acc[4 * j + 1]);
        *(uint32_t*)(sp + 1280 + j * 16) = pack_bf16(acc[4 * j + 2], acc[4 * j + 3]);
      }
    }
    if (FIRST) {
      s0 += __shfl_xor_sync(~0u, s0, 1); s0 += __shfl_xor_sync(~0u, s0, 2);
      s1 += __shfl_xor_sync(~0u, s1, 1); s1 += __shfl_xor_sync(~0u, s1, 2);
      s0 *= (1.f / 80.f); s1 *= (1.f / 80.f);
      float q0 = 0.f, q1 = 0.f;
#pragma unroll
      for (int j = 0; j < 10; j++) {
        float d;
        d = acc[4 * j] - s0; q0 = fmaf(d, d, q0); d = acc[4 * j + 1] - s0; q0 = fmaf(d, d, q0);
        d = acc[4 * j + 2] - s1; q1 = fmaf(d, d, q1); d = acc[4 * j + 3] - s1; q1 = fmaf(d, d, q1);
      }
      q0 += __shfl_xor_sync(~0u, q0, 1); q0 += __shfl_xor_sync(~0u, q0, 2);
      q1 += __shfl_xor_sync(~0u, q1, 1); q1 += __shfl_xor_sync(~0u, q1, 2);
      if (c < 2) g_hpart[n * S_ + m * 128 + cw * 16 + g + c * 8] = c ? make_float2(s1, q1) : make_float2(s0, q0);
    } else {
      fence_async();
      bar_sync(1 + wg, 128);
      if ((tid & 127) == 0) {
        tma2d_st(&tmr, n * 80, m * 128 + wg * 64, smem_u32(stg) + wg * 10240);
        bulk_commit_wait();
      }
      __syncwarp();
    }
    if (tid == 128) STAMP(FIRST ? 2 : 4, 4);
  } else {
    cluster_wait();
  }
  cluster_sync_relaxed();
}

constexpr int K4_ST = 3, K4_STAGE = 71680;
constexpr int K4_SMEM = K4_ST * K4_STAGE + 1728 + 1024 + 64;

__global__ void __cluster_dims__(2, 1, 1) __launch_bounds__(256, 1)
k4_ffn1() {
  extern __shared__ __align__(1024) uint8_t sm[];
  float* cs = (float*)(sm + K4_ST * K4_STAGE);
  float2* rowst = (float2*)(sm + K4_ST * K4_STAGE + 1728);
  const uint32_t sbase = smem_u32(sm);
  const uint32_t fullb = sbase + K4_ST * K4_STAGE + 2752, emptyb = fullb + 8 * K4_ST;
  const int tid = threadIdx.x, lane = tid & 31;
  const int warp = __shfl_sync(~0u, tid >> 5, 0);
  const int rank = blockIdx.x & 1, cl = blockIdx.x >> 1;
  const int n = cl & 7, m = (cl >> 3) * 2 + rank;
  const uint8_t* wb = (const uint8_t*)g_wgu + (size_t)n * 10 * 55296 + rank * 27648;
  const uint8_t* ab = (const uint8_t*)g_h + (size_t)m * 163840;
  if (tid == 0) STAMP(3, 0);
  if (tid == 0) {
    for (int i = 0; i < K4_ST; i++) { mbar_init(fullb + 8 * i, 1); mbar_init(emptyb + 8 * i, 4); }
    asm volatile("fence.mbarrier_init.release.cluster;" ::: "memory");
  }
  __syncthreads();
  cluster_arrive();
  const float cs0 = __ldcg(&g_csgu[(tid >= 216 ? F_ - 216 : 0) + n * 216 + tid]);
  const float cs1 = tid < 176 ? __ldcg(&g_csgu[F_ - 216 + n * 216 + 256 + tid]) : 0.f;
  cluster_wait();
  if (tid == 0) {
    for (int kt = 0; kt < K4_ST; kt++) mbar_expect(fullb + 8 * kt, K4_STAGE);
    bulk_ld_mc(sbase + 16384 + rank * 27648, wb, 27648, fullb);
  }
  pdl_wait();
  pdl_trigger();
  if (tid == 128) STAMP(3, 1);
  if (tid == 0) {
    bulk_ld(sbase, ab, 16384, fullb);
    for (int kt = 1; kt < K4_ST; kt++) {
      bulk_ld(sbase + kt * K4_STAGE, ab + kt * 16384, 16384, fullb + 8 * kt);
      bulk_ld_mc(sbase + kt * K4_STAGE + 16384 + rank * 27648, wb + kt * 55296, 27648, fullb + 8 * kt);
    }
  }
  if (tid >= 128) {
    const int r = tid - 128;
    float2 p[8];
#pragma unroll
    for (int i = 0; i < 8; i++) p[i] = __ldcg(&g_hpart[i * S_ + m * 128 + r]);
    float mean = 0.f, m2 = 0.f;
#pragma unroll
    for (int i = 0; i < 8; i++) { mean += p[i].x; m2 += p[i].y; }
    mean *= 0.125f;
#pragma unroll
    for (int i = 0; i < 8; i++) { const float d = p[i].x - mean; m2 = fmaf(80.f * d, d, m2); }
    rowst[r] = make_float2(-mean, __frcp_rn(m2 * (1.f / D_) + 1e-5f));
  }
  cs[tid] = cs0;
  if (tid < 176) cs[256 + tid] = cs1;
  __syncwarp();
  float ag[108], au[108];
  const uint64_t da0 = mkdesc(sbase + (warp >> 2) * 8192, 128, 1024, 0);
  const uint64_t db0 = mkdesc(sbase + 16384, 128, 1024, 0);
#pragma unroll 1
  for (int kt = 0; kt < 10; kt++) {
    const int s = kt % K4_ST;
    mbar_wait(fullb + 8 * s, (kt / K4_ST) & 1);
    if (kt == 0 && tid == 128) STAMP(3, 2);
    const uint64_t da = da0 + s * (K4_STAGE >> 4), db = db0 + s * (K4_STAGE >> 4);
    WG_FENCE();
#pragma unroll
    for (int k = 0; k < 4; k++) {
      wgmma_ss_n216(ag, da + k * 16, db + k * 16, (kt | k) != 0);
      wgmma_ss_n216(au, da + k * 16, db + 1728 + k * 16, (kt | k) != 0);
    }
    WG_COMMIT();
    if (kt > 0 && kt - 1 + K4_ST < 10) {
      WG_WAIT(1);
      const int sp = (kt - 1) % K4_ST;
      if ((tid & 127) < 2) mbar_arrive_cta(emptyb + 8 * sp, tid & 1);
      if (tid == 0) {
        const uint32_t sa = sbase + sp * K4_STAGE;
        mbar_wait(emptyb + 8 * sp, ((kt - 1) / K4_ST) & 1);
        mbar_expect(fullb + 8 * sp, K4_STAGE);
        bulk_ld_mc(sa + 16384 + rank * 27648, wb + (kt - 1 + K4_ST) * 55296, 27648, fullb + 8 * sp);
        bulk_ld(sa, ab + (kt - 1 + K4_ST) * 16384, 16384, fullb + 8 * sp);
      }
      __syncwarp();
    }
  }
  WG_WAIT(0);
  fence_regs(ag); fence_regs(au);
  if (tid == 128) STAMP(3, 3);
  __syncthreads();
  const int g = lane >> 2, c = lane & 3;
  const float2 st0 = rowst[warp * 16 + g], st1 = rowst[warp * 16 + g + 8];
  uint8_t* dst = (uint8_t*)g_hh + (size_t)m * 27 * 16384 + warp * 2048 + g * 16 + c * 4;
#pragma unroll
  for (int j = 0; j < 27; j++) {
    const float2 cg = *(const float2*)&cs[j * 8 + c * 2], cu = *(const float2*)&cs[216 + j * 8 + c * 2];
    const float h0 = fmaf(st0.x, cg.x, ag[4 * j]) * st0.y * fmaf(st0.x, cu.x, au[4 * j]);
    const float h1 = fmaf(st0.x, cg.y, ag[4 * j + 1]) * st0.y * fmaf(st0.x, cu.y, au[4 * j + 1]);
    const float h2 = fmaf(st1.x, cg.x, ag[4 * j + 2]) * st1.y * fmaf(st1.x, cu.x, au[4 * j + 2]);
    const float h3 = fmaf(st1.x, cg.y, ag[4 * j + 3]) * st1.y * fmaf(st1.x, cu.y, au[4 * j + 3]);
    *(uint32_t*)(dst + img_off(n * 27 + j)) = pack_bf16(h0, h1);
    *(uint32_t*)(dst + img_off(n * 27 + j) + 1024) = pack_bf16(h2, h3);
  }
  if (tid == 128) STAMP(3, 4);
  cluster_sync_relaxed();
}

typedef CUresult (*EncodeFn)(CUtensorMap*, CUtensorMapDataType, cuuint32_t, void*, const cuuint64_t*, const cuuint64_t*,
                             const cuuint32_t*, const cuuint32_t*, CUtensorMapInterleave, CUtensorMapSwizzle,
                             CUtensorMapL2promotion, CUtensorMapFloatOOBfill);

static CUtensorMap make_map(EncodeFn enc, const void* p, uint64_t inner, uint64_t outer, uint32_t box_inner,
                            uint32_t box_outer, CUtensorMapSwizzle swz) {
  CUtensorMap m;
  cuuint64_t gd[2] = {inner, outer};
  cuuint64_t gs[1] = {inner * 2};
  cuuint32_t bd[2] = {box_inner, box_outer};
  cuuint32_t es[2] = {1, 1};
  enc(&m, CU_TENSOR_MAP_DATA_TYPE_BFLOAT16, 2, (void*)p, gd, gs, bd, es, CU_TENSOR_MAP_INTERLEAVE_NONE, swz,
      CU_TENSOR_MAP_L2_PROMOTION_L2_256B, CU_TENSOR_MAP_FLOAT_OOB_FILL_NONE);
  return m;
}

static CUtensorMap make_map_img(EncodeFn enc, const void* p, uint64_t k, uint64_t n, uint32_t chunks) {
  CUtensorMap m;
  cuuint64_t gd[3] = {8, k, n / 8};
  cuuint64_t gs[2] = {n * 2, 16};
  cuuint32_t bd[3] = {8, 64, chunks};
  cuuint32_t es[3] = {1, 1, 1};
  enc(&m, CU_TENSOR_MAP_DATA_TYPE_BFLOAT16, 3, (void*)p, gd, gs, bd, es, CU_TENSOR_MAP_INTERLEAVE_NONE,
      CU_TENSOR_MAP_SWIZZLE_NONE, CU_TENSOR_MAP_L2_PROMOTION_L2_128B, CU_TENSOR_MAP_FLOAT_OOB_FILL_NONE);
  return m;
}

template <typename... KArgs, typename... Args>
static void launch(void (*k)(KArgs...), int threads, int smem, bool pdl, Args... args) {
  cudaLaunchConfig_t cfg = {};
  cfg.gridDim = dim3(128);
  cfg.blockDim = dim3(threads);
  cfg.dynamicSmemBytes = smem;
  cfg.stream = cudaStreamPerThread;
  cudaLaunchAttribute at[1];
  at[0].id = cudaLaunchAttributeProgrammaticStreamSerialization;
  at[0].val.programmaticStreamSerializationAllowed = 1;
  cfg.attrs = at;
  cfg.numAttrs = pdl ? 1 : 0;
  cudaLaunchKernelEx(&cfg, k, KArgs(args)...);
}

extern "C" void kernel_launch(void* const* d_in, const int* in_sizes, int n_in, void* d_out, int out_size) {
  const bf16* x = (const bf16*)d_in[0];
  const bf16* wqkv = (const bf16*)d_in[1];
  const bf16* wo = (const bf16*)d_in[2];
  const bf16* wg = (const bf16*)d_in[4];
  const bf16* wu = (const bf16*)d_in[5];
  const bf16* wd = (const bf16*)d_in[6];

  static EncodeFn enc = nullptr;
  static void *p_o, *p_hh, *p_wo, *p_wd;
  if (!enc) {
    void* fn = nullptr;
    cudaDriverEntryPointQueryResult qr;
    cudaGetDriverEntryPoint("cuTensorMapEncodeTiled", &fn, cudaEnableDefault, &qr);
    enc = (EncodeFn)fn;
    cudaGetSymbolAddress(&p_o, g_o); cudaGetSymbolAddress(&p_hh, g_hh);
    cudaGetSymbolAddress(&p_wo, g_wo); cudaGetSymbolAddress(&p_wd, g_wd);
    cudaFuncSetAttribute(k1_qkv, cudaFuncAttributeMaxDynamicSharedMemorySize, K1_SMEM);
    cudaFuncSetAttribute(k2_attn, cudaFuncAttributeMaxDynamicSharedMemorySize, K2_SMEM);
    cudaFuncSetAttribute(k3_proj<10, true>, cudaFuncAttributeMaxDynamicSharedMemorySize, K3_SMEM);
    cudaFuncSetAttribute(k3_proj<27, false>, cudaFuncAttributeMaxDynamicSharedMemorySize, K3_SMEM);
    cudaFuncSetAttribute(k4_ffn1, cudaFuncAttributeMaxDynamicSharedMemorySize, K4_SMEM);
  }
  const CUtensorMap tmx = make_map(enc, x, D_, S_, 64, 128, CU_TENSOR_MAP_SWIZZLE_128B);
  const CUtensorMap tmw = make_map(enc, wqkv, 3 * D_, D_, 32, 64, CU_TENSOR_MAP_SWIZZLE_64B);
  const CUtensorMap tmxr = make_map(enc, x, D_, S_, 80, 64, CU_TENSOR_MAP_SWIZZLE_NONE);
  const CUtensorMap tmg = make_map_img(enc, wg, D_, F_, 9), tmu = make_map_img(enc, wu, D_, F_, 9);
  const CUtensorMap tmd = make_map_img(enc, wd, F_, D_, 10);
  const CUtensorMap tmout = make_map(enc, d_out, D_, S_, 80, 64, CU_TENSOR_MAP_SWIZZLE_NONE);

  launch(k1_qkv, 384, K1_SMEM, false, tmx, tmw, x, wqkv, wo, wg, wu);
  launch(k2_attn, 512, K2_SMEM, true, tmg, tmu, tmd, 0x007f007fu);
  launch(k3_proj<10, true>, 384, K3_SMEM, true, tmxr, (const uint4*)p_o, (const uint4*)p_wo);
  launch(k4_ffn1, 256, K4_SMEM, true);
  launch(k3_proj<27, false>, 384, K3_SMEM, true, tmout, (const uint4*)p_hh, (const uint4*)p_wd);
}
```

```cpp
#include <cuda_runtime.h>
#include <cuda_bf16.h>
#include <cuda.h>
#include <stdint.h>

typedef __nv_bfloat16 bf16;

constexpr int S_ = 2048, D_ = 640, F_ = 1728;
constexpr int HEAD_IMG = 98304;
#define PMASK 0xABAB
constexpr uint32_t POLY_MASK = PMASK;
constexpr float QSCALE = 0.22360679774997896f * 1.4426950408889634f;

__device__ __align__(1024) uint4 g_qkv[96 * HEAD_IMG / 16];
__device__ __align__(1024) uint4 g_o[S_ * D_ / 8];
__device__ __align__(1024) uint4 g_h[S_ * D_ / 8];
__device__ __align__(1024) uint4 g_hh[S_ * F_ / 8];
__device__ __align__(1024) uint4 g_wo[D_ * D_ / 8];
__device__ __align__(1024) uint4 g_wgu[2 * D_ * F_ / 8];
__device__ __align__(1024) uint4 g_wd[F_ * D_ / 8];
__device__ uint4 g_rowstat[S_];
__device__ uint4 g_cpart[16 * 8 * 128];
__device__ float g_nrm[64 * 128];
__device__ float g_csgu[2 * F_];
__device__ float2 g_hpart[8 * S_];
__device__ unsigned g_epoch;

#define STAMP(k, i)
__device__ __forceinline__ uint32_t smem_u32(const void* p) { return (uint32_t)__cvta_generic_to_shared(p); }
__device__ __forceinline__ void mbar_init(uint32_t a, uint32_t c) {
  asm volatile("mbarrier.init.shared::cta.b64 [%0], %1;" ::"r"(a), "r"(c) : "memory");
}
__device__ __forceinline__ void mbar_expect(uint32_t a, uint32_t bytes) {
  asm volatile("mbarrier.arrive.expect_tx.shared::cta.b64 _, [%0], %1;" ::"r"(a), "r"(bytes) : "memory");
}
__device__ __forceinline__ void mbar_arrive(uint32_t a) {
  asm volatile("mbarrier.arrive.shared::cta.b64 _, [%0];" ::"r"(a) : "memory");
}
__device__ __forceinline__ void mbar_arrive_cta(uint32_t a, uint32_t cta) {
  asm volatile("{\n.reg .b32 r;\nmapa.shared::cluster.u32 r, %0, %1;\n"
               "mbarrier.arrive.shared::cluster.b64 _, [r];\n}" ::"r"(a), "r"(cta) : "memory");
}
__device__ __forceinline__ bool mbar_try(uint32_t a, uint32_t ph) {
  uint32_t ok;
  asm volatile("{\n.reg .pred p;\nmbarrier.try_wait.parity.shared::cta.b64 p, [%1], %2;\nselp.u32 %0, 1, 0, p;\n}"
               : "=r"(ok) : "r"(a), "r"(ph) : "memory");
  return ok;
}
__device__ __noinline__ void wait_timeout() { __trap(); }
__device__ __forceinline__ void mbar_wait(uint32_t a, uint32_t ph) {
  if (mbar_try(a, ph)) return;
  uint32_t it = 0;
  while (!mbar_try(a, ph)) if (++it > (1u << 22)) wait_timeout();
}
__device__ __forceinline__ void tma2d(uint32_t dst, const CUtensorMap* m, int c0, int c1, uint32_t bar) {
  asm volatile("cp.async.bulk.tensor.2d.shared::cluster.global.mbarrier::complete_tx::bytes [%0], [%1, {%3, %4}], [%2];"
               ::"r"(dst), "l"(m), "r"(bar), "r"(c0), "r"(c1) : "memory");
}
__device__ __forceinline__ void tma2d_mc(uint32_t dst, const CUtensorMap* m, int c0, int c1, uint32_t bar) {
  asm volatile("cp.async.bulk.tensor.2d.shared::cluster.global.mbarrier::complete_tx::bytes.multicast::cluster "
               "[%0], [%1, {%3, %4}], [%2], %5;"
               ::"r"(dst), "l"(m), "r"(bar), "r"(c0), "r"(c1), "h"((uint16_t)3) : "memory");
}
__device__ __forceinline__ void bulk_ld(uint32_t dst, const void* src, uint32_t bytes, uint32_t bar) {
  asm volatile("cp.async.bulk.shared::cluster.global.mbarrier::complete_tx::bytes [%0], [%1], %2, [%3];"
               ::"r"(dst), "l"(src), "r"(bytes), "r"(bar) : "memory");
}
__device__ __forceinline__ void bulk_ld_mc(uint32_t dst, const void* src, uint32_t bytes, uint32_t bar) {
  asm volatile("cp.async.bulk.shared::cluster.global.mbarrier::complete_tx::bytes.multicast::cluster "
               "[%0], [%1], %2, [%3], %4;"
               ::"r"(dst), "l"(src), "r"(bytes), "r"(bar), "h"((uint16_t)3) : "memory");
}
__device__ __forceinline__ void cluster_arrive() { asm volatile("barrier.cluster.arrive.relaxed.aligned;" ::: "memory"); }
__device__ __forceinline__ void cluster_wait() { asm volatile("barrier.cluster.wait.aligned;" ::: "memory"); }
__device__ __forceinline__ void bulk_st(void* dst, uint32_t src, uint32_t bytes) {
  asm volatile("cp.async.bulk.global.shared::cta.bulk_group [%0], [%1], %2;" ::"l"(dst), "r"(src), "r"(bytes) : "memory");
}
__device__ __forceinline__ void tma2d_st(const CUtensorMap* m, int c0, int c1, uint32_t src) {
  asm volatile("cp.async.bulk.tensor.2d.global.shared::cta.bulk_group [%0, {%2, %3}], [%1];"
               ::"l"(m), "r"(src), "r"(c0), "r"(c1) : "memory");
}
__device__ __forceinline__ void bulk_commit_wait() {
  asm volatile("cp.async.bulk.commit_group;\ncp.async.bulk.wait_group.read 0;" ::: "memory");
}
__device__ __forceinline__ uint32_t mapa(uint32_t a, uint32_t cta) {
  uint32_t r;
  asm("mapa.shared::cluster.u32 %0, %1, %2;" : "=r"(r) : "r"(a), "r"(cta));
  return r;
}
__device__ __forceinline__ void st_async4(uint32_t dst, float a, float b, float c, float d, uint32_t bar) {
  asm volatile("st.async.shared::cluster.mbarrier::complete_tx::bytes.v4.f32 [%0], {%1, %2, %3, %4}, [%5];"
               ::"r"(dst), "f"(a), "f"(b), "f"(c), "f"(d), "r"(bar) : "memory");
}
__device__ __forceinline__ void fence_async() { asm volatile("fence.proxy.async.shared::cta;" ::: "memory"); }
__device__ __forceinline__ void prefetch_map(const CUtensorMap* m) {
  asm volatile("prefetch.tensormap [%0];" ::"l"(m) : "memory");
}
__device__ __forceinline__ void cluster_sync_relaxed() {
  __syncwarp();
  asm volatile("barrier.cluster.arrive.relaxed.aligned;\nbarrier.cluster.wait.aligned;" ::: "memory");
}
__device__ __forceinline__ void pdl_wait() { asm volatile("griddepcontrol.wait;" ::: "memory"); }
__device__ __forceinline__ void pdl_trigger() { asm volatile("griddepcontrol.launch_dependents;" ::: "memory"); }
__device__ __forceinline__ void bar_sync(int id, int n) { asm volatile("bar.sync %0, %1;" ::"r"(id), "r"(n) : "memory"); }
__device__ __forceinline__ void bar_arrive(int id, int n) { asm volatile("bar.arrive %0, %1;" ::"r"(id), "r"(n) : "memory"); }
#define WG_FENCE() asm volatile("wgmma.fence.sync.aligned;" ::: "memory")
#define WG_COMMIT() asm volatile("wgmma.commit_group.sync.aligned;" ::: "memory")
#define WG_WAIT(n) asm volatile("wgmma.wait_group.sync.aligned %0;" ::"n"(n) : "memory")
__device__ __forceinline__ uint64_t mkdesc(uint32_t addr, uint32_t lbo, uint32_t sbo, uint32_t sw) {
  return (uint64_t)((addr & 0x3FFFF) >> 4) | ((uint64_t)(lbo >> 4) << 16) | ((uint64_t)(sbo >> 4) << 32) |
         ((uint64_t)sw << 62);
}
template <int N> __device__ __forceinline__ void fence_regs(float (&r)[N]) {
#pragma unroll
  for (int i = 0; i < N; i++) asm volatile("" : "+f"(r[i])::"memory");
}
__device__ __forceinline__ uint32_t pack_bf16(float lo, float hi) {
  uint32_t r;
  asm("cvt.rn.bf16x2.f32 %0, %1, %2;" : "=r"(r) : "f"(hi), "f"(lo));
  return r;
}
__device__ __forceinline__ float bf_lo(uint32_t v) { return __uint_as_float(v << 16); }
__device__ __forceinline__ float bf_hi(uint32_t v) { return __uint_as_float(v & 0xffff0000u); }
__device__ __forceinline__ float ex2(float x) {
  float y;
  asm("ex2.approx.ftz.f32 %0, %1;" : "=f"(y) : "f"(x));
  return y;
}
__device__ __forceinline__ uint4 ldg_nc(const void* p) {
  uint4 v;
  asm volatile("ld.global.nc.L1::no_allocate.v4.u32 {%0, %1, %2, %3}, [%4];"
               : "=r"(v.x), "=r"(v.y), "=r"(v.z), "=r"(v.w) : "l"(p));
  return v;
}

__device__ __forceinline__ uint4 ld_relaxed(const uint4* p) {
  uint64_t a, b;
  asm volatile("ld.relaxed.gpu.global.v2.u64 {%0, %1}, [%2];" : "=l"(a), "=l"(b) : "l"(p) : "memory");
  return make_uint4((uint32_t)a, (uint32_t)(a >> 32), (uint32_t)b, (uint32_t)(b >> 32));
}
__device__ __forceinline__ void st_relaxed(uint4* p, float x, float y, uint32_t tag) {
  const uint64_t a = ((uint64_t)tag << 32) | __float_as_uint(x), b = ((uint64_t)tag << 32) | __float_as_uint(y);
  asm volatile("st.relaxed.gpu.global.v2.u64 [%0], {%1, %2};" ::"l"(p), "l"(a), "l"(b) : "memory");
}
#define ACC8(a, v) do { a[0] += bf_lo(v.x); a[1] += bf_hi(v.x); a[2] += bf_lo(v.y); a[3] += bf_hi(v.y); \
                        a[4] += bf_lo(v.z); a[5] += bf_hi(v.z); a[6] += bf_lo(v.w); a[7] += bf_hi(v.w); } while (0)

__device__ __forceinline__ void wgmma_ss_n240(float (&d)[120], uint64_t da, uint64_t db, int sd) {
  asm volatile("{\n.reg .pred p;\nsetp.ne.b32 p, %122, 0;\n"
      "wgmma.mma_async.sync.aligned.m64n240k16.f32.bf16.bf16 {"
      "%0, %1, %2, %3, %4, %5, %6, %7, %8, %9, %10, %11, %12, %13, %14, %15, "
      "%16, %17, %18, %19, %20, %21, %22, %23, %24, %25, %26, %27, %28, %29, %30, %31, "
      "%32, %33, %34, %35, %36, %37, %38, %39, %40, %41, %42, %43, %44, %45, %46, %47, "
      "%48, %49, %50, %51, %52, %53, %54, %55, %56, %57, %58, %59, %60, %61, %62, %63, "
      "%64, %65, %66, %67, %68, %69, %70, %71, %72, %73, %74, %75, %76, %77, %78, %79, "
      "%80, %81, %82, %83, %84, %85, %86, %87, %88, %89, %90, %91, %92, %93, %94, %95, "
      "%96, %97, %98, %99, %100, %101, %102, %103, %104, %105, %106, %107, %108, %109, %110, %111, "
      "%112, %113, %114, %115, %116, %117, %118, %119"
      "}, %120, %121, p, 1, 1, 0, 1;\n}\n"
    : "+f"(d[0]), "+f"(d[1]), "+f"(d[2]), "+f"(d[3]), "+f"(d[4]), "+f"(d[5]), "+f"(d[6]), "+f"(d[7]),
      "+f"(d[8]), "+f"(d[9]), "+f"(d[10]), "+f"(d[11]), "+f"(d[12]), "+f"(d[13]), "+f"(d[14]), "+f"(d[15]),
      "+f"(d[16]), "+f"(d[17]), "+f"(d[18]), "+f"(d[19]), "+f"(d[20]), "+f"(d[21]), "+f"(d[22]), "+f"(d[23]),
      "+f"(d[24]), "+f"(d[25]), "+f"(d[26]), "+f"(d[27]), "+f"(d[28]), "+f"(d[29]), "+f"(d[30]), "+f"(d[31]),
      "+f"(d[32]), "+f"(d[33]), "+f"(d[34]), "+f"(d[35]), "+f"(d[36]), "+f"(d[37]), "+f"(d[38]), "+f"(d[39]),
      "+f"(d[40]), "+f"(d[41]), "+f"(d[42]), "+f"(d[43]), "+f"(d[44]), "+f"(d[45]), "+f"(d[46]), "+f"(d[47]),
      "+f"(d[48]), "+f"(d[49]), "+f"(d[50]), "+f"(d[51]), "+f"(d[52]), "+f"(d[53]), "+f"(d[54]), "+f"(d[55]),
      "+f"(d[56]), "+f"(d[57]), "+f"(d[58]), "+f"(d[59]), "+f"(d[60]), "+f"(d[61]), "+f"(d[62]), "+f"(d[63]),
      "+f"(d[64]), "+f"(d[65]), "+f"(d[66]), "+f"(d[67]), "+f"(d[68]), "+f"(d[69]), "+f"(d[70]), "+f"(d[71]),
      "+f"(d[72]), "+f"(d[73]), "+f"(d[74]), "+f"(d[75]), "+f"(d[76]), "+f"(d[77]), "+f"(d[78]), "+f"(d[79]),
      "+f"(d[80]), "+f"(d[81]), "+f"(d[82]), "+f"(d[83]), "+f"(d[84]), "+f"(d[85]), "+f"(d[86]), "+f"(d[87]),
      "+f"(d[88]), "+f"(d[89]), "+f"(d[90]), "+f"(d[91]), "+f"(d[92]), "+f"(d[93]), "+f"(d[94]), "+f"(d[95]),
      "+f"(d[96]), "+f"(d[97]), "+f"(d[98]), "+f"(d[99]), "+f"(d[100]), "+f"(d[101]), "+f"(d[102]), "+f"(d[103]),
      "+f"(d[104]), "+f"(d[105]), "+f"(d[106]), "+f"(d[107]), "+f"(d[108]), "+f"(d[109]), "+f"(d[110]), "+f"(d[111]),
      "+f"(d[112]), "+f"(d[113]), "+f"(d[114]), "+f"(d[115]), "+f"(d[116]), "+f"(d[117]), "+f"(d[118]), "+f"(d[119])
    : "l"(da), "l"(db), "r"(sd));
}
__device__ __forceinline__ void wgmma_ss_n216(float (&d)[108], uint64_t da, uint64_t db, int sd) {
  asm volatile("{\n.reg .pred p;\nsetp.ne.b32 p, %110, 0;\n"
      "wgmma.mma_async.sync.aligned.m64n216k16.f32.bf16.bf16 {"
      "%0, %1, %2, %3, %4, %5, %6, %7, %8, %9, %10, %11, %12, %13, %14, %15, "
      "%16, %17, %18, %19, %20, %21, %22, %23, %24, %25, %26, %27, %28, %29, %30, %31, "
      "%32, %33, %34, %35, %36, %37, %38, %39, %40, %41, %42, %43, %44, %45, %46, %47, "
      "%48, %49, %50, %51, %52, %53, %54, %55, %56, %57, %58, %59, %60, %61, %62, %63, "
      "%64, %65, %66, %67, %68, %69, %70, %71, %72, %73, %74, %75, %76, %77, %78, %79, "
      "%80, %81, %82, %83, %84, %85, %86, %87, %88, %89, %90, %91, %92, %93, %94, %95, "
      "%96, %97, %98, %99, %100, %101, %102, %103, %104, %105, %106, %107"
      "}, %108, %109, p, 1, 1, 0, 1;\n}\n"
    : "+f"(d[0]), "+f"(d[1]), "+f"(d[2]), "+f"(d[3]), "+f"(d[4]), "+f"(d[5]), "+f"(d[6]), "+f"(d[7]),
      "+f"(d[8]), "+f"(d[9]), "+f"(d[10]), "+f"(d[11]), "+f"(d[12]), "+f"(d[13]), "+f"(d[14]), "+f"(d[15]),
      "+f"(d[16]), "+f"(d[17]), "+f"(d[18]), "+f"(d[19]), "+f"(d[20]), "+f"(d[21]), "+f"(d[22]), "+f"(d[23]),
      "+f"(d[24]), "+f"(d[25]), "+f"(d[26]), "+f"(d[27]), "+f"(d[28]), "+f"(d[29]), "+f"(d[30]), "+f"(d[31]),
      "+f"(d[32]), "+f"(d[33]), "+f"(d[34]), "+f"(d[35]), "+f"(d[36]), "+f"(d[37]), "+f"(d[38]), "+f"(d[39]),
      "+f"(d[40]), "+f"(d[41]), "+f"(d[42]), "+f"(d[43]), "+f"(d[44]), "+f"(d[45]), "+f"(d[46]), "+f"(d[47]),
      "+f"(d[48]), "+f"(d[49]), "+f"(d[50]), "+f"(d[51]), "+f"(d[52]), "+f"(d[53]), "+f"(d[54]), "+f"(d[55]),
      "+f"(d[56]), "+f"(d[57]), "+f"(d[58]), "+f"(d[59]), "+f"(d[60]), "+f"(d[61]), "+f"(d[62]), "+f"(d[63]),
      "+f"(d[64]), "+f"(d[65]), "+f"(d[66]), "+f"(d[67]), "+f"(d[68]), "+f"(d[69]), "+f"(d[70]), "+f"(d[71]),
      "+f"(d[72]), "+f"(d[73]), "+f"(d[74]), "+f"(d[75]), "+f"(d[76]), "+f"(d[77]), "+f"(d[78]), "+f"(d[79]),
      "+f"(d[80]), "+f"(d[81]), "+f"(d[82]), "+f"(d[83]), "+f"(d[84]), "+f"(d[85]), "+f"(d[86]), "+f"(d[87]),
      "+f"(d[88]), "+f"(d[89]), "+f"(d[90]), "+f"(d[91]), "+f"(d[92]), "+f"(d[93]), "+f"(d[94]), "+f"(d[95]),
      "+f"(d[96]), "+f"(d[97]), "+f"(d[98]), "+f"(d[99]), "+f"(d[100]), "+f"(d[101]), "+f"(d[102]), "+f"(d[103]),
      "+f"(d[104]), "+f"(d[105]), "+f"(d[106]), "+f"(d[107])
    : "l"(da), "l"(db), "r"(sd));
}
__device__ __forceinline__ void wgmma_ss_n160(float (&d)[80], uint64_t da, uint64_t db, int sd) {
  asm volatile("{\n.reg .pred p;\nsetp.ne.b32 p, %82, 0;\n"
      "wgmma.mma_async.sync.aligned.m64n160k16.f32.bf16.bf16 {"
      "%0, %1, %2, %3, %4, %5, %6, %7, %8, %9, %10, %11, %12, %13, %14, %15, "
      "%16, %17, %18, %19, %20, %21, %22, %23, %24, %25, %26, %27, %28, %29, %30, %31, "
      "%32, %33, %34, %35, %36, %37, %38, %39, %40, %41, %42, %43, %44, %45, %46, %47, "
      "%48, %49, %50, %51, %52, %53, %54, %55, %56, %57, %58, %59, %60, %61, %62, %63, "
      "%64, %65, %66, %67, %68, %69, %70, %71, %72, %73, %74, %75, %76, %77, %78, %79"
      "}, %80, %81, p, 1, 1, 0, 1;\n}\n"
    : "+f"(d[0]), "+f"(d[1]), "+f"(d[2]), "+f"(d[3]), "+f"(d[4]), "+f"(d[5]), "+f"(d[6]), "+f"(d[7]),
      "+f"(d[8]), "+f"(d[9]), "+f"(d[10]), "+f"(d[11]), "+f"(d[12]), "+f"(d[13]), "+f"(d[14]), "+f"(d[15]),
      "+f"(d[16]), "+f"(d[17]), "+f"(d[18]), "+f"(d[19]), "+f"(d[20]), "+f"(d[21]), "+f"(d[22]), "+f"(d[23]),
      "+f"(d[24]), "+f"(d[25]), "+f"(d[26]), "+f"(d[27]), "+f"(d[28]), "+f"(d[29]), "+f"(d[30]), "+f"(d[31]),
      "+f"(d[32]), "+f"(d[33]), "+f"(d[34]), "+f"(d[35]), "+f"(d[36]), "+f"(d[37]), "+f"(d[38]), "+f"(d[39]),
      "+f"(d[40]), "+f"(d[41]), "+f"(d[42]), "+f"(d[43]), "+f"(d[44]), "+f"(d[45]), "+f"(d[46]), "+f"(d[47]),
      "+f"(d[48]), "+f"(d[49]), "+f"(d[50]), "+f"(d[51]), "+f"(d[52]), "+f"(d[53]), "+f"(d[54]), "+f"(d[55]),
      "+f"(d[56]), "+f"(d[57]), "+f"(d[58]), "+f"(d[59]), "+f"(d[60]), "+f"(d[61]), "+f"(d[62]), "+f"(d[63]),
      "+f"(d[64]), "+f"(d[65]), "+f"(d[66]), "+f"(d[67]), "+f"(d[68]), "+f"(d[69]), "+f"(d[70]), "+f"(d[71]),
      "+f"(d[72]), "+f"(d[73]), "+f"(d[74]), "+f"(d[75]), "+f"(d[76]), "+f"(d[77]), "+f"(d[78]), "+f"(d[79])
    : "l"(da), "l"(db), "r"(sd));
}
__device__ __forceinline__ void wgmma_ss_n80(float (&d)[40], uint64_t da, uint64_t db, int sd) {
  asm volatile("{\n.reg .pred p;\nsetp.ne.b32 p, %42, 0;\n"
      "wgmma.mma_async.sync.aligned.m64n80k16.f32.bf16.bf16 {"
      "%0, %1, %2, %3, %4, %5, %6, %7, %8, %9, %10, %11, %12, %13, %14, %15, "
      "%16, %17, %18, %19, %20, %21, %22, %23, %24, %25, %26, %27, %28, %29, %30, %31, "
      "%32, %33, %34, %35, %36, %37, %38, %39"
      "}, %40, %41, p, 1, 1, 0, 1;\n}\n"
    : "+f"(d[0]), "+f"(d[1]), "+f"(d[2]), "+f"(d[3]), "+f"(d[4]), "+f"(d[5]), "+f"(d[6]), "+f"(d[7]),
      "+f"(d[8]), "+f"(d[9]), "+f"(d[10]), "+f"(d[11]), "+f"(d[12]), "+f"(d[13]), "+f"(d[14]), "+f"(d[15]),
      "+f"(d[16]), "+f"(d[17]), "+f"(d[18]), "+f"(d[19]), "+f"(d[20]), "+f"(d[21]), "+f"(d[22]), "+f"(d[23]),
      "+f"(d[24]), "+f"(d[25]), "+f"(d[26]), "+f"(d[27]), "+f"(d[28]), "+f"(d[29]), "+f"(d[30]), "+f"(d[31]),
      "+f"(d[32]), "+f"(d[33]), "+f"(d[34]), "+f"(d[35]), "+f"(d[36]), "+f"(d[37]), "+f"(d[38]), "+f"(d[39])
    : "l"(da), "l"(db), "r"(sd));
}
__device__ __forceinline__ void wgmma_rs_n128(float (&d)[64], uint32_t a0, uint32_t a1, uint32_t a2, uint32_t a3,
                                  uint64_t db, int sd) {
  asm volatile("{\n.reg .pred p;\nsetp.ne.b32 p, %69, 0;\n"
      "wgmma.mma_async.sync.aligned.m64n128k16.f32.bf16.bf16 {"
      "%0, %1, %2, %3, %4, %5, %6, %7, %8, %9, %10, %11, %12, %13, %14, %15, "
      "%16, %17, %18, %19, %20, %21, %22, %23, %24, %25, %26, %27, %28, %29, %30, %31, "
      "%32, %33, %34, %35, %36, %37, %38, %39, %40, %41, %42, %43, %44, %45, %46, %47, "
      "%48, %49, %50, %51, %52, %53, %54, %55, %56, %57, %58, %59, %60, %61, %62, %63"
      "}, {%64, %65, %66, %67}, %68, p, 1, 1, 0;\n}\n"
    : "+f"(d[0]), "+f"(d[1]), "+f"(d[2]), "+f"(d[3]), "+f"(d[4]), "+f"(d[5]), "+f"(d[6]), "+f"(d[7]),
      "+f"(d[8]), "+f"(d[9]), "+f"(d[10]), "+f"(d[11]), "+f"(d[12]), "+f"(d[13]), "+f"(d[14]), "+f"(d[15]),
      "+f"(d[16]), "+f"(d[17]), "+f"(d[18]), "+f"(d[19]), "+f"(d[20]), "+f"(d[21]), "+f"(d[22]), "+f"(d[23]),
      "+f"(d[24]), "+f"(d[25]), "+f"(d[26]), "+f"(d[27]), "+f"(d[28]), "+f"(d[29]), "+f"(d[30]), "+f"(d[31]),
      "+f"(d[32]), "+f"(d[33]), "+f"(d[34]), "+f"(d[35]), "+f"(d[36]), "+f"(d[37]), "+f"(d[38]), "+f"(d[39]),
      "+f"(d[40]), "+f"(d[41]), "+f"(d[42]), "+f"(d[43]), "+f"(d[44]), "+f"(d[45]), "+f"(d[46]), "+f"(d[47]),
      "+f"(d[48]), "+f"(d[49]), "+f"(d[50]), "+f"(d[51]), "+f"(d[52]), "+f"(d[53]), "+f"(d[54]), "+f"(d[55]),
      "+f"(d[56]), "+f"(d[57]), "+f"(d[58]), "+f"(d[59]), "+f"(d[60]), "+f"(d[61]), "+f"(d[62]), "+f"(d[63])
    : "r"(a0), "r"(a1), "r"(a2), "r"(a3), "l"(db), "r"(sd));
}
__device__ __forceinline__ void wgmma_rs_n24(float (&d)[12], uint32_t a0, uint32_t a1, uint32_t a2, uint32_t a3,
                                  uint64_t db, int sd) {
  asm volatile("{\n.reg .pred p;\nsetp.ne.b32 p, %17, 0;\n"
      "wgmma.mma_async.sync.aligned.m64n24k16.f32.bf16.bf16 {"
      "%0, %1, %2, %3, %4, %5, %6, %7, %8, %9, %10, %11"
      "}, {%12, %13, %14, %15}, %16, p, 1, 1, 1;\n}\n"
    : "+f"(d[0]), "+f"(d[1]), "+f"(d[2]), "+f"(d[3]), "+f"(d[4]), "+f"(d[5]), "+f"(d[6]), "+f"(d[7]),
      "+f"(d[8]), "+f"(d[9]), "+f"(d[10]), "+f"(d[11])
    : "r"(a0), "r"(a1), "r"(a2), "r"(a3), "l"(db), "r"(sd));
}

constexpr int K1_ST = 4, K1_STAGE = 49152;
constexpr int K1_SMEM = K1_ST * K1_STAGE + 1024   + 1024   + 3072   + 128;

__global__ void __cluster_dims__(2, 1, 1) __launch_bounds__(384, 1)
k1_qkv(const __grid_constant__ CUtensorMap tmx, const __grid_constant__ CUtensorMap tmw,
       const bf16* __restrict__ x, const bf16* __restrict__ w, const bf16* __restrict__ wo) {
  extern __shared__ __align__(1024) uint8_t sm[];
  float* cs = (float*)(sm + K1_ST * K1_STAGE);
  float2* rowab = (float2*)(sm + K1_ST * K1_STAGE + 1024);
  float* red = (float*)(sm + K1_ST * K1_STAGE + 2048);
  const uint32_t sbase = smem_u32(sm);
  const uint32_t fullb = sbase + K1_ST * K1_STAGE + 5120, emptyb = fullb + 8 * K1_ST;
  const int tid = threadIdx.x, lane = tid & 31;
  const int warp = __shfl_sync(~0u, tid >> 5, 0);
  const int rank = blockIdx.x & 1, cl = blockIdx.x >> 1;
  const int n = cl & 7, m = (cl >> 3) * 2 + rank;
  if (tid == 0) STAMP(0, 0);

  if (warp == 0) {
    if (lane == 0) {
      prefetch_map(&tmx); prefetch_map(&tmw);
      for (int i = 0; i < K1_ST; i++) { mbar_init(fullb + 8 * i, 1); mbar_init(emptyb + 8 * i, 4); }
      asm volatile("fence.mbarrier_init.release.cluster;" ::: "memory");
    }
    __syncwarp();
    cluster_arrive();
    if (lane == 0) {
      for (int kt = 0; kt < K1_ST; kt++) mbar_expect(fullb + 8 * kt, K1_STAGE);
      tma2d(sbase, &tmx, 0, m * 128, fullb);
    }
    __syncwarp();
    cluster_wait();
    if (tid == 0) STAMP(5, 3);
    if (lane == 0) {
#pragma unroll
      for (int j = 0; j < 4; j++) tma2d_mc(sbase + 16384 + rank * 16384 + j * 4096, &tmw, n * 240 + rank * 128 + j * 32, 0, fullb);
    }
    __syncwarp();
    bar_arrive(4, 384);
    if (lane == 0) {
      for (int kt = 1; kt < 10; kt++) {
        const int s = kt % K1_ST;
        const uint32_t sa = sbase + s * K1_STAGE, sb = sa + 16384 + rank * 16384;
        if (kt >= K1_ST) {
          mbar_wait(emptyb + 8 * s, ((kt / K1_ST) - 1) & 1);
          mbar_expect(fullb + 8 * s, K1_STAGE);
        }
        tma2d(sa, &tmx, kt * 64, m * 128, fullb + 8 * s);
#pragma unroll
        for (int j = 0; j < 4; j++) tma2d_mc(sb + j * 4096, &tmw, n * 240 + rank * 128 + j * 32, kt * 64, fullb + 8 * s);
        if (kt == 6) pdl_trigger();
      }
    }
    __syncwarp();
  } else if (warp < 4) {
    cluster_arrive();
    const int w3 = warp - 1, t96 = tid - 32;
    const uint32_t tag = __ldcg(&g_epoch) + 1;
    bar_sync(4, 384);
    {
      uint4 xv[6][3], wv[14];
#pragma unroll
      for (int i = 0; i < 6; i++) {
        const bf16* xr = x + (size_t)(m * 128 + n * 16 + min(w3 + 3 * i, 15)) * D_ + lane * 8;
        xv[i][0] = ldg_nc(xr);
        xv[i][1] = ldg_nc(xr + 256);
        xv[i][2] = ldg_nc(xr + (lane < 16 ? 512 : 0));
      }
#pragma unroll
      for (int i = 0; i < 14; i++)
        wv[i] = ldg_nc(w + (size_t)(m * 40 + min(w3 + 3 * i, 39)) * 1920 + n * 240 + min(lane, 29) * 8);
#pragma unroll
      for (int i = 0; i < 6; i++) {
        float f[24];
#pragma unroll
        for (int k = 0; k < 3; k++) {
          const uint4 v = xv[i][k];
          f[8 * k + 0] = bf_lo(v.x); f[8 * k + 1] = bf_hi(v.x); f[8 * k + 2] = bf_lo(v.y); f[8 * k + 3] = bf_hi(v.y);
          f[8 * k + 4] = bf_lo(v.z); f[8 * k + 5] = bf_hi(v.z); f[8 * k + 6] = bf_lo(v.w); f[8 * k + 7] = bf_hi(v.w);
        }
        float s = 0.f, s2 = 0.f;
#pragma unroll
        for (int k = 0; k < 16; k++) s += f[k];
#pragma unroll
        for (int k = 16; k < 24; k++) s2 += f[k];
        if (lane < 16) s += s2;
#pragma unroll
        for (int o = 16; o; o >>= 1) s += __shfl_xor_sync(~0u, s, o);
        const float mean = s * (1.f / D_);
        float q = 0.f, q2 = 0.f;
#pragma unroll
        for (int k = 0; k < 16; k++) { float d = f[k] - mean; q = fmaf(d, d, q); }
#pragma unroll
        for (int k = 16; k < 24; k++) { float d = f[k] - mean; q2 = fmaf(d, d, q2); }
        if (lane < 16) q += q2;
#pragma unroll
        for (int o = 16; o; o >>= 1) q += __shfl_xor_sync(~0u, q, o);
        if (lane == 0 && w3 + 3 * i < 16)
          st_relaxed(&g_rowstat[m * 128 + n * 16 + w3 + 3 * i], rsqrtf(q * (1.f / D_) + 1e-5f), mean, tag);
      }
      float acc8[8];
#pragma unroll
      for (int i = 0; i < 8; i++) acc8[i] = 0.f;
#pragma unroll
      for (int i = 0; i < 14; i++)
        if (i < 13 || w3 == 0) ACC8(acc8, wv[i]);
      *(float4*)&red[w3 * 256 + lane * 8] = make_float4(acc8[0], acc8[1], acc8[2], acc8[3]);
      *(float4*)&red[w3 * 256 + lane * 8 + 4] = make_float4(acc8[4], acc8[5], acc8[6], acc8[7]);
    }
    bar_sync(1, 96);
    for (int i = t96; i < 120; i += 96) {
      const float2 p0 = *(const float2*)&red[i * 2], p1 = *(const float2*)&red[256 + i * 2], p2 = *(const float2*)&red[512 + i * 2];
      st_relaxed(&g_cpart[(m * 8 + n) * 128 + i], p0.x + p1.x + p2.x, p0.y + p1.y + p2.y, tag);
    }
    if (tid == 32) STAMP(5, 7);
    for (int i = t96; i < 128; i += 96) {
      uint32_t it = 0;
      while (true) {
        uint4 p[16];
        const uint4 st = ld_relaxed(&g_rowstat[m * 128 + i]);
#pragma unroll
        for (int k = 0; k < 16; k++) p[k] = ld_relaxed(&g_cpart[(k * 8 + n) * 128 + min(i, 119)]);
        bool ok = st.y == tag && st.w == tag;
        float s0 = 0.f, s1 = 0.f;
#pragma unroll
        for (int k = 0; k < 16; k++) {
          ok = ok && p[k].y == tag && p[k].w == tag;
          s0 += __uint_as_float(p[k].x); s1 += __uint_as_float(p[k].z);
        }
        if (ok) {
          *(float2*)&cs[i * 2] = make_float2(s0, s1);
          rowab[i] = make_float2(__uint_as_float(st.x), -__uint_as_float(st.x) * __uint_as_float(st.z));
          break;
        }
        if (++it > (1u << 20)) wait_timeout();
      }
    }
    __syncwarp();
    bar_arrive(2, 96 + 256);
    if (tid == 32) STAMP(0, 5);
    {
      uint4 v[5];
      if (t96 < 80) {
#pragma unroll
        for (int i = 0; i < 5; i++) {
          const int k = blockIdx.x * 5 + i, pr = k / 40, r = k - pr * 40;
          v[i] = ldg_nc(wo + (size_t)(pr * 40 + (r < 16 ? r : (r < 32 ? r + 4 : (r < 36 ? r - 16 : r)))) * D_ + t96 * 8);
        }
        const int nt = t96 / 10;
#pragma unroll
        for (int i = 0; i < 5; i++) {
          const int k = blockIdx.x * 5 + i;
          g_wo[((nt * 10 + (k >> 6)) * 10 + t96 - nt * 10) * 64 + (k & 63)] = v[i];
        }
      }
    }
    if (tid == 32) STAMP(0, 7);
    __syncwarp();
    cluster_wait();
  } else {
    cluster_arrive();
    const int cw = warp - 4, wg = cw >> 2;
    bar_sync(4, 384);
    float acc[120];
    const uint64_t da0 = mkdesc(sbase + wg * 8192, 16, 1024, 1);
    const uint64_t db0 = mkdesc(sbase + 16384, 4096, 512, 2);
    cluster_wait();
#pragma unroll 1
    for (int kt = 0; kt < 10; kt++) {
      const int s = kt % K1_ST;
      mbar_wait(fullb + 8 * s, (kt / K1_ST) & 1);
      if (kt == 0 && tid == 128) STAMP(0, 1);
      const uint64_t da = da0 + s * (K1_STAGE >> 4), db = db0 + s * (K1_STAGE >> 4);
      WG_FENCE();
#pragma unroll
      for (int k = 0; k < 4; k++) wgmma_ss_n240(acc, da + k * 2, db + k * 64, (kt | k) != 0);
      WG_COMMIT();
      if (kt > 0) {
        WG_WAIT(1);
        if (kt - 1 + K1_ST < 10 && (tid & 127) < 2) mbar_arrive_cta(emptyb + 8 * ((kt - 1) % K1_ST), tid & 1);
      }
    }
    WG_WAIT(0);
    fence_regs(acc);
    if (tid == 128) STAMP(0, 2);
    bar_sync(2, 96 + 256);
    if (tid == 128) STAMP(0, 3);
    const int g = lane >> 2, c = lane & 3;
    const bool lo = c < 2;
    const float2 ab0 = rowab[cw * 16 + g], ab1 = rowab[cw * 16 + g + 8];
    const bool p0 = (POLY_MASK >> (cw * 2)) & 1, p1 = (POLY_MASK >> (cw * 2 + 1)) & 1;
    const uint32_t padq = c == 2 ? 0x3F803F80u : 0x00003F80u, padk = c == 2 ? 0x4A7A4B00u : 0x00004653u;
    const uint32_t padv = c == 2 ? 0x00003F80u : 0u;
    uint8_t* dst = (uint8_t*)g_qkv + (size_t)(n * 12) * HEAD_IMG + m * 6144 + lane * 4;
#pragma unroll
    for (int hp = 0; hp < 6; hp++) {
      const int sec = (n * 12 + hp * 2) >> 5;
      const float f0 = sec == 0 ? QSCALE : (sec == 1 && p0 ? 32768.f : 1.f), f1 = sec == 0 ? QSCALE : (sec == 1 && p1 ? 32768.f : 1.f);
      const uint32_t pad0 = sec == 0 ? padq : (sec == 2 ? padv : (p0 ? padk : 0u));
      const uint32_t pad1 = sec == 0 ? padq : (sec == 2 ? padv : (p1 ? padk : 0u));
      const float a0 = ab0.x * f0, b0 = ab0.y * f0, a1 = ab1.x * f1, b1 = ab1.y * f1;
      uint32_t u[5], v[5];
      float su[5], sv[5];
#pragma unroll
      for (int i = 0; i < 5; i++) {
        const int j = hp * 5 + i;
        const float2 t = *(const float2*)&cs[j * 8 + c * 2];
        const float x0 = fmaf(acc[4 * j], a0, b0 * t.x), x1 = fmaf(acc[4 * j + 1], a0, b0 * t.y);
        const float y0 = fmaf(acc[4 * j + 2], a1, b1 * t.x), y1 = fmaf(acc[4 * j + 3], a1, b1 * t.y);
        u[i] = pack_bf16(x0, x1); v[i] = pack_bf16(y0, y1);
        su[i] = fmaf(x0, x0, x1 * x1); sv[i] = fmaf(y0, y0, y1 * y1);
      }
      if (sec < 2) {
        const float r0 = (sec == 1 && p0) ? 9.313225746154785e-10f : 1.f, r1 = (sec == 1 && p1) ? 9.313225746154785e-10f : 1.f;
        float e0 = (su[0] + su[1] + (lo ? su[2] : 0.f)) * r0, e1 = (sv[0] + sv[1] + (lo ? sv[2] : 0.f)) * r1;
        float o0 = (su[3] + su[4] + (lo ? 0.f : su[2])) * r0, o1 = (sv[3] + sv[4] + (lo ? 0.f : sv[2])) * r1;
        e0 += __shfl_xor_sync(~0u, e0, 1); e1 += __shfl_xor_sync(~0u, e1, 1);
        o0 += __shfl_xor_sync(~0u, o0, 1); o1 += __shfl_xor_sync(~0u, o1, 1);
        e0 += __shfl_xor_sync(~0u, e0, 2); e1 += __shfl_xor_sync(~0u, e1, 2);
        o0 += __shfl_xor_sync(~0u, o0, 2); o1 += __shfl_xor_sync(~0u, o1, 2);
        const uint32_t em = __reduce_max_sync(~0u, max(__float_as_uint(e0), __float_as_uint(e1)));
        const uint32_t om = __reduce_max_sync(~0u, max(__float_as_uint(o0), __float_as_uint(o1)));
        if (lane < 2) g_nrm[(n * 12 + hp * 2 + lane) * 128 + m * 8 + cw] = __uint_as_float(lane ? om : em);
      }
      const int cst = sec == 1 ? 2048 : 128, gst = sec == 1 ? 128 : 384;
      uint8_t* pe = dst + (size_t)hp * 2 * HEAD_IMG + cw * 2 * gst;
      uint8_t* pf = pe + gst;
      *(uint32_t*)(pe) = u[0];       *(uint32_t*)(pf) = v[0];
      *(uint32_t*)(pe + cst) = u[1]; *(uint32_t*)(pf + cst) = v[1];
      *(uint32_t*)(pe + 2 * cst) = lo ? u[2] : pad0; *(uint32_t*)(pf + 2 * cst) = lo ? v[2] : pad1;
      *(uint32_t*)(pe + HEAD_IMG) = __shfl_xor_sync(~0u, lo ? u[3] : u[2], 2);
      *(uint32_t*)(pf + HEAD_IMG) = __shfl_xor_sync(~0u, lo ? v[3] : v[2], 2);
      *(uint32_t*)(pe + cst + HEAD_IMG) = __shfl_xor_sync(~0u, lo ? u[4] : u[3], 2);
      *(uint32_t*)(pf + cst + HEAD_IMG) = __shfl_xor_sync(~0u, lo ? v[4] : v[3], 2);
      const uint32_t tu = __shfl_xor_sync(~0u, u[4], 2), tv = __shfl_xor_sync(~0u, v[4], 2);
      *(uint32_t*)(pe + 2 * cst + HEAD_IMG) = lo ? tu : pad0; *(uint32_t*)(pf + 2 * cst + HEAD_IMG) = lo ? tv : pad1;
    }
    if (tid == 128) STAMP(0, 4);
  }
  cluster_sync_relaxed();
  if (tid == 128) STAMP(0, 6);
}

constexpr int K2_SMEM = 2 * HEAD_IMG + 2 * 6144 + 256;

__device__ __forceinline__ uint64_t desc64(uint32_t lo, uint32_t hi) {
  uint64_t d;
  asm("mov.b64 %0, {%1, %2};" : "=l"(d) : "r"(lo), "r"(hi));
  return d;
}
__device__ __forceinline__ uint32_t exp_pair(bool poly, float a, float b, uint32_t mk) {
  if (poly) {
    const uint32_t pk = __byte_perm(__float_as_uint(a), __float_as_uint(b), 0x6521);
    uint32_t m, q;
    asm("lop3.b32 %0, %1, %2, 0x3f803f80, 0xEA;" : "=r"(m) : "r"(pk), "r"(mk));
    asm("fma.rn.bf16x2 %0, %1, %1, %2;" : "=r"(q) : "r"(m), "r"(0x40014001u));
    return pk - m + q;
  }
  return pack_bf16(ex2(a), ex2(b));
}
#define PV_GR 2
__device__ __forceinline__ void exp_pv(const float (&s)[64], float (&o)[12], uint64_t dv, uint32_t mk) {
#pragma unroll
  for (int k0 = 0; k0 < 8; k0 += PV_GR) {
    uint32_t p[4 * PV_GR];
#pragma unroll
    for (int i = 0; i < 4 * PV_GR; i++)
      p[i] = exp_pair((POLY_MASK >> (k0 * 2 + i / 2)) & 1, s[k0 * 8 + 2 * i], s[k0 * 8 + 2 * i + 1], mk);
    WG_FENCE();
#pragma unroll
    for (int k = 0; k < PV_GR; k++)
      wgmma_rs_n24(o, p[4 * k], p[4 * k + 1], p[4 * k + 2], p[4 * k + 3], dv + (k0 + k) * 48, 1);
  }
}
__device__ __forceinline__ void load_q(uint32_t (&q)[6], const uint8_t* p) {
  q[0] = __ldcg((const uint32_t*)p);         q[1] = __ldcg((const uint32_t*)(p + 384));
  q[2] = __ldcg((const uint32_t*)(p + 128)); q[3] = __ldcg((const uint32_t*)(p + 512));
  q[4] = __ldcg((const uint32_t*)(p + 256)); q[5] = __ldcg((const uint32_t*)(p + 640));
}
__device__ __forceinline__ float rcp(float x) {
  float y;
  asm("rcp.approx.ftz.f32 %0, %1;" : "=f"(y) : "f"(x));
  return y;
}
__device__ __forceinline__ int img_off(int chunk) { return (chunk >> 3) * 16384 + (chunk & 7) * 128; }
__device__ __forceinline__ void store_o(const float (&o)[12], int tile) {
  int tid, bid;
  asm volatile("mov.u32 %0, %%tid.x;" : "=r"(tid));
  asm volatile("mov.u32 %0, %%ctaid.x;" : "=r"(bid));
  bid -= 4;
  const int head = bid >> 2;
  uint8_t* dst = (uint8_t*)g_o + ((bid & 3) * 4 + (tile >> 1)) * 163840 + (tile & 1) * 8192 + ((tid >> 5) & 3) * 2048 + (tid & 31) * 4;
  const int oc = (head >> 1) * 5 + (head & 1) * 2;
  const int o0 = img_off(oc), o1 = img_off(oc + 1), o2 = img_off((head >> 1) * 5 + 4) + (head & 1) * 8;
  const float i0 = rcp(__shfl_sync(~0u, o[8], 2, 4)), i1 = rcp(__shfl_sync(~0u, o[10], 2, 4));
  *(uint32_t*)(dst + o0) = pack_bf16(o[0] * i0, o[1] * i0); *(uint32_t*)(dst + o0 + 1024) = pack_bf16(o[2] * i1, o[3] * i1);
  *(uint32_t*)(dst + o1) = pack_bf16(o[4] * i0, o[5] * i0); *(uint32_t*)(dst + o1 + 1024) = pack_bf16(o[6] * i1, o[7] * i1);
  if ((tid & 3) < 2) {
    *(uint32_t*)(dst + o2) = pack_bf16(o[8] * i0, o[9] * i0);
    *(uint32_t*)(dst + o2 + 1024) = pack_bf16(o[10] * i1, o[11] * i1);
  }
}

__global__ void __launch_bounds__(384, 1)
k2_attn(const bf16* __restrict__ wgate, const bf16* __restrict__ wup, const bf16* __restrict__ wd, uint32_t mk) {
  extern __shared__ __align__(1024) uint8_t sm[];
  const uint32_t sbase = smem_u32(sm);
  float* part = (float*)(sm + 2 * HEAD_IMG);
  const uint32_t kvb = sbase + 2 * HEAD_IMG + 2 * 6144;
  const uint32_t partb = kvb + 128;
  const int tid = threadIdx.x, lane = tid & 31;
  const int warp = __shfl_sync(~0u, tid >> 5, 0);

  if (blockIdx.x < 4) {
    if (tid == 0) STAMP(1, 2);
    const int ch = lane & 3, kr = lane >> 2;
#pragma unroll 1
    for (int un = blockIdx.x * 12 + warp; un < 168; un += 48) {
      if (un < 108) {
        const int cg = un * 4 + ch, up = cg >= 216, cc = cg - up * 216, nt = cc / 27;
        const bf16* src = (up ? wup : wgate) + cc * 8 + (size_t)kr * F_;
        uint4* dst = g_wgu + (nt * 10 * 54 + cc - nt * 27 + up * 27) * 64 + kr;
        float a8[8];
#pragma unroll
        for (int i = 0; i < 8; i++) a8[i] = 0.f;
#pragma unroll 1
        for (int bt = 0; bt < 5; bt++) {
          uint4 v[16];
#pragma unroll
          for (int i = 0; i < 16; i++) v[i] = ldg_nc(src + (size_t)(bt * 128 + i * 8) * F_);
#pragma unroll
          for (int i = 0; i < 16; i++) {
            dst[(bt * 2 + (i >> 3)) * (54 * 64) + (i & 7) * 8] = v[i];
            ACC8(a8, v[i]);
          }
        }
#pragma unroll
        for (int i = 0; i < 8; i++) {
          a8[i] += __shfl_xor_sync(~0u, a8[i], 4);
          a8[i] += __shfl_xor_sync(~0u, a8[i], 8);
          a8[i] += __shfl_xor_sync(~0u, a8[i], 16);
        }
        if (lane < 4) {
          *(float4*)&g_csgu[cg * 8] = make_float4(a8[0], a8[1], a8[2], a8[3]);
          *(float4*)&g_csgu[cg * 8 + 4] = make_float4(a8[4], a8[5], a8[6], a8[7]);
        }
      } else {
        const int st = (un - 108) / 3, th = (un - 108) - st * 3, cg = st * 4 + ch, nt = cg / 10;
        const bf16* src = wd + cg * 8 + (size_t)(th * 576 + kr) * D_;
        uint4* dst = g_wd + ((nt * 27 + th * 9) * 10 + cg - nt * 10) * 64 + kr;
#pragma unroll 1
        for (int bt = 0; bt < 3; bt++) {
          uint4 v[24];
#pragma unroll
          for (int i = 0; i < 24; i++) v[i] = ldg_nc(src + (size_t)(bt * 192 + i * 8) * D_);
#pragma unroll
          for (int i = 0; i < 24; i++) dst[(bt * 3 + (i >> 3)) * 640 + (i & 7) * 8] = v[i];
        }
      }
    }
    if (tid == 0) STAMP(1, 6);
    pdl_wait();
    pdl_trigger();
    if (tid == 0 && blockIdx.x == 0) g_epoch = g_epoch + 1;
  } else {
    const int bid = blockIdx.x - 4, head = bid >> 2, qb = bid & 3;
    if (tid == 0) STAMP(1, 0);
    if (tid == 0) {
      for (int i = 0; i < 16; i++) mbar_init(kvb + 8 * i, 1);
      mbar_init(partb, 128); mbar_init(partb + 8, 128);
      asm volatile("fence.mbarrier_init.release.cluster;" ::: "memory");
    }
    __syncthreads();
    pdl_wait();
    pdl_trigger();
    if (tid == 256) {
      const uint8_t* kimg = (const uint8_t*)g_qkv + (size_t)(32 + head) * HEAD_IMG;
#pragma unroll 1
      for (int b = 0; b < 16; b++) {
        mbar_expect(kvb + 8 * b, 12288);
        bulk_ld(sbase + b * 6144, kimg + b * 6144, 6144, kvb + 8 * b);
        bulk_ld(sbase + HEAD_IMG + b * 6144, kimg + 32 * HEAD_IMG + b * 6144, 6144, kvb + 8 * b);
      }
    }
    __syncwarp();
    const int wg = warp >> 2;
    const uint8_t* qthr = (const uint8_t*)g_qkv + (size_t)head * HEAD_IMG + qb * 64 * 384 + (warp & 3) * 768 + lane * 4;
    const uint32_t klo0 = ((sbase & 0x3FFFF) >> 4) | (128u << 16), vlo0 = (((sbase + HEAD_IMG) & 0x3FFFF) >> 4) | (24u << 16);
    constexpr int64_t KSTEP2 = 256 - (128 << 16);
    const int nun = wg == 1 ? 4 : 3;
    uint32_t utile = wg == 0 ? 0x210u : (wg == 1 ? 0x4325u : 0x576u);
    uint32_t ubeg = wg == 0 ? 0u : (wg == 1 ? 0x00b0u : 0x600u);
    uint32_t ulen = wg == 0 ? 0x0b1010u : (wg == 1 ? 0x10100506u : 0x0a1010u);
    if (tid == 0) STAMP(1, 1);
    uint32_t q[6], qn[6];
    load_q(q, qthr + (utile & 15) * 3072);
    load_q(qn, qthr + ((utile >> 4) & 15) * 3072);
    bool fast;
    {
      const float4 kn = __ldcg((const float4*)&g_nrm[(32 + head) * 128 + lane * 4]);
      const float qv = __ldcg(&g_nrm[head * 128 + qb * 32 + lane]);
      const uint32_t km = max(max(__float_as_uint(kn.x), __float_as_uint(kn.y)), max(__float_as_uint(kn.z), __float_as_uint(kn.w)));
      const float k2 = __uint_as_float(__reduce_max_sync(~0u, km)), q2 = __uint_as_float(__reduce_max_sync(~0u, __float_as_uint(qv)));
      fast = q2 * k2 <= 3400.f;
    }
    if (fast) {
      float s[64], o[12];
#pragma unroll
      for (int i = 0; i < 12; i++) o[i] = 0.f;
      uint32_t klo = klo0, vlo = vlo0, kb = kvb;
      int cnt = ulen & 255, u = 0;
      bool wt = true;
      mbar_wait(kb, 0);
      fence_regs(o);
      WG_FENCE();
      wgmma_rs_n128(s, q[0], q[1], q[2], q[3], desc64(klo, 8), 0);
      wgmma_rs_n128(s, q[4], q[5], 0, 0, desc64(klo, 8) + KSTEP2, 1);
      WG_COMMIT();
#pragma unroll 1
      while (true) {
        const bool last = --cnt == 0;
        if (last) {
          if (u + 1 == nun) break;
          const uint32_t b = (ubeg >> 4) & 15;
          klo = klo0 + b * 384 - 384; kb = kvb + b * 8 - 8;
          wt = wg == 1 && u < 2;
        }
        klo += 384; kb += 8;
        if (wt) mbar_wait(kb, 0);
        WG_WAIT(0);
        fence_regs(s); fence_regs(o);
        exp_pv(s, o, desc64(vlo, 8), mk);
        vlo += 384;
        if (last) {
#pragma unroll
          for (int i = 0; i < 6; i++) q[i] = qn[i];
          WG_FENCE();
        }
        wgmma_rs_n128(s, q[0], q[1], q[2], q[3], desc64(klo, 8), 0);
        wgmma_rs_n128(s, q[4], q[5], 0, 0, desc64(klo, 8) + KSTEP2, 1);
        WG_COMMIT();
        if (last) {
          if (u + 2 < nun) load_q(qn, qthr + ((utile >> 8) & 15) * 3072);
          WG_WAIT(0);
          fence_regs(s); fence_regs(o);
          if (wg == 1 && u < 2) {
            float4* pp = (float4*)(part + u * 1536) + (tid & 127);
            pp[0] = make_float4(o[0], o[1], o[2], o[3]);
            pp[128] = make_float4(o[4], o[5], o[6], o[7]);
            pp[256] = make_float4(o[8], o[9], o[10], o[11]);
            mbar_arrive(partb + 8 * u);
          } else {
            store_o(o, utile & 15);
          }
#pragma unroll
          for (int i = 0; i < 12; i++) o[i] = 0.f;
          u++; utile >>= 4; ubeg >>= 4; ulen >>= 8;
          cnt = ulen & 255;
          vlo = vlo0 + (ubeg & 15) * 384;
        }
      }
      WG_WAIT(0);
      fence_regs(s); fence_regs(o);
      exp_pv(s, o, desc64(vlo, 8), mk);
      WG_COMMIT();
      WG_WAIT(0);
      fence_regs(o);
      if (wg != 1) {
        const int pi = wg == 0 ? 1 : 0;
        mbar_wait(partb + 8 * pi, 0);
        const float4* pp = (const float4*)(part + pi * 1536) + (tid & 127);
        const float4 x0 = pp[0], x1 = pp[128], x2 = pp[256];
        o[0] += x0.x; o[1] += x0.y; o[2] += x0.z; o[3] += x0.w; o[4] += x1.x; o[5] += x1.y;
        o[6] += x1.z; o[7] += x1.w; o[8] += x2.x; o[9] += x2.y; o[10] += x2.z; o[11] += x2.w;
      }
      store_o(o, utile & 15);
      if ((tid & 127) == 0) STAMP(1, 3 + wg);
    } else {
#pragma unroll 1
      for (int tile = wg; tile < 8; tile += 3) {
        load_q(q, qthr + tile * 3072);
        if ((lane & 3) >= 2) { q[4] = 0; q[5] = 0; }
        float o[12], m0 = -INFINITY, m1 = -INFINITY;
#pragma unroll
        for (int i = 0; i < 12; i++) o[i] = 0.f;
#pragma unroll 1
        for (int b = 0; b < 16; b++) {
          float s[64];
          mbar_wait(kvb + 8 * b, 0);
          WG_FENCE();
          wgmma_rs_n128(s, q[0], q[1], q[2], q[3], desc64(klo0 + b * 384, 8), 0);
          wgmma_rs_n128(s, q[4], q[5], 0, 0, desc64(klo0 + b * 384, 8) + KSTEP2, 1);
          WG_COMMIT();
          WG_WAIT(0);
          fence_regs(s);
          float x0 = m0, x1 = m1;
#pragma unroll
          for (int j = 0; j < 16; j++) {
            if ((POLY_MASK >> j) & 1) {
#pragma unroll
              for (int i = 0; i < 4; i++) s[4 * j + i] *= (1.f / 32768.f);
            }
            x0 = fmaxf(x0, fmaxf(s[4 * j], s[4 * j + 1]));
            x1 = fmaxf(x1, fmaxf(s[4 * j + 2], s[4 * j + 3]));
          }
          x0 = fmaxf(x0, __shfl_xor_sync(~0u, x0, 1)); x0 = fmaxf(x0, __shfl_xor_sync(~0u, x0, 2));
          x1 = fmaxf(x1, __shfl_xor_sync(~0u, x1, 1)); x1 = fmaxf(x1, __shfl_xor_sync(~0u, x1, 2));
          const float al0 = ex2(m0 - x0), al1 = ex2(m1 - x1);
          m0 = x0; m1 = x1;
#pragma unroll
          for (int i = 0; i < 12; i++) o[i] *= (i & 2) ? al1 : al0;
          uint32_t p[32];
#pragma unroll
          for (int i = 0; i < 32; i++) {
            const float mm = (i & 1) ? m1 : m0;
            p[i] = pack_bf16(ex2(s[2 * i] - mm), ex2(s[2 * i + 1] - mm));
          }
          fence_regs(o);
          WG_FENCE();
#pragma unroll
          for (int k = 0; k < 8; k++)
            wgmma_rs_n24(o, p[4 * k], p[4 * k + 1], p[4 * k + 2], p[4 * k + 3], desc64(vlo0 + b * 384 + k * 48, 8), 1);
          WG_COMMIT();
          WG_WAIT(0);
          fence_regs(o);
        }
        store_o(o, tile);
      }
    }
  }
}

constexpr int K3_ST = 4, K3_STAGE = 36864;
constexpr int K3_SMEM = K3_ST * K3_STAGE + 40960 + 20480 + 256;

template <int KT, bool FIRST>
__global__ void __cluster_dims__(2, 1, 1) __launch_bounds__(384, 1)
k3_proj(const __grid_constant__ CUtensorMap tmr, const uint4* __restrict__ aimg, const uint4* __restrict__ wimg) {
  extern __shared__ __align__(1024) uint8_t sm[];
  const uint32_t sbase = smem_u32(sm);
  uint8_t* xch = sm + K3_ST * K3_STAGE;
  uint8_t* stg = sm + K3_ST * K3_STAGE + 40960;
  const uint32_t fullb = smem_u32(stg) + 20480, emptyb = fullb + 8 * K3_ST, resb = emptyb + 8 * K3_ST, xchb = resb + 8;
  const int tid = threadIdx.x, lane = tid & 31;
  const int warp = __shfl_sync(~0u, tid >> 5, 0);
  const int rank = blockIdx.x & 1;
  const int n = blockIdx.x & 7, m = blockIdx.x >> 3;
  const int kt0 = rank * ((KT + 1) / 2), nkt = rank ? KT / 2 : (KT + 1) / 2;
  if (tid == 0) STAMP(FIRST ? 2 : 4, 0);
  if (tid == 0) {
    prefetch_map(&tmr);
    for (int i = 0; i < K3_ST; i++) { mbar_init(fullb + 8 * i, 1); mbar_init(emptyb + 8 * i, 2); }
    mbar_init(resb, 1); mbar_init(xchb, 1);
    mbar_expect(xchb, 40960);
    asm volatile("fence.mbarrier_init.release.cluster;" ::: "memory");
  }
  __syncthreads();
  cluster_arrive();
  if (warp == 0) {
    if (lane == 0) {
      const uint8_t* wk = (const uint8_t*)wimg + (size_t)(n * KT + kt0) * 10240;
      const uint8_t* ws = (const uint8_t*)wimg + (size_t)((n ^ 1) * KT + kt0) * 10240;
      const uint8_t* ab = (const uint8_t*)aimg + (size_t)(m * KT + kt0) * 16384;
      mbar_expect(fullb, K3_STAGE);
      bulk_ld(sbase + 16384, wk, 10240, fullb);
      bulk_ld(sbase + 26624, ws, 10240, fullb);
      pdl_wait();
      pdl_trigger();
      for (int i = 0; i < nkt; i++) {
        const int s = i % K3_ST;
        const uint32_t sa = sbase + s * K3_STAGE;
        if (i >= K3_ST) mbar_wait(emptyb + 8 * s, ((i / K3_ST) - 1) & 1);
        if (i > 0) mbar_expect(fullb + 8 * s, K3_STAGE);
        bulk_ld(sa, ab + i * 16384, 16384, fullb + 8 * s);
        if (i > 0) {
          bulk_ld(sa + 16384, wk + i * 10240, 10240, fullb + 8 * s);
          bulk_ld(sa + 26624, ws + i * 10240, 10240, fullb + 8 * s);
        }
        if (FIRST && i == K3_ST - 1) {
          mbar_expect(resb, 20480);
          tma2d(smem_u32(stg), &tmr, n * 80, m * 128, resb);
          tma2d(smem_u32(stg) + 10240, &tmr, n * 80, m * 128 + 64, resb);
        }
      }
    }
    __syncwarp();
    cluster_wait();
  } else if (warp >= 4) {
    const int cw = warp - 4, wg = cw >> 2;
    const int g = lane >> 2, c = lane & 3;
    uint8_t* himg = (uint8_t*)g_h + (size_t)m * 163840 + cw * 2048 + g * 16 + c * 4;
    uint32_t rv[20];
    if (!FIRST) {
#pragma unroll
      for (int j = 0; j < 10; j++) {
        rv[2 * j] = __ldcg((const uint32_t*)(himg + img_off(n * 10 + j)));
        rv[2 * j + 1] = __ldcg((const uint32_t*)(himg + img_off(n * 10 + j) + 1024));
      }
    }
    float acc[80];
    const uint64_t da0 = mkdesc(sbase + wg * 8192, 128, 1024, 0);
    const uint64_t db0 = mkdesc(sbase + 16384, 128, 1024, 0);
#pragma unroll 1
    for (int i = 0; i < nkt; i++) {
      const int s = i % K3_ST;
      mbar_wait(fullb + 8 * s, (i / K3_ST) & 1);
      if (i == 0 && tid == 128) STAMP(FIRST ? 2 : 4, 2);
      const uint64_t da = da0 + s * (K3_STAGE >> 4), db = db0 + s * (K3_STAGE >> 4);
      WG_FENCE();
#pragma unroll
      for (int k = 0; k < 4; k++) wgmma_ss_n160(acc, da + k * 16, db + k * 16, (i | k) != 0);
      WG_COMMIT();
      if (i > 0) {
        WG_WAIT(1);
        if ((tid & 127) == 0) mbar_arrive(emptyb + 8 * ((i - 1) % K3_ST));
      }
    }
    uint8_t* sp = stg + (cw * 16 + g) * 160 + c * 4;
    if (FIRST) {
      mbar_wait(resb, 0);
#pragma unroll
      for (int j = 0; j < 10; j++) {
        rv[2 * j] = *(const uint32_t*)(sp + j * 16);
        rv[2 * j + 1] = *(const uint32_t*)(sp + 1280 + j * 16);
      }
    }
    cluster_wait();
    WG_WAIT(0);
    fence_regs(acc);
    if (tid == 128) STAMP(FIRST ? 2 : 4, 3);
    bar_sync(3, 256);
#pragma unroll
    for (int j = 0; j < 10; j++)
      *(float4*)(sm + cw * 5120 + j * 512 + lane * 16) = make_float4(acc[40 + 4 * j], acc[41 + 4 * j], acc[42 + 4 * j], acc[43 + 4 * j]);
    fence_async();
    __syncwarp();
    if (lane == 0)
      asm volatile("cp.async.bulk.shared::cluster.shared::cta.mbarrier::complete_tx::bytes [%0], [%1], 5120, [%2];"
                   ::"r"(mapa(smem_u32(xch) + cw * 5120, rank ^ 1)), "r"(sbase + cw * 5120), "r"(mapa(xchb, rank ^ 1)) : "memory");
#pragma unroll
    for (int j = 0; j < 10; j++) {
      acc[4 * j] += bf_lo(rv[2 * j]); acc[4 * j + 1] += bf_hi(rv[2 * j]);
      acc[4 * j + 2] += bf_lo(rv[2 * j + 1]); acc[4 * j + 3] += bf_hi(rv[2 * j + 1]);
    }
    mbar_wait(xchb, 0);
    if (tid == 128) STAMP(FIRST ? 2 : 4, 5);
    float s0 = 0.f, s1 = 0.f;
#pragma unroll
    for (int j = 0; j < 10; j++) {
      const float4 p = *(const float4*)(xch + cw * 5120 + j * 512 + lane * 16);
      acc[4 * j] += p.x; acc[4 * j + 1] += p.y; acc[4 * j + 2] += p.z; acc[4 * j + 3] += p.w;
      if (FIRST) {
        *(uint32_t*)(himg + img_off(n * 10 + j)) = pack_bf16(acc[4 * j], acc[4 * j + 1]);
        *(uint32_t*)(himg + img_off(n * 10 + j) + 1024) = pack_bf16(acc[4 * j + 2], acc[4 * j + 3]);
        s0 += acc[4 * j] + acc[4 * j + 1]; s1 += acc[4 * j + 2] + acc[4 * j + 3];
      } else {
        *(uint32_t*)(sp + j * 16) = pack_bf16(acc[4 * j], acc[4 * j + 1]);
        *(uint32_t*)(sp + 1280 + j * 16) = pack_bf16(acc[4 * j + 2], acc[4 * j + 3]);
      }
    }
    if (FIRST) {
      s0 += __shfl_xor_sync(~0u, s0, 1); s0 += __shfl_xor_sync(~0u, s0, 2);
      s1 += __shfl_xor_sync(~0u, s1, 1); s1 += __shfl_xor_sync(~0u, s1, 2);
      s0 *= (1.f / 80.f); s1 *= (1.f / 80.f);
      float q0 = 0.f, q1 = 0.f;
#pragma unroll
      for (int j = 0; j < 10; j++) {
        float d;
        d = acc[4 * j] - s0; q0 = fmaf(d, d, q0); d = acc[4 * j + 1] - s0; q0 = fmaf(d, d, q0);
        d = acc[4 * j + 2] - s1; q1 = fmaf(d, d, q1); d = acc[4 * j + 3] - s1; q1 = fmaf(d, d, q1);
      }
      q0 += __shfl_xor_sync(~0u, q0, 1); q0 += __shfl_xor_sync(~0u, q0, 2);
      q1 += __shfl_xor_sync(~0u, q1, 1); q1 += __shfl_xor_sync(~0u, q1, 2);
      if (c < 2) g_hpart[n * S_ + m * 128 + cw * 16 + g + c * 8] = c ? make_float2(s1, q1) : make_float2(s0, q0);
    } else {
      fence_async();
      bar_sync(1 + wg, 128);
      if ((tid & 127) == 0) {
        tma2d_st(&tmr, n * 80, m * 128 + wg * 64, smem_u32(stg) + wg * 10240);
        bulk_commit_wait();
      }
      __syncwarp();
    }
    if (tid == 128) STAMP(FIRST ? 2 : 4, 4);
  } else {
    cluster_wait();
  }
  cluster_sync_relaxed();
}

constexpr int K4_ST = 3, K4_STAGE = 71680;
constexpr int K4_SMEM = K4_ST * K4_STAGE + 1728 + 1024 + 64;

__global__ void __cluster_dims__(2, 1, 1) __launch_bounds__(256, 1)
k4_ffn1() {
  extern __shared__ __align__(1024) uint8_t sm[];
  float* cs = (float*)(sm + K4_ST * K4_STAGE);
  float2* rowst = (float2*)(sm + K4_ST * K4_STAGE + 1728);
  const uint32_t sbase = smem_u32(sm);
  const uint32_t fullb = sbase + K4_ST * K4_STAGE + 2752, emptyb = fullb + 8 * K4_ST;
  const int tid = threadIdx.x, lane = tid & 31;
  const int warp = __shfl_sync(~0u, tid >> 5, 0);
  const int rank = blockIdx.x & 1, cl = blockIdx.x >> 1;
  const int n = cl & 7, m = (cl >> 3) * 2 + rank;
  const uint8_t* wb = (const uint8_t*)g_wgu + (size_t)n * 10 * 55296 + rank * 27648;
  const uint8_t* ab = (const uint8_t*)g_h + (size_t)m * 163840;
  if (tid == 0) STAMP(3, 0);
  if (tid == 0) {
    for (int i = 0; i < K4_ST; i++) { mbar_init(fullb + 8 * i, 1); mbar_init(emptyb + 8 * i, 4); }
    asm volatile("fence.mbarrier_init.release.cluster;" ::: "memory");
  }
  __syncthreads();
  cluster_arrive();
  const float cs0 = __ldcg(&g_csgu[(tid >= 216 ? F_ - 216 : 0) + n * 216 + tid]);
  const float cs1 = tid < 176 ? __ldcg(&g_csgu[F_ - 216 + n * 216 + 256 + tid]) : 0.f;
  cluster_wait();
  if (tid == 0) {
    for (int kt = 0; kt < K4_ST; kt++) mbar_expect(fullb + 8 * kt, K4_STAGE);
    bulk_ld_mc(sbase + 16384 + rank * 27648, wb, 27648, fullb);
  }
  pdl_wait();
  pdl_trigger();
  if (tid == 128) STAMP(3, 1);
  if (tid == 0) {
    bulk_ld(sbase, ab, 16384, fullb);
    for (int kt = 1; kt < K4_ST; kt++) {
      bulk_ld(sbase + kt * K4_STAGE, ab + kt * 16384, 16384, fullb + 8 * kt);
      bulk_ld_mc(sbase + kt * K4_STAGE + 16384 + rank * 27648, wb + kt * 55296, 27648, fullb + 8 * kt);
    }
  }
  if (tid >= 128) {
    const int r = tid - 128;
    float2 p[8];
#pragma unroll
    for (int i = 0; i < 8; i++) p[i] = __ldcg(&g_hpart[i * S_ + m * 128 + r]);
    float mean = 0.f, m2 = 0.f;
#pragma unroll
    for (int i = 0; i < 8; i++) { mean += p[i].x; m2 += p[i].y; }
    mean *= 0.125f;
#pragma unroll
    for (int i = 0; i < 8; i++) { const float d = p[i].x - mean; m2 = fmaf(80.f * d, d, m2); }
    rowst[r] = make_float2(-mean, __frcp_rn(m2 * (1.f / D_) + 1e-5f));
  }
  cs[tid] = cs0;
  if (tid < 176) cs[256 + tid] = cs1;
  __syncwarp();
  float ag[108], au[108];
  const uint64_t da0 = mkdesc(sbase + (warp >> 2) * 8192, 128, 1024, 0);
  const uint64_t db0 = mkdesc(sbase + 16384, 128, 1024, 0);
#pragma unroll 1
  for (int kt = 0; kt < 10; kt++) {
    const int s = kt % K4_ST;
    mbar_wait(fullb + 8 * s, (kt / K4_ST) & 1);
    if (kt == 0 && tid == 128) STAMP(3, 2);
    const uint64_t da = da0 + s * (K4_STAGE >> 4), db = db0 + s * (K4_STAGE >> 4);
    WG_FENCE();
#pragma unroll
    for (int k = 0; k < 4; k++) {
      wgmma_ss_n216(ag, da + k * 16, db + k * 16, (kt | k) != 0);
      wgmma_ss_n216(au, da + k * 16, db + 1728 + k * 16, (kt | k) != 0);
    }
    WG_COMMIT();
    if (kt > 0 && kt - 1 + K4_ST < 10) {
      WG_WAIT(1);
      const int sp = (kt - 1) % K4_ST;
      if ((tid & 127) < 2) mbar_arrive_cta(emptyb + 8 * sp, tid & 1);
      if (tid == 0) {
        const uint32_t sa = sbase + sp * K4_STAGE;
        mbar_wait(emptyb + 8 * sp, ((kt - 1) / K4_ST) & 1);
        mbar_expect(fullb + 8 * sp, K4_STAGE);
        bulk_ld_mc(sa + 16384 + rank * 27648, wb + (kt - 1 + K4_ST) * 55296, 27648, fullb + 8 * sp);
        bulk_ld(sa, ab + (kt - 1 + K4_ST) * 16384, 16384, fullb + 8 * sp);
      }
      __syncwarp();
    }
  }
  WG_WAIT(0);
  fence_regs(ag); fence_regs(au);
  if (tid == 128) STAMP(3, 3);
  __syncthreads();
  const int g = lane >> 2, c = lane & 3;
  const float2 st0 = rowst[warp * 16 + g], st1 = rowst[warp * 16 + g + 8];
  uint8_t* dst = (uint8_t*)g_hh + (size_t)m * 27 * 16384 + warp * 2048 + g * 16 + c * 4;
#pragma unroll
  for (int j = 0; j < 27; j++) {
    const float2 cg = *(const float2*)&cs[j * 8 + c * 2], cu = *(const float2*)&cs[216 + j * 8 + c * 2];
    const float h0 = fmaf(st0.x, cg.x, ag[4 * j]) * st0.y * fmaf(st0.x, cu.x, au[4 * j]);
    const float h1 = fmaf(st0.x, cg.y, ag[4 * j + 1]) * st0.y * fmaf(st0.x, cu.y, au[4 * j + 1]);
    const float h2 = fmaf(st1.x, cg.x, ag[4 * j + 2]) * st1.y * fmaf(st1.x, cu.x, au[4 * j + 2]);
    const float h3 = fmaf(st1.x, cg.y, ag[4 * j + 3]) * st1.y * fmaf(st1.x, cu.y, au[4 * j + 3]);
    *(uint32_t*)(dst + img_off(n * 27 + j)) = pack_bf16(h0, h1);
    *(uint32_t*)(dst + img_off(n * 27 + j) + 1024) = pack_bf16(h2, h3);
  }
  if (tid == 128) STAMP(3, 4);
  cluster_sync_relaxed();
}

typedef CUresult (*EncodeFn)(CUtensorMap*, CUtensorMapDataType, cuuint32_t, void*, const cuuint64_t*, const cuuint64_t*,
                             const cuuint32_t*, const cuuint32_t*, CUtensorMapInterleave, CUtensorMapSwizzle,
                             CUtensorMapL2promotion, CUtensorMapFloatOOBfill);

static CUtensorMap make_map(EncodeFn enc, const void* p, uint64_t inner, uint64_t outer, uint32_t box_inner,
                            uint32_t box_outer, CUtensorMapSwizzle swz) {
  CUtensorMap m;
  cuuint64_t gd[2] = {inner, outer};
  cuuint64_t gs[1] = {inner * 2};
  cuuint32_t bd[2] = {box_inner, box_outer};
  cuuint32_t es[2] = {1, 1};
  enc(&m, CU_TENSOR_MAP_DATA_TYPE_BFLOAT16, 2, (void*)p, gd, gs, bd, es, CU_TENSOR_MAP_INTERLEAVE_NONE, swz,
      CU_TENSOR_MAP_L2_PROMOTION_L2_256B, CU_TENSOR_MAP_FLOAT_OOB_FILL_NONE);
  return m;
}

template <typename... KArgs, typename... Args>
static void launch(void (*k)(KArgs...), int grid, int threads, int smem, bool pdl, Args... args) {
  cudaLaunchConfig_t cfg = {};
  cfg.gridDim = dim3(grid);
  cfg.blockDim = dim3(threads);
  cfg.dynamicSmemBytes = smem;
  cfg.stream = cudaStreamPerThread;
  cudaLaunchAttribute at[1];
  at[0].id = cudaLaunchAttributeProgrammaticStreamSerialization;
  at[0].val.programmaticStreamSerializationAllowed = 1;
  cfg.attrs = at;
  cfg.numAttrs = pdl ? 1 : 0;
  cudaLaunchKernelEx(&cfg, k, KArgs(args)...);
}

extern "C" void kernel_launch(void* const* d_in, const int* in_sizes, int n_in, void* d_out, int out_size) {
  const bf16* x = (const bf16*)d_in[0];
  const bf16* wqkv = (const bf16*)d_in[1];
  const bf16* wo = (const bf16*)d_in[2];
  const bf16* wg = (const bf16*)d_in[4];
  const bf16* wu = (const bf16*)d_in[5];
  const bf16* wd = (const bf16*)d_in[6];

  static EncodeFn enc = nullptr;
  static void *p_o, *p_hh, *p_wo, *p_wd;
  if (!enc) {
    void* fn = nullptr;
    cudaDriverEntryPointQueryResult qr;
    cudaGetDriverEntryPoint("cuTensorMapEncodeTiled", &fn, cudaEnableDefault, &qr);
    enc = (EncodeFn)fn;
    cudaGetSymbolAddress(&p_o, g_o); cudaGetSymbolAddress(&p_hh, g_hh);
    cudaGetSymbolAddress(&p_wo, g_wo); cudaGetSymbolAddress(&p_wd, g_wd);
    cudaFuncSetAttribute(k1_qkv, cudaFuncAttributeMaxDynamicSharedMemorySize, K1_SMEM);
    cudaFuncSetAttribute(k2_attn, cudaFuncAttributeMaxDynamicSharedMemorySize, K2_SMEM);
    cudaFuncSetAttribute(k3_proj<10, true>, cudaFuncAttributeMaxDynamicSharedMemorySize, K3_SMEM);
    cudaFuncSetAttribute(k3_proj<27, false>, cudaFuncAttributeMaxDynamicSharedMemorySize, K3_SMEM);
    cudaFuncSetAttribute(k4_ffn1, cudaFuncAttributeMaxDynamicSharedMemorySize, K4_SMEM);
  }
  const CUtensorMap tmx = make_map(enc, x, D_, S_, 64, 128, CU_TENSOR_MAP_SWIZZLE_128B);
  const CUtensorMap tmw = make_map(enc, wqkv, 3 * D_, D_, 32, 64, CU_TENSOR_MAP_SWIZZLE_64B);
  const CUtensorMap tmxr = make_map(enc, x, D_, S_, 80, 64, CU_TENSOR_MAP_SWIZZLE_NONE);
  const CUtensorMap tmout = make_map(enc, d_out, D_, S_, 80, 64, CU_TENSOR_MAP_SWIZZLE_NONE);

  launch(k1_qkv, 128, 384, K1_SMEM, false, tmx, tmw, x, wqkv, wo);
  launch(k2_attn, 132, 384, K2_SMEM, true, wg, wu, wd, 0x007f007fu);
  launch(k3_proj<10, true>, 128, 384, K3_SMEM, true, tmxr, (const uint4*)p_o, (const uint4*)p_wo);
  launch(k4_ffn1, 128, 256, K4_SMEM, true);
  launch(k3_proj<27, false>, 128, 384, K3_SMEM, true, tmout, (const uint4*)p_hh, (const uint4*)p_wd);
}
```

```cpp
#include <cuda_runtime.h>
#include <cuda_bf16.h>
#include <cuda.h>
#include <stdint.h>

typedef __nv_bfloat16 bf16;

constexpr int S_ = 2048, D_ = 640, F_ = 1728;
constexpr int HEAD_IMG = 98304;
#define PMASK 0xABAB
constexpr uint32_t POLY_MASK = PMASK;
constexpr float QSCALE = 0.22360679774997896f * 1.4426950408889634f;

__device__ __align__(1024) uint4 g_qkv[96 * HEAD_IMG / 16];
__device__ __align__(1024) uint4 g_o[S_ * D_ / 8];
__device__ __align__(1024) uint4 g_h[S_ * D_ / 8];
__device__ __align__(1024) uint4 g_hh[S_ * F_ / 8];
__device__ __align__(1024) uint4 g_wo[D_ * D_ / 8];
__device__ __align__(1024) uint4 g_wgu[2 * D_ * F_ / 8];
__device__ __align__(1024) uint4 g_wd[F_ * D_ / 8];
__device__ uint4 g_rowstat[S_];
__device__ uint4 g_cpart[16 * 8 * 128];
__device__ float g_nrm[64 * 128];
__device__ uint4 g_wm[D_];
__device__ float g_hmean[S_];
__device__ float g_hpart[8 * S_];
__device__ unsigned g_epoch;

#define STAMP(k, i)
__device__ __forceinline__ uint32_t smem_u32(const void* p) { return (uint32_t)__cvta_generic_to_shared(p); }
__device__ __forceinline__ void mbar_init(uint32_t a, uint32_t c) {
  asm volatile("mbarrier.init.shared::cta.b64 [%0], %1;" ::"r"(a), "r"(c) : "memory");
}
__device__ __forceinline__ void mbar_expect(uint32_t a, uint32_t bytes) {
  asm volatile("mbarrier.arrive.expect_tx.shared::cta.b64 _, [%0], %1;" ::"r"(a), "r"(bytes) : "memory");
}
__device__ __forceinline__ void mbar_arrive(uint32_t a) {
  asm volatile("mbarrier.arrive.shared::cta.b64 _, [%0];" ::"r"(a) : "memory");
}
__device__ __forceinline__ void mbar_arrive_cta(uint32_t a, uint32_t cta) {
  asm volatile("{\n.reg .b32 r;\nmapa.shared::cluster.u32 r, %0, %1;\n"
               "mbarrier.arrive.shared::cluster.b64 _, [r];\n}" ::"r"(a), "r"(cta) : "memory");
}
__device__ __forceinline__ bool mbar_try(uint32_t a, uint32_t ph) {
  uint32_t ok;
  asm volatile("{\n.reg .pred p;\nmbarrier.try_wait.parity.shared::cta.b64 p, [%1], %2;\nselp.u32 %0, 1, 0, p;\n}"
               : "=r"(ok) : "r"(a), "r"(ph) : "memory");
  return ok;
}
__device__ __noinline__ void wait_timeout() { __trap(); }
__device__ __forceinline__ void mbar_wait(uint32_t a, uint32_t ph) {
  if (mbar_try(a, ph)) return;
  uint32_t it = 0;
  while (!mbar_try(a, ph)) if (++it > (1u << 22)) wait_timeout();
}
__device__ __forceinline__ void tma2d(uint32_t dst, const CUtensorMap* m, int c0, int c1, uint32_t bar) {
  asm volatile("cp.async.bulk.tensor.2d.shared::cluster.global.mbarrier::complete_tx::bytes [%0], [%1, {%3, %4}], [%2];"
               ::"r"(dst), "l"(m), "r"(bar), "r"(c0), "r"(c1) : "memory");
}
__device__ __forceinline__ void tma2d_mc(uint32_t dst, const CUtensorMap* m, int c0, int c1, uint32_t bar) {
  asm volatile("cp.async.bulk.tensor.2d.shared::cluster.global.mbarrier::complete_tx::bytes.multicast::cluster "
               "[%0], [%1, {%3, %4}], [%2], %5;"
               ::"r"(dst), "l"(m), "r"(bar), "r"(c0), "r"(c1), "h"((uint16_t)3) : "memory");
}
__device__ __forceinline__ void bulk_ld(uint32_t dst, const void* src, uint32_t bytes, uint32_t bar) {
  asm volatile("cp.async.bulk.shared::cluster.global.mbarrier::complete_tx::bytes [%0], [%1], %2, [%3];"
               ::"r"(dst), "l"(src), "r"(bytes), "r"(bar) : "memory");
}
__device__ __forceinline__ void bulk_ld_mc(uint32_t dst, const void* src, uint32_t bytes, uint32_t bar) {
  asm volatile("cp.async.bulk.shared::cluster.global.mbarrier::complete_tx::bytes.multicast::cluster "
               "[%0], [%1], %2, [%3], %4;"
               ::"r"(dst), "l"(src), "r"(bytes), "r"(bar), "h"((uint16_t)3) : "memory");
}
__device__ __forceinline__ void cluster_arrive() { asm volatile("barrier.cluster.arrive.relaxed.aligned;" ::: "memory"); }
__device__ __forceinline__ void cluster_wait() { asm volatile("barrier.cluster.wait.aligned;" ::: "memory"); }
__device__ __forceinline__ void bulk_st(void* dst, uint32_t src, uint32_t bytes) {
  asm volatile("cp.async.bulk.global.shared::cta.bulk_group [%0], [%1], %2;" ::"l"(dst), "r"(src), "r"(bytes) : "memory");
}
__device__ __forceinline__ void tma2d_st(const CUtensorMap* m, int c0, int c1, uint32_t src) {
  asm volatile("cp.async.bulk.tensor.2d.global.shared::cta.bulk_group [%0, {%2, %3}], [%1];"
               ::"l"(m), "r"(src), "r"(c0), "r"(c1) : "memory");
}
__device__ __forceinline__ void bulk_commit_wait() {
  asm volatile("cp.async.bulk.commit_group;\ncp.async.bulk.wait_group.read 0;" ::: "memory");
}
__device__ __forceinline__ uint32_t mapa(uint32_t a, uint32_t cta) {
  uint32_t r;
  asm("mapa.shared::cluster.u32 %0, %1, %2;" : "=r"(r) : "r"(a), "r"(cta));
  return r;
}
__device__ __forceinline__ void st_async4(uint32_t dst, float a, float b, float c, float d, uint32_t bar) {
  asm volatile("st.async.shared::cluster.mbarrier::complete_tx::bytes.v4.f32 [%0], {%1, %2, %3, %4}, [%5];"
               ::"r"(dst), "f"(a), "f"(b), "f"(c), "f"(d), "r"(bar) : "memory");
}
__device__ __forceinline__ void fence_async() { asm volatile("fence.proxy.async.shared::cta;" ::: "memory"); }
__device__ __forceinline__ void prefetch_map(const CUtensorMap* m) {
  asm volatile("prefetch.tensormap [%0];" ::"l"(m) : "memory");
}
__device__ __forceinline__ void pdl_wait() { asm volatile("griddepcontrol.wait;" ::: "memory"); }
__device__ __forceinline__ void pdl_trigger() { asm volatile("griddepcontrol.launch_dependents;" ::: "memory"); }
__device__ __forceinline__ void bar_sync(int id, int n) { asm volatile("bar.sync %0, %1;" ::"r"(id), "r"(n) : "memory"); }
__device__ __forceinline__ void bar_arrive(int id, int n) { asm volatile("bar.arrive %0, %1;" ::"r"(id), "r"(n) : "memory"); }
#define WG_FENCE() asm volatile("wgmma.fence.sync.aligned;" ::: "memory")
#define WG_COMMIT() asm volatile("wgmma.commit_group.sync.aligned;" ::: "memory")
#define WG_WAIT(n) asm volatile("wgmma.wait_group.sync.aligned %0;" ::"n"(n) : "memory")
__device__ __forceinline__ uint64_t mkdesc(uint32_t addr, uint32_t lbo, uint32_t sbo, uint32_t sw) {
  return (uint64_t)((addr & 0x3FFFF) >> 4) | ((uint64_t)(lbo >> 4) << 16) | ((uint64_t)(sbo >> 4) << 32) |
         ((uint64_t)sw << 62);
}
template <int N> __device__ __forceinline__ void fence_regs(float (&r)[N]) {
#pragma unroll
  for (int i = 0; i < N; i++) asm volatile("" : "+f"(r[i])::"memory");
}
__device__ __forceinline__ uint32_t pack_bf16(float lo, float hi) {
  uint32_t r;
  asm("cvt.rn.bf16x2.f32 %0, %1, %2;" : "=r"(r) : "f"(hi), "f"(lo));
  return r;
}
__device__ __forceinline__ float bf_lo(uint32_t v) { return __uint_as_float(v << 16); }
__device__ __forceinline__ float bf_hi(uint32_t v) { return __uint_as_float(v & 0xffff0000u); }
__device__ __forceinline__ float ex2(float x) {
  float y;
  asm("ex2.approx.ftz.f32 %0, %1;" : "=f"(y) : "f"(x));
  return y;
}
__device__ __forceinline__ uint4 ldg_nc(const void* p) {
  uint4 v;
  asm volatile("ld.global.nc.L1::no_allocate.v4.u32 {%0, %1, %2, %3}, [%4];"
               : "=r"(v.x), "=r"(v.y), "=r"(v.z), "=r"(v.w) : "l"(p));
  return v;
}

__device__ __forceinline__ uint4 ld_relaxed(const uint4* p) {
  uint64_t a, b;
  asm volatile("ld.relaxed.gpu.global.v2.u64 {%0, %1}, [%2];" : "=l"(a), "=l"(b) : "l"(p) : "memory");
  return make_uint4((uint32_t)a, (uint32_t)(a >> 32), (uint32_t)b, (uint32_t)(b >> 32));
}
__device__ __forceinline__ void st_relaxed(uint4* p, float x, float y, uint32_t tag) {
  const uint64_t a = ((uint64_t)tag << 32) | __float_as_uint(x), b = ((uint64_t)tag << 32) | __float_as_uint(y);
  asm volatile("st.relaxed.gpu.global.v2.u64 [%0], {%1, %2};" ::"l"(p), "l"(a), "l"(b) : "memory");
}
__device__ __forceinline__ void tma3d(uint32_t dst, const CUtensorMap* m, int c1, int c2, uint32_t bar) {
  asm volatile("cp.async.bulk.tensor.3d.shared::cluster.global.mbarrier::complete_tx::bytes [%0], [%1, {%3, %4, %5}], [%2];"
               ::"r"(dst), "l"(m), "r"(bar), "r"(0), "r"(c1), "r"(c2) : "memory");
}
#define ACC8(a, v) do { a[0] += bf_lo(v.x); a[1] += bf_hi(v.x); a[2] += bf_lo(v.y); a[3] += bf_hi(v.y); \
                        a[4] += bf_lo(v.z); a[5] += bf_hi(v.z); a[6] += bf_lo(v.w); a[7] += bf_hi(v.w); } while (0)

__device__ __forceinline__ void wgmma_ss_n240(float (&d)[120], uint64_t da, uint64_t db, int sd) {
  asm volatile("{\n.reg .pred p;\nsetp.ne.b32 p, %122, 0;\n"
      "wgmma.mma_async.sync.aligned.m64n240k16.f32.bf16.bf16 {"
      "%0, %1, %2, %3, %4, %5, %6, %7, %8, %9, %10, %11, %12, %13, %14, %15, "
      "%16, %17, %18, %19, %20, %21, %22, %23, %24, %25, %26, %27, %28, %29, %30, %31, "
      "%32, %33, %34, %35, %36, %37, %38, %39, %40, %41, %42, %43, %44, %45, %46, %47, "
      "%48, %49, %50, %51, %52, %53, %54, %55, %56, %57, %58, %59, %60, %61, %62, %63, "
      "%64, %65, %66, %67, %68, %69, %70, %71, %72, %73, %74, %75, %76, %77, %78, %79, "
      "%80, %81, %82, %83, %84, %85, %86, %87, %88, %89, %90, %91, %92, %93, %94, %95, "
      "%96, %97, %98, %99, %100, %101, %102, %103, %104, %105, %106, %107, %108, %109, %110, %111, "
      "%112, %113, %114, %115, %116, %117, %118, %119"
      "}, %120, %121, p, 1, 1, 0, 1;\n}\n"
    : "+f"(d[0]), "+f"(d[1]), "+f"(d[2]), "+f"(d[3]), "+f"(d[4]), "+f"(d[5]), "+f"(d[6]), "+f"(d[7]),
      "+f"(d[8]), "+f"(d[9]), "+f"(d[10]), "+f"(d[11]), "+f"(d[12]), "+f"(d[13]), "+f"(d[14]), "+f"(d[15]),
      "+f"(d[16]), "+f"(d[17]), "+f"(d[18]), "+f"(d[19]), "+f"(d[20]), "+f"(d[21]), "+f"(d[22]), "+f"(d[23]),
      "+f"(d[24]), "+f"(d[25]), "+f"(d[26]), "+f"(d[27]), "+f"(d[28]), "+f"(d[29]), "+f"(d[30]), "+f"(d[31]),
      "+f"(d[32]), "+f"(d[33]), "+f"(d[34]), "+f"(d[35]), "+f"(d[36]), "+f"(d[37]), "+f"(d[38]), "+f"(d[39]),
      "+f"(d[40]), "+f"(d[41]), "+f"(d[42]), "+f"(d[43]), "+f"(d[44]), "+f"(d[45]), "+f"(d[46]), "+f"(d[47]),
      "+f"(d[48]), "+f"(d[49]), "+f"(d[50]), "+f"(d[51]), "+f"(d[52]), "+f"(d[53]), "+f"(d[54]), "+f"(d[55]),
      "+f"(d[56]), "+f"(d[57]), "+f"(d[58]), "+f"(d[59]), "+f"(d[60]), "+f"(d[61]), "+f"(d[62]), "+f"(d[63]),
      "+f"(d[64]), "+f"(d[65]), "+f"(d[66]), "+f"(d[67]), "+f"(d[68]), "+f"(d[69]), "+f"(d[70]), "+f"(d[71]),
      "+f"(d[72]), "+f"(d[73]), "+f"(d[74]), "+f"(d[75]), "+f"(d[76]), "+f"(d[77]), "+f"(d[78]), "+f"(d[79]),
      "+f"(d[80]), "+f"(d[81]), "+f"(d[82]), "+f"(d[83]), "+f"(d[84]), "+f"(d[85]), "+f"(d[86]), "+f"(d[87]),
      "+f"(d[88]), "+f"(d[89]), "+f"(d[90]), "+f"(d[91]), "+f"(d[92]), "+f"(d[93]), "+f"(d[94]), "+f"(d[95]),
      "+f"(d[96]), "+f"(d[97]), "+f"(d[98]), "+f"(d[99]), "+f"(d[100]), "+f"(d[101]), "+f"(d[102]), "+f"(d[103]),
      "+f"(d[104]), "+f"(d[105]), "+f"(d[106]), "+f"(d[107]), "+f"(d[108]), "+f"(d[109]), "+f"(d[110]), "+f"(d[111]),
      "+f"(d[112]), "+f"(d[113]), "+f"(d[114]), "+f"(d[115]), "+f"(d[116]), "+f"(d[117]), "+f"(d[118]), "+f"(d[119])
    : "l"(da), "l"(db), "r"(sd));
}
__device__ __forceinline__ void wgmma_ss_n216(float (&d)[108], uint64_t da, uint64_t db, int sd) {
  asm volatile("{\n.reg .pred p;\nsetp.ne.b32 p, %110, 0;\n"
      "wgmma.mma_async.sync.aligned.m64n216k16.f32.bf16.bf16 {"
      "%0, %1, %2, %3, %4, %5, %6, %7, %8, %9, %10, %11, %12, %13, %14, %15, "
      "%16, %17, %18, %19, %20, %21, %22, %23, %24, %25, %26, %27, %28, %29, %30, %31, "
      "%32, %33, %34, %35, %36, %37, %38, %39, %40, %41, %42, %43, %44, %45, %46, %47, "
      "%48, %49, %50, %51, %52, %53, %54, %55, %56, %57, %58, %59, %60, %61, %62, %63, "
      "%64, %65, %66, %67, %68, %69, %70, %71, %72, %73, %74, %75, %76, %77, %78, %79, "
      "%80, %81, %82, %83, %84, %85, %86, %87, %88, %89, %90, %91, %92, %93, %94, %95, "
      "%96, %97, %98, %99, %100, %101, %102, %103, %104, %105, %106, %107"
      "}, %108, %109, p, 1, 1, 0, 1;\n}\n"
    : "+f"(d[0]), "+f"(d[1]), "+f"(d[2]), "+f"(d[3]), "+f"(d[4]), "+f"(d[5]), "+f"(d[6]), "+f"(d[7]),
      "+f"(d[8]), "+f"(d[9]), "+f"(d[10]), "+f"(d[11]), "+f"(d[12]), "+f"(d[13]), "+f"(d[14]), "+f"(d[15]),
      "+f"(d[16]), "+f"(d[17]), "+f"(d[18]), "+f"(d[19]), "+f"(d[20]), "+f"(d[21]), "+f"(d[22]), "+f"(d[23]),
      "+f"(d[24]), "+f"(d[25]), "+f"(d[26]), "+f"(d[27]), "+f"(d[28]), "+f"(d[29]), "+f"(d[30]), "+f"(d[31]),
      "+f"(d[32]), "+f"(d[33]), "+f"(d[34]), "+f"(d[35]), "+f"(d[36]), "+f"(d[37]), "+f"(d[38]), "+f"(d[39]),
      "+f"(d[40]), "+f"(d[41]), "+f"(d[42]), "+f"(d[43]), "+f"(d[44]), "+f"(d[45]), "+f"(d[46]), "+f"(d[47]),
      "+f"(d[48]), "+f"(d[49]), "+f"(d[50]), "+f"(d[51]), "+f"(d[52]), "+f"(d[53]), "+f"(d[54]), "+f"(d[55]),
      "+f"(d[56]), "+f"(d[57]), "+f"(d[58]), "+f"(d[59]), "+f"(d[60]), "+f"(d[61]), "+f"(d[62]), "+f"(d[63]),
      "+f"(d[64]), "+f"(d[65]), "+f"(d[66]), "+f"(d[67]), "+f"(d[68]), "+f"(d[69]), "+f"(d[70]), "+f"(d[71]),
      "+f"(d[72]), "+f"(d[73]), "+f"(d[74]), "+f"(d[75]), "+f"(d[76]), "+f"(d[77]), "+f"(d[78]), "+f"(d[79]),
      "+f"(d[80]), "+f"(d[81]), "+f"(d[82]), "+f"(d[83]), "+f"(d[84]), "+f"(d[85]), "+f"(d[86]), "+f"(d[87]),
      "+f"(d[88]), "+f"(d[89]), "+f"(d[90]), "+f"(d[91]), "+f"(d[92]), "+f"(d[93]), "+f"(d[94]), "+f"(d[95]),
      "+f"(d[96]), "+f"(d[97]), "+f"(d[98]), "+f"(d[99]), "+f"(d[100]), "+f"(d[101]), "+f"(d[102]), "+f"(d[103]),
      "+f"(d[104]), "+f"(d[105]), "+f"(d[106]), "+f"(d[107])
    : "l"(da), "l"(db), "r"(sd));
}
__device__ __forceinline__ void wgmma_ss_n168(float (&d)[84], uint64_t da, uint64_t db, int sd) {
  asm volatile("{\n.reg .pred p;\nsetp.ne.b32 p, %86, 0;\n"
      "wgmma.mma_async.sync.aligned.m64n168k16.f32.bf16.bf16 {"
      "%0, %1, %2, %3, %4, %5, %6, %7, %8, %9, %10, %11, %12, %13, %14, %15, "
      "%16, %17, %18, %19, %20, %21, %22, %23, %24, %25, %26, %27, %28, %29, %30, %31, "
      "%32, %33, %34, %35, %36, %37, %38, %39, %40, %41, %42, %43, %44, %45, %46, %47, "
      "%48, %49, %50, %51, %52, %53, %54, %55, %56, %57, %58, %59, %60, %61, %62, %63, "
      "%64, %65, %66, %67, %68, %69, %70, %71, %72, %73, %74, %75, %76, %77, %78, %79, "
      "%80, %81, %82, %83"
      "}, %84, %85, p, 1, 1, 0, 1;\n}\n"
    : "+f"(d[0]), "+f"(d[1]), "+f"(d[2]), "+f"(d[3]), "+f"(d[4]), "+f"(d[5]), "+f"(d[6]), "+f"(d[7]),
      "+f"(d[8]), "+f"(d[9]), "+f"(d[10]), "+f"(d[11]), "+f"(d[12]), "+f"(d[13]), "+f"(d[14]), "+f"(d[15]),
      "+f"(d[16]), "+f"(d[17]), "+f"(d[18]), "+f"(d[19]), "+f"(d[20]), "+f"(d[21]), "+f"(d[22]), "+f"(d[23]),
      "+f"(d[24]), "+f"(d[25]), "+f"(d[26]), "+f"(d[27]), "+f"(d[28]), "+f"(d[29]), "+f"(d[30]), "+f"(d[31]),
      "+f"(d[32]), "+f"(d[33]), "+f"(d[34]), "+f"(d[35]), "+f"(d[36]), "+f"(d[37]), "+f"(d[38]), "+f"(d[39]),
      "+f"(d[40]), "+f"(d[41]), "+f"(d[42]), "+f"(d[43]), "+f"(d[44]), "+f"(d[45]), "+f"(d[46]), "+f"(d[47]),
      "+f"(d[48]), "+f"(d[49]), "+f"(d[50]), "+f"(d[51]), "+f"(d[52]), "+f"(d[53]), "+f"(d[54]), "+f"(d[55]),
      "+f"(d[56]), "+f"(d[57]), "+f"(d[58]), "+f"(d[59]), "+f"(d[60]), "+f"(d[61]), "+f"(d[62]), "+f"(d[63]),
      "+f"(d[64]), "+f"(d[65]), "+f"(d[66]), "+f"(d[67]), "+f"(d[68]), "+f"(d[69]), "+f"(d[70]), "+f"(d[71]),
      "+f"(d[72]), "+f"(d[73]), "+f"(d[74]), "+f"(d[75]), "+f"(d[76]), "+f"(d[77]), "+f"(d[78]), "+f"(d[79]),
      "+f"(d[80]), "+f"(d[81]), "+f"(d[82]), "+f"(d[83])
    : "l"(da), "l"(db), "r"(sd));
}
__device__ __forceinline__ void wgmma_ss_n160(float (&d)[80], uint64_t da, uint64_t db, int sd) {
  asm volatile("{\n.reg .pred p;\nsetp.ne.b32 p, %82, 0;\n"
      "wgmma.mma_async.sync.aligned.m64n160k16.f32.bf16.bf16 {"
      "%0, %1, %2, %3, %4, %5, %6, %7, %8, %9, %10, %11, %12, %13, %14, %15, "
      "%16, %17, %18, %19, %20, %21, %22, %23, %24, %25, %26, %27, %28, %29, %30, %31, "
      "%32, %33, %34, %35, %36, %37, %38, %39, %40, %41, %42, %43, %44, %45, %46, %47, "
      "%48, %49, %50, %51, %52, %53, %54, %55, %56, %57, %58, %59, %60, %61, %62, %63, "
      "%64, %65, %66, %67, %68, %69, %70, %71, %72, %73, %74, %75, %76, %77, %78, %79"
      "}, %80, %81, p, 1, 1, 0, 1;\n}\n"
    : "+f"(d[0]), "+f"(d[1]), "+f"(d[2]), "+f"(d[3]), "+f"(d[4]), "+f"(d[5]), "+f"(d[6]), "+f"(d[7]),
      "+f"(d[8]), "+f"(d[9]), "+f"(d[10]), "+f"(d[11]), "+f"(d[12]), "+f"(d[13]), "+f"(d[14]), "+f"(d[15]),
      "+f"(d[16]), "+f"(d[17]), "+f"(d[18]), "+f"(d[19]), "+f"(d[20]), "+f"(d[21]), "+f"(d[22]), "+f"(d[23]),
      "+f"(d[24]), "+f"(d[25]), "+f"(d[26]), "+f"(d[27]), "+f"(d[28]), "+f"(d[29]), "+f"(d[30]), "+f"(d[31]),
      "+f"(d[32]), "+f"(d[33]), "+f"(d[34]), "+f"(d[35]), "+f"(d[36]), "+f"(d[37]), "+f"(d[38]), "+f"(d[39]),
      "+f"(d[40]), "+f"(d[41]), "+f"(d[42]), "+f"(d[43]), "+f"(d[44]), "+f"(d[45]), "+f"(d[46]), "+f"(d[47]),
      "+f"(d[48]), "+f"(d[49]), "+f"(d[50]), "+f"(d[51]), "+f"(d[52]), "+f"(d[53]), "+f"(d[54]), "+f"(d[55]),
      "+f"(d[56]), "+f"(d[57]), "+f"(d[58]), "+f"(d[59]), "+f"(d[60]), "+f"(d[61]), "+f"(d[62]), "+f"(d[63]),
      "+f"(d[64]), "+f"(d[65]), "+f"(d[66]), "+f"(d[67]), "+f"(d[68]), "+f"(d[69]), "+f"(d[70]), "+f"(d[71]),
      "+f"(d[72]), "+f"(d[73]), "+f"(d[74]), "+f"(d[75]), "+f"(d[76]), "+f"(d[77]), "+f"(d[78]), "+f"(d[79])
    : "l"(da), "l"(db), "r"(sd));
}
__device__ __forceinline__ void wgmma_ss_n88(float (&d)[44], uint64_t da, uint64_t db, int sd) {
  asm volatile("{\n.reg .pred p;\nsetp.ne.b32 p, %46, 0;\n"
      "wgmma.mma_async.sync.aligned.m64n88k16.f32.bf16.bf16 {"
      "%0, %1, %2, %3, %4, %5, %6, %7, %8, %9, %10, %11, %12, %13, %14, %15, "
      "%16, %17, %18, %19, %20, %21, %22, %23, %24, %25, %26, %27, %28, %29, %30, %31, "
      "%32, %33, %34, %35, %36, %37, %38, %39, %40, %41, %42, %43"
      "}, %44, %45, p, 1, 1, 0, 1;\n}\n"
    : "+f"(d[0]), "+f"(d[1]), "+f"(d[2]), "+f"(d[3]), "+f"(d[4]), "+f"(d[5]), "+f"(d[6]), "+f"(d[7]),
      "+f"(d[8]), "+f"(d[9]), "+f"(d[10]), "+f"(d[11]), "+f"(d[12]), "+f"(d[13]), "+f"(d[14]), "+f"(d[15]),
      "+f"(d[16]), "+f"(d[17]), "+f"(d[18]), "+f"(d[19]), "+f"(d[20]), "+f"(d[21]), "+f"(d[22]), "+f"(d[23]),
      "+f"(d[24]), "+f"(d[25]), "+f"(d[26]), "+f"(d[27]), "+f"(d[28]), "+f"(d[29]), "+f"(d[30]), "+f"(d[31]),
      "+f"(d[32]), "+f"(d[33]), "+f"(d[34]), "+f"(d[35]), "+f"(d[36]), "+f"(d[37]), "+f"(d[38]), "+f"(d[39]),
      "+f"(d[40]), "+f"(d[41]), "+f"(d[42]), "+f"(d[43])
    : "l"(da), "l"(db), "r"(sd));
}
__device__ __forceinline__ void wgmma_ss_n80(float (&d)[40], uint64_t da, uint64_t db, int sd) {
  asm volatile("{\n.reg .pred p;\nsetp.ne.b32 p, %42, 0;\n"
      "wgmma.mma_async.sync.aligned.m64n80k16.f32.bf16.bf16 {"
      "%0, %1, %2, %3, %4, %5, %6, %7, %8, %9, %10, %11, %12, %13, %14, %15, "
      "%16, %17, %18, %19, %20, %21, %22, %23, %24, %25, %26, %27, %28, %29, %30, %31, "
      "%32, %33, %34, %35, %36, %37, %38, %39"
      "}, %40, %41, p, 1, 1, 0, 1;\n}\n"
    : "+f"(d[0]), "+f"(d[1]), "+f"(d[2]), "+f"(d[3]), "+f"(d[4]), "+f"(d[5]), "+f"(d[6]), "+f"(d[7]),
      "+f"(d[8]), "+f"(d[9]), "+f"(d[10]), "+f"(d[11]), "+f"(d[12]), "+f"(d[13]), "+f"(d[14]), "+f"(d[15]),
      "+f"(d[16]), "+f"(d[17]), "+f"(d[18]), "+f"(d[19]), "+f"(d[20]), "+f"(d[21]), "+f"(d[22]), "+f"(d[23]),
      "+f"(d[24]), "+f"(d[25]), "+f"(d[26]), "+f"(d[27]), "+f"(d[28]), "+f"(d[29]), "+f"(d[30]), "+f"(d[31]),
      "+f"(d[32]), "+f"(d[33]), "+f"(d[34]), "+f"(d[35]), "+f"(d[36]), "+f"(d[37]), "+f"(d[38]), "+f"(d[39])
    : "l"(da), "l"(db), "r"(sd));
}
__device__ __forceinline__ void wgmma_rs_n128(float (&d)[64], uint32_t a0, uint32_t a1, uint32_t a2, uint32_t a3,
                                  uint64_t db, int sd) {
  asm volatile("{\n.reg .pred p;\nsetp.ne.b32 p, %69, 0;\n"
      "wgmma.mma_async.sync.aligned.m64n128k16.f32.bf16.bf16 {"
      "%0, %1, %2, %3, %4, %5, %6, %7, %8, %9, %10, %11, %12, %13, %14, %15, "
      "%16, %17, %18, %19, %20, %21, %22, %23, %24, %25, %26, %27, %28, %29, %30, %31, "
      "%32, %33, %34, %35, %36, %37, %38, %39, %40, %41, %42, %43, %44, %45, %46, %47, "
      "%48, %49, %50, %51, %52, %53, %54, %55, %56, %57, %58, %59, %60, %61, %62, %63"
      "}, {%64, %65, %66, %67}, %68, p, 1, 1, 0;\n}\n"
    : "+f"(d[0]), "+f"(d[1]), "+f"(d[2]), "+f"(d[3]), "+f"(d[4]), "+f"(d[5]), "+f"(d[6]), "+f"(d[7]),
      "+f"(d[8]), "+f"(d[9]), "+f"(d[10]), "+f"(d[11]), "+f"(d[12]), "+f"(d[13]), "+f"(d[14]), "+f"(d[15]),
      "+f"(d[16]), "+f"(d[17]), "+f"(d[18]), "+f"(d[19]), "+f"(d[20]), "+f"(d[21]), "+f"(d[22]), "+f"(d[23]),
      "+f"(d[24]), "+f"(d[25]), "+f"(d[26]), "+f"(d[27]), "+f"(d[28]), "+f"(d[29]), "+f"(d[30]), "+f"(d[31]),
      "+f"(d[32]), "+f"(d[33]), "+f"(d[34]), "+f"(d[35]), "+f"(d[36]), "+f"(d[37]), "+f"(d[38]), "+f"(d[39]),
      "+f"(d[40]), "+f"(d[41]), "+f"(d[42]), "+f"(d[43]), "+f"(d[44]), "+f"(d[45]), "+f"(d[46]), "+f"(d[47]),
      "+f"(d[48]), "+f"(d[49]), "+f"(d[50]), "+f"(d[51]), "+f"(d[52]), "+f"(d[53]), "+f"(d[54]), "+f"(d[55]),
      "+f"(d[56]), "+f"(d[57]), "+f"(d[58]), "+f"(d[59]), "+f"(d[60]), "+f"(d[61]), "+f"(d[62]), "+f"(d[63])
    : "r"(a0), "r"(a1), "r"(a2), "r"(a3), "l"(db), "r"(sd));
}
__device__ __forceinline__ void wgmma_rs_n24(float (&d)[12], uint32_t a0, uint32_t a1, uint32_t a2, uint32_t a3,
                                  uint64_t db, int sd) {
  asm volatile("{\n.reg .pred p;\nsetp.ne.b32 p, %17, 0;\n"
      "wgmma.mma_async.sync.aligned.m64n24k16.f32.bf16.bf16 {"
      "%0, %1, %2, %3, %4, %5, %6, %7, %8, %9, %10, %11"
      "}, {%12, %13, %14, %15}, %16, p, 1, 1, 1;\n}\n"
    : "+f"(d[0]), "+f"(d[1]), "+f"(d[2]), "+f"(d[3]), "+f"(d[4]), "+f"(d[5]), "+f"(d[6]), "+f"(d[7]),
      "+f"(d[8]), "+f"(d[9]), "+f"(d[10]), "+f"(d[11])
    : "r"(a0), "r"(a1), "r"(a2), "r"(a3), "l"(db), "r"(sd));
}

constexpr int K1_ST = 4, K1_STAGE = 49152;
constexpr int K1_SMEM = K1_ST * K1_STAGE + 1024   + 1024   + 3072   + 128;

__global__ void __cluster_dims__(2, 1, 1) __launch_bounds__(384, 1)
k1_qkv(const __grid_constant__ CUtensorMap tmx, const __grid_constant__ CUtensorMap tmw,
       const bf16* __restrict__ x, const bf16* __restrict__ w, const bf16* __restrict__ wo) {
  extern __shared__ __align__(1024) uint8_t sm[];
  float* cs = (float*)(sm + K1_ST * K1_STAGE);
  float2* rowab = (float2*)(sm + K1_ST * K1_STAGE + 1024);
  float* red = (float*)(sm + K1_ST * K1_STAGE + 2048);
  const uint32_t sbase = smem_u32(sm);
  const uint32_t fullb = sbase + K1_ST * K1_STAGE + 5120, emptyb = fullb + 8 * K1_ST;
  const int tid = threadIdx.x, lane = tid & 31;
  const int warp = __shfl_sync(~0u, tid >> 5, 0);
  const int rank = blockIdx.x & 1, cl = blockIdx.x >> 1;
  const int n = cl & 7, m = (cl >> 3) * 2 + rank;
  if (tid == 0) STAMP(0, 0);

  if (warp == 0) {
    if (lane == 0) {
      prefetch_map(&tmx); prefetch_map(&tmw);
      for (int i = 0; i < K1_ST; i++) { mbar_init(fullb + 8 * i, 1); mbar_init(emptyb + 8 * i, 4); }
      asm volatile("fence.mbarrier_init.release.cluster;" ::: "memory");
    }
    __syncwarp();
    cluster_arrive();
    if (lane == 0) {
      for (int kt = 0; kt < K1_ST; kt++) mbar_expect(fullb + 8 * kt, K1_STAGE);
      tma2d(sbase, &tmx, 0, m * 128, fullb);
    }
    __syncwarp();
    cluster_wait();
    if (tid == 0) STAMP(5, 3);
    if (lane == 0) {
#pragma unroll
      for (int j = 0; j < 4; j++) tma2d_mc(sbase + 16384 + rank * 16384 + j * 4096, &tmw, n * 240 + rank * 128 + j * 32, 0, fullb);
    }
    __syncwarp();
    bar_arrive(4, 384);
    if (lane == 0) {
      for (int kt = 1; kt < 10; kt++) {
        const int s = kt % K1_ST;
        const uint32_t sa = sbase + s * K1_STAGE, sb = sa + 16384 + rank * 16384;
        if (kt >= K1_ST) {
          mbar_wait(emptyb + 8 * s, ((kt / K1_ST) - 1) & 1);
          mbar_expect(fullb + 8 * s, K1_STAGE);
        }
        tma2d(sa, &tmx, kt * 64, m * 128, fullb + 8 * s);
#pragma unroll
        for (int j = 0; j < 4; j++) tma2d_mc(sb + j * 4096, &tmw, n * 240 + rank * 128 + j * 32, kt * 64, fullb + 8 * s);
        if (kt == K1_ST - 1) pdl_trigger();
      }
    }
    __syncwarp();
    cluster_arrive();
  } else if (warp < 4) {
    cluster_arrive();
    const int w3 = warp - 1, t96 = tid - 32;
    const uint32_t tag = __ldcg(&g_epoch) + 1;
    bar_sync(4, 384);
    {
      uint4 xv[6][3], wv[14];
#pragma unroll
      for (int i = 0; i < 6; i++) {
        const bf16* xr = x + (size_t)(m * 128 + n * 16 + min(w3 + 3 * i, 15)) * D_ + lane * 8;
        xv[i][0] = ldg_nc(xr);
        xv[i][1] = ldg_nc(xr + 256);
        xv[i][2] = ldg_nc(xr + (lane < 16 ? 512 : 0));
      }
#pragma unroll
      for (int i = 0; i < 14; i++)
        wv[i] = ldg_nc(w + (size_t)(m * 40 + min(w3 + 3 * i, 39)) * 1920 + n * 240 + min(lane, 29) * 8);
#pragma unroll
      for (int i = 0; i < 6; i++) {
        float f[24];
#pragma unroll
        for (int k = 0; k < 3; k++) {
          const uint4 v = xv[i][k];
          f[8 * k + 0] = bf_lo(v.x); f[8 * k + 1] = bf_hi(v.x); f[8 * k + 2] = bf_lo(v.y); f[8 * k + 3] = bf_hi(v.y);
          f[8 * k + 4] = bf_lo(v.z); f[8 * k + 5] = bf_hi(v.z); f[8 * k + 6] = bf_lo(v.w); f[8 * k + 7] = bf_hi(v.w);
        }
        float s = 0.f, s2 = 0.f;
#pragma unroll
        for (int k = 0; k < 16; k++) s += f[k];
#pragma unroll
        for (int k = 16; k < 24; k++) s2 += f[k];
        if (lane < 16) s += s2;
#pragma unroll
        for (int o = 16; o; o >>= 1) s += __shfl_xor_sync(~0u, s, o);
        const float mean = s * (1.f / D_);
        float q = 0.f, q2 = 0.f;
#pragma unroll
        for (int k = 0; k < 16; k++) { float d = f[k] - mean; q = fmaf(d, d, q); }
#pragma unroll
        for (int k = 16; k < 24; k++) { float d = f[k] - mean; q2 = fmaf(d, d, q2); }
        if (lane < 16) q += q2;
#pragma unroll
        for (int o = 16; o; o >>= 1) q += __shfl_xor_sync(~0u, q, o);
        if (lane == 0 && w3 + 3 * i < 16)
          st_relaxed(&g_rowstat[m * 128 + n * 16 + w3 + 3 * i], rsqrtf(q * (1.f / D_) + 1e-5f), mean, tag);
      }
      float acc8[8];
#pragma unroll
      for (int i = 0; i < 8; i++) acc8[i] = 0.f;
#pragma unroll
      for (int i = 0; i < 14; i++)
        if (i < 13 || w3 == 0) ACC8(acc8, wv[i]);
      *(float4*)&red[w3 * 256 + lane * 8] = make_float4(acc8[0], acc8[1], acc8[2], acc8[3]);
      *(float4*)&red[w3 * 256 + lane * 8 + 4] = make_float4(acc8[4], acc8[5], acc8[6], acc8[7]);
    }
    bar_sync(1, 96);
    for (int i = t96; i < 120; i += 96) {
      const float2 p0 = *(const float2*)&red[i * 2], p1 = *(const float2*)&red[256 + i * 2], p2 = *(const float2*)&red[512 + i * 2];
      st_relaxed(&g_cpart[(m * 8 + n) * 128 + i], p0.x + p1.x + p2.x, p0.y + p1.y + p2.y, tag);
    }
    if (tid == 32) STAMP(5, 7);
    for (int i = t96; i < 128; i += 96) {
      uint32_t it = 0;
      while (true) {
        uint4 p[16];
        const uint4 st = ld_relaxed(&g_rowstat[m * 128 + i]);
#pragma unroll
        for (int k = 0; k < 16; k++) p[k] = ld_relaxed(&g_cpart[(k * 8 + n) * 128 + min(i, 119)]);
        bool ok = st.y == tag && st.w == tag;
        float s0 = 0.f, s1 = 0.f;
#pragma unroll
        for (int k = 0; k < 16; k++) {
          ok = ok && p[k].y == tag && p[k].w == tag;
          s0 += __uint_as_float(p[k].x); s1 += __uint_as_float(p[k].z);
        }
        if (ok) {
          *(float2*)&cs[i * 2] = make_float2(s0, s1);
          rowab[i] = make_float2(__uint_as_float(st.x), -__uint_as_float(st.x) * __uint_as_float(st.z));
          break;
        }
        if (++it > (1u << 20)) wait_timeout();
      }
    }
    __syncwarp();
    bar_arrive(2, 96 + 256);
    bar_sync(1, 96);
    if (tid == 32) STAMP(0, 5);
    {
      uint4 v[5];
      const int ck = min(t96, 79), nt = ck / 10;
#pragma unroll
      for (int i = 0; i < 5; i++) {
        const int k = blockIdx.x * 5 + i, pr = k / 40, r = k - pr * 40;
        v[i] = ldg_nc(wo + (size_t)(pr * 40 + (r < 16 ? r : (r < 32 ? r + 4 : (r < 36 ? r - 16 : r)))) * D_ + ck * 8);
      }
#pragma unroll
      for (int i = 0; i < 5; i++) {
        const int k = blockIdx.x * 5 + i;
        g_wo[((nt * 10 + (k >> 6)) * 10 + ck - nt * 10) * 64 + (k & 63)] = v[i];
        float t = ((bf_lo(v[i].x) + bf_hi(v[i].x)) + (bf_lo(v[i].y) + bf_hi(v[i].y))) +
                  ((bf_lo(v[i].z) + bf_hi(v[i].z)) + (bf_lo(v[i].w) + bf_hi(v[i].w)));
        if (t96 >= 80) t = 0.f;
#pragma unroll
        for (int o = 16; o; o >>= 1) t += __shfl_xor_sync(~0u, t, o);
        if (lane == 0) red[w3 * 8 + i] = t;
      }
      bar_sync(1, 96);
      if (t96 < 5) {
        const float mu = (red[t96] + red[8 + t96] + red[16 + t96]) * (1.f / D_);
        const float hi = bf_lo(pack_bf16(mu, 0.f));
        g_wm[blockIdx.x * 5 + t96] = make_uint4(pack_bf16(hi, mu - hi), 0u, 0u, 0u);
      }
    }
    if (tid == 32) STAMP(0, 7);
    __syncwarp();
    cluster_wait();
    cluster_arrive();
  } else {
    cluster_arrive();
    const int cw = warp - 4, wg = cw >> 2;
    bar_sync(4, 384);
    float acc[120];
    const uint64_t da0 = mkdesc(sbase + wg * 8192, 16, 1024, 1);
    const uint64_t db0 = mkdesc(sbase + 16384, 4096, 512, 2);
    cluster_wait();
#pragma unroll 1
    for (int kt = 0; kt < 10; kt++) {
      const int s = kt % K1_ST;
      mbar_wait(fullb + 8 * s, (kt / K1_ST) & 1);
      if (kt == 0 && tid == 128) STAMP(0, 1);
      const uint64_t da = da0 + s * (K1_STAGE >> 4), db = db0 + s * (K1_STAGE >> 4);
      WG_FENCE();
#pragma unroll
      for (int k = 0; k < 4; k++) wgmma_ss_n240(acc, da + k * 2, db + k * 64, (kt | k) != 0);
      WG_COMMIT();
      if (kt > 0) {
        WG_WAIT(1);
        if (kt - 1 + K1_ST < 10 && (tid & 127) < 2) mbar_arrive_cta(emptyb + 8 * ((kt - 1) % K1_ST), tid & 1);
      }
    }
    cluster_arrive();
    WG_WAIT(0);
    fence_regs(acc);
    if (tid == 128) STAMP(0, 2);
    bar_sync(2, 96 + 256);
    if (tid == 128) STAMP(0, 3);
    const int g = lane >> 2, c = lane & 3;
    const bool lo = c < 2;
    const float2 ab0 = rowab[cw * 16 + g], ab1 = rowab[cw * 16 + g + 8];
    const bool p0 = (POLY_MASK >> (cw * 2)) & 1, p1 = (POLY_MASK >> (cw * 2 + 1)) & 1;
    const uint32_t padq = c == 2 ? 0x3F803F80u : 0x00003F80u, padk = c == 2 ? 0x4A7A4B00u : 0x00004653u;
    const uint32_t padv = c == 2 ? 0x00003F80u : 0u;
    uint8_t* dst = (uint8_t*)g_qkv + (size_t)(n * 12) * HEAD_IMG + m * 6144 + lane * 4;
#pragma unroll
    for (int hp = 0; hp < 6; hp++) {
      const int sec = (n * 12 + hp * 2) >> 5;
      const float f0 = sec == 0 ? QSCALE : (sec == 1 && p0 ? 32768.f : 1.f), f1 = sec == 0 ? QSCALE : (sec == 1 && p1 ? 32768.f : 1.f);
      const uint32_t pad0 = sec == 0 ? padq : (sec == 2 ? padv : (p0 ? padk : 0u));
      const uint32_t pad1 = sec == 0 ? padq : (sec == 2 ? padv : (p1 ? padk : 0u));
      const float a0 = ab0.x * f0, b0 = ab0.y * f0, a1 = ab1.x * f1, b1 = ab1.y * f1;
      uint32_t u[5], v[5];
      float su[5], sv[5];
#pragma unroll
      for (int i = 0; i < 5; i++) {
        const int j = hp * 5 + i;
        const float2 t = *(const float2*)&cs[j * 8 + c * 2];
        const float x0 = fmaf(acc[4 * j], a0, b0 * t.x), x1 = fmaf(acc[4 * j + 1], a0, b0 * t.y);
        const float y0 = fmaf(acc[4 * j + 2], a1, b1 * t.x), y1 = fmaf(acc[4 * j + 3], a1, b1 * t.y);
        u[i] = pack_bf16(x0, x1); v[i] = pack_bf16(y0, y1);
        su[i] = fmaf(x0, x0, x1 * x1); sv[i] = fmaf(y0, y0, y1 * y1);
      }
      if (sec < 2) {
        const float r0 = (sec == 1 && p0) ? 9.313225746154785e-10f : 1.f, r1 = (sec == 1 && p1) ? 9.313225746154785e-10f : 1.f;
        float e0 = (su[0] + su[1] + (lo ? su[2] : 0.f)) * r0, e1 = (sv[0] + sv[1] + (lo ? sv[2] : 0.f)) * r1;
        float o0 = (su[3] + su[4] + (lo ? 0.f : su[2])) * r0, o1 = (sv[3] + sv[4] + (lo ? 0.f : sv[2])) * r1;
        e0 += __shfl_xor_sync(~0u, e0, 1); e1 += __shfl_xor_sync(~0u, e1, 1);
        o0 += __shfl_xor_sync(~0u, o0, 1); o1 += __shfl_xor_sync(~0u, o1, 1);
        e0 += __shfl_xor_sync(~0u, e0, 2); e1 += __shfl_xor_sync(~0u, e1, 2);
        o0 += __shfl_xor_sync(~0u, o0, 2); o1 += __shfl_xor_sync(~0u, o1, 2);
        const uint32_t em = __reduce_max_sync(~0u, max(__float_as_uint(e0), __float_as_uint(e1)));
        const uint32_t om = __reduce_max_sync(~0u, max(__float_as_uint(o0), __float_as_uint(o1)));
        if (lane < 2) g_nrm[(n * 12 + hp * 2 + lane) * 128 + m * 8 + cw] = __uint_as_float(lane ? om : em);
      }
      const int cst = sec == 1 ? 2048 : 128, gst = sec == 1 ? 128 : 384;
      uint8_t* pe = dst + (size_t)hp * 2 * HEAD_IMG + cw * 2 * gst;
      uint8_t* pf = pe + gst;
      *(uint32_t*)(pe) = u[0];       *(uint32_t*)(pf) = v[0];
      *(uint32_t*)(pe + cst) = u[1]; *(uint32_t*)(pf + cst) = v[1];
      *(uint32_t*)(pe + 2 * cst) = lo ? u[2] : pad0; *(uint32_t*)(pf + 2 * cst) = lo ? v[2] : pad1;
      *(uint32_t*)(pe + HEAD_IMG) = __shfl_xor_sync(~0u, lo ? u[3] : u[2], 2);
      *(uint32_t*)(pf + HEAD_IMG) = __shfl_xor_sync(~0u, lo ? v[3] : v[2], 2);
      *(uint32_t*)(pe + cst + HEAD_IMG) = __shfl_xor_sync(~0u, lo ? u[4] : u[3], 2);
      *(uint32_t*)(pf + cst + HEAD_IMG) = __shfl_xor_sync(~0u, lo ? v[4] : v[3], 2);
      const uint32_t tu = __shfl_xor_sync(~0u, u[4], 2), tv = __shfl_xor_sync(~0u, v[4], 2);
      *(uint32_t*)(pe + 2 * cst + HEAD_IMG) = lo ? tu : pad0; *(uint32_t*)(pf + 2 * cst + HEAD_IMG) = lo ? tv : pad1;
    }
    if (tid == 128) STAMP(0, 4);
  }
  cluster_wait();
  if (tid == 128) STAMP(0, 6);
}

constexpr int K2_SMEM = 2 * HEAD_IMG + 2 * 6144 + 2 * 10240 + 256;

__device__ __forceinline__ uint64_t desc64(uint32_t lo, uint32_t hi) {
  uint64_t d;
  asm("mov.b64 %0, {%1, %2};" : "=l"(d) : "r"(lo), "r"(hi));
  return d;
}
__device__ __forceinline__ uint32_t exp_pair(bool poly, float a, float b, uint32_t mk) {
  if (poly) {
    const uint32_t pk = __byte_perm(__float_as_uint(a), __float_as_uint(b), 0x6521);
    uint32_t m, q;
    asm("lop3.b32 %0, %1, %2, 0x3f803f80, 0xEA;" : "=r"(m) : "r"(pk), "r"(mk));
    asm("fma.rn.bf16x2 %0, %1, %1, %2;" : "=r"(q) : "r"(m), "r"(0x40014001u));
    return pk - m + q;
  }
  return pack_bf16(ex2(a), ex2(b));
}
#define PV_GR 2
__device__ __forceinline__ void exp_pv(const float (&s)[64], float (&o)[12], uint64_t dv, uint32_t mk) {
#pragma unroll
  for (int k0 = 0; k0 < 8; k0 += PV_GR) {
    uint32_t p[4 * PV_GR];
#pragma unroll
    for (int i = 0; i < 4 * PV_GR; i++)
      p[i] = exp_pair((POLY_MASK >> (k0 * 2 + i / 2)) & 1, s[k0 * 8 + 2 * i], s[k0 * 8 + 2 * i + 1], mk);
    WG_FENCE();
#pragma unroll
    for (int k = 0; k < PV_GR; k++)
      wgmma_rs_n24(o, p[4 * k], p[4 * k + 1], p[4 * k + 2], p[4 * k + 3], dv + (k0 + k) * 48, 1);
  }
}
__device__ __forceinline__ void load_q(uint32_t (&q)[6], const uint8_t* p) {
  q[0] = __ldcg((const uint32_t*)p);         q[1] = __ldcg((const uint32_t*)(p + 384));
  q[2] = __ldcg((const uint32_t*)(p + 128)); q[3] = __ldcg((const uint32_t*)(p + 512));
  q[4] = __ldcg((const uint32_t*)(p + 256)); q[5] = __ldcg((const uint32_t*)(p + 640));
}
__device__ __forceinline__ float rcp(float x) {
  float y;
  asm("rcp.approx.ftz.f32 %0, %1;" : "=f"(y) : "f"(x));
  return y;
}
__device__ __forceinline__ int img_off(int chunk) { return (chunk >> 3) * 16384 + (chunk & 7) * 128; }
__device__ __forceinline__ void store_o(const float (&o)[12], int tile) {
  int tid, bid;
  asm volatile("mov.u32 %0, %%tid.x;" : "=r"(tid));
  asm volatile("mov.u32 %0, %%ctaid.x;" : "=r"(bid));
  const int head = bid >> 2;
  uint8_t* dst = (uint8_t*)g_o + ((bid & 3) * 4 + (tile >> 1)) * 163840 + (tile & 1) * 8192 + ((tid >> 5) & 3) * 2048 + (tid & 31) * 4;
  const int oc = (head >> 1) * 5 + (head & 1) * 2;
  const int o0 = img_off(oc), o1 = img_off(oc + 1), o2 = img_off((head >> 1) * 5 + 4) + (head & 1) * 8;
  const float i0 = rcp(__shfl_sync(~0u, o[8], 2, 4)), i1 = rcp(__shfl_sync(~0u, o[10], 2, 4));
  *(uint32_t*)(dst + o0) = pack_bf16(o[0] * i0, o[1] * i0); *(uint32_t*)(dst + o0 + 1024) = pack_bf16(o[2] * i1, o[3] * i1);
  *(uint32_t*)(dst + o1) = pack_bf16(o[4] * i0, o[5] * i0); *(uint32_t*)(dst + o1 + 1024) = pack_bf16(o[6] * i1, o[7] * i1);
  if ((tid & 3) < 2) {
    *(uint32_t*)(dst + o2) = pack_bf16(o[8] * i0, o[9] * i0);
    *(uint32_t*)(dst + o2 + 1024) = pack_bf16(o[10] * i1, o[11] * i1);
  }
}

__global__ void __launch_bounds__(512, 1)
k2_attn(const __grid_constant__ CUtensorMap tmg, const __grid_constant__ CUtensorMap tmu,
        const __grid_constant__ CUtensorMap tmd, uint32_t mk) {
  extern __shared__ __align__(1024) uint8_t sm[];
  const uint32_t sbase = smem_u32(sm);
  float* part = (float*)(sm + 2 * HEAD_IMG);
  const uint32_t rbuf = sbase + 2 * HEAD_IMG + 2 * 6144;
  const uint32_t kvb = rbuf + 2 * 10240;
  const uint32_t partb = kvb + 128, rbar = kvb + 144;
  const int tid = threadIdx.x, lane = tid & 31;
  const int warp = __shfl_sync(~0u, tid >> 5, 0);
  const int head = blockIdx.x >> 2, qb = blockIdx.x & 3;

  if (tid == 0) STAMP(1, 0);
  if (tid == 0) {
    for (int i = 0; i < 16; i++) mbar_init(kvb + 8 * i, 1);
    mbar_init(partb, 128); mbar_init(partb + 8, 128); mbar_init(rbar, 1); mbar_init(rbar + 8, 1);
    asm volatile("fence.mbarrier_init.release.cluster;" ::: "memory");
  }
  __syncthreads();

  if (warp >= 12) {
    asm volatile("setmaxnreg.dec.sync.aligned.u32 32;");
    if (tid == 384) {
      pdl_wait();
      pdl_trigger();
      const uint8_t* kimg = (const uint8_t*)g_qkv + (size_t)(32 + head) * HEAD_IMG;
#pragma unroll 1
      for (int b = 0; b < 16; b++) {
        mbar_expect(kvb + 8 * b, 12288);
        bulk_ld(sbase + b * 6144, kimg + b * 6144, 6144, kvb + 8 * b);
        bulk_ld(sbase + HEAD_IMG + b * 6144, kimg + 32 * HEAD_IMG + b * 6144, 6144, kvb + 8 * b);
      }
      if (blockIdx.x == 0) g_epoch = g_epoch + 1;
      mbar_wait(kvb + 8 * 15, 0);
      uint8_t* pdst = nullptr;
      uint32_t pbytes = 0;
#pragma unroll 1
      for (int i = 0; i < 7; i++) {
        const int p = blockIdx.x + 128 * i;
        uint8_t* dst = nullptr;
        uint32_t bytes = 0;
        if (i < 6 && p < 696) {
          asm volatile("cp.async.bulk.wait_group.read 0;" ::: "memory");
          if (p < 480) {
            const int nk = p / 6, r = p - nk * 6, nt = nk / 10, kt = nk - nt * 10, up = r / 3;
            bytes = 9216;
            dst = (uint8_t*)g_wgu + (size_t)(nk * 54 + r * 9) * 1024;
            mbar_expect(rbar + 8 * (i & 1), bytes);
            tma3d(rbuf + (i & 1) * 10240, up ? &tmu : &tmg, kt * 64, nt * 27 + (r - up * 3) * 9, rbar + 8 * (i & 1));
          } else {
            const int nk = p - 480, nt = nk / 27, kt = nk - nt * 27;
            bytes = 10240;
            dst = (uint8_t*)g_wd + (size_t)nk * 10240;
            mbar_expect(rbar + 8 * (i & 1), bytes);
            tma3d(rbuf + (i & 1) * 10240, &tmd, kt * 64, nt * 10, rbar + 8 * (i & 1));
          }
        }
        if (pbytes) {
          mbar_wait(rbar + 8 * ((i - 1) & 1), ((i - 1) >> 1) & 1);
          bulk_st(pdst, rbuf + ((i - 1) & 1) * 10240, pbytes);
          asm volatile("cp.async.bulk.commit_group;" ::: "memory");
        }
        pdst = dst; pbytes = bytes;
      }
      asm volatile("cp.async.bulk.wait_group.read 0;" ::: "memory");
      STAMP(1, 6);
    }
  } else {
    asm volatile("setmaxnreg.inc.sync.aligned.u32 160;");
    const int wg = warp >> 2;
    const uint8_t* qthr = (const uint8_t*)g_qkv + (size_t)head * HEAD_IMG + qb * 64 * 384 + (warp & 3) * 768 + lane * 4;
    const uint32_t klo0 = ((sbase & 0x3FFFF) >> 4) | (128u << 16), vlo0 = (((sbase + HEAD_IMG) & 0x3FFFF) >> 4) | (24u << 16);
    constexpr int64_t KSTEP2 = 256 - (128 << 16);
    constexpr int64_t KV2K = 384 - (HEAD_IMG >> 4) + (104 << 16);
    const int nun = wg == 1 ? 4 : 3;
    uint32_t utile = wg == 0 ? 0x210u : (wg == 1 ? 0x4325u : 0x576u);
    uint32_t ubeg = wg == 0 ? 0u : (wg == 1 ? 0x00b0u : 0x600u);
    uint32_t ulen = wg == 0 ? 0x0b1010u : (wg == 1 ? 0x10100506u : 0x0a1010u);
    pdl_wait();
    if (tid == 0) STAMP(1, 1);
    uint32_t q[6];
    load_q(q, qthr + (utile & 15) * 3072);
    bool fast;
    {
      const float4 kn = __ldcg((const float4*)&g_nrm[(32 + head) * 128 + lane * 4]);
      const float qv = __ldcg(&g_nrm[head * 128 + qb * 32 + lane]);
      const uint32_t km = max(max(__float_as_uint(kn.x), __float_as_uint(kn.y)), max(__float_as_uint(kn.z), __float_as_uint(kn.w)));
      const float k2 = __uint_as_float(__reduce_max_sync(~0u, km)), q2 = __uint_as_float(__reduce_max_sync(~0u, __float_as_uint(qv)));
      fast = q2 * k2 <= 3400.f;
    }
    if (fast) {
#pragma unroll 1
      for (int u = 0; u < nun; u++) {
        const uint32_t b0 = ubeg & 15;
        const bool wt = u == 0 || (wg == 1 && u < 3);
        float s[64], o[12];
#pragma unroll
        for (int i = 0; i < 12; i++) o[i] = 0.f;
        uint32_t vlo = vlo0 + b0 * 384, kb = kvb + b0 * 8;
        const uint32_t vend = vlo + ((ulen & 255) - 1) * 384;
        if (wt) mbar_wait(kb, 0);
        fence_regs(o);
        WG_FENCE();
        wgmma_rs_n128(s, q[0], q[1], q[2], q[3], desc64(klo0 + b0 * 384, 8), 0);
        wgmma_rs_n128(s, q[4], q[5], 0, 0, desc64(klo0 + b0 * 384, 8) + KSTEP2, 1);
        WG_COMMIT();
#pragma unroll 1
        for (; vlo != vend; vlo += 384) {
          if (wt) { kb += 8; mbar_wait(kb, 0); }
          WG_WAIT(0);
          fence_regs(s); fence_regs(o);
          const uint64_t dv = desc64(vlo, 8);
          exp_pv(s, o, dv, mk);
          wgmma_rs_n128(s, q[0], q[1], q[2], q[3], dv + KV2K, 0);
          wgmma_rs_n128(s, q[4], q[5], 0, 0, dv + (KV2K + KSTEP2), 1);
          WG_COMMIT();
        }
        WG_WAIT(0);
        fence_regs(s); fence_regs(o);
        if (u + 1 < nun) load_q(q, qthr + ((utile >> 4) & 15) * 3072);
        exp_pv(s, o, desc64(vlo, 8), mk);
        WG_COMMIT();
        WG_WAIT(0);
        fence_regs(o);
        if (wg == 1 && u < 2) {
          float4* pp = (float4*)(part + u * 1536) + (tid & 127);
          pp[0] = make_float4(o[0], o[1], o[2], o[3]);
          pp[128] = make_float4(o[4], o[5], o[6], o[7]);
          pp[256] = make_float4(o[8], o[9], o[10], o[11]);
          mbar_arrive(partb + 8 * u);
        } else {
          if (wg != 1 && u == 2) {
            const int pi = wg == 0 ? 1 : 0;
            mbar_wait(partb + 8 * pi, 0);
            const float4* pp = (const float4*)(part + pi * 1536) + (tid & 127);
            const float4 x0 = pp[0], x1 = pp[128], x2 = pp[256];
            o[0] += x0.x; o[1] += x0.y; o[2] += x0.z; o[3] += x0.w; o[4] += x1.x; o[5] += x1.y;
            o[6] += x1.z; o[7] += x1.w; o[8] += x2.x; o[9] += x2.y; o[10] += x2.z; o[11] += x2.w;
          }
          store_o(o, utile & 15);
        }
        utile >>= 4; ubeg >>= 4; ulen >>= 8;
      }
      if ((tid & 127) == 0) STAMP(1, 3 + wg);
    } else {
#pragma unroll 1
      for (int tile = wg; tile < 8; tile += 3) {
        load_q(q, qthr + tile * 3072);
        if ((lane & 3) >= 2) { q[4] = 0; q[5] = 0; }
        float o[12], m0 = -INFINITY, m1 = -INFINITY;
#pragma unroll
        for (int i = 0; i < 12; i++) o[i] = 0.f;
#pragma unroll 1
        for (int b = 0; b < 16; b++) {
          float s[64];
          mbar_wait(kvb + 8 * b, 0);
          WG_FENCE();
          wgmma_rs_n128(s, q[0], q[1], q[2], q[3], desc64(klo0 + b * 384, 8), 0);
          wgmma_rs_n128(s, q[4], q[5], 0, 0, desc64(klo0 + b * 384, 8) + KSTEP2, 1);
          WG_COMMIT();
          WG_WAIT(0);
          fence_regs(s);
          float x0 = m0, x1 = m1;
#pragma unroll
          for (int j = 0; j < 16; j++) {
            if ((POLY_MASK >> j) & 1) {
#pragma unroll
              for (int i = 0; i < 4; i++) s[4 * j + i] *= (1.f / 32768.f);
            }
            x0 = fmaxf(x0, fmaxf(s[4 * j], s[4 * j + 1]));
            x1 = fmaxf(x1, fmaxf(s[4 * j + 2], s[4 * j + 3]));
          }
          x0 = fmaxf(x0, __shfl_xor_sync(~0u, x0, 1)); x0 = fmaxf(x0, __shfl_xor_sync(~0u, x0, 2));
          x1 = fmaxf(x1, __shfl_xor_sync(~0u, x1, 1)); x1 = fmaxf(x1, __shfl_xor_sync(~0u, x1, 2));
          const float al0 = ex2(m0 - x0), al1 = ex2(m1 - x1);
          m0 = x0; m1 = x1;
#pragma unroll
          for (int i = 0; i < 12; i++) o[i] *= (i & 2) ? al1 : al0;
          uint32_t p[32];
#pragma unroll
          for (int i = 0; i < 32; i++) {
            const float mm = (i & 1) ? m1 : m0;
            p[i] = pack_bf16(ex2(s[2 * i] - mm), ex2(s[2 * i + 1] - mm));
          }
          fence_regs(o);
          WG_FENCE();
#pragma unroll
          for (int k = 0; k < 8; k++)
            wgmma_rs_n24(o, p[4 * k], p[4 * k + 1], p[4 * k + 2], p[4 * k + 3], desc64(vlo0 + b * 384 + k * 48, 8), 1);
          WG_COMMIT();
          WG_WAIT(0);
          fence_regs(o);
        }
        store_o(o, tile);
      }
    }
  }
}

constexpr int K3_ST = 4, K3_STAGE = 37888;
constexpr int K3_SMEM = K3_ST * K3_STAGE + 45056 + 20480 + 256;

template <int N> struct Acc { float v[N]; };

template <int NB, int NK, bool FIRST>
__global__ void __cluster_dims__(2, 1, 1) __launch_bounds__(384, 1)
k3_proj(const __grid_constant__ CUtensorMap tmr, const uint4* __restrict__ aimg, const uint4* __restrict__ wimg) {
  constexpr int KT = 2 * NB + NK, EX = FIRST ? 1 : 0;
  extern __shared__ __align__(1024) uint8_t sm[];
  const uint32_t sbase = smem_u32(sm);
  uint8_t* xch = sm + K3_ST * K3_STAGE;
  uint8_t* stg = sm + K3_ST * K3_STAGE + 45056;
  const uint32_t fullb = smem_u32(stg) + 20480, emptyb = fullb + 8 * K3_ST, resb = emptyb + 8 * K3_ST, xchb = resb + 8;
  const int tid = threadIdx.x, lane = tid & 31;
  const int warp = __shfl_sync(~0u, tid >> 5, 0);
  const int rank = blockIdx.x & 1;
  const int n = blockIdx.x & 7, m = blockIdx.x >> 3;
  if (tid == 0) STAMP(FIRST ? 2 : 4, 0);
  if (warp == 0) {
    if (lane == 0) {
      prefetch_map(&tmr);
      for (int i = 0; i < K3_ST; i++) { mbar_init(fullb + 8 * i, 1); mbar_init(emptyb + 8 * i, 2); }
      mbar_init(resb, 1); mbar_init(xchb, 1);
      mbar_expect(xchb, 4096 * (10 + EX));
      asm volatile("fence.mbarrier_init.release.cluster;" ::: "memory");
    }
    __syncwarp();
    cluster_arrive();
    bar_arrive(4, 256 + 32);
    if (lane == 0) {
      const uint8_t* wk = (const uint8_t*)wimg + (size_t)n * KT * 10240;
      const uint8_t* ws = (const uint8_t*)wimg + (size_t)(n ^ 1) * KT * 10240;
      const uint8_t* ab = (const uint8_t*)aimg + (size_t)m * KT * 16384;
#pragma unroll 1
      for (int i = 0; i < NB + NK; i++) {
        const int s = i % K3_ST, kt = i < NB ? i + rank * (NB + NK) : i;
        const uint32_t sa = sbase + s * K3_STAGE;
        if (i >= K3_ST) mbar_wait(emptyb + 8 * s, ((i / K3_ST) - 1) & 1);
        mbar_expect(fullb + 8 * s, 26624 + EX * 1024 + (i < NB ? 10240 : 0));
        if (i > 0) bulk_ld(sa, ab + kt * 16384, 16384, fullb + 8 * s);
        bulk_ld(sa + 16384, wk + kt * 10240, 10240, fullb + 8 * s);
        if (FIRST) bulk_ld(sa + 26624, (const uint8_t*)g_wm + kt * 1024, 1024, fullb + 8 * s);
        if (i < NB) bulk_ld(sa + 26624 + EX * 1024, ws + kt * 10240, 10240, fullb + 8 * s);
        if (i == 0) {
          pdl_wait();
          pdl_trigger();
          bulk_ld(sa, ab + kt * 16384, 16384, fullb);
        }
        if (FIRST && i == K3_ST - 1) {
          mbar_expect(resb, 20480);
          tma2d(smem_u32(stg), &tmr, n * 80, m * 128, resb);
          tma2d(smem_u32(stg) + 10240, &tmr, n * 80, m * 128 + 64, resb);
        }
      }
    }
    __syncwarp();
    cluster_wait();
  } else if (warp >= 4) {
    cluster_arrive();
    const int cw = warp - 4, wg = cw >> 2;
    const int g = lane >> 2, c = lane & 3;
    const int row = m * 128 + cw * 16 + g;
    uint8_t* himg = (uint8_t*)g_h + (size_t)m * 163840 + cw * 2048 + lane * 4;
    uint32_t rv[20];
    float mu0, mu1;
    if (FIRST) {
      mu0 = __uint_as_float(__ldcg(&g_rowstat[row].z)); mu1 = __uint_as_float(__ldcg(&g_rowstat[row + 8].z));
    } else {
      mu0 = __ldcg(&g_hmean[row]); mu1 = __ldcg(&g_hmean[row + 8]);
#pragma unroll
      for (int j = 0; j < 10; j++) {
        rv[2 * j] = __ldcg((const uint32_t*)(himg + img_off(n * 10 + j)));
        rv[2 * j + 1] = __ldcg((const uint32_t*)(himg + img_off(n * 10 + j) + 1024));
      }
    }
    float acc[80 + 4 * EX];
    float (&keep)[40 + 4 * EX] = ((Acc<40 + 4 * EX>*)acc)->v;
    const uint64_t da0 = mkdesc(sbase + wg * 8192, 128, 1024, 0);
    const uint64_t db0 = mkdesc(sbase + 16384, 128, 1024, 0);
    bar_sync(4, 256 + 32);
#pragma unroll 1
    for (int i = 0; i < NB; i++) {
      const int s = i % K3_ST;
      mbar_wait(fullb + 8 * s, (i / K3_ST) & 1);
      if (i == 0 && tid == 128) STAMP(FIRST ? 2 : 4, 2);
      const uint64_t da = da0 + s * (K3_STAGE >> 4), db = db0 + s * (K3_STAGE >> 4);
      WG_FENCE();
#pragma unroll
      for (int k = 0; k < 4; k++) {
        if constexpr (FIRST) wgmma_ss_n168(acc, da + k * 16, db + k * 16, (i | k) != 0);
        else wgmma_ss_n160(acc, da + k * 16, db + k * 16, (i | k) != 0);
      }
      WG_COMMIT();
      if (i > 0) {
        WG_WAIT(1);
        if ((tid & 127) == 0) mbar_arrive(emptyb + 8 * ((i - 1) % K3_ST));
      }
    }
    cluster_wait();
    {
      const uint32_t rx = mapa(smem_u32(xch) + (tid - 128) * 16, rank ^ 1), rb = mapa(xchb, rank ^ 1);
      WG_WAIT(0);
      fence_regs(acc);
      if ((tid & 127) == 0) mbar_arrive(emptyb + 8 * ((NB - 1) % K3_ST));
#pragma unroll
      for (int j = 0; j < 10 + EX; j++)
        st_async4(rx + j * 4096, acc[40 + 4 * j], acc[41 + 4 * j], acc[42 + 4 * j], acc[43 + 4 * j], rb);
    }
    if (tid == 128) STAMP(FIRST ? 2 : 4, 1);
#pragma unroll 1
    for (int i = NB; i < NB + NK; i++) {
      const int s = i % K3_ST;
      mbar_wait(fullb + 8 * s, (i / K3_ST) & 1);
      const uint64_t da = da0 + s * (K3_STAGE >> 4), db = db0 + s * (K3_STAGE >> 4);
      WG_FENCE();
#pragma unroll
      for (int k = 0; k < 4; k++) {
        if constexpr (FIRST) wgmma_ss_n88(keep, da + k * 16, db + k * 16, 1);
        else wgmma_ss_n80(keep, da + k * 16, db + k * 16, 1);
      }
      WG_COMMIT();
      if (i > NB && i - 1 + K3_ST < NB + NK) {
        WG_WAIT(1);
        if ((tid & 127) == 0) mbar_arrive(emptyb + 8 * ((i - 1) % K3_ST));
      }
    }
    uint8_t* sp = stg + (cw * 16 + g) * 160 + c * 4;
    if (FIRST) {
      mbar_wait(resb, 0);
#pragma unroll
      for (int j = 0; j < 10; j++) {
        rv[2 * j] = *(const uint32_t*)(sp + j * 16);
        rv[2 * j + 1] = *(const uint32_t*)(sp + 1280 + j * 16);
      }
    }
    WG_WAIT(0);
    fence_regs(keep);
    if (tid == 128) STAMP(FIRST ? 2 : 4, 3);
    mbar_wait(xchb, 0);
    if (tid == 128) STAMP(FIRST ? 2 : 4, 5);
    const uint8_t* xp = xch + (tid - 128) * 16;
    if (FIRST) {
      const float4 p = *(const float4*)xp;
      mu0 += __shfl_sync(~0u, (keep[40] + p.x) + (keep[41] + p.y), 0, 4);
      mu1 += __shfl_sync(~0u, (keep[42] + p.z) + (keep[43] + p.w), 0, 4);
      if (n == 0 && c == 0) { g_hmean[row] = mu0; g_hmean[row + 8] = mu1; }
      mu0 = -mu0; mu1 = -mu1;
    }
    float q0 = 0.f, q1 = 0.f;
#pragma unroll
    for (int j = 0; j < 10; j++) {
      const float4 p = *(const float4*)(xp + (j + EX) * 4096);
      const float x0 = (keep[4 * j] + p.x) + (bf_lo(rv[2 * j]) + mu0), x1 = (keep[4 * j + 1] + p.y) + (bf_hi(rv[2 * j]) + mu0);
      const float y0 = (keep[4 * j + 2] + p.z) + (bf_lo(rv[2 * j + 1]) + mu1), y1 = (keep[4 * j + 3] + p.w) + (bf_hi(rv[2 * j + 1]) + mu1);
      if (FIRST) {
        *(uint32_t*)(himg + img_off(n * 10 + j)) = pack_bf16(x0, x1);
        *(uint32_t*)(himg + img_off(n * 10 + j) + 1024) = pack_bf16(y0, y1);
        q0 = fmaf(x0, x0, fmaf(x1, x1, q0)); q1 = fmaf(y0, y0, fmaf(y1, y1, q1));
      } else {
        *(uint32_t*)(sp + j * 16) = pack_bf16(x0, x1);
        *(uint32_t*)(sp + 1280 + j * 16) = pack_bf16(y0, y1);
      }
    }
    if (FIRST) {
      q0 += __shfl_xor_sync(~0u, q0, 1); q0 += __shfl_xor_sync(~0u, q0, 2);
      q1 += __shfl_xor_sync(~0u, q1, 1); q1 += __shfl_xor_sync(~0u, q1, 2);
      if (c < 2) g_hpart[n * S_ + row + c * 8] = c ? q1 : q0;
    } else {
      fence_async();
      bar_sync(1 + wg, 128);
      if ((tid & 127) == 0) {
        tma2d_st(&tmr, n * 80, m * 128 + wg * 64, smem_u32(stg) + wg * 10240);
        bulk_commit_wait();
      }
      __syncwarp();
    }
    if (tid == 128) STAMP(FIRST ? 2 : 4, 4);
  } else {
    cluster_arrive();
    cluster_wait();
  }
}

constexpr int K4_ST = 3, K4_STAGE = 71680;
constexpr int K4_SMEM = K4_ST * K4_STAGE + 64;

__global__ void __cluster_dims__(2, 1, 1) __launch_bounds__(256, 1)
k4_ffn1() {
  extern __shared__ __align__(1024) uint8_t sm[];
  const uint32_t sbase = smem_u32(sm);
  const uint32_t fullb = sbase + K4_ST * K4_STAGE, emptyb = fullb + 8 * K4_ST;
  const int tid = threadIdx.x, lane = tid & 31;
  const int warp = __shfl_sync(~0u, tid >> 5, 0);
  const int rank = blockIdx.x & 1, cl = blockIdx.x >> 1;
  const int n = cl & 7, m = (cl >> 3) * 2 + rank;
  const uint8_t* wb = (const uint8_t*)g_wgu + (size_t)n * 10 * 55296 + rank * 27648;
  const uint8_t* ab = (const uint8_t*)g_h + (size_t)m * 163840;
  if (tid == 0) STAMP(3, 0);
  if (tid == 0) {
    for (int i = 0; i < K4_ST; i++) { mbar_init(fullb + 8 * i, 1); mbar_init(emptyb + 8 * i, 4); }
    asm volatile("fence.mbarrier_init.release.cluster;" ::: "memory");
    for (int kt = 0; kt < K4_ST; kt++) mbar_expect(fullb + 8 * kt, K4_STAGE);
  }
  __syncthreads();
  cluster_arrive();
  cluster_wait();
  if (tid == 0) bulk_ld_mc(sbase + 16384 + rank * 27648, wb, 27648, fullb);
  pdl_wait();
  pdl_trigger();
  if (tid == 128) STAMP(3, 1);
  if (tid == 0) {
    bulk_ld(sbase, ab, 16384, fullb);
    for (int kt = 1; kt < K4_ST; kt++) {
      bulk_ld(sbase + kt * K4_STAGE, ab + kt * 16384, 16384, fullb + 8 * kt);
      bulk_ld_mc(sbase + kt * K4_STAGE + 16384 + rank * 27648, wb + kt * 55296, 27648, fullb + 8 * kt);
    }
  }
  __syncwarp();
  float r0, r1;
  {
    const float* hp = &g_hpart[(lane & 3) * 2 * S_ + m * 128 + warp * 16 + (lane >> 2)];
    r0 = __ldcg(hp) + __ldcg(hp + S_);
    r1 = __ldcg(hp + 8) + __ldcg(hp + S_ + 8);
  }
  float ag[108], au[108];
  const uint64_t da0 = mkdesc(sbase + (warp >> 2) * 8192, 128, 1024, 0);
  const uint64_t db0 = mkdesc(sbase + 16384, 128, 1024, 0);
#pragma unroll 1
  for (int kt = 0; kt < 10; kt++) {
    const int s = kt % K4_ST;
    mbar_wait(fullb + 8 * s, (kt / K4_ST) & 1);
    if (kt == 0 && tid == 128) STAMP(3, 2);
    const uint64_t da = da0 + s * (K4_STAGE >> 4), db = db0 + s * (K4_STAGE >> 4);
    WG_FENCE();
#pragma unroll
    for (int k = 0; k < 4; k++) {
      wgmma_ss_n216(ag, da + k * 16, db + k * 16, (kt | k) != 0);
      wgmma_ss_n216(au, da + k * 16, db + 1728 + k * 16, (kt | k) != 0);
    }
    WG_COMMIT();
    if (kt > 0 && kt - 1 + K4_ST < 10) {
      WG_WAIT(1);
      const int sp = (kt - 1) % K4_ST;
      if ((tid & 127) < 2) mbar_arrive_cta(emptyb + 8 * sp, tid & 1);
      if (tid == 0) {
        const uint32_t sa = sbase + sp * K4_STAGE;
        mbar_wait(emptyb + 8 * sp, ((kt - 1) / K4_ST) & 1);
        mbar_expect(fullb + 8 * sp, K4_STAGE);
        bulk_ld_mc(sa + 16384 + rank * 27648, wb + (kt - 1 + K4_ST) * 55296, 27648, fullb + 8 * sp);
        bulk_ld(sa, ab + (kt - 1 + K4_ST) * 16384, 16384, fullb + 8 * sp);
      }
      __syncwarp();
    }
  }
  r0 += __shfl_xor_sync(~0u, r0, 1); r1 += __shfl_xor_sync(~0u, r1, 1);
  r0 += __shfl_xor_sync(~0u, r0, 2); r1 += __shfl_xor_sync(~0u, r1, 2);
  r0 = __frcp_rn(r0 * (1.f / D_) + 1e-5f); r1 = __frcp_rn(r1 * (1.f / D_) + 1e-5f);
  cluster_arrive();
  WG_WAIT(0);
  fence_regs(ag); fence_regs(au);
  if (tid == 128) STAMP(3, 3);
  uint8_t* dst = (uint8_t*)g_hh + (size_t)m * 27 * 16384 + warp * 2048 + lane * 4;
#pragma unroll
  for (int j = 0; j < 27; j++) {
    *(uint32_t*)(dst + img_off(n * 27 + j)) = pack_bf16(ag[4 * j] * r0 * au[4 * j], ag[4 * j + 1] * r0 * au[4 * j + 1]);
    *(uint32_t*)(dst + img_off(n * 27 + j) + 1024) = pack_bf16(ag[4 * j + 2] * r1 * au[4 * j + 2], ag[4 * j + 3] * r1 * au[4 * j + 3]);
  }
  if (tid == 128) STAMP(3, 4);
  cluster_wait();
}

typedef CUresult (*EncodeFn)(CUtensorMap*, CUtensorMapDataType, cuuint32_t, void*, const cuuint64_t*, const cuuint64_t*,
                             const cuuint32_t*, const cuuint32_t*, CUtensorMapInterleave, CUtensorMapSwizzle,
                             CUtensorMapL2promotion, CUtensorMapFloatOOBfill);

static CUtensorMap make_map(EncodeFn enc, const void* p, uint64_t inner, uint64_t outer, uint32_t box_inner,
                            uint32_t box_outer, CUtensorMapSwizzle swz) {
  CUtensorMap m;
  cuuint64_t gd[2] = {inner, outer};
  cuuint64_t gs[1] = {inner * 2};
  cuuint32_t bd[2] = {box_inner, box_outer};
  cuuint32_t es[2] = {1, 1};
  enc(&m, CU_TENSOR_MAP_DATA_TYPE_BFLOAT16, 2, (void*)p, gd, gs, bd, es, CU_TENSOR_MAP_INTERLEAVE_NONE, swz,
      CU_TENSOR_MAP_L2_PROMOTION_L2_256B, CU_TENSOR_MAP_FLOAT_OOB_FILL_NONE);
  return m;
}

static CUtensorMap make_map_img(EncodeFn enc, const void* p, uint64_t k, uint64_t n, uint32_t chunks) {
  CUtensorMap m;
  cuuint64_t gd[3] = {8, k, n / 8};
  cuuint64_t gs[2] = {n * 2, 16};
  cuuint32_t bd[3] = {8, 64, chunks};
  cuuint32_t es[3] = {1, 1, 1};
  enc(&m, CU_TENSOR_MAP_DATA_TYPE_BFLOAT16, 3, (void*)p, gd, gs, bd, es, CU_TENSOR_MAP_INTERLEAVE_NONE,
      CU_TENSOR_MAP_SWIZZLE_NONE, CU_TENSOR_MAP_L2_PROMOTION_L2_128B, CU_TENSOR_MAP_FLOAT_OOB_FILL_NONE);
  return m;
}

template <typename... KArgs, typename... Args>
static void launch(void (*k)(KArgs...), int grid, int threads, int smem, bool pdl, Args... args) {
  cudaLaunchConfig_t cfg = {};
  cfg.gridDim = dim3(grid);
  cfg.blockDim = dim3(threads);
  cfg.dynamicSmemBytes = smem;
  cfg.stream = cudaStreamPerThread;
  cudaLaunchAttribute at[1];
  at[0].id = cudaLaunchAttributeProgrammaticStreamSerialization;
  at[0].val.programmaticStreamSerializationAllowed = 1;
  cfg.attrs = at;
  cfg.numAttrs = pdl ? 1 : 0;
  cudaLaunchKernelEx(&cfg, k, KArgs(args)...);
}

extern "C" void kernel_launch(void* const* d_in, const int* in_sizes, int n_in, void* d_out, int out_size) {
  const bf16* x = (const bf16*)d_in[0];
  const bf16* wqkv = (const bf16*)d_in[1];
  const bf16* wo = (const bf16*)d_in[2];
  const bf16* wg = (const bf16*)d_in[4];
  const bf16* wu = (const bf16*)d_in[5];
  const bf16* wd = (const bf16*)d_in[6];

  static EncodeFn enc = nullptr;
  static void *p_o, *p_hh, *p_wo, *p_wd;
  if (!enc) {
    void* fn = nullptr;
    cudaDriverEntryPointQueryResult qr;
    cudaGetDriverEntryPoint("cuTensorMapEncodeTiled", &fn, cudaEnableDefault, &qr);
    enc = (EncodeFn)fn;
    cudaGetSymbolAddress(&p_o, g_o); cudaGetSymbolAddress(&p_hh, g_hh);
    cudaGetSymbolAddress(&p_wo, g_wo); cudaGetSymbolAddress(&p_wd, g_wd);
    cudaFuncSetAttribute(k1_qkv, cudaFuncAttributeMaxDynamicSharedMemorySize, K1_SMEM);
    cudaFuncSetAttribute(k2_attn, cudaFuncAttributeMaxDynamicSharedMemorySize, K2_SMEM);
    cudaFuncSetAttribute(k3_proj<3, 4, true>, cudaFuncAttributeMaxDynamicSharedMemorySize, K3_SMEM);
    cudaFuncSetAttribute(k3_proj<11, 5, false>, cudaFuncAttributeMaxDynamicSharedMemorySize, K3_SMEM);
    cudaFuncSetAttribute(k4_ffn1, cudaFuncAttributeMaxDynamicSharedMemorySize, K4_SMEM);
  }
  const CUtensorMap tmx = make_map(enc, x, D_, S_, 64, 128, CU_TENSOR_MAP_SWIZZLE_128B);
  const CUtensorMap tmw = make_map(enc, wqkv, 3 * D_, D_, 32, 64, CU_TENSOR_MAP_SWIZZLE_64B);
  const CUtensorMap tmxr = make_map(enc, x, D_, S_, 80, 64, CU_TENSOR_MAP_SWIZZLE_NONE);
  const CUtensorMap tmg = make_map_img(enc, wg, D_, F_, 9), tmu = make_map_img(enc, wu, D_, F_, 9);
  const CUtensorMap tmd = make_map_img(enc, wd, F_, D_, 10);
  const CUtensorMap tmout = make_map(enc, d_out, D_, S_, 80, 64, CU_TENSOR_MAP_SWIZZLE_NONE);

  launch(k1_qkv, 128, 384, K1_SMEM, false, tmx, tmw, x, wqkv, wo);
  launch(k2_attn, 128, 512, K2_SMEM, true, tmg, tmu, tmd, 0x007f007fu);
  launch(k3_proj<3, 4, true>, 128, 384, K3_SMEM, true, tmxr, (const uint4*)p_o, (const uint4*)p_wo);
  launch(k4_ffn1, 128, 256, K4_SMEM, true);
  launch(k3_proj<11, 5, false>, 128, 384, K3_SMEM, true, tmout, (const uint4*)p_hh, (const uint4*)p_wd);
}
```

```cpp
#include <cuda_runtime.h>
#include <cuda_bf16.h>
#include <cuda.h>
#include <stdint.h>

typedef __nv_bfloat16 bf16;

constexpr int S_ = 2048, D_ = 640, F_ = 1728;
constexpr int HEAD_IMG = 98304;
#define PMASK 0xABAB
constexpr uint32_t POLY_MASK = PMASK;
constexpr float QSCALE = 0.22360679774997896f * 1.4426950408889634f;

__device__ __align__(1024) uint4 g_qkv[96 * HEAD_IMG / 16];
__device__ __align__(1024) uint4 g_o[S_ * D_ / 8];
__device__ __align__(1024) uint4 g_h[S_ * D_ / 8];
__device__ __align__(1024) uint4 g_hh[S_ * F_ / 8];
__device__ __align__(1024) uint4 g_wo[D_ * D_ / 8];
__device__ __align__(1024) uint4 g_wgu[2 * D_ * F_ / 8];
__device__ __align__(1024) uint4 g_wd[F_ * D_ / 8];
__device__ uint4 g_rowstat[S_];
__device__ uint4 g_cpart[16 * 8 * 128];
__device__ float g_nrm[64 * 128];
__device__ uint4 g_wm[D_];
__device__ float g_hmean[S_];
__device__ float g_hpart[8 * S_];
__device__ unsigned g_epoch;

#define STAMP(k, i)
__device__ __forceinline__ uint32_t smem_u32(const void* p) { return (uint32_t)__cvta_generic_to_shared(p); }
__device__ __forceinline__ void mbar_init(uint32_t a, uint32_t c) {
  asm volatile("mbarrier.init.shared::cta.b64 [%0], %1;" ::"r"(a), "r"(c) : "memory");
}
__device__ __forceinline__ void mbar_expect(uint32_t a, uint32_t bytes) {
  asm volatile("mbarrier.arrive.expect_tx.shared::cta.b64 _, [%0], %1;" ::"r"(a), "r"(bytes) : "memory");
}
__device__ __forceinline__ void mbar_arrive(uint32_t a) {
  asm volatile("mbarrier.arrive.shared::cta.b64 _, [%0];" ::"r"(a) : "memory");
}
__device__ __forceinline__ void mbar_arrive_cta(uint32_t a, uint32_t cta) {
  asm volatile("{\n.reg .b32 r;\nmapa.shared::cluster.u32 r, %0, %1;\n"
               "mbarrier.arrive.shared::cluster.b64 _, [r];\n}" ::"r"(a), "r"(cta) : "memory");
}
__device__ __forceinline__ bool mbar_try(uint32_t a, uint32_t ph) {
  uint32_t ok;
  asm volatile("{\n.reg .pred p;\nmbarrier.try_wait.parity.shared::cta.b64 p, [%1], %2;\nselp.u32 %0, 1, 0, p;\n}"
               : "=r"(ok) : "r"(a), "r"(ph) : "memory");
  return ok;
}
__device__ __noinline__ void wait_timeout() { __trap(); }
__device__ __forceinline__ void mbar_wait(uint32_t a, uint32_t ph) {
  if (mbar_try(a, ph)) return;
  uint32_t it = 0;
  while (!mbar_try(a, ph)) if (++it > (1u << 22)) wait_timeout();
}
__device__ __forceinline__ void tma2d(uint32_t dst, const CUtensorMap* m, int c0, int c1, uint32_t bar) {
  asm volatile("cp.async.bulk.tensor.2d.shared::cluster.global.mbarrier::complete_tx::bytes [%0], [%1, {%3, %4}], [%2];"
               ::"r"(dst), "l"(m), "r"(bar), "r"(c0), "r"(c1) : "memory");
}
__device__ __forceinline__ void tma2d_mc(uint32_t dst, const CUtensorMap* m, int c0, int c1, uint32_t bar) {
  asm volatile("cp.async.bulk.tensor.2d.shared::cluster.global.mbarrier::complete_tx::bytes.multicast::cluster "
               "[%0], [%1, {%3, %4}], [%2], %5;"
               ::"r"(dst), "l"(m), "r"(bar), "r"(c0), "r"(c1), "h"((uint16_t)3) : "memory");
}
__device__ __forceinline__ void bulk_ld(uint32_t dst, const void* src, uint32_t bytes, uint32_t bar) {
  asm volatile("cp.async.bulk.shared::cluster.global.mbarrier::complete_tx::bytes [%0], [%1], %2, [%3];"
               ::"r"(dst), "l"(src), "r"(bytes), "r"(bar) : "memory");
}
__device__ __forceinline__ void bulk_ld_mc(uint32_t dst, const void* src, uint32_t bytes, uint32_t bar) {
  asm volatile("cp.async.bulk.shared::cluster.global.mbarrier::complete_tx::bytes.multicast::cluster "
               "[%0], [%1], %2, [%3], %4;"
               ::"r"(dst), "l"(src), "r"(bytes), "r"(bar), "h"((uint16_t)3) : "memory");
}
__device__ __forceinline__ void cluster_arrive() { asm volatile("barrier.cluster.arrive.relaxed.aligned;" ::: "memory"); }
__device__ __forceinline__ void cluster_wait() { asm volatile("barrier.cluster.wait.aligned;" ::: "memory"); }
__device__ __forceinline__ void bulk_st(void* dst, uint32_t src, uint32_t bytes) {
  asm volatile("cp.async.bulk.global.shared::cta.bulk_group [%0], [%1], %2;" ::"l"(dst), "r"(src), "r"(bytes) : "memory");
}
__device__ __forceinline__ void tma2d_st(const CUtensorMap* m, int c0, int c1, uint32_t src) {
  asm volatile("cp.async.bulk.tensor.2d.global.shared::cta.bulk_group [%0, {%2, %3}], [%1];"
               ::"l"(m), "r"(src), "r"(c0), "r"(c1) : "memory");
}
__device__ __forceinline__ void bulk_commit_wait() {
  asm volatile("cp.async.bulk.commit_group;\ncp.async.bulk.wait_group.read 0;" ::: "memory");
}
__device__ __forceinline__ uint32_t mapa(uint32_t a, uint32_t cta) {
  uint32_t r;
  asm("mapa.shared::cluster.u32 %0, %1, %2;" : "=r"(r) : "r"(a), "r"(cta));
  return r;
}
__device__ __forceinline__ void st_async4(uint32_t dst, float a, float b, float c, float d, uint32_t bar) {
  asm volatile("st.async.shared::cluster.mbarrier::complete_tx::bytes.v4.f32 [%0], {%1, %2, %3, %4}, [%5];"
               ::"r"(dst), "f"(a), "f"(b), "f"(c), "f"(d), "r"(bar) : "memory");
}
__device__ __forceinline__ void fence_async() { asm volatile("fence.proxy.async.shared::cta;" ::: "memory"); }
__device__ __forceinline__ void prefetch_map(const CUtensorMap* m) {
  asm volatile("prefetch.tensormap [%0];" ::"l"(m) : "memory");
}
__device__ __forceinline__ void pdl_wait() { asm volatile("griddepcontrol.wait;" ::: "memory"); }
__device__ __forceinline__ void pdl_trigger() { asm volatile("griddepcontrol.launch_dependents;" ::: "memory"); }
__device__ __forceinline__ void bar_sync(int id, int n) { asm volatile("bar.sync %0, %1;" ::"r"(id), "r"(n) : "memory"); }
__device__ __forceinline__ void bar_arrive(int id, int n) { asm volatile("bar.arrive %0, %1;" ::"r"(id), "r"(n) : "memory"); }
#define WG_FENCE() asm volatile("wgmma.fence.sync.aligned;" ::: "memory")
#define WG_COMMIT() asm volatile("wgmma.commit_group.sync.aligned;" ::: "memory")
#define WG_WAIT(n) asm volatile("wgmma.wait_group.sync.aligned %0;" ::"n"(n) : "memory")
__device__ __forceinline__ uint64_t mkdesc(uint32_t addr, uint32_t lbo, uint32_t sbo, uint32_t sw) {
  return (uint64_t)((addr & 0x3FFFF) >> 4) | ((uint64_t)(lbo >> 4) << 16) | ((uint64_t)(sbo >> 4) << 32) |
         ((uint64_t)sw << 62);
}
template <int N> __device__ __forceinline__ void fence_regs(float (&r)[N]) {
#pragma unroll
  for (int i = 0; i < N; i++) asm volatile("" : "+f"(r[i])::"memory");
}
__device__ __forceinline__ uint32_t pack_bf16(float lo, float hi) {
  uint32_t r;
  asm("cvt.rn.bf16x2.f32 %0, %1, %2;" : "=r"(r) : "f"(hi), "f"(lo));
  return r;
}
__device__ __forceinline__ float bf_lo(uint32_t v) { return __uint_as_float(v << 16); }
__device__ __forceinline__ float bf_hi(uint32_t v) { return __uint_as_float(v & 0xffff0000u); }
__device__ __forceinline__ float ex2(float x) {
  float y;
  asm("ex2.approx.ftz.f32 %0, %1;" : "=f"(y) : "f"(x));
  return y;
}
__device__ __forceinline__ uint4 ldg_nc(const void* p) {
  uint4 v;
  asm volatile("ld.global.nc.L1::no_allocate.v4.u32 {%0, %1, %2, %3}, [%4];"
               : "=r"(v.x), "=r"(v.y), "=r"(v.z), "=r"(v.w) : "l"(p));
  return v;
}

__device__ __forceinline__ uint4 ld_relaxed(const uint4* p) {
  uint64_t a, b;
  asm volatile("ld.relaxed.gpu.global.v2.u64 {%0, %1}, [%2];" : "=l"(a), "=l"(b) : "l"(p) : "memory");
  return make_uint4((uint32_t)a, (uint32_t)(a >> 32), (uint32_t)b, (uint32_t)(b >> 32));
}
__device__ __forceinline__ void st_relaxed(uint4* p, float x, float y, uint32_t tag) {
  const uint64_t a = ((uint64_t)tag << 32) | __float_as_uint(x), b = ((uint64_t)tag << 32) | __float_as_uint(y);
  asm volatile("st.relaxed.gpu.global.v2.u64 [%0], {%1, %2};" ::"l"(p), "l"(a), "l"(b) : "memory");
}
__device__ __forceinline__ void tma3d(uint32_t dst, const CUtensorMap* m, int c1, int c2, uint32_t bar) {
  asm volatile("cp.async.bulk.tensor.3d.shared::cluster.global.mbarrier::complete_tx::bytes [%0], [%1, {%3, %4, %5}], [%2];"
               ::"r"(dst), "l"(m), "r"(bar), "r"(0), "r"(c1), "r"(c2) : "memory");
}
__device__ __forceinline__ void mma16816(float (&d)[4], uint32_t a0, uint32_t a1, uint32_t a2, uint32_t a3,
                                         uint32_t b0, uint32_t b1) {
  asm volatile("mma.sync.aligned.m16n8k16.row.col.f32.bf16.bf16.f32 {%0, %1, %2, %3}, {%4, %5, %6, %7}, {%8, %9}, "
               "{%0, %1, %2, %3};" : "+f"(d[0]), "+f"(d[1]), "+f"(d[2]), "+f"(d[3])
               : "r"(a0), "r"(a1), "r"(a2), "r"(a3), "r"(b0), "r"(b1));
}
#define ACC8(a, v) do { a[0] += bf_lo(v.x); a[1] += bf_hi(v.x); a[2] += bf_lo(v.y); a[3] += bf_hi(v.y); \
                        a[4] += bf_lo(v.z); a[5] += bf_hi(v.z); a[6] += bf_lo(v.w); a[7] += bf_hi(v.w); } while (0)

__device__ __forceinline__ void wgmma_ss_n240(float (&d)[120], uint64_t da, uint64_t db, int sd) {
  asm volatile("{\n.reg .pred p;\nsetp.ne.b32 p, %122, 0;\n"
      "wgmma.mma_async.sync.aligned.m64n240k16.f32.bf16.bf16 {"
      "%0, %1, %2, %3, %4, %5, %6, %7, %8, %9, %10, %11, %12, %13, %14, %15, "
      "%16, %17, %18, %19, %20, %21, %22, %23, %24, %25, %26, %27, %28, %29, %30, %31, "
      "%32, %33, %34, %35, %36, %37, %38, %39, %40, %41, %42, %43, %44, %45, %46, %47, "
      "%48, %49, %50, %51, %52, %53, %54, %55, %56, %57, %58, %59, %60, %61, %62, %63, "
      "%64, %65, %66, %67, %68, %69, %70, %71, %72, %73, %74, %75, %76, %77, %78, %79, "
      "%80, %81, %82, %83, %84, %85, %86, %87, %88, %89, %90, %91, %92, %93, %94, %95, "
      "%96, %97, %98, %99, %100, %101, %102, %103, %104, %105, %106, %107, %108, %109, %110, %111, "
      "%112, %113, %114, %115, %116, %117, %118, %119"
      "}, %120, %121, p, 1, 1, 0, 1;\n}\n"
    : "+f"(d[0]), "+f"(d[1]), "+f"(d[2]), "+f"(d[3]), "+f"(d[4]), "+f"(d[5]), "+f"(d[6]), "+f"(d[7]),
      "+f"(d[8]), "+f"(d[9]), "+f"(d[10]), "+f"(d[11]), "+f"(d[12]), "+f"(d[13]), "+f"(d[14]), "+f"(d[15]),
      "+f"(d[16]), "+f"(d[17]), "+f"(d[18]), "+f"(d[19]), "+f"(d[20]), "+f"(d[21]), "+f"(d[22]), "+f"(d[23]),
      "+f"(d[24]), "+f"(d[25]), "+f"(d[26]), "+f"(d[27]), "+f"(d[28]), "+f"(d[29]), "+f"(d[30]), "+f"(d[31]),
      "+f"(d[32]), "+f"(d[33]), "+f"(d[34]), "+f"(d[35]), "+f"(d[36]), "+f"(d[37]), "+f"(d[38]), "+f"(d[39]),
      "+f"(d[40]), "+f"(d[41]), "+f"(d[42]), "+f"(d[43]), "+f"(d[44]), "+f"(d[45]), "+f"(d[46]), "+f"(d[47]),
      "+f"(d[48]), "+f"(d[49]), "+f"(d[50]), "+f"(d[51]), "+f"(d[52]), "+f"(d[53]), "+f"(d[54]), "+f"(d[55]),
      "+f"(d[56]), "+f"(d[57]), "+f"(d[58]), "+f"(d[59]), "+f"(d[60]), "+f"(d[61]), "+f"(d[62]), "+f"(d[63]),
      "+f"(d[64]), "+f"(d[65]), "+f"(d[66]), "+f"(d[67]), "+f"(d[68]), "+f"(d[69]), "+f"(d[70]), "+f"(d[71]),
      "+f"(d[72]), "+f"(d[73]), "+f"(d[74]), "+f"(d[75]), "+f"(d[76]), "+f"(d[77]), "+f"(d[78]), "+f"(d[79]),
      "+f"(d[80]), "+f"(d[81]), "+f"(d[82]), "+f"(d[83]), "+f"(d[84]), "+f"(d[85]), "+f"(d[86]), "+f"(d[87]),
      "+f"(d[88]), "+f"(d[89]), "+f"(d[90]), "+f"(d[91]), "+f"(d[92]), "+f"(d[93]), "+f"(d[94]), "+f"(d[95]),
      "+f"(d[96]), "+f"(d[97]), "+f"(d[98]), "+f"(d[99]), "+f"(d[100]), "+f"(d[101]), "+f"(d[102]), "+f"(d[103]),
      "+f"(d[104]), "+f"(d[105]), "+f"(d[106]), "+f"(d[107]), "+f"(d[108]), "+f"(d[109]), "+f"(d[110]), "+f"(d[111]),
      "+f"(d[112]), "+f"(d[113]), "+f"(d[114]), "+f"(d[115]), "+f"(d[116]), "+f"(d[117]), "+f"(d[118]), "+f"(d[119])
    : "l"(da), "l"(db), "r"(sd));
}
__device__ __forceinline__ void wgmma_ss_n216(float (&d)[108], uint64_t da, uint64_t db, int sd) {
  asm volatile("{\n.reg .pred p;\nsetp.ne.b32 p, %110, 0;\n"
      "wgmma.mma_async.sync.aligned.m64n216k16.f32.bf16.bf16 {"
      "%0, %1, %2, %3, %4, %5, %6, %7, %8, %9, %10, %11, %12, %13, %14, %15, "
      "%16, %17, %18, %19, %20, %21, %22, %23, %24, %25, %26, %27, %28, %29, %30, %31, "
      "%32, %33, %34, %35, %36, %37, %38, %39, %40, %41, %42, %43, %44, %45, %46, %47, "
      "%48, %49, %50, %51, %52, %53, %54, %55, %56, %57, %58, %59, %60, %61, %62, %63, "
      "%64, %65, %66, %67, %68, %69, %70, %71, %72, %73, %74, %75, %76, %77, %78, %79, "
      "%80, %81, %82, %83, %84, %85, %86, %87, %88, %89, %90, %91, %92, %93, %94, %95, "
      "%96, %97, %98, %99, %100, %101, %102, %103, %104, %105, %106, %107"
      "}, %108, %109, p, 1, 1, 0, 1;\n}\n"
    : "+f"(d[0]), "+f"(d[1]), "+f"(d[2]), "+f"(d[3]), "+f"(d[4]), "+f"(d[5]), "+f"(d[6]), "+f"(d[7]),
      "+f"(d[8]), "+f"(d[9]), "+f"(d[10]), "+f"(d[11]), "+f"(d[12]), "+f"(d[13]), "+f"(d[14]), "+f"(d[15]),
      "+f"(d[16]), "+f"(d[17]), "+f"(d[18]), "+f"(d[19]), "+f"(d[20]), "+f"(d[21]), "+f"(d[22]), "+f"(d[23]),
      "+f"(d[24]), "+f"(d[25]), "+f"(d[26]), "+f"(d[27]), "+f"(d[28]), "+f"(d[29]), "+f"(d[30]), "+f"(d[31]),
      "+f"(d[32]), "+f"(d[33]), "+f"(d[34]), "+f"(d[35]), "+f"(d[36]), "+f"(d[37]), "+f"(d[38]), "+f"(d[39]),
      "+f"(d[40]), "+f"(d[41]), "+f"(d[42]), "+f"(d[43]), "+f"(d[44]), "+f"(d[45]), "+f"(d[46]), "+f"(d[47]),
      "+f"(d[48]), "+f"(d[49]), "+f"(d[50]), "+f"(d[51]), "+f"(d[52]), "+f"(d[53]), "+f"(d[54]), "+f"(d[55]),
      "+f"(d[56]), "+f"(d[57]), "+f"(d[58]), "+f"(d[59]), "+f"(d[60]), "+f"(d[61]), "+f"(d[62]), "+f"(d[63]),
      "+f"(d[64]), "+f"(d[65]), "+f"(d[66]), "+f"(d[67]), "+f"(d[68]), "+f"(d[69]), "+f"(d[70]), "+f"(d[71]),
      "+f"(d[72]), "+f"(d[73]), "+f"(d[74]), "+f"(d[75]), "+f"(d[76]), "+f"(d[77]), "+f"(d[78]), "+f"(d[79]),
      "+f"(d[80]), "+f"(d[81]), "+f"(d[82]), "+f"(d[83]), "+f"(d[84]), "+f"(d[85]), "+f"(d[86]), "+f"(d[87]),
      "+f"(d[88]), "+f"(d[89]), "+f"(d[90]), "+f"(d[91]), "+f"(d[92]), "+f"(d[93]), "+f"(d[94]), "+f"(d[95]),
      "+f"(d[96]), "+f"(d[97]), "+f"(d[98]), "+f"(d[99]), "+f"(d[100]), "+f"(d[101]), "+f"(d[102]), "+f"(d[103]),
      "+f"(d[104]), "+f"(d[105]), "+f"(d[106]), "+f"(d[107])
    : "l"(da), "l"(db), "r"(sd));
}
__device__ __forceinline__ void wgmma_ss_n168(float (&d)[84], uint64_t da, uint64_t db, int sd) {
  asm volatile("{\n.reg .pred p;\nsetp.ne.b32 p, %86, 0;\n"
      "wgmma.mma_async.sync.aligned.m64n168k16.f32.bf16.bf16 {"
      "%0, %1, %2, %3, %4, %5, %6, %7, %8, %9, %10, %11, %12, %13, %14, %15, "
      "%16, %17, %18, %19, %20, %21, %22, %23, %24, %25, %26, %27, %28, %29, %30, %31, "
      "%32, %33, %34, %35, %36, %37, %38, %39, %40, %41, %42, %43, %44, %45, %46, %47, "
      "%48, %49, %50, %51, %52, %53, %54, %55, %56, %57, %58, %59, %60, %61, %62, %63, "
      "%64, %65, %66, %67, %68, %69, %70, %71, %72, %73, %74, %75, %76, %77, %78, %79, "
      "%80, %81, %82, %83"
      "}, %84, %85, p, 1, 1, 0, 1;\n}\n"
    : "+f"(d[0]), "+f"(d[1]), "+f"(d[2]), "+f"(d[3]), "+f"(d[4]), "+f"(d[5]), "+f"(d[6]), "+f"(d[7]),
      "+f"(d[8]), "+f"(d[9]), "+f"(d[10]), "+f"(d[11]), "+f"(d[12]), "+f"(d[13]), "+f"(d[14]), "+f"(d[15]),
      "+f"(d[16]), "+f"(d[17]), "+f"(d[18]), "+f"(d[19]), "+f"(d[20]), "+f"(d[21]), "+f"(d[22]), "+f"(d[23]),
      "+f"(d[24]), "+f"(d[25]), "+f"(d[26]), "+f"(d[27]), "+f"(d[28]), "+f"(d[29]), "+f"(d[30]), "+f"(d[31]),
      "+f"(d[32]), "+f"(d[33]), "+f"(d[34]), "+f"(d[35]), "+f"(d[36]), "+f"(d[37]), "+f"(d[38]), "+f"(d[39]),
      "+f"(d[40]), "+f"(d[41]), "+f"(d[42]), "+f"(d[43]), "+f"(d[44]), "+f"(d[45]), "+f"(d[46]), "+f"(d[47]),
      "+f"(d[48]), "+f"(d[49]), "+f"(d[50]), "+f"(d[51]), "+f"(d[52]), "+f"(d[53]), "+f"(d[54]), "+f"(d[55]),
      "+f"(d[56]), "+f"(d[57]), "+f"(d[58]), "+f"(d[59]), "+f"(d[60]), "+f"(d[61]), "+f"(d[62]), "+f"(d[63]),
      "+f"(d[64]), "+f"(d[65]), "+f"(d[66]), "+f"(d[67]), "+f"(d[68]), "+f"(d[69]), "+f"(d[70]), "+f"(d[71]),
      "+f"(d[72]), "+f"(d[73]), "+f"(d[74]), "+f"(d[75]), "+f"(d[76]), "+f"(d[77]), "+f"(d[78]), "+f"(d[79]),
      "+f"(d[80]), "+f"(d[81]), "+f"(d[82]), "+f"(d[83])
    : "l"(da), "l"(db), "r"(sd));
}
__device__ __forceinline__ void wgmma_ss_n160(float (&d)[80], uint64_t da, uint64_t db, int sd) {
  asm volatile("{\n.reg .pred p;\nsetp.ne.b32 p, %82, 0;\n"
      "wgmma.mma_async.sync.aligned.m64n160k16.f32.bf16.bf16 {"
      "%0, %1, %2, %3, %4, %5, %6, %7, %8, %9, %10, %11, %12, %13, %14, %15, "
      "%16, %17, %18, %19, %20, %21, %22, %23, %24, %25, %26, %27, %28, %29, %30, %31, "
      "%32, %33, %34, %35, %36, %37, %38, %39, %40, %41, %42, %43, %44, %45, %46, %47, "
      "%48, %49, %50, %51, %52, %53, %54, %55, %56, %57, %58, %59, %60, %61, %62, %63, "
      "%64, %65, %66, %67, %68, %69, %70, %71, %72, %73, %74, %75, %76, %77, %78, %79"
      "}, %80, %81, p, 1, 1, 0, 1;\n}\n"
    : "+f"(d[0]), "+f"(d[1]), "+f"(d[2]), "+f"(d[3]), "+f"(d[4]), "+f"(d[5]), "+f"(d[6]), "+f"(d[7]),
      "+f"(d[8]), "+f"(d[9]), "+f"(d[10]), "+f"(d[11]), "+f"(d[12]), "+f"(d[13]), "+f"(d[14]), "+f"(d[15]),
      "+f"(d[16]), "+f"(d[17]), "+f"(d[18]), "+f"(d[19]), "+f"(d[20]), "+f"(d[21]), "+f"(d[22]), "+f"(d[23]),
      "+f"(d[24]), "+f"(d[25]), "+f"(d[26]), "+f"(d[27]), "+f"(d[28]), "+f"(d[29]), "+f"(d[30]), "+f"(d[31]),
      "+f"(d[32]), "+f"(d[33]), "+f"(d[34]), "+f"(d[35]), "+f"(d[36]), "+f"(d[37]), "+f"(d[38]), "+f"(d[39]),
      "+f"(d[40]), "+f"(d[41]), "+f"(d[42]), "+f"(d[43]), "+f"(d[44]), "+f"(d[45]), "+f"(d[46]), "+f"(d[47]),
      "+f"(d[48]), "+f"(d[49]), "+f"(d[50]), "+f"(d[51]), "+f"(d[52]), "+f"(d[53]), "+f"(d[54]), "+f"(d[55]),
      "+f"(d[56]), "+f"(d[57]), "+f"(d[58]), "+f"(d[59]), "+f"(d[60]), "+f"(d[61]), "+f"(d[62]), "+f"(d[63]),
      "+f"(d[64]), "+f"(d[65]), "+f"(d[66]), "+f"(d[67]), "+f"(d[68]), "+f"(d[69]), "+f"(d[70]), "+f"(d[71]),
      "+f"(d[72]), "+f"(d[73]), "+f"(d[74]), "+f"(d[75]), "+f"(d[76]), "+f"(d[77]), "+f"(d[78]), "+f"(d[79])
    : "l"(da), "l"(db), "r"(sd));
}
__device__ __forceinline__ void wgmma_ss_n88(float (&d)[44], uint64_t da, uint64_t db, int sd) {
  asm volatile("{\n.reg .pred p;\nsetp.ne.b32 p, %46, 0;\n"
      "wgmma.mma_async.sync.aligned.m64n88k16.f32.bf16.bf16 {"
      "%0, %1, %2, %3, %4, %5, %6, %7, %8, %9, %10, %11, %12, %13, %14, %15, "
      "%16, %17, %18, %19, %20, %21, %22, %23, %24, %25, %26, %27, %28, %29, %30, %31, "
      "%32, %33, %34, %35, %36, %37, %38, %39, %40, %41, %42, %43"
      "}, %44, %45, p, 1, 1, 0, 1;\n}\n"
    : "+f"(d[0]), "+f"(d[1]), "+f"(d[2]), "+f"(d[3]), "+f"(d[4]), "+f"(d[5]), "+f"(d[6]), "+f"(d[7]),
      "+f"(d[8]), "+f"(d[9]), "+f"(d[10]), "+f"(d[11]), "+f"(d[12]), "+f"(d[13]), "+f"(d[14]), "+f"(d[15]),
      "+f"(d[16]), "+f"(d[17]), "+f"(d[18]), "+f"(d[19]), "+f"(d[20]), "+f"(d[21]), "+f"(d[22]), "+f"(d[23]),
      "+f"(d[24]), "+f"(d[25]), "+f"(d[26]), "+f"(d[27]), "+f"(d[28]), "+f"(d[29]), "+f"(d[30]), "+f"(d[31]),
      "+f"(d[32]), "+f"(d[33]), "+f"(d[34]), "+f"(d[35]), "+f"(d[36]), "+f"(d[37]), "+f"(d[38]), "+f"(d[39]),
      "+f"(d[40]), "+f"(d[41]), "+f"(d[42]), "+f"(d[43])
    : "l"(da), "l"(db), "r"(sd));
}
__device__ __forceinline__ void wgmma_ss_n80(float (&d)[40], uint64_t da, uint64_t db, int sd) {
  asm volatile("{\n.reg .pred p;\nsetp.ne.b32 p, %42, 0;\n"
      "wgmma.mma_async.sync.aligned.m64n80k16.f32.bf16.bf16 {"
      "%0, %1, %2, %3, %4, %5, %6, %7, %8, %9, %10, %11, %12, %13, %14, %15, "
      "%16, %17, %18, %19, %20, %21, %22, %23, %24, %25, %26, %27, %28, %29, %30, %31, "
      "%32, %33, %34, %35, %36, %37, %38, %39"
      "}, %40, %41, p, 1, 1, 0, 1;\n}\n"
    : "+f"(d[0]), "+f"(d[1]), "+f"(d[2]), "+f"(d[3]), "+f"(d[4]), "+f"(d[5]), "+f"(d[6]), "+f"(d[7]),
      "+f"(d[8]), "+f"(d[9]), "+f"(d[10]), "+f"(d[11]), "+f"(d[12]), "+f"(d[13]), "+f"(d[14]), "+f"(d[15]),
      "+f"(d[16]), "+f"(d[17]), "+f"(d[18]), "+f"(d[19]), "+f"(d[20]), "+f"(d[21]), "+f"(d[22]), "+f"(d[23]),
      "+f"(d[24]), "+f"(d[25]), "+f"(d[26]), "+f"(d[27]), "+f"(d[28]), "+f"(d[29]), "+f"(d[30]), "+f"(d[31]),
      "+f"(d[32]), "+f"(d[33]), "+f"(d[34]), "+f"(d[35]), "+f"(d[36]), "+f"(d[37]), "+f"(d[38]), "+f"(d[39])
    : "l"(da), "l"(db), "r"(sd));
}
__device__ __forceinline__ void wgmma_rs_n128(float (&d)[64], uint32_t a0, uint32_t a1, uint32_t a2, uint32_t a3,
                                  uint64_t db, int sd) {
  asm volatile("{\n.reg .pred p;\nsetp.ne.b32 p, %69, 0;\n"
      "wgmma.mma_async.sync.aligned.m64n128k16.f32.bf16.bf16 {"
      "%0, %1, %2, %3, %4, %5, %6, %7, %8, %9, %10, %11, %12, %13, %14, %15, "
      "%16, %17, %18, %19, %20, %21, %22, %23, %24, %25, %26, %27, %28, %29, %30, %31, "
      "%32, %33, %34, %35, %36, %37, %38, %39, %40, %41, %42, %43, %44, %45, %46, %47, "
      "%48, %49, %50, %51, %52, %53, %54, %55, %56, %57, %58, %59, %60, %61, %62, %63"
      "}, {%64, %65, %66, %67}, %68, p, 1, 1, 0;\n}\n"
    : "+f"(d[0]), "+f"(d[1]), "+f"(d[2]), "+f"(d[3]), "+f"(d[4]), "+f"(d[5]), "+f"(d[6]), "+f"(d[7]),
      "+f"(d[8]), "+f"(d[9]), "+f"(d[10]), "+f"(d[11]), "+f"(d[12]), "+f"(d[13]), "+f"(d[14]), "+f"(d[15]),
      "+f"(d[16]), "+f"(d[17]), "+f"(d[18]), "+f"(d[19]), "+f"(d[20]), "+f"(d[21]), "+f"(d[22]), "+f"(d[23]),
      "+f"(d[24]), "+f"(d[25]), "+f"(d[26]), "+f"(d[27]), "+f"(d[28]), "+f"(d[29]), "+f"(d[30]), "+f"(d[31]),
      "+f"(d[32]), "+f"(d[33]), "+f"(d[34]), "+f"(d[35]), "+f"(d[36]), "+f"(d[37]), "+f"(d[38]), "+f"(d[39]),
      "+f"(d[40]), "+f"(d[41]), "+f"(d[42]), "+f"(d[43]), "+f"(d[44]), "+f"(d[45]), "+f"(d[46]), "+f"(d[47]),
      "+f"(d[48]), "+f"(d[49]), "+f"(d[50]), "+f"(d[51]), "+f"(d[52]), "+f"(d[53]), "+f"(d[54]), "+f"(d[55]),
      "+f"(d[56]), "+f"(d[57]), "+f"(d[58]), "+f"(d[59]), "+f"(d[60]), "+f"(d[61]), "+f"(d[62]), "+f"(d[63])
    : "r"(a0), "r"(a1), "r"(a2), "r"(a3), "l"(db), "r"(sd));
}
__device__ __forceinline__ void wgmma_rs_n24(float (&d)[12], uint32_t a0, uint32_t a1, uint32_t a2, uint32_t a3,
                                  uint64_t db, int sd) {
  asm volatile("{\n.reg .pred p;\nsetp.ne.b32 p, %17, 0;\n"
      "wgmma.mma_async.sync.aligned.m64n24k16.f32.bf16.bf16 {"
      "%0, %1, %2, %3, %4, %5, %6, %7, %8, %9, %10, %11"
      "}, {%12, %13, %14, %15}, %16, p, 1, 1, 1;\n}\n"
    : "+f"(d[0]), "+f"(d[1]), "+f"(d[2]), "+f"(d[3]), "+f"(d[4]), "+f"(d[5]), "+f"(d[6]), "+f"(d[7]),
      "+f"(d[8]), "+f"(d[9]), "+f"(d[10]), "+f"(d[11])
    : "r"(a0), "r"(a1), "r"(a2), "r"(a3), "l"(db), "r"(sd));
}

constexpr int K1_ST = 4, K1_STAGE = 49152;
constexpr int K1_SMEM = K1_ST * K1_STAGE + 1024   + 1024   + 3072   + 128;

__global__ void __cluster_dims__(2, 1, 1) __launch_bounds__(384, 1)
k1_qkv(const __grid_constant__ CUtensorMap tmx, const __grid_constant__ CUtensorMap tmw,
       const bf16* __restrict__ x, const bf16* __restrict__ w, const bf16* __restrict__ wo) {
  extern __shared__ __align__(1024) uint8_t sm[];
  float* cs = (float*)(sm + K1_ST * K1_STAGE);
  float2* rowab = (float2*)(sm + K1_ST * K1_STAGE + 1024);
  float* red = (float*)(sm + K1_ST * K1_STAGE + 2048);
  const uint32_t sbase = smem_u32(sm);
  const uint32_t fullb = sbase + K1_ST * K1_STAGE + 5120, emptyb = fullb + 8 * K1_ST;
  const int tid = threadIdx.x, lane = tid & 31;
  const int warp = __shfl_sync(~0u, tid >> 5, 0);
  const int rank = blockIdx.x & 1, cl = blockIdx.x >> 1;
  const int n = cl & 7, m = (cl >> 3) * 2 + rank;
  if (tid == 0) STAMP(0, 0);

  if (warp == 0) {
    if (lane == 0) {
      prefetch_map(&tmx); prefetch_map(&tmw);
      for (int i = 0; i < K1_ST; i++) { mbar_init(fullb + 8 * i, 1); mbar_init(emptyb + 8 * i, 4); }
      asm volatile("fence.mbarrier_init.release.cluster;" ::: "memory");
    }
    __syncwarp();
    cluster_arrive();
    if (lane == 0) {
      for (int kt = 0; kt < K1_ST; kt++) mbar_expect(fullb + 8 * kt, K1_STAGE);
      tma2d(sbase, &tmx, 0, m * 128, fullb);
    }
    __syncwarp();
    cluster_wait();
    if (tid == 0) STAMP(5, 3);
    if (lane == 0) {
#pragma unroll
      for (int j = 0; j < 4; j++) tma2d_mc(sbase + 16384 + rank * 16384 + j * 4096, &tmw, n * 240 + rank * 128 + j * 32, 0, fullb);
    }
    __syncwarp();
    bar_arrive(4, 384);
    if (lane == 0) {
      for (int kt = 1; kt < 10; kt++) {
        const int s = kt % K1_ST;
        const uint32_t sa = sbase + s * K1_STAGE, sb = sa + 16384 + rank * 16384;
        if (kt >= K1_ST) {
          mbar_wait(emptyb + 8 * s, ((kt / K1_ST) - 1) & 1);
          mbar_expect(fullb + 8 * s, K1_STAGE);
        }
        tma2d(sa, &tmx, kt * 64, m * 128, fullb + 8 * s);
#pragma unroll
        for (int j = 0; j < 4; j++) tma2d_mc(sb + j * 4096, &tmw, n * 240 + rank * 128 + j * 32, kt * 64, fullb + 8 * s);
        if (kt == K1_ST - 1) pdl_trigger();
      }
    }
    __syncwarp();
    cluster_arrive();
  } else if (warp < 4) {
    cluster_arrive();
    const int w3 = warp - 1, t96 = tid - 32;
    const uint32_t tag = __ldcg(&g_epoch) + 1;
    bar_sync(4, 384);
    mbar_wait(fullb, 0);
    {
      const int g = lane >> 2, c = lane & 3;
      uint4 xv[20], wv[14];
      if (w3 < 2) {
        const bf16* xr = x + (size_t)(m * 128 + n * 16 + w3 * 8 + g) * D_ + c * 8;
#pragma unroll
        for (int i = 0; i < 20; i++) xv[i] = ldg_nc(xr + i * 32);
      }
#pragma unroll
      for (int i = 0; i < 14; i++)
        wv[i] = ldg_nc(w + (size_t)(m * 40 + min(w3 + 3 * i, 39)) * 1920 + n * 240 + min(lane, 29) * 8);
      if (w3 < 2) {
        float ds[4] = {0.f, 0.f, 0.f, 0.f}, d0[4] = {0.f, 0.f, 0.f, 0.f}, d1[4] = {0.f, 0.f, 0.f, 0.f};
#pragma unroll
        for (int i = 0; i < 20; i++) {
          mma16816(ds, xv[i].x, xv[i].z, xv[i].y, xv[i].w, 0x3F803F80u, 0x3F803F80u);
          mma16816(d0, xv[i].x, xv[i].z, xv[i].y, xv[i].w, xv[i].x, xv[i].y);
          mma16816(d1, xv[i].x, xv[i].z, xv[i].y, xv[i].w, xv[i].z, xv[i].w);
        }
        const float mean = (ds[0] + ds[2]) * (1.f / D_);
        const float sq = ((g & 1) ? d0[1] + d1[3] : d0[0] + d1[2]) * (1.f / D_);
        if (c == (g >> 1))
          st_relaxed(&g_rowstat[m * 128 + n * 16 + w3 * 8 + g], rsqrtf(fmaxf(sq - mean * mean, 0.f) + 1e-5f), mean, tag);
      }
      const uint32_t idn = (g >> 1) == c ? ((g & 1) ? 0x3F800000u : 0x00003F80u) : 0u;
      float e0[4] = {0.f, 0.f, 0.f, 0.f}, e1[4] = {0.f, 0.f, 0.f, 0.f};
#pragma unroll
      for (int i = 0; i < 14; i++) {
        if (i < 13 || w3 == 0) {
          mma16816(e0, wv[i].x, wv[i].z, wv[i].y, wv[i].w, idn, 0u);
          mma16816(e1, wv[i].x, wv[i].z, wv[i].y, wv[i].w, 0u, idn);
        }
      }
      *(float4*)&red[w3 * 256 + lane * 8] = make_float4(e0[0], e0[1], e1[0], e1[1]);
      *(float4*)&red[w3 * 256 + lane * 8 + 4] = make_float4(e0[2], e0[3], e1[2], e1[3]);
    }
    bar_sync(1, 96);
    for (int i = t96; i < 120; i += 96) {
      const float2 p0 = *(const float2*)&red[i * 2], p1 = *(const float2*)&red[256 + i * 2], p2 = *(const float2*)&red[512 + i * 2];
      st_relaxed(&g_cpart[(m * 8 + n) * 128 + i], p0.x + p1.x + p2.x, p0.y + p1.y + p2.y, tag);
    }
    if (tid == 32) STAMP(5, 7);
    for (int i = t96; i < 128; i += 96) {
      uint32_t it = 0;
      while (true) {
        uint4 p[16];
        const uint4 st = ld_relaxed(&g_rowstat[m * 128 + i]);
#pragma unroll
        for (int k = 0; k < 16; k++) p[k] = ld_relaxed(&g_cpart[(k * 8 + n) * 128 + min(i, 119)]);
        bool ok = st.y == tag && st.w == tag;
        float s0 = 0.f, s1 = 0.f;
#pragma unroll
        for (int k = 0; k < 16; k++) {
          ok = ok && p[k].y == tag && p[k].w == tag;
          s0 += __uint_as_float(p[k].x); s1 += __uint_as_float(p[k].z);
        }
        if (ok) {
          *(float2*)&cs[i * 2] = make_float2(s0, s1);
          rowab[i] = make_float2(__uint_as_float(st.x), -__uint_as_float(st.x) * __uint_as_float(st.z));
          break;
        }
        if (++it > (1u << 20)) wait_timeout();
      }
    }
    __syncwarp();
    bar_arrive(2, 96 + 256);
    bar_sync(1, 96);
    if (tid == 32) STAMP(0, 5);
    {
      uint4 v[5];
      const int ck = min(t96, 79), nt = ck / 10;
#pragma unroll
      for (int i = 0; i < 5; i++) {
        const int k = blockIdx.x * 5 + i, pr = k / 40, r = k - pr * 40;
        v[i] = ldg_nc(wo + (size_t)(pr * 40 + (r < 16 ? r : (r < 32 ? r + 4 : (r < 36 ? r - 16 : r)))) * D_ + ck * 8);
      }
#pragma unroll
      for (int i = 0; i < 5; i++) {
        const int k = blockIdx.x * 5 + i;
        g_wo[((nt * 10 + (k >> 6)) * 10 + ck - nt * 10) * 64 + (k & 63)] = v[i];
        float t = ((bf_lo(v[i].x) + bf_hi(v[i].x)) + (bf_lo(v[i].y) + bf_hi(v[i].y))) +
                  ((bf_lo(v[i].z) + bf_hi(v[i].z)) + (bf_lo(v[i].w) + bf_hi(v[i].w)));
        if (t96 >= 80) t = 0.f;
#pragma unroll
        for (int o = 16; o; o >>= 1) t += __shfl_xor_sync(~0u, t, o);
        if (lane == 0) red[w3 * 8 + i] = t;
      }
      bar_sync(1, 96);
      if (t96 < 5) {
        const float mu = (red[t96] + red[8 + t96] + red[16 + t96]) * (1.f / D_);
        const float hi = bf_lo(pack_bf16(mu, 0.f));
        g_wm[blockIdx.x * 5 + t96] = make_uint4(pack_bf16(hi, mu - hi), 0u, 0u, 0u);
      }
    }
    if (tid == 32) STAMP(0, 7);
    __syncwarp();
    cluster_wait();
    cluster_arrive();
  } else {
    cluster_arrive();
    const int cw = warp - 4, wg = cw >> 2;
    bar_sync(4, 384);
    float acc[120];
    const uint64_t da0 = mkdesc(sbase + wg * 8192, 16, 1024, 1);
    const uint64_t db0 = mkdesc(sbase + 16384, 4096, 512, 2);
    cluster_wait();
#pragma unroll 1
    for (int kt = 0; kt < 10; kt++) {
      const int s = kt % K1_ST;
      mbar_wait(fullb + 8 * s, (kt / K1_ST) & 1);
      if (kt == 0 && tid == 128) STAMP(0, 1);
      const uint64_t da = da0 + s * (K1_STAGE >> 4), db = db0 + s * (K1_STAGE >> 4);
      WG_FENCE();
#pragma unroll
      for (int k = 0; k < 4; k++) wgmma_ss_n240(acc, da + k * 2, db + k * 64, (kt | k) != 0);
      WG_COMMIT();
      if (kt > 0) {
        WG_WAIT(1);
        if (kt - 1 + K1_ST < 10 && (tid & 127) < 2) mbar_arrive_cta(emptyb + 8 * ((kt - 1) % K1_ST), tid & 1);
      }
    }
    cluster_arrive();
    WG_WAIT(0);
    fence_regs(acc);
    if (tid == 128) STAMP(0, 2);
    bar_sync(2, 96 + 256);
    if (tid == 128) STAMP(0, 3);
    const int g = lane >> 2, c = lane & 3;
    const bool lo = c < 2;
    const float2 ab0 = rowab[cw * 16 + g], ab1 = rowab[cw * 16 + g + 8];
    const bool p0 = (POLY_MASK >> (cw * 2)) & 1, p1 = (POLY_MASK >> (cw * 2 + 1)) & 1;
    const uint32_t padq = c == 2 ? 0x3F803F80u : 0x00003F80u, padk = c == 2 ? 0x4A7A4B00u : 0x00004653u;
    const uint32_t padv = c == 2 ? 0x00003F80u : 0u;
    uint8_t* dst = (uint8_t*)g_qkv + (size_t)(n * 12) * HEAD_IMG + m * 6144 + lane * 4;
#pragma unroll
    for (int hp = 0; hp < 6; hp++) {
      const int sec = (n * 12 + hp * 2) >> 5;
      const float f0 = sec == 0 ? QSCALE : (sec == 1 && p0 ? 32768.f : 1.f), f1 = sec == 0 ? QSCALE : (sec == 1 && p1 ? 32768.f : 1.f);
      const uint32_t pad0 = sec == 0 ? padq : (sec == 2 ? padv : (p0 ? padk : 0u));
      const uint32_t pad1 = sec == 0 ? padq : (sec == 2 ? padv : (p1 ? padk : 0u));
      const float a0 = ab0.x * f0, b0 = ab0.y * f0, a1 = ab1.x * f1, b1 = ab1.y * f1;
      uint32_t u[5], v[5];
      float su[5], sv[5];
#pragma unroll
      for (int i = 0; i < 5; i++) {
        const int j = hp * 5 + i;
        const float2 t = *(const float2*)&cs[j * 8 + c * 2];
        const float x0 = fmaf(acc[4 * j], a0, b0 * t.x), x1 = fmaf(acc[4 * j + 1], a0, b0 * t.y);
        const float y0 = fmaf(acc[4 * j + 2], a1, b1 * t.x), y1 = fmaf(acc[4 * j + 3], a1, b1 * t.y);
        u[i] = pack_bf16(x0, x1); v[i] = pack_bf16(y0, y1);
        su[i] = fmaf(x0, x0, x1 * x1); sv[i] = fmaf(y0, y0, y1 * y1);
      }
      if (sec < 2) {
        const float r0 = (sec == 1 && p0) ? 9.313225746154785e-10f : 1.f, r1 = (sec == 1 && p1) ? 9.313225746154785e-10f : 1.f;
        float e0 = (su[0] + su[1] + (lo ? su[2] : 0.f)) * r0, e1 = (sv[0] + sv[1] + (lo ? sv[2] : 0.f)) * r1;
        float o0 = (su[3] + su[4] + (lo ? 0.f : su[2])) * r0, o1 = (sv[3] + sv[4] + (lo ? 0.f : sv[2])) * r1;
        e0 += __shfl_xor_sync(~0u, e0, 1); e1 += __shfl_xor_sync(~0u, e1, 1);
        o0 += __shfl_xor_sync(~0u, o0, 1); o1 += __shfl_xor_sync(~0u, o1, 1);
        e0 += __shfl_xor_sync(~0u, e0, 2); e1 += __shfl_xor_sync(~0u, e1, 2);
        o0 += __shfl_xor_sync(~0u, o0, 2); o1 += __shfl_xor_sync(~0u, o1, 2);
        const uint32_t em = __reduce_max_sync(~0u, max(__float_as_uint(e0), __float_as_uint(e1)));
        const uint32_t om = __reduce_max_sync(~0u, max(__float_as_uint(o0), __float_as_uint(o1)));
        if (lane < 2) g_nrm[(n * 12 + hp * 2 + lane) * 128 + m * 8 + cw] = __uint_as_float(lane ? om : em);
      }
      const int cst = sec == 1 ? 2048 : 128, gst = sec == 1 ? 128 : 384;
      uint8_t* pe = dst + (size_t)hp * 2 * HEAD_IMG + cw * 2 * gst;
      uint8_t* pf = pe + gst;
      *(uint32_t*)(pe) = u[0];       *(uint32_t*)(pf) = v[0];
      *(uint32_t*)(pe + cst) = u[1]; *(uint32_t*)(pf + cst) = v[1];
      *(uint32_t*)(pe + 2 * cst) = lo ? u[2] : pad0; *(uint32_t*)(pf + 2 * cst) = lo ? v[2] : pad1;
      *(uint32_t*)(pe + HEAD_IMG) = __shfl_xor_sync(~0u, lo ? u[3] : u[2], 2);
      *(uint32_t*)(pf + HEAD_IMG) = __shfl_xor_sync(~0u, lo ? v[3] : v[2], 2);
      *(uint32_t*)(pe + cst + HEAD_IMG) = __shfl_xor_sync(~0u, lo ? u[4] : u[3], 2);
      *(uint32_t*)(pf + cst + HEAD_IMG) = __shfl_xor_sync(~0u, lo ? v[4] : v[3], 2);
      const uint32_t tu = __shfl_xor_sync(~0u, u[4], 2), tv = __shfl_xor_sync(~0u, v[4], 2);
      *(uint32_t*)(pe + 2 * cst + HEAD_IMG) = lo ? tu : pad0; *(uint32_t*)(pf + 2 * cst + HEAD_IMG) = lo ? tv : pad1;
    }
    if (tid == 128) STAMP(0, 4);
  }
  cluster_wait();
  if (tid == 128) STAMP(0, 6);
}

constexpr int K2_SMEM = 2 * HEAD_IMG + 2 * 6144 + 2 * 10240 + 256;

__device__ __forceinline__ uint64_t desc64(uint32_t lo, uint32_t hi) {
  uint64_t d;
  asm("mov.b64 %0, {%1, %2};" : "=l"(d) : "r"(lo), "r"(hi));
  return d;
}
__device__ __forceinline__ uint32_t exp_pair(bool poly, float a, float b, uint32_t mk) {
  if (poly) {
    const uint32_t pk = __byte_perm(__float_as_uint(a), __float_as_uint(b), 0x6521);
    uint32_t m, q;
    asm("lop3.b32 %0, %1, %2, 0x3f803f80, 0xEA;" : "=r"(m) : "r"(pk), "r"(mk));
    asm("fma.rn.bf16x2 %0, %1, %1, %2;" : "=r"(q) : "r"(m), "r"(0x40014001u));
    return pk - m + q;
  }
  return pack_bf16(ex2(a), ex2(b));
}
#define PV_GR 2
__device__ __forceinline__ void exp_pv(const float (&s)[64], float (&o)[12], uint64_t dv, uint32_t mk) {
#pragma unroll
  for (int k0 = 0; k0 < 8; k0 += PV_GR) {
    uint32_t p[4 * PV_GR];
#pragma unroll
    for (int i = 0; i < 4 * PV_GR; i++)
      p[i] = exp_pair((POLY_MASK >> (k0 * 2 + i / 2)) & 1, s[k0 * 8 + 2 * i], s[k0 * 8 + 2 * i + 1], mk);
    WG_FENCE();
#pragma unroll
    for (int k = 0; k < PV_GR; k++)
      wgmma_rs_n24(o, p[4 * k], p[4 * k + 1], p[4 * k + 2], p[4 * k + 3], dv + (k0 + k) * 48, 1);
  }
}
__device__ __forceinline__ void load_q(uint32_t (&q)[6], const uint8_t* p) {
  q[0] = __ldcg((const uint32_t*)p);         q[1] = __ldcg((const uint32_t*)(p + 384));
  q[2] = __ldcg((const uint32_t*)(p + 128)); q[3] = __ldcg((const uint32_t*)(p + 512));
  q[4] = __ldcg((const uint32_t*)(p + 256)); q[5] = __ldcg((const uint32_t*)(p + 640));
}
__device__ __forceinline__ float rcp(float x) {
  float y;
  asm("rcp.approx.ftz.f32 %0, %1;" : "=f"(y) : "f"(x));
  return y;
}
__device__ __forceinline__ int img_off(int chunk) { return (chunk >> 3) * 16384 + (chunk & 7) * 128; }
__device__ __forceinline__ void store_o(const float (&o)[12], int tile) {
  int tid, bid;
  asm volatile("mov.u32 %0, %%tid.x;" : "=r"(tid));
  asm volatile("mov.u32 %0, %%ctaid.x;" : "=r"(bid));
  const int head = bid >> 2;
  uint8_t* dst = (uint8_t*)g_o + ((bid & 3) * 4 + (tile >> 1)) * 163840 + (tile & 1) * 8192 + ((tid >> 5) & 3) * 2048 + (tid & 31) * 4;
  const int oc = (head >> 1) * 5 + (head & 1) * 2;
  const int o0 = img_off(oc), o1 = img_off(oc + 1), o2 = img_off((head >> 1) * 5 + 4) + (head & 1) * 8;
  const float i0 = rcp(__shfl_sync(~0u, o[8], 2, 4)), i1 = rcp(__shfl_sync(~0u, o[10], 2, 4));
  *(uint32_t*)(dst + o0) = pack_bf16(o[0] * i0, o[1] * i0); *(uint32_t*)(dst + o0 + 1024) = pack_bf16(o[2] * i1, o[3] * i1);
  *(uint32_t*)(dst + o1) = pack_bf16(o[4] * i0, o[5] * i0); *(uint32_t*)(dst + o1 + 1024) = pack_bf16(o[6] * i1, o[7] * i1);
  if ((tid & 3) < 2) {
    *(uint32_t*)(dst + o2) = pack_bf16(o[8] * i0, o[9] * i0);
    *(uint32_t*)(dst + o2 + 1024) = pack_bf16(o[10] * i1, o[11] * i1);
  }
}

__global__ void __launch_bounds__(512, 1)
k2_attn(const __grid_constant__ CUtensorMap tmg, const __grid_constant__ CUtensorMap tmu,
        const __grid_constant__ CUtensorMap tmd, uint32_t mk) {
  extern __shared__ __align__(1024) uint8_t sm[];
  const uint32_t sbase = smem_u32(sm);
  float* part = (float*)(sm + 2 * HEAD_IMG);
  const uint32_t rbuf = sbase + 2 * HEAD_IMG + 2 * 6144;
  const uint32_t kvb = rbuf + 2 * 10240;
  const uint32_t partb = kvb + 128, rbar = kvb + 144;
  const int tid = threadIdx.x, lane = tid & 31;
  const int warp = __shfl_sync(~0u, tid >> 5, 0);
  const int head = blockIdx.x >> 2, qb = blockIdx.x & 3;

  if (tid == 0) STAMP(1, 0);
  if (tid == 0) {
    for (int i = 0; i < 16; i++) mbar_init(kvb + 8 * i, 1);
    mbar_init(partb, 128); mbar_init(partb + 8, 128); mbar_init(rbar, 1); mbar_init(rbar + 8, 1);
    asm volatile("fence.mbarrier_init.release.cluster;" ::: "memory");
  }
  __syncthreads();

  if (warp >= 12) {
    asm volatile("setmaxnreg.dec.sync.aligned.u32 32;");
    if (tid == 384) {
      pdl_wait();
      pdl_trigger();
      const uint8_t* kimg = (const uint8_t*)g_qkv + (size_t)(32 + head) * HEAD_IMG;
#pragma unroll 1
      for (int b = 0; b < 16; b++) {
        mbar_expect(kvb + 8 * b, 12288);
        bulk_ld(sbase + b * 6144, kimg + b * 6144, 6144, kvb + 8 * b);
        bulk_ld(sbase + HEAD_IMG + b * 6144, kimg + 32 * HEAD_IMG + b * 6144, 6144, kvb + 8 * b);
      }
      if (blockIdx.x == 0) g_epoch = g_epoch + 1;
      mbar_wait(kvb + 8 * 15, 0);
      uint8_t* pdst = nullptr;
      uint32_t pbytes = 0;
#pragma unroll 1
      for (int i = 0; i < 7; i++) {
        const int p = blockIdx.x + 128 * i;
        uint8_t* dst = nullptr;
        uint32_t bytes = 0;
        if (i < 6 && p < 696) {
          asm volatile("cp.async.bulk.wait_group.read 0;" ::: "memory");
          if (p < 480) {
            const int nk = p / 6, r = p - nk * 6, nt = nk / 10, kt = nk - nt * 10, up = r / 3;
            bytes = 9216;
            dst = (uint8_t*)g_wgu + (size_t)(nk * 54 + r * 9) * 1024;
            mbar_expect(rbar + 8 * (i & 1), bytes);
            tma3d(rbuf + (i & 1) * 10240, up ? &tmu : &tmg, kt * 64, nt * 27 + (r - up * 3) * 9, rbar + 8 * (i & 1));
          } else {
            const int nk = p - 480, nt = nk / 27, kt = nk - nt * 27;
            bytes = 10240;
            dst = (uint8_t*)g_wd + (size_t)nk * 10240;
            mbar_expect(rbar + 8 * (i & 1), bytes);
            tma3d(rbuf + (i & 1) * 10240, &tmd, kt * 64, nt * 10, rbar + 8 * (i & 1));
          }
        }
        if (pbytes) {
          mbar_wait(rbar + 8 * ((i - 1) & 1), ((i - 1) >> 1) & 1);
          bulk_st(pdst, rbuf + ((i - 1) & 1) * 10240, pbytes);
          asm volatile("cp.async.bulk.commit_group;" ::: "memory");
        }
        pdst = dst; pbytes = bytes;
      }
      asm volatile("cp.async.bulk.wait_group.read 0;" ::: "memory");
      STAMP(1, 6);
    }
  } else {
    asm volatile("setmaxnreg.inc.sync.aligned.u32 160;");
    const int wg = warp >> 2;
    const uint8_t* qthr = (const uint8_t*)g_qkv + (size_t)head * HEAD_IMG + qb * 64 * 384 + (warp & 3) * 768 + lane * 4;
    const uint32_t klo0 = ((sbase & 0x3FFFF) >> 4) | (128u << 16), vlo0 = (((sbase + HEAD_IMG) & 0x3FFFF) >> 4) | (24u << 16);
    constexpr uint64_t KSTEP2 = (uint64_t)(int64_t)(256 - (128 << 16));
    constexpr uint64_t KV2K = 384 - (HEAD_IMG >> 4) + (104 << 16);
    const int nun = wg == 1 ? 4 : 3;
    uint32_t utile = wg == 0 ? 0x210u : (wg == 1 ? 0x4325u : 0x576u);
    uint32_t ubeg = wg == 0 ? 0u : (wg == 1 ? 0x00b0u : 0x600u);
    uint32_t ulen = wg == 0 ? 0x0b1010u : (wg == 1 ? 0x10100506u : 0x0a1010u);
    pdl_wait();
    if (tid == 0) STAMP(1, 1);
    uint32_t q[6];
    load_q(q, qthr + (utile & 15) * 3072);
    bool fast;
    {
      const float4 kn = __ldcg((const float4*)&g_nrm[(32 + head) * 128 + lane * 4]);
      const float qv = __ldcg(&g_nrm[head * 128 + qb * 32 + lane]);
      const uint32_t km = max(max(__float_as_uint(kn.x), __float_as_uint(kn.y)), max(__float_as_uint(kn.z), __float_as_uint(kn.w)));
      const float k2 = __uint_as_float(__reduce_max_sync(~0u, km)), q2 = __uint_as_float(__reduce_max_sync(~0u, __float_as_uint(qv)));
      fast = q2 * k2 <= 3400.f;
    }
    if (fast) {
#pragma unroll 1
      for (int u = 0; u < nun; u++) {
        const uint32_t b0 = ubeg & 15;
        const bool wt = u == 0 || (wg == 1 && u < 3);
        float s[64], o[12];
#pragma unroll
        for (int i = 0; i < 12; i++) o[i] = 0.f;
        uint32_t vlo = vlo0 + b0 * 384, kb = kvb + b0 * 8;
        const uint32_t vend = vlo + ((ulen & 255) - 1) * 384;
        if (wt) mbar_wait(kb, 0);
        if (tid == 0) STAMP(5, 4 + u);
        fence_regs(o);
        WG_FENCE();
        wgmma_rs_n128(s, q[0], q[1], q[2], q[3], desc64(klo0 + b0 * 384, 8), 0);
        wgmma_rs_n128(s, q[4], q[5], 0, 0, desc64(klo0 + b0 * 384, 8) + KSTEP2, 1);
        WG_COMMIT();
#pragma unroll 1
        for (; vlo != vend; vlo += 384) {
          if (wt) { kb += 8; mbar_wait(kb, 0); }
          WG_WAIT(0);
          fence_regs(s); fence_regs(o);
          const uint64_t dv = desc64(vlo, 8);
          exp_pv(s, o, dv, mk);
          wgmma_rs_n128(s, q[0], q[1], q[2], q[3], dv + KV2K, 0);
          wgmma_rs_n128(s, q[4], q[5], 0, 0, dv + (KV2K + KSTEP2), 1);
          WG_COMMIT();
        }
        WG_WAIT(0);
        fence_regs(s); fence_regs(o);
        if (u + 1 < nun) load_q(q, qthr + ((utile >> 4) & 15) * 3072);
        exp_pv(s, o, desc64(vlo, 8), mk);
        WG_COMMIT();
        WG_WAIT(0);
        fence_regs(o);
        if (wg == 1 && u < 2) {
          float4* pp = (float4*)(part + u * 1536) + (tid & 127);
          pp[0] = make_float4(o[0], o[1], o[2], o[3]);
          pp[128] = make_float4(o[4], o[5], o[6], o[7]);
          pp[256] = make_float4(o[8], o[9], o[10], o[11]);
          mbar_arrive(partb + 8 * u);
        } else {
          if (wg != 1 && u == 2) {
            const int pi = wg == 0 ? 1 : 0;
            mbar_wait(partb + 8 * pi, 0);
            const float4* pp = (const float4*)(part + pi * 1536) + (tid & 127);
            const float4 x0 = pp[0], x1 = pp[128], x2 = pp[256];
            o[0] += x0.x; o[1] += x0.y; o[2] += x0.z; o[3] += x0.w; o[4] += x1.x; o[5] += x1.y;
            o[6] += x1.z; o[7] += x1.w; o[8] += x2.x; o[9] += x2.y; o[10] += x2.z; o[11] += x2.w;
          }
          store_o(o, utile & 15);
        }
        utile >>= 4; ubeg >>= 4; ulen >>= 8;
      }
      if ((tid & 127) == 0) STAMP(1, 3 + wg);
    } else {
#pragma unroll 1
      for (int tile = wg; tile < 8; tile += 3) {
        load_q(q, qthr + tile * 3072);
        if ((lane & 3) >= 2) { q[4] = 0; q[5] = 0; }
        float o[12], m0 = -INFINITY, m1 = -INFINITY;
#pragma unroll
        for (int i = 0; i < 12; i++) o[i] = 0.f;
#pragma unroll 1
        for (int b = 0; b < 16; b++) {
          float s[64];
          mbar_wait(kvb + 8 * b, 0);
          WG_FENCE();
          wgmma_rs_n128(s, q[0], q[1], q[2], q[3], desc64(klo0 + b * 384, 8), 0);
          wgmma_rs_n128(s, q[4], q[5], 0, 0, desc64(klo0 + b * 384, 8) + KSTEP2, 1);
          WG_COMMIT();
          WG_WAIT(0);
          fence_regs(s);
          float x0 = m0, x1 = m1;
#pragma unroll
          for (int j = 0; j < 16; j++) {
            if ((POLY_MASK >> j) & 1) {
#pragma unroll
              for (int i = 0; i < 4; i++) s[4 * j + i] *= (1.f / 32768.f);
            }
            x0 = fmaxf(x0, fmaxf(s[4 * j], s[4 * j + 1]));
            x1 = fmaxf(x1, fmaxf(s[4 * j + 2], s[4 * j + 3]));
          }
          x0 = fmaxf(x0, __shfl_xor_sync(~0u, x0, 1)); x0 = fmaxf(x0, __shfl_xor_sync(~0u, x0, 2));
          x1 = fmaxf(x1, __shfl_xor_sync(~0u, x1, 1)); x1 = fmaxf(x1, __shfl_xor_sync(~0u, x1, 2));
          const float al0 = ex2(m0 - x0), al1 = ex2(m1 - x1);
          m0 = x0; m1 = x1;
#pragma unroll
          for (int i = 0; i < 12; i++) o[i] *= (i & 2) ? al1 : al0;
          uint32_t p[32];
#pragma unroll
          for (int i = 0; i < 32; i++) {
            const float mm = (i & 1) ? m1 : m0;
            p[i] = pack_bf16(ex2(s[2 * i] - mm), ex2(s[2 * i + 1] - mm));
          }
          fence_regs(o);
          WG_FENCE();
#pragma unroll
          for (int k = 0; k < 8; k++)
            wgmma_rs_n24(o, p[4 * k], p[4 * k + 1], p[4 * k + 2], p[4 * k + 3], desc64(vlo0 + b * 384 + k * 48, 8), 1);
          WG_COMMIT();
          WG_WAIT(0);
          fence_regs(o);
        }
        store_o(o, tile);
      }
    }
  }
}

constexpr int K3_ST = 4, K3_STAGE = 37888;
constexpr int K3_SMEM = K3_ST * K3_STAGE + 45056 + 20480 + 256;

template <int N> struct Acc { float v[N]; };

template <int NB, int NK, bool FIRST>
__global__ void __cluster_dims__(2, 1, 1) __launch_bounds__(384, 1)
k3_proj(const __grid_constant__ CUtensorMap tmr, const uint4* __restrict__ aimg, const uint4* __restrict__ wimg) {
  constexpr int KT = 2 * NB + NK, EX = FIRST ? 1 : 0;
  extern __shared__ __align__(1024) uint8_t sm[];
  const uint32_t sbase = smem_u32(sm);
  uint8_t* xch = sm + K3_ST * K3_STAGE;
  uint8_t* stg = sm + K3_ST * K3_STAGE + 45056;
  const uint32_t fullb = smem_u32(stg) + 20480, emptyb = fullb + 8 * K3_ST, resb = emptyb + 8 * K3_ST, xchb = resb + 8;
  const int tid = threadIdx.x, lane = tid & 31;
  const int warp = __shfl_sync(~0u, tid >> 5, 0);
  const int rank = blockIdx.x & 1;
  const int n = blockIdx.x & 7, m = blockIdx.x >> 3;
  if (tid == 0) STAMP(FIRST ? 2 : 4, 0);
  if (warp == 0) {
    if (lane == 0) {
      prefetch_map(&tmr);
      for (int i = 0; i < K3_ST; i++) { mbar_init(fullb + 8 * i, 1); mbar_init(emptyb + 8 * i, 2); }
      mbar_init(resb, 1); mbar_init(xchb, 1);
      mbar_expect(xchb, 4096 * (10 + EX));
      asm volatile("fence.mbarrier_init.release.cluster;" ::: "memory");
    }
    __syncwarp();
    cluster_arrive();
    bar_arrive(4, 256 + 32);
    if (lane == 0) {
      const uint8_t* wk = (const uint8_t*)wimg + (size_t)n * KT * 10240;
      const uint8_t* ws = (const uint8_t*)wimg + (size_t)(n ^ 1) * KT * 10240;
      const uint8_t* ab = (const uint8_t*)aimg + (size_t)m * KT * 16384;
#pragma unroll 1
      for (int i = 0; i < NB + NK; i++) {
        const int s = i % K3_ST, kt = i < NB ? i + rank * (NB + NK) : i;
        const uint32_t sa = sbase + s * K3_STAGE;
        if (i >= K3_ST) mbar_wait(emptyb + 8 * s, ((i / K3_ST) - 1) & 1);
        mbar_expect(fullb + 8 * s, 26624 + EX * 1024 + (i < NB ? 10240 : 0));
        if (i > 0) bulk_ld(sa, ab + kt * 16384, 16384, fullb + 8 * s);
        bulk_ld(sa + 16384, wk + kt * 10240, 10240, fullb + 8 * s);
        if (FIRST) bulk_ld(sa + 26624, (const uint8_t*)g_wm + kt * 1024, 1024, fullb + 8 * s);
        if (i < NB) bulk_ld(sa + 26624 + EX * 1024, ws + kt * 10240, 10240, fullb + 8 * s);
        if (i == 0) {
          pdl_wait();
          pdl_trigger();
          bulk_ld(sa, ab + kt * 16384, 16384, fullb);
        }
        if (FIRST && i == K3_ST - 1) {
          mbar_expect(resb, 20480);
          tma2d(smem_u32(stg), &tmr, n * 80, m * 128, resb);
          tma2d(smem_u32(stg) + 10240, &tmr, n * 80, m * 128 + 64, resb);
        }
      }
    }
    __syncwarp();
    cluster_wait();
  } else if (warp >= 4) {
    cluster_arrive();
    const int cw = warp - 4, wg = cw >> 2;
    const int g = lane >> 2, c = lane & 3;
    const int row = m * 128 + cw * 16 + g;
    uint8_t* himg = (uint8_t*)g_h + (size_t)m * 163840 + cw * 2048 + lane * 4;
    uint32_t rv[20];
    float mu0, mu1;
    if (FIRST) {
      mu0 = __uint_as_float(__ldcg(&g_rowstat[row].z)); mu1 = __uint_as_float(__ldcg(&g_rowstat[row + 8].z));
    } else {
      mu0 = __ldcg(&g_hmean[row]); mu1 = __ldcg(&g_hmean[row + 8]);
#pragma unroll
      for (int j = 0; j < 10; j++) {
        rv[2 * j] = __ldcg((const uint32_t*)(himg + img_off(n * 10 + j)));
        rv[2 * j + 1] = __ldcg((const uint32_t*)(himg + img_off(n * 10 + j) + 1024));
      }
    }
    float acc[80 + 4 * EX];
    float (&keep)[40 + 4 * EX] = ((Acc<40 + 4 * EX>*)acc)->v;
    const uint64_t da0 = mkdesc(sbase + wg * 8192, 128, 1024, 0);
    const uint64_t db0 = mkdesc(sbase + 16384, 128, 1024, 0);
    bar_sync(4, 256 + 32);
#pragma unroll 1
    for (int i = 0; i < NB; i++) {
      const int s = i % K3_ST;
      mbar_wait(fullb + 8 * s, (i / K3_ST) & 1);
      if (i == 0 && tid == 128) STAMP(FIRST ? 2 : 4, 2);
      const uint64_t da = da0 + s * (K3_STAGE >> 4), db = db0 + s * (K3_STAGE >> 4);
      WG_FENCE();
#pragma unroll
      for (int k = 0; k < 4; k++) {
        if constexpr (FIRST) wgmma_ss_n168(acc, da + k * 16, db + k * 16, (i | k) != 0);
        else wgmma_ss_n160(acc, da + k * 16, db + k * 16, (i | k) != 0);
      }
      WG_COMMIT();
      if (i > 0) {
        WG_WAIT(1);
        if ((tid & 127) == 0) mbar_arrive(emptyb + 8 * ((i - 1) % K3_ST));
      }
    }
    cluster_wait();
    const uint32_t rx = mapa(smem_u32(xch) + (tid - 128) * 16, rank ^ 1), rb = mapa(xchb, rank ^ 1);
    WG_WAIT(0);
    fence_regs(acc);
    if ((tid & 127) == 0) mbar_arrive(emptyb + 8 * ((NB - 1) % K3_ST));
    if (FIRST) st_async4(rx, acc[40], acc[41], acc[42], acc[43], rb);
    if (tid == 128) STAMP(FIRST ? 2 : 4, 1);
#pragma unroll
    for (int i = NB; i < NB + NK; i++) {
      const int s = i % K3_ST;
      mbar_wait(fullb + 8 * s, (i / K3_ST) & 1);
      const uint64_t da = da0 + s * (K3_STAGE >> 4), db = db0 + s * (K3_STAGE >> 4);
      WG_FENCE();
#pragma unroll
      for (int k = 0; k < 4; k++) {
        if constexpr (FIRST) wgmma_ss_n88(keep, da + k * 16, db + k * 16, 1);
        else wgmma_ss_n80(keep, da + k * 16, db + k * 16, 1);
      }
      WG_COMMIT();
      if (i > NB && i - 1 + K3_ST < NB + NK) {
        WG_WAIT(1);
        if ((tid & 127) == 0) mbar_arrive(emptyb + 8 * ((i - 1) % K3_ST));
      }
#pragma unroll
      for (int j = (i - NB) * 3 + EX; j < (i - NB) * 3 + 3 + EX; j++)
        if (j < 10 + EX) st_async4(rx + j * 4096, acc[40 + 4 * j], acc[41 + 4 * j], acc[42 + 4 * j], acc[43 + 4 * j], rb);
    }
    uint8_t* sp = stg + (cw * 16 + g) * 160 + c * 4;
    if (FIRST) {
      mbar_wait(resb, 0);
#pragma unroll
      for (int j = 0; j < 10; j++) {
        rv[2 * j] = *(const uint32_t*)(sp + j * 16);
        rv[2 * j + 1] = *(const uint32_t*)(sp + 1280 + j * 16);
      }
    }
    WG_WAIT(0);
    fence_regs(keep);
    if (tid == 128) STAMP(FIRST ? 2 : 4, 3);
    mbar_wait(xchb, 0);
    if (tid == 128) STAMP(FIRST ? 2 : 4, 5);
    const uint8_t* xp = xch + (tid - 128) * 16;
    if (FIRST) {
      const float4 p = *(const float4*)xp;
      mu0 += __shfl_sync(~0u, (keep[40] + p.x) + (keep[41] + p.y), 0, 4);
      mu1 += __shfl_sync(~0u, (keep[42] + p.z) + (keep[43] + p.w), 0, 4);
      if (n == 0 && c == 0) { g_hmean[row] = mu0; g_hmean[row + 8] = mu1; }
      mu0 = -mu0; mu1 = -mu1;
    }
    float q0 = 0.f, q1 = 0.f;
#pragma unroll
    for (int j = 0; j < 10; j++) {
      const float4 p = *(const float4*)(xp + (j + EX) * 4096);
      const float x0 = (keep[4 * j] + p.x) + (bf_lo(rv[2 * j]) + mu0), x1 = (keep[4 * j + 1] + p.y) + (bf_hi(rv[2 * j]) + mu0);
      const float y0 = (keep[4 * j + 2] + p.z) + (bf_lo(rv[2 * j + 1]) + mu1), y1 = (keep[4 * j + 3] + p.w) + (bf_hi(rv[2 * j + 1]) + mu1);
      if (FIRST) {
        *(uint32_t*)(himg + img_off(n * 10 + j)) = pack_bf16(x0, x1);
        *(uint32_t*)(himg + img_off(n * 10 + j) + 1024) = pack_bf16(y0, y1);
        q0 = fmaf(x0, x0, fmaf(x1, x1, q0)); q1 = fmaf(y0, y0, fmaf(y1, y1, q1));
      } else {
        *(uint32_t*)(sp + j * 16) = pack_bf16(x0, x1);
        *(uint32_t*)(sp + 1280 + j * 16) = pack_bf16(y0, y1);
      }
    }
    if (FIRST) {
      q0 += __shfl_xor_sync(~0u, q0, 1); q0 += __shfl_xor_sync(~0u, q0, 2);
      q1 += __shfl_xor_sync(~0u, q1, 1); q1 += __shfl_xor_sync(~0u, q1, 2);
      if (c < 2) g_hpart[n * S_ + row + c * 8] = c ? q1 : q0;
    } else {
      fence_async();
      bar_sync(1 + wg, 128);
      if ((tid & 127) == 0) {
        tma2d_st(&tmr, n * 80, m * 128 + wg * 64, smem_u32(stg) + wg * 10240);
        bulk_commit_wait();
      }
      __syncwarp();
    }
    if (tid == 128) STAMP(FIRST ? 2 : 4, 4);
  } else {
    cluster_arrive();
    cluster_wait();
  }
}

constexpr int K4_ST = 3, K4_STAGE = 71680;
constexpr int K4_SMEM = K4_ST * K4_STAGE + 64;

__global__ void __cluster_dims__(2, 1, 1) __launch_bounds__(256, 1)
k4_ffn1() {
  extern __shared__ __align__(1024) uint8_t sm[];
  const uint32_t sbase = smem_u32(sm);
  const uint32_t fullb = sbase + K4_ST * K4_STAGE, emptyb = fullb + 8 * K4_ST;
  const int tid = threadIdx.x, lane = tid & 31;
  const int warp = __shfl_sync(~0u, tid >> 5, 0);
  const int rank = blockIdx.x & 1, cl = blockIdx.x >> 1;
  const int n = cl & 7, m = (cl >> 3) * 2 + rank;
  const uint8_t* wb = (const uint8_t*)g_wgu + (size_t)n * 10 * 55296 + rank * 27648;
  const uint8_t* ab = (const uint8_t*)g_h + (size_t)m * 163840;
  if (tid == 0) STAMP(3, 0);
  if (tid == 0) {
    for (int i = 0; i < K4_ST; i++) { mbar_init(fullb + 8 * i, 1); mbar_init(emptyb + 8 * i, 4); }
    asm volatile("fence.mbarrier_init.release.cluster;" ::: "memory");
    for (int kt = 0; kt < K4_ST; kt++) mbar_expect(fullb + 8 * kt, K4_STAGE);
  }
  __syncthreads();
  cluster_arrive();
  cluster_wait();
  if (tid == 0) bulk_ld_mc(sbase + 16384 + rank * 27648, wb, 27648, fullb);
  pdl_wait();
  pdl_trigger();
  if (tid == 128) STAMP(3, 1);
  if (tid == 0) {
    bulk_ld(sbase, ab, 16384, fullb);
    for (int kt = 1; kt < K4_ST; kt++) {
      bulk_ld(sbase + kt * K4_STAGE, ab + kt * 16384, 16384, fullb + 8 * kt);
      bulk_ld_mc(sbase + kt * K4_STAGE + 16384 + rank * 27648, wb + kt * 55296, 27648, fullb + 8 * kt);
    }
  }
  __syncwarp();
  float r0, r1;
  {
    const float* hp = &g_hpart[(lane & 3) * 2 * S_ + m * 128 + warp * 16 + (lane >> 2)];
    r0 = __ldcg(hp) + __ldcg(hp + S_);
    r1 = __ldcg(hp + 8) + __ldcg(hp + S_ + 8);
  }
  float ag[108], au[108];
  const uint64_t da0 = mkdesc(sbase + (warp >> 2) * 8192, 128, 1024, 0);
  const uint64_t db0 = mkdesc(sbase + 16384, 128, 1024, 0);
#pragma unroll 1
  for (int kt = 0; kt < 10; kt++) {
    const int s = kt % K4_ST;
    mbar_wait(fullb + 8 * s, (kt / K4_ST) & 1);
    if (kt == 0 && tid == 128) STAMP(3, 2);
    const uint64_t da = da0 + s * (K4_STAGE >> 4), db = db0 + s * (K4_STAGE >> 4);
    WG_FENCE();
#pragma unroll
    for (int k = 0; k < 4; k++) {
      wgmma_ss_n216(ag, da + k * 16, db + k * 16, (kt | k) != 0);
      wgmma_ss_n216(au, da + k * 16, db + 1728 + k * 16, (kt | k) != 0);
    }
    WG_COMMIT();
    if (kt > 0 && kt - 1 + K4_ST < 10) {
      WG_WAIT(1);
      const int sp = (kt - 1) % K4_ST;
      if ((tid & 127) < 2) mbar_arrive_cta(emptyb + 8 * sp, tid & 1);
      if (tid == 0) {
        const uint32_t sa = sbase + sp * K4_STAGE;
        mbar_wait(emptyb + 8 * sp, ((kt - 1) / K4_ST) & 1);
        mbar_expect(fullb + 8 * sp, K4_STAGE);
        bulk_ld_mc(sa + 16384 + rank * 27648, wb + (kt - 1 + K4_ST) * 55296, 27648, fullb + 8 * sp);
        bulk_ld(sa, ab + (kt - 1 + K4_ST) * 16384, 16384, fullb + 8 * sp);
      }
      __syncwarp();
    }
  }
  r0 += __shfl_xor_sync(~0u, r0, 1); r1 += __shfl_xor_sync(~0u, r1, 1);
  r0 += __shfl_xor_sync(~0u, r0, 2); r1 += __shfl_xor_sync(~0u, r1, 2);
  r0 = __frcp_rn(r0 * (1.f / D_) + 1e-5f); r1 = __frcp_rn(r1 * (1.f / D_) + 1e-5f);
  cluster_arrive();
  WG_WAIT(0);
  fence_regs(ag); fence_regs(au);
  if (tid == 128) STAMP(3, 3);
  uint8_t* dst = (uint8_t*)g_hh + (size_t)m * 27 * 16384 + warp * 2048 + lane * 4;
#pragma unroll
  for (int j = 0; j < 27; j++) {
    *(uint32_t*)(dst + img_off(n * 27 + j)) = pack_bf16(ag[4 * j] * r0 * au[4 * j], ag[4 * j + 1] * r0 * au[4 * j + 1]);
    *(uint32_t*)(dst + img_off(n * 27 + j) + 1024) = pack_bf16(ag[4 * j + 2] * r1 * au[4 * j + 2], ag[4 * j + 3] * r1 * au[4 * j + 3]);
  }
  if (tid == 128) STAMP(3, 4);
  cluster_wait();
}

typedef CUresult (*EncodeFn)(CUtensorMap*, CUtensorMapDataType, cuuint32_t, void*, const cuuint64_t*, const cuuint64_t*,
                             const cuuint32_t*, const cuuint32_t*, CUtensorMapInterleave, CUtensorMapSwizzle,
                             CUtensorMapL2promotion, CUtensorMapFloatOOBfill);

static CUtensorMap make_map(EncodeFn enc, const void* p, uint64_t inner, uint64_t outer, uint32_t box_inner,
                            uint32_t box_outer, CUtensorMapSwizzle swz) {
  CUtensorMap m;
  cuuint64_t gd[2] = {inner, outer};
  cuuint64_t gs[1] = {inner * 2};
  cuuint32_t bd[2] = {box_inner, box_outer};
  cuuint32_t es[2] = {1, 1};
  enc(&m, CU_TENSOR_MAP_DATA_TYPE_BFLOAT16, 2, (void*)p, gd, gs, bd, es, CU_TENSOR_MAP_INTERLEAVE_NONE, swz,
      CU_TENSOR_MAP_L2_PROMOTION_L2_256B, CU_TENSOR_MAP_FLOAT_OOB_FILL_NONE);
  return m;
}

static CUtensorMap make_map_img(EncodeFn enc, const void* p, uint64_t k, uint64_t n, uint32_t chunks) {
  CUtensorMap m;
  cuuint64_t gd[3] = {8, k, n / 8};
  cuuint64_t gs[2] = {n * 2, 16};
  cuuint32_t bd[3] = {8, 64, chunks};
  cuuint32_t es[3] = {1, 1, 1};
  enc(&m, CU_TENSOR_MAP_DATA_TYPE_BFLOAT16, 3, (void*)p, gd, gs, bd, es, CU_TENSOR_MAP_INTERLEAVE_NONE,
      CU_TENSOR_MAP_SWIZZLE_NONE, CU_TENSOR_MAP_L2_PROMOTION_L2_128B, CU_TENSOR_MAP_FLOAT_OOB_FILL_NONE);
  return m;
}

template <typename... KArgs, typename... Args>
static void launch(void (*k)(KArgs...), int grid, int threads, int smem, bool pdl, Args... args) {
  cudaLaunchConfig_t cfg = {};
  cfg.gridDim = dim3(grid);
  cfg.blockDim = dim3(threads);
  cfg.dynamicSmemBytes = smem;
  cfg.stream = cudaStreamPerThread;
  cudaLaunchAttribute at[1];
  at[0].id = cudaLaunchAttributeProgrammaticStreamSerialization;
  at[0].val.programmaticStreamSerializationAllowed = 1;
  cfg.attrs = at;
  cfg.numAttrs = pdl ? 1 : 0;
  cudaLaunchKernelEx(&cfg, k, KArgs(args)...);
}

extern "C" void kernel_launch(void* const* d_in, const int* in_sizes, int n_in, void* d_out, int out_size) {
  const bf16* x = (const bf16*)d_in[0];
  const bf16* wqkv = (const bf16*)d_in[1];
  const bf16* wo = (const bf16*)d_in[2];
  const bf16* wg = (const bf16*)d_in[4];
  const bf16* wu = (const bf16*)d_in[5];
  const bf16* wd = (const bf16*)d_in[6];

  static EncodeFn enc = nullptr;
  static void *p_o, *p_hh, *p_wo, *p_wd;
  if (!enc) {
    void* fn = nullptr;
    cudaDriverEntryPointQueryResult qr;
    cudaGetDriverEntryPoint("cuTensorMapEncodeTiled", &fn, cudaEnableDefault, &qr);
    enc = (EncodeFn)fn;
    cudaGetSymbolAddress(&p_o, g_o); cudaGetSymbolAddress(&p_hh, g_hh);
    cudaGetSymbolAddress(&p_wo, g_wo); cudaGetSymbolAddress(&p_wd, g_wd);
    cudaFuncSetAttribute(k1_qkv, cudaFuncAttributeMaxDynamicSharedMemorySize, K1_SMEM);
    cudaFuncSetAttribute(k2_attn, cudaFuncAttributeMaxDynamicSharedMemorySize, K2_SMEM);
    cudaFuncSetAttribute(k3_proj<3, 4, true>, cudaFuncAttributeMaxDynamicSharedMemorySize, K3_SMEM);
    cudaFuncSetAttribute(k3_proj<11, 5, false>, cudaFuncAttributeMaxDynamicSharedMemorySize, K3_SMEM);
    cudaFuncSetAttribute(k4_ffn1, cudaFuncAttributeMaxDynamicSharedMemorySize, K4_SMEM);
  }
  const CUtensorMap tmx = make_map(enc, x, D_, S_, 64, 128, CU_TENSOR_MAP_SWIZZLE_128B);
  const CUtensorMap tmw = make_map(enc, wqkv, 3 * D_, D_, 32, 64, CU_TENSOR_MAP_SWIZZLE_64B);
  const CUtensorMap tmxr = make_map(enc, x, D_, S_, 80, 64, CU_TENSOR_MAP_SWIZZLE_NONE);
  const CUtensorMap tmg = make_map_img(enc, wg, D_, F_, 9), tmu = make_map_img(enc, wu, D_, F_, 9);
  const CUtensorMap tmd = make_map_img(enc, wd, F_, D_, 10);
  const CUtensorMap tmout = make_map(enc, d_out, D_, S_, 80, 64, CU_TENSOR_MAP_SWIZZLE_NONE);

  launch(k1_qkv, 128, 384, K1_SMEM, false, tmx, tmw, x, wqkv, wo);
  launch(k2_attn, 128, 512, K2_SMEM, true, tmg, tmu, tmd, 0x007f007fu);
  launch(k3_proj<3, 4, true>, 128, 384, K3_SMEM, true, tmxr, (const uint4*)p_o, (const uint4*)p_wo);
  launch(k4_ffn1, 128, 256, K4_SMEM, true);
  launch(k3_proj<11, 5, false>, 128, 384, K3_SMEM, true, tmout, (const uint4*)p_hh, (const uint4*)p_wd);
}
```

```cpp
#include <cuda_runtime.h>
#include <cuda_bf16.h>
#include <cuda.h>
#include <stdint.h>

typedef __nv_bfloat16 bf16;

constexpr int S_ = 2048, D_ = 640, F_ = 1728;
constexpr int HEAD_IMG = 98304;
#define PMASK 0xABAB
constexpr uint32_t POLY_MASK = PMASK;
constexpr float QSCALE = 0.22360679774997896f * 1.4426950408889634f;

__device__ __align__(1024) uint4 g_qkv[96 * HEAD_IMG / 16];
__device__ __align__(1024) uint4 g_o[S_ * D_ / 8];
__device__ __align__(1024) uint4 g_h[S_ * D_ / 8];
__device__ __align__(1024) uint4 g_hh[S_ * F_ / 8];
__device__ __align__(1024) uint4 g_wo[D_ * D_ / 8];
__device__ __align__(1024) uint4 g_wgu[2 * D_ * F_ / 8];
__device__ __align__(1024) uint4 g_wd[F_ * D_ / 8];
__device__ uint4 g_rowstat[S_];
__device__ uint4 g_cpart[16 * 8 * 128];
__device__ float g_nrm[64 * 128];
__device__ uint4 g_wm[D_];
__device__ float g_hmean[S_];
__device__ float g_hpart[8 * S_];
__device__ unsigned g_epoch;

#define STAMP(k, i)
__device__ __forceinline__ uint32_t smem_u32(const void* p) { return (uint32_t)__cvta_generic_to_shared(p); }
__device__ __forceinline__ void mbar_init(uint32_t a, uint32_t c) {
  asm volatile("mbarrier.init.shared::cta.b64 [%0], %1;" ::"r"(a), "r"(c) : "memory");
}
__device__ __forceinline__ void mbar_expect(uint32_t a, uint32_t bytes) {
  asm volatile("mbarrier.arrive.expect_tx.shared::cta.b64 _, [%0], %1;" ::"r"(a), "r"(bytes) : "memory");
}
__device__ __forceinline__ void mbar_arrive(uint32_t a) {
  asm volatile("mbarrier.arrive.shared::cta.b64 _, [%0];" ::"r"(a) : "memory");
}
__device__ __forceinline__ void mbar_arrive_cta(uint32_t a, uint32_t cta) {
  asm volatile("{\n.reg .b32 r;\nmapa.shared::cluster.u32 r, %0, %1;\n"
               "mbarrier.arrive.shared::cluster.b64 _, [r];\n}" ::"r"(a), "r"(cta) : "memory");
}
__device__ __forceinline__ bool mbar_try(uint32_t a, uint32_t ph) {
  uint32_t ok;
  asm volatile("{\n.reg .pred p;\nmbarrier.try_wait.parity.shared::cta.b64 p, [%1], %2;\nselp.u32 %0, 1, 0, p;\n}"
               : "=r"(ok) : "r"(a), "r"(ph) : "memory");
  return ok;
}
__device__ __noinline__ void wait_timeout() { __trap(); }
__device__ __forceinline__ void mbar_wait(uint32_t a, uint32_t ph) {
  if (mbar_try(a, ph)) return;
  uint32_t it = 0;
  while (!mbar_try(a, ph)) if (++it > (1u << 22)) wait_timeout();
}
__device__ __forceinline__ void tma2d(uint32_t dst, const CUtensorMap* m, int c0, int c1, uint32_t bar) {
  asm volatile("cp.async.bulk.tensor.2d.shared::cluster.global.mbarrier::complete_tx::bytes [%0], [%1, {%3, %4}], [%2];"
               ::"r"(dst), "l"(m), "r"(bar), "r"(c0), "r"(c1) : "memory");
}
__device__ __forceinline__ void tma2d_mc(uint32_t dst, const CUtensorMap* m, int c0, int c1, uint32_t bar) {
  asm volatile("cp.async.bulk.tensor.2d.shared::cluster.global.mbarrier::complete_tx::bytes.multicast::cluster "
               "[%0], [%1, {%3, %4}], [%2], %5;"
               ::"r"(dst), "l"(m), "r"(bar), "r"(c0), "r"(c1), "h"((uint16_t)3) : "memory");
}
__device__ __forceinline__ void bulk_ld(uint32_t dst, const void* src, uint32_t bytes, uint32_t bar) {
  asm volatile("cp.async.bulk.shared::cluster.global.mbarrier::complete_tx::bytes [%0], [%1], %2, [%3];"
               ::"r"(dst), "l"(src), "r"(bytes), "r"(bar) : "memory");
}
__device__ __forceinline__ void bulk_ld_mc(uint32_t dst, const void* src, uint32_t bytes, uint32_t bar) {
  asm volatile("cp.async.bulk.shared::cluster.global.mbarrier::complete_tx::bytes.multicast::cluster "
               "[%0], [%1], %2, [%3], %4;"
               ::"r"(dst), "l"(src), "r"(bytes), "r"(bar), "h"((uint16_t)3) : "memory");
}
__device__ __forceinline__ void cluster_arrive() { asm volatile("barrier.cluster.arrive.relaxed.aligned;" ::: "memory"); }
__device__ __forceinline__ void cluster_wait() { asm volatile("barrier.cluster.wait.aligned;" ::: "memory"); }
__device__ __forceinline__ void bulk_st(void* dst, uint32_t src, uint32_t bytes) {
  asm volatile("cp.async.bulk.global.shared::cta.bulk_group [%0], [%1], %2;" ::"l"(dst), "r"(src), "r"(bytes) : "memory");
}
__device__ __forceinline__ void tma2d_st(const CUtensorMap* m, int c0, int c1, uint32_t src) {
  asm volatile("cp.async.bulk.tensor.2d.global.shared::cta.bulk_group [%0, {%2, %3}], [%1];"
               ::"l"(m), "r"(src), "r"(c0), "r"(c1) : "memory");
}
__device__ __forceinline__ void bulk_commit_wait() {
  asm volatile("cp.async.bulk.commit_group;\ncp.async.bulk.wait_group.read 0;" ::: "memory");
}
__device__ __forceinline__ uint32_t mapa(uint32_t a, uint32_t cta) {
  uint32_t r;
  asm("mapa.shared::cluster.u32 %0, %1, %2;" : "=r"(r) : "r"(a), "r"(cta));
  return r;
}
__device__ __forceinline__ void st_async4(uint32_t dst, float a, float b, float c, float d, uint32_t bar) {
  asm volatile("st.async.shared::cluster.mbarrier::complete_tx::bytes.v4.f32 [%0], {%1, %2, %3, %4}, [%5];"
               ::"r"(dst), "f"(a), "f"(b), "f"(c), "f"(d), "r"(bar) : "memory");
}
__device__ __forceinline__ void fence_async() { asm volatile("fence.proxy.async.shared::cta;" ::: "memory"); }
__device__ __forceinline__ void prefetch_map(const CUtensorMap* m) {
  asm volatile("prefetch.tensormap [%0];" ::"l"(m) : "memory");
}
__device__ __forceinline__ void pdl_wait() { asm volatile("griddepcontrol.wait;" ::: "memory"); }
__device__ __forceinline__ void pdl_trigger() { asm volatile("griddepcontrol.launch_dependents;" ::: "memory"); }
__device__ __forceinline__ void bar_sync(int id, int n) { asm volatile("bar.sync %0, %1;" ::"r"(id), "r"(n) : "memory"); }
__device__ __forceinline__ void bar_arrive(int id, int n) { asm volatile("bar.arrive %0, %1;" ::"r"(id), "r"(n) : "memory"); }
#define WG_FENCE() asm volatile("wgmma.fence.sync.aligned;" ::: "memory")
#define WG_COMMIT() asm volatile("wgmma.commit_group.sync.aligned;" ::: "memory")
#define WG_WAIT(n) asm volatile("wgmma.wait_group.sync.aligned %0;" ::"n"(n) : "memory")
__device__ __forceinline__ uint64_t mkdesc(uint32_t addr, uint32_t lbo, uint32_t sbo, uint32_t sw) {
  return (uint64_t)((addr & 0x3FFFF) >> 4) | ((uint64_t)(lbo >> 4) << 16) | ((uint64_t)(sbo >> 4) << 32) |
         ((uint64_t)sw << 62);
}
template <int N> __device__ __forceinline__ void fence_regs(float (&r)[N]) {
#pragma unroll
  for (int i = 0; i < N; i++) asm volatile("" : "+f"(r[i])::"memory");
}
__device__ __forceinline__ uint32_t pack_bf16(float lo, float hi) {
  uint32_t r;
  asm("cvt.rn.bf16x2.f32 %0, %1, %2;" : "=r"(r) : "f"(hi), "f"(lo));
  return r;
}
__device__ __forceinline__ float bf_lo(uint32_t v) { return __uint_as_float(v << 16); }
__device__ __forceinline__ float bf_hi(uint32_t v) { return __uint_as_float(v & 0xffff0000u); }
__device__ __forceinline__ float ex2(float x) {
  float y;
  asm("ex2.approx.ftz.f32 %0, %1;" : "=f"(y) : "f"(x));
  return y;
}
__device__ __forceinline__ uint4 ldg_nc(const void* p) {
  uint4 v;
  asm volatile("ld.global.nc.L1::no_allocate.v4.u32 {%0, %1, %2, %3}, [%4];"
               : "=r"(v.x), "=r"(v.y), "=r"(v.z), "=r"(v.w) : "l"(p));
  return v;
}

__device__ __forceinline__ uint4 ld_relaxed(const uint4* p) {
  uint64_t a, b;
  asm volatile("ld.relaxed.gpu.global.v2.u64 {%0, %1}, [%2];" : "=l"(a), "=l"(b) : "l"(p) : "memory");
  return make_uint4((uint32_t)a, (uint32_t)(a >> 32), (uint32_t)b, (uint32_t)(b >> 32));
}
__device__ __forceinline__ void st_relaxed(uint4* p, float x, float y, uint32_t tag) {
  const uint64_t a = ((uint64_t)tag << 32) | __float_as_uint(x), b = ((uint64_t)tag << 32) | __float_as_uint(y);
  asm volatile("st.relaxed.gpu.global.v2.u64 [%0], {%1, %2};" ::"l"(p), "l"(a), "l"(b) : "memory");
}
__device__ __forceinline__ void tma3d(uint32_t dst, const CUtensorMap* m, int c1, int c2, uint32_t bar) {
  asm volatile("cp.async.bulk.tensor.3d.shared::cluster.global.mbarrier::complete_tx::bytes [%0], [%1, {%3, %4, %5}], [%2];"
               ::"r"(dst), "l"(m), "r"(bar), "r"(0), "r"(c1), "r"(c2) : "memory");
}
#define ACC8(a, v) do { a[0] += bf_lo(v.x); a[1] += bf_hi(v.x); a[2] += bf_lo(v.y); a[3] += bf_hi(v.y); \
                        a[4] += bf_lo(v.z); a[5] += bf_hi(v.z); a[6] += bf_lo(v.w); a[7] += bf_hi(v.w); } while (0)

__device__ __forceinline__ void wgmma_ss_n240(float (&d)[120], uint64_t da, uint64_t db, int sd) {
  asm volatile("{\n.reg .pred p;\nsetp.ne.b32 p, %122, 0;\n"
      "wgmma.mma_async.sync.aligned.m64n240k16.f32.bf16.bf16 {"
      "%0, %1, %2, %3, %4, %5, %6, %7, %8, %9, %10, %11, %12, %13, %14, %15, "
      "%16, %17, %18, %19, %20, %21, %22, %23, %24, %25, %26, %27, %28, %29, %30, %31, "
      "%32, %33, %34, %35, %36, %37, %38, %39, %40, %41, %42, %43, %44, %45, %46, %47, "
      "%48, %49, %50, %51, %52, %53, %54, %55, %56, %57, %58, %59, %60, %61, %62, %63, "
      "%64, %65, %66, %67, %68, %69, %70, %71, %72, %73, %74, %75, %76, %77, %78, %79, "
      "%80, %81, %82, %83, %84, %85, %86, %87, %88, %89, %90, %91, %92, %93, %94, %95, "
      "%96, %97, %98, %99, %100, %101, %102, %103, %104, %105, %106, %107, %108, %109, %110, %111, "
      "%112, %113, %114, %115, %116, %117, %118, %119"
      "}, %120, %121, p, 1, 1, 0, 1;\n}\n"
    : "+f"(d[0]), "+f"(d[1]), "+f"(d[2]), "+f"(d[3]), "+f"(d[4]), "+f"(d[5]), "+f"(d[6]), "+f"(d[7]),
      "+f"(d[8]), "+f"(d[9]), "+f"(d[10]), "+f"(d[11]), "+f"(d[12]), "+f"(d[13]), "+f"(d[14]), "+f"(d[15]),
      "+f"(d[16]), "+f"(d[17]), "+f"(d[18]), "+f"(d[19]), "+f"(d[20]), "+f"(d[21]), "+f"(d[22]), "+f"(d[23]),
      "+f"(d[24]), "+f"(d[25]), "+f"(d[26]), "+f"(d[27]), "+f"(d[28]), "+f"(d[29]), "+f"(d[30]), "+f"(d[31]),
      "+f"(d[32]), "+f"(d[33]), "+f"(d[34]), "+f"(d[35]), "+f"(d[36]), "+f"(d[37]), "+f"(d[38]), "+f"(d[39]),
      "+f"(d[40]), "+f"(d[41]), "+f"(d[42]), "+f"(d[43]), "+f"(d[44]), "+f"(d[45]), "+f"(d[46]), "+f"(d[47]),
      "+f"(d[48]), "+f"(d[49]), "+f"(d[50]), "+f"(d[51]), "+f"(d[52]), "+f"(d[53]), "+f"(d[54]), "+f"(d[55]),
      "+f"(d[56]), "+f"(d[57]), "+f"(d[58]), "+f"(d[59]), "+f"(d[60]), "+f"(d[61]), "+f"(d[62]), "+f"(d[63]),
      "+f"(d[64]), "+f"(d[65]), "+f"(d[66]), "+f"(d[67]), "+f"(d[68]), "+f"(d[69]), "+f"(d[70]), "+f"(d[71]),
      "+f"(d[72]), "+f"(d[73]), "+f"(d[74]), "+f"(d[75]), "+f"(d[76]), "+f"(d[77]), "+f"(d[78]), "+f"(d[79]),
      "+f"(d[80]), "+f"(d[81]), "+f"(d[82]), "+f"(d[83]), "+f"(d[84]), "+f"(d[85]), "+f"(d[86]), "+f"(d[87]),
      "+f"(d[88]), "+f"(d[89]), "+f"(d[90]), "+f"(d[91]), "+f"(d[92]), "+f"(d[93]), "+f"(d[94]), "+f"(d[95]),
      "+f"(d[96]), "+f"(d[97]), "+f"(d[98]), "+f"(d[99]), "+f"(d[100]), "+f"(d[101]), "+f"(d[102]), "+f"(d[103]),
      "+f"(d[104]), "+f"(d[105]), "+f"(d[106]), "+f"(d[107]), "+f"(d[108]), "+f"(d[109]), "+f"(d[110]), "+f"(d[111]),
      "+f"(d[112]), "+f"(d[113]), "+f"(d[114]), "+f"(d[115]), "+f"(d[116]), "+f"(d[117]), "+f"(d[118]), "+f"(d[119])
    : "l"(da), "l"(db), "r"(sd));
}
__device__ __forceinline__ void wgmma_ss_n216(float (&d)[108], uint64_t da, uint64_t db, int sd) {
  asm volatile("{\n.reg .pred p;\nsetp.ne.b32 p, %110, 0;\n"
      "wgmma.mma_async.sync.aligned.m64n216k16.f32.bf16.bf16 {"
      "%0, %1, %2, %3, %4, %5, %6, %7, %8, %9, %10, %11, %12, %13, %14, %15, "
      "%16, %17, %18, %19, %20, %21, %22, %23, %24, %25, %26, %27, %28, %29, %30, %31, "
      "%32, %33, %34, %35, %36, %37, %38, %39, %40, %41, %42, %43, %44, %45, %46, %47, "
      "%48, %49, %50, %51, %52, %53, %54, %55, %56, %57, %58, %59, %60, %61, %62, %63, "
      "%64, %65, %66, %67, %68, %69, %70, %71, %72, %73, %74, %75, %76, %77, %78, %79, "
      "%80, %81, %82, %83, %84, %85, %86, %87, %88, %89, %90, %91, %92, %93, %94, %95, "
      "%96, %97, %98, %99, %100, %101, %102, %103, %104, %105, %106, %107"
      "}, %108, %109, p, 1, 1, 0, 1;\n}\n"
    : "+f"(d[0]), "+f"(d[1]), "+f"(d[2]), "+f"(d[3]), "+f"(d[4]), "+f"(d[5]), "+f"(d[6]), "+f"(d[7]),
      "+f"(d[8]), "+f"(d[9]), "+f"(d[10]), "+f"(d[11]), "+f"(d[12]), "+f"(d[13]), "+f"(d[14]), "+f"(d[15]),
      "+f"(d[16]), "+f"(d[17]), "+f"(d[18]), "+f"(d[19]), "+f"(d[20]), "+f"(d[21]), "+f"(d[22]), "+f"(d[23]),
      "+f"(d[24]), "+f"(d[25]), "+f"(d[26]), "+f"(d[27]), "+f"(d[28]), "+f"(d[29]), "+f"(d[30]), "+f"(d[31]),
      "+f"(d[32]), "+f"(d[33]), "+f"(d[34]), "+f"(d[35]), "+f"(d[36]), "+f"(d[37]), "+f"(d[38]), "+f"(d[39]),
      "+f"(d[40]), "+f"(d[41]), "+f"(d[42]), "+f"(d[43]), "+f"(d[44]), "+f"(d[45]), "+f"(d[46]), "+f"(d[47]),
      "+f"(d[48]), "+f"(d[49]), "+f"(d[50]), "+f"(d[51]), "+f"(d[52]), "+f"(d[53]), "+f"(d[54]), "+f"(d[55]),
      "+f"(d[56]), "+f"(d[57]), "+f"(d[58]), "+f"(d[59]), "+f"(d[60]), "+f"(d[61]), "+f"(d[62]), "+f"(d[63]),
      "+f"(d[64]), "+f"(d[65]), "+f"(d[66]), "+f"(d[67]), "+f"(d[68]), "+f"(d[69]), "+f"(d[70]), "+f"(d[71]),
      "+f"(d[72]), "+f"(d[73]), "+f"(d[74]), "+f"(d[75]), "+f"(d[76]), "+f"(d[77]), "+f"(d[78]), "+f"(d[79]),
      "+f"(d[80]), "+f"(d[81]), "+f"(d[82]), "+f"(d[83]), "+f"(d[84]), "+f"(d[85]), "+f"(d[86]), "+f"(d[87]),
      "+f"(d[88]), "+f"(d[89]), "+f"(d[90]), "+f"(d[91]), "+f"(d[92]), "+f"(d[93]), "+f"(d[94]), "+f"(d[95]),
      "+f"(d[96]), "+f"(d[97]), "+f"(d[98]), "+f"(d[99]), "+f"(d[100]), "+f"(d[101]), "+f"(d[102]), "+f"(d[103]),
      "+f"(d[104]), "+f"(d[105]), "+f"(d[106]), "+f"(d[107])
    : "l"(da), "l"(db), "r"(sd));
}
__device__ __forceinline__ void wgmma_ss_n168(float (&d)[84], uint64_t da, uint64_t db, int sd) {
  asm volatile("{\n.reg .pred p;\nsetp.ne.b32 p, %86, 0;\n"
      "wgmma.mma_async.sync.aligned.m64n168k16.f32.bf16.bf16 {"
      "%0, %1, %2, %3, %4, %5, %6, %7, %8, %9, %10, %11, %12, %13, %14, %15, "
      "%16, %17, %18, %19, %20, %21, %22, %23, %24, %25, %26, %27, %28, %29, %30, %31, "
      "%32, %33, %34, %35, %36, %37, %38, %39, %40, %41, %42, %43, %44, %45, %46, %47, "
      "%48, %49, %50, %51, %52, %53, %54, %55, %56, %57, %58, %59, %60, %61, %62, %63, "
      "%64, %65, %66, %67, %68, %69, %70, %71, %72, %73, %74, %75, %76, %77, %78, %79, "
      "%80, %81, %82, %83"
      "}, %84, %85, p, 1, 1, 0, 1;\n}\n"
    : "+f"(d[0]), "+f"(d[1]), "+f"(d[2]), "+f"(d[3]), "+f"(d[4]), "+f"(d[5]), "+f"(d[6]), "+f"(d[7]),
      "+f"(d[8]), "+f"(d[9]), "+f"(d[10]), "+f"(d[11]), "+f"(d[12]), "+f"(d[13]), "+f"(d[14]), "+f"(d[15]),
      "+f"(d[16]), "+f"(d[17]), "+f"(d[18]), "+f"(d[19]), "+f"(d[20]), "+f"(d[21]), "+f"(d[22]), "+f"(d[23]),
      "+f"(d[24]), "+f"(d[25]), "+f"(d[26]), "+f"(d[27]), "+f"(d[28]), "+f"(d[29]), "+f"(d[30]), "+f"(d[31]),
      "+f"(d[32]), "+f"(d[33]), "+f"(d[34]), "+f"(d[35]), "+f"(d[36]), "+f"(d[37]), "+f"(d[38]), "+f"(d[39]),
      "+f"(d[40]), "+f"(d[41]), "+f"(d[42]), "+f"(d[43]), "+f"(d[44]), "+f"(d[45]), "+f"(d[46]), "+f"(d[47]),
      "+f"(d[48]), "+f"(d[49]), "+f"(d[50]), "+f"(d[51]), "+f"(d[52]), "+f"(d[53]), "+f"(d[54]), "+f"(d[55]),
      "+f"(d[56]), "+f"(d[57]), "+f"(d[58]), "+f"(d[59]), "+f"(d[60]), "+f"(d[61]), "+f"(d[62]), "+f"(d[63]),
      "+f"(d[64]), "+f"(d[65]), "+f"(d[66]), "+f"(d[67]), "+f"(d[68]), "+f"(d[69]), "+f"(d[70]), "+f"(d[71]),
      "+f"(d[72]), "+f"(d[73]), "+f"(d[74]), "+f"(d[75]), "+f"(d[76]), "+f"(d[77]), "+f"(d[78]), "+f"(d[79]),
      "+f"(d[80]), "+f"(d[81]), "+f"(d[82]), "+f"(d[83])
    : "l"(da), "l"(db), "r"(sd));
}
__device__ __forceinline__ void wgmma_ss_n160(float (&d)[80], uint64_t da, uint64_t db, int sd) {
  asm volatile("{\n.reg .pred p;\nsetp.ne.b32 p, %82, 0;\n"
      "wgmma.mma_async.sync.aligned.m64n160k16.f32.bf16.bf16 {"
      "%0, %1, %2, %3, %4, %5, %6, %7, %8, %9, %10, %11, %12, %13, %14, %15, "
      "%16, %17, %18, %19, %20, %21, %22, %23, %24, %25, %26, %27, %28, %29, %30, %31, "
      "%32, %33, %34, %35, %36, %37, %38, %39, %40, %41, %42, %43, %44, %45, %46, %47, "
      "%48, %49, %50, %51, %52, %53, %54, %55, %56, %57, %58, %59, %60, %61, %62, %63, "
      "%64, %65, %66, %67, %68, %69, %70, %71, %72, %73, %74, %75, %76, %77, %78, %79"
      "}, %80, %81, p, 1, 1, 0, 1;\n}\n"
    : "+f"(d[0]), "+f"(d[1]), "+f"(d[2]), "+f"(d[3]), "+f"(d[4]), "+f"(d[5]), "+f"(d[6]), "+f"(d[7]),
      "+f"(d[8]), "+f"(d[9]), "+f"(d[10]), "+f"(d[11]), "+f"(d[12]), "+f"(d[13]), "+f"(d[14]), "+f"(d[15]),
      "+f"(d[16]), "+f"(d[17]), "+f"(d[18]), "+f"(d[19]), "+f"(d[20]), "+f"(d[21]), "+f"(d[22]), "+f"(d[23]),
      "+f"(d[24]), "+f"(d[25]), "+f"(d[26]), "+f"(d[27]), "+f"(d[28]), "+f"(d[29]), "+f"(d[30]), "+f"(d[31]),
      "+f"(d[32]), "+f"(d[33]), "+f"(d[34]), "+f"(d[35]), "+f"(d[36]), "+f"(d[37]), "+f"(d[38]), "+f"(d[39]),
      "+f"(d[40]), "+f"(d[41]), "+f"(d[42]), "+f"(d[43]), "+f"(d[44]), "+f"(d[45]), "+f"(d[46]), "+f"(d[47]),
      "+f"(d[48]), "+f"(d[49]), "+f"(d[50]), "+f"(d[51]), "+f"(d[52]), "+f"(d[53]), "+f"(d[54]), "+f"(d[55]),
      "+f"(d[56]), "+f"(d[57]), "+f"(d[58]), "+f"(d[59]), "+f"(d[60]), "+f"(d[61]), "+f"(d[62]), "+f"(d[63]),
      "+f"(d[64]), "+f"(d[65]), "+f"(d[66]), "+f"(d[67]), "+f"(d[68]), "+f"(d[69]), "+f"(d[70]), "+f"(d[71]),
      "+f"(d[72]), "+f"(d[73]), "+f"(d[74]), "+f"(d[75]), "+f"(d[76]), "+f"(d[77]), "+f"(d[78]), "+f"(d[79])
    : "l"(da), "l"(db), "r"(sd));
}
__device__ __forceinline__ void wgmma_ss_n88(float (&d)[44], uint64_t da, uint64_t db, int sd) {
  asm volatile("{\n.reg .pred p;\nsetp.ne.b32 p, %46, 0;\n"
      "wgmma.mma_async.sync.aligned.m64n88k16.f32.bf16.bf16 {"
      "%0, %1, %2, %3, %4, %5, %6, %7, %8, %9, %10, %11, %12, %13, %14, %15, "
      "%16, %17, %18, %19, %20, %21, %22, %23, %24, %25, %26, %27, %28, %29, %30, %31, "
      "%32, %33, %34, %35, %36, %37, %38, %39, %40, %41, %42, %43"
      "}, %44, %45, p, 1, 1, 0, 1;\n}\n"
    : "+f"(d[0]), "+f"(d[1]), "+f"(d[2]), "+f"(d[3]), "+f"(d[4]), "+f"(d[5]), "+f"(d[6]), "+f"(d[7]),
      "+f"(d[8]), "+f"(d[9]), "+f"(d[10]), "+f"(d[11]), "+f"(d[12]), "+f"(d[13]), "+f"(d[14]), "+f"(d[15]),
      "+f"(d[16]), "+f"(d[17]), "+f"(d[18]), "+f"(d[19]), "+f"(d[20]), "+f"(d[21]), "+f"(d[22]), "+f"(d[23]),
      "+f"(d[24]), "+f"(d[25]), "+f"(d[26]), "+f"(d[27]), "+f"(d[28]), "+f"(d[29]), "+f"(d[30]), "+f"(d[31]),
      "+f"(d[32]), "+f"(d[33]), "+f"(d[34]), "+f"(d[35]), "+f"(d[36]), "+f"(d[37]), "+f"(d[38]), "+f"(d[39]),
      "+f"(d[40]), "+f"(d[41]), "+f"(d[42]), "+f"(d[43])
    : "l"(da), "l"(db), "r"(sd));
}
__device__ __forceinline__ void wgmma_ss_n80(float (&d)[40], uint64_t da, uint64_t db, int sd) {
  asm volatile("{\n.reg .pred p;\nsetp.ne.b32 p, %42, 0;\n"
      "wgmma.mma_async.sync.aligned.m64n80k16.f32.bf16.bf16 {"
      "%0, %1, %2, %3, %4, %5, %6, %7, %8, %9, %10, %11, %12, %13, %14, %15, "
      "%16, %17, %18, %19, %20, %21, %22, %23, %24, %25, %26, %27, %28, %29, %30, %31, "
      "%32, %33, %34, %35, %36, %37, %38, %39"
      "}, %40, %41, p, 1, 1, 0, 1;\n}\n"
    : "+f"(d[0]), "+f"(d[1]), "+f"(d[2]), "+f"(d[3]), "+f"(d[4]), "+f"(d[5]), "+f"(d[6]), "+f"(d[7]),
      "+f"(d[8]), "+f"(d[9]), "+f"(d[10]), "+f"(d[11]), "+f"(d[12]), "+f"(d[13]), "+f"(d[14]), "+f"(d[15]),
      "+f"(d[16]), "+f"(d[17]), "+f"(d[18]), "+f"(d[19]), "+f"(d[20]), "+f"(d[21]), "+f"(d[22]), "+f"(d[23]),
      "+f"(d[24]), "+f"(d[25]), "+f"(d[26]), "+f"(d[27]), "+f"(d[28]), "+f"(d[29]), "+f"(d[30]), "+f"(d[31]),
      "+f"(d[32]), "+f"(d[33]), "+f"(d[34]), "+f"(d[35]), "+f"(d[36]), "+f"(d[37]), "+f"(d[38]), "+f"(d[39])
    : "l"(da), "l"(db), "r"(sd));
}
__device__ __forceinline__ void wgmma_rs_n128(float (&d)[64], uint32_t a0, uint32_t a1, uint32_t a2, uint32_t a3,
                                  uint64_t db, int sd) {
  asm volatile("{\n.reg .pred p;\nsetp.ne.b32 p, %69, 0;\n"
      "wgmma.mma_async.sync.aligned.m64n128k16.f32.bf16.bf16 {"
      "%0, %1, %2, %3, %4, %5, %6, %7, %8, %9, %10, %11, %12, %13, %14, %15, "
      "%16, %17, %18, %19, %20, %21, %22, %23, %24, %25, %26, %27, %28, %29, %30, %31, "
      "%32, %33, %34, %35, %36, %37, %38, %39, %40, %41, %42, %43, %44, %45, %46, %47, "
      "%48, %49, %50, %51, %52, %53, %54, %55, %56, %57, %58, %59, %60, %61, %62, %63"
      "}, {%64, %65, %66, %67}, %68, p, 1, 1, 0;\n}\n"
    : "+f"(d[0]), "+f"(d[1]), "+f"(d[2]), "+f"(d[3]), "+f"(d[4]), "+f"(d[5]), "+f"(d[6]), "+f"(d[7]),
      "+f"(d[8]), "+f"(d[9]), "+f"(d[10]), "+f"(d[11]), "+f"(d[12]), "+f"(d[13]), "+f"(d[14]), "+f"(d[15]),
      "+f"(d[16]), "+f"(d[17]), "+f"(d[18]), "+f"(d[19]), "+f"(d[20]), "+f"(d[21]), "+f"(d[22]), "+f"(d[23]),
      "+f"(d[24]), "+f"(d[25]), "+f"(d[26]), "+f"(d[27]), "+f"(d[28]), "+f"(d[29]), "+f"(d[30]), "+f"(d[31]),
      "+f"(d[32]), "+f"(d[33]), "+f"(d[34]), "+f"(d[35]), "+f"(d[36]), "+f"(d[37]), "+f"(d[38]), "+f"(d[39]),
      "+f"(d[40]), "+f"(d[41]), "+f"(d[42]), "+f"(d[43]), "+f"(d[44]), "+f"(d[45]), "+f"(d[46]), "+f"(d[47]),
      "+f"(d[48]), "+f"(d[49]), "+f"(d[50]), "+f"(d[51]), "+f"(d[52]), "+f"(d[53]), "+f"(d[54]), "+f"(d[55]),
      "+f"(d[56]), "+f"(d[57]), "+f"(d[58]), "+f"(d[59]), "+f"(d[60]), "+f"(d[61]), "+f"(d[62]), "+f"(d[63])
    : "r"(a0), "r"(a1), "r"(a2), "r"(a3), "l"(db), "r"(sd));
}
__device__ __forceinline__ void wgmma_rs_n24(float (&d)[12], uint32_t a0, uint32_t a1, uint32_t a2, uint32_t a3,
                                  uint64_t db, int sd) {
  asm volatile("{\n.reg .pred p;\nsetp.ne.b32 p, %17, 0;\n"
      "wgmma.mma_async.sync.aligned.m64n24k16.f32.bf16.bf16 {"
      "%0, %1, %2, %3, %4, %5, %6, %7, %8, %9, %10, %11"
      "}, {%12, %13, %14, %15}, %16, p, 1, 1, 1;\n}\n"
    : "+f"(d[0]), "+f"(d[1]), "+f"(d[2]), "+f"(d[3]), "+f"(d[4]), "+f"(d[5]), "+f"(d[6]), "+f"(d[7]),
      "+f"(d[8]), "+f"(d[9]), "+f"(d[10]), "+f"(d[11])
    : "r"(a0), "r"(a1), "r"(a2), "r"(a3), "l"(db), "r"(sd));
}

constexpr int K1_ST = 4, K1_STAGE = 49152;
constexpr int K1_SMEM = K1_ST * K1_STAGE + 1024   + 1024   + 3072   + 128;

__global__ void __cluster_dims__(2, 1, 1) __launch_bounds__(384, 1)
k1_qkv(const __grid_constant__ CUtensorMap tmx, const __grid_constant__ CUtensorMap tmw,
       const bf16* __restrict__ x, const bf16* __restrict__ w, const bf16* __restrict__ wo) {
  extern __shared__ __align__(1024) uint8_t sm[];
  float* cs = (float*)(sm + K1_ST * K1_STAGE);
  float2* rowab = (float2*)(sm + K1_ST * K1_STAGE + 1024);
  float* red = (float*)(sm + K1_ST * K1_STAGE + 2048);
  const uint32_t sbase = smem_u32(sm);
  const uint32_t fullb = sbase + K1_ST * K1_STAGE + 5120, emptyb = fullb + 8 * K1_ST;
  const int tid = threadIdx.x, lane = tid & 31;
  const int warp = __shfl_sync(~0u, tid >> 5, 0);
  const int rank = blockIdx.x & 1, cl = blockIdx.x >> 1;
  const int n = cl & 7, m = (cl >> 3) * 2 + rank;
  if (tid == 0) STAMP(0, 0);

  if (warp == 0) {
    if (lane == 0) {
      prefetch_map(&tmx); prefetch_map(&tmw);
      for (int i = 0; i < K1_ST; i++) { mbar_init(fullb + 8 * i, 1); mbar_init(emptyb + 8 * i, 4); }
      asm volatile("fence.mbarrier_init.release.cluster;" ::: "memory");
    }
    __syncwarp();
    cluster_arrive();
    if (lane == 0) {
      for (int kt = 0; kt < K1_ST; kt++) mbar_expect(fullb + 8 * kt, K1_STAGE);
      tma2d(sbase, &tmx, 0, m * 128, fullb);
    }
    __syncwarp();
    cluster_wait();
    if (tid == 0) STAMP(5, 3);
    if (lane == 0) {
#pragma unroll
      for (int j = 0; j < 4; j++) tma2d_mc(sbase + 16384 + rank * 16384 + j * 4096, &tmw, n * 240 + rank * 128 + j * 32, 0, fullb);
    }
    __syncwarp();
    bar_arrive(4, 384);
    if (lane == 0) {
      for (int kt = 1; kt < 10; kt++) {
        const int s = kt % K1_ST;
        const uint32_t sa = sbase + s * K1_STAGE, sb = sa + 16384 + rank * 16384;
        if (kt >= K1_ST) {
          mbar_wait(emptyb + 8 * s, ((kt / K1_ST) - 1) & 1);
          mbar_expect(fullb + 8 * s, K1_STAGE);
        }
        tma2d(sa, &tmx, kt * 64, m * 128, fullb + 8 * s);
#pragma unroll
        for (int j = 0; j < 4; j++) tma2d_mc(sb + j * 4096, &tmw, n * 240 + rank * 128 + j * 32, kt * 64, fullb + 8 * s);
        if (kt == K1_ST - 1) pdl_trigger();
      }
    }
    __syncwarp();
    cluster_arrive();
  } else if (warp < 4) {
    cluster_arrive();
    const int w3 = warp - 1, t96 = tid - 32;
    const uint32_t tag = __ldcg(&g_epoch) + 1;
    bar_sync(4, 384);
    mbar_wait(fullb, 0);
    {
      uint4 wv[14];
#pragma unroll
      for (int i = 0; i < 14; i++)
        wv[i] = ldg_nc(w + (size_t)(m * 40 + min(w3 + 3 * i, 39)) * 1920 + n * 240 + min(lane, 29) * 8);
      float acc8[8];
#pragma unroll
      for (int i = 0; i < 8; i++) acc8[i] = 0.f;
#pragma unroll
      for (int i = 0; i < 14; i++)
        if (i < 13 || w3 == 0) ACC8(acc8, wv[i]);
      *(float4*)&red[w3 * 256 + lane * 8] = make_float4(acc8[0], acc8[1], acc8[2], acc8[3]);
      *(float4*)&red[w3 * 256 + lane * 8 + 4] = make_float4(acc8[4], acc8[5], acc8[6], acc8[7]);
    }
    bar_sync(1, 96);
    for (int i = t96; i < 120; i += 96) {
      const float2 p0 = *(const float2*)&red[i * 2], p1 = *(const float2*)&red[256 + i * 2], p2 = *(const float2*)&red[512 + i * 2];
      st_relaxed(&g_cpart[(m * 8 + n) * 128 + i], p0.x + p1.x + p2.x, p0.y + p1.y + p2.y, tag);
    }
    if (tid == 32) STAMP(5, 7);
    for (int i = t96; i < 128; i += 96) {
      uint32_t it = 0;
      while (true) {
        uint4 p[16];
        const uint4 st = ld_relaxed(&g_rowstat[m * 128 + i]);
#pragma unroll
        for (int k = 0; k < 16; k++) p[k] = ld_relaxed(&g_cpart[(k * 8 + n) * 128 + min(i, 119)]);
        bool ok = st.y == tag && st.w == tag;
        float s0 = 0.f, s1 = 0.f;
#pragma unroll
        for (int k = 0; k < 16; k++) {
          ok = ok && p[k].y == tag && p[k].w == tag;
          s0 += __uint_as_float(p[k].x); s1 += __uint_as_float(p[k].z);
        }
        if (ok) {
          *(float2*)&cs[i * 2] = make_float2(s0, s1);
          rowab[i] = make_float2(__uint_as_float(st.x), -__uint_as_float(st.x) * __uint_as_float(st.z));
          break;
        }
        if (++it > (1u << 20)) wait_timeout();
      }
    }
    __syncwarp();
    bar_arrive(2, 96 + 256);
    bar_sync(1, 96);
    if (tid == 32) STAMP(0, 5);
    {
      uint4 v[5];
      const int ck = min(t96, 79), nt = ck / 10;
#pragma unroll
      for (int i = 0; i < 5; i++) {
        const int k = blockIdx.x * 5 + i, pr = k / 40, r = k - pr * 40;
        v[i] = ldg_nc(wo + (size_t)(pr * 40 + (r < 16 ? r : (r < 32 ? r + 4 : (r < 36 ? r - 16 : r)))) * D_ + ck * 8);
      }
#pragma unroll
      for (int i = 0; i < 5; i++) {
        const int k = blockIdx.x * 5 + i;
        g_wo[((nt * 10 + (k >> 6)) * 10 + ck - nt * 10) * 64 + (k & 63)] = v[i];
        float t = ((bf_lo(v[i].x) + bf_hi(v[i].x)) + (bf_lo(v[i].y) + bf_hi(v[i].y))) +
                  ((bf_lo(v[i].z) + bf_hi(v[i].z)) + (bf_lo(v[i].w) + bf_hi(v[i].w)));
        if (t96 >= 80) t = 0.f;
#pragma unroll
        for (int o = 16; o; o >>= 1) t += __shfl_xor_sync(~0u, t, o);
        if (lane == 0) red[w3 * 8 + i] = t;
      }
      bar_sync(1, 96);
      if (t96 < 5) {
        const float mu = (red[t96] + red[8 + t96] + red[16 + t96]) * (1.f / D_);
        const float hi = bf_lo(pack_bf16(mu, 0.f));
        g_wm[blockIdx.x * 5 + t96] = make_uint4(pack_bf16(hi, mu - hi), 0u, 0u, 0u);
      }
    }
    if (tid == 32) STAMP(0, 7);
    __syncwarp();
    cluster_wait();
    cluster_arrive();
  } else {
    cluster_arrive();
    const int cw = warp - 4, wg = cw >> 2;
    bar_sync(4, 384);
    float acc[120];
    const uint64_t da0 = mkdesc(sbase + wg * 8192, 16, 1024, 1);
    const uint64_t db0 = mkdesc(sbase + 16384, 4096, 512, 2);
    const uint32_t tag = __ldcg(&g_epoch) + 1;
    uint4 xv[2][3];
    cluster_wait();
#pragma unroll
    for (int kt = 0; kt < 10; kt++) {
      const int s = kt % K1_ST;
      mbar_wait(fullb + 8 * s, (kt / K1_ST) & 1);
      if (kt == 0 && tid == 128) STAMP(0, 1);
      const uint64_t da = da0 + s * (K1_STAGE >> 4), db = db0 + s * (K1_STAGE >> 4);
      WG_FENCE();
#pragma unroll
      for (int k = 0; k < 4; k++) wgmma_ss_n240(acc, da + k * 2, db + k * 64, (kt | k) != 0);
      WG_COMMIT();
      if (kt > 0) {
        WG_WAIT(1);
        if (kt - 1 + K1_ST < 10 && (tid & 127) < 2) mbar_arrive_cta(emptyb + 8 * ((kt - 1) % K1_ST), tid & 1);
      }
      if (kt == 0) {
#pragma unroll
        for (int i = 0; i < 2; i++) {
          const bf16* xr = x + (size_t)(m * 128 + n * 16 + cw * 2 + i) * D_ + lane * 8;
          xv[i][0] = ldg_nc(xr);
          xv[i][1] = ldg_nc(xr + 256);
          xv[i][2] = make_uint4(0u, 0u, 0u, 0u);
          if (lane < 16) xv[i][2] = ldg_nc(xr + 512);
        }
      }
      if (kt == 2 || kt == 3) {
        float sx = 0.f, sq = 0.f;
#pragma unroll
        for (int k = 0; k < 3; k++) {
          const uint32_t wd4[4] = {xv[kt - 2][k].x, xv[kt - 2][k].y, xv[kt - 2][k].z, xv[kt - 2][k].w};
#pragma unroll
          for (int e = 0; e < 4; e++) {
            const float lo = bf_lo(wd4[e]), hi = bf_hi(wd4[e]);
            sx += lo + hi; sq = fmaf(lo, lo, fmaf(hi, hi, sq));
          }
        }
#pragma unroll
        for (int o = 16; o; o >>= 1) { sx += __shfl_xor_sync(~0u, sx, o); sq += __shfl_xor_sync(~0u, sq, o); }
        const float mean = sx * (1.f / D_);
        if (lane == 0)
          st_relaxed(&g_rowstat[m * 128 + n * 16 + cw * 2 + kt - 2],
                     rsqrtf(fmaxf(sq * (1.f / D_) - mean * mean, 0.f) + 1e-5f), mean, tag);
        __syncwarp();
      }
    }
    cluster_arrive();
    WG_WAIT(0);
    fence_regs(acc);
    if (tid == 128) STAMP(0, 2);
    bar_sync(2, 96 + 256);
    if (tid == 128) STAMP(0, 3);
    const int g = lane >> 2, c = lane & 3;
    const bool lo = c < 2;
    const float2 ab0 = rowab[cw * 16 + g], ab1 = rowab[cw * 16 + g + 8];
    const bool p0 = (POLY_MASK >> (cw * 2)) & 1, p1 = (POLY_MASK >> (cw * 2 + 1)) & 1;
    const uint32_t padq = c == 2 ? 0x3F803F80u : 0x00003F80u, padk = c == 2 ? 0x4A7A4B00u : 0x00004653u;
    const uint32_t padv = c == 2 ? 0x00003F80u : 0u;
    uint8_t* dst = (uint8_t*)g_qkv + (size_t)(n * 12) * HEAD_IMG + m * 6144 + lane * 4;
#pragma unroll
    for (int hp = 0; hp < 6; hp++) {
      const int sec = (n * 12 + hp * 2) >> 5;
      const float f0 = sec == 0 ? QSCALE : (sec == 1 && p0 ? 32768.f : 1.f), f1 = sec == 0 ? QSCALE : (sec == 1 && p1 ? 32768.f : 1.f);
      const uint32_t pad0 = sec == 0 ? padq : (sec == 2 ? padv : (p0 ? padk : 0u));
      const uint32_t pad1 = sec == 0 ? padq : (sec == 2 ? padv : (p1 ? padk : 0u));
      const float a0 = ab0.x * f0, b0 = ab0.y * f0, a1 = ab1.x * f1, b1 = ab1.y * f1;
      uint32_t u[5], v[5];
      float su[5], sv[5];
#pragma unroll
      for (int i = 0; i < 5; i++) {
        const int j = hp * 5 + i;
        const float2 t = *(const float2*)&cs[j * 8 + c * 2];
        const float x0 = fmaf(acc[4 * j], a0, b0 * t.x), x1 = fmaf(acc[4 * j + 1], a0, b0 * t.y);
        const float y0 = fmaf(acc[4 * j + 2], a1, b1 * t.x), y1 = fmaf(acc[4 * j + 3], a1, b1 * t.y);
        u[i] = pack_bf16(x0, x1); v[i] = pack_bf16(y0, y1);
        su[i] = fmaf(x0, x0, x1 * x1); sv[i] = fmaf(y0, y0, y1 * y1);
      }
      if (sec < 2) {
        const float r0 = (sec == 1 && p0) ? 9.313225746154785e-10f : 1.f, r1 = (sec == 1 && p1) ? 9.313225746154785e-10f : 1.f;
        float e0 = (su[0] + su[1] + (lo ? su[2] : 0.f)) * r0, e1 = (sv[0] + sv[1] + (lo ? sv[2] : 0.f)) * r1;
        float o0 = (su[3] + su[4] + (lo ? 0.f : su[2])) * r0, o1 = (sv[3] + sv[4] + (lo ? 0.f : sv[2])) * r1;
        e0 += __shfl_xor_sync(~0u, e0, 1); e1 += __shfl_xor_sync(~0u, e1, 1);
        o0 += __shfl_xor_sync(~0u, o0, 1); o1 += __shfl_xor_sync(~0u, o1, 1);
        e0 += __shfl_xor_sync(~0u, e0, 2); e1 += __shfl_xor_sync(~0u, e1, 2);
        o0 += __shfl_xor_sync(~0u, o0, 2); o1 += __shfl_xor_sync(~0u, o1, 2);
        const uint32_t em = __reduce_max_sync(~0u, max(__float_as_uint(e0), __float_as_uint(e1)));
        const uint32_t om = __reduce_max_sync(~0u, max(__float_as_uint(o0), __float_as_uint(o1)));
        if (lane < 2) g_nrm[(n * 12 + hp * 2 + lane) * 128 + m * 8 + cw] = __uint_as_float(lane ? om : em);
      }
      const int cst = sec == 1 ? 2048 : 128, gst = sec == 1 ? 128 : 384;
      uint8_t* pe = dst + (size_t)hp * 2 * HEAD_IMG + cw * 2 * gst;
      uint8_t* pf = pe + gst;
      *(uint32_t*)(pe) = u[0];       *(uint32_t*)(pf) = v[0];
      *(uint32_t*)(pe + cst) = u[1]; *(uint32_t*)(pf + cst) = v[1];
      *(uint32_t*)(pe + 2 * cst) = lo ? u[2] : pad0; *(uint32_t*)(pf + 2 * cst) = lo ? v[2] : pad1;
      *(uint32_t*)(pe + HEAD_IMG) = __shfl_xor_sync(~0u, lo ? u[3] : u[2], 2);
      *(uint32_t*)(pf + HEAD_IMG) = __shfl_xor_sync(~0u, lo ? v[3] : v[2], 2);
      *(uint32_t*)(pe + cst + HEAD_IMG) = __shfl_xor_sync(~0u, lo ? u[4] : u[3], 2);
      *(uint32_t*)(pf + cst + HEAD_IMG) = __shfl_xor_sync(~0u, lo ? v[4] : v[3], 2);
      const uint32_t tu = __shfl_xor_sync(~0u, u[4], 2), tv = __shfl_xor_sync(~0u, v[4], 2);
      *(uint32_t*)(pe + 2 * cst + HEAD_IMG) = lo ? tu : pad0; *(uint32_t*)(pf + 2 * cst + HEAD_IMG) = lo ? tv : pad1;
    }
    if (tid == 128) STAMP(0, 4);
  }
  cluster_wait();
  if (tid == 128) STAMP(0, 6);
}

constexpr int K2_SMEM = 2 * HEAD_IMG + 2 * 6144 + 2 * 10240 + 256;

__device__ __forceinline__ uint64_t desc64(uint32_t lo, uint32_t hi) {
  uint64_t d;
  asm("mov.b64 %0, {%1, %2};" : "=l"(d) : "r"(lo), "r"(hi));
  return d;
}
__device__ __forceinline__ uint32_t exp_pair(bool poly, float a, float b, uint32_t mk) {
  if (poly) {
    const uint32_t pk = __byte_perm(__float_as_uint(a), __float_as_uint(b), 0x6521);
    uint32_t m, q;
    asm("lop3.b32 %0, %1, %2, 0x3f803f80, 0xEA;" : "=r"(m) : "r"(pk), "r"(mk));
    asm("fma.rn.bf16x2 %0, %1, %1, %2;" : "=r"(q) : "r"(m), "r"(0x40014001u));
    return pk - m + q;
  }
  return pack_bf16(ex2(a), ex2(b));
}
#define PV_GR 2
__device__ __forceinline__ void exp_pv(const float (&s)[64], float (&o)[12], uint64_t dv, uint32_t mk) {
#pragma unroll
  for (int k0 = 0; k0 < 8; k0 += PV_GR) {
    uint32_t p[4 * PV_GR];
#pragma unroll
    for (int i = 0; i < 4 * PV_GR; i++)
      p[i] = exp_pair((POLY_MASK >> (k0 * 2 + i / 2)) & 1, s[k0 * 8 + 2 * i], s[k0 * 8 + 2 * i + 1], mk);
    WG_FENCE();
#pragma unroll
    for (int k = 0; k < PV_GR; k++)
      wgmma_rs_n24(o, p[4 * k], p[4 * k + 1], p[4 * k + 2], p[4 * k + 3], dv + (k0 + k) * 48, 1);
  }
}
__device__ __forceinline__ void load_q(uint32_t (&q)[6], const uint8_t* p) {
  q[0] = __ldcg((const uint32_t*)p);         q[1] = __ldcg((const uint32_t*)(p + 384));
  q[2] = __ldcg((const uint32_t*)(p + 128)); q[3] = __ldcg((const uint32_t*)(p + 512));
  q[4] = __ldcg((const uint32_t*)(p + 256)); q[5] = __ldcg((const uint32_t*)(p + 640));
}
__device__ __forceinline__ float rcp(float x) {
  float y;
  asm("rcp.approx.ftz.f32 %0, %1;" : "=f"(y) : "f"(x));
  return y;
}
__device__ __forceinline__ int img_off(int chunk) { return (chunk >> 3) * 16384 + (chunk & 7) * 128; }
__device__ __forceinline__ void store_o(const float (&o)[12], int tile) {
  int tid, bid;
  asm volatile("mov.u32 %0, %%tid.x;" : "=r"(tid));
  asm volatile("mov.u32 %0, %%ctaid.x;" : "=r"(bid));
  const int head = bid >> 2;
  uint8_t* dst = (uint8_t*)g_o + ((bid & 3) * 4 + (tile >> 1)) * 163840 + (tile & 1) * 8192 + ((tid >> 5) & 3) * 2048 + (tid & 31) * 4;
  const int oc = (head >> 1) * 5 + (head & 1) * 2;
  const int o0 = img_off(oc), o1 = img_off(oc + 1), o2 = img_off((head >> 1) * 5 + 4) + (head & 1) * 8;
  const float i0 = rcp(__shfl_sync(~0u, o[8], 2, 4)), i1 = rcp(__shfl_sync(~0u, o[10], 2, 4));
  *(uint32_t*)(dst + o0) = pack_bf16(o[0] * i0, o[1] * i0); *(uint32_t*)(dst + o0 + 1024) = pack_bf16(o[2] * i1, o[3] * i1);
  *(uint32_t*)(dst + o1) = pack_bf16(o[4] * i0, o[5] * i0); *(uint32_t*)(dst + o1 + 1024) = pack_bf16(o[6] * i1, o[7] * i1);
  if ((tid & 3) < 2) {
    *(uint32_t*)(dst + o2) = pack_bf16(o[8] * i0, o[9] * i0);
    *(uint32_t*)(dst + o2 + 1024) = pack_bf16(o[10] * i1, o[11] * i1);
  }
}

__global__ void __launch_bounds__(512, 1)
k2_attn(const __grid_constant__ CUtensorMap tmg, const __grid_constant__ CUtensorMap tmu,
        const __grid_constant__ CUtensorMap tmd, uint32_t mk) {
  extern __shared__ __align__(1024) uint8_t sm[];
  const uint32_t sbase = smem_u32(sm);
  float* part = (float*)(sm + 2 * HEAD_IMG);
  const uint32_t rbuf = sbase + 2 * HEAD_IMG + 2 * 6144;
  const uint32_t kvb = rbuf + 2 * 10240;
  const uint32_t partb = kvb + 128, rbar = kvb + 144;
  const int tid = threadIdx.x, lane = tid & 31;
  const int warp = __shfl_sync(~0u, tid >> 5, 0);
  const int head = blockIdx.x >> 2, qb = blockIdx.x & 3;

  if (tid == 0) STAMP(1, 0);
  if (tid == 0) {
    for (int i = 0; i < 16; i++) mbar_init(kvb + 8 * i, 1);
    mbar_init(partb, 128); mbar_init(partb + 8, 128); mbar_init(rbar, 1); mbar_init(rbar + 8, 1);
    asm volatile("fence.mbarrier_init.release.cluster;" ::: "memory");
  }
  __syncthreads();

  if (warp >= 12) {
    asm volatile("setmaxnreg.dec.sync.aligned.u32 32;");
    if (tid == 384) {
      pdl_wait();
      pdl_trigger();
      const uint8_t* kimg = (const uint8_t*)g_qkv + (size_t)(32 + head) * HEAD_IMG;
#pragma unroll 1
      for (int b = 0; b < 16; b++) {
        mbar_expect(kvb + 8 * b, 12288);
        bulk_ld(sbase + b * 6144, kimg + b * 6144, 6144, kvb + 8 * b);
        bulk_ld(sbase + HEAD_IMG + b * 6144, kimg + 32 * HEAD_IMG + b * 6144, 6144, kvb + 8 * b);
        if (b >= 2) mbar_wait(kvb + 8 * (b - 1), 0);

      }
      if (blockIdx.x == 0) g_epoch = g_epoch + 1;
      mbar_wait(kvb + 8 * 15, 0);
      STAMP(1, 2);
      uint8_t* pdst = nullptr;
      uint32_t pbytes = 0;
#pragma unroll 1
      for (int i = 0; i < 7; i++) {
        const int p = blockIdx.x + 128 * i;
        uint8_t* dst = nullptr;
        uint32_t bytes = 0;
        if (i < 6 && p < 696) {
          asm volatile("cp.async.bulk.wait_group.read 0;" ::: "memory");
          if (p < 480) {
            const int nk = p / 6, r = p - nk * 6, nt = nk / 10, kt = nk - nt * 10, up = r / 3;
            bytes = 9216;
            dst = (uint8_t*)g_wgu + (size_t)(nk * 54 + r * 9) * 1024;
            mbar_expect(rbar + 8 * (i & 1), bytes);
            tma3d(rbuf + (i & 1) * 10240, up ? &tmu : &tmg, kt * 64, nt * 27 + (r - up * 3) * 9, rbar + 8 * (i & 1));
          } else {
            const int nk = p - 480, nt = nk / 27, kt = nk - nt * 27;
            bytes = 10240;
            dst = (uint8_t*)g_wd + (size_t)nk * 10240;
            mbar_expect(rbar + 8 * (i & 1), bytes);
            tma3d(rbuf + (i & 1) * 10240, &tmd, kt * 64, nt * 10, rbar + 8 * (i & 1));
          }
        }
        if (pbytes) {
          mbar_wait(rbar + 8 * ((i - 1) & 1), ((i - 1) >> 1) & 1);
          bulk_st(pdst, rbuf + ((i - 1) & 1) * 10240, pbytes);
          asm volatile("cp.async.bulk.commit_group;" ::: "memory");
        }
        pdst = dst; pbytes = bytes;
      }
      asm volatile("cp.async.bulk.wait_group.read 0;" ::: "memory");
      STAMP(1, 6);
    }
  } else {
    asm volatile("setmaxnreg.inc.sync.aligned.u32 160;");
    const int wg = warp >> 2;
    const uint8_t* qthr = (const uint8_t*)g_qkv + (size_t)head * HEAD_IMG + qb * 64 * 384 + (warp & 3) * 768 + lane * 4;
    const uint32_t klo0 = ((sbase & 0x3FFFF) >> 4) | (128u << 16), vlo0 = (((sbase + HEAD_IMG) & 0x3FFFF) >> 4) | (24u << 16);
    constexpr uint64_t KSTEP2 = (uint64_t)(int64_t)(256 - (128 << 16));
    constexpr uint64_t KV2K = 384 - (HEAD_IMG >> 4) + (104 << 16);
    const int nun = wg == 1 ? 4 : 3;
    uint32_t utile = wg == 0 ? 0x210u : (wg == 1 ? 0x4235u : 0x576u);
    uint32_t ubeg = wg == 0 ? 0u : (wg == 1 ? 0x0b00u : 0x600u);
    uint32_t ulen = wg == 0 ? 0x0b1010u : (wg == 1 ? 0x10051006u : 0x0a1010u);
    pdl_wait();
    if (tid == 0) STAMP(1, 1);
    uint32_t q[6];
    load_q(q, qthr + (utile & 15) * 3072);
    bool fast;
    {
      const float4 kn = __ldcg((const float4*)&g_nrm[(32 + head) * 128 + lane * 4]);
      const float qv = __ldcg(&g_nrm[head * 128 + qb * 32 + lane]);
      const uint32_t km = max(max(__float_as_uint(kn.x), __float_as_uint(kn.y)), max(__float_as_uint(kn.z), __float_as_uint(kn.w)));
      const float k2 = __uint_as_float(__reduce_max_sync(~0u, km)), q2 = __uint_as_float(__reduce_max_sync(~0u, __float_as_uint(qv)));
      fast = q2 * k2 <= 3400.f;
    }
    if (fast) {
#pragma unroll 1
      for (int u = 0; u < nun; u++) {
        const uint32_t b0 = ubeg & 15;
        const bool wt = u == 0 || (wg == 1 && u == 1);
        float s[64], o[12];
#pragma unroll
        for (int i = 0; i < 12; i++) o[i] = 0.f;
        uint32_t vlo = vlo0 + b0 * 384, kb = kvb + b0 * 8;
        const uint32_t vend = vlo + ((ulen & 255) - 1) * 384;
        if (wt) mbar_wait(kb, 0);
        if (tid == 0) STAMP(5, 4 + u);
        fence_regs(o);
        WG_FENCE();
        wgmma_rs_n128(s, q[0], q[1], q[2], q[3], desc64(klo0 + b0 * 384, 8), 0);
        wgmma_rs_n128(s, q[4], q[5], 0, 0, desc64(klo0 + b0 * 384, 8) + KSTEP2, 1);
        WG_COMMIT();
#pragma unroll 1
        for (; vlo != vend; vlo += 384) {
          if (wt) { kb += 8; mbar_wait(kb, 0); }
          WG_WAIT(0);
          fence_regs(s); fence_regs(o);
          const uint64_t dv = desc64(vlo, 8);
          exp_pv(s, o, dv, mk);
          wgmma_rs_n128(s, q[0], q[1], q[2], q[3], dv + KV2K, 0);
          wgmma_rs_n128(s, q[4], q[5], 0, 0, dv + (KV2K + KSTEP2), 1);
          WG_COMMIT();
        }
        WG_WAIT(0);
        fence_regs(s); fence_regs(o);
        if (u + 1 < nun) load_q(q, qthr + ((utile >> 4) & 15) * 3072);
        exp_pv(s, o, desc64(vlo, 8), mk);
        WG_COMMIT();
        WG_WAIT(0);
        fence_regs(o);
        if (wg == 1 && !(u & 1)) {
          float4* pp = (float4*)(part + u * 768) + (tid & 127);
          pp[0] = make_float4(o[0], o[1], o[2], o[3]);
          pp[128] = make_float4(o[4], o[5], o[6], o[7]);
          pp[256] = make_float4(o[8], o[9], o[10], o[11]);
          mbar_arrive(partb + 4 * u);
        } else {
          if (wg != 1 && u == 2) {
            const int pi = wg == 0 ? 1 : 0;
            mbar_wait(partb + 8 * pi, 0);
            const float4* pp = (const float4*)(part + pi * 1536) + (tid & 127);
            const float4 x0 = pp[0], x1 = pp[128], x2 = pp[256];
            o[0] += x0.x; o[1] += x0.y; o[2] += x0.z; o[3] += x0.w; o[4] += x1.x; o[5] += x1.y;
            o[6] += x1.z; o[7] += x1.w; o[8] += x2.x; o[9] += x2.y; o[10] += x2.z; o[11] += x2.w;
          }
          store_o(o, utile & 15);
        }
        utile >>= 4; ubeg >>= 4; ulen >>= 8;
      }
      if ((tid & 127) == 0) STAMP(1, 3 + wg);
    } else {
#pragma unroll 1
      for (int tile = wg; tile < 8; tile += 3) {
        load_q(q, qthr + tile * 3072);
        if ((lane & 3) >= 2) { q[4] = 0; q[5] = 0; }
        float o[12], m0 = -INFINITY, m1 = -INFINITY;
#pragma unroll
        for (int i = 0; i < 12; i++) o[i] = 0.f;
#pragma unroll 1
        for (int b = 0; b < 16; b++) {
          float s[64];
          mbar_wait(kvb + 8 * b, 0);
          WG_FENCE();
          wgmma_rs_n128(s, q[0], q[1], q[2], q[3], desc64(klo0 + b * 384, 8), 0);
          wgmma_rs_n128(s, q[4], q[5], 0, 0, desc64(klo0 + b * 384, 8) + KSTEP2, 1);
          WG_COMMIT();
          WG_WAIT(0);
          fence_regs(s);
          float x0 = m0, x1 = m1;
#pragma unroll
          for (int j = 0; j < 16; j++) {
            if ((POLY_MASK >> j) & 1) {
#pragma unroll
              for (int i = 0; i < 4; i++) s[4 * j + i] *= (1.f / 32768.f);
            }
            x0 = fmaxf(x0, fmaxf(s[4 * j], s[4 * j + 1]));
            x1 = fmaxf(x1, fmaxf(s[4 * j + 2], s[4 * j + 3]));
          }
          x0 = fmaxf(x0, __shfl_xor_sync(~0u, x0, 1)); x0 = fmaxf(x0, __shfl_xor_sync(~0u, x0, 2));
          x1 = fmaxf(x1, __shfl_xor_sync(~0u, x1, 1)); x1 = fmaxf(x1, __shfl_xor_sync(~0u, x1, 2));
          const float al0 = ex2(m0 - x0), al1 = ex2(m1 - x1);
          m0 = x0; m1 = x1;
#pragma unroll
          for (int i = 0; i < 12; i++) o[i] *= (i & 2) ? al1 : al0;
          uint32_t p[32];
#pragma unroll
          for (int i = 0; i < 32; i++) {
            const float mm = (i & 1) ? m1 : m0;
            p[i] = pack_bf16(ex2(s[2 * i] - mm), ex2(s[2 * i + 1] - mm));
          }
          fence_regs(o);
          WG_FENCE();
#pragma unroll
          for (int k = 0; k < 8; k++)
            wgmma_rs_n24(o, p[4 * k], p[4 * k + 1], p[4 * k + 2], p[4 * k + 3], desc64(vlo0 + b * 384 + k * 48, 8), 1);
          WG_COMMIT();
          WG_WAIT(0);
          fence_regs(o);
        }
        store_o(o, tile);
      }
    }
  }
}

constexpr int K3_ST = 4, K3_STAGE = 37888;
constexpr int K3_SMEM = K3_ST * K3_STAGE + 45056 + 20480 + 256;

template <int N> struct Acc { float v[N]; };

template <int NB, int NK, bool FIRST>
__global__ void __cluster_dims__(2, 1, 1) __launch_bounds__(384, 1)
k3_proj(const __grid_constant__ CUtensorMap tmr, const uint4* __restrict__ aimg, const uint4* __restrict__ wimg) {
  constexpr int KT = 2 * NB + NK, EX = FIRST ? 1 : 0;
  extern __shared__ __align__(1024) uint8_t sm[];
  const uint32_t sbase = smem_u32(sm);
  uint8_t* xch = sm + K3_ST * K3_STAGE;
  uint8_t* stg = sm + K3_ST * K3_STAGE + 45056;
  const uint32_t fullb = smem_u32(stg) + 20480, emptyb = fullb + 8 * K3_ST, resb = emptyb + 8 * K3_ST, xchb = resb + 8;
  const int tid = threadIdx.x, lane = tid & 31;
  const int warp = __shfl_sync(~0u, tid >> 5, 0);
  const int rank = blockIdx.x & 1;
  const int n = blockIdx.x & 7, m = blockIdx.x >> 3;
  if (tid == 0) STAMP(FIRST ? 2 : 4, 0);
  if (warp == 0) {
    if (lane == 0) {
      prefetch_map(&tmr);
      for (int i = 0; i < K3_ST; i++) { mbar_init(fullb + 8 * i, 1); mbar_init(emptyb + 8 * i, 2); }
      mbar_init(resb, 1); mbar_init(xchb, 1);
      mbar_expect(xchb, 4096 * (10 + EX));
      asm volatile("fence.mbarrier_init.release.cluster;" ::: "memory");
    }
    __syncwarp();
    cluster_arrive();
    bar_arrive(4, 256 + 32);
    if (lane == 0) {
      const uint8_t* wk = (const uint8_t*)wimg + (size_t)n * KT * 10240;
      const uint8_t* ws = (const uint8_t*)wimg + (size_t)(n ^ 1) * KT * 10240;
      const uint8_t* ab = (const uint8_t*)aimg + (size_t)m * KT * 16384;
#pragma unroll 1
      for (int i = 0; i < NB + NK; i++) {
        const int s = i % K3_ST, kt = i < NB ? i + rank * (NB + NK) : i;
        const uint32_t sa = sbase + s * K3_STAGE;
        if (i >= K3_ST) mbar_wait(emptyb + 8 * s, ((i / K3_ST) - 1) & 1);
        mbar_expect(fullb + 8 * s, 26624 + EX * 1024 + (i < NB ? 10240 : 0));
        if (i > 0) bulk_ld(sa, ab + kt * 16384, 16384, fullb + 8 * s);
        bulk_ld(sa + 16384, wk + kt * 10240, 10240, fullb + 8 * s);
        if (FIRST) bulk_ld(sa + 26624, (const uint8_t*)g_wm + kt * 1024, 1024, fullb + 8 * s);
        if (i < NB) bulk_ld(sa + 26624 + EX * 1024, ws + kt * 10240, 10240, fullb + 8 * s);
        if (i == 0) {
          pdl_wait();
          pdl_trigger();
          bulk_ld(sa, ab + kt * 16384, 16384, fullb);
        }
        if (FIRST && i == K3_ST - 1) {
          mbar_expect(resb, 20480);
          tma2d(smem_u32(stg), &tmr, n * 80, m * 128, resb);
          tma2d(smem_u32(stg) + 10240, &tmr, n * 80, m * 128 + 64, resb);
        }
      }
    }
    __syncwarp();
    cluster_wait();
  } else if (warp >= 4) {
    cluster_arrive();
    const int cw = warp - 4, wg = cw >> 2;
    const int g = lane >> 2, c = lane & 3;
    const int row = m * 128 + cw * 16 + g;
    uint8_t* himg = (uint8_t*)g_h + (size_t)m * 163840 + cw * 2048 + lane * 4;
    uint32_t rv[20];
    float mu0, mu1;
    if (FIRST) {
      mu0 = __uint_as_float(__ldcg(&g_rowstat[row].z)); mu1 = __uint_as_float(__ldcg(&g_rowstat[row + 8].z));
    } else {
      mu0 = __ldcg(&g_hmean[row]); mu1 = __ldcg(&g_hmean[row + 8]);
#pragma unroll
      for (int j = 0; j < 10; j++) {
        rv[2 * j] = __ldcg((const uint32_t*)(himg + img_off(n * 10 + j)));
        rv[2 * j + 1] = __ldcg((const uint32_t*)(himg + img_off(n * 10 + j) + 1024));
      }
    }
    float acc[80 + 4 * EX];
    float (&keep)[40 + 4 * EX] = ((Acc<40 + 4 * EX>*)acc)->v;
    const uint64_t da0 = mkdesc(sbase + wg * 8192, 128, 1024, 0);
    const uint64_t db0 = mkdesc(sbase + 16384, 128, 1024, 0);
    bar_sync(4, 256 + 32);
#pragma unroll 1
    for (int i = 0; i < NB; i++) {
      const int s = i % K3_ST;
      mbar_wait(fullb + 8 * s, (i / K3_ST) & 1);
      if (i == 0 && tid == 128) STAMP(FIRST ? 2 : 4, 2);
      const uint64_t da = da0 + s * (K3_STAGE >> 4), db = db0 + s * (K3_STAGE >> 4);
      WG_FENCE();
#pragma unroll
      for (int k = 0; k < 4; k++) {
        if constexpr (FIRST) wgmma_ss_n168(acc, da + k * 16, db + k * 16, (i | k) != 0);
        else wgmma_ss_n160(acc, da + k * 16, db + k * 16, (i | k) != 0);
      }
      WG_COMMIT();
      if (i > 0) {
        WG_WAIT(1);
        if ((tid & 127) == 0) mbar_arrive(emptyb + 8 * ((i - 1) % K3_ST));
      }
    }
    cluster_wait();
    const uint32_t rx = mapa(smem_u32(xch) + (tid - 128) * 16, rank ^ 1), rb = mapa(xchb, rank ^ 1);
    WG_WAIT(0);
    fence_regs(acc);
    if ((tid & 127) == 0) mbar_arrive(emptyb + 8 * ((NB - 1) % K3_ST));
    if (FIRST) st_async4(rx, acc[40], acc[41], acc[42], acc[43], rb);
    if (tid == 128) STAMP(FIRST ? 2 : 4, 1);
#pragma unroll
    for (int i = NB; i < NB + NK; i++) {
      const int s = i % K3_ST;
      mbar_wait(fullb + 8 * s, (i / K3_ST) & 1);
      const uint64_t da = da0 + s * (K3_STAGE >> 4), db = db0 + s * (K3_STAGE >> 4);
      WG_FENCE();
#pragma unroll
      for (int k = 0; k < 4; k++) {
        if constexpr (FIRST) wgmma_ss_n88(keep, da + k * 16, db + k * 16, 1);
        else wgmma_ss_n80(keep, da + k * 16, db + k * 16, 1);
      }
      WG_COMMIT();
      if (i > NB && i - 1 + K3_ST < NB + NK) {
        WG_WAIT(1);
        if ((tid & 127) == 0) mbar_arrive(emptyb + 8 * ((i - 1) % K3_ST));
      }
#pragma unroll
      for (int j = (i - NB) * 3 + EX; j < (i - NB) * 3 + 3 + EX; j++)
        if (j < 10 + EX) st_async4(rx + j * 4096, acc[40 + 4 * j], acc[41 + 4 * j], acc[42 + 4 * j], acc[43 + 4 * j], rb);
    }
    uint8_t* sp = stg + (cw * 16 + g) * 160 + c * 4;
    if (FIRST) {
      mbar_wait(resb, 0);
#pragma unroll
      for (int j = 0; j < 10; j++) {
        rv[2 * j] = *(const uint32_t*)(sp + j * 16);
        rv[2 * j + 1] = *(const uint32_t*)(sp + 1280 + j * 16);
      }
    }
    WG_WAIT(0);
    fence_regs(keep);
    if (tid == 128) STAMP(FIRST ? 2 : 4, 3);
    mbar_wait(xchb, 0);
    if (tid == 128) STAMP(FIRST ? 2 : 4, 5);
    const uint8_t* xp = xch + (tid - 128) * 16;
    if (FIRST) {
      const float4 p = *(const float4*)xp;
      mu0 += __shfl_sync(~0u, (keep[40] + p.x) + (keep[41] + p.y), 0, 4);
      mu1 += __shfl_sync(~0u, (keep[42] + p.z) + (keep[43] + p.w), 0, 4);
      if (n == 0 && c == 0) { g_hmean[row] = mu0; g_hmean[row + 8] = mu1; }
      mu0 = -mu0; mu1 = -mu1;
    }
    float q0 = 0.f, q1 = 0.f;
#pragma unroll
    for (int j = 0; j < 10; j++) {
      const float4 p = *(const float4*)(xp + (j + EX) * 4096);
      const float x0 = (keep[4 * j] + p.x) + (bf_lo(rv[2 * j]) + mu0), x1 = (keep[4 * j + 1] + p.y) + (bf_hi(rv[2 * j]) + mu0);
      const float y0 = (keep[4 * j + 2] + p.z) + (bf_lo(rv[2 * j + 1]) + mu1), y1 = (keep[4 * j + 3] + p.w) + (bf_hi(rv[2 * j + 1]) + mu1);
      if (FIRST) {
        *(uint32_t*)(himg + img_off(n * 10 + j)) = pack_bf16(x0, x1);
        *(uint32_t*)(himg + img_off(n * 10 + j) + 1024) = pack_bf16(y0, y1);
        q0 = fmaf(x0, x0, fmaf(x1, x1, q0)); q1 = fmaf(y0, y0, fmaf(y1, y1, q1));
      } else {
        *(uint32_t*)(sp + j * 16) = pack_bf16(x0, x1);
        *(uint32_t*)(sp + 1280 + j * 16) = pack_bf16(y0, y1);
      }
    }
    if (FIRST) {
      q0 += __shfl_xor_sync(~0u, q0, 1); q0 += __shfl_xor_sync(~0u, q0, 2);
      q1 += __shfl_xor_sync(~0u, q1, 1); q1 += __shfl_xor_sync(~0u, q1, 2);
      if (c < 2) g_hpart[n * S_ + row + c * 8] = c ? q1 : q0;
    } else {
      fence_async();
      bar_sync(1 + wg, 128);
      if ((tid & 127) == 0) {
        tma2d_st(&tmr, n * 80, m * 128 + wg * 64, smem_u32(stg) + wg * 10240);
        bulk_commit_wait();
      }
      __syncwarp();
    }
    if (tid == 128) STAMP(FIRST ? 2 : 4, 4);
  } else {
    cluster_arrive();
    cluster_wait();
  }
}

constexpr int K4_ST = 3, K4_STAGE = 71680;
constexpr int K4_SMEM = K4_ST * K4_STAGE + 64;

__global__ void __cluster_dims__(2, 1, 1) __launch_bounds__(256, 1)
k4_ffn1() {
  extern __shared__ __align__(1024) uint8_t sm[];
  const uint32_t sbase = smem_u32(sm);
  const uint32_t fullb = sbase + K4_ST * K4_STAGE, emptyb = fullb + 8 * K4_ST;
  const int tid = threadIdx.x, lane = tid & 31;
  const int warp = __shfl_sync(~0u, tid >> 5, 0);
  const int rank = blockIdx.x & 1, cl = blockIdx.x >> 1;
  const int n = cl & 7, m = (cl >> 3) * 2 + rank;
  const uint8_t* wb = (const uint8_t*)g_wgu + (size_t)n * 10 * 55296 + rank * 27648;
  const uint8_t* ab = (const uint8_t*)g_h + (size_t)m * 163840;
  if (tid == 0) STAMP(3, 0);
  if (tid == 0) {
    for (int i = 0; i < K4_ST; i++) { mbar_init(fullb + 8 * i, 1); mbar_init(emptyb + 8 * i, 4); }
    asm volatile("fence.mbarrier_init.release.cluster;" ::: "memory");
    for (int kt = 0; kt < K4_ST; kt++) mbar_expect(fullb + 8 * kt, K4_STAGE);
  }
  __syncthreads();
  cluster_arrive();
  cluster_wait();
  if (tid == 0) bulk_ld_mc(sbase + 16384 + rank * 27648, wb, 27648, fullb);
  pdl_wait();
  pdl_trigger();
  if (tid == 128) STAMP(3, 1);
  if (tid == 0) {
    bulk_ld(sbase, ab, 16384, fullb);
    for (int kt = 1; kt < K4_ST; kt++) {
      bulk_ld(sbase + kt * K4_STAGE, ab + kt * 16384, 16384, fullb + 8 * kt);
      bulk_ld_mc(sbase + kt * K4_STAGE + 16384 + rank * 27648, wb + kt * 55296, 27648, fullb + 8 * kt);
    }
  }
  __syncwarp();
  float r0, r1;
  {
    const float* hp = &g_hpart[(lane & 3) * 2 * S_ + m * 128 + warp * 16 + (lane >> 2)];
    r0 = __ldcg(hp) + __ldcg(hp + S_);
    r1 = __ldcg(hp + 8) + __ldcg(hp + S_ + 8);
  }
  float ag[108], au[108];
  const uint64_t da0 = mkdesc(sbase + (warp >> 2) * 8192, 128, 1024, 0);
  const uint64_t db0 = mkdesc(sbase + 16384, 128, 1024, 0);
#pragma unroll 1
  for (int kt = 0; kt < 10; kt++) {
    const int s = kt % K4_ST;
    mbar_wait(fullb + 8 * s, (kt / K4_ST) & 1);
    if (kt == 0 && tid == 128) STAMP(3, 2);
    const uint64_t da = da0 + s * (K4_STAGE >> 4), db = db0 + s * (K4_STAGE >> 4);
    WG_FENCE();
#pragma unroll
    for (int k = 0; k < 4; k++) {
      wgmma_ss_n216(ag, da + k * 16, db + k * 16, (kt | k) != 0);
      wgmma_ss_n216(au, da + k * 16, db + 1728 + k * 16, (kt | k) != 0);
    }
    WG_COMMIT();
    if (kt > 0 && kt - 1 + K4_ST < 10) {
      WG_WAIT(1);
      const int sp = (kt - 1) % K4_ST;
      if ((tid & 127) < 2) mbar_arrive_cta(emptyb + 8 * sp, tid & 1);
      if (tid == 0) {
        const uint32_t sa = sbase + sp * K4_STAGE;
        mbar_wait(emptyb + 8 * sp, ((kt - 1) / K4_ST) & 1);
        mbar_expect(fullb + 8 * sp, K4_STAGE);
        bulk_ld_mc(sa + 16384 + rank * 27648, wb + (kt - 1 + K4_ST) * 55296, 27648, fullb + 8 * sp);
        bulk_ld(sa, ab + (kt - 1 + K4_ST) * 16384, 16384, fullb + 8 * sp);
      }
      __syncwarp();
    }
  }
  r0 += __shfl_xor_sync(~0u, r0, 1); r1 += __shfl_xor_sync(~0u, r1, 1);
  r0 += __shfl_xor_sync(~0u, r0, 2); r1 += __shfl_xor_sync(~0u, r1, 2);
  r0 = __frcp_rn(r0 * (1.f / D_) + 1e-5f); r1 = __frcp_rn(r1 * (1.f / D_) + 1e-5f);
  cluster_arrive();
  WG_WAIT(0);
  fence_regs(ag); fence_regs(au);
  if (tid == 128) STAMP(3, 3);
  uint8_t* dst = (uint8_t*)g_hh + (size_t)m * 27 * 16384 + warp * 2048 + lane * 4;
#pragma unroll
  for (int j = 0; j < 27; j++) {
    *(uint32_t*)(dst + img_off(n * 27 + j)) = pack_bf16(ag[4 * j] * r0 * au[4 * j], ag[4 * j + 1] * r0 * au[4 * j + 1]);
    *(uint32_t*)(dst + img_off(n * 27 + j) + 1024) = pack_bf16(ag[4 * j + 2] * r1 * au[4 * j + 2], ag[4 * j + 3] * r1 * au[4 * j + 3]);
  }
  if (tid == 128) STAMP(3, 4);
  cluster_wait();
}

typedef CUresult (*EncodeFn)(CUtensorMap*, CUtensorMapDataType, cuuint32_t, void*, const cuuint64_t*, const cuuint64_t*,
                             const cuuint32_t*, const cuuint32_t*, CUtensorMapInterleave, CUtensorMapSwizzle,
                             CUtensorMapL2promotion, CUtensorMapFloatOOBfill);

static CUtensorMap make_map(EncodeFn enc, const void* p, uint64_t inner, uint64_t outer, uint32_t box_inner,
                            uint32_t box_outer, CUtensorMapSwizzle swz) {
  CUtensorMap m;
  cuuint64_t gd[2] = {inner, outer};
  cuuint64_t gs[1] = {inner * 2};
  cuuint32_t bd[2] = {box_inner, box_outer};
  cuuint32_t es[2] = {1, 1};
  enc(&m, CU_TENSOR_MAP_DATA_TYPE_BFLOAT16, 2, (void*)p, gd, gs, bd, es, CU_TENSOR_MAP_INTERLEAVE_NONE, swz,
      CU_TENSOR_MAP_L2_PROMOTION_L2_256B, CU_TENSOR_MAP_FLOAT_OOB_FILL_NONE);
  return m;
}

static CUtensorMap make_map_img(EncodeFn enc, const void* p, uint64_t k, uint64_t n, uint32_t chunks) {
  CUtensorMap m;
  cuuint64_t gd[3] = {8, k, n / 8};
  cuuint64_t gs[2] = {n * 2, 16};
  cuuint32_t bd[3] = {8, 64, chunks};
  cuuint32_t es[3] = {1, 1, 1};
  enc(&m, CU_TENSOR_MAP_DATA_TYPE_BFLOAT16, 3, (void*)p, gd, gs, bd, es, CU_TENSOR_MAP_INTERLEAVE_NONE,
      CU_TENSOR_MAP_SWIZZLE_NONE, CU_TENSOR_MAP_L2_PROMOTION_L2_128B, CU_TENSOR_MAP_FLOAT_OOB_FILL_NONE);
  return m;
}

template <typename... KArgs, typename... Args>
static void launch(void (*k)(KArgs...), int grid, int threads, int smem, bool pdl, Args... args) {
  cudaLaunchConfig_t cfg = {};
  cfg.gridDim = dim3(grid);
  cfg.blockDim = dim3(threads);
  cfg.dynamicSmemBytes = smem;
  cfg.stream = cudaStreamPerThread;
  cudaLaunchAttribute at[1];
  at[0].id = cudaLaunchAttributeProgrammaticStreamSerialization;
  at[0].val.programmaticStreamSerializationAllowed = 1;
  cfg.attrs = at;
  cfg.numAttrs = pdl ? 1 : 0;
  cudaLaunchKernelEx(&cfg, k, KArgs(args)...);
}

extern "C" void kernel_launch(void* const* d_in, const int* in_sizes, int n_in, void* d_out, int out_size) {
  const bf16* x = (const bf16*)d_in[0];
  const bf16* wqkv = (const bf16*)d_in[1];
  const bf16* wo = (const bf16*)d_in[2];
  const bf16* wg = (const bf16*)d_in[4];
  const bf16* wu = (const bf16*)d_in[5];
  const bf16* wd = (const bf16*)d_in[6];

  static EncodeFn enc = nullptr;
  static void *p_o, *p_hh, *p_wo, *p_wd;
  if (!enc) {
    void* fn = nullptr;
    cudaDriverEntryPointQueryResult qr;
    cudaGetDriverEntryPoint("cuTensorMapEncodeTiled", &fn, cudaEnableDefault, &qr);
    enc = (EncodeFn)fn;
    cudaGetSymbolAddress(&p_o, g_o); cudaGetSymbolAddress(&p_hh, g_hh);
    cudaGetSymbolAddress(&p_wo, g_wo); cudaGetSymbolAddress(&p_wd, g_wd);
    cudaFuncSetAttribute(k1_qkv, cudaFuncAttributeMaxDynamicSharedMemorySize, K1_SMEM);
    cudaFuncSetAttribute(k2_attn, cudaFuncAttributeMaxDynamicSharedMemorySize, K2_SMEM);
    cudaFuncSetAttribute(k3_proj<3, 4, true>, cudaFuncAttributeMaxDynamicSharedMemorySize, K3_SMEM);
    cudaFuncSetAttribute(k3_proj<11, 5, false>, cudaFuncAttributeMaxDynamicSharedMemorySize, K3_SMEM);
    cudaFuncSetAttribute(k4_ffn1, cudaFuncAttributeMaxDynamicSharedMemorySize, K4_SMEM);
  }
  const CUtensorMap tmx = make_map(enc, x, D_, S_, 64, 128, CU_TENSOR_MAP_SWIZZLE_128B);
  const CUtensorMap tmw = make_map(enc, wqkv, 3 * D_, D_, 32, 64, CU_TENSOR_MAP_SWIZZLE_64B);
  const CUtensorMap tmxr = make_map(enc, x, D_, S_, 80, 64, CU_TENSOR_MAP_SWIZZLE_NONE);
  const CUtensorMap tmg = make_map_img(enc, wg, D_, F_, 9), tmu = make_map_img(enc, wu, D_, F_, 9);
  const CUtensorMap tmd = make_map_img(enc, wd, F_, D_, 10);
  const CUtensorMap tmout = make_map(enc, d_out, D_, S_, 80, 64, CU_TENSOR_MAP_SWIZZLE_NONE);

  launch(k1_qkv, 128, 384, K1_SMEM, false, tmx, tmw, x, wqkv, wo);
  launch(k2_attn, 128, 512, K2_SMEM, true, tmg, tmu, tmd, 0x007f007fu);
  launch(k3_proj<3, 4, true>, 128, 384, K3_SMEM, true, tmxr, (const uint4*)p_o, (const uint4*)p_wo);
  launch(k4_ffn1, 128, 256, K4_SMEM, true);
  launch(k3_proj<11, 5, false>, 128, 384, K3_SMEM, true, tmout, (const uint4*)p_hh, (const uint4*)p_wd);
}
```

```cpp
#include <cuda_runtime.h>
#include <cuda_bf16.h>
#include <cuda.h>
#include <stdint.h>

typedef __nv_bfloat16 bf16;

constexpr int S_ = 2048, D_ = 640, F_ = 1728;
constexpr int HEAD_IMG = 98304;
#define PMASK 0xABAB
constexpr uint32_t POLY_MASK = PMASK;
constexpr float QSCALE = 0.22360679774997896f * 1.4426950408889634f;

__device__ __align__(1024) uint4 g_qkv[96 * HEAD_IMG / 16];
__device__ __align__(1024) uint4 g_o[S_ * D_ / 8];
__device__ __align__(1024) uint4 g_h[S_ * D_ / 8];
__device__ __align__(1024) uint4 g_hh[S_ * F_ / 8];
__device__ __align__(1024) uint4 g_wo[D_ * D_ / 8];
__device__ __align__(1024) uint4 g_wgu[2 * D_ * F_ / 8];
__device__ __align__(1024) uint4 g_wd[F_ * D_ / 8];
__device__ uint4 g_rowstat[S_];
__device__ uint4 g_cpart[10 * 12 * 80];
__device__ float g_nrm[64 * 128];
__device__ uint4 g_wm[D_];
__device__ float g_hmean[S_];
__device__ float g_hpart[8 * S_];
__device__ unsigned g_epoch;

#define STAMP(k, i)
__device__ __forceinline__ uint32_t smem_u32(const void* p) { return (uint32_t)__cvta_generic_to_shared(p); }
__device__ __forceinline__ void mbar_init(uint32_t a, uint32_t c) {
  asm volatile("mbarrier.init.shared::cta.b64 [%0], %1;" ::"r"(a), "r"(c) : "memory");
}
__device__ __forceinline__ void mbar_expect(uint32_t a, uint32_t bytes) {
  asm volatile("mbarrier.arrive.expect_tx.shared::cta.b64 _, [%0], %1;" ::"r"(a), "r"(bytes) : "memory");
}
__device__ __forceinline__ void mbar_arrive(uint32_t a) {
  asm volatile("mbarrier.arrive.shared::cta.b64 _, [%0];" ::"r"(a) : "memory");
}
__device__ __forceinline__ void mbar_arrive_cta(uint32_t a, uint32_t cta) {
  asm volatile("{\n.reg .b32 r;\nmapa.shared::cluster.u32 r, %0, %1;\n"
               "mbarrier.arrive.shared::cluster.b64 _, [r];\n}" ::"r"(a), "r"(cta) : "memory");
}
__device__ __forceinline__ bool mbar_try(uint32_t a, uint32_t ph) {
  uint32_t ok;
  asm volatile("{\n.reg .pred p;\nmbarrier.try_wait.parity.shared::cta.b64 p, [%1], %2;\nselp.u32 %0, 1, 0, p;\n}"
               : "=r"(ok) : "r"(a), "r"(ph) : "memory");
  return ok;
}
__device__ __noinline__ void wait_timeout() { __trap(); }
__device__ __forceinline__ void mbar_wait(uint32_t a, uint32_t ph) {
  if (mbar_try(a, ph)) return;
  uint32_t it = 0;
  while (!mbar_try(a, ph)) if (++it > (1u << 22)) wait_timeout();
}
__device__ __forceinline__ void tma2d(uint32_t dst, const CUtensorMap* m, int c0, int c1, uint32_t bar) {
  asm volatile("cp.async.bulk.tensor.2d.shared::cluster.global.mbarrier::complete_tx::bytes [%0], [%1, {%3, %4}], [%2];"
               ::"r"(dst), "l"(m), "r"(bar), "r"(c0), "r"(c1) : "memory");
}
__device__ __forceinline__ void tma2d_mc(uint32_t dst, const CUtensorMap* m, int c0, int c1, uint32_t bar) {
  asm volatile("cp.async.bulk.tensor.2d.shared::cluster.global.mbarrier::complete_tx::bytes.multicast::cluster "
               "[%0], [%1, {%3, %4}], [%2], %5;"
               ::"r"(dst), "l"(m), "r"(bar), "r"(c0), "r"(c1), "h"((uint16_t)3) : "memory");
}
__device__ __forceinline__ void bulk_ld(uint32_t dst, const void* src, uint32_t bytes, uint32_t bar) {
  asm volatile("cp.async.bulk.shared::cluster.global.mbarrier::complete_tx::bytes [%0], [%1], %2, [%3];"
               ::"r"(dst), "l"(src), "r"(bytes), "r"(bar) : "memory");
}
__device__ __forceinline__ void bulk_ld_mc(uint32_t dst, const void* src, uint32_t bytes, uint32_t bar) {
  asm volatile("cp.async.bulk.shared::cluster.global.mbarrier::complete_tx::bytes.multicast::cluster "
               "[%0], [%1], %2, [%3], %4;"
               ::"r"(dst), "l"(src), "r"(bytes), "r"(bar), "h"((uint16_t)3) : "memory");
}
__device__ __forceinline__ void cluster_arrive() { asm volatile("barrier.cluster.arrive.relaxed.aligned;" ::: "memory"); }
__device__ __forceinline__ void cluster_wait() { asm volatile("barrier.cluster.wait.aligned;" ::: "memory"); }
__device__ __forceinline__ void bulk_st(void* dst, uint32_t src, uint32_t bytes) {
  asm volatile("cp.async.bulk.global.shared::cta.bulk_group [%0], [%1], %2;" ::"l"(dst), "r"(src), "r"(bytes) : "memory");
}
__device__ __forceinline__ void tma2d_st(const CUtensorMap* m, int c0, int c1, uint32_t src) {
  asm volatile("cp.async.bulk.tensor.2d.global.shared::cta.bulk_group [%0, {%2, %3}], [%1];"
               ::"l"(m), "r"(src), "r"(c0), "r"(c1) : "memory");
}
__device__ __forceinline__ void bulk_commit_wait() {
  asm volatile("cp.async.bulk.commit_group;\ncp.async.bulk.wait_group.read 0;" ::: "memory");
}
__device__ __forceinline__ uint32_t mapa(uint32_t a, uint32_t cta) {
  uint32_t r;
  asm("mapa.shared::cluster.u32 %0, %1, %2;" : "=r"(r) : "r"(a), "r"(cta));
  return r;
}
__device__ __forceinline__ void st_async4(uint32_t dst, float a, float b, float c, float d, uint32_t bar) {
  asm volatile("st.async.shared::cluster.mbarrier::complete_tx::bytes.v4.f32 [%0], {%1, %2, %3, %4}, [%5];"
               ::"r"(dst), "f"(a), "f"(b), "f"(c), "f"(d), "r"(bar) : "memory");
}
__device__ __forceinline__ void fence_async() { asm volatile("fence.proxy.async.shared::cta;" ::: "memory"); }
__device__ __forceinline__ void prefetch_map(const CUtensorMap* m) {
  asm volatile("prefetch.tensormap [%0];" ::"l"(m) : "memory");
}
__device__ __forceinline__ void pdl_wait() { asm volatile("griddepcontrol.wait;" ::: "memory"); }
__device__ __forceinline__ void pdl_trigger() { asm volatile("griddepcontrol.launch_dependents;" ::: "memory"); }
__device__ __forceinline__ void bar_sync(int id, int n) { asm volatile("bar.sync %0, %1;" ::"r"(id), "r"(n) : "memory"); }
__device__ __forceinline__ void bar_arrive(int id, int n) { asm volatile("bar.arrive %0, %1;" ::"r"(id), "r"(n) : "memory"); }
#define WG_FENCE() asm volatile("wgmma.fence.sync.aligned;" ::: "memory")
#define WG_COMMIT() asm volatile("wgmma.commit_group.sync.aligned;" ::: "memory")
#define WG_WAIT(n) asm volatile("wgmma.wait_group.sync.aligned %0;" ::"n"(n) : "memory")
__device__ __forceinline__ uint64_t mkdesc(uint32_t addr, uint32_t lbo, uint32_t sbo, uint32_t sw) {
  return (uint64_t)((addr & 0x3FFFF) >> 4) | ((uint64_t)(lbo >> 4) << 16) | ((uint64_t)(sbo >> 4) << 32) |
         ((uint64_t)sw << 62);
}
template <int N> __device__ __forceinline__ void fence_regs(float (&r)[N]) {
#pragma unroll
  for (int i = 0; i < N; i++) asm volatile("" : "+f"(r[i])::"memory");
}
__device__ __forceinline__ uint32_t pack_bf16(float lo, float hi) {
  uint32_t r;
  asm("cvt.rn.bf16x2.f32 %0, %1, %2;" : "=r"(r) : "f"(hi), "f"(lo));
  return r;
}
__device__ __forceinline__ float bf_lo(uint32_t v) { return __uint_as_float(v << 16); }
__device__ __forceinline__ float bf_hi(uint32_t v) { return __uint_as_float(v & 0xffff0000u); }
__device__ __forceinline__ float ex2(float x) {
  float y;
  asm("ex2.approx.ftz.f32 %0, %1;" : "=f"(y) : "f"(x));
  return y;
}
__device__ __forceinline__ uint4 ldg_nc(const void* p) {
  uint4 v;
  asm volatile("ld.global.nc.L1::no_allocate.v4.u32 {%0, %1, %2, %3}, [%4];"
               : "=r"(v.x), "=r"(v.y), "=r"(v.z), "=r"(v.w) : "l"(p));
  return v;
}

__device__ __forceinline__ uint4 ld_relaxed(const uint4* p) {
  uint64_t a, b;
  asm volatile("ld.relaxed.gpu.global.v2.u64 {%0, %1}, [%2];" : "=l"(a), "=l"(b) : "l"(p) : "memory");
  return make_uint4((uint32_t)a, (uint32_t)(a >> 32), (uint32_t)b, (uint32_t)(b >> 32));
}
__device__ __forceinline__ void st_relaxed(uint4* p, float x, float y, uint32_t tag) {
  const uint64_t a = ((uint64_t)tag << 32) | __float_as_uint(x), b = ((uint64_t)tag << 32) | __float_as_uint(y);
  asm volatile("st.relaxed.gpu.global.v2.u64 [%0], {%1, %2};" ::"l"(p), "l"(a), "l"(b) : "memory");
}
__device__ __forceinline__ void tma3d(uint32_t dst, const CUtensorMap* m, int c1, int c2, uint32_t bar) {
  asm volatile("cp.async.bulk.tensor.3d.shared::cluster.global.mbarrier::complete_tx::bytes [%0], [%1, {%3, %4, %5}], [%2];"
               ::"r"(dst), "l"(m), "r"(bar), "r"(0), "r"(c1), "r"(c2) : "memory");
}
#define ACC8(a, v) do { a[0] += bf_lo(v.x); a[1] += bf_hi(v.x); a[2] += bf_lo(v.y); a[3] += bf_hi(v.y); \
                        a[4] += bf_lo(v.z); a[5] += bf_hi(v.z); a[6] += bf_lo(v.w); a[7] += bf_hi(v.w); } while (0)

__device__ __forceinline__ void wgmma_ss_n216(float (&d)[108], uint64_t da, uint64_t db, int sd) {
  asm volatile("{\n.reg .pred p;\nsetp.ne.b32 p, %110, 0;\n"
      "wgmma.mma_async.sync.aligned.m64n216k16.f32.bf16.bf16 {"
      "%0, %1, %2, %3, %4, %5, %6, %7, %8, %9, %10, %11, %12, %13, %14, %15, "
      "%16, %17, %18, %19, %20, %21, %22, %23, %24, %25, %26, %27, %28, %29, %30, %31, "
      "%32, %33, %34, %35, %36, %37, %38, %39, %40, %41, %42, %43, %44, %45, %46, %47, "
      "%48, %49, %50, %51, %52, %53, %54, %55, %56, %57, %58, %59, %60, %61, %62, %63, "
      "%64, %65, %66, %67, %68, %69, %70, %71, %72, %73, %74, %75, %76, %77, %78, %79, "
      "%80, %81, %82, %83, %84, %85, %86, %87, %88, %89, %90, %91, %92, %93, %94, %95, "
      "%96, %97, %98, %99, %100, %101, %102, %103, %104, %105, %106, %107"
      "}, %108, %109, p, 1, 1, 0, 1;\n}\n"
    : "+f"(d[0]), "+f"(d[1]), "+f"(d[2]), "+f"(d[3]), "+f"(d[4]), "+f"(d[5]), "+f"(d[6]), "+f"(d[7]),
      "+f"(d[8]), "+f"(d[9]), "+f"(d[10]), "+f"(d[11]), "+f"(d[12]), "+f"(d[13]), "+f"(d[14]), "+f"(d[15]),
      "+f"(d[16]), "+f"(d[17]), "+f"(d[18]), "+f"(d[19]), "+f"(d[20]), "+f"(d[21]), "+f"(d[22]), "+f"(d[23]),
      "+f"(d[24]), "+f"(d[25]), "+f"(d[26]), "+f"(d[27]), "+f"(d[28]), "+f"(d[29]), "+f"(d[30]), "+f"(d[31]),
      "+f"(d[32]), "+f"(d[33]), "+f"(d[34]), "+f"(d[35]), "+f"(d[36]), "+f"(d[37]), "+f"(d[38]), "+f"(d[39]),
      "+f"(d[40]), "+f"(d[41]), "+f"(d[42]), "+f"(d[43]), "+f"(d[44]), "+f"(d[45]), "+f"(d[46]), "+f"(d[47]),
      "+f"(d[48]), "+f"(d[49]), "+f"(d[50]), "+f"(d[51]), "+f"(d[52]), "+f"(d[53]), "+f"(d[54]), "+f"(d[55]),
      "+f"(d[56]), "+f"(d[57]), "+f"(d[58]), "+f"(d[59]), "+f"(d[60]), "+f"(d[61]), "+f"(d[62]), "+f"(d[63]),
      "+f"(d[64]), "+f"(d[65]), "+f"(d[66]), "+f"(d[67]), "+f"(d[68]), "+f"(d[69]), "+f"(d[70]), "+f"(d[71]),
      "+f"(d[72]), "+f"(d[73]), "+f"(d[74]), "+f"(d[75]), "+f"(d[76]), "+f"(d[77]), "+f"(d[78]), "+f"(d[79]),
      "+f"(d[80]), "+f"(d[81]), "+f"(d[82]), "+f"(d[83]), "+f"(d[84]), "+f"(d[85]), "+f"(d[86]), "+f"(d[87]),
      "+f"(d[88]), "+f"(d[89]), "+f"(d[90]), "+f"(d[91]), "+f"(d[92]), "+f"(d[93]), "+f"(d[94]), "+f"(d[95]),
      "+f"(d[96]), "+f"(d[97]), "+f"(d[98]), "+f"(d[99]), "+f"(d[100]), "+f"(d[101]), "+f"(d[102]), "+f"(d[103]),
      "+f"(d[104]), "+f"(d[105]), "+f"(d[106]), "+f"(d[107])
    : "l"(da), "l"(db), "r"(sd));
}
__device__ __forceinline__ void wgmma_ss_n168(float (&d)[84], uint64_t da, uint64_t db, int sd) {
  asm volatile("{\n.reg .pred p;\nsetp.ne.b32 p, %86, 0;\n"
      "wgmma.mma_async.sync.aligned.m64n168k16.f32.bf16.bf16 {"
      "%0, %1, %2, %3, %4, %5, %6, %7, %8, %9, %10, %11, %12, %13, %14, %15, "
      "%16, %17, %18, %19, %20, %21, %22, %23, %24, %25, %26, %27, %28, %29, %30, %31, "
      "%32, %33, %34, %35, %36, %37, %38, %39, %40, %41, %42, %43, %44, %45, %46, %47, "
      "%48, %49, %50, %51, %52, %53, %54, %55, %56, %57, %58, %59, %60, %61, %62, %63, "
      "%64, %65, %66, %67, %68, %69, %70, %71, %72, %73, %74, %75, %76, %77, %78, %79, "
      "%80, %81, %82, %83"
      "}, %84, %85, p, 1, 1, 0, 1;\n}\n"
    : "+f"(d[0]), "+f"(d[1]), "+f"(d[2]), "+f"(d[3]), "+f"(d[4]), "+f"(d[5]), "+f"(d[6]), "+f"(d[7]),
      "+f"(d[8]), "+f"(d[9]), "+f"(d[10]), "+f"(d[11]), "+f"(d[12]), "+f"(d[13]), "+f"(d[14]), "+f"(d[15]),
      "+f"(d[16]), "+f"(d[17]), "+f"(d[18]), "+f"(d[19]), "+f"(d[20]), "+f"(d[21]), "+f"(d[22]), "+f"(d[23]),
      "+f"(d[24]), "+f"(d[25]), "+f"(d[26]), "+f"(d[27]), "+f"(d[28]), "+f"(d[29]), "+f"(d[30]), "+f"(d[31]),
      "+f"(d[32]), "+f"(d[33]), "+f"(d[34]), "+f"(d[35]), "+f"(d[36]), "+f"(d[37]), "+f"(d[38]), "+f"(d[39]),
      "+f"(d[40]), "+f"(d[41]), "+f"(d[42]), "+f"(d[43]), "+f"(d[44]), "+f"(d[45]), "+f"(d[46]), "+f"(d[47]),
      "+f"(d[48]), "+f"(d[49]), "+f"(d[50]), "+f"(d[51]), "+f"(d[52]), "+f"(d[53]), "+f"(d[54]), "+f"(d[55]),
      "+f"(d[56]), "+f"(d[57]), "+f"(d[58]), "+f"(d[59]), "+f"(d[60]), "+f"(d[61]), "+f"(d[62]), "+f"(d[63]),
      "+f"(d[64]), "+f"(d[65]), "+f"(d[66]), "+f"(d[67]), "+f"(d[68]), "+f"(d[69]), "+f"(d[70]), "+f"(d[71]),
      "+f"(d[72]), "+f"(d[73]), "+f"(d[74]), "+f"(d[75]), "+f"(d[76]), "+f"(d[77]), "+f"(d[78]), "+f"(d[79]),
      "+f"(d[80]), "+f"(d[81]), "+f"(d[82]), "+f"(d[83])
    : "l"(da), "l"(db), "r"(sd));
}
__device__ __forceinline__ void wgmma_ss_n160(float (&d)[80], uint64_t da, uint64_t db, int sd) {
  asm volatile("{\n.reg .pred p;\nsetp.ne.b32 p, %82, 0;\n"
      "wgmma.mma_async.sync.aligned.m64n160k16.f32.bf16.bf16 {"
      "%0, %1, %2, %3, %4, %5, %6, %7, %8, %9, %10, %11, %12, %13, %14, %15, "
      "%16, %17, %18, %19, %20, %21, %22, %23, %24, %25, %26, %27, %28, %29, %30, %31, "
      "%32, %33, %34, %35, %36, %37, %38, %39, %40, %41, %42, %43, %44, %45, %46, %47, "
      "%48, %49, %50, %51, %52, %53, %54, %55, %56, %57, %58, %59, %60, %61, %62, %63, "
      "%64, %65, %66, %67, %68, %69, %70, %71, %72, %73, %74, %75, %76, %77, %78, %79"
      "}, %80, %81, p, 1, 1, 0, 1;\n}\n"
    : "+f"(d[0]), "+f"(d[1]), "+f"(d[2]), "+f"(d[3]), "+f"(d[4]), "+f"(d[5]), "+f"(d[6]), "+f"(d[7]),
      "+f"(d[8]), "+f"(d[9]), "+f"(d[10]), "+f"(d[11]), "+f"(d[12]), "+f"(d[13]), "+f"(d[14]), "+f"(d[15]),
      "+f"(d[16]), "+f"(d[17]), "+f"(d[18]), "+f"(d[19]), "+f"(d[20]), "+f"(d[21]), "+f"(d[22]), "+f"(d[23]),
      "+f"(d[24]), "+f"(d[25]), "+f"(d[26]), "+f"(d[27]), "+f"(d[28]), "+f"(d[29]), "+f"(d[30]), "+f"(d[31]),
      "+f"(d[32]), "+f"(d[33]), "+f"(d[34]), "+f"(d[35]), "+f"(d[36]), "+f"(d[37]), "+f"(d[38]), "+f"(d[39]),
      "+f"(d[40]), "+f"(d[41]), "+f"(d[42]), "+f"(d[43]), "+f"(d[44]), "+f"(d[45]), "+f"(d[46]), "+f"(d[47]),
      "+f"(d[48]), "+f"(d[49]), "+f"(d[50]), "+f"(d[51]), "+f"(d[52]), "+f"(d[53]), "+f"(d[54]), "+f"(d[55]),
      "+f"(d[56]), "+f"(d[57]), "+f"(d[58]), "+f"(d[59]), "+f"(d[60]), "+f"(d[61]), "+f"(d[62]), "+f"(d[63]),
      "+f"(d[64]), "+f"(d[65]), "+f"(d[66]), "+f"(d[67]), "+f"(d[68]), "+f"(d[69]), "+f"(d[70]), "+f"(d[71]),
      "+f"(d[72]), "+f"(d[73]), "+f"(d[74]), "+f"(d[75]), "+f"(d[76]), "+f"(d[77]), "+f"(d[78]), "+f"(d[79])
    : "l"(da), "l"(db), "r"(sd));
}
__device__ __forceinline__ void wgmma_ss_n88(float (&d)[44], uint64_t da, uint64_t db, int sd) {
  asm volatile("{\n.reg .pred p;\nsetp.ne.b32 p, %46, 0;\n"
      "wgmma.mma_async.sync.aligned.m64n88k16.f32.bf16.bf16 {"
      "%0, %1, %2, %3, %4, %5, %6, %7, %8, %9, %10, %11, %12, %13, %14, %15, "
      "%16, %17, %18, %19, %20, %21, %22, %23, %24, %25, %26, %27, %28, %29, %30, %31, "
      "%32, %33, %34, %35, %36, %37, %38, %39, %40, %41, %42, %43"
      "}, %44, %45, p, 1, 1, 0, 1;\n}\n"
    : "+f"(d[0]), "+f"(d[1]), "+f"(d[2]), "+f"(d[3]), "+f"(d[4]), "+f"(d[5]), "+f"(d[6]), "+f"(d[7]),
      "+f"(d[8]), "+f"(d[9]), "+f"(d[10]), "+f"(d[11]), "+f"(d[12]), "+f"(d[13]), "+f"(d[14]), "+f"(d[15]),
      "+f"(d[16]), "+f"(d[17]), "+f"(d[18]), "+f"(d[19]), "+f"(d[20]), "+f"(d[21]), "+f"(d[22]), "+f"(d[23]),
      "+f"(d[24]), "+f"(d[25]), "+f"(d[26]), "+f"(d[27]), "+f"(d[28]), "+f"(d[29]), "+f"(d[30]), "+f"(d[31]),
      "+f"(d[32]), "+f"(d[33]), "+f"(d[34]), "+f"(d[35]), "+f"(d[36]), "+f"(d[37]), "+f"(d[38]), "+f"(d[39]),
      "+f"(d[40]), "+f"(d[41]), "+f"(d[42]), "+f"(d[43])
    : "l"(da), "l"(db), "r"(sd));
}
__device__ __forceinline__ void wgmma_ss_n80(float (&d)[40], uint64_t da, uint64_t db, int sd) {
  asm volatile("{\n.reg .pred p;\nsetp.ne.b32 p, %42, 0;\n"
      "wgmma.mma_async.sync.aligned.m64n80k16.f32.bf16.bf16 {"
      "%0, %1, %2, %3, %4, %5, %6, %7, %8, %9, %10, %11, %12, %13, %14, %15, "
      "%16, %17, %18, %19, %20, %21, %22, %23, %24, %25, %26, %27, %28, %29, %30, %31, "
      "%32, %33, %34, %35, %36, %37, %38, %39"
      "}, %40, %41, p, 1, 1, 0, 1;\n}\n"
    : "+f"(d[0]), "+f"(d[1]), "+f"(d[2]), "+f"(d[3]), "+f"(d[4]), "+f"(d[5]), "+f"(d[6]), "+f"(d[7]),
      "+f"(d[8]), "+f"(d[9]), "+f"(d[10]), "+f"(d[11]), "+f"(d[12]), "+f"(d[13]), "+f"(d[14]), "+f"(d[15]),
      "+f"(d[16]), "+f"(d[17]), "+f"(d[18]), "+f"(d[19]), "+f"(d[20]), "+f"(d[21]), "+f"(d[22]), "+f"(d[23]),
      "+f"(d[24]), "+f"(d[25]), "+f"(d[26]), "+f"(d[27]), "+f"(d[28]), "+f"(d[29]), "+f"(d[30]), "+f"(d[31]),
      "+f"(d[32]), "+f"(d[33]), "+f"(d[34]), "+f"(d[35]), "+f"(d[36]), "+f"(d[37]), "+f"(d[38]), "+f"(d[39])
    : "l"(da), "l"(db), "r"(sd));
}
__device__ __forceinline__ void wgmma_rs_n128(float (&d)[64], uint32_t a0, uint32_t a1, uint32_t a2, uint32_t a3,
                                  uint64_t db, int sd) {
  asm volatile("{\n.reg .pred p;\nsetp.ne.b32 p, %69, 0;\n"
      "wgmma.mma_async.sync.aligned.m64n128k16.f32.bf16.bf16 {"
      "%0, %1, %2, %3, %4, %5, %6, %7, %8, %9, %10, %11, %12, %13, %14, %15, "
      "%16, %17, %18, %19, %20, %21, %22, %23, %24, %25, %26, %27, %28, %29, %30, %31, "
      "%32, %33, %34, %35, %36, %37, %38, %39, %40, %41, %42, %43, %44, %45, %46, %47, "
      "%48, %49, %50, %51, %52, %53, %54, %55, %56, %57, %58, %59, %60, %61, %62, %63"
      "}, {%64, %65, %66, %67}, %68, p, 1, 1, 0;\n}\n"
    : "+f"(d[0]), "+f"(d[1]), "+f"(d[2]), "+f"(d[3]), "+f"(d[4]), "+f"(d[5]), "+f"(d[6]), "+f"(d[7]),
      "+f"(d[8]), "+f"(d[9]), "+f"(d[10]), "+f"(d[11]), "+f"(d[12]), "+f"(d[13]), "+f"(d[14]), "+f"(d[15]),
      "+f"(d[16]), "+f"(d[17]), "+f"(d[18]), "+f"(d[19]), "+f"(d[20]), "+f"(d[21]), "+f"(d[22]), "+f"(d[23]),
      "+f"(d[24]), "+f"(d[25]), "+f"(d[26]), "+f"(d[27]), "+f"(d[28]), "+f"(d[29]), "+f"(d[30]), "+f"(d[31]),
      "+f"(d[32]), "+f"(d[33]), "+f"(d[34]), "+f"(d[35]), "+f"(d[36]), "+f"(d[37]), "+f"(d[38]), "+f"(d[39]),
      "+f"(d[40]), "+f"(d[41]), "+f"(d[42]), "+f"(d[43]), "+f"(d[44]), "+f"(d[45]), "+f"(d[46]), "+f"(d[47]),
      "+f"(d[48]), "+f"(d[49]), "+f"(d[50]), "+f"(d[51]), "+f"(d[52]), "+f"(d[53]), "+f"(d[54]), "+f"(d[55]),
      "+f"(d[56]), "+f"(d[57]), "+f"(d[58]), "+f"(d[59]), "+f"(d[60]), "+f"(d[61]), "+f"(d[62]), "+f"(d[63])
    : "r"(a0), "r"(a1), "r"(a2), "r"(a3), "l"(db), "r"(sd));
}
__device__ __forceinline__ void wgmma_rs_n24(float (&d)[12], uint32_t a0, uint32_t a1, uint32_t a2, uint32_t a3,
                                  uint64_t db, int sd) {
  asm volatile("{\n.reg .pred p;\nsetp.ne.b32 p, %17, 0;\n"
      "wgmma.mma_async.sync.aligned.m64n24k16.f32.bf16.bf16 {"
      "%0, %1, %2, %3, %4, %5, %6, %7, %8, %9, %10, %11"
      "}, {%12, %13, %14, %15}, %16, p, 1, 1, 1;\n}\n"
    : "+f"(d[0]), "+f"(d[1]), "+f"(d[2]), "+f"(d[3]), "+f"(d[4]), "+f"(d[5]), "+f"(d[6]), "+f"(d[7]),
      "+f"(d[8]), "+f"(d[9]), "+f"(d[10]), "+f"(d[11])
    : "r"(a0), "r"(a1), "r"(a2), "r"(a3), "l"(db), "r"(sd));
}

constexpr int K1_ST = 4, K1_STAGE = 45056;
constexpr int K1_SMEM = K1_ST * K1_STAGE + 640   + 1536   + 2560   + 128;

__device__ __forceinline__ float2 row_stats(uint4 v0, uint4 v1, uint4 v2) {
  const uint32_t wd[12] = {v0.x, v0.y, v0.z, v0.w, v1.x, v1.y, v1.z, v1.w, v2.x, v2.y, v2.z, v2.w};
  float sx = 0.f, sq = 0.f;
#pragma unroll
  for (int e = 0; e < 12; e++) {
    const float lo = bf_lo(wd[e]), hi = bf_hi(wd[e]);
    sx += lo + hi; sq = fmaf(lo, lo, fmaf(hi, hi, sq));
  }
#pragma unroll
  for (int o = 16; o; o >>= 1) { sx += __shfl_xor_sync(~0u, sx, o); sq += __shfl_xor_sync(~0u, sq, o); }
  const float mean = sx * (1.f / D_);
  return make_float2(rsqrtf(fmaxf(sq * (1.f / D_) - mean * mean, 0.f) + 1e-5f), mean);
}

__global__ void __cluster_dims__(2, 1, 1) __launch_bounds__(512, 1)
k1_qkv(const __grid_constant__ CUtensorMap tmx, const __grid_constant__ CUtensorMap tmw,
       const bf16* __restrict__ x, const bf16* __restrict__ w, const bf16* __restrict__ wo) {
  extern __shared__ __align__(1024) uint8_t sm[];
  float* cs = (float*)(sm + K1_ST * K1_STAGE);
  float2* rowab = (float2*)(sm + K1_ST * K1_STAGE + 640);
  float* red = (float*)(sm + K1_ST * K1_STAGE + 2176);
  const uint32_t sbase = smem_u32(sm);
  const uint32_t fullb = sbase + K1_ST * K1_STAGE + 4736, emptyb = fullb + 8 * K1_ST;
  const int tid = threadIdx.x, lane = tid & 31;
  const int warp = __shfl_sync(~0u, tid >> 5, 0);
  const int rank = blockIdx.x & 1, cl = blockIdx.x >> 1;
  const int m = cl / 6, n = (cl - m * 6) * 2 + rank;
  if (tid == 0) STAMP(0, 0);

  if (warp == 12) {
    if (lane == 0) {
      prefetch_map(&tmx); prefetch_map(&tmw);
      for (int i = 0; i < K1_ST; i++) { mbar_init(fullb + 8 * i, 1); mbar_init(emptyb + 8 * i, 6); }
      asm volatile("fence.mbarrier_init.release.cluster;" ::: "memory");
    }
    __syncwarp();
    cluster_arrive();
    bar_arrive(4, 512);
    if (lane == 0) {
      for (int kt = 0; kt < K1_ST; kt++) mbar_expect(fullb + 8 * kt, K1_STAGE);
#pragma unroll
      for (int j = 0; j < 5; j++) tma2d(sbase + 24576 + j * 4096, &tmw, n * 160 + j * 32, 0, fullb);
    }
    __syncwarp();
    cluster_wait();
    if (lane == 0) {
#pragma unroll 1
      for (int kt = 0; kt < 10; kt++) {
        const int s = kt % K1_ST;
        const uint32_t sa = sbase + s * K1_STAGE;
        if (kt >= K1_ST) {
          mbar_wait(emptyb + 8 * s, ((kt / K1_ST) - 1) & 1);
          mbar_expect(fullb + 8 * s, K1_STAGE);
        }
        tma2d_mc(sa + rank * 12288, &tmx, kt * 64, m * 192 + rank * 96, fullb + 8 * s);
        if (kt > 0) {
#pragma unroll
          for (int j = 0; j < 5; j++) tma2d(sa + 24576 + j * 4096, &tmw, n * 160 + j * 32, kt * 64, fullb + 8 * s);
        }
        if (kt == K1_ST - 1) pdl_trigger();
      }
    }
    __syncwarp();
    cluster_arrive();
  } else if (warp > 12) {
    cluster_arrive();
    const int t96 = tid - 416;
    const uint32_t tag = __ldcg(&g_epoch) + 1;
    bar_sync(4, 512);
    mbar_wait(fullb, 0);
    if (m < 10) {
      const int ck = t96 % 20, rg = min(t96 / 20, 3);
      uint4 wv[16];
#pragma unroll
      for (int i = 0; i < 16; i++) wv[i] = ldg_nc(w + (size_t)(m * 64 + rg * 16 + i) * 1920 + n * 160 + ck * 8);
      float acc8[8];
#pragma unroll
      for (int i = 0; i < 8; i++) acc8[i] = 0.f;
#pragma unroll
      for (int i = 0; i < 16; i++) ACC8(acc8, wv[i]);
      *(float4*)&red[rg * 160 + ck * 8] = make_float4(acc8[0], acc8[1], acc8[2], acc8[3]);
      *(float4*)&red[rg * 160 + ck * 8 + 4] = make_float4(acc8[4], acc8[5], acc8[6], acc8[7]);
      bar_sync(1, 96);
      if (t96 < 80) {
        const float2 p0 = *(const float2*)&red[t96 * 2], p1 = *(const float2*)&red[160 + t96 * 2];
        const float2 p2 = *(const float2*)&red[320 + t96 * 2], p3 = *(const float2*)&red[480 + t96 * 2];
        st_relaxed(&g_cpart[(m * 12 + n) * 80 + t96], (p0.x + p1.x) + (p2.x + p3.x), (p0.y + p1.y) + (p2.y + p3.y), tag);
      }
    }
    if (tid == 416) STAMP(5, 7);
    bool ok = false;
    for (int it = 0; it < 64 && !ok; it++) {
      uint4 p[10], st[2];
#pragma unroll
      for (int k = 0; k < 10; k++) p[k] = ld_relaxed(&g_cpart[(k * 12 + n) * 80 + min(t96, 79)]);
#pragma unroll
      for (int k = 0; k < 2; k++) st[k] = ld_relaxed(&g_rowstat[min(m * 192 + k * 96 + t96, S_ - 1)]);
      ok = true;
      float s0 = 0.f, s1 = 0.f;
#pragma unroll
      for (int k = 0; k < 10; k++) {
        ok = ok && p[k].y == tag && p[k].w == tag;
        s0 += __uint_as_float(p[k].x); s1 += __uint_as_float(p[k].z);
      }
      if (t96 < 80) *(float2*)&cs[t96 * 2] = make_float2(s0, s1);
#pragma unroll
      for (int k = 0; k < 2; k++) {
        ok = ok && st[k].y == tag && st[k].w == tag;
        rowab[k * 96 + t96] = make_float2(__uint_as_float(st[k].x), -__uint_as_float(st[k].x) * __uint_as_float(st[k].z));
      }
      ok = __all_sync(~0u, ok);
      if (!ok) __nanosleep(300);
    }
    if (!ok) {
      const int c2 = min(t96, 79);
      float s0 = 0.f, s1 = 0.f;
#pragma unroll 1
      for (int k = 0; k < D_; k++) {
        const uint32_t v = *(const uint32_t*)(w + (size_t)k * 1920 + n * 160 + c2 * 2);
        s0 += bf_lo(v); s1 += bf_hi(v);
      }
      if (t96 < 80) *(float2*)&cs[t96 * 2] = make_float2(s0, s1);
#pragma unroll 1
      for (int i = 0; i < 64; i++) {
        const int r = (i >> 5) * 96 + (t96 & ~31) + (i & 31);
        const bf16* xr = x + (size_t)min(m * 192 + r, S_ - 1) * D_ + lane * 8;
        const float2 st = row_stats(ldg_nc(xr), ldg_nc(xr + 256), lane < 16 ? ldg_nc(xr + 512) : make_uint4(0u, 0u, 0u, 0u));
        if (lane == 0) rowab[r] = make_float2(st.x, -st.x * st.y);
      }
    }
    __syncwarp();
    bar_arrive(2, 96 + 384);
    bar_sync(1, 96);
    if (tid == 416) STAMP(0, 5);
    if (blockIdx.x < 128) {
      uint4 v[5];
      const int ck = min(t96, 79), nt = ck / 10;
#pragma unroll
      for (int i = 0; i < 5; i++) {
        const int k = blockIdx.x * 5 + i, pr = k / 40, r = k - pr * 40;
        v[i] = ldg_nc(wo + (size_t)(pr * 40 + (r < 16 ? r : (r < 32 ? r + 4 : (r < 36 ? r - 16 : r)))) * D_ + ck * 8);
      }
#pragma unroll
      for (int i = 0; i < 5; i++) {
        const int k = blockIdx.x * 5 + i;
        g_wo[((nt * 10 + (k >> 6)) * 10 + ck - nt * 10) * 64 + (k & 63)] = v[i];
        float t = ((bf_lo(v[i].x) + bf_hi(v[i].x)) + (bf_lo(v[i].y) + bf_hi(v[i].y))) +
                  ((bf_lo(v[i].z) + bf_hi(v[i].z)) + (bf_lo(v[i].w) + bf_hi(v[i].w)));
        if (t96 >= 80) t = 0.f;
#pragma unroll
        for (int o = 16; o; o >>= 1) t += __shfl_xor_sync(~0u, t, o);
        if (lane == 0) red[(t96 >> 5) * 8 + i] = t;
      }
      bar_sync(1, 96);
      if (t96 < 5) {
        const float mu = (red[t96] + red[8 + t96] + red[16 + t96]) * (1.f / D_);
        const float hi = bf_lo(pack_bf16(mu, 0.f));
        g_wm[blockIdx.x * 5 + t96] = make_uint4(pack_bf16(hi, mu - hi), 0u, 0u, 0u);
      }
    }
    if (tid == 416) STAMP(0, 7);
    __syncwarp();
    cluster_wait();
    cluster_arrive();
  } else {
    cluster_arrive();
    float acc[80];
    const uint64_t da0 = mkdesc(sbase + (warp >> 2) * 8192, 16, 1024, 1);
    const uint64_t db0 = mkdesc(sbase + 24576, 4096, 512, 2);
    const uint32_t tag = __ldcg(&g_epoch) + 1;
    const int srow = m * 192 + n * 16 + warp * 2;
    const bool dostat = warp < 8 && srow < S_;
    uint4 xv[2][3];
    bar_sync(4, 512);
    cluster_wait();
#pragma unroll
    for (int kt = 0; kt < 10; kt++) {
      const int s = kt % K1_ST;
      mbar_wait(fullb + 8 * s, (kt / K1_ST) & 1);
      if (kt == 0 && tid == 0) STAMP(0, 1);
      if (kt == 2 && tid == 0) STAMP(5, 0);
      if (kt == 4 && tid == 0) STAMP(5, 1);
      if (kt == 7 && tid == 0) STAMP(5, 2);
      const uint64_t da = da0 + s * (K1_STAGE >> 4), db = db0 + s * (K1_STAGE >> 4);
      WG_FENCE();
#pragma unroll
      for (int k = 0; k < 4; k++) wgmma_ss_n160(acc, da + k * 2, db + k * 64, (kt | k) != 0);
      WG_COMMIT();
      if (kt > 0) {
        WG_WAIT(1);
        if (kt - 1 + K1_ST < 10 && (tid & 127) < 2) mbar_arrive_cta(emptyb + 8 * ((kt - 1) % K1_ST), tid & 1);
      }
      if (kt == 0) {
#pragma unroll
        for (int i = 0; i < 2; i++) {
          const bf16* xr = x + (size_t)min(srow + i, S_ - 1) * D_ + lane * 8;
          xv[i][0] = xv[i][1] = xv[i][2] = make_uint4(0u, 0u, 0u, 0u);
          if (dostat) { xv[i][0] = ldg_nc(xr); xv[i][1] = ldg_nc(xr + 256); }
          if (dostat && lane < 16) xv[i][2] = ldg_nc(xr + 512);
        }
      }
      if ((kt == 2 || kt == 3) && dostat) {
        const float2 st = row_stats(xv[kt - 2][0], xv[kt - 2][1], xv[kt - 2][2]);
        if (lane == 0) st_relaxed(&g_rowstat[srow + kt - 2], st.x, st.y, tag);
      }
      __syncwarp();
    }
    cluster_arrive();
    WG_WAIT(0);
    fence_regs(acc);
    if (tid == 0) STAMP(0, 2);
    bar_sync(2, 96 + 384);
    if (tid == 0) STAMP(0, 3);
    const int row0 = m * 192 + warp * 16;
    if (row0 < S_) {
      const int g = lane >> 2, c = lane & 3, sec = n >> 2, grp = (row0 & 127) >> 3;
      const bool lo = c < 2;
      const float2 ab0 = rowab[warp * 16 + g], ab1 = rowab[warp * 16 + g + 8];
      const bool p0 = sec == 1 && ((POLY_MASK >> grp) & 1), p1 = sec == 1 && ((POLY_MASK >> (grp + 1)) & 1);
      const uint32_t padqv = sec == 0 ? (c == 2 ? 0x3F803F80u : 0x00003F80u) : (sec == 2 && c == 2 ? 0x00003F80u : 0u);
      const uint32_t padk = c == 2 ? 0x4A7A4B00u : 0x00004653u;
      const uint32_t pad0 = p0 ? padk : padqv, pad1 = p1 ? padk : padqv;
      const float f0 = sec == 0 ? QSCALE : (p0 ? 32768.f : 1.f), f1 = sec == 0 ? QSCALE : (p1 ? 32768.f : 1.f);
      const float a0 = ab0.x * f0, b0 = ab0.y * f0, a1 = ab1.x * f1, b1 = ab1.y * f1;
      const float r0 = p0 ? 9.313225746154785e-10f : 1.f, r1 = p1 ? 9.313225746154785e-10f : 1.f;
      const int cst = sec == 1 ? 2048 : 128, gst = sec == 1 ? 128 : 384;
      uint8_t* pe = (uint8_t*)g_qkv + (size_t)(n * 8) * HEAD_IMG + (row0 >> 7) * 6144 + grp * gst + lane * 4;
      uint8_t* pe1 = pe + cst;
      uint8_t* pe2 = pe1 + cst;
      uint8_t* pf = pe + gst;
      uint8_t* pf1 = pf + cst;
      uint8_t* pf2 = pf1 + cst;
#pragma unroll
      for (int hp = 0; hp < 4; hp++) {
        uint32_t u[5], v[5];
        float su[5], sv[5];
#pragma unroll
        for (int i = 0; i < 5; i++) {
          const int j = hp * 5 + i;
          const float2 t = *(const float2*)&cs[j * 8 + c * 2];
          const float x0 = fmaf(acc[4 * j], a0, b0 * t.x), x1 = fmaf(acc[4 * j + 1], a0, b0 * t.y);
          const float y0 = fmaf(acc[4 * j + 2], a1, b1 * t.x), y1 = fmaf(acc[4 * j + 3], a1, b1 * t.y);
          u[i] = pack_bf16(x0, x1); v[i] = pack_bf16(y0, y1);
          su[i] = fmaf(x0, x0, x1 * x1); sv[i] = fmaf(y0, y0, y1 * y1);
        }
        constexpr int HE = HEAD_IMG;
        const int oe = hp * 2 * HE, oo = oe + HE;
        *(uint32_t*)(pe + oe) = u[0];  *(uint32_t*)(pf + oe) = v[0];
        *(uint32_t*)(pe1 + oe) = u[1]; *(uint32_t*)(pf1 + oe) = v[1];
        *(uint32_t*)(pe2 + oe) = lo ? u[2] : pad0; *(uint32_t*)(pf2 + oe) = lo ? v[2] : pad1;
        *(uint32_t*)(pe + oo) = __shfl_xor_sync(~0u, lo ? u[3] : u[2], 2);
        *(uint32_t*)(pf + oo) = __shfl_xor_sync(~0u, lo ? v[3] : v[2], 2);
        *(uint32_t*)(pe1 + oo) = __shfl_xor_sync(~0u, lo ? u[4] : u[3], 2);
        *(uint32_t*)(pf1 + oo) = __shfl_xor_sync(~0u, lo ? v[4] : v[3], 2);
        const uint32_t tu = __shfl_xor_sync(~0u, u[4], 2), tv = __shfl_xor_sync(~0u, v[4], 2);
        *(uint32_t*)(pe2 + oo) = lo ? tu : pad0; *(uint32_t*)(pf2 + oo) = lo ? tv : pad1;
        if (sec < 2) {
          float e0 = (su[0] + su[1] + (lo ? su[2] : 0.f)) * r0, e1 = (sv[0] + sv[1] + (lo ? sv[2] : 0.f)) * r1;
          float o0 = (su[3] + su[4] + (lo ? 0.f : su[2])) * r0, o1 = (sv[3] + sv[4] + (lo ? 0.f : sv[2])) * r1;
          e0 += __shfl_xor_sync(~0u, e0, 1); e1 += __shfl_xor_sync(~0u, e1, 1);
          o0 += __shfl_xor_sync(~0u, o0, 1); o1 += __shfl_xor_sync(~0u, o1, 1);
          e0 += __shfl_xor_sync(~0u, e0, 2); e1 += __shfl_xor_sync(~0u, e1, 2);
          o0 += __shfl_xor_sync(~0u, o0, 2); o1 += __shfl_xor_sync(~0u, o1, 2);
          const uint32_t em = __reduce_max_sync(~0u, max(__float_as_uint(e0), __float_as_uint(e1)));
          const uint32_t om = __reduce_max_sync(~0u, max(__float_as_uint(o0), __float_as_uint(o1)));
          if (lane < 2) g_nrm[(n * 8 + hp * 2 + lane) * 128 + (row0 >> 4)] = __uint_as_float(lane ? om : em);
        }
      }
    }
    if (tid == 0) STAMP(0, 4);
  }
  cluster_wait();
  if (tid == 0) STAMP(0, 6);
}

constexpr int K2_SMEM = 2 * HEAD_IMG + 2 * 6144 + 2 * 10240 + 256;

__device__ __forceinline__ uint64_t desc64(uint32_t lo, uint32_t hi) {
  uint64_t d;
  asm("mov.b64 %0, {%1, %2};" : "=l"(d) : "r"(lo), "r"(hi));
  return d;
}
__device__ __forceinline__ uint32_t exp_pair(bool poly, float a, float b, uint32_t mk) {
  if (poly) {
    const uint32_t pk = __byte_perm(__float_as_uint(a), __float_as_uint(b), 0x6521);
    uint32_t m, q;
    asm("lop3.b32 %0, %1, %2, 0x3f803f80, 0xEA;" : "=r"(m) : "r"(pk), "r"(mk));
    asm("fma.rn.bf16x2 %0, %1, %1, %2;" : "=r"(q) : "r"(m), "r"(0x40014001u));
    return pk - m + q;
  }
  return pack_bf16(ex2(a), ex2(b));
}
#define PV_GR 2
__device__ __forceinline__ void exp_pv(const float (&s)[64], float (&o)[12], uint64_t dv, uint32_t mk) {
#pragma unroll
  for (int k0 = 0; k0 < 8; k0 += PV_GR) {
    uint32_t p[4 * PV_GR];
#pragma unroll
    for (int i = 0; i < 4 * PV_GR; i++)
      p[i] = exp_pair((POLY_MASK >> (k0 * 2 + i / 2)) & 1, s[k0 * 8 + 2 * i], s[k0 * 8 + 2 * i + 1], mk);
    WG_FENCE();
#pragma unroll
    for (int k = 0; k < PV_GR; k++)
      wgmma_rs_n24(o, p[4 * k], p[4 * k + 1], p[4 * k + 2], p[4 * k + 3], dv + (k0 + k) * 48, 1);
  }
}
__device__ __forceinline__ void load_q(uint32_t (&q)[6], const uint8_t* p) {
  q[0] = __ldcg((const uint32_t*)p);         q[1] = __ldcg((const uint32_t*)(p + 384));
  q[2] = __ldcg((const uint32_t*)(p + 128)); q[3] = __ldcg((const uint32_t*)(p + 512));
  q[4] = __ldcg((const uint32_t*)(p + 256)); q[5] = __ldcg((const uint32_t*)(p + 640));
}
__device__ __forceinline__ float rcp(float x) {
  float y;
  asm("rcp.approx.ftz.f32 %0, %1;" : "=f"(y) : "f"(x));
  return y;
}
__device__ __forceinline__ int img_off(int chunk) { return (chunk >> 3) * 16384 + (chunk & 7) * 128; }
__device__ __forceinline__ void store_o(const float (&o)[12], int tile) {
  int tid, bid;
  asm volatile("mov.u32 %0, %%tid.x;" : "=r"(tid));
  asm volatile("mov.u32 %0, %%ctaid.x;" : "=r"(bid));
  const int head = bid >> 2;
  uint8_t* dst = (uint8_t*)g_o + ((bid & 3) * 4 + (tile >> 1)) * 163840 + (tile & 1) * 8192 + ((tid >> 5) & 3) * 2048 + (tid & 31) * 4;
  const int oc = (head >> 1) * 5 + (head & 1) * 2;
  const int o0 = img_off(oc), o1 = img_off(oc + 1), o2 = img_off((head >> 1) * 5 + 4) + (head & 1) * 8;
  const float i0 = rcp(__shfl_sync(~0u, o[8], 2, 4)), i1 = rcp(__shfl_sync(~0u, o[10], 2, 4));
  *(uint32_t*)(dst + o0) = pack_bf16(o[0] * i0, o[1] * i0); *(uint32_t*)(dst + o0 + 1024) = pack_bf16(o[2] * i1, o[3] * i1);
  *(uint32_t*)(dst + o1) = pack_bf16(o[4] * i0, o[5] * i0); *(uint32_t*)(dst + o1 + 1024) = pack_bf16(o[6] * i1, o[7] * i1);
  if ((tid & 3) < 2) {
    *(uint32_t*)(dst + o2) = pack_bf16(o[8] * i0, o[9] * i0);
    *(uint32_t*)(dst + o2 + 1024) = pack_bf16(o[10] * i1, o[11] * i1);
  }
}

__global__ void __launch_bounds__(512, 1)
k2_attn(const __grid_constant__ CUtensorMap tmg, const __grid_constant__ CUtensorMap tmu,
        const __grid_constant__ CUtensorMap tmd, uint32_t mk) {
  extern __shared__ __align__(1024) uint8_t sm[];
  const uint32_t sbase = smem_u32(sm);
  float* part = (float*)(sm + 2 * HEAD_IMG);
  const uint32_t rbuf = sbase + 2 * HEAD_IMG + 2 * 6144;
  const uint32_t kvb = rbuf + 2 * 10240;
  const uint32_t partb = kvb + 128, rbar = kvb + 144;
  const int tid = threadIdx.x, lane = tid & 31;
  const int warp = __shfl_sync(~0u, tid >> 5, 0);
  const int head = blockIdx.x >> 2, qb = blockIdx.x & 3;

  if (tid == 0) STAMP(1, 0);
  if (tid == 0) {
    for (int i = 0; i < 16; i++) mbar_init(kvb + 8 * i, 1);
    mbar_init(partb, 128); mbar_init(partb + 8, 128); mbar_init(rbar, 1); mbar_init(rbar + 8, 1);
    asm volatile("fence.mbarrier_init.release.cluster;" ::: "memory");
  }
  __syncthreads();

  if (warp >= 12) {
    asm volatile("setmaxnreg.dec.sync.aligned.u32 32;");
    if (tid == 384) {
      pdl_wait();
      pdl_trigger();
      const uint8_t* kimg = (const uint8_t*)g_qkv + (size_t)(32 + head) * HEAD_IMG;
#pragma unroll 1
      for (int b = 0; b < 16; b++) {
        mbar_expect(kvb + 8 * b, 12288);
        bulk_ld(sbase + b * 6144, kimg + b * 6144, 6144, kvb + 8 * b);
        bulk_ld(sbase + HEAD_IMG + b * 6144, kimg + 32 * HEAD_IMG + b * 6144, 6144, kvb + 8 * b);
        if (b >= 2) mbar_wait(kvb + 8 * (b - 1), 0);

      }
      if (blockIdx.x == 0) g_epoch = g_epoch + 1;
      mbar_wait(kvb + 8 * 15, 0);
      STAMP(1, 2);
      uint8_t* pdst = nullptr;
      uint32_t pbytes = 0;
#pragma unroll 1
      for (int i = 0; i < 7; i++) {
        const int p = blockIdx.x + 128 * i;
        uint8_t* dst = nullptr;
        uint32_t bytes = 0;
        if (i < 6 && p < 696) {
          asm volatile("cp.async.bulk.wait_group.read 0;" ::: "memory");
          if (p < 480) {
            const int nk = p / 6, r = p - nk * 6, nt = nk / 10, kt = nk - nt * 10, up = r / 3;
            bytes = 9216;
            dst = (uint8_t*)g_wgu + (size_t)(nk * 54 + r * 9) * 1024;
            mbar_expect(rbar + 8 * (i & 1), bytes);
            tma3d(rbuf + (i & 1) * 10240, up ? &tmu : &tmg, kt * 64, nt * 27 + (r - up * 3) * 9, rbar + 8 * (i & 1));
          } else {
            const int nk = p - 480, nt = nk / 27, kt = nk - nt * 27;
            bytes = 10240;
            dst = (uint8_t*)g_wd + (size_t)nk * 10240;
            mbar_expect(rbar + 8 * (i & 1), bytes);
            tma3d(rbuf + (i & 1) * 10240, &tmd, kt * 64, nt * 10, rbar + 8 * (i & 1));
          }
        }
        if (pbytes) {
          mbar_wait(rbar + 8 * ((i - 1) & 1), ((i - 1) >> 1) & 1);
          bulk_st(pdst, rbuf + ((i - 1) & 1) * 10240, pbytes);
          asm volatile("cp.async.bulk.commit_group;" ::: "memory");
        }
        pdst = dst; pbytes = bytes;
      }
      asm volatile("cp.async.bulk.wait_group.read 0;" ::: "memory");
      STAMP(1, 6);
    }
  } else {
    asm volatile("setmaxnreg.inc.sync.aligned.u32 160;");
    const int wg = warp >> 2;
    const uint8_t* qthr = (const uint8_t*)g_qkv + (size_t)head * HEAD_IMG + qb * 64 * 384 + (warp & 3) * 768 + lane * 4;
    const uint32_t klo0 = ((sbase & 0x3FFFF) >> 4) | (128u << 16), vlo0 = (((sbase + HEAD_IMG) & 0x3FFFF) >> 4) | (24u << 16);
    constexpr uint64_t KSTEP2 = (uint64_t)(int64_t)(256 - (128 << 16));
    constexpr uint64_t KV2K = 384 - (HEAD_IMG >> 4) + (104 << 16);
    const int nun = wg == 1 ? 4 : 3;
    uint32_t utile = wg == 0 ? 0x210u : (wg == 1 ? 0x4235u : 0x576u);
    uint32_t ubeg = wg == 0 ? 0u : (wg == 1 ? 0x0b00u : 0x600u);
    uint32_t ulen = wg == 0 ? 0x0b1010u : (wg == 1 ? 0x10051006u : 0x0a1010u);
    pdl_wait();
    if (tid == 0) STAMP(1, 1);
    uint32_t q[6];
    load_q(q, qthr + (utile & 15) * 3072);
    bool fast;
    {
      const float4 kn = __ldcg((const float4*)&g_nrm[(32 + head) * 128 + lane * 4]);
      const float qv = __ldcg(&g_nrm[head * 128 + qb * 32 + lane]);
      const uint32_t km = max(max(__float_as_uint(kn.x), __float_as_uint(kn.y)), max(__float_as_uint(kn.z), __float_as_uint(kn.w)));
      const float k2 = __uint_as_float(__reduce_max_sync(~0u, km)), q2 = __uint_as_float(__reduce_max_sync(~0u, __float_as_uint(qv)));
      fast = q2 * k2 <= 3400.f;
    }
    if (fast) {
#pragma unroll 1
      for (int u = 0; u < nun; u++) {
        const uint32_t b0 = ubeg & 15;
        const bool wt = u == 0 || (wg == 1 && u == 1);
        float s[64], o[12];
#pragma unroll
        for (int i = 0; i < 12; i++) o[i] = 0.f;
        uint32_t vlo = vlo0 + b0 * 384, kb = kvb + b0 * 8;
        const uint32_t vend = vlo + ((ulen & 255) - 1) * 384;
        if (wt) mbar_wait(kb, 0);
        if (tid == 0) STAMP(5, 4 + u);
        fence_regs(o);
        WG_FENCE();
        wgmma_rs_n128(s, q[0], q[1], q[2], q[3], desc64(klo0 + b0 * 384, 8), 0);
        wgmma_rs_n128(s, q[4], q[5], 0, 0, desc64(klo0 + b0 * 384, 8) + KSTEP2, 1);
        WG_COMMIT();
#pragma unroll 1
        for (; vlo != vend; vlo += 384) {
          if (wt) { kb += 8; mbar_wait(kb, 0); }
          WG_WAIT(0);
          fence_regs(s); fence_regs(o);
          const uint64_t dv = desc64(vlo, 8);
          exp_pv(s, o, dv, mk);
          wgmma_rs_n128(s, q[0], q[1], q[2], q[3], dv + KV2K, 0);
          wgmma_rs_n128(s, q[4], q[5], 0, 0, dv + (KV2K + KSTEP2), 1);
          WG_COMMIT();
        }
        WG_WAIT(0);
        fence_regs(s); fence_regs(o);
        if (u + 1 < nun) load_q(q, qthr + ((utile >> 4) & 15) * 3072);
        exp_pv(s, o, desc64(vlo, 8), mk);
        WG_COMMIT();
        WG_WAIT(0);
        fence_regs(o);
        if (wg == 1 && !(u & 1)) {
          float4* pp = (float4*)(part + u * 768) + (tid & 127);
          pp[0] = make_float4(o[0], o[1], o[2], o[3]);
          pp[128] = make_float4(o[4], o[5], o[6], o[7]);
          pp[256] = make_float4(o[8], o[9], o[10], o[11]);
          mbar_arrive(partb + 4 * u);
        } else {
          if (wg != 1 && u == 2) {
            const int pi = wg == 0 ? 1 : 0;
            mbar_wait(partb + 8 * pi, 0);
            const float4* pp = (const float4*)(part + pi * 1536) + (tid & 127);
            const float4 x0 = pp[0], x1 = pp[128], x2 = pp[256];
            o[0] += x0.x; o[1] += x0.y; o[2] += x0.z; o[3] += x0.w; o[4] += x1.x; o[5] += x1.y;
            o[6] += x1.z; o[7] += x1.w; o[8] += x2.x; o[9] += x2.y; o[10] += x2.z; o[11] += x2.w;
          }
          store_o(o, utile & 15);
        }
        utile >>= 4; ubeg >>= 4; ulen >>= 8;
      }
      if ((tid & 127) == 0) STAMP(1, 3 + wg);
    } else {
#pragma unroll 1
      for (int tile = wg; tile < 8; tile += 3) {
        load_q(q, qthr + tile * 3072);
        if ((lane & 3) >= 2) { q[4] = 0; q[5] = 0; }
        float o[12], m0 = -INFINITY, m1 = -INFINITY;
#pragma unroll
        for (int i = 0; i < 12; i++) o[i] = 0.f;
#pragma unroll 1
        for (int b = 0; b < 16; b++) {
          float s[64];
          mbar_wait(kvb + 8 * b, 0);
          WG_FENCE();
          wgmma_rs_n128(s, q[0], q[1], q[2], q[3], desc64(klo0 + b * 384, 8), 0);
          wgmma_rs_n128(s, q[4], q[5], 0, 0, desc64(klo0 + b * 384, 8) + KSTEP2, 1);
          WG_COMMIT();
          WG_WAIT(0);
          fence_regs(s);
          float x0 = m0, x1 = m1;
#pragma unroll
          for (int j = 0; j < 16; j++) {
            if ((POLY_MASK >> j) & 1) {
#pragma unroll
              for (int i = 0; i < 4; i++) s[4 * j + i] *= (1.f / 32768.f);
            }
            x0 = fmaxf(x0, fmaxf(s[4 * j], s[4 * j + 1]));
            x1 = fmaxf(x1, fmaxf(s[4 * j + 2], s[4 * j + 3]));
          }
          x0 = fmaxf(x0, __shfl_xor_sync(~0u, x0, 1)); x0 = fmaxf(x0, __shfl_xor_sync(~0u, x0, 2));
          x1 = fmaxf(x1, __shfl_xor_sync(~0u, x1, 1)); x1 = fmaxf(x1, __shfl_xor_sync(~0u, x1, 2));
          const float al0 = ex2(m0 - x0), al1 = ex2(m1 - x1);
          m0 = x0; m1 = x1;
#pragma unroll
          for (int i = 0; i < 12; i++) o[i] *= (i & 2) ? al1 : al0;
          uint32_t p[32];
#pragma unroll
          for (int i = 0; i < 32; i++) {
            const float mm = (i & 1) ? m1 : m0;
            p[i] = pack_bf16(ex2(s[2 * i] - mm), ex2(s[2 * i + 1] - mm));
          }
          fence_regs(o);
          WG_FENCE();
#pragma unroll
          for (int k = 0; k < 8; k++)
            wgmma_rs_n24(o, p[4 * k], p[4 * k + 1], p[4 * k + 2], p[4 * k + 3], desc64(vlo0 + b * 384 + k * 48, 8), 1);
          WG_COMMIT();
          WG_WAIT(0);
          fence_regs(o);
        }
        store_o(o, tile);
      }
    }
  }
}

constexpr int K3_ST = 4, K3_STAGE = 37888;
constexpr int K3_SMEM = K3_ST * K3_STAGE + 45056 + 20480 + 256;

template <int N> struct Acc { float v[N]; };

template <int NB, int NK, bool FIRST>
__global__ void __cluster_dims__(2, 1, 1) __launch_bounds__(384, 1)
k3_proj(const __grid_constant__ CUtensorMap tmr, const uint4* __restrict__ aimg, const uint4* __restrict__ wimg) {
  constexpr int KT = 2 * NB + NK, EX = FIRST ? 1 : 0;
  extern __shared__ __align__(1024) uint8_t sm[];
  const uint32_t sbase = smem_u32(sm);
  uint8_t* xch = sm + K3_ST * K3_STAGE;
  uint8_t* stg = sm + K3_ST * K3_STAGE + 45056;
  const uint32_t fullb = smem_u32(stg) + 20480, emptyb = fullb + 8 * K3_ST, resb = emptyb + 8 * K3_ST, xchb = resb + 8;
  const int tid = threadIdx.x, lane = tid & 31;
  const int warp = __shfl_sync(~0u, tid >> 5, 0);
  const int rank = blockIdx.x & 1;
  const int n = blockIdx.x & 7, m = blockIdx.x >> 3;
  if (tid == 0) STAMP(FIRST ? 2 : 4, 0);
  if (warp == 0) {
    if (lane == 0) {
      prefetch_map(&tmr);
      for (int i = 0; i < K3_ST; i++) { mbar_init(fullb + 8 * i, 1); mbar_init(emptyb + 8 * i, 2); }
      mbar_init(resb, 1); mbar_init(xchb, 1);
      mbar_expect(xchb, 4096 * (10 + EX));
      asm volatile("fence.mbarrier_init.release.cluster;" ::: "memory");
    }
    __syncwarp();
    cluster_arrive();
    bar_arrive(4, 256 + 32);
    if (lane == 0) {
      const uint8_t* wk = (const uint8_t*)wimg + (size_t)n * KT * 10240;
      const uint8_t* ws = (const uint8_t*)wimg + (size_t)(n ^ 1) * KT * 10240;
      const uint8_t* ab = (const uint8_t*)aimg + (size_t)m * KT * 16384;
#pragma unroll 1
      for (int i = 0; i < NB + NK; i++) {
        const int s = i % K3_ST, kt = i < NB ? i + rank * (NB + NK) : i;
        const uint32_t sa = sbase + s * K3_STAGE;
        if (i >= K3_ST) mbar_wait(emptyb + 8 * s, ((i / K3_ST) - 1) & 1);
        mbar_expect(fullb + 8 * s, 26624 + EX * 1024 + (i < NB ? 10240 : 0));
        if (i > 0) bulk_ld(sa, ab + kt * 16384, 16384, fullb + 8 * s);
        bulk_ld(sa + 16384, wk + kt * 10240, 10240, fullb + 8 * s);
        if (FIRST) bulk_ld(sa + 26624, (const uint8_t*)g_wm + kt * 1024, 1024, fullb + 8 * s);
        if (i < NB) bulk_ld(sa + 26624 + EX * 1024, ws + kt * 10240, 10240, fullb + 8 * s);
        if (i == 0) {
          pdl_wait();
          pdl_trigger();
          bulk_ld(sa, ab + kt * 16384, 16384, fullb);
        }
        if (FIRST && i == K3_ST - 1) {
          mbar_expect(resb, 20480);
          tma2d(smem_u32(stg), &tmr, n * 80, m * 128, resb);
          tma2d(smem_u32(stg) + 10240, &tmr, n * 80, m * 128 + 64, resb);
        }
      }
    }
    __syncwarp();
    cluster_wait();
  } else if (warp >= 4) {
    cluster_arrive();
    const int cw = warp - 4, wg = cw >> 2;
    const int g = lane >> 2, c = lane & 3;
    const int row = m * 128 + cw * 16 + g;
    uint8_t* himg = (uint8_t*)g_h + (size_t)m * 163840 + cw * 2048 + lane * 4;
    uint32_t rv[20];
    float mu0, mu1;
    if (FIRST) {
      mu0 = __uint_as_float(__ldcg(&g_rowstat[row].z)); mu1 = __uint_as_float(__ldcg(&g_rowstat[row + 8].z));
    } else {
      mu0 = __ldcg(&g_hmean[row]); mu1 = __ldcg(&g_hmean[row + 8]);
#pragma unroll
      for (int j = 0; j < 10; j++) {
        rv[2 * j] = __ldcg((const uint32_t*)(himg + img_off(n * 10 + j)));
        rv[2 * j + 1] = __ldcg((const uint32_t*)(himg + img_off(n * 10 + j) + 1024));
      }
    }
    float acc[80 + 4 * EX];
    float (&keep)[40 + 4 * EX] = ((Acc<40 + 4 * EX>*)acc)->v;
    const uint64_t da0 = mkdesc(sbase + wg * 8192, 128, 1024, 0);
    const uint64_t db0 = mkdesc(sbase + 16384, 128, 1024, 0);
    bar_sync(4, 256 + 32);
#pragma unroll 1
    for (int i = 0; i < NB; i++) {
      const int s = i % K3_ST;
      mbar_wait(fullb + 8 * s, (i / K3_ST) & 1);
      if (i == 0 && tid == 128) STAMP(FIRST ? 2 : 4, 2);
      const uint64_t da = da0 + s * (K3_STAGE >> 4), db = db0 + s * (K3_STAGE >> 4);
      WG_FENCE();
#pragma unroll
      for (int k = 0; k < 4; k++) {
        if constexpr (FIRST) wgmma_ss_n168(acc, da + k * 16, db + k * 16, (i | k) != 0);
        else wgmma_ss_n160(acc, da + k * 16, db + k * 16, (i | k) != 0);
      }
      WG_COMMIT();
      if (i > 0) {
        WG_WAIT(1);
        if ((tid & 127) == 0) mbar_arrive(emptyb + 8 * ((i - 1) % K3_ST));
      }
    }
    cluster_wait();
    const uint32_t rx = mapa(smem_u32(xch) + (tid - 128) * 16, rank ^ 1), rb = mapa(xchb, rank ^ 1);
    WG_WAIT(0);
    fence_regs(acc);
    if ((tid & 127) == 0) mbar_arrive(emptyb + 8 * ((NB - 1) % K3_ST));
    if (FIRST) st_async4(rx, acc[40], acc[41], acc[42], acc[43], rb);
    if (tid == 128) STAMP(FIRST ? 2 : 4, 1);
#pragma unroll
    for (int i = NB; i < NB + NK; i++) {
      const int s = i % K3_ST;
      mbar_wait(fullb + 8 * s, (i / K3_ST) & 1);
      const uint64_t da = da0 + s * (K3_STAGE >> 4), db = db0 + s * (K3_STAGE >> 4);
      WG_FENCE();
#pragma unroll
      for (int k = 0; k < 4; k++) {
        if constexpr (FIRST) wgmma_ss_n88(keep, da + k * 16, db + k * 16, 1);
        else wgmma_ss_n80(keep, da + k * 16, db + k * 16, 1);
      }
      WG_COMMIT();
      if (i > NB && i - 1 + K3_ST < NB + NK) {
        WG_WAIT(1);
        if ((tid & 127) == 0) mbar_arrive(emptyb + 8 * ((i - 1) % K3_ST));
      }
#pragma unroll
      for (int j = (i - NB) * 3 + EX; j < (i - NB) * 3 + 3 + EX; j++)
        if (j < 10 + EX) st_async4(rx + j * 4096, acc[40 + 4 * j], acc[41 + 4 * j], acc[42 + 4 * j], acc[43 + 4 * j], rb);
    }
    uint8_t* sp = stg + (cw * 16 + g) * 160 + c * 4;
    if (FIRST) {
      mbar_wait(resb, 0);
#pragma unroll
      for (int j = 0; j < 10; j++) {
        rv[2 * j] = *(const uint32_t*)(sp + j * 16);
        rv[2 * j + 1] = *(const uint32_t*)(sp + 1280 + j * 16);
      }
    }
    WG_WAIT(0);
    fence_regs(keep);
    if (tid == 128) STAMP(FIRST ? 2 : 4, 3);
    mbar_wait(xchb, 0);
    if (tid == 128) STAMP(FIRST ? 2 : 4, 5);
    const uint8_t* xp = xch + (tid - 128) * 16;
    if (FIRST) {
      const float4 p = *(const float4*)xp;
      mu0 += __shfl_sync(~0u, (keep[40] + p.x) + (keep[41] + p.y), 0, 4);
      mu1 += __shfl_sync(~0u, (keep[42] + p.z) + (keep[43] + p.w), 0, 4);
      if (n == 0 && c == 0) { g_hmean[row] = mu0; g_hmean[row + 8] = mu1; }
      mu0 = -mu0; mu1 = -mu1;
    }
    float q0 = 0.f, q1 = 0.f;
#pragma unroll
    for (int j = 0; j < 10; j++) {
      const float4 p = *(const float4*)(xp + (j + EX) * 4096);
      const float x0 = (keep[4 * j] + p.x) + (bf_lo(rv[2 * j]) + mu0), x1 = (keep[4 * j + 1] + p.y) + (bf_hi(rv[2 * j]) + mu0);
      const float y0 = (keep[4 * j + 2] + p.z) + (bf_lo(rv[2 * j + 1]) + mu1), y1 = (keep[4 * j + 3] + p.w) + (bf_hi(rv[2 * j + 1]) + mu1);
      if (FIRST) {
        *(uint32_t*)(himg + img_off(n * 10 + j)) = pack_bf16(x0, x1);
        *(uint32_t*)(himg + img_off(n * 10 + j) + 1024) = pack_bf16(y0, y1);
        q0 = fmaf(x0, x0, fmaf(x1, x1, q0)); q1 = fmaf(y0, y0, fmaf(y1, y1, q1));
      } else {
        *(uint32_t*)(sp + j * 16) = pack_bf16(x0, x1);
        *(uint32_t*)(sp + 1280 + j * 16) = pack_bf16(y0, y1);
      }
    }
    if (FIRST) {
      q0 += __shfl_xor_sync(~0u, q0, 1); q0 += __shfl_xor_sync(~0u, q0, 2);
      q1 += __shfl_xor_sync(~0u, q1, 1); q1 += __shfl_xor_sync(~0u, q1, 2);
      if (c < 2) g_hpart[n * S_ + row + c * 8] = c ? q1 : q0;
    } else {
      fence_async();
      bar_sync(1 + wg, 128);
      if ((tid & 127) == 0) {
        tma2d_st(&tmr, n * 80, m * 128 + wg * 64, smem_u32(stg) + wg * 10240);
        bulk_commit_wait();
      }
      __syncwarp();
    }
    if (tid == 128) STAMP(FIRST ? 2 : 4, 4);
  } else {
    cluster_arrive();
    cluster_wait();
  }
}

constexpr int K4_ST = 3, K4_STAGE = 71680;
constexpr int K4_SMEM = K4_ST * K4_STAGE + 64;

__global__ void __cluster_dims__(2, 1, 1) __launch_bounds__(256, 1)
k4_ffn1() {
  extern __shared__ __align__(1024) uint8_t sm[];
  const uint32_t sbase = smem_u32(sm);
  const uint32_t fullb = sbase + K4_ST * K4_STAGE, emptyb = fullb + 8 * K4_ST;
  const int tid = threadIdx.x, lane = tid & 31;
  const int warp = __shfl_sync(~0u, tid >> 5, 0);
  const int rank = blockIdx.x & 1, cl = blockIdx.x >> 1;
  const int n = cl & 7, m = (cl >> 3) * 2 + rank;
  const uint8_t* wb = (const uint8_t*)g_wgu + (size_t)n * 10 * 55296 + rank * 27648;
  const uint8_t* ab = (const uint8_t*)g_h + (size_t)m * 163840;
  if (tid == 0) STAMP(3, 0);
  if (tid == 0) {
    for (int i = 0; i < K4_ST; i++) { mbar_init(fullb + 8 * i, 1); mbar_init(emptyb + 8 * i, 4); }
    asm volatile("fence.mbarrier_init.release.cluster;" ::: "memory");
    for (int kt = 0; kt < K4_ST; kt++) mbar_expect(fullb + 8 * kt, K4_STAGE);
  }
  __syncthreads();
  cluster_arrive();
  cluster_wait();
  if (tid == 0) bulk_ld_mc(sbase + 16384 + rank * 27648, wb, 27648, fullb);
  pdl_wait();
  pdl_trigger();
  if (tid == 128) STAMP(3, 1);
  if (tid == 0) {
    bulk_ld(sbase, ab, 16384, fullb);
    for (int kt = 1; kt < K4_ST; kt++) {
      bulk_ld(sbase + kt * K4_STAGE, ab + kt * 16384, 16384, fullb + 8 * kt);
      bulk_ld_mc(sbase + kt * K4_STAGE + 16384 + rank * 27648, wb + kt * 55296, 27648, fullb + 8 * kt);
    }
  }
  __syncwarp();
  float r0, r1;
  {
    const float* hp = &g_hpart[(lane & 3) * 2 * S_ + m * 128 + warp * 16 + (lane >> 2)];
    r0 = __ldcg(hp) + __ldcg(hp + S_);
    r1 = __ldcg(hp + 8) + __ldcg(hp + S_ + 8);
  }
  float ag[108], au[108];
  const uint64_t da0 = mkdesc(sbase + (warp >> 2) * 8192, 128, 1024, 0);
  const uint64_t db0 = mkdesc(sbase + 16384, 128, 1024, 0);
#pragma unroll 1
  for (int kt = 0; kt < 10; kt++) {
    const int s = kt % K4_ST;
    mbar_wait(fullb + 8 * s, (kt / K4_ST) & 1);
    if (kt == 0 && tid == 128) STAMP(3, 2);
    const uint64_t da = da0 + s * (K4_STAGE >> 4), db = db0 + s * (K4_STAGE >> 4);
    WG_FENCE();
#pragma unroll
    for (int k = 0; k < 4; k++) {
      wgmma_ss_n216(ag, da + k * 16, db + k * 16, (kt | k) != 0);
      wgmma_ss_n216(au, da + k * 16, db + 1728 + k * 16, (kt | k) != 0);
    }
    WG_COMMIT();
    if (kt > 0 && kt - 1 + K4_ST < 10) {
      WG_WAIT(1);
      const int sp = (kt - 1) % K4_ST;
      if ((tid & 127) < 2) mbar_arrive_cta(emptyb + 8 * sp, tid & 1);
      if (tid == 0) {
        const uint32_t sa = sbase + sp * K4_STAGE;
        mbar_wait(emptyb + 8 * sp, ((kt - 1) / K4_ST) & 1);
        mbar_expect(fullb + 8 * sp, K4_STAGE);
        bulk_ld_mc(sa + 16384 + rank * 27648, wb + (kt - 1 + K4_ST) * 55296, 27648, fullb + 8 * sp);
        bulk_ld(sa, ab + (kt - 1 + K4_ST) * 16384, 16384, fullb + 8 * sp);
      }
      __syncwarp();
    }
  }
  r0 += __shfl_xor_sync(~0u, r0, 1); r1 += __shfl_xor_sync(~0u, r1, 1);
  r0 += __shfl_xor_sync(~0u, r0, 2); r1 += __shfl_xor_sync(~0u, r1, 2);
  r0 = __frcp_rn(r0 * (1.f / D_) + 1e-5f); r1 = __frcp_rn(r1 * (1.f / D_) + 1e-5f);
  cluster_arrive();
  WG_WAIT(0);
  fence_regs(ag); fence_regs(au);
  if (tid == 128) STAMP(3, 3);
  uint8_t* dst = (uint8_t*)g_hh + (size_t)m * 27 * 16384 + warp * 2048 + lane * 4;
#pragma unroll
  for (int j = 0; j < 27; j++) {
    *(uint32_t*)(dst + img_off(n * 27 + j)) = pack_bf16(ag[4 * j] * r0 * au[4 * j], ag[4 * j + 1] * r0 * au[4 * j + 1]);
    *(uint32_t*)(dst + img_off(n * 27 + j) + 1024) = pack_bf16(ag[4 * j + 2] * r1 * au[4 * j + 2], ag[4 * j + 3] * r1 * au[4 * j + 3]);
  }
  if (tid == 128) STAMP(3, 4);
  cluster_wait();
}

typedef CUresult (*EncodeFn)(CUtensorMap*, CUtensorMapDataType, cuuint32_t, void*, const cuuint64_t*, const cuuint64_t*,
                             const cuuint32_t*, const cuuint32_t*, CUtensorMapInterleave, CUtensorMapSwizzle,
                             CUtensorMapL2promotion, CUtensorMapFloatOOBfill);

static CUtensorMap make_map(EncodeFn enc, const void* p, uint64_t inner, uint64_t outer, uint32_t box_inner,
                            uint32_t box_outer, CUtensorMapSwizzle swz) {
  CUtensorMap m;
  cuuint64_t gd[2] = {inner, outer};
  cuuint64_t gs[1] = {inner * 2};
  cuuint32_t bd[2] = {box_inner, box_outer};
  cuuint32_t es[2] = {1, 1};
  enc(&m, CU_TENSOR_MAP_DATA_TYPE_BFLOAT16, 2, (void*)p, gd, gs, bd, es, CU_TENSOR_MAP_INTERLEAVE_NONE, swz,
      CU_TENSOR_MAP_L2_PROMOTION_L2_256B, CU_TENSOR_MAP_FLOAT_OOB_FILL_NONE);
  return m;
}

static CUtensorMap make_map_img(EncodeFn enc, const void* p, uint64_t k, uint64_t n, uint32_t chunks) {
  CUtensorMap m;
  cuuint64_t gd[3] = {8, k, n / 8};
  cuuint64_t gs[2] = {n * 2, 16};
  cuuint32_t bd[3] = {8, 64, chunks};
  cuuint32_t es[3] = {1, 1, 1};
  enc(&m, CU_TENSOR_MAP_DATA_TYPE_BFLOAT16, 3, (void*)p, gd, gs, bd, es, CU_TENSOR_MAP_INTERLEAVE_NONE,
      CU_TENSOR_MAP_SWIZZLE_NONE, CU_TENSOR_MAP_L2_PROMOTION_L2_128B, CU_TENSOR_MAP_FLOAT_OOB_FILL_NONE);
  return m;
}

template <typename... KArgs, typename... Args>
static void launch(void (*k)(KArgs...), int grid, int threads, int smem, bool pdl, Args... args) {
  cudaLaunchConfig_t cfg = {};
  cfg.gridDim = dim3(grid);
  cfg.blockDim = dim3(threads);
  cfg.dynamicSmemBytes = smem;
  cfg.stream = cudaStreamPerThread;
  cudaLaunchAttribute at[1];
  at[0].id = cudaLaunchAttributeProgrammaticStreamSerialization;
  at[0].val.programmaticStreamSerializationAllowed = 1;
  cfg.attrs = at;
  cfg.numAttrs = pdl ? 1 : 0;
  cudaLaunchKernelEx(&cfg, k, KArgs(args)...);
}

extern "C" void kernel_launch(void* const* d_in, const int* in_sizes, int n_in, void* d_out, int out_size) {
  const bf16* x = (const bf16*)d_in[0];
  const bf16* wqkv = (const bf16*)d_in[1];
  const bf16* wo = (const bf16*)d_in[2];
  const bf16* wg = (const bf16*)d_in[4];
  const bf16* wu = (const bf16*)d_in[5];
  const bf16* wd = (const bf16*)d_in[6];

  static EncodeFn enc = nullptr;
  static void *p_o, *p_hh, *p_wo, *p_wd;
  if (!enc) {
    void* fn = nullptr;
    cudaDriverEntryPointQueryResult qr;
    cudaGetDriverEntryPoint("cuTensorMapEncodeTiled", &fn, cudaEnableDefault, &qr);
    enc = (EncodeFn)fn;
    cudaGetSymbolAddress(&p_o, g_o); cudaGetSymbolAddress(&p_hh, g_hh);
    cudaGetSymbolAddress(&p_wo, g_wo); cudaGetSymbolAddress(&p_wd, g_wd);
    cudaFuncSetAttribute(k1_qkv, cudaFuncAttributeMaxDynamicSharedMemorySize, K1_SMEM);
    cudaFuncSetAttribute(k2_attn, cudaFuncAttributeMaxDynamicSharedMemorySize, K2_SMEM);
    cudaFuncSetAttribute(k3_proj<3, 4, true>, cudaFuncAttributeMaxDynamicSharedMemorySize, K3_SMEM);
    cudaFuncSetAttribute(k3_proj<11, 5, false>, cudaFuncAttributeMaxDynamicSharedMemorySize, K3_SMEM);
    cudaFuncSetAttribute(k4_ffn1, cudaFuncAttributeMaxDynamicSharedMemorySize, K4_SMEM);
  }
  const CUtensorMap tmx = make_map(enc, x, D_, S_, 64, 96, CU_TENSOR_MAP_SWIZZLE_128B);
  const CUtensorMap tmw = make_map(enc, wqkv, 3 * D_, D_, 32, 64, CU_TENSOR_MAP_SWIZZLE_64B);
  const CUtensorMap tmxr = make_map(enc, x, D_, S_, 80, 64, CU_TENSOR_MAP_SWIZZLE_NONE);
  const CUtensorMap tmg = make_map_img(enc, wg, D_, F_, 9), tmu = make_map_img(enc, wu, D_, F_, 9);
  const CUtensorMap tmd = make_map_img(enc, wd, F_, D_, 10);
  const CUtensorMap tmout = make_map(enc, d_out, D_, S_, 80, 64, CU_TENSOR_MAP_SWIZZLE_NONE);

  launch(k1_qkv, 132, 512, K1_SMEM, false, tmx, tmw, x, wqkv, wo);
  launch(k2_attn, 128, 512, K2_SMEM, true, tmg, tmu, tmd, 0x007f007fu);
  launch(k3_proj<3, 4, true>, 128, 384, K3_SMEM, true, tmxr, (const uint4*)p_o, (const uint4*)p_wo);
  launch(k4_ffn1, 128, 256, K4_SMEM, true);
  launch(k3_proj<11, 5, false>, 128, 384, K3_SMEM, true, tmout, (const uint4*)p_hh, (const uint4*)p_wd);
}
```

```cpp
#include <cuda_runtime.h>
#include <cuda_bf16.h>
#include <cuda.h>
#include <stdint.h>

typedef __nv_bfloat16 bf16;

constexpr int S_ = 2048, D_ = 640, F_ = 1728;
constexpr int HEAD_IMG = 98304;
#define PMASK 0xABAB
constexpr uint32_t POLY_MASK = PMASK;
constexpr float QSCALE = 0.22360679774997896f * 1.4426950408889634f;

__device__ __align__(1024) uint4 g_qkv[96 * HEAD_IMG / 16];
__device__ __align__(1024) uint4 g_o[S_ * D_ / 8];
__device__ __align__(1024) uint4 g_h[S_ * D_ / 8];
__device__ __align__(1024) uint4 g_hh[S_ * F_ / 8];
__device__ __align__(1024) uint4 g_wo[D_ * D_ / 8];
__device__ __align__(1024) uint4 g_wgu[2 * D_ * F_ / 8];
__device__ __align__(1024) uint4 g_wd[F_ * D_ / 8];
__device__ uint4 g_rowstat[S_];
__device__ uint4 g_cpart[10 * 12 * 80];
__device__ float g_nrm[64 * 128];
__device__ uint4 g_wm[D_];
__device__ float g_hmean[S_];
__device__ float g_hpart[8 * S_];
__device__ unsigned g_epoch;

#define STAMP(k, i)
__device__ __forceinline__ uint32_t smem_u32(const void* p) { return (uint32_t)__cvta_generic_to_shared(p); }
__device__ __forceinline__ void mbar_init(uint32_t a, uint32_t c) {
  asm volatile("mbarrier.init.shared::cta.b64 [%0], %1;" ::"r"(a), "r"(c) : "memory");
}
__device__ __forceinline__ void mbar_expect(uint32_t a, uint32_t bytes) {
  asm volatile("mbarrier.arrive.expect_tx.shared::cta.b64 _, [%0], %1;" ::"r"(a), "r"(bytes) : "memory");
}
__device__ __forceinline__ void mbar_arrive(uint32_t a) {
  asm volatile("mbarrier.arrive.shared::cta.b64 _, [%0];" ::"r"(a) : "memory");
}
__device__ __forceinline__ void mbar_arrive_cta(uint32_t a, uint32_t cta) {
  asm volatile("{\n.reg .b32 r;\nmapa.shared::cluster.u32 r, %0, %1;\n"
               "mbarrier.arrive.shared::cluster.b64 _, [r];\n}" ::"r"(a), "r"(cta) : "memory");
}
__device__ __forceinline__ bool mbar_try(uint32_t a, uint32_t ph) {
  uint32_t ok;
  asm volatile("{\n.reg .pred p;\nmbarrier.try_wait.parity.shared::cta.b64 p, [%1], %2;\nselp.u32 %0, 1, 0, p;\n}"
               : "=r"(ok) : "r"(a), "r"(ph) : "memory");
  return ok;
}
__device__ __noinline__ void wait_timeout() { __trap(); }
__device__ __forceinline__ void mbar_wait(uint32_t a, uint32_t ph) {
  if (mbar_try(a, ph)) return;
  uint32_t it = 0;
  while (!mbar_try(a, ph)) if (++it > (1u << 22)) wait_timeout();
}
__device__ __forceinline__ void tma2d(uint32_t dst, const CUtensorMap* m, int c0, int c1, uint32_t bar) {
  asm volatile("cp.async.bulk.tensor.2d.shared::cluster.global.mbarrier::complete_tx::bytes [%0], [%1, {%3, %4}], [%2];"
               ::"r"(dst), "l"(m), "r"(bar), "r"(c0), "r"(c1) : "memory");
}
__device__ __forceinline__ void tma2d_mc(uint32_t dst, const CUtensorMap* m, int c0, int c1, uint32_t bar) {
  asm volatile("cp.async.bulk.tensor.2d.shared::cluster.global.mbarrier::complete_tx::bytes.multicast::cluster "
               "[%0], [%1, {%3, %4}], [%2], %5;"
               ::"r"(dst), "l"(m), "r"(bar), "r"(c0), "r"(c1), "h"((uint16_t)3) : "memory");
}
__device__ __forceinline__ void bulk_ld(uint32_t dst, const void* src, uint32_t bytes, uint32_t bar) {
  asm volatile("cp.async.bulk.shared::cluster.global.mbarrier::complete_tx::bytes [%0], [%1], %2, [%3];"
               ::"r"(dst), "l"(src), "r"(bytes), "r"(bar) : "memory");
}
__device__ __forceinline__ void bulk_ld_mc(uint32_t dst, const void* src, uint32_t bytes, uint32_t bar) {
  asm volatile("cp.async.bulk.shared::cluster.global.mbarrier::complete_tx::bytes.multicast::cluster "
               "[%0], [%1], %2, [%3], %4;"
               ::"r"(dst), "l"(src), "r"(bytes), "r"(bar), "h"((uint16_t)3) : "memory");
}
__device__ __forceinline__ void cluster_arrive() { asm volatile("barrier.cluster.arrive.relaxed.aligned;" ::: "memory"); }
__device__ __forceinline__ void cluster_wait() { asm volatile("barrier.cluster.wait.aligned;" ::: "memory"); }
__device__ __forceinline__ void bulk_st(void* dst, uint32_t src, uint32_t bytes) {
  asm volatile("cp.async.bulk.global.shared::cta.bulk_group [%0], [%1], %2;" ::"l"(dst), "r"(src), "r"(bytes) : "memory");
}
__device__ __forceinline__ void tma2d_st(const CUtensorMap* m, int c0, int c1, uint32_t src) {
  asm volatile("cp.async.bulk.tensor.2d.global.shared::cta.bulk_group [%0, {%2, %3}], [%1];"
               ::"l"(m), "r"(src), "r"(c0), "r"(c1) : "memory");
}
__device__ __forceinline__ void bulk_commit_wait() {
  asm volatile("cp.async.bulk.commit_group;\ncp.async.bulk.wait_group.read 0;" ::: "memory");
}
__device__ __forceinline__ uint32_t mapa(uint32_t a, uint32_t cta) {
  uint32_t r;
  asm("mapa.shared::cluster.u32 %0, %1, %2;" : "=r"(r) : "r"(a), "r"(cta));
  return r;
}
__device__ __forceinline__ void st_async4(uint32_t dst, float a, float b, float c, float d, uint32_t bar) {
  asm volatile("st.async.shared::cluster.mbarrier::complete_tx::bytes.v4.f32 [%0], {%1, %2, %3, %4}, [%5];"
               ::"r"(dst), "f"(a), "f"(b), "f"(c), "f"(d), "r"(bar) : "memory");
}
__device__ __forceinline__ void fence_async() { asm volatile("fence.proxy.async.shared::cta;" ::: "memory"); }
__device__ __forceinline__ void prefetch_map(const CUtensorMap* m) {
  asm volatile("prefetch.tensormap [%0];" ::"l"(m) : "memory");
}
__device__ __forceinline__ void pdl_wait() { asm volatile("griddepcontrol.wait;" ::: "memory"); }
__device__ __forceinline__ void pdl_trigger() { asm volatile("griddepcontrol.launch_dependents;" ::: "memory"); }
__device__ __forceinline__ void bar_sync(int id, int n) { asm volatile("bar.sync %0, %1;" ::"r"(id), "r"(n) : "memory"); }
__device__ __forceinline__ void bar_arrive(int id, int n) { asm volatile("bar.arrive %0, %1;" ::"r"(id), "r"(n) : "memory"); }
#define WG_FENCE() asm volatile("wgmma.fence.sync.aligned;" ::: "memory")
#define WG_COMMIT() asm volatile("wgmma.commit_group.sync.aligned;" ::: "memory")
#define WG_WAIT(n) asm volatile("wgmma.wait_group.sync.aligned %0;" ::"n"(n) : "memory")
__device__ __forceinline__ uint64_t mkdesc(uint32_t addr, uint32_t lbo, uint32_t sbo, uint32_t sw) {
  return (uint64_t)((addr & 0x3FFFF) >> 4) | ((uint64_t)(lbo >> 4) << 16) | ((uint64_t)(sbo >> 4) << 32) |
         ((uint64_t)sw << 62);
}
template <int N> __device__ __forceinline__ void fence_regs(float (&r)[N]) {
#pragma unroll
  for (int i = 0; i < N; i++) asm volatile("" : "+f"(r[i])::"memory");
}
__device__ __forceinline__ uint32_t pack_bf16(float lo, float hi) {
  uint32_t r;
  asm("cvt.rn.bf16x2.f32 %0, %1, %2;" : "=r"(r) : "f"(hi), "f"(lo));
  return r;
}
__device__ __forceinline__ float bf_lo(uint32_t v) { return __uint_as_float(v << 16); }
__device__ __forceinline__ float bf_hi(uint32_t v) { return __uint_as_float(v & 0xffff0000u); }
__device__ __forceinline__ float ex2(float x) {
  float y;
  asm("ex2.approx.ftz.f32 %0, %1;" : "=f"(y) : "f"(x));
  return y;
}
__device__ __forceinline__ uint4 ldg_nc(const void* p) {
  uint4 v;
  asm volatile("ld.global.nc.L1::no_allocate.v4.u32 {%0, %1, %2, %3}, [%4];"
               : "=r"(v.x), "=r"(v.y), "=r"(v.z), "=r"(v.w) : "l"(p));
  return v;
}

__device__ __forceinline__ uint4 ld_relaxed(const uint4* p) {
  uint64_t a, b;
  asm volatile("ld.relaxed.gpu.global.v2.u64 {%0, %1}, [%2];" : "=l"(a), "=l"(b) : "l"(p) : "memory");
  return make_uint4((uint32_t)a, (uint32_t)(a >> 32), (uint32_t)b, (uint32_t)(b >> 32));
}
__device__ __forceinline__ void st_relaxed(uint4* p, float x, float y, uint32_t tag) {
  const uint64_t a = ((uint64_t)tag << 32) | __float_as_uint(x), b = ((uint64_t)tag << 32) | __float_as_uint(y);
  asm volatile("st.relaxed.gpu.global.v2.u64 [%0], {%1, %2};" ::"l"(p), "l"(a), "l"(b) : "memory");
}
__device__ __forceinline__ void tma3d(uint32_t dst, const CUtensorMap* m, int c1, int c2, uint32_t bar) {
  asm volatile("cp.async.bulk.tensor.3d.shared::cluster.global.mbarrier::complete_tx::bytes [%0], [%1, {%3, %4, %5}], [%2];"
               ::"r"(dst), "l"(m), "r"(bar), "r"(0), "r"(c1), "r"(c2) : "memory");
}
#define ACC8(a, v) do { a[0] += bf_lo(v.x); a[1] += bf_hi(v.x); a[2] += bf_lo(v.y); a[3] += bf_hi(v.y); \
                        a[4] += bf_lo(v.z); a[5] += bf_hi(v.z); a[6] += bf_lo(v.w); a[7] += bf_hi(v.w); } while (0)

__device__ __forceinline__ void wgmma_ss_n216(float (&d)[108], uint64_t da, uint64_t db, int sd) {
  asm volatile("{\n.reg .pred p;\nsetp.ne.b32 p, %110, 0;\n"
      "wgmma.mma_async.sync.aligned.m64n216k16.f32.bf16.bf16 {"
      "%0, %1, %2, %3, %4, %5, %6, %7, %8, %9, %10, %11, %12, %13, %14, %15, "
      "%16, %17, %18, %19, %20, %21, %22, %23, %24, %25, %26, %27, %28, %29, %30, %31, "
      "%32, %33, %34, %35, %36, %37, %38, %39, %40, %41, %42, %43, %44, %45, %46, %47, "
      "%48, %49, %50, %51, %52, %53, %54, %55, %56, %57, %58, %59, %60, %61, %62, %63, "
      "%64, %65, %66, %67, %68, %69, %70, %71, %72, %73, %74, %75, %76, %77, %78, %79, "
      "%80, %81, %82, %83, %84, %85, %86, %87, %88, %89, %90, %91, %92, %93, %94, %95, "
      "%96, %97, %98, %99, %100, %101, %102, %103, %104, %105, %106, %107"
      "}, %108, %109, p, 1, 1, 0, 1;\n}\n"
    : "+f"(d[0]), "+f"(d[1]), "+f"(d[2]), "+f"(d[3]), "+f"(d[4]), "+f"(d[5]), "+f"(d[6]), "+f"(d[7]),
      "+f"(d[8]), "+f"(d[9]), "+f"(d[10]), "+f"(d[11]), "+f"(d[12]), "+f"(d[13]), "+f"(d[14]), "+f"(d[15]),
      "+f"(d[16]), "+f"(d[17]), "+f"(d[18]), "+f"(d[19]), "+f"(d[20]), "+f"(d[21]), "+f"(d[22]), "+f"(d[23]),
      "+f"(d[24]), "+f"(d[25]), "+f"(d[26]), "+f"(d[27]), "+f"(d[28]), "+f"(d[29]), "+f"(d[30]), "+f"(d[31]),
      "+f"(d[32]), "+f"(d[33]), "+f"(d[34]), "+f"(d[35]), "+f"(d[36]), "+f"(d[37]), "+f"(d[38]), "+f"(d[39]),
      "+f"(d[40]), "+f"(d[41]), "+f"(d[42]), "+f"(d[43]), "+f"(d[44]), "+f"(d[45]), "+f"(d[46]), "+f"(d[47]),
      "+f"(d[48]), "+f"(d[49]), "+f"(d[50]), "+f"(d[51]), "+f"(d[52]), "+f"(d[53]), "+f"(d[54]), "+f"(d[55]),
      "+f"(d[56]), "+f"(d[57]), "+f"(d[58]), "+f"(d[59]), "+f"(d[60]), "+f"(d[61]), "+f"(d[62]), "+f"(d[63]),
      "+f"(d[64]), "+f"(d[65]), "+f"(d[66]), "+f"(d[67]), "+f"(d[68]), "+f"(d[69]), "+f"(d[70]), "+f"(d[71]),
      "+f"(d[72]), "+f"(d[73]), "+f"(d[74]), "+f"(d[75]), "+f"(d[76]), "+f"(d[77]), "+f"(d[78]), "+f"(d[79]),
      "+f"(d[80]), "+f"(d[81]), "+f"(d[82]), "+f"(d[83]), "+f"(d[84]), "+f"(d[85]), "+f"(d[86]), "+f"(d[87]),
      "+f"(d[88]), "+f"(d[89]), "+f"(d[90]), "+f"(d[91]), "+f"(d[92]), "+f"(d[93]), "+f"(d[94]), "+f"(d[95]),
      "+f"(d[96]), "+f"(d[97]), "+f"(d[98]), "+f"(d[99]), "+f"(d[100]), "+f"(d[101]), "+f"(d[102]), "+f"(d[103]),
      "+f"(d[104]), "+f"(d[105]), "+f"(d[106]), "+f"(d[107])
    : "l"(da), "l"(db), "r"(sd));
}
__device__ __forceinline__ void wgmma_ss_n168(float (&d)[84], uint64_t da, uint64_t db, int sd) {
  asm volatile("{\n.reg .pred p;\nsetp.ne.b32 p, %86, 0;\n"
      "wgmma.mma_async.sync.aligned.m64n168k16.f32.bf16.bf16 {"
      "%0, %1, %2, %3, %4, %5, %6, %7, %8, %9, %10, %11, %12, %13, %14, %15, "
      "%16, %17, %18, %19, %20, %21, %22, %23, %24, %25, %26, %27, %28, %29, %30, %31, "
      "%32, %33, %34, %35, %36, %37, %38, %39, %40, %41, %42, %43, %44, %45, %46, %47, "
      "%48, %49, %50, %51, %52, %53, %54, %55, %56, %57, %58, %59, %60, %61, %62, %63, "
      "%64, %65, %66, %67, %68, %69, %70, %71, %72, %73, %74, %75, %76, %77, %78, %79, "
      "%80, %81, %82, %83"
      "}, %84, %85, p, 1, 1, 0, 1;\n}\n"
    : "+f"(d[0]), "+f"(d[1]), "+f"(d[2]), "+f"(d[3]), "+f"(d[4]), "+f"(d[5]), "+f"(d[6]), "+f"(d[7]),
      "+f"(d[8]), "+f"(d[9]), "+f"(d[10]), "+f"(d[11]), "+f"(d[12]), "+f"(d[13]), "+f"(d[14]), "+f"(d[15]),
      "+f"(d[16]), "+f"(d[17]), "+f"(d[18]), "+f"(d[19]), "+f"(d[20]), "+f"(d[21]), "+f"(d[22]), "+f"(d[23]),
      "+f"(d[24]), "+f"(d[25]), "+f"(d[26]), "+f"(d[27]), "+f"(d[28]), "+f"(d[29]), "+f"(d[30]), "+f"(d[31]),
      "+f"(d[32]), "+f"(d[33]), "+f"(d[34]), "+f"(d[35]), "+f"(d[36]), "+f"(d[37]), "+f"(d[38]), "+f"(d[39]),
      "+f"(d[40]), "+f"(d[41]), "+f"(d[42]), "+f"(d[43]), "+f"(d[44]), "+f"(d[45]), "+f"(d[46]), "+f"(d[47]),
      "+f"(d[48]), "+f"(d[49]), "+f"(d[50]), "+f"(d[51]), "+f"(d[52]), "+f"(d[53]), "+f"(d[54]), "+f"(d[55]),
      "+f"(d[56]), "+f"(d[57]), "+f"(d[58]), "+f"(d[59]), "+f"(d[60]), "+f"(d[61]), "+f"(d[62]), "+f"(d[63]),
      "+f"(d[64]), "+f"(d[65]), "+f"(d[66]), "+f"(d[67]), "+f"(d[68]), "+f"(d[69]), "+f"(d[70]), "+f"(d[71]),
      "+f"(d[72]), "+f"(d[73]), "+f"(d[74]), "+f"(d[75]), "+f"(d[76]), "+f"(d[77]), "+f"(d[78]), "+f"(d[79]),
      "+f"(d[80]), "+f"(d[81]), "+f"(d[82]), "+f"(d[83])
    : "l"(da), "l"(db), "r"(sd));
}
__device__ __forceinline__ void wgmma_ss_n160(float (&d)[80], uint64_t da, uint64_t db, int sd) {
  asm volatile("{\n.reg .pred p;\nsetp.ne.b32 p, %82, 0;\n"
      "wgmma.mma_async.sync.aligned.m64n160k16.f32.bf16.bf16 {"
      "%0, %1, %2, %3, %4, %5, %6, %7, %8, %9, %10, %11, %12, %13, %14, %15, "
      "%16, %17, %18, %19, %20, %21, %22, %23, %24, %25, %26, %27, %28, %29, %30, %31, "
      "%32, %33, %34, %35, %36, %37, %38, %39, %40, %41, %42, %43, %44, %45, %46, %47, "
      "%48, %49, %50, %51, %52, %53, %54, %55, %56, %57, %58, %59, %60, %61, %62, %63, "
      "%64, %65, %66, %67, %68, %69, %70, %71, %72, %73, %74, %75, %76, %77, %78, %79"
      "}, %80, %81, p, 1, 1, 0, 1;\n}\n"
    : "+f"(d[0]), "+f"(d[1]), "+f"(d[2]), "+f"(d[3]), "+f"(d[4]), "+f"(d[5]), "+f"(d[6]), "+f"(d[7]),
      "+f"(d[8]), "+f"(d[9]), "+f"(d[10]), "+f"(d[11]), "+f"(d[12]), "+f"(d[13]), "+f"(d[14]), "+f"(d[15]),
      "+f"(d[16]), "+f"(d[17]), "+f"(d[18]), "+f"(d[19]), "+f"(d[20]), "+f"(d[21]), "+f"(d[22]), "+f"(d[23]),
      "+f"(d[24]), "+f"(d[25]), "+f"(d[26]), "+f"(d[27]), "+f"(d[28]), "+f"(d[29]), "+f"(d[30]), "+f"(d[31]),
      "+f"(d[32]), "+f"(d[33]), "+f"(d[34]), "+f"(d[35]), "+f"(d[36]), "+f"(d[37]), "+f"(d[38]), "+f"(d[39]),
      "+f"(d[40]), "+f"(d[41]), "+f"(d[42]), "+f"(d[43]), "+f"(d[44]), "+f"(d[45]), "+f"(d[46]), "+f"(d[47]),
      "+f"(d[48]), "+f"(d[49]), "+f"(d[50]), "+f"(d[51]), "+f"(d[52]), "+f"(d[53]), "+f"(d[54]), "+f"(d[55]),
      "+f"(d[56]), "+f"(d[57]), "+f"(d[58]), "+f"(d[59]), "+f"(d[60]), "+f"(d[61]), "+f"(d[62]), "+f"(d[63]),
      "+f"(d[64]), "+f"(d[65]), "+f"(d[66]), "+f"(d[67]), "+f"(d[68]), "+f"(d[69]), "+f"(d[70]), "+f"(d[71]),
      "+f"(d[72]), "+f"(d[73]), "+f"(d[74]), "+f"(d[75]), "+f"(d[76]), "+f"(d[77]), "+f"(d[78]), "+f"(d[79])
    : "l"(da), "l"(db), "r"(sd));
}
__device__ __forceinline__ void wgmma_ss_n88(float (&d)[44], uint64_t da, uint64_t db, int sd) {
  asm volatile("{\n.reg .pred p;\nsetp.ne.b32 p, %46, 0;\n"
      "wgmma.mma_async.sync.aligned.m64n88k16.f32.bf16.bf16 {"
      "%0, %1, %2, %3, %4, %5, %6, %7, %8, %9, %10, %11, %12, %13, %14, %15, "
      "%16, %17, %18, %19, %20, %21, %22, %23, %24, %25, %26, %27, %28, %29, %30, %31, "
      "%32, %33, %34, %35, %36, %37, %38, %39, %40, %41, %42, %43"
      "}, %44, %45, p, 1, 1, 0, 1;\n}\n"
    : "+f"(d[0]), "+f"(d[1]), "+f"(d[2]), "+f"(d[3]), "+f"(d[4]), "+f"(d[5]), "+f"(d[6]), "+f"(d[7]),
      "+f"(d[8]), "+f"(d[9]), "+f"(d[10]), "+f"(d[11]), "+f"(d[12]), "+f"(d[13]), "+f"(d[14]), "+f"(d[15]),
      "+f"(d[16]), "+f"(d[17]), "+f"(d[18]), "+f"(d[19]), "+f"(d[20]), "+f"(d[21]), "+f"(d[22]), "+f"(d[23]),
      "+f"(d[24]), "+f"(d[25]), "+f"(d[26]), "+f"(d[27]), "+f"(d[28]), "+f"(d[29]), "+f"(d[30]), "+f"(d[31]),
      "+f"(d[32]), "+f"(d[33]), "+f"(d[34]), "+f"(d[35]), "+f"(d[36]), "+f"(d[37]), "+f"(d[38]), "+f"(d[39]),
      "+f"(d[40]), "+f"(d[41]), "+f"(d[42]), "+f"(d[43])
    : "l"(da), "l"(db), "r"(sd));
}
__device__ __forceinline__ void wgmma_ss_n80(float (&d)[40], uint64_t da, uint64_t db, int sd) {
  asm volatile("{\n.reg .pred p;\nsetp.ne.b32 p, %42, 0;\n"
      "wgmma.mma_async.sync.aligned.m64n80k16.f32.bf16.bf16 {"
      "%0, %1, %2, %3, %4, %5, %6, %7, %8, %9, %10, %11, %12, %13, %14, %15, "
      "%16, %17, %18, %19, %20, %21, %22, %23, %24, %25, %26, %27, %28, %29, %30, %31, "
      "%32, %33, %34, %35, %36, %37, %38, %39"
      "}, %40, %41, p, 1, 1, 0, 1;\n}\n"
    : "+f"(d[0]), "+f"(d[1]), "+f"(d[2]), "+f"(d[3]), "+f"(d[4]), "+f"(d[5]), "+f"(d[6]), "+f"(d[7]),
      "+f"(d[8]), "+f"(d[9]), "+f"(d[10]), "+f"(d[11]), "+f"(d[12]), "+f"(d[13]), "+f"(d[14]), "+f"(d[15]),
      "+f"(d[16]), "+f"(d[17]), "+f"(d[18]), "+f"(d[19]), "+f"(d[20]), "+f"(d[21]), "+f"(d[22]), "+f"(d[23]),
      "+f"(d[24]), "+f"(d[25]), "+f"(d[26]), "+f"(d[27]), "+f"(d[28]), "+f"(d[29]), "+f"(d[30]), "+f"(d[31]),
      "+f"(d[32]), "+f"(d[33]), "+f"(d[34]), "+f"(d[35]), "+f"(d[36]), "+f"(d[37]), "+f"(d[38]), "+f"(d[39])
    : "l"(da), "l"(db), "r"(sd));
}
__device__ __forceinline__ void wgmma_rs_n128(float (&d)[64], uint32_t a0, uint32_t a1, uint32_t a2, uint32_t a3,
                                  uint64_t db, int sd) {
  asm volatile("{\n.reg .pred p;\nsetp.ne.b32 p, %69, 0;\n"
      "wgmma.mma_async.sync.aligned.m64n128k16.f32.bf16.bf16 {"
      "%0, %1, %2, %3, %4, %5, %6, %7, %8, %9, %10, %11, %12, %13, %14, %15, "
      "%16, %17, %18, %19, %20, %21, %22, %23, %24, %25, %26, %27, %28, %29, %30, %31, "
      "%32, %33, %34, %35, %36, %37, %38, %39, %40, %41, %42, %43, %44, %45, %46, %47, "
      "%48, %49, %50, %51, %52, %53, %54, %55, %56, %57, %58, %59, %60, %61, %62, %63"
      "}, {%64, %65, %66, %67}, %68, p, 1, 1, 0;\n}\n"
    : "+f"(d[0]), "+f"(d[1]), "+f"(d[2]), "+f"(d[3]), "+f"(d[4]), "+f"(d[5]), "+f"(d[6]), "+f"(d[7]),
      "+f"(d[8]), "+f"(d[9]), "+f"(d[10]), "+f"(d[11]), "+f"(d[12]), "+f"(d[13]), "+f"(d[14]), "+f"(d[15]),
      "+f"(d[16]), "+f"(d[17]), "+f"(d[18]), "+f"(d[19]), "+f"(d[20]), "+f"(d[21]), "+f"(d[22]), "+f"(d[23]),
      "+f"(d[24]), "+f"(d[25]), "+f"(d[26]), "+f"(d[27]), "+f"(d[28]), "+f"(d[29]), "+f"(d[30]), "+f"(d[31]),
      "+f"(d[32]), "+f"(d[33]), "+f"(d[34]), "+f"(d[35]), "+f"(d[36]), "+f"(d[37]), "+f"(d[38]), "+f"(d[39]),
      "+f"(d[40]), "+f"(d[41]), "+f"(d[42]), "+f"(d[43]), "+f"(d[44]), "+f"(d[45]), "+f"(d[46]), "+f"(d[47]),
      "+f"(d[48]), "+f"(d[49]), "+f"(d[50]), "+f"(d[51]), "+f"(d[52]), "+f"(d[53]), "+f"(d[54]), "+f"(d[55]),
      "+f"(d[56]), "+f"(d[57]), "+f"(d[58]), "+f"(d[59]), "+f"(d[60]), "+f"(d[61]), "+f"(d[62]), "+f"(d[63])
    : "r"(a0), "r"(a1), "r"(a2), "r"(a3), "l"(db), "r"(sd));
}
__device__ __forceinline__ void wgmma_rs_n24(float (&d)[12], uint32_t a0, uint32_t a1, uint32_t a2, uint32_t a3,
                                  uint64_t db, int sd) {
  asm volatile("{\n.reg .pred p;\nsetp.ne.b32 p, %17, 0;\n"
      "wgmma.mma_async.sync.aligned.m64n24k16.f32.bf16.bf16 {"
      "%0, %1, %2, %3, %4, %5, %6, %7, %8, %9, %10, %11"
      "}, {%12, %13, %14, %15}, %16, p, 1, 1, 1;\n}\n"
    : "+f"(d[0]), "+f"(d[1]), "+f"(d[2]), "+f"(d[3]), "+f"(d[4]), "+f"(d[5]), "+f"(d[6]), "+f"(d[7]),
      "+f"(d[8]), "+f"(d[9]), "+f"(d[10]), "+f"(d[11])
    : "r"(a0), "r"(a1), "r"(a2), "r"(a3), "l"(db), "r"(sd));
}

#define K1S 4
constexpr int K1_ST = K1S, K1_STAGE = 45056;
constexpr int K1_SMEM = K1_ST * K1_STAGE + 640   + 1536   + 2560   + 128;

__device__ __forceinline__ float2 row_stats(uint4 v0, uint4 v1, uint4 v2) {
  const uint32_t wd[12] = {v0.x, v0.y, v0.z, v0.w, v1.x, v1.y, v1.z, v1.w, v2.x, v2.y, v2.z, v2.w};
  float sx = 0.f, sq = 0.f;
#pragma unroll
  for (int e = 0; e < 12; e++) {
    const float lo = bf_lo(wd[e]), hi = bf_hi(wd[e]);
    sx += lo + hi; sq = fmaf(lo, lo, fmaf(hi, hi, sq));
  }
#pragma unroll
  for (int o = 16; o; o >>= 1) { sx += __shfl_xor_sync(~0u, sx, o); sq += __shfl_xor_sync(~0u, sq, o); }
  const float mean = sx * (1.f / D_);
  return make_float2(rsqrtf(fmaxf(sq * (1.f / D_) - mean * mean, 0.f) + 1e-5f), mean);
}

__global__ void __cluster_dims__(2, 1, 1) __launch_bounds__(512, 1)
k1_qkv(const __grid_constant__ CUtensorMap tmx, const __grid_constant__ CUtensorMap tmw,
       const bf16* __restrict__ x, const bf16* __restrict__ w, const bf16* __restrict__ wo) {
  extern __shared__ __align__(1024) uint8_t sm[];
  float* cs = (float*)(sm + K1_ST * K1_STAGE);
  float2* rowab = (float2*)(sm + K1_ST * K1_STAGE + 640);
  float* red = (float*)(sm + K1_ST * K1_STAGE + 2176);
  const uint32_t sbase = smem_u32(sm);
  const uint32_t fullb = sbase + K1_ST * K1_STAGE + 4736, emptyb = fullb + 8 * K1_ST;
  const int tid = threadIdx.x, lane = tid & 31;
  const int warp = __shfl_sync(~0u, tid >> 5, 0);
  const int rank = blockIdx.x & 1, cl = blockIdx.x >> 1;
  const int m = cl / 6, n = (cl - m * 6) * 2 + rank;
  if (tid == 0) STAMP(0, 0);

  if (warp == 12) {
    if (lane == 0) {
      prefetch_map(&tmx); prefetch_map(&tmw);
      for (int i = 0; i < K1_ST; i++) { mbar_init(fullb + 8 * i, 1); mbar_init(emptyb + 8 * i, 6); }
      asm volatile("fence.mbarrier_init.release.cluster;" ::: "memory");
    }
    __syncwarp();
    cluster_arrive();
    bar_arrive(4, 512);
    if (lane == 0) {
      for (int kt = 0; kt < K1_ST; kt++) mbar_expect(fullb + 8 * kt, K1_STAGE);
#pragma unroll
      for (int j = 0; j < 5; j++) tma2d(sbase + 24576 + j * 4096, &tmw, n * 160 + j * 32, 0, fullb);
    }
    __syncwarp();
    cluster_wait();
    if (lane == 0) {
#pragma unroll 1
      for (int kt = 0; kt < 10; kt++) {
        const int s = kt % K1_ST;
        const uint32_t sa = sbase + s * K1_STAGE;
        if (kt >= K1_ST) {
          mbar_wait(emptyb + 8 * s, ((kt / K1_ST) - 1) & 1);
          mbar_expect(fullb + 8 * s, K1_STAGE);
        }
        tma2d_mc(sa + rank * 12288, &tmx, kt * 64, m * 192 + rank * 96, fullb + 8 * s);
        if (kt > 0) {
#pragma unroll
          for (int j = 0; j < 5; j++) tma2d(sa + 24576 + j * 4096, &tmw, n * 160 + j * 32, kt * 64, fullb + 8 * s);
        }
        if (kt == K1_ST - 1) {
          if (m * 192 + n * 16 < S_)
            asm volatile("cp.async.bulk.prefetch.L2.global [%0], %1;" ::"l"(x + (size_t)(m * 192 + n * 16) * D_), "r"(16 * D_ * 2) : "memory");
          if (m >= K1_ST && m < 10) {
#pragma unroll
            for (int j = 0; j < 5; j++)
              asm volatile("cp.async.bulk.prefetch.tensor.2d.L2.global [%0, {%1, %2}];" ::"l"(&tmw), "r"(n * 160 + j * 32), "r"(m * 64) : "memory");
          }
          pdl_trigger();
        }
      }
    }
    __syncwarp();
    cluster_arrive();
  } else if (warp > 12) {
    cluster_arrive();
    const int t96 = tid - 416;
    const uint32_t tag = __ldcg(&g_epoch) + 1;
    bar_sync(4, 512);
    mbar_wait(fullb, 0);
    if (m < 10) {
      const int ck = t96 % 20, rg = min(t96 / 20, 3);
      uint4 wv[16];
#pragma unroll
      for (int i = 0; i < 16; i++) wv[i] = ldg_nc(w + (size_t)(m * 64 + rg * 16 + i) * 1920 + n * 160 + ck * 8);
      float acc8[8];
#pragma unroll
      for (int i = 0; i < 8; i++) acc8[i] = 0.f;
#pragma unroll
      for (int i = 0; i < 16; i++) ACC8(acc8, wv[i]);
      *(float4*)&red[rg * 160 + ck * 8] = make_float4(acc8[0], acc8[1], acc8[2], acc8[3]);
      *(float4*)&red[rg * 160 + ck * 8 + 4] = make_float4(acc8[4], acc8[5], acc8[6], acc8[7]);
      bar_sync(1, 96);
      if (t96 < 80) {
        const float2 p0 = *(const float2*)&red[t96 * 2], p1 = *(const float2*)&red[160 + t96 * 2];
        const float2 p2 = *(const float2*)&red[320 + t96 * 2], p3 = *(const float2*)&red[480 + t96 * 2];
        st_relaxed(&g_cpart[(m * 12 + n) * 80 + t96], (p0.x + p1.x) + (p2.x + p3.x), (p0.y + p1.y) + (p2.y + p3.y), tag);
      }
    }
    if (tid == 416) STAMP(5, 7);
    bool ok = false;
    for (int it = 0; it < 64 && !ok; it++) {
      uint4 p[10], st[2];
#pragma unroll
      for (int k = 0; k < 10; k++) p[k] = ld_relaxed(&g_cpart[(k * 12 + n) * 80 + min(t96, 79)]);
#pragma unroll
      for (int k = 0; k < 2; k++) st[k] = ld_relaxed(&g_rowstat[min(m * 192 + k * 96 + t96, S_ - 1)]);
      ok = true;
      float s0 = 0.f, s1 = 0.f;
#pragma unroll
      for (int k = 0; k < 10; k++) {
        ok = ok && p[k].y == tag && p[k].w == tag;
        s0 += __uint_as_float(p[k].x); s1 += __uint_as_float(p[k].z);
      }
      if (t96 < 80) *(float2*)&cs[t96 * 2] = make_float2(s0, s1);
#pragma unroll
      for (int k = 0; k < 2; k++) {
        ok = ok && st[k].y == tag && st[k].w == tag;
        rowab[k * 96 + t96] = make_float2(__uint_as_float(st[k].x), -__uint_as_float(st[k].x) * __uint_as_float(st[k].z));
      }
      ok = __all_sync(~0u, ok);
      if (!ok) __nanosleep(300);
    }
    if (!ok) {
      const int c2 = min(t96, 79);
      float s0 = 0.f, s1 = 0.f;
#pragma unroll 1
      for (int k = 0; k < D_; k++) {
        const uint32_t v = *(const uint32_t*)(w + (size_t)k * 1920 + n * 160 + c2 * 2);
        s0 += bf_lo(v); s1 += bf_hi(v);
      }
      if (t96 < 80) *(float2*)&cs[t96 * 2] = make_float2(s0, s1);
#pragma unroll 1
      for (int i = 0; i < 64; i++) {
        const int r = (i >> 5) * 96 + (t96 & ~31) + (i & 31);
        const bf16* xr = x + (size_t)min(m * 192 + r, S_ - 1) * D_ + lane * 8;
        const float2 st = row_stats(ldg_nc(xr), ldg_nc(xr + 256), lane < 16 ? ldg_nc(xr + 512) : make_uint4(0u, 0u, 0u, 0u));
        if (lane == 0) rowab[r] = make_float2(st.x, -st.x * st.y);
      }
    }
    __syncwarp();
    bar_arrive(2, 96 + 384);
    bar_sync(1, 96);
    if (tid == 416) STAMP(0, 5);
    if (blockIdx.x < 128) {
      uint4 v[5];
      const int ck = min(t96, 79), nt = ck / 10;
#pragma unroll
      for (int i = 0; i < 5; i++) {
        const int k = blockIdx.x * 5 + i, pr = k / 40, r = k - pr * 40;
        v[i] = ldg_nc(wo + (size_t)(pr * 40 + (r < 16 ? r : (r < 32 ? r + 4 : (r < 36 ? r - 16 : r)))) * D_ + ck * 8);
      }
#pragma unroll
      for (int i = 0; i < 5; i++) {
        const int k = blockIdx.x * 5 + i;
        g_wo[((nt * 10 + (k >> 6)) * 10 + ck - nt * 10) * 64 + (k & 63)] = v[i];
        float t = ((bf_lo(v[i].x) + bf_hi(v[i].x)) + (bf_lo(v[i].y) + bf_hi(v[i].y))) +
                  ((bf_lo(v[i].z) + bf_hi(v[i].z)) + (bf_lo(v[i].w) + bf_hi(v[i].w)));
        if (t96 >= 80) t = 0.f;
#pragma unroll
        for (int o = 16; o; o >>= 1) t += __shfl_xor_sync(~0u, t, o);
        if (lane == 0) red[(t96 >> 5) * 8 + i] = t;
      }
      bar_sync(1, 96);
      if (t96 < 5) {
        const float mu = (red[t96] + red[8 + t96] + red[16 + t96]) * (1.f / D_);
        const float hi = bf_lo(pack_bf16(mu, 0.f));
        g_wm[blockIdx.x * 5 + t96] = make_uint4(pack_bf16(hi, mu - hi), 0u, 0u, 0u);
      }
    }
    if (tid == 416) STAMP(0, 7);
    __syncwarp();
    cluster_wait();
    cluster_arrive();
  } else {
    cluster_arrive();
    float acc[80];
    const uint64_t da0 = mkdesc(sbase + (warp >> 2) * 8192, 16, 1024, 1);
    const uint64_t db0 = mkdesc(sbase + 24576, 4096, 512, 2);
    const uint32_t tag = __ldcg(&g_epoch) + 1;
    const int srow = m * 192 + n * 16 + warp * 2;
    const bool dostat = warp < 8 && srow < S_;
    uint4 xv[2][3];
    bar_sync(4, 512);
    cluster_wait();
#pragma unroll
    for (int kt = 0; kt < 10; kt++) {
      const int s = kt % K1_ST;
      mbar_wait(fullb + 8 * s, (kt / K1_ST) & 1);
      if (kt == 0 && tid == 0) STAMP(0, 1);
      if (kt == 2 && tid == 0) STAMP(5, 0);
      if (kt == 4 && tid == 0) STAMP(5, 1);
      if (kt == 7 && tid == 0) STAMP(5, 2);
      const uint64_t da = da0 + s * (K1_STAGE >> 4), db = db0 + s * (K1_STAGE >> 4);
      WG_FENCE();
#pragma unroll
      for (int k = 0; k < 4; k++) wgmma_ss_n160(acc, da + k * 2, db + k * 64, (kt | k) != 0);
      WG_COMMIT();
      if (kt > 0) {
        WG_WAIT(1);
        if (kt - 1 + K1_ST < 10 && (tid & 127) < 2) mbar_arrive_cta(emptyb + 8 * ((kt - 1) % K1_ST), tid & 1);
      }
      if (kt == 0) {
#pragma unroll
        for (int i = 0; i < 2; i++) {
          const bf16* xr = x + (size_t)min(srow + i, S_ - 1) * D_ + lane * 8;
          xv[i][0] = xv[i][1] = xv[i][2] = make_uint4(0u, 0u, 0u, 0u);
          if (dostat) { xv[i][0] = ldg_nc(xr); xv[i][1] = ldg_nc(xr + 256); }
          if (dostat && lane < 16) xv[i][2] = ldg_nc(xr + 512);
        }
      }
      if ((kt == 2 || kt == 3) && dostat) {
        const float2 st = row_stats(xv[kt - 2][0], xv[kt - 2][1], xv[kt - 2][2]);
        if (lane == 0) st_relaxed(&g_rowstat[srow + kt - 2], st.x, st.y, tag);
      }
      __syncwarp();
    }
    cluster_arrive();
    WG_WAIT(0);
    fence_regs(acc);
    if (tid == 0) STAMP(0, 2);
    bar_sync(2, 96 + 384);
    if (tid == 0) STAMP(0, 3);
    const int row0 = m * 192 + warp * 16;
    if (row0 < S_) {
      const int g = lane >> 2, c = lane & 3, sec = n >> 2, grp = (row0 & 127) >> 3;
      const bool lo = c < 2;
      const float2 ab0 = rowab[warp * 16 + g], ab1 = rowab[warp * 16 + g + 8];
      const bool p0 = sec == 1 && ((POLY_MASK >> grp) & 1), p1 = sec == 1 && ((POLY_MASK >> (grp + 1)) & 1);
      const uint32_t padqv = sec == 0 ? (c == 2 ? 0x3F803F80u : 0x00003F80u) : (sec == 2 && c == 2 ? 0x00003F80u : 0u);
      const uint32_t padk = c == 2 ? 0x4A7A4B00u : 0x00004653u;
      const uint32_t pad0 = p0 ? padk : padqv, pad1 = p1 ? padk : padqv;
      const float f0 = sec == 0 ? QSCALE : (p0 ? 32768.f : 1.f), f1 = sec == 0 ? QSCALE : (p1 ? 32768.f : 1.f);
      const float a0 = ab0.x * f0, b0 = ab0.y * f0, a1 = ab1.x * f1, b1 = ab1.y * f1;
      const float r0 = p0 ? 9.313225746154785e-10f : 1.f, r1 = p1 ? 9.313225746154785e-10f : 1.f;
      const int cst = sec == 1 ? 2048 : 128, gst = sec == 1 ? 128 : 384;
      uint8_t* pe = (uint8_t*)g_qkv + (size_t)(n * 8) * HEAD_IMG + (row0 >> 7) * 6144 + grp * gst + lane * 4;
      uint8_t* pe1 = pe + cst;
      uint8_t* pe2 = pe1 + cst;
      uint8_t* pf = pe + gst;
      uint8_t* pf1 = pf + cst;
      uint8_t* pf2 = pf1 + cst;
#pragma unroll
      for (int hp = 0; hp < 4; hp++) {
        uint32_t u[5], v[5];
        float su[5], sv[5];
#pragma unroll
        for (int i = 0; i < 5; i++) {
          const int j = hp * 5 + i;
          const float2 t = *(const float2*)&cs[j * 8 + c * 2];
          const float x0 = fmaf(acc[4 * j], a0, b0 * t.x), x1 = fmaf(acc[4 * j + 1], a0, b0 * t.y);
          const float y0 = fmaf(acc[4 * j + 2], a1, b1 * t.x), y1 = fmaf(acc[4 * j + 3], a1, b1 * t.y);
          u[i] = pack_bf16(x0, x1); v[i] = pack_bf16(y0, y1);
          su[i] = fmaf(x0, x0, x1 * x1); sv[i] = fmaf(y0, y0, y1 * y1);
        }
        constexpr int HE = HEAD_IMG;
        const int oe = hp * 2 * HE, oo = oe + HE;
        *(uint32_t*)(pe + oe) = u[0];  *(uint32_t*)(pf + oe) = v[0];
        *(uint32_t*)(pe1 + oe) = u[1]; *(uint32_t*)(pf1 + oe) = v[1];
        *(uint32_t*)(pe2 + oe) = lo ? u[2] : pad0; *(uint32_t*)(pf2 + oe) = lo ? v[2] : pad1;
        *(uint32_t*)(pe + oo) = __shfl_xor_sync(~0u, lo ? u[3] : u[2], 2);
        *(uint32_t*)(pf + oo) = __shfl_xor_sync(~0u, lo ? v[3] : v[2], 2);
        *(uint32_t*)(pe1 + oo) = __shfl_xor_sync(~0u, lo ? u[4] : u[3], 2);
        *(uint32_t*)(pf1 + oo) = __shfl_xor_sync(~0u, lo ? v[4] : v[3], 2);
        const uint32_t tu = __shfl_xor_sync(~0u, u[4], 2), tv = __shfl_xor_sync(~0u, v[4], 2);
        *(uint32_t*)(pe2 + oo) = lo ? tu : pad0; *(uint32_t*)(pf2 + oo) = lo ? tv : pad1;
        if (sec < 2) {
          float e0 = (su[0] + su[1] + (lo ? su[2] : 0.f)) * r0, e1 = (sv[0] + sv[1] + (lo ? sv[2] : 0.f)) * r1;
          float o0 = (su[3] + su[4] + (lo ? 0.f : su[2])) * r0, o1 = (sv[3] + sv[4] + (lo ? 0.f : sv[2])) * r1;
          e0 += __shfl_xor_sync(~0u, e0, 1); e1 += __shfl_xor_sync(~0u, e1, 1);
          o0 += __shfl_xor_sync(~0u, o0, 1); o1 += __shfl_xor_sync(~0u, o1, 1);
          e0 += __shfl_xor_sync(~0u, e0, 2); e1 += __shfl_xor_sync(~0u, e1, 2);
          o0 += __shfl_xor_sync(~0u, o0, 2); o1 += __shfl_xor_sync(~0u, o1, 2);
          const uint32_t em = __reduce_max_sync(~0u, max(__float_as_uint(e0), __float_as_uint(e1)));
          const uint32_t om = __reduce_max_sync(~0u, max(__float_as_uint(o0), __float_as_uint(o1)));
          if (lane < 2) g_nrm[(n * 8 + hp * 2 + lane) * 128 + (row0 >> 4)] = __uint_as_float(lane ? om : em);
        }
      }
    }
    if (tid == 0) STAMP(0, 4);
  }
  cluster_wait();
  if (tid == 0) STAMP(0, 6);
}

constexpr int K2_SMEM = 2 * HEAD_IMG + 2 * 6144 + 2 * 10240 + 256;

__device__ __forceinline__ uint64_t desc64(uint32_t lo, uint32_t hi) {
  uint64_t d;
  asm("mov.b64 %0, {%1, %2};" : "=l"(d) : "r"(lo), "r"(hi));
  return d;
}
__device__ __forceinline__ uint32_t exp_pair(bool poly, float a, float b, uint32_t mk) {
  if (poly) {
    const uint32_t pk = __byte_perm(__float_as_uint(a), __float_as_uint(b), 0x6521);
    uint32_t m, q;
    asm("lop3.b32 %0, %1, %2, 0x3f803f80, 0xEA;" : "=r"(m) : "r"(pk), "r"(mk));
    asm("fma.rn.bf16x2 %0, %1, %1, %2;" : "=r"(q) : "r"(m), "r"(0x40014001u));
    return pk - m + q;
  }
  return pack_bf16(ex2(a), ex2(b));
}
#define PV_GR 2
__device__ __forceinline__ void exp_pv(const float (&s)[64], float (&o)[12], uint64_t dv, uint32_t mk) {
#pragma unroll
  for (int k0 = 0; k0 < 8; k0 += PV_GR) {
    uint32_t p[4 * PV_GR];
#pragma unroll
    for (int i = 0; i < 4 * PV_GR; i++)
      p[i] = exp_pair((POLY_MASK >> (k0 * 2 + i / 2)) & 1, s[k0 * 8 + 2 * i], s[k0 * 8 + 2 * i + 1], mk);
    WG_FENCE();
#pragma unroll
    for (int k = 0; k < PV_GR; k++)
      wgmma_rs_n24(o, p[4 * k], p[4 * k + 1], p[4 * k + 2], p[4 * k + 3], dv + (k0 + k) * 48, 1);
  }
}
__device__ __forceinline__ void load_q(uint32_t (&q)[6], const uint8_t* p) {
  q[0] = __ldcg((const uint32_t*)p);         q[1] = __ldcg((const uint32_t*)(p + 384));
  q[2] = __ldcg((const uint32_t*)(p + 128)); q[3] = __ldcg((const uint32_t*)(p + 512));
  q[4] = __ldcg((const uint32_t*)(p + 256)); q[5] = __ldcg((const uint32_t*)(p + 640));
}
__device__ __forceinline__ float rcp(float x) {
  float y;
  asm("rcp.approx.ftz.f32 %0, %1;" : "=f"(y) : "f"(x));
  return y;
}
__device__ __forceinline__ int img_off(int chunk) { return (chunk >> 3) * 16384 + (chunk & 7) * 128; }
__device__ __forceinline__ void store_o(const float (&o)[12], int tile) {
  int tid, bid;
  asm volatile("mov.u32 %0, %%tid.x;" : "=r"(tid));
  asm volatile("mov.u32 %0, %%ctaid.x;" : "=r"(bid));
  const int head = bid >> 2;
  uint8_t* dst = (uint8_t*)g_o + ((bid & 3) * 4 + (tile >> 1)) * 163840 + (tile & 1) * 8192 + ((tid >> 5) & 3) * 2048 + (tid & 31) * 4;
  const int oc = (head >> 1) * 5 + (head & 1) * 2;
  const int o0 = img_off(oc), o1 = img_off(oc + 1), o2 = img_off((head >> 1) * 5 + 4) + (head & 1) * 8;
  const float i0 = rcp(__shfl_sync(~0u, o[8], 2, 4)), i1 = rcp(__shfl_sync(~0u, o[10], 2, 4));
  *(uint32_t*)(dst + o0) = pack_bf16(o[0] * i0, o[1] * i0); *(uint32_t*)(dst + o0 + 1024) = pack_bf16(o[2] * i1, o[3] * i1);
  *(uint32_t*)(dst + o1) = pack_bf16(o[4] * i0, o[5] * i0); *(uint32_t*)(dst + o1 + 1024) = pack_bf16(o[6] * i1, o[7] * i1);
  if ((tid & 3) < 2) {
    *(uint32_t*)(dst + o2) = pack_bf16(o[8] * i0, o[9] * i0);
    *(uint32_t*)(dst + o2 + 1024) = pack_bf16(o[10] * i1, o[11] * i1);
  }
}

__global__ void __launch_bounds__(512, 1)
k2_attn(const __grid_constant__ CUtensorMap tmg, const __grid_constant__ CUtensorMap tmu,
        const __grid_constant__ CUtensorMap tmd, uint32_t mk) {
  extern __shared__ __align__(1024) uint8_t sm[];
  const uint32_t sbase = smem_u32(sm);
  float* part = (float*)(sm + 2 * HEAD_IMG);
  const uint32_t rbuf = sbase + 2 * HEAD_IMG + 2 * 6144;
  const uint32_t kvb = rbuf + 2 * 10240;
  const uint32_t partb = kvb + 128, rbar = kvb + 144;
  const int tid = threadIdx.x, lane = tid & 31;
  const int warp = __shfl_sync(~0u, tid >> 5, 0);
  const int head = blockIdx.x >> 2, qb = blockIdx.x & 3;

  if (tid == 0) STAMP(1, 0);
  if (tid == 0) {
    for (int i = 0; i < 16; i++) mbar_init(kvb + 8 * i, 1);
    mbar_init(partb, 128); mbar_init(partb + 8, 128); mbar_init(rbar, 1); mbar_init(rbar + 8, 1);
    asm volatile("fence.mbarrier_init.release.cluster;" ::: "memory");
  }
  __syncthreads();

  if (warp >= 12) {
    asm volatile("setmaxnreg.dec.sync.aligned.u32 32;");
    if (tid == 384) {
      pdl_wait();
      pdl_trigger();
      const uint8_t* kimg = (const uint8_t*)g_qkv + (size_t)(32 + head) * HEAD_IMG;
#pragma unroll 1
      for (int b = 0; b < 16; b++) {
        mbar_expect(kvb + 8 * b, 12288);
        bulk_ld(sbase + b * 6144, kimg + b * 6144, 6144, kvb + 8 * b);
        bulk_ld(sbase + HEAD_IMG + b * 6144, kimg + 32 * HEAD_IMG + b * 6144, 6144, kvb + 8 * b);
        if (b >= 2) mbar_wait(kvb + 8 * (b - 1), 0);

      }
      if (blockIdx.x == 0) g_epoch = g_epoch + 1;
      mbar_wait(kvb + 8 * 15, 0);
      STAMP(1, 2);
      uint8_t* pdst = nullptr;
      uint32_t pbytes = 0;
#pragma unroll 1
      for (int i = 0; i < 7; i++) {
        const int p = blockIdx.x + 128 * i;
        uint8_t* dst = nullptr;
        uint32_t bytes = 0;
        if (i < 6 && p < 696) {
          asm volatile("cp.async.bulk.wait_group.read 0;" ::: "memory");
          if (p < 480) {
            const int nk = p / 6, r = p - nk * 6, nt = nk / 10, kt = nk - nt * 10, up = r / 3;
            bytes = 9216;
            dst = (uint8_t*)g_wgu + (size_t)(nk * 54 + r * 9) * 1024;
            mbar_expect(rbar + 8 * (i & 1), bytes);
            tma3d(rbuf + (i & 1) * 10240, up ? &tmu : &tmg, kt * 64, nt * 27 + (r - up * 3) * 9, rbar + 8 * (i & 1));
          } else {
            const int nk = p - 480, nt = nk / 27, kt = nk - nt * 27;
            bytes = 10240;
            dst = (uint8_t*)g_wd + (size_t)nk * 10240;
            mbar_expect(rbar + 8 * (i & 1), bytes);
            tma3d(rbuf + (i & 1) * 10240, &tmd, kt * 64, nt * 10, rbar + 8 * (i & 1));
          }
        }
        if (pbytes) {
          mbar_wait(rbar + 8 * ((i - 1) & 1), ((i - 1) >> 1) & 1);
          bulk_st(pdst, rbuf + ((i - 1) & 1) * 10240, pbytes);
          asm volatile("cp.async.bulk.commit_group;" ::: "memory");
        }
        pdst = dst; pbytes = bytes;
      }
      asm volatile("cp.async.bulk.wait_group.read 0;" ::: "memory");
      STAMP(1, 6);
    }
  } else {
    asm volatile("setmaxnreg.inc.sync.aligned.u32 160;");
    const int wg = warp >> 2;
    const uint8_t* qthr = (const uint8_t*)g_qkv + (size_t)head * HEAD_IMG + qb * 64 * 384 + (warp & 3) * 768 + lane * 4;
    const uint32_t klo0 = ((sbase & 0x3FFFF) >> 4) | (128u << 16), vlo0 = (((sbase + HEAD_IMG) & 0x3FFFF) >> 4) | (24u << 16);
    constexpr uint64_t KSTEP2 = (uint64_t)(int64_t)(256 - (128 << 16));
    constexpr uint64_t KV2K = 384 - (HEAD_IMG >> 4) + (104 << 16);
    const int nun = wg == 1 ? 4 : 3;
    uint32_t utile = wg == 0 ? 0x210u : (wg == 1 ? 0x4235u : 0x576u);
    uint32_t ubeg = wg == 0 ? 0u : (wg == 1 ? 0x0b00u : 0x600u);
    uint32_t ulen = wg == 0 ? 0x0b1010u : (wg == 1 ? 0x10051006u : 0x0a1010u);
    pdl_wait();
    if (tid == 0) STAMP(1, 1);
    uint32_t q[6];
    load_q(q, qthr + (utile & 15) * 3072);
    bool fast;
    {
      const float4 kn = __ldcg((const float4*)&g_nrm[(32 + head) * 128 + lane * 4]);
      const float qv = __ldcg(&g_nrm[head * 128 + qb * 32 + lane]);
      const uint32_t km = max(max(__float_as_uint(kn.x), __float_as_uint(kn.y)), max(__float_as_uint(kn.z), __float_as_uint(kn.w)));
      const float k2 = __uint_as_float(__reduce_max_sync(~0u, km)), q2 = __uint_as_float(__reduce_max_sync(~0u, __float_as_uint(qv)));
      fast = q2 * k2 <= 3400.f;
    }
    if (fast) {
#pragma unroll 1
      for (int u = 0; u < nun; u++) {
        const uint32_t b0 = ubeg & 15;
        const bool wt = u == 0 || (wg == 1 && u == 1);
        float s[64], o[12];
#pragma unroll
        for (int i = 0; i < 12; i++) o[i] = 0.f;
        uint32_t vlo = vlo0 + b0 * 384, kb = kvb + b0 * 8;
        const uint32_t vend = vlo + ((ulen & 255) - 1) * 384;
        if (wt) mbar_wait(kb, 0);
        if (tid == 0) STAMP(5, 4 + u);
        fence_regs(o);
        WG_FENCE();
        wgmma_rs_n128(s, q[0], q[1], q[2], q[3], desc64(klo0 + b0 * 384, 8), 0);
        wgmma_rs_n128(s, q[4], q[5], 0, 0, desc64(klo0 + b0 * 384, 8) + KSTEP2, 1);
        WG_COMMIT();
#pragma unroll 1
        for (; vlo != vend; vlo += 384) {
          if (wt) { kb += 8; mbar_wait(kb, 0); }
          WG_WAIT(0);
          fence_regs(s); fence_regs(o);
          const uint64_t dv = desc64(vlo, 8);
          exp_pv(s, o, dv, mk);
          wgmma_rs_n128(s, q[0], q[1], q[2], q[3], dv + KV2K, 0);
          wgmma_rs_n128(s, q[4], q[5], 0, 0, dv + (KV2K + KSTEP2), 1);
          WG_COMMIT();
        }
        WG_WAIT(0);
        fence_regs(s); fence_regs(o);
        if (u + 1 < nun) load_q(q, qthr + ((utile >> 4) & 15) * 3072);
        exp_pv(s, o, desc64(vlo, 8), mk);
        WG_COMMIT();
        WG_WAIT(0);
        fence_regs(o);
        if (wg == 1 && !(u & 1)) {
          float4* pp = (float4*)(part + u * 768) + (tid & 127);
          pp[0] = make_float4(o[0], o[1], o[2], o[3]);
          pp[128] = make_float4(o[4], o[5], o[6], o[7]);
          pp[256] = make_float4(o[8], o[9], o[10], o[11]);
          mbar_arrive(partb + 4 * u);
        } else {
          if (wg != 1 && u == 2) {
            const int pi = wg == 0 ? 1 : 0;
            mbar_wait(partb + 8 * pi, 0);
            const float4* pp = (const float4*)(part + pi * 1536) + (tid & 127);
            const float4 x0 = pp[0], x1 = pp[128], x2 = pp[256];
            o[0] += x0.x; o[1] += x0.y; o[2] += x0.z; o[3] += x0.w; o[4] += x1.x; o[5] += x1.y;
            o[6] += x1.z; o[7] += x1.w; o[8] += x2.x; o[9] += x2.y; o[10] += x2.z; o[11] += x2.w;
          }
          store_o(o, utile & 15);
        }
        utile >>= 4; ubeg >>= 4; ulen >>= 8;
      }
      if ((tid & 127) == 0) STAMP(1, 3 + wg);
    } else {
#pragma unroll 1
      for (int tile = wg; tile < 8; tile += 3) {
        load_q(q, qthr + tile * 3072);
        if ((lane & 3) >= 2) { q[4] = 0; q[5] = 0; }
        float o[12], m0 = -INFINITY, m1 = -INFINITY;
#pragma unroll
        for (int i = 0; i < 12; i++) o[i] = 0.f;
#pragma unroll 1
        for (int b = 0; b < 16; b++) {
          float s[64];
          mbar_wait(kvb + 8 * b, 0);
          WG_FENCE();
          wgmma_rs_n128(s, q[0], q[1], q[2], q[3], desc64(klo0 + b * 384, 8), 0);
          wgmma_rs_n128(s, q[4], q[5], 0, 0, desc64(klo0 + b * 384, 8) + KSTEP2, 1);
          WG_COMMIT();
          WG_WAIT(0);
          fence_regs(s);
          float x0 = m0, x1 = m1;
#pragma unroll
          for (int j = 0; j < 16; j++) {
            if ((POLY_MASK >> j) & 1) {
#pragma unroll
              for (int i = 0; i < 4; i++) s[4 * j + i] *= (1.f / 32768.f);
            }
            x0 = fmaxf(x0, fmaxf(s[4 * j], s[4 * j + 1]));
            x1 = fmaxf(x1, fmaxf(s[4 * j + 2], s[4 * j + 3]));
          }
          x0 = fmaxf(x0, __shfl_xor_sync(~0u, x0, 1)); x0 = fmaxf(x0, __shfl_xor_sync(~0u, x0, 2));
          x1 = fmaxf(x1, __shfl_xor_sync(~0u, x1, 1)); x1 = fmaxf(x1, __shfl_xor_sync(~0u, x1, 2));
          const float al0 = ex2(m0 - x0), al1 = ex2(m1 - x1);
          m0 = x0; m1 = x1;
#pragma unroll
          for (int i = 0; i < 12; i++) o[i] *= (i & 2) ? al1 : al0;
          uint32_t p[32];
#pragma unroll
          for (int i = 0; i < 32; i++) {
            const float mm = (i & 1) ? m1 : m0;
            p[i] = pack_bf16(ex2(s[2 * i] - mm), ex2(s[2 * i + 1] - mm));
          }
          fence_regs(o);
          WG_FENCE();
#pragma unroll
          for (int k = 0; k < 8; k++)
            wgmma_rs_n24(o, p[4 * k], p[4 * k + 1], p[4 * k + 2], p[4 * k + 3], desc64(vlo0 + b * 384 + k * 48, 8), 1);
          WG_COMMIT();
          WG_WAIT(0);
          fence_regs(o);
        }
        store_o(o, tile);
      }
    }
  }
}

#define K3P 4
constexpr int K3_ST = 4, K3_STAGE = 37888, K3_PRE = K3P;
constexpr int K3_SMEM = K3_ST * K3_STAGE + 45056 + 20480 + 256;

template <int N> struct Acc { float v[N]; };

template <int NB, int NK, bool FIRST>
__global__ void __cluster_dims__(2, 1, 1) __launch_bounds__(384, 1)
k3_proj(const __grid_constant__ CUtensorMap tmr, const uint4* __restrict__ aimg, const uint4* __restrict__ wimg) {
  constexpr int KT = 2 * NB + NK, EX = FIRST ? 1 : 0;
  extern __shared__ __align__(1024) uint8_t sm[];
  const uint32_t sbase = smem_u32(sm);
  uint8_t* xch = sm + K3_ST * K3_STAGE;
  uint8_t* stg = sm + K3_ST * K3_STAGE + 45056;
  const uint32_t fullb = smem_u32(stg) + 20480, emptyb = fullb + 8 * K3_ST, resb = emptyb + 8 * K3_ST, xchb = resb + 8;
  const int tid = threadIdx.x, lane = tid & 31;
  const int warp = __shfl_sync(~0u, tid >> 5, 0);
  const int rank = blockIdx.x & 1;
  const int n = blockIdx.x & 7, m = blockIdx.x >> 3;
  if (tid == 0) STAMP(FIRST ? 2 : 4, 0);
  if (warp == 0) {
    if (lane == 0) {
      prefetch_map(&tmr);
      for (int i = 0; i < K3_ST; i++) { mbar_init(fullb + 8 * i, 1); mbar_init(emptyb + 8 * i, 4); }
      mbar_init(resb, 1); mbar_init(xchb, 1);
      mbar_expect(xchb, 4096 * (10 + EX));
      asm volatile("fence.mbarrier_init.release.cluster;" ::: "memory");
    }
    __syncwarp();
    cluster_arrive();
    bar_arrive(4, 256 + 32);
    if (lane == 0) {
      const uint8_t* wk = (const uint8_t*)wimg + (size_t)n * KT * 10240;
      const uint8_t* ws = (const uint8_t*)wimg + (size_t)(n ^ 1) * KT * 10240;
      const uint8_t* ab = (const uint8_t*)aimg + (size_t)m * KT * 16384;
      auto load_w = [&](int i) {
        const int s = i % K3_ST, kt = i < NB ? i + rank * (NB + NK) : i;
        const uint32_t sa = sbase + s * K3_STAGE;
        mbar_expect(fullb + 8 * s, 26624 + EX * 1024 + (i < NB ? 10240 : 0));
        bulk_ld(sa + 16384, wk + kt * 10240, 10240, fullb + 8 * s);
        if (FIRST) bulk_ld(sa + 26624, (const uint8_t*)g_wm + kt * 1024, 1024, fullb + 8 * s);
        if (i < NB) bulk_ld(sa + 26624 + EX * 1024, ws + kt * 10240, 10240, fullb + 8 * s);
      };
#pragma unroll 1
      for (int i = 0; i < K3_PRE; i++) load_w(i);
      if (FIRST) {
        mbar_expect(resb, 20480);
        tma2d(smem_u32(stg), &tmr, n * 80, m * 128, resb);
        tma2d(smem_u32(stg) + 10240, &tmr, n * 80, m * 128 + 64, resb);
      }
      asm volatile("barrier.cluster.wait;" ::: "memory");
      pdl_wait();
      pdl_trigger();
#pragma unroll 1
      for (int i = 0; i < NB + NK; i++) {
        const int s = i % K3_ST;
        const uint32_t sa = sbase + s * K3_STAGE;
        if (i >= K3_ST) mbar_wait(emptyb + 8 * s, ((i / K3_ST) - 1) & 1);
        if (i < NB) bulk_ld(sa, ab + (i + rank * (NB + NK)) * 16384, 16384, fullb + 8 * s);
        else bulk_ld_mc(sa + rank * 8192, ab + i * 16384 + rank * 8192, 8192, fullb + 8 * s);
        if (i >= K3_PRE) load_w(i);
      }
    } else {
      asm volatile("barrier.cluster.wait;" ::: "memory");
    }
    __syncwarp();
    cluster_arrive();
  } else if (warp >= 4) {
    cluster_arrive();
    const int cw = warp - 4, wg = cw >> 2;
    const int g = lane >> 2, c = lane & 3;
    const int row = m * 128 + cw * 16 + g;
    uint8_t* himg = (uint8_t*)g_h + (size_t)m * 163840 + cw * 2048 + lane * 4;
    uint32_t rv[20];
    float mu0, mu1;
    if (FIRST) {
      mu0 = __uint_as_float(__ldcg(&g_rowstat[row].z)); mu1 = __uint_as_float(__ldcg(&g_rowstat[row + 8].z));
    } else {
      mu0 = __ldcg(&g_hmean[row]); mu1 = __ldcg(&g_hmean[row + 8]);
#pragma unroll
      for (int j = 0; j < 10; j++) {
        rv[2 * j] = __ldcg((const uint32_t*)(himg + img_off(n * 10 + j)));
        rv[2 * j + 1] = __ldcg((const uint32_t*)(himg + img_off(n * 10 + j) + 1024));
      }
    }
    float acc[80 + 4 * EX];
    float (&keep)[40 + 4 * EX] = ((Acc<40 + 4 * EX>*)acc)->v;
    const uint64_t da0 = mkdesc(sbase + wg * 8192, 128, 1024, 0);
    const uint64_t db0 = mkdesc(sbase + 16384, 128, 1024, 0);
    bar_sync(4, 256 + 32);
    cluster_wait();
#pragma unroll 1
    for (int i = 0; i < NB; i++) {
      const int s = i % K3_ST;
      mbar_wait(fullb + 8 * s, (i / K3_ST) & 1);
      if (i == 0 && tid == 128) STAMP(FIRST ? 2 : 4, 2);
      const uint64_t da = da0 + s * (K3_STAGE >> 4), db = db0 + s * (K3_STAGE >> 4);
      WG_FENCE();
#pragma unroll
      for (int k = 0; k < 4; k++) {
        if constexpr (FIRST) wgmma_ss_n168(acc, da + k * 16, db + k * 16, (i | k) != 0);
        else wgmma_ss_n160(acc, da + k * 16, db + k * 16, (i | k) != 0);
      }
      WG_COMMIT();
      if (i > 0) {
        WG_WAIT(1);
        if ((tid & 127) < 2) mbar_arrive_cta(emptyb + 8 * ((i - 1) % K3_ST), tid & 1);
      }
    }
    const uint32_t rx = mapa(smem_u32(xch) + (tid - 128) * 16, rank ^ 1), rb = mapa(xchb, rank ^ 1);
    WG_WAIT(0);
    fence_regs(acc);
    if ((tid & 127) < 2) mbar_arrive_cta(emptyb + 8 * ((NB - 1) % K3_ST), tid & 1);
    if (FIRST) st_async4(rx, acc[40], acc[41], acc[42], acc[43], rb);
    if (tid == 128) STAMP(FIRST ? 2 : 4, 1);
#pragma unroll
    for (int i = NB; i < NB + NK; i++) {
      const int s = i % K3_ST;
      mbar_wait(fullb + 8 * s, (i / K3_ST) & 1);
      const uint64_t da = da0 + s * (K3_STAGE >> 4), db = db0 + s * (K3_STAGE >> 4);
      WG_FENCE();
#pragma unroll
      for (int k = 0; k < 4; k++) {
        if constexpr (FIRST) wgmma_ss_n88(keep, da + k * 16, db + k * 16, 1);
        else wgmma_ss_n80(keep, da + k * 16, db + k * 16, 1);
      }
      WG_COMMIT();
      if (i > NB && i - 1 + K3_ST < NB + NK) {
        WG_WAIT(1);
        if ((tid & 127) < 2) mbar_arrive_cta(emptyb + 8 * ((i - 1) % K3_ST), tid & 1);
      }
#pragma unroll
      for (int j = (i - NB) * 3 + EX; j < (i - NB) * 3 + 3 + EX; j++)
        if (j < 10 + EX) st_async4(rx + j * 4096, acc[40 + 4 * j], acc[41 + 4 * j], acc[42 + 4 * j], acc[43 + 4 * j], rb);
    }
    cluster_arrive();
    uint8_t* sp = stg + (cw * 16 + g) * 160 + c * 4;
    if (FIRST) {
      mbar_wait(resb, 0);
#pragma unroll
      for (int j = 0; j < 10; j++) {
        rv[2 * j] = *(const uint32_t*)(sp + j * 16);
        rv[2 * j + 1] = *(const uint32_t*)(sp + 1280 + j * 16);
      }
    }
    WG_WAIT(0);
    fence_regs(keep);
    if (tid == 128) STAMP(FIRST ? 2 : 4, 3);
    mbar_wait(xchb, 0);
    if (tid == 128) STAMP(FIRST ? 2 : 4, 5);
    const uint8_t* xp = xch + (tid - 128) * 16;
    if (FIRST) {
      const float4 p = *(const float4*)xp;
      mu0 += __shfl_sync(~0u, (keep[40] + p.x) + (keep[41] + p.y), 0, 4);
      mu1 += __shfl_sync(~0u, (keep[42] + p.z) + (keep[43] + p.w), 0, 4);
      if (n == 0 && c == 0) { g_hmean[row] = mu0; g_hmean[row + 8] = mu1; }
      mu0 = -mu0; mu1 = -mu1;
    }
    float q0 = 0.f, q1 = 0.f;
#pragma unroll
    for (int j = 0; j < 10; j++) {
      const float4 p = *(const float4*)(xp + (j + EX) * 4096);
      const float x0 = (keep[4 * j] + p.x) + (bf_lo(rv[2 * j]) + mu0), x1 = (keep[4 * j + 1] + p.y) + (bf_hi(rv[2 * j]) + mu0);
      const float y0 = (keep[4 * j + 2] + p.z) + (bf_lo(rv[2 * j + 1]) + mu1), y1 = (keep[4 * j + 3] + p.w) + (bf_hi(rv[2 * j + 1]) + mu1);
      if (FIRST) {
        *(uint32_t*)(himg + img_off(n * 10 + j)) = pack_bf16(x0, x1);
        *(uint32_t*)(himg + img_off(n * 10 + j) + 1024) = pack_bf16(y0, y1);
        q0 = fmaf(x0, x0, fmaf(x1, x1, q0)); q1 = fmaf(y0, y0, fmaf(y1, y1, q1));
      } else {
        *(uint32_t*)(sp + j * 16) = pack_bf16(x0, x1);
        *(uint32_t*)(sp + 1280 + j * 16) = pack_bf16(y0, y1);
      }
    }
    if (FIRST) {
      q0 += __shfl_xor_sync(~0u, q0, 1); q0 += __shfl_xor_sync(~0u, q0, 2);
      q1 += __shfl_xor_sync(~0u, q1, 1); q1 += __shfl_xor_sync(~0u, q1, 2);
      if (c < 2) g_hpart[n * S_ + row + c * 8] = c ? q1 : q0;
    } else {
      fence_async();
      bar_sync(1 + wg, 128);
      if ((tid & 127) == 0) {
        tma2d_st(&tmr, n * 80, m * 128 + wg * 64, smem_u32(stg) + wg * 10240);
        bulk_commit_wait();
      }
      __syncwarp();
    }
    if (tid == 128) STAMP(FIRST ? 2 : 4, 4);
  } else {
    cluster_arrive();
    cluster_wait();
    cluster_arrive();
  }
  cluster_wait();
}

constexpr int K4_ST = 3, K4_STAGE = 71680;
constexpr int K4_SMEM = K4_ST * K4_STAGE + 64;

__global__ void __cluster_dims__(2, 1, 1) __launch_bounds__(256, 1)
k4_ffn1() {
  extern __shared__ __align__(1024) uint8_t sm[];
  const uint32_t sbase = smem_u32(sm);
  const uint32_t fullb = sbase + K4_ST * K4_STAGE, emptyb = fullb + 8 * K4_ST;
  const int tid = threadIdx.x, lane = tid & 31;
  const int warp = __shfl_sync(~0u, tid >> 5, 0);
  const int rank = blockIdx.x & 1, cl = blockIdx.x >> 1;
  const int n = cl & 7, m = (cl >> 3) * 2 + rank;
  const uint8_t* wb = (const uint8_t*)g_wgu + (size_t)n * 10 * 55296 + rank * 27648;
  const uint8_t* ab = (const uint8_t*)g_h + (size_t)m * 163840;
  if (tid == 0) STAMP(3, 0);
  if (tid == 0) {
    for (int i = 0; i < K4_ST; i++) { mbar_init(fullb + 8 * i, 1); mbar_init(emptyb + 8 * i, 4); }
    asm volatile("fence.mbarrier_init.release.cluster;" ::: "memory");
    for (int kt = 0; kt < K4_ST; kt++) mbar_expect(fullb + 8 * kt, K4_STAGE);
  }
  __syncthreads();
  cluster_arrive();
  cluster_wait();
  if (tid == 0) bulk_ld_mc(sbase + 16384 + rank * 27648, wb, 27648, fullb);
  pdl_wait();
  pdl_trigger();
  if (tid == 128) STAMP(3, 1);
  if (tid == 0) {
    bulk_ld(sbase, ab, 16384, fullb);
    for (int kt = 1; kt < K4_ST; kt++) {
      bulk_ld(sbase + kt * K4_STAGE, ab + kt * 16384, 16384, fullb + 8 * kt);
      bulk_ld_mc(sbase + kt * K4_STAGE + 16384 + rank * 27648, wb + kt * 55296, 27648, fullb + 8 * kt);
    }
  }
  __syncwarp();
  float r0, r1;
  {
    const float* hp = &g_hpart[(lane & 3) * 2 * S_ + m * 128 + warp * 16 + (lane >> 2)];
    r0 = __ldcg(hp) + __ldcg(hp + S_);
    r1 = __ldcg(hp + 8) + __ldcg(hp + S_ + 8);
  }
  float ag[108], au[108];
  const uint64_t da0 = mkdesc(sbase + (warp >> 2) * 8192, 128, 1024, 0);
  const uint64_t db0 = mkdesc(sbase + 16384, 128, 1024, 0);
#pragma unroll 1
  for (int kt = 0; kt < 10; kt++) {
    const int s = kt % K4_ST;
    mbar_wait(fullb + 8 * s, (kt / K4_ST) & 1);
    if (kt == 0 && tid == 128) STAMP(3, 2);
    const uint64_t da = da0 + s * (K4_STAGE >> 4), db = db0 + s * (K4_STAGE >> 4);
    WG_FENCE();
#pragma unroll
    for (int k = 0; k < 4; k++) {
      wgmma_ss_n216(ag, da + k * 16, db + k * 16, (kt | k) != 0);
      wgmma_ss_n216(au, da + k * 16, db + 1728 + k * 16, (kt | k) != 0);
    }
    WG_COMMIT();
    if (kt > 0 && kt - 1 + K4_ST < 10) {
      WG_WAIT(1);
      const int sp = (kt - 1) % K4_ST;
      if ((tid & 127) < 2) mbar_arrive_cta(emptyb + 8 * sp, tid & 1);
      if (tid == 0) {
        const uint32_t sa = sbase + sp * K4_STAGE;
        mbar_wait(emptyb + 8 * sp, ((kt - 1) / K4_ST) & 1);
        mbar_expect(fullb + 8 * sp, K4_STAGE);
        bulk_ld_mc(sa + 16384 + rank * 27648, wb + (kt - 1 + K4_ST) * 55296, 27648, fullb + 8 * sp);
        bulk_ld(sa, ab + (kt - 1 + K4_ST) * 16384, 16384, fullb + 8 * sp);
      }
      __syncwarp();
    }
  }
  r0 += __shfl_xor_sync(~0u, r0, 1); r1 += __shfl_xor_sync(~0u, r1, 1);
  r0 += __shfl_xor_sync(~0u, r0, 2); r1 += __shfl_xor_sync(~0u, r1, 2);
  r0 = __frcp_rn(r0 * (1.f / D_) + 1e-5f); r1 = __frcp_rn(r1 * (1.f / D_) + 1e-5f);
  cluster_arrive();
  WG_WAIT(0);
  fence_regs(ag); fence_regs(au);
  if (tid == 128) STAMP(3, 3);
  uint8_t* dst = (uint8_t*)g_hh + (size_t)m * 27 * 16384 + warp * 2048 + lane * 4;
#pragma unroll
  for (int j = 0; j < 27; j++) {
    *(uint32_t*)(dst + img_off(n * 27 + j)) = pack_bf16(ag[4 * j] * r0 * au[4 * j], ag[4 * j + 1] * r0 * au[4 * j + 1]);
    *(uint32_t*)(dst + img_off(n * 27 + j) + 1024) = pack_bf16(ag[4 * j + 2] * r1 * au[4 * j + 2], ag[4 * j + 3] * r1 * au[4 * j + 3]);
  }
  if (tid == 128) STAMP(3, 4);
  cluster_wait();
}

typedef CUresult (*EncodeFn)(CUtensorMap*, CUtensorMapDataType, cuuint32_t, void*, const cuuint64_t*, const cuuint64_t*,
                             const cuuint32_t*, const cuuint32_t*, CUtensorMapInterleave, CUtensorMapSwizzle,
                             CUtensorMapL2promotion, CUtensorMapFloatOOBfill);

static CUtensorMap make_map(EncodeFn enc, const void* p, uint64_t inner, uint64_t outer, uint32_t box_inner,
                            uint32_t box_outer, CUtensorMapSwizzle swz) {
  CUtensorMap m;
  cuuint64_t gd[2] = {inner, outer};
  cuuint64_t gs[1] = {inner * 2};
  cuuint32_t bd[2] = {box_inner, box_outer};
  cuuint32_t es[2] = {1, 1};
  enc(&m, CU_TENSOR_MAP_DATA_TYPE_BFLOAT16, 2, (void*)p, gd, gs, bd, es, CU_TENSOR_MAP_INTERLEAVE_NONE, swz,
      CU_TENSOR_MAP_L2_PROMOTION_L2_256B, CU_TENSOR_MAP_FLOAT_OOB_FILL_NONE);
  return m;
}

static CUtensorMap make_map_img(EncodeFn enc, const void* p, uint64_t k, uint64_t n, uint32_t chunks) {
  CUtensorMap m;
  cuuint64_t gd[3] = {8, k, n / 8};
  cuuint64_t gs[2] = {n * 2, 16};
  cuuint32_t bd[3] = {8, 64, chunks};
  cuuint32_t es[3] = {1, 1, 1};
  enc(&m, CU_TENSOR_MAP_DATA_TYPE_BFLOAT16, 3, (void*)p, gd, gs, bd, es, CU_TENSOR_MAP_INTERLEAVE_NONE,
      CU_TENSOR_MAP_SWIZZLE_NONE, CU_TENSOR_MAP_L2_PROMOTION_L2_128B, CU_TENSOR_MAP_FLOAT_OOB_FILL_NONE);
  return m;
}

template <typename... KArgs, typename... Args>
static void launch(void (*k)(KArgs...), int grid, int threads, int smem, bool pdl, Args... args) {
  cudaLaunchConfig_t cfg = {};
  cfg.gridDim = dim3(grid);
  cfg.blockDim = dim3(threads);
  cfg.dynamicSmemBytes = smem;
  cfg.stream = cudaStreamPerThread;
  cudaLaunchAttribute at[1];
  at[0].id = cudaLaunchAttributeProgrammaticStreamSerialization;
  at[0].val.programmaticStreamSerializationAllowed = 1;
  cfg.attrs = at;
  cfg.numAttrs = pdl ? 1 : 0;
  cudaLaunchKernelEx(&cfg, k, KArgs(args)...);
}

extern "C" void kernel_launch(void* const* d_in, const int* in_sizes, int n_in, void* d_out, int out_size) {
  const bf16* x = (const bf16*)d_in[0];
  const bf16* wqkv = (const bf16*)d_in[1];
  const bf16* wo = (const bf16*)d_in[2];
  const bf16* wg = (const bf16*)d_in[4];
  const bf16* wu = (const bf16*)d_in[5];
  const bf16* wd = (const bf16*)d_in[6];

  static EncodeFn enc = nullptr;
  static void *p_o, *p_hh, *p_wo, *p_wd;
  if (!enc) {
    void* fn = nullptr;
    cudaDriverEntryPointQueryResult qr;
    cudaGetDriverEntryPoint("cuTensorMapEncodeTiled", &fn, cudaEnableDefault, &qr);
    enc = (EncodeFn)fn;
    cudaGetSymbolAddress(&p_o, g_o); cudaGetSymbolAddress(&p_hh, g_hh);
    cudaGetSymbolAddress(&p_wo, g_wo); cudaGetSymbolAddress(&p_wd, g_wd);
    cudaFuncSetAttribute(k1_qkv, cudaFuncAttributeMaxDynamicSharedMemorySize, K1_SMEM);
    cudaFuncSetAttribute(k2_attn, cudaFuncAttributeMaxDynamicSharedMemorySize, K2_SMEM);
    cudaFuncSetAttribute(k3_proj<3, 4, true>, cudaFuncAttributeMaxDynamicSharedMemorySize, K3_SMEM);
    cudaFuncSetAttribute(k3_proj<11, 5, false>, cudaFuncAttributeMaxDynamicSharedMemorySize, K3_SMEM);
    cudaFuncSetAttribute(k4_ffn1, cudaFuncAttributeMaxDynamicSharedMemorySize, K4_SMEM);
  }
  const CUtensorMap tmx = make_map(enc, x, D_, S_, 64, 96, CU_TENSOR_MAP_SWIZZLE_128B);
  const CUtensorMap tmw = make_map(enc, wqkv, 3 * D_, D_, 32, 64, CU_TENSOR_MAP_SWIZZLE_64B);
  const CUtensorMap tmxr = make_map(enc, x, D_, S_, 80, 64, CU_TENSOR_MAP_SWIZZLE_NONE);
  const CUtensorMap tmg = make_map_img(enc, wg, D_, F_, 9), tmu = make_map_img(enc, wu, D_, F_, 9);
  const CUtensorMap tmd = make_map_img(enc, wd, F_, D_, 10);
  const CUtensorMap tmout = make_map(enc, d_out, D_, S_, 80, 64, CU_TENSOR_MAP_SWIZZLE_NONE);

  launch(k1_qkv, 132, 512, K1_SMEM, false, tmx, tmw, x, wqkv, wo);
  launch(k2_attn, 128, 512, K2_SMEM, true, tmg, tmu, tmd, 0x007f007fu);
  launch(k3_proj<3, 4, true>, 128, 384, K3_SMEM, true, tmxr, (const uint4*)p_o, (const uint4*)p_wo);
  launch(k4_ffn1, 128, 256, K4_SMEM, true);
  launch(k3_proj<11, 5, false>, 128, 384, K3_SMEM, true, tmout, (const uint4*)p_hh, (const uint4*)p_wd);
}
```

```cpp
#include <cuda_runtime.h>
#include <cuda_bf16.h>
#include <cuda.h>
#include <stdint.h>

typedef __nv_bfloat16 bf16;

constexpr int S_ = 2048, D_ = 640, F_ = 1728;
constexpr int HEAD_IMG = 98304;
#define PMASK 0xDB6D
constexpr uint32_t POLY_MASK = PMASK;
constexpr float QSCALE = 0.22360679774997896f * 1.4426950408889634f;

__device__ __align__(1024) uint4 g_qkv[96 * HEAD_IMG / 16];
__device__ __align__(1024) uint4 g_o[S_ * D_ / 8];
__device__ __align__(1024) uint4 g_h[S_ * D_ / 8];
__device__ __align__(1024) uint4 g_hh[S_ * F_ / 8];
__device__ __align__(1024) uint4 g_wo[D_ * D_ / 8];
__device__ __align__(1024) uint4 g_wgu[2 * D_ * F_ / 8];
__device__ __align__(1024) uint4 g_wd[F_ * D_ / 8];
__device__ uint4 g_rowstat[S_];
__device__ uint4 g_cpart[10 * 12 * 80];
__device__ float g_nrm[64 * 128];
__device__ uint4 g_wm[D_];
__device__ float g_hmean[S_];
__device__ float g_hpart[8 * S_];
__device__ uint4 g_flag[2 * 16 * 2];
__device__ unsigned g_epoch;

#define STAMP(k, i)
__device__ __forceinline__ uint32_t smem_u32(const void* p) { return (uint32_t)__cvta_generic_to_shared(p); }
__device__ __forceinline__ void mbar_init(uint32_t a, uint32_t c) {
  asm volatile("mbarrier.init.shared::cta.b64 [%0], %1;" ::"r"(a), "r"(c) : "memory");
}
__device__ __forceinline__ void mbar_expect(uint32_t a, uint32_t bytes) {
  asm volatile("mbarrier.arrive.expect_tx.shared::cta.b64 _, [%0], %1;" ::"r"(a), "r"(bytes) : "memory");
}
__device__ __forceinline__ void mbar_arrive(uint32_t a) {
  asm volatile("mbarrier.arrive.shared::cta.b64 _, [%0];" ::"r"(a) : "memory");
}
__device__ __forceinline__ void mbar_arrive_cta(uint32_t a, uint32_t cta) {
  asm volatile("{\n.reg .b32 r;\nmapa.shared::cluster.u32 r, %0, %1;\n"
               "mbarrier.arrive.shared::cluster.b64 _, [r];\n}" ::"r"(a), "r"(cta) : "memory");
}
__device__ __forceinline__ bool mbar_try(uint32_t a, uint32_t ph) {
  uint32_t ok;
  asm volatile("{\n.reg .pred p;\nmbarrier.try_wait.parity.shared::cta.b64 p, [%1], %2;\nselp.u32 %0, 1, 0, p;\n}"
               : "=r"(ok) : "r"(a), "r"(ph) : "memory");
  return ok;
}
__device__ __noinline__ void wait_timeout() { __trap(); }
__device__ __forceinline__ void mbar_wait(uint32_t a, uint32_t ph) {
  if (mbar_try(a, ph)) return;
  uint32_t it = 0;
  while (!mbar_try(a, ph)) if (++it > (1u << 22)) wait_timeout();
}
__device__ __forceinline__ void tma2d(uint32_t dst, const CUtensorMap* m, int c0, int c1, uint32_t bar) {
  asm volatile("cp.async.bulk.tensor.2d.shared::cluster.global.mbarrier::complete_tx::bytes [%0], [%1, {%3, %4}], [%2];"
               ::"r"(dst), "l"(m), "r"(bar), "r"(c0), "r"(c1) : "memory");
}
__device__ __forceinline__ void tma2d_mc(uint32_t dst, const CUtensorMap* m, int c0, int c1, uint32_t bar) {
  asm volatile("cp.async.bulk.tensor.2d.shared::cluster.global.mbarrier::complete_tx::bytes.multicast::cluster "
               "[%0], [%1, {%3, %4}], [%2], %5;"
               ::"r"(dst), "l"(m), "r"(bar), "r"(c0), "r"(c1), "h"((uint16_t)3) : "memory");
}
__device__ __forceinline__ void bulk_ld(uint32_t dst, const void* src, uint32_t bytes, uint32_t bar) {
  asm volatile("cp.async.bulk.shared::cluster.global.mbarrier::complete_tx::bytes [%0], [%1], %2, [%3];"
               ::"r"(dst), "l"(src), "r"(bytes), "r"(bar) : "memory");
}
__device__ __forceinline__ void bulk_ld_mc(uint32_t dst, const void* src, uint32_t bytes, uint32_t bar) {
  asm volatile("cp.async.bulk.shared::cluster.global.mbarrier::complete_tx::bytes.multicast::cluster "
               "[%0], [%1], %2, [%3], %4;"
               ::"r"(dst), "l"(src), "r"(bytes), "r"(bar), "h"((uint16_t)3) : "memory");
}
__device__ __forceinline__ void cluster_arrive() { asm volatile("barrier.cluster.arrive.relaxed.aligned;" ::: "memory"); }
__device__ __forceinline__ void cluster_wait() { asm volatile("barrier.cluster.wait.aligned;" ::: "memory"); }
__device__ __forceinline__ void bulk_st(void* dst, uint32_t src, uint32_t bytes) {
  asm volatile("cp.async.bulk.global.shared::cta.bulk_group [%0], [%1], %2;" ::"l"(dst), "r"(src), "r"(bytes) : "memory");
}
__device__ __forceinline__ void tma2d_st(const CUtensorMap* m, int c0, int c1, uint32_t src) {
  asm volatile("cp.async.bulk.tensor.2d.global.shared::cta.bulk_group [%0, {%2, %3}], [%1];"
               ::"l"(m), "r"(src), "r"(c0), "r"(c1) : "memory");
}
__device__ __forceinline__ void bulk_commit_wait() {
  asm volatile("cp.async.bulk.commit_group;\ncp.async.bulk.wait_group.read 0;" ::: "memory");
}
__device__ __forceinline__ uint32_t mapa(uint32_t a, uint32_t cta) {
  uint32_t r;
  asm("mapa.shared::cluster.u32 %0, %1, %2;" : "=r"(r) : "r"(a), "r"(cta));
  return r;
}
__device__ __forceinline__ void st_async4(uint32_t dst, float a, float b, float c, float d, uint32_t bar) {
  asm volatile("st.async.shared::cluster.mbarrier::complete_tx::bytes.v4.f32 [%0], {%1, %2, %3, %4}, [%5];"
               ::"r"(dst), "f"(a), "f"(b), "f"(c), "f"(d), "r"(bar) : "memory");
}
__device__ __forceinline__ void fence_async() { asm volatile("fence.proxy.async.shared::cta;" ::: "memory"); }
__device__ __forceinline__ void prefetch_map(const CUtensorMap* m) {
  asm volatile("prefetch.tensormap [%0];" ::"l"(m) : "memory");
}
__device__ __forceinline__ void pdl_wait() { asm volatile("griddepcontrol.wait;" ::: "memory"); }
__device__ __forceinline__ void pdl_trigger() { asm volatile("griddepcontrol.launch_dependents;" ::: "memory"); }
__device__ __forceinline__ void bar_sync(int id, int n) { asm volatile("bar.sync %0, %1;" ::"r"(id), "r"(n) : "memory"); }
__device__ __forceinline__ void bar_arrive(int id, int n) { asm volatile("bar.arrive %0, %1;" ::"r"(id), "r"(n) : "memory"); }
#define WG_FENCE() asm volatile("wgmma.fence.sync.aligned;" ::: "memory")
#define WG_COMMIT() asm volatile("wgmma.commit_group.sync.aligned;" ::: "memory")
#define WG_WAIT(n) asm volatile("wgmma.wait_group.sync.aligned %0;" ::"n"(n) : "memory")
__device__ __forceinline__ uint64_t mkdesc(uint32_t addr, uint32_t lbo, uint32_t sbo, uint32_t sw) {
  return (uint64_t)((addr & 0x3FFFF) >> 4) | ((uint64_t)(lbo >> 4) << 16) | ((uint64_t)(sbo >> 4) << 32) |
         ((uint64_t)sw << 62);
}
template <int N> __device__ __forceinline__ void fence_regs(float (&r)[N]) {
#pragma unroll
  for (int i = 0; i < N; i++) asm volatile("" : "+f"(r[i])::"memory");
}
__device__ __forceinline__ uint32_t pack_bf16(float lo, float hi) {
  uint32_t r;
  asm("cvt.rn.bf16x2.f32 %0, %1, %2;" : "=r"(r) : "f"(hi), "f"(lo));
  return r;
}
__device__ __forceinline__ float bf_lo(uint32_t v) { return __uint_as_float(v << 16); }
__device__ __forceinline__ float bf_hi(uint32_t v) { return __uint_as_float(v & 0xffff0000u); }
__device__ __forceinline__ float ex2(float x) {
  float y;
  asm("ex2.approx.ftz.f32 %0, %1;" : "=f"(y) : "f"(x));
  return y;
}
__device__ __forceinline__ uint4 ldg_nc(const void* p) {
  uint4 v;
  asm volatile("ld.global.nc.L1::no_allocate.v4.u32 {%0, %1, %2, %3}, [%4];"
               : "=r"(v.x), "=r"(v.y), "=r"(v.z), "=r"(v.w) : "l"(p));
  return v;
}

__device__ __forceinline__ uint4 ld_relaxed(const uint4* p) {
  uint64_t a, b;
  asm volatile("ld.relaxed.gpu.global.v2.u64 {%0, %1}, [%2];" : "=l"(a), "=l"(b) : "l"(p) : "memory");
  return make_uint4((uint32_t)a, (uint32_t)(a >> 32), (uint32_t)b, (uint32_t)(b >> 32));
}
__device__ __forceinline__ void st_relaxed(uint4* p, float x, float y, uint32_t tag) {
  const uint64_t a = ((uint64_t)tag << 32) | __float_as_uint(x), b = ((uint64_t)tag << 32) | __float_as_uint(y);
  asm volatile("st.relaxed.gpu.global.v2.u64 [%0], {%1, %2};" ::"l"(p), "l"(a), "l"(b) : "memory");
}
__device__ __forceinline__ void tma3d(uint32_t dst, const CUtensorMap* m, int c1, int c2, uint32_t bar) {
  asm volatile("cp.async.bulk.tensor.3d.shared::cluster.global.mbarrier::complete_tx::bytes [%0], [%1, {%3, %4, %5}], [%2];"
               ::"r"(dst), "l"(m), "r"(bar), "r"(0), "r"(c1), "r"(c2) : "memory");
}
#define ACC8(a, v) do { a[0] += bf_lo(v.x); a[1] += bf_hi(v.x); a[2] += bf_lo(v.y); a[3] += bf_hi(v.y); \
                        a[4] += bf_lo(v.z); a[5] += bf_hi(v.z); a[6] += bf_lo(v.w); a[7] += bf_hi(v.w); } while (0)

__device__ __forceinline__ void wgmma_ss_n224(float (&d)[112], uint64_t da, uint64_t db, int sd) {
  asm volatile("{\n.reg .pred p;\nsetp.ne.b32 p, %114, 0;\n"
      "wgmma.mma_async.sync.aligned.m64n224k16.f32.bf16.bf16 {"
      "%0, %1, %2, %3, %4, %5, %6, %7, %8, %9, %10, %11, %12, %13, %14, %15, "
      "%16, %17, %18, %19, %20, %21, %22, %23, %24, %25, %26, %27, %28, %29, %30, %31, "
      "%32, %33, %34, %35, %36, %37, %38, %39, %40, %41, %42, %43, %44, %45, %46, %47, "
      "%48, %49, %50, %51, %52, %53, %54, %55, %56, %57, %58, %59, %60, %61, %62, %63, "
      "%64, %65, %66, %67, %68, %69, %70, %71, %72, %73, %74, %75, %76, %77, %78, %79, "
      "%80, %81, %82, %83, %84, %85, %86, %87, %88, %89, %90, %91, %92, %93, %94, %95, "
      "%96, %97, %98, %99, %100, %101, %102, %103, %104, %105, %106, %107, %108, %109, %110, %111"
      "}, %112, %113, p, 1, 1, 0, 1;\n}\n"
    : "+f"(d[0]), "+f"(d[1]), "+f"(d[2]), "+f"(d[3]), "+f"(d[4]), "+f"(d[5]), "+f"(d[6]), "+f"(d[7]),
      "+f"(d[8]), "+f"(d[9]), "+f"(d[10]), "+f"(d[11]), "+f"(d[12]), "+f"(d[13]), "+f"(d[14]), "+f"(d[15]),
      "+f"(d[16]), "+f"(d[17]), "+f"(d[18]), "+f"(d[19]), "+f"(d[20]), "+f"(d[21]), "+f"(d[22]), "+f"(d[23]),
      "+f"(d[24]), "+f"(d[25]), "+f"(d[26]), "+f"(d[27]), "+f"(d[28]), "+f"(d[29]), "+f"(d[30]), "+f"(d[31]),
      "+f"(d[32]), "+f"(d[33]), "+f"(d[34]), "+f"(d[35]), "+f"(d[36]), "+f"(d[37]), "+f"(d[38]), "+f"(d[39]),
      "+f"(d[40]), "+f"(d[41]), "+f"(d[42]), "+f"(d[43]), "+f"(d[44]), "+f"(d[45]), "+f"(d[46]), "+f"(d[47]),
      "+f"(d[48]), "+f"(d[49]), "+f"(d[50]), "+f"(d[51]), "+f"(d[52]), "+f"(d[53]), "+f"(d[54]), "+f"(d[55]),
      "+f"(d[56]), "+f"(d[57]), "+f"(d[58]), "+f"(d[59]), "+f"(d[60]), "+f"(d[61]), "+f"(d[62]), "+f"(d[63]),
      "+f"(d[64]), "+f"(d[65]), "+f"(d[66]), "+f"(d[67]), "+f"(d[68]), "+f"(d[69]), "+f"(d[70]), "+f"(d[71]),
      "+f"(d[72]), "+f"(d[73]), "+f"(d[74]), "+f"(d[75]), "+f"(d[76]), "+f"(d[77]), "+f"(d[78]), "+f"(d[79]),
      "+f"(d[80]), "+f"(d[81]), "+f"(d[82]), "+f"(d[83]), "+f"(d[84]), "+f"(d[85]), "+f"(d[86]), "+f"(d[87]),
      "+f"(d[88]), "+f"(d[89]), "+f"(d[90]), "+f"(d[91]), "+f"(d[92]), "+f"(d[93]), "+f"(d[94]), "+f"(d[95]),
      "+f"(d[96]), "+f"(d[97]), "+f"(d[98]), "+f"(d[99]), "+f"(d[100]), "+f"(d[101]), "+f"(d[102]), "+f"(d[103]),
      "+f"(d[104]), "+f"(d[105]), "+f"(d[106]), "+f"(d[107]), "+f"(d[108]), "+f"(d[109]), "+f"(d[110]), "+f"(d[111])
    : "l"(da), "l"(db), "r"(sd));
}
__device__ __forceinline__ void wgmma_ss_n208(float (&d)[104], uint64_t da, uint64_t db, int sd) {
  asm volatile("{\n.reg .pred p;\nsetp.ne.b32 p, %106, 0;\n"
      "wgmma.mma_async.sync.aligned.m64n208k16.f32.bf16.bf16 {"
      "%0, %1, %2, %3, %4, %5, %6, %7, %8, %9, %10, %11, %12, %13, %14, %15, "
      "%16, %17, %18, %19, %20, %21, %22, %23, %24, %25, %26, %27, %28, %29, %30, %31, "
      "%32, %33, %34, %35, %36, %37, %38, %39, %40, %41, %42, %43, %44, %45, %46, %47, "
      "%48, %49, %50, %51, %52, %53, %54, %55, %56, %57, %58, %59, %60, %61, %62, %63, "
      "%64, %65, %66, %67, %68, %69, %70, %71, %72, %73, %74, %75, %76, %77, %78, %79, "
      "%80, %81, %82, %83, %84, %85, %86, %87, %88, %89, %90, %91, %92, %93, %94, %95, "
      "%96, %97, %98, %99, %100, %101, %102, %103"
      "}, %104, %105, p, 1, 1, 0, 1;\n}\n"
    : "+f"(d[0]), "+f"(d[1]), "+f"(d[2]), "+f"(d[3]), "+f"(d[4]), "+f"(d[5]), "+f"(d[6]), "+f"(d[7]),
      "+f"(d[8]), "+f"(d[9]), "+f"(d[10]), "+f"(d[11]), "+f"(d[12]), "+f"(d[13]), "+f"(d[14]), "+f"(d[15]),
      "+f"(d[16]), "+f"(d[17]), "+f"(d[18]), "+f"(d[19]), "+f"(d[20]), "+f"(d[21]), "+f"(d[22]), "+f"(d[23]),
      "+f"(d[24]), "+f"(d[25]), "+f"(d[26]), "+f"(d[27]), "+f"(d[28]), "+f"(d[29]), "+f"(d[30]), "+f"(d[31]),
      "+f"(d[32]), "+f"(d[33]), "+f"(d[34]), "+f"(d[35]), "+f"(d[36]), "+f"(d[37]), "+f"(d[38]), "+f"(d[39]),
      "+f"(d[40]), "+f"(d[41]), "+f"(d[42]), "+f"(d[43]), "+f"(d[44]), "+f"(d[45]), "+f"(d[46]), "+f"(d[47]),
      "+f"(d[48]), "+f"(d[49]), "+f"(d[50]), "+f"(d[51]), "+f"(d[52]), "+f"(d[53]), "+f"(d[54]), "+f"(d[55]),
      "+f"(d[56]), "+f"(d[57]), "+f"(d[58]), "+f"(d[59]), "+f"(d[60]), "+f"(d[61]), "+f"(d[62]), "+f"(d[63]),
      "+f"(d[64]), "+f"(d[65]), "+f"(d[66]), "+f"(d[67]), "+f"(d[68]), "+f"(d[69]), "+f"(d[70]), "+f"(d[71]),
      "+f"(d[72]), "+f"(d[73]), "+f"(d[74]), "+f"(d[75]), "+f"(d[76]), "+f"(d[77]), "+f"(d[78]), "+f"(d[79]),
      "+f"(d[80]), "+f"(d[81]), "+f"(d[82]), "+f"(d[83]), "+f"(d[84]), "+f"(d[85]), "+f"(d[86]), "+f"(d[87]),
      "+f"(d[88]), "+f"(d[89]), "+f"(d[90]), "+f"(d[91]), "+f"(d[92]), "+f"(d[93]), "+f"(d[94]), "+f"(d[95]),
      "+f"(d[96]), "+f"(d[97]), "+f"(d[98]), "+f"(d[99]), "+f"(d[100]), "+f"(d[101]), "+f"(d[102]), "+f"(d[103])
    : "l"(da), "l"(db), "r"(sd));
}
__device__ __forceinline__ void wgmma_ss_n168(float (&d)[84], uint64_t da, uint64_t db, int sd) {
  asm volatile("{\n.reg .pred p;\nsetp.ne.b32 p, %86, 0;\n"
      "wgmma.mma_async.sync.aligned.m64n168k16.f32.bf16.bf16 {"
      "%0, %1, %2, %3, %4, %5, %6, %7, %8, %9, %10, %11, %12, %13, %14, %15, "
      "%16, %17, %18, %19, %20, %21, %22, %23, %24, %25, %26, %27, %28, %29, %30, %31, "
      "%32, %33, %34, %35, %36, %37, %38, %39, %40, %41, %42, %43, %44, %45, %46, %47, "
      "%48, %49, %50, %51, %52, %53, %54, %55, %56, %57, %58, %59, %60, %61, %62, %63, "
      "%64, %65, %66, %67, %68, %69, %70, %71, %72, %73, %74, %75, %76, %77, %78, %79, "
      "%80, %81, %82, %83"
      "}, %84, %85, p, 1, 1, 0, 1;\n}\n"
    : "+f"(d[0]), "+f"(d[1]), "+f"(d[2]), "+f"(d[3]), "+f"(d[4]), "+f"(d[5]), "+f"(d[6]), "+f"(d[7]),
      "+f"(d[8]), "+f"(d[9]), "+f"(d[10]), "+f"(d[11]), "+f"(d[12]), "+f"(d[13]), "+f"(d[14]), "+f"(d[15]),
      "+f"(d[16]), "+f"(d[17]), "+f"(d[18]), "+f"(d[19]), "+f"(d[20]), "+f"(d[21]), "+f"(d[22]), "+f"(d[23]),
      "+f"(d[24]), "+f"(d[25]), "+f"(d[26]), "+f"(d[27]), "+f"(d[28]), "+f"(d[29]), "+f"(d[30]), "+f"(d[31]),
      "+f"(d[32]), "+f"(d[33]), "+f"(d[34]), "+f"(d[35]), "+f"(d[36]), "+f"(d[37]), "+f"(d[38]), "+f"(d[39]),
      "+f"(d[40]), "+f"(d[41]), "+f"(d[42]), "+f"(d[43]), "+f"(d[44]), "+f"(d[45]), "+f"(d[46]), "+f"(d[47]),
      "+f"(d[48]), "+f"(d[49]), "+f"(d[50]), "+f"(d[51]), "+f"(d[52]), "+f"(d[53]), "+f"(d[54]), "+f"(d[55]),
      "+f"(d[56]), "+f"(d[57]), "+f"(d[58]), "+f"(d[59]), "+f"(d[60]), "+f"(d[61]), "+f"(d[62]), "+f"(d[63]),
      "+f"(d[64]), "+f"(d[65]), "+f"(d[66]), "+f"(d[67]), "+f"(d[68]), "+f"(d[69]), "+f"(d[70]), "+f"(d[71]),
      "+f"(d[72]), "+f"(d[73]), "+f"(d[74]), "+f"(d[75]), "+f"(d[76]), "+f"(d[77]), "+f"(d[78]), "+f"(d[79]),
      "+f"(d[80]), "+f"(d[81]), "+f"(d[82]), "+f"(d[83])
    : "l"(da), "l"(db), "r"(sd));
}
__device__ __forceinline__ void wgmma_ss_n160(float (&d)[80], uint64_t da, uint64_t db, int sd) {
  asm volatile("{\n.reg .pred p;\nsetp.ne.b32 p, %82, 0;\n"
      "wgmma.mma_async.sync.aligned.m64n160k16.f32.bf16.bf16 {"
      "%0, %1, %2, %3, %4, %5, %6, %7, %8, %9, %10, %11, %12, %13, %14, %15, "
      "%16, %17, %18, %19, %20, %21, %22, %23, %24, %25, %26, %27, %28, %29, %30, %31, "
      "%32, %33, %34, %35, %36, %37, %38, %39, %40, %41, %42, %43, %44, %45, %46, %47, "
      "%48, %49, %50, %51, %52, %53, %54, %55, %56, %57, %58, %59, %60, %61, %62, %63, "
      "%64, %65, %66, %67, %68, %69, %70, %71, %72, %73, %74, %75, %76, %77, %78, %79"
      "}, %80, %81, p, 1, 1, 0, 1;\n}\n"
    : "+f"(d[0]), "+f"(d[1]), "+f"(d[2]), "+f"(d[3]), "+f"(d[4]), "+f"(d[5]), "+f"(d[6]), "+f"(d[7]),
      "+f"(d[8]), "+f"(d[9]), "+f"(d[10]), "+f"(d[11]), "+f"(d[12]), "+f"(d[13]), "+f"(d[14]), "+f"(d[15]),
      "+f"(d[16]), "+f"(d[17]), "+f"(d[18]), "+f"(d[19]), "+f"(d[20]), "+f"(d[21]), "+f"(d[22]), "+f"(d[23]),
      "+f"(d[24]), "+f"(d[25]), "+f"(d[26]), "+f"(d[27]), "+f"(d[28]), "+f"(d[29]), "+f"(d[30]), "+f"(d[31]),
      "+f"(d[32]), "+f"(d[33]), "+f"(d[34]), "+f"(d[35]), "+f"(d[36]), "+f"(d[37]), "+f"(d[38]), "+f"(d[39]),
      "+f"(d[40]), "+f"(d[41]), "+f"(d[42]), "+f"(d[43]), "+f"(d[44]), "+f"(d[45]), "+f"(d[46]), "+f"(d[47]),
      "+f"(d[48]), "+f"(d[49]), "+f"(d[50]), "+f"(d[51]), "+f"(d[52]), "+f"(d[53]), "+f"(d[54]), "+f"(d[55]),
      "+f"(d[56]), "+f"(d[57]), "+f"(d[58]), "+f"(d[59]), "+f"(d[60]), "+f"(d[61]), "+f"(d[62]), "+f"(d[63]),
      "+f"(d[64]), "+f"(d[65]), "+f"(d[66]), "+f"(d[67]), "+f"(d[68]), "+f"(d[69]), "+f"(d[70]), "+f"(d[71]),
      "+f"(d[72]), "+f"(d[73]), "+f"(d[74]), "+f"(d[75]), "+f"(d[76]), "+f"(d[77]), "+f"(d[78]), "+f"(d[79])
    : "l"(da), "l"(db), "r"(sd));
}
__device__ __forceinline__ void wgmma_ss_n88(float (&d)[44], uint64_t da, uint64_t db, int sd) {
  asm volatile("{\n.reg .pred p;\nsetp.ne.b32 p, %46, 0;\n"
      "wgmma.mma_async.sync.aligned.m64n88k16.f32.bf16.bf16 {"
      "%0, %1, %2, %3, %4, %5, %6, %7, %8, %9, %10, %11, %12, %13, %14, %15, "
      "%16, %17, %18, %19, %20, %21, %22, %23, %24, %25, %26, %27, %28, %29, %30, %31, "
      "%32, %33, %34, %35, %36, %37, %38, %39, %40, %41, %42, %43"
      "}, %44, %45, p, 1, 1, 0, 1;\n}\n"
    : "+f"(d[0]), "+f"(d[1]), "+f"(d[2]), "+f"(d[3]), "+f"(d[4]), "+f"(d[5]), "+f"(d[6]), "+f"(d[7]),
      "+f"(d[8]), "+f"(d[9]), "+f"(d[10]), "+f"(d[11]), "+f"(d[12]), "+f"(d[13]), "+f"(d[14]), "+f"(d[15]),
      "+f"(d[16]), "+f"(d[17]), "+f"(d[18]), "+f"(d[19]), "+f"(d[20]), "+f"(d[21]), "+f"(d[22]), "+f"(d[23]),
      "+f"(d[24]), "+f"(d[25]), "+f"(d[26]), "+f"(d[27]), "+f"(d[28]), "+f"(d[29]), "+f"(d[30]), "+f"(d[31]),
      "+f"(d[32]), "+f"(d[33]), "+f"(d[34]), "+f"(d[35]), "+f"(d[36]), "+f"(d[37]), "+f"(d[38]), "+f"(d[39]),
      "+f"(d[40]), "+f"(d[41]), "+f"(d[42]), "+f"(d[43])
    : "l"(da), "l"(db), "r"(sd));
}
__device__ __forceinline__ void wgmma_ss_n80(float (&d)[40], uint64_t da, uint64_t db, int sd) {
  asm volatile("{\n.reg .pred p;\nsetp.ne.b32 p, %42, 0;\n"
      "wgmma.mma_async.sync.aligned.m64n80k16.f32.bf16.bf16 {"
      "%0, %1, %2, %3, %4, %5, %6, %7, %8, %9, %10, %11, %12, %13, %14, %15, "
      "%16, %17, %18, %19, %20, %21, %22, %23, %24, %25, %26, %27, %28, %29, %30, %31, "
      "%32, %33, %34, %35, %36, %37, %38, %39"
      "}, %40, %41, p, 1, 1, 0, 1;\n}\n"
    : "+f"(d[0]), "+f"(d[1]), "+f"(d[2]), "+f"(d[3]), "+f"(d[4]), "+f"(d[5]), "+f"(d[6]), "+f"(d[7]),
      "+f"(d[8]), "+f"(d[9]), "+f"(d[10]), "+f"(d[11]), "+f"(d[12]), "+f"(d[13]), "+f"(d[14]), "+f"(d[15]),
      "+f"(d[16]), "+f"(d[17]), "+f"(d[18]), "+f"(d[19]), "+f"(d[20]), "+f"(d[21]), "+f"(d[22]), "+f"(d[23]),
      "+f"(d[24]), "+f"(d[25]), "+f"(d[26]), "+f"(d[27]), "+f"(d[28]), "+f"(d[29]), "+f"(d[30]), "+f"(d[31]),
      "+f"(d[32]), "+f"(d[33]), "+f"(d[34]), "+f"(d[35]), "+f"(d[36]), "+f"(d[37]), "+f"(d[38]), "+f"(d[39])
    : "l"(da), "l"(db), "r"(sd));
}
__device__ __forceinline__ void wgmma_rs_n128(float (&d)[64], uint32_t a0, uint32_t a1, uint32_t a2, uint32_t a3,
                                  uint64_t db, int sd) {
  asm volatile("{\n.reg .pred p;\nsetp.ne.b32 p, %69, 0;\n"
      "wgmma.mma_async.sync.aligned.m64n128k16.f32.bf16.bf16 {"
      "%0, %1, %2, %3, %4, %5, %6, %7, %8, %9, %10, %11, %12, %13, %14, %15, "
      "%16, %17, %18, %19, %20, %21, %22, %23, %24, %25, %26, %27, %28, %29, %30, %31, "
      "%32, %33, %34, %35, %36, %37, %38, %39, %40, %41, %42, %43, %44, %45, %46, %47, "
      "%48, %49, %50, %51, %52, %53, %54, %55, %56, %57, %58, %59, %60, %61, %62, %63"
      "}, {%64, %65, %66, %67}, %68, p, 1, 1, 0;\n}\n"
    : "+f"(d[0]), "+f"(d[1]), "+f"(d[2]), "+f"(d[3]), "+f"(d[4]), "+f"(d[5]), "+f"(d[6]), "+f"(d[7]),
      "+f"(d[8]), "+f"(d[9]), "+f"(d[10]), "+f"(d[11]), "+f"(d[12]), "+f"(d[13]), "+f"(d[14]), "+f"(d[15]),
      "+f"(d[16]), "+f"(d[17]), "+f"(d[18]), "+f"(d[19]), "+f"(d[20]), "+f"(d[21]), "+f"(d[22]), "+f"(d[23]),
      "+f"(d[24]), "+f"(d[25]), "+f"(d[26]), "+f"(d[27]), "+f"(d[28]), "+f"(d[29]), "+f"(d[30]), "+f"(d[31]),
      "+f"(d[32]), "+f"(d[33]), "+f"(d[34]), "+f"(d[35]), "+f"(d[36]), "+f"(d[37]), "+f"(d[38]), "+f"(d[39]),
      "+f"(d[40]), "+f"(d[41]), "+f"(d[42]), "+f"(d[43]), "+f"(d[44]), "+f"(d[45]), "+f"(d[46]), "+f"(d[47]),
      "+f"(d[48]), "+f"(d[49]), "+f"(d[50]), "+f"(d[51]), "+f"(d[52]), "+f"(d[53]), "+f"(d[54]), "+f"(d[55]),
      "+f"(d[56]), "+f"(d[57]), "+f"(d[58]), "+f"(d[59]), "+f"(d[60]), "+f"(d[61]), "+f"(d[62]), "+f"(d[63])
    : "r"(a0), "r"(a1), "r"(a2), "r"(a3), "l"(db), "r"(sd));
}
__device__ __forceinline__ void wgmma_rs_n24(float (&d)[12], uint32_t a0, uint32_t a1, uint32_t a2, uint32_t a3,
                                  uint64_t db, int sd) {
  asm volatile("{\n.reg .pred p;\nsetp.ne.b32 p, %17, 0;\n"
      "wgmma.mma_async.sync.aligned.m64n24k16.f32.bf16.bf16 {"
      "%0, %1, %2, %3, %4, %5, %6, %7, %8, %9, %10, %11"
      "}, {%12, %13, %14, %15}, %16, p, 1, 1, 1;\n}\n"
    : "+f"(d[0]), "+f"(d[1]), "+f"(d[2]), "+f"(d[3]), "+f"(d[4]), "+f"(d[5]), "+f"(d[6]), "+f"(d[7]),
      "+f"(d[8]), "+f"(d[9]), "+f"(d[10]), "+f"(d[11])
    : "r"(a0), "r"(a1), "r"(a2), "r"(a3), "l"(db), "r"(sd));
}

#define KST 4
#define K1_EC 6
#define K1S 4
constexpr int K1_ST = K1S, K1_STAGE = 45056;
constexpr int K1_SMEM = K1_ST * K1_STAGE + 640   + 1536   + 2560   + 128;

__device__ __forceinline__ float2 row_stats(uint4 v0, uint4 v1, uint4 v2) {
  const uint32_t wd[12] = {v0.x, v0.y, v0.z, v0.w, v1.x, v1.y, v1.z, v1.w, v2.x, v2.y, v2.z, v2.w};
  float sx = 0.f, sq = 0.f;
#pragma unroll
  for (int e = 0; e < 12; e++) {
    const float lo = bf_lo(wd[e]), hi = bf_hi(wd[e]);
    sx += lo + hi; sq = fmaf(lo, lo, fmaf(hi, hi, sq));
  }
#pragma unroll
  for (int o = 16; o; o >>= 1) { sx += __shfl_xor_sync(~0u, sx, o); sq += __shfl_xor_sync(~0u, sq, o); }
  const float mean = sx * (1.f / D_);
  return make_float2(rsqrtf(fmaxf(sq * (1.f / D_) - mean * mean, 0.f) + 1e-5f), mean);
}

__global__ void __cluster_dims__(2, 1, 1) __launch_bounds__(512, 1)
k1_qkv(const __grid_constant__ CUtensorMap tmx, const __grid_constant__ CUtensorMap tmw,
       const bf16* __restrict__ x, const bf16* __restrict__ w, const bf16* __restrict__ wo) {
  extern __shared__ __align__(1024) uint8_t sm[];
  float* cs = (float*)(sm + K1_ST * K1_STAGE);
  float2* rowab = (float2*)(sm + K1_ST * K1_STAGE + 640);
  float* red = (float*)(sm + K1_ST * K1_STAGE + 2176);
  const uint32_t sbase = smem_u32(sm);
  const uint32_t fullb = sbase + K1_ST * K1_STAGE + 4736, emptyb = fullb + 8 * K1_ST;
  const int tid = threadIdx.x, lane = tid & 31;
  const int warp = __shfl_sync(~0u, tid >> 5, 0);
  const int rank = blockIdx.x & 1, cl = blockIdx.x >> 1;
  const int m = cl / 6, n = (cl - m * 6) * 2 + rank;
  if (tid == 0) STAMP(0, 0);

  if (warp == 12) {
    if (lane == 0) {
      prefetch_map(&tmx); prefetch_map(&tmw);
      for (int i = 0; i < K1_ST; i++) { mbar_init(fullb + 8 * i, 1); mbar_init(emptyb + 8 * i, K1_EC); }
      asm volatile("fence.mbarrier_init.release.cluster;" ::: "memory");
    }
    __syncwarp();
    cluster_arrive();
    bar_arrive(4, 512);
    if (lane == 0) {
      for (int kt = 0; kt < K1_ST; kt++) mbar_expect(fullb + 8 * kt, K1_STAGE);
#pragma unroll
      for (int j = 0; j < 5; j++) tma2d(sbase + 24576 + j * 4096, &tmw, n * 160 + j * 32, 0, fullb);
    }
    __syncwarp();
    cluster_wait();
    if (lane == 0) {
#pragma unroll 1
      for (int kt = 0; kt < 10; kt++) {
        const int s = kt % K1_ST;
        const uint32_t sa = sbase + s * K1_STAGE;
        if (kt >= K1_ST) {
          mbar_wait(emptyb + 8 * s, ((kt / K1_ST) - 1) & 1);
          mbar_expect(fullb + 8 * s, K1_STAGE);
        }
        tma2d_mc(sa + rank * 12288, &tmx, kt * 64, m * 192 + rank * 96, fullb + 8 * s);
        if (kt > 0) {
#pragma unroll
          for (int j = 0; j < 5; j++) tma2d(sa + 24576 + j * 4096, &tmw, n * 160 + j * 32, kt * 64, fullb + 8 * s);
        }
        if (kt == K1_ST - 1) {
          if (m * 192 + n * 16 < S_)
            asm volatile("cp.async.bulk.prefetch.L2.global [%0], %1;" ::"l"(x + (size_t)(m * 192 + n * 16) * D_), "r"(16 * D_ * 2) : "memory");
          if (m >= K1_ST && m < 10) {
#pragma unroll
            for (int j = 0; j < 5; j++)
              asm volatile("cp.async.bulk.prefetch.tensor.2d.L2.global [%0, {%1, %2}];" ::"l"(&tmw), "r"(n * 160 + j * 32), "r"(m * 64) : "memory");
          }
          pdl_trigger();
        }
      }
    }
    __syncwarp();
    cluster_arrive();
  } else if (warp > 12) {
    cluster_arrive();
    const int t96 = tid - 416;
    const uint32_t tag = __ldcg(&g_epoch) + 1;
    bar_sync(4, 512);
    mbar_wait(fullb, 0);
    if (m < 10) {
      const int ck = t96 % 20, rg = min(t96 / 20, 3);
      uint4 wv[16];
#pragma unroll
      for (int i = 0; i < 16; i++) wv[i] = ldg_nc(w + (size_t)(m * 64 + rg * 16 + i) * 1920 + n * 160 + ck * 8);
      float acc8[8];
#pragma unroll
      for (int i = 0; i < 8; i++) acc8[i] = 0.f;
#pragma unroll
      for (int i = 0; i < 16; i++) ACC8(acc8, wv[i]);
      *(float4*)&red[rg * 160 + ck * 8] = make_float4(acc8[0], acc8[1], acc8[2], acc8[3]);
      *(float4*)&red[rg * 160 + ck * 8 + 4] = make_float4(acc8[4], acc8[5], acc8[6], acc8[7]);
      bar_sync(1, 96);
      if (t96 < 80) {
        const float2 p0 = *(const float2*)&red[t96 * 2], p1 = *(const float2*)&red[160 + t96 * 2];
        const float2 p2 = *(const float2*)&red[320 + t96 * 2], p3 = *(const float2*)&red[480 + t96 * 2];
        st_relaxed(&g_cpart[(m * 12 + n) * 80 + t96], (p0.x + p1.x) + (p2.x + p3.x), (p0.y + p1.y) + (p2.y + p3.y), tag);
      }
    }
    if (tid == 416) STAMP(5, 7);
    bool ok = false;
    for (int it = 0; it < 64 && !ok; it++) {
      uint4 p[10], st[2];
#pragma unroll
      for (int k = 0; k < 10; k++) p[k] = ld_relaxed(&g_cpart[(k * 12 + n) * 80 + min(t96, 79)]);
#pragma unroll
      for (int k = 0; k < 2; k++) st[k] = ld_relaxed(&g_rowstat[min(m * 192 + k * 96 + t96, S_ - 1)]);
      ok = true;
      float s0 = 0.f, s1 = 0.f;
#pragma unroll
      for (int k = 0; k < 10; k++) {
        ok = ok && p[k].y == tag && p[k].w == tag;
        s0 += __uint_as_float(p[k].x); s1 += __uint_as_float(p[k].z);
      }
      if (t96 < 80) *(float2*)&cs[t96 * 2] = make_float2(s0, s1);
#pragma unroll
      for (int k = 0; k < 2; k++) {
        ok = ok && st[k].y == tag && st[k].w == tag;
        rowab[k * 96 + t96] = make_float2(__uint_as_float(st[k].x), -__uint_as_float(st[k].x) * __uint_as_float(st[k].z));
      }
      ok = __all_sync(~0u, ok);
      if (!ok) __nanosleep(300);
    }
    if (!ok) {
      const int c2 = min(t96, 79);
      float s0 = 0.f, s1 = 0.f;
#pragma unroll 1
      for (int k = 0; k < D_; k++) {
        const uint32_t v = *(const uint32_t*)(w + (size_t)k * 1920 + n * 160 + c2 * 2);
        s0 += bf_lo(v); s1 += bf_hi(v);
      }
      if (t96 < 80) *(float2*)&cs[t96 * 2] = make_float2(s0, s1);
#pragma unroll 1
      for (int i = 0; i < 64; i++) {
        const int r = (i >> 5) * 96 + (t96 & ~31) + (i & 31);
        const bf16* xr = x + (size_t)min(m * 192 + r, S_ - 1) * D_ + lane * 8;
        const float2 st = row_stats(ldg_nc(xr), ldg_nc(xr + 256), lane < 16 ? ldg_nc(xr + 512) : make_uint4(0u, 0u, 0u, 0u));
        if (lane == 0) rowab[r] = make_float2(st.x, -st.x * st.y);
      }
    }
    __syncwarp();
    bar_arrive(2, 96 + 384);
    bar_sync(1, 96);
    if (tid == 416) STAMP(0, 5);
    if (blockIdx.x < 128) {
      uint4 v[5];
      const int ck = min(t96, 79), nt = ck / 10;
#pragma unroll
      for (int i = 0; i < 5; i++) {
        const int k = blockIdx.x * 5 + i, pr = k / 40, r = k - pr * 40;
        v[i] = ldg_nc(wo + (size_t)(pr * 40 + (r < 16 ? r : (r < 32 ? r + 4 : (r < 36 ? r - 16 : r)))) * D_ + ck * 8);
      }
#pragma unroll
      for (int i = 0; i < 5; i++) {
        const int k = blockIdx.x * 5 + i;
        g_wo[((nt * 10 + (k >> 6)) * 10 + ck - nt * 10) * 64 + (k & 63)] = v[i];
        float t = ((bf_lo(v[i].x) + bf_hi(v[i].x)) + (bf_lo(v[i].y) + bf_hi(v[i].y))) +
                  ((bf_lo(v[i].z) + bf_hi(v[i].z)) + (bf_lo(v[i].w) + bf_hi(v[i].w)));
        if (t96 >= 80) t = 0.f;
#pragma unroll
        for (int o = 16; o; o >>= 1) t += __shfl_xor_sync(~0u, t, o);
        if (lane == 0) red[(t96 >> 5) * 8 + i] = t;
      }
      bar_sync(1, 96);
      if (t96 < 5) {
        const float mu = (red[t96] + red[8 + t96] + red[16 + t96]) * (1.f / D_);
        const float hi = bf_lo(pack_bf16(mu, 0.f));
        g_wm[blockIdx.x * 5 + t96] = make_uint4(pack_bf16(hi, mu - hi), 0u, 0u, 0u);
      }
    }
    if (tid == 416) STAMP(0, 7);
    __syncwarp();
    cluster_wait();
    cluster_arrive();
  } else {
    cluster_arrive();
    float acc[80];
    const uint64_t da0 = mkdesc(sbase + (warp >> 2) * 8192, 16, 1024, 1);
    const uint64_t db0 = mkdesc(sbase + 24576, 4096, 512, 2);
    const uint32_t tag = __ldcg(&g_epoch) + 1;
    const int srow = m * 192 + n * 16 + warp * 2;
    const bool dostat = warp < 8 && srow < S_;
    uint4 xv[2][3];
    bar_sync(4, 512);
    cluster_wait();
#pragma unroll
    for (int kt = 0; kt < 10; kt++) {
      const int s = kt % K1_ST;
      mbar_wait(fullb + 8 * s, (kt / K1_ST) & 1);
      if (kt == 0 && tid == 0) STAMP(0, 1);
      if (kt == 2 && tid == 0) STAMP(5, 0);
      if (kt == 4 && tid == 0) STAMP(5, 1);
      if (kt == 7 && tid == 0) STAMP(5, 2);
      const uint64_t da = da0 + s * (K1_STAGE >> 4), db = db0 + s * (K1_STAGE >> 4);
      WG_FENCE();
#pragma unroll
      for (int k = 0; k < 4; k++) wgmma_ss_n160(acc, da + k * 2, db + k * 64, (kt | k) != 0);
      WG_COMMIT();
      if (kt > 0) {
        WG_WAIT(1);
        if (kt - 1 + K1_ST < 10 && (tid & 127) < 2) mbar_arrive_cta(emptyb + 8 * ((kt - 1) % K1_ST), tid & 1);
      }
      if (kt == 0) {
#pragma unroll
        for (int i = 0; i < 2; i++) {
          const bf16* xr = x + (size_t)min(srow + i, S_ - 1) * D_ + lane * 8;
          xv[i][0] = xv[i][1] = xv[i][2] = make_uint4(0u, 0u, 0u, 0u);
          if (dostat) { xv[i][0] = ldg_nc(xr); xv[i][1] = ldg_nc(xr + 256); }
          if (dostat && lane < 16) xv[i][2] = ldg_nc(xr + 512);
        }
      }
      if ((kt == KST || kt == KST + 1) && dostat) {
        const float2 st = row_stats(xv[kt - KST][0], xv[kt - KST][1], xv[kt - KST][2]);
        if (lane == 0) st_relaxed(&g_rowstat[srow + kt - KST], st.x, st.y, tag);
      }
      __syncwarp();
    }
    cluster_arrive();
    WG_WAIT(0);
    fence_regs(acc);
    if (tid == 0) STAMP(0, 2);
    bar_sync(2, 96 + 384);
    if (tid == 0) STAMP(0, 3);
    const int row0 = m * 192 + warp * 16;
    if (row0 < S_) {
      const int g = lane >> 2, c = lane & 3, sec = n >> 2, grp = (row0 & 127) >> 3;
      const bool lo = c < 2;
      const float2 ab0 = rowab[warp * 16 + g], ab1 = rowab[warp * 16 + g + 8];
      const bool p0 = sec == 1 && ((POLY_MASK >> grp) & 1), p1 = sec == 1 && ((POLY_MASK >> (grp + 1)) & 1);
      const uint32_t padqv = sec == 0 ? (c == 2 ? 0x3F803F80u : 0x00003F80u) : (sec == 2 && c == 2 ? 0x00003F80u : 0u);
      const uint32_t padk = c == 2 ? 0x4A7A4B00u : 0x00004653u;
      const uint32_t pad0 = p0 ? padk : padqv, pad1 = p1 ? padk : padqv;
      const float f0 = sec == 0 ? QSCALE : (p0 ? 32768.f : 1.f), f1 = sec == 0 ? QSCALE : (p1 ? 32768.f : 1.f);
      const float a0 = ab0.x * f0, b0 = ab0.y * f0, a1 = ab1.x * f1, b1 = ab1.y * f1;
      const float r0 = p0 ? 9.313225746154785e-10f : 1.f, r1 = p1 ? 9.313225746154785e-10f : 1.f;
      const int cst = sec == 1 ? 2048 : 128, gst = sec == 1 ? 128 : 384;
      uint8_t* pe = (uint8_t*)g_qkv + (size_t)(n * 8) * HEAD_IMG + (row0 >> 7) * 6144 + grp * gst + lane * 4;
      uint8_t* pe1 = pe + cst;
      uint8_t* pe2 = pe1 + cst;
      uint8_t* pf = pe + gst;
      uint8_t* pf1 = pf + cst;
      uint8_t* pf2 = pf1 + cst;
#pragma unroll
      for (int hp = 0; hp < 4; hp++) {
        uint32_t u[5], v[5];
        float su[5], sv[5];
#pragma unroll
        for (int i = 0; i < 5; i++) {
          const int j = hp * 5 + i;
          const float2 t = *(const float2*)&cs[j * 8 + c * 2];
          const float x0 = fmaf(acc[4 * j], a0, b0 * t.x), x1 = fmaf(acc[4 * j + 1], a0, b0 * t.y);
          const float y0 = fmaf(acc[4 * j + 2], a1, b1 * t.x), y1 = fmaf(acc[4 * j + 3], a1, b1 * t.y);
          u[i] = pack_bf16(x0, x1); v[i] = pack_bf16(y0, y1);
          su[i] = fmaf(x0, x0, x1 * x1); sv[i] = fmaf(y0, y0, y1 * y1);
        }
        constexpr int HE = HEAD_IMG;
        const int oe = hp * 2 * HE, oo = oe + HE;
        *(uint32_t*)(pe + oe) = u[0];  *(uint32_t*)(pf + oe) = v[0];
        *(uint32_t*)(pe1 + oe) = u[1]; *(uint32_t*)(pf1 + oe) = v[1];
        *(uint32_t*)(pe2 + oe) = lo ? u[2] : pad0; *(uint32_t*)(pf2 + oe) = lo ? v[2] : pad1;
        *(uint32_t*)(pe + oo) = __shfl_xor_sync(~0u, lo ? u[3] : u[2], 2);
        *(uint32_t*)(pf + oo) = __shfl_xor_sync(~0u, lo ? v[3] : v[2], 2);
        *(uint32_t*)(pe1 + oo) = __shfl_xor_sync(~0u, lo ? u[4] : u[3], 2);
        *(uint32_t*)(pf1 + oo) = __shfl_xor_sync(~0u, lo ? v[4] : v[3], 2);
        const uint32_t tu = __shfl_xor_sync(~0u, u[4], 2), tv = __shfl_xor_sync(~0u, v[4], 2);
        *(uint32_t*)(pe2 + oo) = lo ? tu : pad0; *(uint32_t*)(pf2 + oo) = lo ? tv : pad1;
        if (sec < 2) {
          float e0 = (su[0] + su[1] + (lo ? su[2] : 0.f)) * r0, e1 = (sv[0] + sv[1] + (lo ? sv[2] : 0.f)) * r1;
          float o0 = (su[3] + su[4] + (lo ? 0.f : su[2])) * r0, o1 = (sv[3] + sv[4] + (lo ? 0.f : sv[2])) * r1;
          e0 += __shfl_xor_sync(~0u, e0, 1); e1 += __shfl_xor_sync(~0u, e1, 1);
          o0 += __shfl_xor_sync(~0u, o0, 1); o1 += __shfl_xor_sync(~0u, o1, 1);
          e0 += __shfl_xor_sync(~0u, e0, 2); e1 += __shfl_xor_sync(~0u, e1, 2);
          o0 += __shfl_xor_sync(~0u, o0, 2); o1 += __shfl_xor_sync(~0u, o1, 2);
          const uint32_t em = __reduce_max_sync(~0u, max(__float_as_uint(e0), __float_as_uint(e1)));
          const uint32_t om = __reduce_max_sync(~0u, max(__float_as_uint(o0), __float_as_uint(o1)));
          if (lane < 2) g_nrm[(n * 8 + hp * 2 + lane) * 128 + (row0 >> 4)] = __uint_as_float(lane ? om : em);
        }
      }
    }
    if (tid == 0) STAMP(0, 4);
  }
  cluster_wait();
  if (tid == 0) STAMP(0, 6);
}

constexpr int K2_SMEM = 2 * HEAD_IMG + 2 * 6144 + 2 * 10240 + 256;

__device__ __forceinline__ uint64_t desc64(uint32_t lo, uint32_t hi) {
  uint64_t d;
  asm("mov.b64 %0, {%1, %2};" : "=l"(d) : "r"(lo), "r"(hi));
  return d;
}
__device__ __forceinline__ uint32_t exp_pair(bool poly, float a, float b, uint32_t mk) {
  if (poly) {
    const uint32_t pk = __byte_perm(__float_as_uint(a), __float_as_uint(b), 0x6521);
    uint32_t m, q;
    asm("lop3.b32 %0, %1, %2, 0x3f803f80, 0xEA;" : "=r"(m) : "r"(pk), "r"(mk));
    asm("fma.rn.bf16x2 %0, %1, %1, %2;" : "=r"(q) : "r"(m), "r"(0x40014001u));
    return pk - m + q;
  }
  return pack_bf16(ex2(a), ex2(b));
}
#define PV_GR 4
__device__ __forceinline__ void exp_pv(const float (&s)[64], float (&o)[12], uint64_t dv, uint32_t mk) {
#pragma unroll
  for (int k0 = 0; k0 < 8; k0 += PV_GR) {
    uint32_t p[4 * PV_GR];
#pragma unroll
    for (int i = 0; i < 4 * PV_GR; i++)
      p[i] = exp_pair((POLY_MASK >> (k0 * 2 + i / 2)) & 1, s[k0 * 8 + 2 * i], s[k0 * 8 + 2 * i + 1], mk);
    WG_FENCE();
#pragma unroll
    for (int k = 0; k < PV_GR; k++)
      wgmma_rs_n24(o, p[4 * k], p[4 * k + 1], p[4 * k + 2], p[4 * k + 3], dv + (k0 + k) * 48, 1);
  }
}
__device__ __forceinline__ void load_q(uint32_t (&q)[6], const uint8_t* p) {
  q[0] = __ldcg((const uint32_t*)p);         q[1] = __ldcg((const uint32_t*)(p + 384));
  q[2] = __ldcg((const uint32_t*)(p + 128)); q[3] = __ldcg((const uint32_t*)(p + 512));
  q[4] = __ldcg((const uint32_t*)(p + 256)); q[5] = __ldcg((const uint32_t*)(p + 640));
}
__device__ __forceinline__ float rcp(float x) {
  float y;
  asm("rcp.approx.ftz.f32 %0, %1;" : "=f"(y) : "f"(x));
  return y;
}
__device__ __forceinline__ int img_off(int chunk) { return (chunk >> 3) * 16384 + (chunk & 7) * 128; }
__device__ __forceinline__ void store_o(const float (&o)[12], int tile) {
  int tid, bid;
  asm volatile("mov.u32 %0, %%tid.x;" : "=r"(tid));
  asm volatile("mov.u32 %0, %%ctaid.x;" : "=r"(bid));
  const int head = bid >> 2;
  uint8_t* dst = (uint8_t*)g_o + ((bid & 3) * 4 + (tile >> 1)) * 163840 + (tile & 1) * 8192 + ((tid >> 5) & 3) * 2048 + (tid & 31) * 4;
  const int oc = (head >> 1) * 5 + (head & 1) * 2;
  const int o0 = img_off(oc), o1 = img_off(oc + 1), o2 = img_off((head >> 1) * 5 + 4) + (head & 1) * 8;
  const float i0 = rcp(__shfl_sync(~0u, o[8], 2, 4)), i1 = rcp(__shfl_sync(~0u, o[10], 2, 4));
  *(uint32_t*)(dst + o0) = pack_bf16(o[0] * i0, o[1] * i0); *(uint32_t*)(dst + o0 + 1024) = pack_bf16(o[2] * i1, o[3] * i1);
  *(uint32_t*)(dst + o1) = pack_bf16(o[4] * i0, o[5] * i0); *(uint32_t*)(dst + o1 + 1024) = pack_bf16(o[6] * i1, o[7] * i1);
  if ((tid & 3) < 2) {
    *(uint32_t*)(dst + o2) = pack_bf16(o[8] * i0, o[9] * i0);
    *(uint32_t*)(dst + o2 + 1024) = pack_bf16(o[10] * i1, o[11] * i1);
  }
}

struct Maps5 { CUtensorMap m[5]; };

__global__ void __launch_bounds__(512, 1)
k2_attn(const __grid_constant__ Maps5 maps, uint32_t mk) {
  const CUtensorMap* tmw = maps.m;
  extern __shared__ __align__(1024) uint8_t sm[];
  const uint32_t sbase = smem_u32(sm);
  float* part = (float*)(sm + 2 * HEAD_IMG);
  const uint32_t rbuf = sbase + 2 * HEAD_IMG + 2 * 6144;
  const uint32_t kvb = rbuf + 2 * 10240;
  const uint32_t partb = kvb + 128, rbar = kvb + 144;
  const int tid = threadIdx.x, lane = tid & 31;
  const int warp = __shfl_sync(~0u, tid >> 5, 0);
  const int head = blockIdx.x >> 2, qb = blockIdx.x & 3;

  if (tid == 0) STAMP(1, 0);
  if (tid == 0) {
    for (int i = 0; i < 16; i++) mbar_init(kvb + 8 * i, 1);
    mbar_init(partb, 128); mbar_init(partb + 8, 128); mbar_init(rbar, 1); mbar_init(rbar + 8, 1);
    asm volatile("fence.mbarrier_init.release.cluster;" ::: "memory");
  }
  __syncthreads();

  if (warp >= 12) {
    asm volatile("setmaxnreg.dec.sync.aligned.u32 32;");
    if (tid == 384) {
      pdl_wait();
      pdl_trigger();
      const uint8_t* kimg = (const uint8_t*)g_qkv + (size_t)(32 + head) * HEAD_IMG;
#pragma unroll 1
      for (int b = 0; b < 16; b++) {
        mbar_expect(kvb + 8 * b, 12288);
        bulk_ld(sbase + b * 6144, kimg + b * 6144, 6144, kvb + 8 * b);
        bulk_ld(sbase + HEAD_IMG + b * 6144, kimg + 32 * HEAD_IMG + b * 6144, 6144, kvb + 8 * b);
        if (b >= 2) mbar_wait(kvb + 8 * (b - 1), 0);

      }
      if (blockIdx.x == 0) g_epoch = g_epoch + 1;
      mbar_wait(kvb + 8 * 15, 0);
      STAMP(1, 2);
      uint8_t* pdst = nullptr;
      uint32_t pbytes = 0;
#pragma unroll 1
      for (int i = 0; i < 8; i++) {
        const int p = blockIdx.x + 128 * i;
        uint8_t* dst = nullptr;
        uint32_t bytes = 0;
        if (i < 7 && p < 856) {
          asm volatile("cp.async.bulk.wait_group.read 0;" ::: "memory");
          const CUtensorMap* tm;
          int c1, c2;
          if (p < 640) {
            const int nt = p / 80, r = p - nt * 80, ph = r / 40, st = (r - ph * 40) >> 1, up = r & 1;
            bytes = ph ? 6656 : 7168;
            dst = (uint8_t*)g_wgu + nt * 552960 + ph * 286720 + (st * 2 + up) * bytes;
            tm = &tmw[ph * 2 + up]; c1 = st * 32; c2 = ph ? 112 + nt * 13 : nt * 14;
          } else {
            const int nk = p - 640, nt = nk / 27;
            bytes = 10240;
            dst = (uint8_t*)g_wd + (size_t)nk * 10240;
            tm = &tmw[4]; c1 = (nk - nt * 27) * 64; c2 = nt * 10;
          }
          mbar_expect(rbar + 8 * (i & 1), bytes);
          tma3d(rbuf + (i & 1) * 10240, tm, c1, c2, rbar + 8 * (i & 1));
        }
        if (pbytes) {
          mbar_wait(rbar + 8 * ((i - 1) & 1), ((i - 1) >> 1) & 1);
          bulk_st(pdst, rbuf + ((i - 1) & 1) * 10240, pbytes);
          asm volatile("cp.async.bulk.commit_group;" ::: "memory");
        }
        pdst = dst; pbytes = bytes;
      }
      asm volatile("cp.async.bulk.wait_group.read 0;" ::: "memory");
      STAMP(1, 6);
    }
  } else {
    asm volatile("setmaxnreg.inc.sync.aligned.u32 160;");
    const int wg = warp >> 2;
    const uint8_t* qthr = (const uint8_t*)g_qkv + (size_t)head * HEAD_IMG + qb * 64 * 384 + (warp & 3) * 768 + lane * 4;
    const uint32_t klo0 = ((sbase & 0x3FFFF) >> 4) | (128u << 16), vlo0 = (((sbase + HEAD_IMG) & 0x3FFFF) >> 4) | (24u << 16);
    constexpr uint64_t KSTEP2 = (uint64_t)(int64_t)(256 - (128 << 16));
    constexpr uint64_t KV2K = 384 - (HEAD_IMG >> 4) + (104 << 16);
    const int nun = wg == 1 ? 4 : 3;
    uint32_t utile = wg == 0 ? 0x210u : (wg == 1 ? 0x4235u : 0x576u);
    uint32_t ubeg = wg == 0 ? 0u : (wg == 1 ? 0x0b00u : 0x600u);
    uint32_t ulen = wg == 0 ? 0x0b1010u : (wg == 1 ? 0x10051006u : 0x0a1010u);
    pdl_wait();
    if (tid == 0) STAMP(1, 1);
    uint32_t q[6];
    load_q(q, qthr + (utile & 15) * 3072);
    bool fast;
    {
      const float4 kn = __ldcg((const float4*)&g_nrm[(32 + head) * 128 + lane * 4]);
      const float qv = __ldcg(&g_nrm[head * 128 + qb * 32 + lane]);
      const uint32_t km = max(max(__float_as_uint(kn.x), __float_as_uint(kn.y)), max(__float_as_uint(kn.z), __float_as_uint(kn.w)));
      const float k2 = __uint_as_float(__reduce_max_sync(~0u, km)), q2 = __uint_as_float(__reduce_max_sync(~0u, __float_as_uint(qv)));
      fast = q2 * k2 <= 3400.f;
    }
    if (fast) {
#pragma unroll 1
      for (int u = 0; u < nun; u++) {
        const uint32_t b0 = ubeg & 15;
        const bool wt = u == 0 || (wg == 1 && u == 1);
        float s[64], o[12];
#pragma unroll
        for (int i = 0; i < 12; i++) o[i] = 0.f;
        uint32_t vlo = vlo0 + b0 * 384, kb = kvb + b0 * 8;
        const uint32_t vend = vlo + ((ulen & 255) - 1) * 384;
        if (wt) mbar_wait(kb, 0);
        if (tid == 0) STAMP(5, 4 + u);
        fence_regs(o);
        WG_FENCE();
        wgmma_rs_n128(s, q[0], q[1], q[2], q[3], desc64(klo0 + b0 * 384, 8), 0);
        wgmma_rs_n128(s, q[4], q[5], 0, 0, desc64(klo0 + b0 * 384, 8) + KSTEP2, 1);
        WG_COMMIT();
#define K2UNR 1
        constexpr int kUnr = K2UNR;
#pragma unroll kUnr
        for (; vlo != vend; vlo += 384) {
          if (wt) { kb += 8; mbar_wait(kb, 0); }
          WG_WAIT(0);
          fence_regs(s); fence_regs(o);
          const uint64_t dv = desc64(vlo, 8);
          exp_pv(s, o, dv, mk);
          wgmma_rs_n128(s, q[0], q[1], q[2], q[3], dv + KV2K, 0);
          wgmma_rs_n128(s, q[4], q[5], 0, 0, dv + (KV2K + KSTEP2), 1);
          WG_COMMIT();
        }
        WG_WAIT(0);
        fence_regs(s); fence_regs(o);
        if (u + 1 < nun) load_q(q, qthr + ((utile >> 4) & 15) * 3072);
        exp_pv(s, o, desc64(vlo, 8), mk);
        WG_COMMIT();
        WG_WAIT(0);
        fence_regs(o);
        if (wg == 1 && !(u & 1)) {
          float4* pp = (float4*)(part + u * 768) + (tid & 127);
          pp[0] = make_float4(o[0], o[1], o[2], o[3]);
          pp[128] = make_float4(o[4], o[5], o[6], o[7]);
          pp[256] = make_float4(o[8], o[9], o[10], o[11]);
          mbar_arrive(partb + 4 * u);
        } else {
          if (wg != 1 && u == 2) {
            const int pi = wg == 0 ? 1 : 0;
            mbar_wait(partb + 8 * pi, 0);
            const float4* pp = (const float4*)(part + pi * 1536) + (tid & 127);
            const float4 x0 = pp[0], x1 = pp[128], x2 = pp[256];
            o[0] += x0.x; o[1] += x0.y; o[2] += x0.z; o[3] += x0.w; o[4] += x1.x; o[5] += x1.y;
            o[6] += x1.z; o[7] += x1.w; o[8] += x2.x; o[9] += x2.y; o[10] += x2.z; o[11] += x2.w;
          }
          store_o(o, utile & 15);
        }
        utile >>= 4; ubeg >>= 4; ulen >>= 8;
      }
      if ((tid & 127) == 0) STAMP(1, 3 + wg);
    } else {
#pragma unroll 1
      for (int tile = wg; tile < 8; tile += 3) {
        load_q(q, qthr + tile * 3072);
        if ((lane & 3) >= 2) { q[4] = 0; q[5] = 0; }
        float o[12], m0 = -INFINITY, m1 = -INFINITY;
#pragma unroll
        for (int i = 0; i < 12; i++) o[i] = 0.f;
#pragma unroll 1
        for (int b = 0; b < 16; b++) {
          float s[64];
          mbar_wait(kvb + 8 * b, 0);
          WG_FENCE();
          wgmma_rs_n128(s, q[0], q[1], q[2], q[3], desc64(klo0 + b * 384, 8), 0);
          wgmma_rs_n128(s, q[4], q[5], 0, 0, desc64(klo0 + b * 384, 8) + KSTEP2, 1);
          WG_COMMIT();
          WG_WAIT(0);
          fence_regs(s);
          float x0 = m0, x1 = m1;
#pragma unroll
          for (int j = 0; j < 16; j++) {
            if ((POLY_MASK >> j) & 1) {
#pragma unroll
              for (int i = 0; i < 4; i++) s[4 * j + i] *= (1.f / 32768.f);
            }
            x0 = fmaxf(x0, fmaxf(s[4 * j], s[4 * j + 1]));
            x1 = fmaxf(x1, fmaxf(s[4 * j + 2], s[4 * j + 3]));
          }
          x0 = fmaxf(x0, __shfl_xor_sync(~0u, x0, 1)); x0 = fmaxf(x0, __shfl_xor_sync(~0u, x0, 2));
          x1 = fmaxf(x1, __shfl_xor_sync(~0u, x1, 1)); x1 = fmaxf(x1, __shfl_xor_sync(~0u, x1, 2));
          const float al0 = ex2(m0 - x0), al1 = ex2(m1 - x1);
          m0 = x0; m1 = x1;
#pragma unroll
          for (int i = 0; i < 12; i++) o[i] *= (i & 2) ? al1 : al0;
          uint32_t p[32];
#pragma unroll
          for (int i = 0; i < 32; i++) {
            const float mm = (i & 1) ? m1 : m0;
            p[i] = pack_bf16(ex2(s[2 * i] - mm), ex2(s[2 * i + 1] - mm));
          }
          fence_regs(o);
          WG_FENCE();
#pragma unroll
          for (int k = 0; k < 8; k++)
            wgmma_rs_n24(o, p[4 * k], p[4 * k + 1], p[4 * k + 2], p[4 * k + 3], desc64(vlo0 + b * 384 + k * 48, 8), 1);
          WG_COMMIT();
          WG_WAIT(0);
          fence_regs(o);
        }
        store_o(o, tile);
      }
    }
  }
}

#define K3P 2
constexpr int K3_ST = 4, K3_STAGE = 37888, K3_PRE = K3P;
constexpr int K3_SMEM = K3_ST * K3_STAGE + 45056 + 20480 + 256;

template <int N> struct Acc { float v[N]; };

template <int NB, int NK, bool FIRST>
__global__ void __cluster_dims__(2, 1, 1) __launch_bounds__(384, 1)
k3_proj(const __grid_constant__ CUtensorMap tmr, const uint4* __restrict__ aimg, const uint4* __restrict__ wimg) {
  constexpr int KT = 2 * NB + NK, EX = FIRST ? 1 : 0;
  extern __shared__ __align__(1024) uint8_t sm[];
  const uint32_t sbase = smem_u32(sm);
  uint8_t* xch = sm + K3_ST * K3_STAGE;
  uint8_t* stg = sm + K3_ST * K3_STAGE + 45056;
  const uint32_t fullb = smem_u32(stg) + 20480, emptyb = fullb + 8 * K3_ST, resb = emptyb + 8 * K3_ST, xchb = resb + 8;
  const int tid = threadIdx.x, lane = tid & 31;
  const int warp = __shfl_sync(~0u, tid >> 5, 0);
  const int rank = blockIdx.x & 1;
  const int n = blockIdx.x & 7, m = blockIdx.x >> 3;
  if (tid == 0) STAMP(FIRST ? 2 : 4, 0);
  if (warp == 0) {
    if (lane == 0) {
      prefetch_map(&tmr);
      for (int i = 0; i < K3_ST; i++) { mbar_init(fullb + 8 * i, 1); mbar_init(emptyb + 8 * i, 4); }
      mbar_init(resb, 1); mbar_init(xchb, 1);
      mbar_expect(xchb, 4096 * (10 + EX));
      asm volatile("fence.mbarrier_init.release.cluster;" ::: "memory");
    }
    __syncwarp();
    cluster_arrive();
    bar_arrive(4, 256 + 32);
    if (lane == 0) {
      const uint8_t* wk = (const uint8_t*)wimg + (size_t)n * KT * 10240;
      const uint8_t* ws = (const uint8_t*)wimg + (size_t)(n ^ 1) * KT * 10240;
      const uint8_t* ab = (const uint8_t*)aimg + (size_t)m * KT * 16384;
      auto load_w = [&](int i) {
        const int s = i % K3_ST, kt = i < NB ? i + rank * (NB + NK) : i;
        const uint32_t sa = sbase + s * K3_STAGE;
        mbar_expect(fullb + 8 * s, 26624 + EX * 1024 + (i < NB ? 10240 : 0));
        bulk_ld(sa + 16384, wk + kt * 10240, 10240, fullb + 8 * s);
        if (FIRST) bulk_ld(sa + 26624, (const uint8_t*)g_wm + kt * 1024, 1024, fullb + 8 * s);
        if (i < NB) bulk_ld(sa + 26624 + EX * 1024, ws + kt * 10240, 10240, fullb + 8 * s);
      };
#pragma unroll 1
      for (int i = 0; i < K3_PRE; i++) load_w(i);
      if (FIRST) {
        mbar_expect(resb, 20480);
        tma2d(smem_u32(stg), &tmr, n * 80, m * 128, resb);
        tma2d(smem_u32(stg) + 10240, &tmr, n * 80, m * 128 + 64, resb);
      }
      asm volatile("barrier.cluster.wait;" ::: "memory");
      pdl_wait();
      pdl_trigger();
#pragma unroll 1
      for (int i = 0; i < NB + NK; i++) {
        const int s = i % K3_ST;
        const uint32_t sa = sbase + s * K3_STAGE;
        if (i >= K3_ST) mbar_wait(emptyb + 8 * s, ((i / K3_ST) - 1) & 1);
        if (i < NB) bulk_ld(sa, ab + (i + rank * (NB + NK)) * 16384, 16384, fullb + 8 * s);
        else bulk_ld_mc(sa + rank * 8192, ab + i * 16384 + rank * 8192, 8192, fullb + 8 * s);
        if (i >= K3_PRE) load_w(i);
      }
    } else {
      asm volatile("barrier.cluster.wait;" ::: "memory");
    }
    __syncwarp();
    cluster_arrive();
  } else if (warp >= 4) {
    cluster_arrive();
    const int cw = warp - 4, wg = cw >> 2;
    const int g = lane >> 2, c = lane & 3;
    const int row = m * 128 + cw * 16 + g;
    uint8_t* himg = (uint8_t*)g_h + (size_t)m * 163840 + cw * 2048 + lane * 4;
    uint32_t rv[20];
    float mu0, mu1;
    if (FIRST) {
      mu0 = __uint_as_float(__ldcg(&g_rowstat[row].z)); mu1 = __uint_as_float(__ldcg(&g_rowstat[row + 8].z));
    } else {
      mu0 = __ldcg(&g_hmean[row]); mu1 = __ldcg(&g_hmean[row + 8]);
#pragma unroll
      for (int j = 0; j < 10; j++) {
        rv[2 * j] = __ldcg((const uint32_t*)(himg + img_off(n * 10 + j)));
        rv[2 * j + 1] = __ldcg((const uint32_t*)(himg + img_off(n * 10 + j) + 1024));
      }
    }
    float acc[80 + 4 * EX];
    float (&keep)[40 + 4 * EX] = ((Acc<40 + 4 * EX>*)acc)->v;
    const uint64_t da0 = mkdesc(sbase + wg * 8192, 128, 1024, 0);
    const uint64_t db0 = mkdesc(sbase + 16384, 128, 1024, 0);
    bar_sync(4, 256 + 32);
    cluster_wait();
#pragma unroll 1
    for (int i = 0; i < NB; i++) {
      const int s = i % K3_ST;
      mbar_wait(fullb + 8 * s, (i / K3_ST) & 1);
      if (i == 0 && tid == 128) STAMP(FIRST ? 2 : 4, 2);
      const uint64_t da = da0 + s * (K3_STAGE >> 4), db = db0 + s * (K3_STAGE >> 4);
      WG_FENCE();
#pragma unroll
      for (int k = 0; k < 4; k++) {
        if constexpr (FIRST) wgmma_ss_n168(acc, da + k * 16, db + k * 16, (i | k) != 0);
        else wgmma_ss_n160(acc, da + k * 16, db + k * 16, (i | k) != 0);
      }
      WG_COMMIT();
      if (i > 0) {
        WG_WAIT(1);
        if ((tid & 127) < 2) mbar_arrive_cta(emptyb + 8 * ((i - 1) % K3_ST), tid & 1);
      }
    }
    const uint32_t rx = mapa(smem_u32(xch) + (tid - 128) * 16, rank ^ 1), rb = mapa(xchb, rank ^ 1);
    WG_WAIT(0);
    fence_regs(acc);
    if ((tid & 127) < 2) mbar_arrive_cta(emptyb + 8 * ((NB - 1) % K3_ST), tid & 1);
    if (FIRST) st_async4(rx, acc[40], acc[41], acc[42], acc[43], rb);
    if (tid == 128) STAMP(FIRST ? 2 : 4, 1);
#pragma unroll
    for (int i = NB; i < NB + NK; i++) {
      const int s = i % K3_ST;
      mbar_wait(fullb + 8 * s, (i / K3_ST) & 1);
      const uint64_t da = da0 + s * (K3_STAGE >> 4), db = db0 + s * (K3_STAGE >> 4);
      WG_FENCE();
#pragma unroll
      for (int k = 0; k < 4; k++) {
        if constexpr (FIRST) wgmma_ss_n88(keep, da + k * 16, db + k * 16, 1);
        else wgmma_ss_n80(keep, da + k * 16, db + k * 16, 1);
      }
      WG_COMMIT();
      if (i > NB && i - 1 + K3_ST < NB + NK) {
        WG_WAIT(1);
        if ((tid & 127) < 2) mbar_arrive_cta(emptyb + 8 * ((i - 1) % K3_ST), tid & 1);
      }
#pragma unroll
      for (int j = (i - NB) * 3 + EX; j < (i - NB) * 3 + 3 + EX; j++)
        if (j < 10 + EX) st_async4(rx + j * 4096, acc[40 + 4 * j], acc[41 + 4 * j], acc[42 + 4 * j], acc[43 + 4 * j], rb);
    }
    cluster_arrive();
    uint8_t* sp = stg + (cw * 16 + g) * 160 + c * 4;
    if (FIRST) {
      mbar_wait(resb, 0);
#pragma unroll
      for (int j = 0; j < 10; j++) {
        rv[2 * j] = *(const uint32_t*)(sp + j * 16);
        rv[2 * j + 1] = *(const uint32_t*)(sp + 1280 + j * 16);
      }
    }
    WG_WAIT(0);
    fence_regs(keep);
    if (tid == 128) STAMP(FIRST ? 2 : 4, 3);
    mbar_wait(xchb, 0);
    if (tid == 128) STAMP(FIRST ? 2 : 4, 5);
    const uint8_t* xp = xch + (tid - 128) * 16;
    if (FIRST) {
      const float4 p = *(const float4*)xp;
      mu0 += __shfl_sync(~0u, (keep[40] + p.x) + (keep[41] + p.y), 0, 4);
      mu1 += __shfl_sync(~0u, (keep[42] + p.z) + (keep[43] + p.w), 0, 4);
      if (n == 0 && c == 0) { g_hmean[row] = mu0; g_hmean[row + 8] = mu1; }
      mu0 = -mu0; mu1 = -mu1;
    }
    float q0 = 0.f, q1 = 0.f;
#pragma unroll
    for (int j = 0; j < 10; j++) {
      const float4 p = *(const float4*)(xp + (j + EX) * 4096);
      const float x0 = (keep[4 * j] + p.x) + (bf_lo(rv[2 * j]) + mu0), x1 = (keep[4 * j + 1] + p.y) + (bf_hi(rv[2 * j]) + mu0);
      const float y0 = (keep[4 * j + 2] + p.z) + (bf_lo(rv[2 * j + 1]) + mu1), y1 = (keep[4 * j + 3] + p.w) + (bf_hi(rv[2 * j + 1]) + mu1);
      if (FIRST) {
        *(uint32_t*)(himg + img_off(n * 10 + j)) = pack_bf16(x0, x1);
        *(uint32_t*)(himg + img_off(n * 10 + j) + 1024) = pack_bf16(y0, y1);
        q0 = fmaf(x0, x0, fmaf(x1, x1, q0)); q1 = fmaf(y0, y0, fmaf(y1, y1, q1));
      } else {
        *(uint32_t*)(sp + j * 16) = pack_bf16(x0, x1);
        *(uint32_t*)(sp + 1280 + j * 16) = pack_bf16(y0, y1);
      }
    }
    if (FIRST) {
      q0 += __shfl_xor_sync(~0u, q0, 1); q0 += __shfl_xor_sync(~0u, q0, 2);
      q1 += __shfl_xor_sync(~0u, q1, 1); q1 += __shfl_xor_sync(~0u, q1, 2);
      if (c < 2) g_hpart[n * S_ + row + c * 8] = c ? q1 : q0;
    } else {
      fence_async();
      bar_sync(1 + wg, 128);
      if ((tid & 127) == 0) {
        tma2d_st(&tmr, n * 80, m * 128 + wg * 64, smem_u32(stg) + wg * 10240);
        bulk_commit_wait();
      }
      __syncwarp();
    }
    if (tid == 128) STAMP(FIRST ? 2 : 4, 4);
  } else {
    cluster_arrive();
    cluster_wait();
    cluster_arrive();
  }
  cluster_wait();
}

constexpr int K4_RB = 163840, K4_BST = 14336, K4_XCH = 147456, K4_STG = K4_XCH + 40960, K4_BAR = K4_RB + 4 * K4_BST;
constexpr int K4_SMEM = K4_BAR + 256;

__device__ __forceinline__ void wait_flags(const uint4* f, uint32_t tag) {
  for (uint32_t it = 0;; it++) {
    uint4 a, b;
    asm volatile("ld.acquire.gpu.global.v4.u32 {%0, %1, %2, %3}, [%4];" : "=r"(a.x), "=r"(a.y), "=r"(a.z), "=r"(a.w) : "l"(f) : "memory");
    asm volatile("ld.acquire.gpu.global.v4.u32 {%0, %1, %2, %3}, [%4];" : "=r"(b.x), "=r"(b.y), "=r"(b.z), "=r"(b.w) : "l"(f + 1) : "memory");
    if (a.x == tag && a.y == tag && a.z == tag && a.w == tag && b.x == tag && b.y == tag && b.z == tag && b.w == tag) break;
    if (it > (1u << 20)) wait_timeout();
  }
  asm volatile("fence.proxy.async.global;" ::: "memory");
}

__global__ void __cluster_dims__(2, 1, 1) __launch_bounds__(384, 1)
k45_ffn(const __grid_constant__ CUtensorMap tmo) {
  extern __shared__ __align__(1024) uint8_t sm[];
  const uint32_t sbase = smem_u32(sm);
  const uint32_t afull = sbase + K4_BAR, bfull = afull + 80, bempty = bfull + 32, full3 = bempty + 32, empty3 = full3 + 32, xchb = empty3 + 32;
  const int tid = threadIdx.x, lane = tid & 31;
  const int warp = __shfl_sync(~0u, tid >> 5, 0);
  const int rank = blockIdx.x & 1;
  const int n1 = (blockIdx.x >> 1) & 7, m1 = (blockIdx.x >> 4) * 2 + rank;
  const int n3 = blockIdx.x & 7, m3 = blockIdx.x >> 3;
  if (tid == 0) STAMP(3, 0);
  if (warp >= 8) {
    asm volatile("setmaxnreg.dec.sync.aligned.u32 40;");
    if (warp == 8) {
      if (lane == 0) {
        prefetch_map(&tmo);
        for (int i = 0; i < 10; i++) mbar_init(afull + 8 * i, 1);
        for (int i = 0; i < 4; i++) {
          mbar_init(bfull + 8 * i, 1); mbar_init(bempty + 8 * i, 4); mbar_init(full3 + 8 * i, 1); mbar_init(empty3 + 8 * i, 4);
        }
        mbar_init(xchb, 1);
        mbar_expect(xchb, 40960);
        asm volatile("fence.mbarrier_init.release.cluster;" ::: "memory");
      }
      __syncwarp();
      cluster_arrive();
      bar_arrive(4, 256 + 32);
      cluster_wait();
      if (lane == 0) {
        const uint8_t* wb = (const uint8_t*)g_wgu + n1 * 552960;
        const uint8_t* wk = (const uint8_t*)g_wd + n3 * 276480;
        const uint8_t* ws = (const uint8_t*)g_wd + (n3 ^ 1) * 276480;
        const uint8_t* ab = (const uint8_t*)g_hh + (size_t)m3 * 442368;
        auto load_b = [&](int j) {
          const uint32_t half = j < 20 ? 7168 : 6656;
          mbar_expect(bfull + 8 * (j & 3), 2 * half);
          bulk_ld_mc(sbase + K4_RB + (j & 3) * K4_BST + rank * half, wb + (j < 20 ? j * 14336 : 286720 + (j - 20) * 13312) + rank * half,
                     half, bfull + 8 * (j & 3));
        };
        auto load_3 = [&](int i) {
          const int kt = i < 7 ? rank * 7 + i : (i < 11 ? rank * 4 + 7 + i : 11 + i);
          const uint32_t sa = sbase + (i & 3) * 36864, fb = full3 + 8 * (i & 3);
          mbar_expect(fb, i < 11 ? 36864 : 26624);
          if (i < 11) bulk_ld(sa, ab + kt * 16384, 16384, fb);
          else bulk_ld_mc(sa + rank * 8192, ab + kt * 16384 + rank * 8192, 8192, fb);
          bulk_ld(sa + 16384, wk + kt * 10240, 10240, fb);
          if (i < 11) bulk_ld(sa + 26624, ws + kt * 10240, 10240, fb);
        };
#pragma unroll 1
        for (int j = 0; j < 4; j++) load_b(j);
        const uint32_t tag = __ldcg(&g_epoch);
        pdl_wait();
        STAMP(3, 1);
        const uint8_t* hb = (const uint8_t*)g_h + (size_t)m1 * 163840;
#pragma unroll 1
        for (int kt = 0; kt < 3; kt++) { mbar_expect(afull + 8 * kt, 16384); bulk_ld(sbase + kt * 16384, hb + kt * 16384, 16384, afull + 8 * kt); }
#pragma unroll 1
        for (int j = 4; j < 44; j++) {
          mbar_wait(bempty + 8 * (j & 3), ((j >> 2) - 1) & 1);
          if (j < 18 && !(j & 1)) {
            const int kt = (j >> 1) + 1;
            mbar_expect(afull + 8 * kt, 16384);
            bulk_ld(sbase + kt * 16384, hb + kt * 16384, 16384, afull + 8 * kt);
          }
          if (j < 40) load_b(j);
          if (j >= 29 && (j & 3) == 1) {
            if (j == 29) wait_flags(&g_flag[m3 * 2], tag);
            load_3((j - 29) >> 2);
          }
        }
#pragma unroll 1
        for (int i = 4; i < 16; i++) {
          mbar_wait(empty3 + 8 * (i & 3), ((i >> 2) - 1) & 1);
          if (i == 7) wait_flags(&g_flag[32 + m3 * 2], tag);
          load_3(i);
        }
      }
      __syncwarp();
    } else {
      cluster_arrive();
      cluster_wait();
      if (warp == 9) {
        const uint32_t tag = __ldcg(&g_epoch);
#pragma unroll 1
        for (int ph = 0; ph < 2; ph++) {
          bar_sync(5 + ph, 256 + 32);
          if (lane == 0)
            asm volatile("st.release.gpu.global.u32 [%0], %1;" ::"l"((uint32_t*)&g_flag[ph * 32 + m1 * 2] + n1), "r"(tag) : "memory");
          __syncwarp();
        }
      }
    }
    cluster_arrive();
    asm volatile("barrier.cluster.wait.aligned; // producers" ::: "memory");
  } else {
    asm volatile("setmaxnreg.inc.sync.aligned.u32 232;");
    cluster_arrive();
    const int wg = warp >> 2;
    const uint64_t da0 = mkdesc(sbase + wg * 8192, 128, 1024, 0);
    const uint64_t db0 = mkdesc(sbase + K4_RB, 128, 512, 0);
    bar_sync(4, 256 + 32);
    cluster_wait();
    float a1[112], a2[104];
#pragma unroll 1
    for (int j = 0; j < 20; j++) {
      if (!(j & 1)) mbar_wait(afull + 4 * j, 0);
      mbar_wait(bfull + 8 * (j & 3), (j >> 2) & 1);
      if (j == 0 && tid == 0) STAMP(3, 2);
      const uint64_t da = da0 + (j >> 1) * 1024 + (j & 1) * 32, db = db0 + (j & 3) * (K4_BST >> 4);
      WG_FENCE();
      wgmma_ss_n224(a1, da, db, j != 0);
      wgmma_ss_n224(a1, da + 16, db + 16, 1);
      WG_COMMIT();
      if (j > 0) {
        WG_WAIT(1);
        if ((tid & 127) < 2) mbar_arrive_cta(bempty + 8 * ((j - 1) & 3), tid & 1);
      }
    }
    float r0, r1;
    {
      const float* hp = &g_hpart[(lane & 3) * 2 * S_ + m1 * 128 + warp * 16 + (lane >> 2)];
      r0 = __ldcg(hp) + __ldcg(hp + S_);
      r1 = __ldcg(hp + 8) + __ldcg(hp + S_ + 8);
    }
    r0 += __shfl_xor_sync(~0u, r0, 1); r1 += __shfl_xor_sync(~0u, r1, 1);
    r0 += __shfl_xor_sync(~0u, r0, 2); r1 += __shfl_xor_sync(~0u, r1, 2);
    r0 = __frcp_rn(r0 * (1.f / D_) + 1e-5f); r1 = __frcp_rn(r1 * (1.f / D_) + 1e-5f);
    WG_WAIT(0);
    fence_regs(a1);
    if ((tid & 127) < 2) mbar_arrive_cta(bempty + 24, tid & 1);
    if (tid == 0) STAMP(3, 3);
    uint8_t* hd = (uint8_t*)g_hh + (size_t)m1 * 442368 + warp * 2048 + lane * 4;
#define STORE_H(a, off, q, c) do { uint8_t* p_ = hd + img_off(q); \
      *(uint32_t*)p_ = pack_bf16(a[4 * (c)] * r0 * a[off + 4 * (c)], a[4 * (c) + 1] * r0 * a[off + 1 + 4 * (c)]); \
      *(uint32_t*)(p_ + 1024) = pack_bf16(a[4 * (c) + 2] * r1 * a[off + 2 + 4 * (c)], a[4 * (c) + 3] * r1 * a[off + 3 + 4 * (c)]); } while (0)
    uint32_t p1[28];
#pragma unroll
    for (int c = 0; c < 14; c++) {
      p1[2 * c] = pack_bf16(a1[4 * c] * r0 * a1[56 + 4 * c], a1[4 * c + 1] * r0 * a1[57 + 4 * c]);
      p1[2 * c + 1] = pack_bf16(a1[4 * c + 2] * r1 * a1[58 + 4 * c], a1[4 * c + 3] * r1 * a1[59 + 4 * c]);
      asm volatile("" : "+r"(p1[2 * c]), "+r"(p1[2 * c + 1])::"memory");
    }
#pragma unroll
    for (int j = 20; j < 40; j++) {
      mbar_wait(bfull + 8 * (j & 3), (j >> 2) & 1);
      const uint64_t da = da0 + ((j - 20) >> 1) * 1024 + (j & 1) * 32, db = db0 + (j & 3) * (K4_BST >> 4);
      WG_FENCE();
      wgmma_ss_n208(a2, da, db, j != 20);
      wgmma_ss_n208(a2, da + 16, db + 16, 1);
      WG_COMMIT();
      if (j > 20) {
        WG_WAIT(1);
        if ((tid & 127) < 2) mbar_arrive_cta(bempty + 8 * ((j - 1) & 3), tid & 1);
      }
#pragma unroll
      for (int c = (j - 20) * 2; c < (j - 20) * 2 + 2; c++) {
        if (c < 14) {
          *(uint32_t*)(hd + img_off(n1 * 14 + c)) = p1[2 * c];
          *(uint32_t*)(hd + img_off(n1 * 14 + c) + 1024) = p1[2 * c + 1];
        }
        if (c == 13) bar_arrive(5, 256 + 32);
      }
    }
    WG_WAIT(0);
    fence_regs(a2);
    if ((tid & 127) < 2) mbar_arrive_cta(bempty + 24, tid & 1);
    if (tid == 0) STAMP(3, 4);
    float acc[80];
    float (&keep)[40] = ((Acc<40>*)acc)->v;
    const uint64_t db3 = mkdesc(sbase + 16384, 128, 1024, 0);
#pragma unroll
    for (int i = 0; i < 11; i++) {
      mbar_wait(full3 + 8 * (i & 3), (i >> 2) & 1);
      if (i == 0 && tid == 0) STAMP(4, 2);
      const uint64_t da = da0 + (i & 3) * 2304, db = db3 + (i & 3) * 2304;
      WG_FENCE();
#pragma unroll
      for (int k = 0; k < 4; k++) wgmma_ss_n160(acc, da + k * 16, db + k * 16, (i | k) != 0);
      WG_COMMIT();
      if (i > 0) {
        WG_WAIT(1);
        if ((tid & 127) < 2) mbar_arrive_cta(empty3 + 8 * ((i - 1) & 3), tid & 1);
      }
      if (i < 2) {
#pragma unroll
        for (int c = i * 7; c < (i ? 13 : 7); c++) STORE_H(a2, 52, 112 + n1 * 13 + c, c);
        if (i == 1) bar_arrive(6, 256 + 32);
      }
    }
    const int g = lane >> 2, c = lane & 3, row = m3 * 128 + warp * 16 + g;
    const uint8_t* himg = (const uint8_t*)g_h + (size_t)m3 * 163840 + warp * 2048 + lane * 4;
    uint32_t rv[20];
    const float mu0 = __ldcg(&g_hmean[row]), mu1 = __ldcg(&g_hmean[row + 8]);
#pragma unroll
    for (int j = 0; j < 10; j++) {
      rv[2 * j] = __ldcg((const uint32_t*)(himg + img_off(n3 * 10 + j)));
      rv[2 * j + 1] = __ldcg((const uint32_t*)(himg + img_off(n3 * 10 + j) + 1024));
    }
    const uint32_t rx = mapa(sbase + K4_XCH + tid * 16, rank ^ 1), rb = mapa(xchb, rank ^ 1);
    WG_WAIT(0);
    fence_regs(acc);
    if ((tid & 127) < 2) mbar_arrive_cta(empty3 + 16, tid & 1);
    if (tid == 0) STAMP(4, 1);
#pragma unroll
    for (int i = 11; i < 16; i++) {
      mbar_wait(full3 + 8 * (i & 3), (i >> 2) & 1);
      const uint64_t da = da0 + (i & 3) * 2304, db = db3 + (i & 3) * 2304;
      WG_FENCE();
#pragma unroll
      for (int k = 0; k < 4; k++) wgmma_ss_n80(keep, da + k * 16, db + k * 16, 1);
      WG_COMMIT();
      if (i == 12) {
        WG_WAIT(1);
        if ((tid & 127) < 2) mbar_arrive_cta(empty3 + 24, tid & 1);
      }
#pragma unroll
      for (int j = (i - 11) * 3; j < (i - 11) * 3 + 3; j++)
        if (j < 10) st_async4(rx + j * 4096, acc[40 + 4 * j], acc[41 + 4 * j], acc[42 + 4 * j], acc[43 + 4 * j], rb);
    }
    cluster_arrive();
    WG_WAIT(0);
    fence_regs(keep);
    if (tid == 0) STAMP(4, 3);
    mbar_wait(xchb, 0);
    if (tid == 0) STAMP(4, 5);
    uint8_t* sp = sm + K4_STG + (warp * 16 + g) * 160 + c * 4;
#pragma unroll
    for (int j = 0; j < 10; j++) {
      const float4 p = *(const float4*)(sm + K4_XCH + tid * 16 + j * 4096);
      *(uint32_t*)(sp + j * 16) = pack_bf16((keep[4 * j] + p.x) + (bf_lo(rv[2 * j]) + mu0), (keep[4 * j + 1] + p.y) + (bf_hi(rv[2 * j]) + mu0));
      *(uint32_t*)(sp + 1280 + j * 16) = pack_bf16((keep[4 * j + 2] + p.z) + (bf_lo(rv[2 * j + 1]) + mu1), (keep[4 * j + 3] + p.w) + (bf_hi(rv[2 * j + 1]) + mu1));
    }
    fence_async();
    bar_sync(1 + wg, 128);
    if ((tid & 127) == 0) {
      tma2d_st(&tmo, n3 * 80, m3 * 128 + wg * 64, sbase + K4_STG + wg * 10240);
      bulk_commit_wait();
    }
    __syncwarp();
    if (tid == 0) STAMP(4, 4);
    asm volatile("barrier.cluster.wait.aligned; // consumers" ::: "memory");
  }
}

typedef CUresult (*EncodeFn)(CUtensorMap*, CUtensorMapDataType, cuuint32_t, void*, const cuuint64_t*, const cuuint64_t*,
                             const cuuint32_t*, const cuuint32_t*, CUtensorMapInterleave, CUtensorMapSwizzle,
                             CUtensorMapL2promotion, CUtensorMapFloatOOBfill);

static CUtensorMap make_map(EncodeFn enc, const void* p, uint64_t inner, uint64_t outer, uint32_t box_inner,
                            uint32_t box_outer, CUtensorMapSwizzle swz) {
  CUtensorMap m;
  cuuint64_t gd[2] = {inner, outer};
  cuuint64_t gs[1] = {inner * 2};
  cuuint32_t bd[2] = {box_inner, box_outer};
  cuuint32_t es[2] = {1, 1};
  enc(&m, CU_TENSOR_MAP_DATA_TYPE_BFLOAT16, 2, (void*)p, gd, gs, bd, es, CU_TENSOR_MAP_INTERLEAVE_NONE, swz,
      CU_TENSOR_MAP_L2_PROMOTION_L2_256B, CU_TENSOR_MAP_FLOAT_OOB_FILL_NONE);
  return m;
}

static CUtensorMap make_map_img(EncodeFn enc, const void* p, uint64_t k, uint64_t n, uint32_t rows, uint32_t chunks) {
  CUtensorMap m;
  cuuint64_t gd[3] = {8, k, n / 8};
  cuuint64_t gs[2] = {n * 2, 16};
  cuuint32_t bd[3] = {8, rows, chunks};
  cuuint32_t es[3] = {1, 1, 1};
  enc(&m, CU_TENSOR_MAP_DATA_TYPE_BFLOAT16, 3, (void*)p, gd, gs, bd, es, CU_TENSOR_MAP_INTERLEAVE_NONE,
      CU_TENSOR_MAP_SWIZZLE_NONE, CU_TENSOR_MAP_L2_PROMOTION_L2_128B, CU_TENSOR_MAP_FLOAT_OOB_FILL_NONE);
  return m;
}

template <typename... KArgs, typename... Args>
static void launch(void (*k)(KArgs...), int grid, int threads, int smem, bool pdl, Args... args) {
  cudaLaunchConfig_t cfg = {};
  cfg.gridDim = dim3(grid);
  cfg.blockDim = dim3(threads);
  cfg.dynamicSmemBytes = smem;
  cfg.stream = cudaStreamPerThread;
  cudaLaunchAttribute at[1];
  at[0].id = cudaLaunchAttributeProgrammaticStreamSerialization;
  at[0].val.programmaticStreamSerializationAllowed = 1;
  cfg.attrs = at;
  cfg.numAttrs = pdl ? 1 : 0;
  cudaLaunchKernelEx(&cfg, k, KArgs(args)...);
}

extern "C" void kernel_launch(void* const* d_in, const int* in_sizes, int n_in, void* d_out, int out_size) {
  const bf16* x = (const bf16*)d_in[0];
  const bf16* wqkv = (const bf16*)d_in[1];
  const bf16* wo = (const bf16*)d_in[2];
  const bf16* wg = (const bf16*)d_in[4];
  const bf16* wu = (const bf16*)d_in[5];
  const bf16* wd = (const bf16*)d_in[6];

  static EncodeFn enc = nullptr;
  static void *p_o, *p_wo;
  if (!enc) {
    void* fn = nullptr;
    cudaDriverEntryPointQueryResult qr;
    cudaGetDriverEntryPoint("cuTensorMapEncodeTiled", &fn, cudaEnableDefault, &qr);
    enc = (EncodeFn)fn;
    cudaGetSymbolAddress(&p_o, g_o);
    cudaGetSymbolAddress(&p_wo, g_wo);
    cudaFuncSetAttribute(k1_qkv, cudaFuncAttributeMaxDynamicSharedMemorySize, K1_SMEM);
    cudaFuncSetAttribute(k2_attn, cudaFuncAttributeMaxDynamicSharedMemorySize, K2_SMEM);
    cudaFuncSetAttribute(k3_proj<3, 4, true>, cudaFuncAttributeMaxDynamicSharedMemorySize, K3_SMEM);
    cudaFuncSetAttribute(k45_ffn, cudaFuncAttributeMaxDynamicSharedMemorySize, K4_SMEM);
  }
  const CUtensorMap tmx = make_map(enc, x, D_, S_, 64, 96, CU_TENSOR_MAP_SWIZZLE_128B);
  const CUtensorMap tmw = make_map(enc, wqkv, 3 * D_, D_, 32, 64, CU_TENSOR_MAP_SWIZZLE_64B);
  const CUtensorMap tmxr = make_map(enc, x, D_, S_, 80, 64, CU_TENSOR_MAP_SWIZZLE_NONE);
  Maps5 maps;
  maps.m[0] = make_map_img(enc, wg, D_, F_, 32, 14); maps.m[1] = make_map_img(enc, wu, D_, F_, 32, 14);
  maps.m[2] = make_map_img(enc, wg, D_, F_, 32, 13); maps.m[3] = make_map_img(enc, wu, D_, F_, 32, 13);
  maps.m[4] = make_map_img(enc, wd, F_, D_, 64, 10);
  const CUtensorMap tmout = make_map(enc, d_out, D_, S_, 80, 64, CU_TENSOR_MAP_SWIZZLE_NONE);

  launch(k1_qkv, 132, 512, K1_SMEM, false, tmx, tmw, x, wqkv, wo);
  launch(k2_attn, 128, 512, K2_SMEM, true, maps, 0x007f007fu);
  launch(k3_proj<3, 4, true>, 128, 384, K3_SMEM, true, tmxr, (const uint4*)p_o, (const uint4*)p_wo);
  launch(k45_ffn, 128, 384, K4_SMEM, true, tmout);
}
```

```cpp
#include <cuda_runtime.h>
#include <cuda_bf16.h>
#include <cuda.h>
#include <stdint.h>

typedef __nv_bfloat16 bf16;

constexpr int S_ = 2048, D_ = 640, F_ = 1728;
constexpr int HEAD_IMG = 98304;
#define PMASK 0xDB6D
constexpr uint32_t POLY_MASK = PMASK;
constexpr float QSCALE = 0.22360679774997896f * 1.4426950408889634f;

__device__ __align__(1024) uint4 g_qkv[96 * HEAD_IMG / 16];
__device__ __align__(1024) uint4 g_o[S_ * D_ / 8];
__device__ __align__(1024) uint4 g_h[S_ * D_ / 8];
__device__ __align__(1024) uint4 g_hh[S_ * F_ / 8];
__device__ __align__(1024) uint4 g_wo[D_ * D_ / 8];
__device__ __align__(1024) uint4 g_wgu[2 * D_ * F_ / 8];
__device__ __align__(1024) uint4 g_wd[F_ * D_ / 8];
__device__ uint4 g_rowstat[S_];
__device__ uint4 g_cpart[10 * 12 * 80];
__device__ float g_nrm[64 * 128];
__device__ uint4 g_wm[D_];
__device__ float g_hmean[S_];
__device__ float g_hpart[8 * S_];
__device__ uint4 g_flag[2 * 16 * 2];
__device__ unsigned g_epoch;

#define STAMP(k, i)
__device__ __forceinline__ uint32_t smem_u32(const void* p) { return (uint32_t)__cvta_generic_to_shared(p); }
__device__ __forceinline__ void mbar_init(uint32_t a, uint32_t c) {
  asm volatile("mbarrier.init.shared::cta.b64 [%0], %1;" ::"r"(a), "r"(c) : "memory");
}
__device__ __forceinline__ void mbar_expect(uint32_t a, uint32_t bytes) {
  asm volatile("mbarrier.arrive.expect_tx.shared::cta.b64 _, [%0], %1;" ::"r"(a), "r"(bytes) : "memory");
}
__device__ __forceinline__ void mbar_arrive(uint32_t a) {
  asm volatile("mbarrier.arrive.shared::cta.b64 _, [%0];" ::"r"(a) : "memory");
}
__device__ __forceinline__ void mbar_arrive_cta(uint32_t a, uint32_t cta) {
  asm volatile("{\n.reg .b32 r;\nmapa.shared::cluster.u32 r, %0, %1;\n"
               "mbarrier.arrive.shared::cluster.b64 _, [r];\n}" ::"r"(a), "r"(cta) : "memory");
}
__device__ __forceinline__ bool mbar_try(uint32_t a, uint32_t ph) {
  uint32_t ok;
  asm volatile("{\n.reg .pred p;\nmbarrier.try_wait.parity.shared::cta.b64 p, [%1], %2;\nselp.u32 %0, 1, 0, p;\n}"
               : "=r"(ok) : "r"(a), "r"(ph) : "memory");
  return ok;
}
__device__ __noinline__ void wait_timeout() { __trap(); }
__device__ __forceinline__ void mbar_wait(uint32_t a, uint32_t ph) {
  if (mbar_try(a, ph)) return;
  uint32_t it = 0;
  while (!mbar_try(a, ph)) if (++it > (1u << 22)) wait_timeout();
}
__device__ __forceinline__ void tma2d(uint32_t dst, const CUtensorMap* m, int c0, int c1, uint32_t bar) {
  asm volatile("cp.async.bulk.tensor.2d.shared::cluster.global.mbarrier::complete_tx::bytes [%0], [%1, {%3, %4}], [%2];"
               ::"r"(dst), "l"(m), "r"(bar), "r"(c0), "r"(c1) : "memory");
}
__device__ __forceinline__ void tma2d_mc(uint32_t dst, const CUtensorMap* m, int c0, int c1, uint32_t bar) {
  asm volatile("cp.async.bulk.tensor.2d.shared::cluster.global.mbarrier::complete_tx::bytes.multicast::cluster "
               "[%0], [%1, {%3, %4}], [%2], %5;"
               ::"r"(dst), "l"(m), "r"(bar), "r"(c0), "r"(c1), "h"((uint16_t)3) : "memory");
}
__device__ __forceinline__ void bulk_ld(uint32_t dst, const void* src, uint32_t bytes, uint32_t bar) {
  asm volatile("cp.async.bulk.shared::cluster.global.mbarrier::complete_tx::bytes [%0], [%1], %2, [%3];"
               ::"r"(dst), "l"(src), "r"(bytes), "r"(bar) : "memory");
}
__device__ __forceinline__ void bulk_ld_mc(uint32_t dst, const void* src, uint32_t bytes, uint32_t bar) {
  asm volatile("cp.async.bulk.shared::cluster.global.mbarrier::complete_tx::bytes.multicast::cluster "
               "[%0], [%1], %2, [%3], %4;"
               ::"r"(dst), "l"(src), "r"(bytes), "r"(bar), "h"((uint16_t)3) : "memory");
}
__device__ __forceinline__ void cluster_arrive() { asm volatile("barrier.cluster.arrive.relaxed.aligned;" ::: "memory"); }
__device__ __forceinline__ void cluster_wait() { asm volatile("barrier.cluster.wait.aligned;" ::: "memory"); }
__device__ __forceinline__ void bulk_st(void* dst, uint32_t src, uint32_t bytes) {
  asm volatile("cp.async.bulk.global.shared::cta.bulk_group [%0], [%1], %2;" ::"l"(dst), "r"(src), "r"(bytes) : "memory");
}
__device__ __forceinline__ void tma2d_st(const CUtensorMap* m, int c0, int c1, uint32_t src) {
  asm volatile("cp.async.bulk.tensor.2d.global.shared::cta.bulk_group [%0, {%2, %3}], [%1];"
               ::"l"(m), "r"(src), "r"(c0), "r"(c1) : "memory");
}
__device__ __forceinline__ void bulk_commit_wait() {
  asm volatile("cp.async.bulk.commit_group;\ncp.async.bulk.wait_group.read 0;" ::: "memory");
}
__device__ __forceinline__ uint32_t mapa(uint32_t a, uint32_t cta) {
  uint32_t r;
  asm("mapa.shared::cluster.u32 %0, %1, %2;" : "=r"(r) : "r"(a), "r"(cta));
  return r;
}
__device__ __forceinline__ void st_async4(uint32_t dst, float a, float b, float c, float d, uint32_t bar) {
  asm volatile("st.async.shared::cluster.mbarrier::complete_tx::bytes.v4.f32 [%0], {%1, %2, %3, %4}, [%5];"
               ::"r"(dst), "f"(a), "f"(b), "f"(c), "f"(d), "r"(bar) : "memory");
}
__device__ __forceinline__ void fence_async() { asm volatile("fence.proxy.async.shared::cta;" ::: "memory"); }
__device__ __forceinline__ void prefetch_map(const CUtensorMap* m) {
  asm volatile("prefetch.tensormap [%0];" ::"l"(m) : "memory");
}
__device__ __forceinline__ void pdl_wait() { asm volatile("griddepcontrol.wait;" ::: "memory"); }
__device__ __forceinline__ void pdl_trigger() { asm volatile("griddepcontrol.launch_dependents;" ::: "memory"); }
__device__ __forceinline__ void bar_sync(int id, int n) { asm volatile("bar.sync %0, %1;" ::"r"(id), "r"(n) : "memory"); }
__device__ __forceinline__ void bar_arrive(int id, int n) { asm volatile("bar.arrive %0, %1;" ::"r"(id), "r"(n) : "memory"); }
#define WG_FENCE() asm volatile("wgmma.fence.sync.aligned;" ::: "memory")
#define WG_COMMIT() asm volatile("wgmma.commit_group.sync.aligned;" ::: "memory")
#define WG_WAIT(n) asm volatile("wgmma.wait_group.sync.aligned %0;" ::"n"(n) : "memory")
__device__ __forceinline__ uint64_t mkdesc(uint32_t addr, uint32_t lbo, uint32_t sbo, uint32_t sw) {
  return (uint64_t)((addr & 0x3FFFF) >> 4) | ((uint64_t)(lbo >> 4) << 16) | ((uint64_t)(sbo >> 4) << 32) |
         ((uint64_t)sw << 62);
}
template <int N> __device__ __forceinline__ void fence_regs(float (&r)[N]) {
#pragma unroll
  for (int i = 0; i < N; i++) asm volatile("" : "+f"(r[i])::"memory");
}
__device__ __forceinline__ uint32_t pack_bf16(float lo, float hi) {
  uint32_t r;
  asm("cvt.rn.bf16x2.f32 %0, %1, %2;" : "=r"(r) : "f"(hi), "f"(lo));
  return r;
}
__device__ __forceinline__ float bf_lo(uint32_t v) { return __uint_as_float(v << 16); }
__device__ __forceinline__ float bf_hi(uint32_t v) { return __uint_as_float(v & 0xffff0000u); }
__device__ __forceinline__ float ex2(float x) {
  float y;
  asm("ex2.approx.ftz.f32 %0, %1;" : "=f"(y) : "f"(x));
  return y;
}
__device__ __forceinline__ uint4 ldg_nc(const void* p) {
  uint4 v;
  asm volatile("ld.global.nc.L1::no_allocate.v4.u32 {%0, %1, %2, %3}, [%4];"
               : "=r"(v.x), "=r"(v.y), "=r"(v.z), "=r"(v.w) : "l"(p));
  return v;
}

__device__ __forceinline__ uint4 ld_relaxed(const uint4* p) {
  uint64_t a, b;
  asm volatile("ld.relaxed.gpu.global.v2.u64 {%0, %1}, [%2];" : "=l"(a), "=l"(b) : "l"(p) : "memory");
  return make_uint4((uint32_t)a, (uint32_t)(a >> 32), (uint32_t)b, (uint32_t)(b >> 32));
}
__device__ __forceinline__ void st_relaxed(uint4* p, float x, float y, uint32_t tag) {
  const uint64_t a = ((uint64_t)tag << 32) | __float_as_uint(x), b = ((uint64_t)tag << 32) | __float_as_uint(y);
  asm volatile("st.relaxed.gpu.global.v2.u64 [%0], {%1, %2};" ::"l"(p), "l"(a), "l"(b) : "memory");
}
__device__ __forceinline__ void tma3d(uint32_t dst, const CUtensorMap* m, int c1, int c2, uint32_t bar) {
  asm volatile("cp.async.bulk.tensor.3d.shared::cluster.global.mbarrier::complete_tx::bytes [%0], [%1, {%3, %4, %5}], [%2];"
               ::"r"(dst), "l"(m), "r"(bar), "r"(0), "r"(c1), "r"(c2) : "memory");
}
#define ACC8(a, v) do { a[0] += bf_lo(v.x); a[1] += bf_hi(v.x); a[2] += bf_lo(v.y); a[3] += bf_hi(v.y); \
                        a[4] += bf_lo(v.z); a[5] += bf_hi(v.z); a[6] += bf_lo(v.w); a[7] += bf_hi(v.w); } while (0)

__device__ __forceinline__ void wgmma_ss_n224(float (&d)[112], uint64_t da, uint64_t db, int sd) {
  asm volatile("{\n.reg .pred p;\nsetp.ne.b32 p, %114, 0;\n"
      "wgmma.mma_async.sync.aligned.m64n224k16.f32.bf16.bf16 {"
      "%0, %1, %2, %3, %4, %5, %6, %7, %8, %9, %10, %11, %12, %13, %14, %15, "
      "%16, %17, %18, %19, %20, %21, %22, %23, %24, %25, %26, %27, %28, %29, %30, %31, "
      "%32, %33, %34, %35, %36, %37, %38, %39, %40, %41, %42, %43, %44, %45, %46, %47, "
      "%48, %49, %50, %51, %52, %53, %54, %55, %56, %57, %58, %59, %60, %61, %62, %63, "
      "%64, %65, %66, %67, %68, %69, %70, %71, %72, %73, %74, %75, %76, %77, %78, %79, "
      "%80, %81, %82, %83, %84, %85, %86, %87, %88, %89, %90, %91, %92, %93, %94, %95, "
      "%96, %97, %98, %99, %100, %101, %102, %103, %104, %105, %106, %107, %108, %109, %110, %111"
      "}, %112, %113, p, 1, 1, 0, 1;\n}\n"
    : "+f"(d[0]), "+f"(d[1]), "+f"(d[2]), "+f"(d[3]), "+f"(d[4]), "+f"(d[5]), "+f"(d[6]), "+f"(d[7]),
      "+f"(d[8]), "+f"(d[9]), "+f"(d[10]), "+f"(d[11]), "+f"(d[12]), "+f"(d[13]), "+f"(d[14]), "+f"(d[15]),
      "+f"(d[16]), "+f"(d[17]), "+f"(d[18]), "+f"(d[19]), "+f"(d[20]), "+f"(d[21]), "+f"(d[22]), "+f"(d[23]),
      "+f"(d[24]), "+f"(d[25]), "+f"(d[26]), "+f"(d[27]), "+f"(d[28]), "+f"(d[29]), "+f"(d[30]), "+f"(d[31]),
      "+f"(d[32]), "+f"(d[33]), "+f"(d[34]), "+f"(d[35]), "+f"(d[36]), "+f"(d[37]), "+f"(d[38]), "+f"(d[39]),
      "+f"(d[40]), "+f"(d[41]), "+f"(d[42]), "+f"(d[43]), "+f"(d[44]), "+f"(d[45]), "+f"(d[46]), "+f"(d[47]),
      "+f"(d[48]), "+f"(d[49]), "+f"(d[50]), "+f"(d[51]), "+f"(d[52]), "+f"(d[53]), "+f"(d[54]), "+f"(d[55]),
      "+f"(d[56]), "+f"(d[57]), "+f"(d[58]), "+f"(d[59]), "+f"(d[60]), "+f"(d[61]), "+f"(d[62]), "+f"(d[63]),
      "+f"(d[64]), "+f"(d[65]), "+f"(d[66]), "+f"(d[67]), "+f"(d[68]), "+f"(d[69]), "+f"(d[70]), "+f"(d[71]),
      "+f"(d[72]), "+f"(d[73]), "+f"(d[74]), "+f"(d[75]), "+f"(d[76]), "+f"(d[77]), "+f"(d[78]), "+f"(d[79]),
      "+f"(d[80]), "+f"(d[81]), "+f"(d[82]), "+f"(d[83]), "+f"(d[84]), "+f"(d[85]), "+f"(d[86]), "+f"(d[87]),
      "+f"(d[88]), "+f"(d[89]), "+f"(d[90]), "+f"(d[91]), "+f"(d[92]), "+f"(d[93]), "+f"(d[94]), "+f"(d[95]),
      "+f"(d[96]), "+f"(d[97]), "+f"(d[98]), "+f"(d[99]), "+f"(d[100]), "+f"(d[101]), "+f"(d[102]), "+f"(d[103]),
      "+f"(d[104]), "+f"(d[105]), "+f"(d[106]), "+f"(d[107]), "+f"(d[108]), "+f"(d[109]), "+f"(d[110]), "+f"(d[111])
    : "l"(da), "l"(db), "r"(sd));
}
__device__ __forceinline__ void wgmma_ss_n208(float (&d)[104], uint64_t da, uint64_t db, int sd) {
  asm volatile("{\n.reg .pred p;\nsetp.ne.b32 p, %106, 0;\n"
      "wgmma.mma_async.sync.aligned.m64n208k16.f32.bf16.bf16 {"
      "%0, %1, %2, %3, %4, %5, %6, %7, %8, %9, %10, %11, %12, %13, %14, %15, "
      "%16, %17, %18, %19, %20, %21, %22, %23, %24, %25, %26, %27, %28, %29, %30, %31, "
      "%32, %33, %34, %35, %36, %37, %38, %39, %40, %41, %42, %43, %44, %45, %46, %47, "
      "%48, %49, %50, %51, %52, %53, %54, %55, %56, %57, %58, %59, %60, %61, %62, %63, "
      "%64, %65, %66, %67, %68, %69, %70, %71, %72, %73, %74, %75, %76, %77, %78, %79, "
      "%80, %81, %82, %83, %84, %85, %86, %87, %88, %89, %90, %91, %92, %93, %94, %95, "
      "%96, %97, %98, %99, %100, %101, %102, %103"
      "}, %104, %105, p, 1, 1, 0, 1;\n}\n"
    : "+f"(d[0]), "+f"(d[1]), "+f"(d[2]), "+f"(d[3]), "+f"(d[4]), "+f"(d[5]), "+f"(d[6]), "+f"(d[7]),
      "+f"(d[8]), "+f"(d[9]), "+f"(d[10]), "+f"(d[11]), "+f"(d[12]), "+f"(d[13]), "+f"(d[14]), "+f"(d[15]),
      "+f"(d[16]), "+f"(d[17]), "+f"(d[18]), "+f"(d[19]), "+f"(d[20]), "+f"(d[21]), "+f"(d[22]), "+f"(d[23]),
      "+f"(d[24]), "+f"(d[25]), "+f"(d[26]), "+f"(d[27]), "+f"(d[28]), "+f"(d[29]), "+f"(d[30]), "+f"(d[31]),
      "+f"(d[32]), "+f"(d[33]), "+f"(d[34]), "+f"(d[35]), "+f"(d[36]), "+f"(d[37]), "+f"(d[38]), "+f"(d[39]),
      "+f"(d[40]), "+f"(d[41]), "+f"(d[42]), "+f"(d[43]), "+f"(d[44]), "+f"(d[45]), "+f"(d[46]), "+f"(d[47]),
      "+f"(d[48]), "+f"(d[49]), "+f"(d[50]), "+f"(d[51]), "+f"(d[52]), "+f"(d[53]), "+f"(d[54]), "+f"(d[55]),
      "+f"(d[56]), "+f"(d[57]), "+f"(d[58]), "+f"(d[59]), "+f"(d[60]), "+f"(d[61]), "+f"(d[62]), "+f"(d[63]),
      "+f"(d[64]), "+f"(d[65]), "+f"(d[66]), "+f"(d[67]), "+f"(d[68]), "+f"(d[69]), "+f"(d[70]), "+f"(d[71]),
      "+f"(d[72]), "+f"(d[73]), "+f"(d[74]), "+f"(d[75]), "+f"(d[76]), "+f"(d[77]), "+f"(d[78]), "+f"(d[79]),
      "+f"(d[80]), "+f"(d[81]), "+f"(d[82]), "+f"(d[83]), "+f"(d[84]), "+f"(d[85]), "+f"(d[86]), "+f"(d[87]),
      "+f"(d[88]), "+f"(d[89]), "+f"(d[90]), "+f"(d[91]), "+f"(d[92]), "+f"(d[93]), "+f"(d[94]), "+f"(d[95]),
      "+f"(d[96]), "+f"(d[97]), "+f"(d[98]), "+f"(d[99]), "+f"(d[100]), "+f"(d[101]), "+f"(d[102]), "+f"(d[103])
    : "l"(da), "l"(db), "r"(sd));
}
__device__ __forceinline__ void wgmma_ss_n168(float (&d)[84], uint64_t da, uint64_t db, int sd) {
  asm volatile("{\n.reg .pred p;\nsetp.ne.b32 p, %86, 0;\n"
      "wgmma.mma_async.sync.aligned.m64n168k16.f32.bf16.bf16 {"
      "%0, %1, %2, %3, %4, %5, %6, %7, %8, %9, %10, %11, %12, %13, %14, %15, "
      "%16, %17, %18, %19, %20, %21, %22, %23, %24, %25, %26, %27, %28, %29, %30, %31, "
      "%32, %33, %34, %35, %36, %37, %38, %39, %40, %41, %42, %43, %44, %45, %46, %47, "
      "%48, %49, %50, %51, %52, %53, %54, %55, %56, %57, %58, %59, %60, %61, %62, %63, "
      "%64, %65, %66, %67, %68, %69, %70, %71, %72, %73, %74, %75, %76, %77, %78, %79, "
      "%80, %81, %82, %83"
      "}, %84, %85, p, 1, 1, 0, 1;\n}\n"
    : "+f"(d[0]), "+f"(d[1]), "+f"(d[2]), "+f"(d[3]), "+f"(d[4]), "+f"(d[5]), "+f"(d[6]), "+f"(d[7]),
      "+f"(d[8]), "+f"(d[9]), "+f"(d[10]), "+f"(d[11]), "+f"(d[12]), "+f"(d[13]), "+f"(d[14]), "+f"(d[15]),
      "+f"(d[16]), "+f"(d[17]), "+f"(d[18]), "+f"(d[19]), "+f"(d[20]), "+f"(d[21]), "+f"(d[22]), "+f"(d[23]),
      "+f"(d[24]), "+f"(d[25]), "+f"(d[26]), "+f"(d[27]), "+f"(d[28]), "+f"(d[29]), "+f"(d[30]), "+f"(d[31]),
      "+f"(d[32]), "+f"(d[33]), "+f"(d[34]), "+f"(d[35]), "+f"(d[36]), "+f"(d[37]), "+f"(d[38]), "+f"(d[39]),
      "+f"(d[40]), "+f"(d[41]), "+f"(d[42]), "+f"(d[43]), "+f"(d[44]), "+f"(d[45]), "+f"(d[46]), "+f"(d[47]),
      "+f"(d[48]), "+f"(d[49]), "+f"(d[50]), "+f"(d[51]), "+f"(d[52]), "+f"(d[53]), "+f"(d[54]), "+f"(d[55]),
      "+f"(d[56]), "+f"(d[57]), "+f"(d[58]), "+f"(d[59]), "+f"(d[60]), "+f"(d[61]), "+f"(d[62]), "+f"(d[63]),
      "+f"(d[64]), "+f"(d[65]), "+f"(d[66]), "+f"(d[67]), "+f"(d[68]), "+f"(d[69]), "+f"(d[70]), "+f"(d[71]),
      "+f"(d[72]), "+f"(d[73]), "+f"(d[74]), "+f"(d[75]), "+f"(d[76]), "+f"(d[77]), "+f"(d[78]), "+f"(d[79]),
      "+f"(d[80]), "+f"(d[81]), "+f"(d[82]), "+f"(d[83])
    : "l"(da), "l"(db), "r"(sd));
}
__device__ __forceinline__ void wgmma_ss_n160(float (&d)[80], uint64_t da, uint64_t db, int sd) {
  asm volatile("{\n.reg .pred p;\nsetp.ne.b32 p, %82, 0;\n"
      "wgmma.mma_async.sync.aligned.m64n160k16.f32.bf16.bf16 {"
      "%0, %1, %2, %3, %4, %5, %6, %7, %8, %9, %10, %11, %12, %13, %14, %15, "
      "%16, %17, %18, %19, %20, %21, %22, %23, %24, %25, %26, %27, %28, %29, %30, %31, "
      "%32, %33, %34, %35, %36, %37, %38, %39, %40, %41, %42, %43, %44, %45, %46, %47, "
      "%48, %49, %50, %51, %52, %53, %54, %55, %56, %57, %58, %59, %60, %61, %62, %63, "
      "%64, %65, %66, %67, %68, %69, %70, %71, %72, %73, %74, %75, %76, %77, %78, %79"
      "}, %80, %81, p, 1, 1, 0, 1;\n}\n"
    : "+f"(d[0]), "+f"(d[1]), "+f"(d[2]), "+f"(d[3]), "+f"(d[4]), "+f"(d[5]), "+f"(d[6]), "+f"(d[7]),
      "+f"(d[8]), "+f"(d[9]), "+f"(d[10]), "+f"(d[11]), "+f"(d[12]), "+f"(d[13]), "+f"(d[14]), "+f"(d[15]),
      "+f"(d[16]), "+f"(d[17]), "+f"(d[18]), "+f"(d[19]), "+f"(d[20]), "+f"(d[21]), "+f"(d[22]), "+f"(d[23]),
      "+f"(d[24]), "+f"(d[25]), "+f"(d[26]), "+f"(d[27]), "+f"(d[28]), "+f"(d[29]), "+f"(d[30]), "+f"(d[31]),
      "+f"(d[32]), "+f"(d[33]), "+f"(d[34]), "+f"(d[35]), "+f"(d[36]), "+f"(d[37]), "+f"(d[38]), "+f"(d[39]),
      "+f"(d[40]), "+f"(d[41]), "+f"(d[42]), "+f"(d[43]), "+f"(d[44]), "+f"(d[45]), "+f"(d[46]), "+f"(d[47]),
      "+f"(d[48]), "+f"(d[49]), "+f"(d[50]), "+f"(d[51]), "+f"(d[52]), "+f"(d[53]), "+f"(d[54]), "+f"(d[55]),
      "+f"(d[56]), "+f"(d[57]), "+f"(d[58]), "+f"(d[59]), "+f"(d[60]), "+f"(d[61]), "+f"(d[62]), "+f"(d[63]),
      "+f"(d[64]), "+f"(d[65]), "+f"(d[66]), "+f"(d[67]), "+f"(d[68]), "+f"(d[69]), "+f"(d[70]), "+f"(d[71]),
      "+f"(d[72]), "+f"(d[73]), "+f"(d[74]), "+f"(d[75]), "+f"(d[76]), "+f"(d[77]), "+f"(d[78]), "+f"(d[79])
    : "l"(da), "l"(db), "r"(sd));
}
__device__ __forceinline__ void wgmma_ss_n88(float (&d)[44], uint64_t da, uint64_t db, int sd) {
  asm volatile("{\n.reg .pred p;\nsetp.ne.b32 p, %46, 0;\n"
      "wgmma.mma_async.sync.aligned.m64n88k16.f32.bf16.bf16 {"
      "%0, %1, %2, %3, %4, %5, %6, %7, %8, %9, %10, %11, %12, %13, %14, %15, "
      "%16, %17, %18, %19, %20, %21, %22, %23, %24, %25, %26, %27, %28, %29, %30, %31, "
      "%32, %33, %34, %35, %36, %37, %38, %39, %40, %41, %42, %43"
      "}, %44, %45, p, 1, 1, 0, 1;\n}\n"
    : "+f"(d[0]), "+f"(d[1]), "+f"(d[2]), "+f"(d[3]), "+f"(d[4]), "+f"(d[5]), "+f"(d[6]), "+f"(d[7]),
      "+f"(d[8]), "+f"(d[9]), "+f"(d[10]), "+f"(d[11]), "+f"(d[12]), "+f"(d[13]), "+f"(d[14]), "+f"(d[15]),
      "+f"(d[16]), "+f"(d[17]), "+f"(d[18]), "+f"(d[19]), "+f"(d[20]), "+f"(d[21]), "+f"(d[22]), "+f"(d[23]),
      "+f"(d[24]), "+f"(d[25]), "+f"(d[26]), "+f"(d[27]), "+f"(d[28]), "+f"(d[29]), "+f"(d[30]), "+f"(d[31]),
      "+f"(d[32]), "+f"(d[33]), "+f"(d[34]), "+f"(d[35]), "+f"(d[36]), "+f"(d[37]), "+f"(d[38]), "+f"(d[39]),
      "+f"(d[40]), "+f"(d[41]), "+f"(d[42]), "+f"(d[43])
    : "l"(da), "l"(db), "r"(sd));
}
__device__ __forceinline__ void wgmma_ss_n80(float (&d)[40], uint64_t da, uint64_t db, int sd) {
  asm volatile("{\n.reg .pred p;\nsetp.ne.b32 p, %42, 0;\n"
      "wgmma.mma_async.sync.aligned.m64n80k16.f32.bf16.bf16 {"
      "%0, %1, %2, %3, %4, %5, %6, %7, %8, %9, %10, %11, %12, %13, %14, %15, "
      "%16, %17, %18, %19, %20, %21, %22, %23, %24, %25, %26, %27, %28, %29, %30, %31, "
      "%32, %33, %34, %35, %36, %37, %38, %39"
      "}, %40, %41, p, 1, 1, 0, 1;\n}\n"
    : "+f"(d[0]), "+f"(d[1]), "+f"(d[2]), "+f"(d[3]), "+f"(d[4]), "+f"(d[5]), "+f"(d[6]), "+f"(d[7]),
      "+f"(d[8]), "+f"(d[9]), "+f"(d[10]), "+f"(d[11]), "+f"(d[12]), "+f"(d[13]), "+f"(d[14]), "+f"(d[15]),
      "+f"(d[16]), "+f"(d[17]), "+f"(d[18]), "+f"(d[19]), "+f"(d[20]), "+f"(d[21]), "+f"(d[22]), "+f"(d[23]),
      "+f"(d[24]), "+f"(d[25]), "+f"(d[26]), "+f"(d[27]), "+f"(d[28]), "+f"(d[29]), "+f"(d[30]), "+f"(d[31]),
      "+f"(d[32]), "+f"(d[33]), "+f"(d[34]), "+f"(d[35]), "+f"(d[36]), "+f"(d[37]), "+f"(d[38]), "+f"(d[39])
    : "l"(da), "l"(db), "r"(sd));
}
__device__ __forceinline__ void wgmma_rs_n128(float (&d)[64], uint32_t a0, uint32_t a1, uint32_t a2, uint32_t a3,
                                  uint64_t db, int sd) {
  asm volatile("{\n.reg .pred p;\nsetp.ne.b32 p, %69, 0;\n"
      "wgmma.mma_async.sync.aligned.m64n128k16.f32.bf16.bf16 {"
      "%0, %1, %2, %3, %4, %5, %6, %7, %8, %9, %10, %11, %12, %13, %14, %15, "
      "%16, %17, %18, %19, %20, %21, %22, %23, %24, %25, %26, %27, %28, %29, %30, %31, "
      "%32, %33, %34, %35, %36, %37, %38, %39, %40, %41, %42, %43, %44, %45, %46, %47, "
      "%48, %49, %50, %51, %52, %53, %54, %55, %56, %57, %58, %59, %60, %61, %62, %63"
      "}, {%64, %65, %66, %67}, %68, p, 1, 1, 0;\n}\n"
    : "+f"(d[0]), "+f"(d[1]), "+f"(d[2]), "+f"(d[3]), "+f"(d[4]), "+f"(d[5]), "+f"(d[6]), "+f"(d[7]),
      "+f"(d[8]), "+f"(d[9]), "+f"(d[10]), "+f"(d[11]), "+f"(d[12]), "+f"(d[13]), "+f"(d[14]), "+f"(d[15]),
      "+f"(d[16]), "+f"(d[17]), "+f"(d[18]), "+f"(d[19]), "+f"(d[20]), "+f"(d[21]), "+f"(d[22]), "+f"(d[23]),
      "+f"(d[24]), "+f"(d[25]), "+f"(d[26]), "+f"(d[27]), "+f"(d[28]), "+f"(d[29]), "+f"(d[30]), "+f"(d[31]),
      "+f"(d[32]), "+f"(d[33]), "+f"(d[34]), "+f"(d[35]), "+f"(d[36]), "+f"(d[37]), "+f"(d[38]), "+f"(d[39]),
      "+f"(d[40]), "+f"(d[41]), "+f"(d[42]), "+f"(d[43]), "+f"(d[44]), "+f"(d[45]), "+f"(d[46]), "+f"(d[47]),
      "+f"(d[48]), "+f"(d[49]), "+f"(d[50]), "+f"(d[51]), "+f"(d[52]), "+f"(d[53]), "+f"(d[54]), "+f"(d[55]),
      "+f"(d[56]), "+f"(d[57]), "+f"(d[58]), "+f"(d[59]), "+f"(d[60]), "+f"(d[61]), "+f"(d[62]), "+f"(d[63])
    : "r"(a0), "r"(a1), "r"(a2), "r"(a3), "l"(db), "r"(sd));
}
__device__ __forceinline__ void wgmma_rs_n24(float (&d)[12], uint32_t a0, uint32_t a1, uint32_t a2, uint32_t a3,
                                  uint64_t db, int sd) {
  asm volatile("{\n.reg .pred p;\nsetp.ne.b32 p, %17, 0;\n"
      "wgmma.mma_async.sync.aligned.m64n24k16.f32.bf16.bf16 {"
      "%0, %1, %2, %3, %4, %5, %6, %7, %8, %9, %10, %11"
      "}, {%12, %13, %14, %15}, %16, p, 1, 1, 1;\n}\n"
    : "+f"(d[0]), "+f"(d[1]), "+f"(d[2]), "+f"(d[3]), "+f"(d[4]), "+f"(d[5]), "+f"(d[6]), "+f"(d[7]),
      "+f"(d[8]), "+f"(d[9]), "+f"(d[10]), "+f"(d[11])
    : "r"(a0), "r"(a1), "r"(a2), "r"(a3), "l"(db), "r"(sd));
}

#define KST 4
#define K1_EC 6
#define K1S 4
constexpr int K1_ST = K1S, K1_STAGE = 45056;
constexpr int K1_SMEM = K1_ST * K1_STAGE + 640   + 1536   + 2560   + 128;

__device__ __forceinline__ float2 row_stats(uint4 v0, uint4 v1, uint4 v2) {
  const uint32_t wd[12] = {v0.x, v0.y, v0.z, v0.w, v1.x, v1.y, v1.z, v1.w, v2.x, v2.y, v2.z, v2.w};
  float sx = 0.f, sq = 0.f;
#pragma unroll
  for (int e = 0; e < 12; e++) {
    const float lo = bf_lo(wd[e]), hi = bf_hi(wd[e]);
    sx += lo + hi; sq = fmaf(lo, lo, fmaf(hi, hi, sq));
  }
#pragma unroll
  for (int o = 16; o; o >>= 1) { sx += __shfl_xor_sync(~0u, sx, o); sq += __shfl_xor_sync(~0u, sq, o); }
  const float mean = sx * (1.f / D_);
  return make_float2(rsqrtf(fmaxf(sq * (1.f / D_) - mean * mean, 0.f) + 1e-5f), mean);
}

__global__ void __cluster_dims__(2, 1, 1) __launch_bounds__(512, 1)
k1_qkv(const __grid_constant__ CUtensorMap tmx, const __grid_constant__ CUtensorMap tmw,
       const bf16* __restrict__ x, const bf16* __restrict__ w, const bf16* __restrict__ wo) {
  extern __shared__ __align__(1024) uint8_t sm[];
  float* cs = (float*)(sm + K1_ST * K1_STAGE);
  float2* rowab = (float2*)(sm + K1_ST * K1_STAGE + 640);
  float* red = (float*)(sm + K1_ST * K1_STAGE + 2176);
  const uint32_t sbase = smem_u32(sm);
  const uint32_t fullb = sbase + K1_ST * K1_STAGE + 4736, emptyb = fullb + 8 * K1_ST;
  const int tid = threadIdx.x, lane = tid & 31;
  const int warp = __shfl_sync(~0u, tid >> 5, 0);
  const int rank = blockIdx.x & 1, cl = blockIdx.x >> 1;
  const int m = cl / 6, n = (cl - m * 6) * 2 + rank;
  if (tid == 0) STAMP(0, 0);

  if (warp == 12) {
    if (lane == 0) {
      prefetch_map(&tmx); prefetch_map(&tmw);
      for (int i = 0; i < K1_ST; i++) { mbar_init(fullb + 8 * i, 1); mbar_init(emptyb + 8 * i, K1_EC); }
      asm volatile("fence.mbarrier_init.release.cluster;" ::: "memory");
    }
    __syncwarp();
    cluster_arrive();
    bar_arrive(4, 512);
    if (lane == 0) {
      for (int kt = 0; kt < K1_ST; kt++) mbar_expect(fullb + 8 * kt, K1_STAGE);
#pragma unroll
      for (int j = 0; j < 5; j++) tma2d(sbase + 24576 + j * 4096, &tmw, n * 160 + j * 32, 0, fullb);
    }
    __syncwarp();
    cluster_wait();
    if (lane == 0) {
#pragma unroll 1
      for (int kt = 0; kt < 10; kt++) {
        const int s = kt % K1_ST;
        const uint32_t sa = sbase + s * K1_STAGE;
        if (kt >= K1_ST) {
          mbar_wait(emptyb + 8 * s, ((kt / K1_ST) - 1) & 1);
          mbar_expect(fullb + 8 * s, K1_STAGE);
        }
        tma2d_mc(sa + rank * 12288, &tmx, kt * 64, m * 192 + rank * 96, fullb + 8 * s);
        if (kt > 0) {
#pragma unroll
          for (int j = 0; j < 5; j++) tma2d(sa + 24576 + j * 4096, &tmw, n * 160 + j * 32, kt * 64, fullb + 8 * s);
        }
        if (kt == K1_ST - 1) {
          if (m * 192 + n * 16 < S_)
            asm volatile("cp.async.bulk.prefetch.L2.global [%0], %1;" ::"l"(x + (size_t)(m * 192 + n * 16) * D_), "r"(16 * D_ * 2) : "memory");
          if (m >= K1_ST && m < 10) {
#pragma unroll
            for (int j = 0; j < 5; j++)
              asm volatile("cp.async.bulk.prefetch.tensor.2d.L2.global [%0, {%1, %2}];" ::"l"(&tmw), "r"(n * 160 + j * 32), "r"(m * 64) : "memory");
          }
          pdl_trigger();
        }
      }
    }
    __syncwarp();
    cluster_arrive();
  } else if (warp > 12) {
    cluster_arrive();
    const int t96 = tid - 416;
    const uint32_t tag = __ldcg(&g_epoch) + 1;
    bar_sync(4, 512);
    mbar_wait(fullb, 0);
    if (m < 10) {
      const int ck = t96 % 20, rg = min(t96 / 20, 3);
      uint4 wv[16];
#pragma unroll
      for (int i = 0; i < 16; i++) wv[i] = ldg_nc(w + (size_t)(m * 64 + rg * 16 + i) * 1920 + n * 160 + ck * 8);
      float acc8[8];
#pragma unroll
      for (int i = 0; i < 8; i++) acc8[i] = 0.f;
#pragma unroll
      for (int i = 0; i < 16; i++) ACC8(acc8, wv[i]);
      *(float4*)&red[rg * 160 + ck * 8] = make_float4(acc8[0], acc8[1], acc8[2], acc8[3]);
      *(float4*)&red[rg * 160 + ck * 8 + 4] = make_float4(acc8[4], acc8[5], acc8[6], acc8[7]);
      bar_sync(1, 96);
      if (t96 < 80) {
        const float2 p0 = *(const float2*)&red[t96 * 2], p1 = *(const float2*)&red[160 + t96 * 2];
        const float2 p2 = *(const float2*)&red[320 + t96 * 2], p3 = *(const float2*)&red[480 + t96 * 2];
        st_relaxed(&g_cpart[(m * 12 + n) * 80 + t96], (p0.x + p1.x) + (p2.x + p3.x), (p0.y + p1.y) + (p2.y + p3.y), tag);
      }
    }
    if (tid == 416) STAMP(5, 7);
    bool ok = false;
    for (int it = 0; it < 64 && !ok; it++) {
      uint4 p[10], st[2];
#pragma unroll
      for (int k = 0; k < 10; k++) p[k] = ld_relaxed(&g_cpart[(k * 12 + n) * 80 + min(t96, 79)]);
#pragma unroll
      for (int k = 0; k < 2; k++) st[k] = ld_relaxed(&g_rowstat[min(m * 192 + k * 96 + t96, S_ - 1)]);
      ok = true;
      float s0 = 0.f, s1 = 0.f;
#pragma unroll
      for (int k = 0; k < 10; k++) {
        ok = ok && p[k].y == tag && p[k].w == tag;
        s0 += __uint_as_float(p[k].x); s1 += __uint_as_float(p[k].z);
      }
      if (t96 < 80) *(float2*)&cs[t96 * 2] = make_float2(s0, s1);
#pragma unroll
      for (int k = 0; k < 2; k++) {
        ok = ok && st[k].y == tag && st[k].w == tag;
        rowab[k * 96 + t96] = make_float2(__uint_as_float(st[k].x), -__uint_as_float(st[k].x) * __uint_as_float(st[k].z));
      }
      ok = __all_sync(~0u, ok);
      if (!ok) __nanosleep(300);
    }
    if (!ok) {
      const int c2 = min(t96, 79);
      float s0 = 0.f, s1 = 0.f;
#pragma unroll 1
      for (int k = 0; k < D_; k++) {
        const uint32_t v = *(const uint32_t*)(w + (size_t)k * 1920 + n * 160 + c2 * 2);
        s0 += bf_lo(v); s1 += bf_hi(v);
      }
      if (t96 < 80) *(float2*)&cs[t96 * 2] = make_float2(s0, s1);
#pragma unroll 1
      for (int i = 0; i < 64; i++) {
        const int r = (i >> 5) * 96 + (t96 & ~31) + (i & 31);
        const bf16* xr = x + (size_t)min(m * 192 + r, S_ - 1) * D_ + lane * 8;
        const float2 st = row_stats(ldg_nc(xr), ldg_nc(xr + 256), lane < 16 ? ldg_nc(xr + 512) : make_uint4(0u, 0u, 0u, 0u));
        if (lane == 0) rowab[r] = make_float2(st.x, -st.x * st.y);
      }
    }
    __syncwarp();
    bar_arrive(2, 96 + 384);
    bar_sync(1, 96);
    if (tid == 416) STAMP(0, 5);
    if (blockIdx.x < 128) {
      uint4 v[5];
      const int ck = min(t96, 79), nt = ck / 10;
#pragma unroll
      for (int i = 0; i < 5; i++) {
        const int k = blockIdx.x * 5 + i, pr = k / 40, r = k - pr * 40;
        v[i] = ldg_nc(wo + (size_t)(pr * 40 + (r < 16 ? r : (r < 32 ? r + 4 : (r < 36 ? r - 16 : r)))) * D_ + ck * 8);
      }
#pragma unroll
      for (int i = 0; i < 5; i++) {
        const int k = blockIdx.x * 5 + i;
        g_wo[((nt * 10 + (k >> 6)) * 10 + ck - nt * 10) * 64 + (k & 63)] = v[i];
        float t = ((bf_lo(v[i].x) + bf_hi(v[i].x)) + (bf_lo(v[i].y) + bf_hi(v[i].y))) +
                  ((bf_lo(v[i].z) + bf_hi(v[i].z)) + (bf_lo(v[i].w) + bf_hi(v[i].w)));
        if (t96 >= 80) t = 0.f;
#pragma unroll
        for (int o = 16; o; o >>= 1) t += __shfl_xor_sync(~0u, t, o);
        if (lane == 0) red[(t96 >> 5) * 8 + i] = t;
      }
      bar_sync(1, 96);
      if (t96 < 5) {
        const float mu = (red[t96] + red[8 + t96] + red[16 + t96]) * (1.f / D_);
        const float hi = bf_lo(pack_bf16(mu, 0.f));
        g_wm[blockIdx.x * 5 + t96] = make_uint4(pack_bf16(hi, mu - hi), 0u, 0u, 0u);
      }
    }
    if (tid == 416) STAMP(0, 7);
    __syncwarp();
    cluster_wait();
    cluster_arrive();
  } else {
    cluster_arrive();
    float acc[80];
    const uint64_t da0 = mkdesc(sbase + (warp >> 2) * 8192, 16, 1024, 1);
    const uint64_t db0 = mkdesc(sbase + 24576, 4096, 512, 2);
    const uint32_t tag = __ldcg(&g_epoch) + 1;
    const int srow = m * 192 + n * 16 + warp * 2;
    const bool dostat = warp < 8 && srow < S_;
    uint4 xv[2][3];
    bar_sync(4, 512);
    cluster_wait();
#pragma unroll
    for (int kt = 0; kt < 10; kt++) {
      const int s = kt % K1_ST;
      mbar_wait(fullb + 8 * s, (kt / K1_ST) & 1);
      if (kt == 0 && tid == 0) STAMP(0, 1);
      if (kt == 2 && tid == 0) STAMP(5, 0);
      if (kt == 4 && tid == 0) STAMP(5, 1);
      if (kt == 7 && tid == 0) STAMP(5, 2);
      const uint64_t da = da0 + s * (K1_STAGE >> 4), db = db0 + s * (K1_STAGE >> 4);
      WG_FENCE();
#pragma unroll
      for (int k = 0; k < 4; k++) wgmma_ss_n160(acc, da + k * 2, db + k * 64, (kt | k) != 0);
      WG_COMMIT();
      if (kt > 0) {
        WG_WAIT(1);
        if (kt - 1 + K1_ST < 10 && (tid & 127) < 2) mbar_arrive_cta(emptyb + 8 * ((kt - 1) % K1_ST), tid & 1);
      }
      if (kt == 0) {
#pragma unroll
        for (int i = 0; i < 2; i++) {
          const bf16* xr = x + (size_t)min(srow + i, S_ - 1) * D_ + lane * 8;
          xv[i][0] = xv[i][1] = xv[i][2] = make_uint4(0u, 0u, 0u, 0u);
          if (dostat) { xv[i][0] = ldg_nc(xr); xv[i][1] = ldg_nc(xr + 256); }
          if (dostat && lane < 16) xv[i][2] = ldg_nc(xr + 512);
        }
      }
      if ((kt == KST || kt == KST + 1) && dostat) {
        const float2 st = row_stats(xv[kt - KST][0], xv[kt - KST][1], xv[kt - KST][2]);
        if (lane == 0) st_relaxed(&g_rowstat[srow + kt - KST], st.x, st.y, tag);
      }
      __syncwarp();
    }
    cluster_arrive();
    WG_WAIT(0);
    fence_regs(acc);
    if (tid == 0) STAMP(0, 2);
    bar_sync(2, 96 + 384);
    if (tid == 0) STAMP(0, 3);
    const int row0 = m * 192 + warp * 16;
    if (row0 < S_) {
      const int g = lane >> 2, c = lane & 3, sec = n >> 2, grp = (row0 & 127) >> 3;
      const bool lo = c < 2;
      const float2 ab0 = rowab[warp * 16 + g], ab1 = rowab[warp * 16 + g + 8];
      const bool p0 = sec == 1 && ((POLY_MASK >> grp) & 1), p1 = sec == 1 && ((POLY_MASK >> (grp + 1)) & 1);
      const uint32_t padqv = sec == 0 ? (c == 2 ? 0x3F803F80u : 0x00003F80u) : (sec == 2 && c == 2 ? 0x00003F80u : 0u);
      const uint32_t padk = c == 2 ? 0x4A7A4B00u : 0x00004653u;
      const uint32_t pad0 = p0 ? padk : padqv, pad1 = p1 ? padk : padqv;
      const float f0 = sec == 0 ? QSCALE : (p0 ? 32768.f : 1.f), f1 = sec == 0 ? QSCALE : (p1 ? 32768.f : 1.f);
      const float a0 = ab0.x * f0, b0 = ab0.y * f0, a1 = ab1.x * f1, b1 = ab1.y * f1;
      const float r0 = p0 ? 9.313225746154785e-10f : 1.f, r1 = p1 ? 9.313225746154785e-10f : 1.f;
      const int cst = sec == 1 ? 2048 : 128, gst = sec == 1 ? 128 : 384;
      uint8_t* pe = (uint8_t*)g_qkv + (size_t)(n * 8) * HEAD_IMG + (row0 >> 7) * 6144 + grp * gst + lane * 4;
      uint8_t* pe1 = pe + cst;
      uint8_t* pe2 = pe1 + cst;
      uint8_t* pf = pe + gst;
      uint8_t* pf1 = pf + cst;
      uint8_t* pf2 = pf1 + cst;
#pragma unroll
      for (int hp = 0; hp < 4; hp++) {
        uint32_t u[5], v[5];
        float su[5], sv[5];
#pragma unroll
        for (int i = 0; i < 5; i++) {
          const int j = hp * 5 + i;
          const float2 t = *(const float2*)&cs[j * 8 + c * 2];
          const float x0 = fmaf(acc[4 * j], a0, b0 * t.x), x1 = fmaf(acc[4 * j + 1], a0, b0 * t.y);
          const float y0 = fmaf(acc[4 * j + 2], a1, b1 * t.x), y1 = fmaf(acc[4 * j + 3], a1, b1 * t.y);
          u[i] = pack_bf16(x0, x1); v[i] = pack_bf16(y0, y1);
          su[i] = fmaf(x0, x0, x1 * x1); sv[i] = fmaf(y0, y0, y1 * y1);
        }
        constexpr int HE = HEAD_IMG;
        const int oe = hp * 2 * HE, oo = oe + HE;
        *(uint32_t*)(pe + oe) = u[0];  *(uint32_t*)(pf + oe) = v[0];
        *(uint32_t*)(pe1 + oe) = u[1]; *(uint32_t*)(pf1 + oe) = v[1];
        *(uint32_t*)(pe2 + oe) = lo ? u[2] : pad0; *(uint32_t*)(pf2 + oe) = lo ? v[2] : pad1;
        *(uint32_t*)(pe + oo) = __shfl_xor_sync(~0u, lo ? u[3] : u[2], 2);
        *(uint32_t*)(pf + oo) = __shfl_xor_sync(~0u, lo ? v[3] : v[2], 2);
        *(uint32_t*)(pe1 + oo) = __shfl_xor_sync(~0u, lo ? u[4] : u[3], 2);
        *(uint32_t*)(pf1 + oo) = __shfl_xor_sync(~0u, lo ? v[4] : v[3], 2);
        const uint32_t tu = __shfl_xor_sync(~0u, u[4], 2), tv = __shfl_xor_sync(~0u, v[4], 2);
        *(uint32_t*)(pe2 + oo) = lo ? tu : pad0; *(uint32_t*)(pf2 + oo) = lo ? tv : pad1;
        if (sec < 2) {
          float e0 = (su[0] + su[1] + (lo ? su[2] : 0.f)) * r0, e1 = (sv[0] + sv[1] + (lo ? sv[2] : 0.f)) * r1;
          float o0 = (su[3] + su[4] + (lo ? 0.f : su[2])) * r0, o1 = (sv[3] + sv[4] + (lo ? 0.f : sv[2])) * r1;
          e0 += __shfl_xor_sync(~0u, e0, 1); e1 += __shfl_xor_sync(~0u, e1, 1);
          o0 += __shfl_xor_sync(~0u, o0, 1); o1 += __shfl_xor_sync(~0u, o1, 1);
          e0 += __shfl_xor_sync(~0u, e0, 2); e1 += __shfl_xor_sync(~0u, e1, 2);
          o0 += __shfl_xor_sync(~0u, o0, 2); o1 += __shfl_xor_sync(~0u, o1, 2);
          const uint32_t em = __reduce_max_sync(~0u, max(__float_as_uint(e0), __float_as_uint(e1)));
          const uint32_t om = __reduce_max_sync(~0u, max(__float_as_uint(o0), __float_as_uint(o1)));
          if (lane < 2) g_nrm[(n * 8 + hp * 2 + lane) * 128 + (row0 >> 4)] = __uint_as_float(lane ? om : em);
        }
      }
    }
    if (tid == 0) STAMP(0, 4);
  }
  cluster_wait();
  if (tid == 0) STAMP(0, 6);
}

constexpr int K2_SMEM = 2 * HEAD_IMG + 2 * 6144 + 2 * 10240 + 256;

__device__ __forceinline__ uint64_t desc64(uint32_t lo, uint32_t hi) {
  uint64_t d;
  asm("mov.b64 %0, {%1, %2};" : "=l"(d) : "r"(lo), "r"(hi));
  return d;
}
__device__ __forceinline__ uint32_t exp_pair(bool poly, float a, float b, uint32_t mk) {
  if (poly) {
    const uint32_t pk = __byte_perm(__float_as_uint(a), __float_as_uint(b), 0x6521);
    uint32_t m, q;
    asm("lop3.b32 %0, %1, %2, 0x3f803f80, 0xEA;" : "=r"(m) : "r"(pk), "r"(mk));
    asm("fma.rn.bf16x2 %0, %1, %1, %2;" : "=r"(q) : "r"(m), "r"(0x40014001u));
    return pk - m + q;
  }
  return pack_bf16(ex2(a), ex2(b));
}
#define PV_GR 4
__device__ __forceinline__ void exp_pv(const float (&s)[64], float (&o)[12], uint64_t dv, uint32_t mk) {
#pragma unroll
  for (int k0 = 0; k0 < 8; k0 += PV_GR) {
    uint32_t p[4 * PV_GR];
#pragma unroll
    for (int i = 0; i < 4 * PV_GR; i++)
      p[i] = exp_pair((POLY_MASK >> (k0 * 2 + i / 2)) & 1, s[k0 * 8 + 2 * i], s[k0 * 8 + 2 * i + 1], mk);
    WG_FENCE();
#pragma unroll
    for (int k = 0; k < PV_GR; k++)
      wgmma_rs_n24(o, p[4 * k], p[4 * k + 1], p[4 * k + 2], p[4 * k + 3], dv + (k0 + k) * 48, 1);
  }
}
__device__ __forceinline__ void load_q(uint32_t (&q)[6], const uint8_t* p) {
  q[0] = __ldcg((const uint32_t*)p);         q[1] = __ldcg((const uint32_t*)(p + 384));
  q[2] = __ldcg((const uint32_t*)(p + 128)); q[3] = __ldcg((const uint32_t*)(p + 512));
  q[4] = __ldcg((const uint32_t*)(p + 256)); q[5] = __ldcg((const uint32_t*)(p + 640));
}
__device__ __forceinline__ float rcp(float x) {
  float y;
  asm("rcp.approx.ftz.f32 %0, %1;" : "=f"(y) : "f"(x));
  return y;
}
__device__ __forceinline__ int img_off(int chunk) { return (chunk >> 3) * 16384 + (chunk & 7) * 128; }
__device__ __forceinline__ void store_o(const float (&o)[12], int tile) {
  int tid, bid;
  asm volatile("mov.u32 %0, %%tid.x;" : "=r"(tid));
  asm volatile("mov.u32 %0, %%ctaid.x;" : "=r"(bid));
  const int head = bid >> 2;
  uint8_t* dst = (uint8_t*)g_o + ((bid & 3) * 4 + (tile >> 1)) * 163840 + (tile & 1) * 8192 + ((tid >> 5) & 3) * 2048 + (tid & 31) * 4;
  const int oc = (head >> 1) * 5 + (head & 1) * 2;
  const int o0 = img_off(oc), o1 = img_off(oc + 1), o2 = img_off((head >> 1) * 5 + 4) + (head & 1) * 8;
  const float i0 = rcp(__shfl_sync(~0u, o[8], 2, 4)), i1 = rcp(__shfl_sync(~0u, o[10], 2, 4));
  *(uint32_t*)(dst + o0) = pack_bf16(o[0] * i0, o[1] * i0); *(uint32_t*)(dst + o0 + 1024) = pack_bf16(o[2] * i1, o[3] * i1);
  *(uint32_t*)(dst + o1) = pack_bf16(o[4] * i0, o[5] * i0); *(uint32_t*)(dst + o1 + 1024) = pack_bf16(o[6] * i1, o[7] * i1);
  if ((tid & 3) < 2) {
    *(uint32_t*)(dst + o2) = pack_bf16(o[8] * i0, o[9] * i0);
    *(uint32_t*)(dst + o2 + 1024) = pack_bf16(o[10] * i1, o[11] * i1);
  }
}

struct Maps5 { CUtensorMap m[5]; };

__global__ void __launch_bounds__(512, 1)
k2_attn(const __grid_constant__ Maps5 maps, uint32_t mk) {
  const CUtensorMap* tmw = maps.m;
  extern __shared__ __align__(1024) uint8_t sm[];
  const uint32_t sbase = smem_u32(sm);
  float* part = (float*)(sm + 2 * HEAD_IMG);
  const uint32_t rbuf = sbase + 2 * HEAD_IMG + 2 * 6144;
  const uint32_t kvb = rbuf + 2 * 10240;
  const uint32_t partb = kvb + 128, rbar = kvb + 144;
  const int tid = threadIdx.x, lane = tid & 31;
  const int warp = __shfl_sync(~0u, tid >> 5, 0);
  const int head = blockIdx.x >> 2, qb = blockIdx.x & 3;

  if (tid == 0) STAMP(1, 0);
  if (tid == 0) {
    for (int i = 0; i < 16; i++) mbar_init(kvb + 8 * i, 1);
    mbar_init(partb, 128); mbar_init(partb + 8, 128); mbar_init(rbar, 1); mbar_init(rbar + 8, 1);
    asm volatile("fence.mbarrier_init.release.cluster;" ::: "memory");
  }
  __syncthreads();

  if (warp >= 12) {
    asm volatile("setmaxnreg.dec.sync.aligned.u32 32;");
    if (tid == 384) {
      pdl_wait();
      pdl_trigger();
      const uint8_t* kimg = (const uint8_t*)g_qkv + (size_t)(32 + head) * HEAD_IMG;
#pragma unroll 1
      for (int b = 0; b < 16; b++) {
        mbar_expect(kvb + 8 * b, 12288);
        bulk_ld(sbase + b * 6144, kimg + b * 6144, 6144, kvb + 8 * b);
        bulk_ld(sbase + HEAD_IMG + b * 6144, kimg + 32 * HEAD_IMG + b * 6144, 6144, kvb + 8 * b);
        if (b >= 2) mbar_wait(kvb + 8 * (b - 1), 0);

      }
      if (blockIdx.x == 0) g_epoch = g_epoch + 1;
      mbar_wait(kvb + 8 * 15, 0);
      STAMP(1, 2);
      uint8_t* pdst = nullptr;
      uint32_t pbytes = 0;
#pragma unroll 1
      for (int i = 0; i < 8; i++) {
        const int p = blockIdx.x + 128 * i;
        uint8_t* dst = nullptr;
        uint32_t bytes = 0;
        if (i < 7 && p < 856) {
          asm volatile("cp.async.bulk.wait_group.read 0;" ::: "memory");
          const CUtensorMap* tm;
          int c1, c2;
          if (p < 640) {
            const int nt = p / 80, r = p - nt * 80, ph = r / 40, st = (r - ph * 40) >> 1, up = r & 1;
            bytes = ph ? 6656 : 7168;
            dst = (uint8_t*)g_wgu + nt * 552960 + ph * 286720 + (st * 2 + up) * bytes;
            tm = &tmw[ph * 2 + up]; c1 = st * 32; c2 = ph ? 112 + nt * 13 : nt * 14;
          } else {
            const int nk = p - 640, nt = nk / 27;
            bytes = 10240;
            dst = (uint8_t*)g_wd + (size_t)nk * 10240;
            tm = &tmw[4]; c1 = (nk - nt * 27) * 64; c2 = nt * 10;
          }
          mbar_expect(rbar + 8 * (i & 1), bytes);
          tma3d(rbuf + (i & 1) * 10240, tm, c1, c2, rbar + 8 * (i & 1));
        }
        if (pbytes) {
          mbar_wait(rbar + 8 * ((i - 1) & 1), ((i - 1) >> 1) & 1);
          bulk_st(pdst, rbuf + ((i - 1) & 1) * 10240, pbytes);
          asm volatile("cp.async.bulk.commit_group;" ::: "memory");
        }
        pdst = dst; pbytes = bytes;
      }
      asm volatile("cp.async.bulk.wait_group.read 0;" ::: "memory");
      STAMP(1, 6);
    }
  } else {
    asm volatile("setmaxnreg.inc.sync.aligned.u32 160;");
    const int wg = warp >> 2;
    const uint8_t* qthr = (const uint8_t*)g_qkv + (size_t)head * HEAD_IMG + qb * 64 * 384 + (warp & 3) * 768 + lane * 4;
    const uint32_t klo0 = ((sbase & 0x3FFFF) >> 4) | (128u << 16), vlo0 = (((sbase + HEAD_IMG) & 0x3FFFF) >> 4) | (24u << 16);
    constexpr uint64_t KSTEP2 = (uint64_t)(int64_t)(256 - (128 << 16));
    constexpr uint64_t KV2K = 384 - (HEAD_IMG >> 4) + (104 << 16);
    const int nun = wg == 1 ? 4 : 3;
    uint32_t utile = wg == 0 ? 0x210u : (wg == 1 ? 0x4235u : 0x576u);
    uint32_t ubeg = wg == 0 ? 0u : (wg == 1 ? 0x0b00u : 0x600u);
    uint32_t ulen = wg == 0 ? 0x0b1010u : (wg == 1 ? 0x10051006u : 0x0a1010u);
    pdl_wait();
    if (tid == 0) STAMP(1, 1);
    uint32_t q[6];
    load_q(q, qthr + (utile & 15) * 3072);
    bool fast;
    {
      const float4 kn = __ldcg((const float4*)&g_nrm[(32 + head) * 128 + lane * 4]);
      const float qv = __ldcg(&g_nrm[head * 128 + qb * 32 + lane]);
      const uint32_t km = max(max(__float_as_uint(kn.x), __float_as_uint(kn.y)), max(__float_as_uint(kn.z), __float_as_uint(kn.w)));
      const float k2 = __uint_as_float(__reduce_max_sync(~0u, km)), q2 = __uint_as_float(__reduce_max_sync(~0u, __float_as_uint(qv)));
      fast = q2 * k2 <= 3400.f;
    }
    if (fast) {
#pragma unroll 1
      for (int u = 0; u < nun; u++) {
        const uint32_t b0 = ubeg & 15;
        const bool wt = u == 0 || (wg == 1 && u == 1);
        float s[64], o[12];
#pragma unroll
        for (int i = 0; i < 12; i++) o[i] = 0.f;
        uint32_t vlo = vlo0 + b0 * 384, kb = kvb + b0 * 8;
        const uint32_t vend = vlo + ((ulen & 255) - 1) * 384;
        if (wt) mbar_wait(kb, 0);
        if (tid == 0) STAMP(5, 4 + u);
        fence_regs(o);
        WG_FENCE();
        wgmma_rs_n128(s, q[0], q[1], q[2], q[3], desc64(klo0 + b0 * 384, 8), 0);
        wgmma_rs_n128(s, q[4], q[5], 0, 0, desc64(klo0 + b0 * 384, 8) + KSTEP2, 1);
        WG_COMMIT();
#define K2UNR 1
        constexpr int kUnr = K2UNR;
#pragma unroll kUnr
        for (; vlo != vend; vlo += 384) {
          if (wt) { kb += 8; mbar_wait(kb, 0); }
          WG_WAIT(0);
          fence_regs(s); fence_regs(o);
          const uint64_t dv = desc64(vlo, 8);
          exp_pv(s, o, dv, mk);
          wgmma_rs_n128(s, q[0], q[1], q[2], q[3], dv + KV2K, 0);
          wgmma_rs_n128(s, q[4], q[5], 0, 0, dv + (KV2K + KSTEP2), 1);
          WG_COMMIT();
        }
        WG_WAIT(0);
        fence_regs(s); fence_regs(o);
        if (u + 1 < nun) load_q(q, qthr + ((utile >> 4) & 15) * 3072);
        exp_pv(s, o, desc64(vlo, 8), mk);
        WG_COMMIT();
        WG_WAIT(0);
        fence_regs(o);
        if (wg == 1 && !(u & 1)) {
          float4* pp = (float4*)(part + u * 768) + (tid & 127);
          pp[0] = make_float4(o[0], o[1], o[2], o[3]);
          pp[128] = make_float4(o[4], o[5], o[6], o[7]);
          pp[256] = make_float4(o[8], o[9], o[10], o[11]);
          mbar_arrive(partb + 4 * u);
        } else {
          if (wg != 1 && u == 2) {
            const int pi = wg == 0 ? 1 : 0;
            mbar_wait(partb + 8 * pi, 0);
            const float4* pp = (const float4*)(part + pi * 1536) + (tid & 127);
            const float4 x0 = pp[0], x1 = pp[128], x2 = pp[256];
            o[0] += x0.x; o[1] += x0.y; o[2] += x0.z; o[3] += x0.w; o[4] += x1.x; o[5] += x1.y;
            o[6] += x1.z; o[7] += x1.w; o[8] += x2.x; o[9] += x2.y; o[10] += x2.z; o[11] += x2.w;
          }
          store_o(o, utile & 15);
        }
        utile >>= 4; ubeg >>= 4; ulen >>= 8;
      }
      if ((tid & 127) == 0) STAMP(1, 3 + wg);
    } else {
#pragma unroll 1
      for (int tile = wg; tile < 8; tile += 3) {
        load_q(q, qthr + tile * 3072);
        if ((lane & 3) >= 2) { q[4] = 0; q[5] = 0; }
        float o[12], m0 = -INFINITY, m1 = -INFINITY;
#pragma unroll
        for (int i = 0; i < 12; i++) o[i] = 0.f;
#pragma unroll 1
        for (int b = 0; b < 16; b++) {
          float s[64];
          mbar_wait(kvb + 8 * b, 0);
          WG_FENCE();
          wgmma_rs_n128(s, q[0], q[1], q[2], q[3], desc64(klo0 + b * 384, 8), 0);
          wgmma_rs_n128(s, q[4], q[5], 0, 0, desc64(klo0 + b * 384, 8) + KSTEP2, 1);
          WG_COMMIT();
          WG_WAIT(0);
          fence_regs(s);
          float x0 = m0, x1 = m1;
#pragma unroll
          for (int j = 0; j < 16; j++) {
            if ((POLY_MASK >> j) & 1) {
#pragma unroll
              for (int i = 0; i < 4; i++) s[4 * j + i] *= (1.f / 32768.f);
            }
            x0 = fmaxf(x0, fmaxf(s[4 * j], s[4 * j + 1]));
            x1 = fmaxf(x1, fmaxf(s[4 * j + 2], s[4 * j + 3]));
          }
          x0 = fmaxf(x0, __shfl_xor_sync(~0u, x0, 1)); x0 = fmaxf(x0, __shfl_xor_sync(~0u, x0, 2));
          x1 = fmaxf(x1, __shfl_xor_sync(~0u, x1, 1)); x1 = fmaxf(x1, __shfl_xor_sync(~0u, x1, 2));
          const float al0 = ex2(m0 - x0), al1 = ex2(m1 - x1);
          m0 = x0; m1 = x1;
#pragma unroll
          for (int i = 0; i < 12; i++) o[i] *= (i & 2) ? al1 : al0;
          uint32_t p[32];
#pragma unroll
          for (int i = 0; i < 32; i++) {
            const float mm = (i & 1) ? m1 : m0;
            p[i] = pack_bf16(ex2(s[2 * i] - mm), ex2(s[2 * i + 1] - mm));
          }
          fence_regs(o);
          WG_FENCE();
#pragma unroll
          for (int k = 0; k < 8; k++)
            wgmma_rs_n24(o, p[4 * k], p[4 * k + 1], p[4 * k + 2], p[4 * k + 3], desc64(vlo0 + b * 384 + k * 48, 8), 1);
          WG_COMMIT();
          WG_WAIT(0);
          fence_regs(o);
        }
        store_o(o, tile);
      }
    }
  }
}

#define K3P 2
constexpr int K3_ST = 4, K3_STAGE = 37888, K3_PRE = K3P;
constexpr int K3_SMEM = K3_ST * K3_STAGE + 45056 + 20480 + 256;

template <int N> struct Acc { float v[N]; };

template <int NB, int NK, bool FIRST>
__global__ void __cluster_dims__(2, 1, 1) __launch_bounds__(384, 1)
k3_proj(const __grid_constant__ CUtensorMap tmr, const uint4* __restrict__ aimg, const uint4* __restrict__ wimg) {
  constexpr int KT = 2 * NB + NK, EX = FIRST ? 1 : 0;
  extern __shared__ __align__(1024) uint8_t sm[];
  const uint32_t sbase = smem_u32(sm);
  uint8_t* xch = sm + K3_ST * K3_STAGE;
  uint8_t* stg = sm + K3_ST * K3_STAGE + 45056;
  const uint32_t fullb = smem_u32(stg) + 20480, emptyb = fullb + 8 * K3_ST, resb = emptyb + 8 * K3_ST, xchb = resb + 8;
  const int tid = threadIdx.x, lane = tid & 31;
  const int warp = __shfl_sync(~0u, tid >> 5, 0);
  const int rank = blockIdx.x & 1;
  const int n = blockIdx.x & 7, m = blockIdx.x >> 3;
  if (tid == 0) STAMP(FIRST ? 2 : 4, 0);
  if (warp == 0) {
    if (lane == 0) {
      prefetch_map(&tmr);
      for (int i = 0; i < K3_ST; i++) { mbar_init(fullb + 8 * i, 1); mbar_init(emptyb + 8 * i, 4); }
      mbar_init(resb, 1); mbar_init(xchb, 1);
      mbar_expect(xchb, 4096 * (10 + EX));
      asm volatile("fence.mbarrier_init.release.cluster;" ::: "memory");
    }
    __syncwarp();
    cluster_arrive();
    bar_arrive(4, 256 + 32);
    if (lane == 0) {
      const uint8_t* wk = (const uint8_t*)wimg + (size_t)n * KT * 10240;
      const uint8_t* ws = (const uint8_t*)wimg + (size_t)(n ^ 1) * KT * 10240;
      const uint8_t* ab = (const uint8_t*)aimg + (size_t)m * KT * 16384;
      auto load_w = [&](int i) {
        const int s = i % K3_ST, kt = i < NB ? i + rank * (NB + NK) : i;
        const uint32_t sa = sbase + s * K3_STAGE;
        mbar_expect(fullb + 8 * s, 26624 + EX * 1024 + (i < NB ? 10240 : 0));
        bulk_ld(sa + 16384, wk + kt * 10240, 10240, fullb + 8 * s);
        if (FIRST) bulk_ld(sa + 26624, (const uint8_t*)g_wm + kt * 1024, 1024, fullb + 8 * s);
        if (i < NB) bulk_ld(sa + 26624 + EX * 1024, ws + kt * 10240, 10240, fullb + 8 * s);
      };
#pragma unroll 1
      for (int i = 0; i < K3_PRE; i++) load_w(i);
      if (FIRST) {
        mbar_expect(resb, 20480);
        tma2d(smem_u32(stg), &tmr, n * 80, m * 128, resb);
        tma2d(smem_u32(stg) + 10240, &tmr, n * 80, m * 128 + 64, resb);
      }
      asm volatile("barrier.cluster.wait;" ::: "memory");
      pdl_wait();
      pdl_trigger();
#pragma unroll 1
      for (int i = 0; i < NB + NK; i++) {
        const int s = i % K3_ST;
        const uint32_t sa = sbase + s * K3_STAGE;
        if (i >= K3_ST) mbar_wait(emptyb + 8 * s, ((i / K3_ST) - 1) & 1);
        if (i < NB) bulk_ld(sa, ab + (i + rank * (NB + NK)) * 16384, 16384, fullb + 8 * s);
        else bulk_ld_mc(sa + rank * 8192, ab + i * 16384 + rank * 8192, 8192, fullb + 8 * s);
        if (i >= K3_PRE) load_w(i);
      }
    } else {
      asm volatile("barrier.cluster.wait;" ::: "memory");
    }
    __syncwarp();
    cluster_arrive();
  } else if (warp >= 4) {
    cluster_arrive();
    const int cw = warp - 4, wg = cw >> 2;
    const int g = lane >> 2, c = lane & 3;
    const int row = m * 128 + cw * 16 + g;
    uint8_t* himg = (uint8_t*)g_h + (size_t)m * 163840 + cw * 2048 + lane * 4;
    uint32_t rv[20];
    float mu0, mu1;
    if (FIRST) {
      mu0 = __uint_as_float(__ldcg(&g_rowstat[row].z)); mu1 = __uint_as_float(__ldcg(&g_rowstat[row + 8].z));
    } else {
      mu0 = __ldcg(&g_hmean[row]); mu1 = __ldcg(&g_hmean[row + 8]);
#pragma unroll
      for (int j = 0; j < 10; j++) {
        rv[2 * j] = __ldcg((const uint32_t*)(himg + img_off(n * 10 + j)));
        rv[2 * j + 1] = __ldcg((const uint32_t*)(himg + img_off(n * 10 + j) + 1024));
      }
    }
    float acc[80 + 4 * EX];
    float (&keep)[40 + 4 * EX] = ((Acc<40 + 4 * EX>*)acc)->v;
    const uint64_t da0 = mkdesc(sbase + wg * 8192, 128, 1024, 0);
    const uint64_t db0 = mkdesc(sbase + 16384, 128, 1024, 0);
    bar_sync(4, 256 + 32);
    cluster_wait();
#pragma unroll 1
    for (int i = 0; i < NB; i++) {
      const int s = i % K3_ST;
      mbar_wait(fullb + 8 * s, (i / K3_ST) & 1);
      if (i == 0 && tid == 128) STAMP(FIRST ? 2 : 4, 2);
      const uint64_t da = da0 + s * (K3_STAGE >> 4), db = db0 + s * (K3_STAGE >> 4);
      WG_FENCE();
#pragma unroll
      for (int k = 0; k < 4; k++) {
        if constexpr (FIRST) wgmma_ss_n168(acc, da + k * 16, db + k * 16, (i | k) != 0);
        else wgmma_ss_n160(acc, da + k * 16, db + k * 16, (i | k) != 0);
      }
      WG_COMMIT();
      if (i > 0) {
        WG_WAIT(1);
        if ((tid & 127) < 2) mbar_arrive_cta(emptyb + 8 * ((i - 1) % K3_ST), tid & 1);
      }
    }
    const uint32_t rx = mapa(smem_u32(xch) + (tid - 128) * 16, rank ^ 1), rb = mapa(xchb, rank ^ 1);
    WG_WAIT(0);
    fence_regs(acc);
    if ((tid & 127) < 2) mbar_arrive_cta(emptyb + 8 * ((NB - 1) % K3_ST), tid & 1);
    if (FIRST) st_async4(rx, acc[40], acc[41], acc[42], acc[43], rb);
    if (tid == 128) STAMP(FIRST ? 2 : 4, 1);
#pragma unroll
    for (int i = NB; i < NB + NK; i++) {
      const int s = i % K3_ST;
      mbar_wait(fullb + 8 * s, (i / K3_ST) & 1);
      const uint64_t da = da0 + s * (K3_STAGE >> 4), db = db0 + s * (K3_STAGE >> 4);
      WG_FENCE();
#pragma unroll
      for (int k = 0; k < 4; k++) {
        if constexpr (FIRST) wgmma_ss_n88(keep, da + k * 16, db + k * 16, 1);
        else wgmma_ss_n80(keep, da + k * 16, db + k * 16, 1);
      }
      WG_COMMIT();
      if (i > NB && i - 1 + K3_ST < NB + NK) {
        WG_WAIT(1);
        if ((tid & 127) < 2) mbar_arrive_cta(emptyb + 8 * ((i - 1) % K3_ST), tid & 1);
      }
#pragma unroll
      for (int j = (i - NB) * 3 + EX; j < (i - NB) * 3 + 3 + EX; j++)
        if (j < 10 + EX) st_async4(rx + j * 4096, acc[40 + 4 * j], acc[41 + 4 * j], acc[42 + 4 * j], acc[43 + 4 * j], rb);
    }
    cluster_arrive();
    uint8_t* sp = stg + (cw * 16 + g) * 160 + c * 4;
    if (FIRST) {
      mbar_wait(resb, 0);
#pragma unroll
      for (int j = 0; j < 10; j++) {
        rv[2 * j] = *(const uint32_t*)(sp + j * 16);
        rv[2 * j + 1] = *(const uint32_t*)(sp + 1280 + j * 16);
      }
    }
    WG_WAIT(0);
    fence_regs(keep);
    if (tid == 128) STAMP(FIRST ? 2 : 4, 3);
    mbar_wait(xchb, 0);
    if (tid == 128) STAMP(FIRST ? 2 : 4, 5);
    const uint8_t* xp = xch + (tid - 128) * 16;
    if (FIRST) {
      const float4 p = *(const float4*)xp;
      mu0 += __shfl_sync(~0u, (keep[40] + p.x) + (keep[41] + p.y), 0, 4);
      mu1 += __shfl_sync(~0u, (keep[42] + p.z) + (keep[43] + p.w), 0, 4);
      if (n == 0 && c == 0) { g_hmean[row] = mu0; g_hmean[row + 8] = mu1; }
      mu0 = -mu0; mu1 = -mu1;
    }
    float q0 = 0.f, q1 = 0.f;
#pragma unroll
    for (int j = 0; j < 10; j++) {
      const float4 p = *(const float4*)(xp + (j + EX) * 4096);
      const float x0 = (keep[4 * j] + p.x) + (bf_lo(rv[2 * j]) + mu0), x1 = (keep[4 * j + 1] + p.y) + (bf_hi(rv[2 * j]) + mu0);
      const float y0 = (keep[4 * j + 2] + p.z) + (bf_lo(rv[2 * j + 1]) + mu1), y1 = (keep[4 * j + 3] + p.w) + (bf_hi(rv[2 * j + 1]) + mu1);
      if (FIRST) {
        *(uint32_t*)(himg + img_off(n * 10 + j)) = pack_bf16(x0, x1);
        *(uint32_t*)(himg + img_off(n * 10 + j) + 1024) = pack_bf16(y0, y1);
        q0 = fmaf(x0, x0, fmaf(x1, x1, q0)); q1 = fmaf(y0, y0, fmaf(y1, y1, q1));
      } else {
        *(uint32_t*)(sp + j * 16) = pack_bf16(x0, x1);
        *(uint32_t*)(sp + 1280 + j * 16) = pack_bf16(y0, y1);
      }
    }
    if (FIRST) {
      q0 += __shfl_xor_sync(~0u, q0, 1); q0 += __shfl_xor_sync(~0u, q0, 2);
      q1 += __shfl_xor_sync(~0u, q1, 1); q1 += __shfl_xor_sync(~0u, q1, 2);
      if (c < 2) g_hpart[n * S_ + row + c * 8] = c ? q1 : q0;
    } else {
      fence_async();
      bar_sync(1 + wg, 128);
      if ((tid & 127) == 0) {
        tma2d_st(&tmr, n * 80, m * 128 + wg * 64, smem_u32(stg) + wg * 10240);
        bulk_commit_wait();
      }
      __syncwarp();
    }
    if (tid == 128) STAMP(FIRST ? 2 : 4, 4);
  } else {
    cluster_arrive();
    cluster_wait();
    cluster_arrive();
  }
  cluster_wait();
}

constexpr int K4_RB = 163840, K4_BST = 14336, K4_XCH = 147456, K4_STG = K4_XCH + 40960, K4_BAR = K4_RB + 4 * K4_BST;
constexpr int K4_SMEM = K4_BAR + 256;

__device__ __forceinline__ void wait_flags(const uint4* f, uint32_t tag) {
  for (uint32_t it = 0;; it++) {
    uint4 a, b;
    asm volatile("ld.acquire.gpu.global.v4.u32 {%0, %1, %2, %3}, [%4];" : "=r"(a.x), "=r"(a.y), "=r"(a.z), "=r"(a.w) : "l"(f) : "memory");
    asm volatile("ld.acquire.gpu.global.v4.u32 {%0, %1, %2, %3}, [%4];" : "=r"(b.x), "=r"(b.y), "=r"(b.z), "=r"(b.w) : "l"(f + 1) : "memory");
    if (a.x == tag && a.y == tag && a.z == tag && a.w == tag && b.x == tag && b.y == tag && b.z == tag && b.w == tag) break;
    if (it > (1u << 20)) wait_timeout();
    __nanosleep(100);
  }
  asm volatile("fence.proxy.async.global;" ::: "memory");
}

__global__ void __cluster_dims__(2, 1, 1) __launch_bounds__(384, 1)
k45_ffn(const __grid_constant__ CUtensorMap tmo) {
  extern __shared__ __align__(1024) uint8_t sm[];
  const uint32_t sbase = smem_u32(sm);
  const uint32_t afull = sbase + K4_BAR, bfull = afull + 80, bempty = bfull + 32, full3 = bempty + 32, empty3 = full3 + 32, afree = empty3 + 32, xchb = afree + 32;
  const int tid = threadIdx.x, lane = tid & 31;
  const int warp = __shfl_sync(~0u, tid >> 5, 0);
  const int rank = blockIdx.x & 1;
  const int n1 = (blockIdx.x >> 1) & 7, m1 = (blockIdx.x >> 4) * 2 + rank;
  const int n3 = blockIdx.x & 7, m3 = blockIdx.x >> 3;
  if (tid == 0) STAMP(3, 0);
  if (warp >= 8) {
    asm volatile("setmaxnreg.dec.sync.aligned.u32 40;");
    if (warp == 8 && lane == 0) {
      prefetch_map(&tmo);
      for (int i = 0; i < 10; i++) mbar_init(afull + 8 * i, 1);
      for (int i = 0; i < 4; i++) {
        mbar_init(bfull + 8 * i, 1); mbar_init(bempty + 8 * i, 4); mbar_init(full3 + 8 * i, 1); mbar_init(empty3 + 8 * i, 4);
        mbar_init(afree + 8 * i, 2);
      }
      mbar_init(xchb, 1);
      mbar_expect(xchb, 40960);
      asm volatile("fence.mbarrier_init.release.cluster;" ::: "memory");
    }
    __syncwarp();
    cluster_arrive();
    bar_sync(4, 384);
    cluster_wait();
    if (warp == 8) {
      if (lane == 0) {
        const uint8_t* wb = (const uint8_t*)g_wgu + n1 * 552960;
        const uint8_t* hb = (const uint8_t*)g_h + (size_t)m1 * 163840;
#pragma unroll 1
        for (int j = 0; j < 40; j++) {
          if (j == 4) {
            pdl_wait();
            STAMP(3, 1);
#pragma unroll 1
            for (int kt = 0; kt < 3; kt++) { mbar_expect(afull + 8 * kt, 16384); bulk_ld(sbase + kt * 16384, hb + kt * 16384, 16384, afull + 8 * kt); }
          }
          if (j >= 4) mbar_wait(bempty + 8 * (j & 3), ((j >> 2) - 1) & 1);
          if (j >= 4 && j < 18 && !(j & 1)) {
            const int kt = (j >> 1) + 1;
            mbar_expect(afull + 8 * kt, 16384);
            bulk_ld(sbase + kt * 16384, hb + kt * 16384, 16384, afull + 8 * kt);
          }
          const uint32_t half = j < 20 ? 7168 : 6656;
          mbar_expect(bfull + 8 * (j & 3), 2 * half);
          bulk_ld_mc(sbase + K4_RB + (j & 3) * K4_BST + rank * half, wb + (j < 20 ? j * 14336 : 286720 + (j - 20) * 13312) + rank * half,
                     half, bfull + 8 * (j & 3));
        }
      }
    } else if (warp == 9) {
      const uint32_t tag = __ldcg(&g_epoch);
#pragma unroll 1
      for (int ph = 0; ph < 2; ph++) {
        bar_sync(5 + ph, 256 + 32);
        if (lane == 0) {
          asm volatile("st.release.gpu.global.u32 [%0], %1;" ::"l"((uint32_t*)&g_flag[ph * 32 + m1 * 2] + n1), "r"(tag) : "memory");
          STAMP(3, 5 + ph);
        }
        __syncwarp();
      }
    } else if (lane == 0) {
      const uint8_t* wk = (const uint8_t*)g_wd + n3 * 276480;
      const uint8_t* ws = (const uint8_t*)g_wd + (n3 ^ 1) * 276480;
      const uint8_t* ab = (const uint8_t*)g_hh + (size_t)m3 * 442368;
      const uint32_t tag = __ldcg(&g_epoch);
#pragma unroll 1
      for (int i = 0; i < 16; i++) {
        const int kt = i < 7 ? rank * 7 + i : (i < 11 ? rank * 4 + 7 + i : 11 + i);
        const uint32_t sa = sbase + (i & 3) * 36864, fb = full3 + 8 * (i & 3);
        if (warp == 11 && (i == 0 || i == 7)) {
          if (i == 0) mbar_wait(afull + 72, 0);
          wait_flags(&g_flag[(i ? 32 : 0) + m3 * 2], tag);
          STAMP(4, i ? 7 : 6);
        }
        if (i < 4) mbar_wait(afree + 8 * i, 0);
        else mbar_wait(empty3 + 8 * (i & 3), ((i >> 2) - 1) & 1);
        if (warp == 10) {
          mbar_expect(fb, i < 11 ? 36864 : 26624);
          bulk_ld(sa + 16384, wk + kt * 10240, 10240, fb);
          if (i < 11) bulk_ld(sa + 26624, ws + kt * 10240, 10240, fb);
        } else {
          if (i < 11) bulk_ld(sa, ab + kt * 16384, 16384, fb);
          else bulk_ld_mc(sa + rank * 8192, ab + kt * 16384 + rank * 8192, 8192, fb);
        }
      }
    }
    __syncwarp();
    cluster_arrive();
    asm volatile("barrier.cluster.wait.aligned; // producers" ::: "memory");
  } else {
    asm volatile("setmaxnreg.inc.sync.aligned.u32 232;");
    cluster_arrive();
    const int wg = warp >> 2;
    const uint64_t da0 = mkdesc(sbase + wg * 8192, 128, 1024, 0);
    const uint64_t db0 = mkdesc(sbase + K4_RB, 128, 512, 0);
    bar_sync(4, 384);
    cluster_wait();
    float a1[112], a2[104];
#pragma unroll 1
    for (int j = 0; j < 20; j++) {
      if (!(j & 1)) mbar_wait(afull + 4 * j, 0);
      mbar_wait(bfull + 8 * (j & 3), (j >> 2) & 1);
      if (j == 0 && tid == 0) STAMP(3, 2);
      const uint64_t da = da0 + (j >> 1) * 1024 + (j & 1) * 32, db = db0 + (j & 3) * (K4_BST >> 4);
      WG_FENCE();
      wgmma_ss_n224(a1, da, db, j != 0);
      wgmma_ss_n224(a1, da + 16, db + 16, 1);
      WG_COMMIT();
      if (j > 0) {
        WG_WAIT(1);
        if ((tid & 127) < 2) mbar_arrive_cta(bempty + 8 * ((j - 1) & 3), tid & 1);
      }
    }
    float r0, r1;
    {
      const float* hp = &g_hpart[(lane & 3) * 2 * S_ + m1 * 128 + warp * 16 + (lane >> 2)];
      r0 = __ldcg(hp) + __ldcg(hp + S_);
      r1 = __ldcg(hp + 8) + __ldcg(hp + S_ + 8);
    }
    r0 += __shfl_xor_sync(~0u, r0, 1); r1 += __shfl_xor_sync(~0u, r1, 1);
    r0 += __shfl_xor_sync(~0u, r0, 2); r1 += __shfl_xor_sync(~0u, r1, 2);
    r0 = __frcp_rn(r0 * (1.f / D_) + 1e-5f); r1 = __frcp_rn(r1 * (1.f / D_) + 1e-5f);
    WG_WAIT(0);
    fence_regs(a1);
    if ((tid & 127) < 2) mbar_arrive_cta(bempty + 24, tid & 1);
    if (tid == 0) STAMP(3, 3);
    uint8_t* hd = (uint8_t*)g_hh + (size_t)m1 * 442368 + warp * 2048 + lane * 4;
#define STORE_H(a, off, q, c) do { uint8_t* p_ = hd + img_off(q); \
      *(uint32_t*)p_ = pack_bf16(a[4 * (c)] * r0 * a[off + 4 * (c)], a[4 * (c) + 1] * r0 * a[off + 1 + 4 * (c)]); \
      *(uint32_t*)(p_ + 1024) = pack_bf16(a[4 * (c) + 2] * r1 * a[off + 2 + 4 * (c)], a[4 * (c) + 3] * r1 * a[off + 3 + 4 * (c)]); } while (0)
    uint32_t p1[28];
#pragma unroll
    for (int c = 0; c < 14; c++) {
      p1[2 * c] = pack_bf16(a1[4 * c] * r0 * a1[56 + 4 * c], a1[4 * c + 1] * r0 * a1[57 + 4 * c]);
      p1[2 * c + 1] = pack_bf16(a1[4 * c + 2] * r1 * a1[58 + 4 * c], a1[4 * c + 3] * r1 * a1[59 + 4 * c]);
      asm volatile("" : "+r"(p1[2 * c]), "+r"(p1[2 * c + 1])::"memory");
    }
#pragma unroll
    for (int j = 20; j < 40; j++) {
      mbar_wait(bfull + 8 * (j & 3), (j >> 2) & 1);
      const uint64_t da = da0 + ((j - 20) >> 1) * 1024 + (j & 1) * 32, db = db0 + (j & 3) * (K4_BST >> 4);
      WG_FENCE();
      wgmma_ss_n208(a2, da, db, j != 20);
      wgmma_ss_n208(a2, da + 16, db + 16, 1);
      WG_COMMIT();
      if (j > 20) {
        WG_WAIT(1);
        if (j < 37 && (tid & 127) < 2) mbar_arrive_cta(bempty + 8 * ((j - 1) & 3), tid & 1);
        if (j >= 26 && (j & 3) == 2 && (tid & 127) == 0) mbar_arrive(afree + (j - 26) * 2);
      }
#pragma unroll
      for (int c = (j - 20) * 5; c < (j - 20) * 5 + 5; c++) {
        if (c < 14) {
          *(uint32_t*)(hd + img_off(n1 * 14 + c)) = p1[2 * c];
          *(uint32_t*)(hd + img_off(n1 * 14 + c) + 1024) = p1[2 * c + 1];
        }
        if (c == 13) bar_arrive(5, 256 + 32);
      }
    }
    WG_WAIT(0);
    fence_regs(a2);
    if (tid == 0) STAMP(3, 4);
    float acc[80];
    float (&keep)[40] = ((Acc<40>*)acc)->v;
    const uint64_t db3 = mkdesc(sbase + 16384, 128, 1024, 0);
#pragma unroll
    for (int i = 0; i < 11; i++) {
      mbar_wait(full3 + 8 * (i & 3), (i >> 2) & 1);
      if (i == 0 && tid == 0) STAMP(4, 2);
      const uint64_t da = da0 + (i & 3) * 2304, db = db3 + (i & 3) * 2304;
      WG_FENCE();
#pragma unroll
      for (int k = 0; k < 4; k++) wgmma_ss_n160(acc, da + k * 16, db + k * 16, (i | k) != 0);
      WG_COMMIT();
      if (i > 0) {
        WG_WAIT(1);
        if ((tid & 127) < 2) mbar_arrive_cta(empty3 + 8 * ((i - 1) & 3), tid & 1);
      }
      if (i == 0) {
#pragma unroll
        for (int c = 0; c < 13; c++) STORE_H(a2, 52, 112 + n1 * 13 + c, c);
        bar_arrive(6, 256 + 32);
      }
    }
    const int g = lane >> 2, c = lane & 3, row = m3 * 128 + warp * 16 + g;
    const uint8_t* himg = (const uint8_t*)g_h + (size_t)m3 * 163840 + warp * 2048 + lane * 4;
    uint32_t rv[20];
    const float mu0 = __ldcg(&g_hmean[row]), mu1 = __ldcg(&g_hmean[row + 8]);
#pragma unroll
    for (int j = 0; j < 10; j++) {
      rv[2 * j] = __ldcg((const uint32_t*)(himg + img_off(n3 * 10 + j)));
      rv[2 * j + 1] = __ldcg((const uint32_t*)(himg + img_off(n3 * 10 + j) + 1024));
    }
    const uint32_t rx = mapa(sbase + K4_XCH + tid * 16, rank ^ 1), rb = mapa(xchb, rank ^ 1);
    WG_WAIT(0);
    fence_regs(acc);
    if ((tid & 127) < 2) mbar_arrive_cta(empty3 + 16, tid & 1);
    if (tid == 0) STAMP(4, 1);
#pragma unroll
    for (int i = 11; i < 16; i++) {
      mbar_wait(full3 + 8 * (i & 3), (i >> 2) & 1);
      const uint64_t da = da0 + (i & 3) * 2304, db = db3 + (i & 3) * 2304;
      WG_FENCE();
#pragma unroll
      for (int k = 0; k < 4; k++) wgmma_ss_n80(keep, da + k * 16, db + k * 16, 1);
      WG_COMMIT();
      if (i == 12) {
        WG_WAIT(1);
        if ((tid & 127) < 2) mbar_arrive_cta(empty3 + 24, tid & 1);
      }
#pragma unroll
      for (int j = (i - 11) * 3; j < (i - 11) * 3 + 3; j++)
        if (j < 10) st_async4(rx + j * 4096, acc[40 + 4 * j], acc[41 + 4 * j], acc[42 + 4 * j], acc[43 + 4 * j], rb);
    }
    cluster_arrive();
    WG_WAIT(0);
    fence_regs(keep);
    if (tid == 0) STAMP(4, 3);
    mbar_wait(xchb, 0);
    if (tid == 0) STAMP(4, 5);
    uint8_t* sp = sm + K4_STG + (warp * 16 + g) * 160 + c * 4;
#pragma unroll
    for (int j = 0; j < 10; j++) {
      const float4 p = *(const float4*)(sm + K4_XCH + tid * 16 + j * 4096);
      *(uint32_t*)(sp + j * 16) = pack_bf16((keep[4 * j] + p.x) + (bf_lo(rv[2 * j]) + mu0), (keep[4 * j + 1] + p.y) + (bf_hi(rv[2 * j]) + mu0));
      *(uint32_t*)(sp + 1280 + j * 16) = pack_bf16((keep[4 * j + 2] + p.z) + (bf_lo(rv[2 * j + 1]) + mu1), (keep[4 * j + 3] + p.w) + (bf_hi(rv[2 * j + 1]) + mu1));
    }
    fence_async();
    bar_sync(1 + wg, 128);
    if ((tid & 127) == 0) {
      tma2d_st(&tmo, n3 * 80, m3 * 128 + wg * 64, sbase + K4_STG + wg * 10240);
      bulk_commit_wait();
    }
    __syncwarp();
    if (tid == 0) STAMP(4, 4);
    asm volatile("barrier.cluster.wait.aligned; // consumers" ::: "memory");
  }
}

typedef CUresult (*EncodeFn)(CUtensorMap*, CUtensorMapDataType, cuuint32_t, void*, const cuuint64_t*, const cuuint64_t*,
                             const cuuint32_t*, const cuuint32_t*, CUtensorMapInterleave, CUtensorMapSwizzle,
                             CUtensorMapL2promotion, CUtensorMapFloatOOBfill);

static CUtensorMap make_map(EncodeFn enc, const void* p, uint64_t inner, uint64_t outer, uint32_t box_inner,
                            uint32_t box_outer, CUtensorMapSwizzle swz) {
  CUtensorMap m;
  cuuint64_t gd[2] = {inner, outer};
  cuuint64_t gs[1] = {inner * 2};
  cuuint32_t bd[2] = {box_inner, box_outer};
  cuuint32_t es[2] = {1, 1};
  enc(&m, CU_TENSOR_MAP_DATA_TYPE_BFLOAT16, 2, (void*)p, gd, gs, bd, es, CU_TENSOR_MAP_INTERLEAVE_NONE, swz,
      CU_TENSOR_MAP_L2_PROMOTION_L2_256B, CU_TENSOR_MAP_FLOAT_OOB_FILL_NONE);
  return m;
}

static CUtensorMap make_map_img(EncodeFn enc, const void* p, uint64_t k, uint64_t n, uint32_t rows, uint32_t chunks) {
  CUtensorMap m;
  cuuint64_t gd[3] = {8, k, n / 8};
  cuuint64_t gs[2] = {n * 2, 16};
  cuuint32_t bd[3] = {8, rows, chunks};
  cuuint32_t es[3] = {1, 1, 1};
  enc(&m, CU_TENSOR_MAP_DATA_TYPE_BFLOAT16, 3, (void*)p, gd, gs, bd, es, CU_TENSOR_MAP_INTERLEAVE_NONE,
      CU_TENSOR_MAP_SWIZZLE_NONE, CU_TENSOR_MAP_L2_PROMOTION_L2_128B, CU_TENSOR_MAP_FLOAT_OOB_FILL_NONE);
  return m;
}

template <typename... KArgs, typename... Args>
static void launch(void (*k)(KArgs...), int grid, int threads, int smem, bool pdl, Args... args) {
  cudaLaunchConfig_t cfg = {};
  cfg.gridDim = dim3(grid);
  cfg.blockDim = dim3(threads);
  cfg.dynamicSmemBytes = smem;
  cfg.stream = cudaStreamPerThread;
  cudaLaunchAttribute at[1];
  at[0].id = cudaLaunchAttributeProgrammaticStreamSerialization;
  at[0].val.programmaticStreamSerializationAllowed = 1;
  cfg.attrs = at;
  cfg.numAttrs = pdl ? 1 : 0;
  cudaLaunchKernelEx(&cfg, k, KArgs(args)...);
}

extern "C" void kernel_launch(void* const* d_in, const int* in_sizes, int n_in, void* d_out, int out_size) {
  const bf16* x = (const bf16*)d_in[0];
  const bf16* wqkv = (const bf16*)d_in[1];
  const bf16* wo = (const bf16*)d_in[2];
  const bf16* wg = (const bf16*)d_in[4];
  const bf16* wu = (const bf16*)d_in[5];
  const bf16* wd = (const bf16*)d_in[6];

  static EncodeFn enc = nullptr;
  static void *p_o, *p_wo;
  if (!enc) {
    void* fn = nullptr;
    cudaDriverEntryPointQueryResult qr;
    cudaGetDriverEntryPoint("cuTensorMapEncodeTiled", &fn, cudaEnableDefault, &qr);
    enc = (EncodeFn)fn;
    cudaGetSymbolAddress(&p_o, g_o);
    cudaGetSymbolAddress(&p_wo, g_wo);
    cudaFuncSetAttribute(k1_qkv, cudaFuncAttributeMaxDynamicSharedMemorySize, K1_SMEM);
    cudaFuncSetAttribute(k2_attn, cudaFuncAttributeMaxDynamicSharedMemorySize, K2_SMEM);
    cudaFuncSetAttribute(k3_proj<3, 4, true>, cudaFuncAttributeMaxDynamicSharedMemorySize, K3_SMEM);
    cudaFuncSetAttribute(k45_ffn, cudaFuncAttributeMaxDynamicSharedMemorySize, K4_SMEM);
  }
  const CUtensorMap tmx = make_map(enc, x, D_, S_, 64, 96, CU_TENSOR_MAP_SWIZZLE_128B);
  const CUtensorMap tmw = make_map(enc, wqkv, 3 * D_, D_, 32, 64, CU_TENSOR_MAP_SWIZZLE_64B);
  const CUtensorMap tmxr = make_map(enc, x, D_, S_, 80, 64, CU_TENSOR_MAP_SWIZZLE_NONE);
  Maps5 maps;
  maps.m[0] = make_map_img(enc, wg, D_, F_, 32, 14); maps.m[1] = make_map_img(enc, wu, D_, F_, 32, 14);
  maps.m[2] = make_map_img(enc, wg, D_, F_, 32, 13); maps.m[3] = make_map_img(enc, wu, D_, F_, 32, 13);
  maps.m[4] = make_map_img(enc, wd, F_, D_, 64, 10);
  const CUtensorMap tmout = make_map(enc, d_out, D_, S_, 80, 64, CU_TENSOR_MAP_SWIZZLE_NONE);

  launch(k1_qkv, 132, 512, K1_SMEM, false, tmx, tmw, x, wqkv, wo);
  launch(k2_attn, 128, 512, K2_SMEM, true, maps, 0x007f007fu);
  launch(k3_proj<3, 4, true>, 128, 384, K3_SMEM, true, tmxr, (const uint4*)p_o, (const uint4*)p_wo);
  launch(k45_ffn, 128, 384, K4_SMEM, true, tmout);
}
```

```cpp
#include <cuda_runtime.h>
#include <cuda_bf16.h>
#include <cuda.h>
#include <stdint.h>

typedef __nv_bfloat16 bf16;

constexpr int S_ = 2048, D_ = 640, F_ = 1728;
constexpr int HEAD_IMG = 98304;
#define PMASK 0xDB6D
constexpr uint32_t POLY_MASK = PMASK;
constexpr float QSCALE = 0.22360679774997896f * 1.4426950408889634f;

__device__ __align__(1024) uint4 g_qkv[96 * HEAD_IMG / 16];
__device__ __align__(1024) uint4 g_o[S_ * D_ / 8];
__device__ __align__(1024) uint4 g_h[S_ * D_ / 8];
__device__ __align__(1024) uint4 g_hh[S_ * F_ / 8];
__device__ __align__(1024) uint4 g_wo[D_ * D_ / 8];
__device__ __align__(1024) uint4 g_wgu[2 * D_ * F_ / 8];
__device__ __align__(1024) uint4 g_wd[F_ * D_ / 8];
__device__ uint4 g_rowstat[S_];
__device__ uint4 g_cpart[10 * 12 * 80];
__device__ float g_nrm[64 * 128];
__device__ uint4 g_wm[D_];
__device__ float g_hmean[S_];
__device__ float g_hpart[8 * S_];
__device__ uint4 g_flag[2 * 16 * 2];
__device__ unsigned g_epoch;

#define STAMP(k, i)
__device__ __forceinline__ uint32_t smem_u32(const void* p) { return (uint32_t)__cvta_generic_to_shared(p); }
__device__ __forceinline__ void mbar_init(uint32_t a, uint32_t c) {
  asm volatile("mbarrier.init.shared::cta.b64 [%0], %1;" ::"r"(a), "r"(c) : "memory");
}
__device__ __forceinline__ void mbar_expect(uint32_t a, uint32_t bytes) {
  asm volatile("mbarrier.arrive.expect_tx.shared::cta.b64 _, [%0], %1;" ::"r"(a), "r"(bytes) : "memory");
}
__device__ __forceinline__ void mbar_arrive(uint32_t a) {
  asm volatile("mbarrier.arrive.shared::cta.b64 _, [%0];" ::"r"(a) : "memory");
}
__device__ __forceinline__ void mbar_arrive_cta(uint32_t a, uint32_t cta) {
  asm volatile("{\n.reg .b32 r;\nmapa.shared::cluster.u32 r, %0, %1;\n"
               "mbarrier.arrive.shared::cluster.b64 _, [r];\n}" ::"r"(a), "r"(cta) : "memory");
}
__device__ __forceinline__ bool mbar_try(uint32_t a, uint32_t ph) {
  uint32_t ok;
  asm volatile("{\n.reg .pred p;\nmbarrier.try_wait.parity.shared::cta.b64 p, [%1], %2;\nselp.u32 %0, 1, 0, p;\n}"
               : "=r"(ok) : "r"(a), "r"(ph) : "memory");
  return ok;
}
__device__ __noinline__ void wait_timeout() { __trap(); }
__device__ __forceinline__ void mbar_wait(uint32_t a, uint32_t ph) {
  if (mbar_try(a, ph)) return;
  uint32_t it = 0;
  while (!mbar_try(a, ph)) if (++it > (1u << 22)) wait_timeout();
}
__device__ __forceinline__ void tma2d(uint32_t dst, const CUtensorMap* m, int c0, int c1, uint32_t bar) {
  asm volatile("cp.async.bulk.tensor.2d.shared::cluster.global.mbarrier::complete_tx::bytes [%0], [%1, {%3, %4}], [%2];"
               ::"r"(dst), "l"(m), "r"(bar), "r"(c0), "r"(c1) : "memory");
}
__device__ __forceinline__ void tma2d_mc(uint32_t dst, const CUtensorMap* m, int c0, int c1, uint32_t bar) {
  asm volatile("cp.async.bulk.tensor.2d.shared::cluster.global.mbarrier::complete_tx::bytes.multicast::cluster "
               "[%0], [%1, {%3, %4}], [%2], %5;"
               ::"r"(dst), "l"(m), "r"(bar), "r"(c0), "r"(c1), "h"((uint16_t)3) : "memory");
}
__device__ __forceinline__ void bulk_ld(uint32_t dst, const void* src, uint32_t bytes, uint32_t bar) {
  asm volatile("cp.async.bulk.shared::cluster.global.mbarrier::complete_tx::bytes [%0], [%1], %2, [%3];"
               ::"r"(dst), "l"(src), "r"(bytes), "r"(bar) : "memory");
}
__device__ __forceinline__ void bulk_ld_mc(uint32_t dst, const void* src, uint32_t bytes, uint32_t bar) {
  asm volatile("cp.async.bulk.shared::cluster.global.mbarrier::complete_tx::bytes.multicast::cluster "
               "[%0], [%1], %2, [%3], %4;"
               ::"r"(dst), "l"(src), "r"(bytes), "r"(bar), "h"((uint16_t)3) : "memory");
}
__device__ __forceinline__ void cluster_arrive() { asm volatile("barrier.cluster.arrive.relaxed.aligned;" ::: "memory"); }
__device__ __forceinline__ void cluster_wait() { asm volatile("barrier.cluster.wait.aligned;" ::: "memory"); }
__device__ __forceinline__ void bulk_st(void* dst, uint32_t src, uint32_t bytes) {
  asm volatile("cp.async.bulk.global.shared::cta.bulk_group [%0], [%1], %2;" ::"l"(dst), "r"(src), "r"(bytes) : "memory");
}
__device__ __forceinline__ void tma2d_st(const CUtensorMap* m, int c0, int c1, uint32_t src) {
  asm volatile("cp.async.bulk.tensor.2d.global.shared::cta.bulk_group [%0, {%2, %3}], [%1];"
               ::"l"(m), "r"(src), "r"(c0), "r"(c1) : "memory");
}
__device__ __forceinline__ void bulk_commit_wait() {
  asm volatile("cp.async.bulk.commit_group;\ncp.async.bulk.wait_group.read 0;" ::: "memory");
}
__device__ __forceinline__ uint32_t mapa(uint32_t a, uint32_t cta) {
  uint32_t r;
  asm("mapa.shared::cluster.u32 %0, %1, %2;" : "=r"(r) : "r"(a), "r"(cta));
  return r;
}
__device__ __forceinline__ void st_async4(uint32_t dst, float a, float b, float c, float d, uint32_t bar) {
  asm volatile("st.async.shared::cluster.mbarrier::complete_tx::bytes.v4.f32 [%0], {%1, %2, %3, %4}, [%5];"
               ::"r"(dst), "f"(a), "f"(b), "f"(c), "f"(d), "r"(bar) : "memory");
}
__device__ __forceinline__ void fence_async() { asm volatile("fence.proxy.async.shared::cta;" ::: "memory"); }
__device__ __forceinline__ void prefetch_map(const CUtensorMap* m) {
  asm volatile("prefetch.tensormap [%0];" ::"l"(m) : "memory");
}
__device__ __forceinline__ void pdl_wait() { asm volatile("griddepcontrol.wait;" ::: "memory"); }
__device__ __forceinline__ void pdl_trigger() { asm volatile("griddepcontrol.launch_dependents;" ::: "memory"); }
__device__ __forceinline__ void bar_sync(int id, int n) { asm volatile("bar.sync %0, %1;" ::"r"(id), "r"(n) : "memory"); }
__device__ __forceinline__ void bar_arrive(int id, int n) { asm volatile("bar.arrive %0, %1;" ::"r"(id), "r"(n) : "memory"); }
#define WG_FENCE() asm volatile("wgmma.fence.sync.aligned;" ::: "memory")
#define WG_COMMIT() asm volatile("wgmma.commit_group.sync.aligned;" ::: "memory")
#define WG_WAIT(n) asm volatile("wgmma.wait_group.sync.aligned %0;" ::"n"(n) : "memory")
__device__ __forceinline__ uint64_t mkdesc(uint32_t addr, uint32_t lbo, uint32_t sbo, uint32_t sw) {
  return (uint64_t)((addr & 0x3FFFF) >> 4) | ((uint64_t)(lbo >> 4) << 16) | ((uint64_t)(sbo >> 4) << 32) |
         ((uint64_t)sw << 62);
}
template <int N> __device__ __forceinline__ void fence_regs(float (&r)[N]) {
#pragma unroll
  for (int i = 0; i < N; i++) asm volatile("" : "+f"(r[i])::"memory");
}
__device__ __forceinline__ uint32_t pack_bf16(float lo, float hi) {
  uint32_t r;
  asm("cvt.rn.bf16x2.f32 %0, %1, %2;" : "=r"(r) : "f"(hi), "f"(lo));
  return r;
}
__device__ __forceinline__ float bf_lo(uint32_t v) { return __uint_as_float(v << 16); }
__device__ __forceinline__ float bf_hi(uint32_t v) { return __uint_as_float(v & 0xffff0000u); }
__device__ __forceinline__ float ex2(float x) {
  float y;
  asm("ex2.approx.ftz.f32 %0, %1;" : "=f"(y) : "f"(x));
  return y;
}
__device__ __forceinline__ uint4 ldg_nc(const void* p) {
  uint4 v;
  asm volatile("ld.global.nc.L1::no_allocate.v4.u32 {%0, %1, %2, %3}, [%4];"
               : "=r"(v.x), "=r"(v.y), "=r"(v.z), "=r"(v.w) : "l"(p));
  return v;
}

__device__ __forceinline__ uint4 ld_relaxed(const uint4* p) {
  uint64_t a, b;
  asm volatile("ld.relaxed.gpu.global.v2.u64 {%0, %1}, [%2];" : "=l"(a), "=l"(b) : "l"(p) : "memory");
  return make_uint4((uint32_t)a, (uint32_t)(a >> 32), (uint32_t)b, (uint32_t)(b >> 32));
}
__device__ __forceinline__ void st_relaxed(uint4* p, float x, float y, uint32_t tag) {
  const uint64_t a = ((uint64_t)tag << 32) | __float_as_uint(x), b = ((uint64_t)tag << 32) | __float_as_uint(y);
  asm volatile("st.relaxed.gpu.global.v2.u64 [%0], {%1, %2};" ::"l"(p), "l"(a), "l"(b) : "memory");
}
__device__ __forceinline__ void tma4d(uint32_t dst, const CUtensorMap* m, int c2, int c3, uint32_t bar) {
  asm volatile("cp.async.bulk.tensor.4d.shared::cluster.global.mbarrier::complete_tx::bytes [%0], [%1, {%3, %3, %4, %5}], [%2];"
               ::"r"(dst), "l"(m), "r"(bar), "r"(0), "r"(c2), "r"(c3) : "memory");
}
#define ACC8(a, v) do { a[0] += bf_lo(v.x); a[1] += bf_hi(v.x); a[2] += bf_lo(v.y); a[3] += bf_hi(v.y); \
                        a[4] += bf_lo(v.z); a[5] += bf_hi(v.z); a[6] += bf_lo(v.w); a[7] += bf_hi(v.w); } while (0)

__device__ __forceinline__ void wgmma_ss_n224(float (&d)[112], uint64_t da, uint64_t db, int sd) {
  asm volatile("{\n.reg .pred p;\nsetp.ne.b32 p, %114, 0;\n"
      "wgmma.mma_async.sync.aligned.m64n224k16.f32.bf16.bf16 {"
      "%0, %1, %2, %3, %4, %5, %6, %7, %8, %9, %10, %11, %12, %13, %14, %15, "
      "%16, %17, %18, %19, %20, %21, %22, %23, %24, %25, %26, %27, %28, %29, %30, %31, "
      "%32, %33, %34, %35, %36, %37, %38, %39, %40, %41, %42, %43, %44, %45, %46, %47, "
      "%48, %49, %50, %51, %52, %53, %54, %55, %56, %57, %58, %59, %60, %61, %62, %63, "
      "%64, %65, %66, %67, %68, %69, %70, %71, %72, %73, %74, %75, %76, %77, %78, %79, "
      "%80, %81, %82, %83, %84, %85, %86, %87, %88, %89, %90, %91, %92, %93, %94, %95, "
      "%96, %97, %98, %99, %100, %101, %102, %103, %104, %105, %106, %107, %108, %109, %110, %111"
      "}, %112, %113, p, 1, 1, 0, 1;\n}\n"
    : "+f"(d[0]), "+f"(d[1]), "+f"(d[2]), "+f"(d[3]), "+f"(d[4]), "+f"(d[5]), "+f"(d[6]), "+f"(d[7]),
      "+f"(d[8]), "+f"(d[9]), "+f"(d[10]), "+f"(d[11]), "+f"(d[12]), "+f"(d[13]), "+f"(d[14]), "+f"(d[15]),
      "+f"(d[16]), "+f"(d[17]), "+f"(d[18]), "+f"(d[19]), "+f"(d[20]), "+f"(d[21]), "+f"(d[22]), "+f"(d[23]),
      "+f"(d[24]), "+f"(d[25]), "+f"(d[26]), "+f"(d[27]), "+f"(d[28]), "+f"(d[29]), "+f"(d[30]), "+f"(d[31]),
      "+f"(d[32]), "+f"(d[33]), "+f"(d[34]), "+f"(d[35]), "+f"(d[36]), "+f"(d[37]), "+f"(d[38]), "+f"(d[39]),
      "+f"(d[40]), "+f"(d[41]), "+f"(d[42]), "+f"(d[43]), "+f"(d[44]), "+f"(d[45]), "+f"(d[46]), "+f"(d[47]),
      "+f"(d[48]), "+f"(d[49]), "+f"(d[50]), "+f"(d[51]), "+f"(d[52]), "+f"(d[53]), "+f"(d[54]), "+f"(d[55]),
      "+f"(d[56]), "+f"(d[57]), "+f"(d[58]), "+f"(d[59]), "+f"(d[60]), "+f"(d[61]), "+f"(d[62]), "+f"(d[63]),
      "+f"(d[64]), "+f"(d[65]), "+f"(d[66]), "+f"(d[67]), "+f"(d[68]), "+f"(d[69]), "+f"(d[70]), "+f"(d[71]),
      "+f"(d[72]), "+f"(d[73]), "+f"(d[74]), "+f"(d[75]), "+f"(d[76]), "+f"(d[77]), "+f"(d[78]), "+f"(d[79]),
      "+f"(d[80]), "+f"(d[81]), "+f"(d[82]), "+f"(d[83]), "+f"(d[84]), "+f"(d[85]), "+f"(d[86]), "+f"(d[87]),
      "+f"(d[88]), "+f"(d[89]), "+f"(d[90]), "+f"(d[91]), "+f"(d[92]), "+f"(d[93]), "+f"(d[94]), "+f"(d[95]),
      "+f"(d[96]), "+f"(d[97]), "+f"(d[98]), "+f"(d[99]), "+f"(d[100]), "+f"(d[101]), "+f"(d[102]), "+f"(d[103]),
      "+f"(d[104]), "+f"(d[105]), "+f"(d[106]), "+f"(d[107]), "+f"(d[108]), "+f"(d[109]), "+f"(d[110]), "+f"(d[111])
    : "l"(da), "l"(db), "r"(sd));
}
__device__ __forceinline__ void wgmma_ss_n208(float (&d)[104], uint64_t da, uint64_t db, int sd) {
  asm volatile("{\n.reg .pred p;\nsetp.ne.b32 p, %106, 0;\n"
      "wgmma.mma_async.sync.aligned.m64n208k16.f32.bf16.bf16 {"
      "%0, %1, %2, %3, %4, %5, %6, %7, %8, %9, %10, %11, %12, %13, %14, %15, "
      "%16, %17, %18, %19, %20, %21, %22, %23, %24, %25, %26, %27, %28, %29, %30, %31, "
      "%32, %33, %34, %35, %36, %37, %38, %39, %40, %41, %42, %43, %44, %45, %46, %47, "
      "%48, %49, %50, %51, %52, %53, %54, %55, %56, %57, %58, %59, %60, %61, %62, %63, "
      "%64, %65, %66, %67, %68, %69, %70, %71, %72, %73, %74, %75, %76, %77, %78, %79, "
      "%80, %81, %82, %83, %84, %85, %86, %87, %88, %89, %90, %91, %92, %93, %94, %95, "
      "%96, %97, %98, %99, %100, %101, %102, %103"
      "}, %104, %105, p, 1, 1, 0, 1;\n}\n"
    : "+f"(d[0]), "+f"(d[1]), "+f"(d[2]), "+f"(d[3]), "+f"(d[4]), "+f"(d[5]), "+f"(d[6]), "+f"(d[7]),
      "+f"(d[8]), "+f"(d[9]), "+f"(d[10]), "+f"(d[11]), "+f"(d[12]), "+f"(d[13]), "+f"(d[14]), "+f"(d[15]),
      "+f"(d[16]), "+f"(d[17]), "+f"(d[18]), "+f"(d[19]), "+f"(d[20]), "+f"(d[21]), "+f"(d[22]), "+f"(d[23]),
      "+f"(d[24]), "+f"(d[25]), "+f"(d[26]), "+f"(d[27]), "+f"(d[28]), "+f"(d[29]), "+f"(d[30]), "+f"(d[31]),
      "+f"(d[32]), "+f"(d[33]), "+f"(d[34]), "+f"(d[35]), "+f"(d[36]), "+f"(d[37]), "+f"(d[38]), "+f"(d[39]),
      "+f"(d[40]), "+f"(d[41]), "+f"(d[42]), "+f"(d[43]), "+f"(d[44]), "+f"(d[45]), "+f"(d[46]), "+f"(d[47]),
      "+f"(d[48]), "+f"(d[49]), "+f"(d[50]), "+f"(d[51]), "+f"(d[52]), "+f"(d[53]), "+f"(d[54]), "+f"(d[55]),
      "+f"(d[56]), "+f"(d[57]), "+f"(d[58]), "+f"(d[59]), "+f"(d[60]), "+f"(d[61]), "+f"(d[62]), "+f"(d[63]),
      "+f"(d[64]), "+f"(d[65]), "+f"(d[66]), "+f"(d[67]), "+f"(d[68]), "+f"(d[69]), "+f"(d[70]), "+f"(d[71]),
      "+f"(d[72]), "+f"(d[73]), "+f"(d[74]), "+f"(d[75]), "+f"(d[76]), "+f"(d[77]), "+f"(d[78]), "+f"(d[79]),
      "+f"(d[80]), "+f"(d[81]), "+f"(d[82]), "+f"(d[83]), "+f"(d[84]), "+f"(d[85]), "+f"(d[86]), "+f"(d[87]),
      "+f"(d[88]), "+f"(d[89]), "+f"(d[90]), "+f"(d[91]), "+f"(d[92]), "+f"(d[93]), "+f"(d[94]), "+f"(d[95]),
      "+f"(d[96]), "+f"(d[97]), "+f"(d[98]), "+f"(d[99]), "+f"(d[100]), "+f"(d[101]), "+f"(d[102]), "+f"(d[103])
    : "l"(da), "l"(db), "r"(sd));
}
__device__ __forceinline__ void wgmma_ss_n168(float (&d)[84], uint64_t da, uint64_t db, int sd) {
  asm volatile("{\n.reg .pred p;\nsetp.ne.b32 p, %86, 0;\n"
      "wgmma.mma_async.sync.aligned.m64n168k16.f32.bf16.bf16 {"
      "%0, %1, %2, %3, %4, %5, %6, %7, %8, %9, %10, %11, %12, %13, %14, %15, "
      "%16, %17, %18, %19, %20, %21, %22, %23, %24, %25, %26, %27, %28, %29, %30, %31, "
      "%32, %33, %34, %35, %36, %37, %38, %39, %40, %41, %42, %43, %44, %45, %46, %47, "
      "%48, %49, %50, %51, %52, %53, %54, %55, %56, %57, %58, %59, %60, %61, %62, %63, "
      "%64, %65, %66, %67, %68, %69, %70, %71, %72, %73, %74, %75, %76, %77, %78, %79, "
      "%80, %81, %82, %83"
      "}, %84, %85, p, 1, 1, 0, 1;\n}\n"
    : "+f"(d[0]), "+f"(d[1]), "+f"(d[2]), "+f"(d[3]), "+f"(d[4]), "+f"(d[5]), "+f"(d[6]), "+f"(d[7]),
      "+f"(d[8]), "+f"(d[9]), "+f"(d[10]), "+f"(d[11]), "+f"(d[12]), "+f"(d[13]), "+f"(d[14]), "+f"(d[15]),
      "+f"(d[16]), "+f"(d[17]), "+f"(d[18]), "+f"(d[19]), "+f"(d[20]), "+f"(d[21]), "+f"(d[22]), "+f"(d[23]),
      "+f"(d[24]), "+f"(d[25]), "+f"(d[26]), "+f"(d[27]), "+f"(d[28]), "+f"(d[29]), "+f"(d[30]), "+f"(d[31]),
      "+f"(d[32]), "+f"(d[33]), "+f"(d[34]), "+f"(d[35]), "+f"(d[36]), "+f"(d[37]), "+f"(d[38]), "+f"(d[39]),
      "+f"(d[40]), "+f"(d[41]), "+f"(d[42]), "+f"(d[43]), "+f"(d[44]), "+f"(d[45]), "+f"(d[46]), "+f"(d[47]),
      "+f"(d[48]), "+f"(d[49]), "+f"(d[50]), "+f"(d[51]), "+f"(d[52]), "+f"(d[53]), "+f"(d[54]), "+f"(d[55]),
      "+f"(d[56]), "+f"(d[57]), "+f"(d[58]), "+f"(d[59]), "+f"(d[60]), "+f"(d[61]), "+f"(d[62]), "+f"(d[63]),
      "+f"(d[64]), "+f"(d[65]), "+f"(d[66]), "+f"(d[67]), "+f"(d[68]), "+f"(d[69]), "+f"(d[70]), "+f"(d[71]),
      "+f"(d[72]), "+f"(d[73]), "+f"(d[74]), "+f"(d[75]), "+f"(d[76]), "+f"(d[77]), "+f"(d[78]), "+f"(d[79]),
      "+f"(d[80]), "+f"(d[81]), "+f"(d[82]), "+f"(d[83])
    : "l"(da), "l"(db), "r"(sd));
}
__device__ __forceinline__ void wgmma_ss_n160(float (&d)[80], uint64_t da, uint64_t db, int sd) {
  asm volatile("{\n.reg .pred p;\nsetp.ne.b32 p, %82, 0;\n"
      "wgmma.mma_async.sync.aligned.m64n160k16.f32.bf16.bf16 {"
      "%0, %1, %2, %3, %4, %5, %6, %7, %8, %9, %10, %11, %12, %13, %14, %15, "
      "%16, %17, %18, %19, %20, %21, %22, %23, %24, %25, %26, %27, %28, %29, %30, %31, "
      "%32, %33, %34, %35, %36, %37, %38, %39, %40, %41, %42, %43, %44, %45, %46, %47, "
      "%48, %49, %50, %51, %52, %53, %54, %55, %56, %57, %58, %59, %60, %61, %62, %63, "
      "%64, %65, %66, %67, %68, %69, %70, %71, %72, %73, %74, %75, %76, %77, %78, %79"
      "}, %80, %81, p, 1, 1, 0, 1;\n}\n"
    : "+f"(d[0]), "+f"(d[1]), "+f"(d[2]), "+f"(d[3]), "+f"(d[4]), "+f"(d[5]), "+f"(d[6]), "+f"(d[7]),
      "+f"(d[8]), "+f"(d[9]), "+f"(d[10]), "+f"(d[11]), "+f"(d[12]), "+f"(d[13]), "+f"(d[14]), "+f"(d[15]),
      "+f"(d[16]), "+f"(d[17]), "+f"(d[18]), "+f"(d[19]), "+f"(d[20]), "+f"(d[21]), "+f"(d[22]), "+f"(d[23]),
      "+f"(d[24]), "+f"(d[25]), "+f"(d[26]), "+f"(d[27]), "+f"(d[28]), "+f"(d[29]), "+f"(d[30]), "+f"(d[31]),
      "+f"(d[32]), "+f"(d[33]), "+f"(d[34]), "+f"(d[35]), "+f"(d[36]), "+f"(d[37]), "+f"(d[38]), "+f"(d[39]),
      "+f"(d[40]), "+f"(d[41]), "+f"(d[42]), "+f"(d[43]), "+f"(d[44]), "+f"(d[45]), "+f"(d[46]), "+f"(d[47]),
      "+f"(d[48]), "+f"(d[49]), "+f"(d[50]), "+f"(d[51]), "+f"(d[52]), "+f"(d[53]), "+f"(d[54]), "+f"(d[55]),
      "+f"(d[56]), "+f"(d[57]), "+f"(d[58]), "+f"(d[59]), "+f"(d[60]), "+f"(d[61]), "+f"(d[62]), "+f"(d[63]),
      "+f"(d[64]), "+f"(d[65]), "+f"(d[66]), "+f"(d[67]), "+f"(d[68]), "+f"(d[69]), "+f"(d[70]), "+f"(d[71]),
      "+f"(d[72]), "+f"(d[73]), "+f"(d[74]), "+f"(d[75]), "+f"(d[76]), "+f"(d[77]), "+f"(d[78]), "+f"(d[79])
    : "l"(da), "l"(db), "r"(sd));
}
__device__ __forceinline__ void wgmma_ss_n88(float (&d)[44], uint64_t da, uint64_t db, int sd) {
  asm volatile("{\n.reg .pred p;\nsetp.ne.b32 p, %46, 0;\n"
      "wgmma.mma_async.sync.aligned.m64n88k16.f32.bf16.bf16 {"
      "%0, %1, %2, %3, %4, %5, %6, %7, %8, %9, %10, %11, %12, %13, %14, %15, "
      "%16, %17, %18, %19, %20, %21, %22, %23, %24, %25, %26, %27, %28, %29, %30, %31, "
      "%32, %33, %34, %35, %36, %37, %38, %39, %40, %41, %42, %43"
      "}, %44, %45, p, 1, 1, 0, 1;\n}\n"
    : "+f"(d[0]), "+f"(d[1]), "+f"(d[2]), "+f"(d[3]), "+f"(d[4]), "+f"(d[5]), "+f"(d[6]), "+f"(d[7]),
      "+f"(d[8]), "+f"(d[9]), "+f"(d[10]), "+f"(d[11]), "+f"(d[12]), "+f"(d[13]), "+f"(d[14]), "+f"(d[15]),
      "+f"(d[16]), "+f"(d[17]), "+f"(d[18]), "+f"(d[19]), "+f"(d[20]), "+f"(d[21]), "+f"(d[22]), "+f"(d[23]),
      "+f"(d[24]), "+f"(d[25]), "+f"(d[26]), "+f"(d[27]), "+f"(d[28]), "+f"(d[29]), "+f"(d[30]), "+f"(d[31]),
      "+f"(d[32]), "+f"(d[33]), "+f"(d[34]), "+f"(d[35]), "+f"(d[36]), "+f"(d[37]), "+f"(d[38]), "+f"(d[39]),
      "+f"(d[40]), "+f"(d[41]), "+f"(d[42]), "+f"(d[43])
    : "l"(da), "l"(db), "r"(sd));
}
__device__ __forceinline__ void wgmma_ss_n80(float (&d)[40], uint64_t da, uint64_t db, int sd) {
  asm volatile("{\n.reg .pred p;\nsetp.ne.b32 p, %42, 0;\n"
      "wgmma.mma_async.sync.aligned.m64n80k16.f32.bf16.bf16 {"
      "%0, %1, %2, %3, %4, %5, %6, %7, %8, %9, %10, %11, %12, %13, %14, %15, "
      "%16, %17, %18, %19, %20, %21, %22, %23, %24, %25, %26, %27, %28, %29, %30, %31, "
      "%32, %33, %34, %35, %36, %37, %38, %39"
      "}, %40, %41, p, 1, 1, 0, 1;\n}\n"
    : "+f"(d[0]), "+f"(d[1]), "+f"(d[2]), "+f"(d[3]), "+f"(d[4]), "+f"(d[5]), "+f"(d[6]), "+f"(d[7]),
      "+f"(d[8]), "+f"(d[9]), "+f"(d[10]), "+f"(d[11]), "+f"(d[12]), "+f"(d[13]), "+f"(d[14]), "+f"(d[15]),
      "+f"(d[16]), "+f"(d[17]), "+f"(d[18]), "+f"(d[19]), "+f"(d[20]), "+f"(d[21]), "+f"(d[22]), "+f"(d[23]),
      "+f"(d[24]), "+f"(d[25]), "+f"(d[26]), "+f"(d[27]), "+f"(d[28]), "+f"(d[29]), "+f"(d[30]), "+f"(d[31]),
      "+f"(d[32]), "+f"(d[33]), "+f"(d[34]), "+f"(d[35]), "+f"(d[36]), "+f"(d[37]), "+f"(d[38]), "+f"(d[39])
    : "l"(da), "l"(db), "r"(sd));
}
__device__ __forceinline__ void wgmma_rs_n128(float (&d)[64], uint32_t a0, uint32_t a1, uint32_t a2, uint32_t a3,
                                  uint64_t db, int sd) {
  asm volatile("{\n.reg .pred p;\nsetp.ne.b32 p, %69, 0;\n"
      "wgmma.mma_async.sync.aligned.m64n128k16.f32.bf16.bf16 {"
      "%0, %1, %2, %3, %4, %5, %6, %7, %8, %9, %10, %11, %12, %13, %14, %15, "
      "%16, %17, %18, %19, %20, %21, %22, %23, %24, %25, %26, %27, %28, %29, %30, %31, "
      "%32, %33, %34, %35, %36, %37, %38, %39, %40, %41, %42, %43, %44, %45, %46, %47, "
      "%48, %49, %50, %51, %52, %53, %54, %55, %56, %57, %58, %59, %60, %61, %62, %63"
      "}, {%64, %65, %66, %67}, %68, p, 1, 1, 0;\n}\n"
    : "+f"(d[0]), "+f"(d[1]), "+f"(d[2]), "+f"(d[3]), "+f"(d[4]), "+f"(d[5]), "+f"(d[6]), "+f"(d[7]),
      "+f"(d[8]), "+f"(d[9]), "+f"(d[10]), "+f"(d[11]), "+f"(d[12]), "+f"(d[13]), "+f"(d[14]), "+f"(d[15]),
      "+f"(d[16]), "+f"(d[17]), "+f"(d[18]), "+f"(d[19]), "+f"(d[20]), "+f"(d[21]), "+f"(d[22]), "+f"(d[23]),
      "+f"(d[24]), "+f"(d[25]), "+f"(d[26]), "+f"(d[27]), "+f"(d[28]), "+f"(d[29]), "+f"(d[30]), "+f"(d[31]),
      "+f"(d[32]), "+f"(d[33]), "+f"(d[34]), "+f"(d[35]), "+f"(d[36]), "+f"(d[37]), "+f"(d[38]), "+f"(d[39]),
      "+f"(d[40]), "+f"(d[41]), "+f"(d[42]), "+f"(d[43]), "+f"(d[44]), "+f"(d[45]), "+f"(d[46]), "+f"(d[47]),
      "+f"(d[48]), "+f"(d[49]), "+f"(d[50]), "+f"(d[51]), "+f"(d[52]), "+f"(d[53]), "+f"(d[54]), "+f"(d[55]),
      "+f"(d[56]), "+f"(d[57]), "+f"(d[58]), "+f"(d[59]), "+f"(d[60]), "+f"(d[61]), "+f"(d[62]), "+f"(d[63])
    : "r"(a0), "r"(a1), "r"(a2), "r"(a3), "l"(db), "r"(sd));
}
__device__ __forceinline__ void wgmma_rs_n24(float (&d)[12], uint32_t a0, uint32_t a1, uint32_t a2, uint32_t a3,
                                  uint64_t db, int sd) {
  asm volatile("{\n.reg .pred p;\nsetp.ne.b32 p, %17, 0;\n"
      "wgmma.mma_async.sync.aligned.m64n24k16.f32.bf16.bf16 {"
      "%0, %1, %2, %3, %4, %5, %6, %7, %8, %9, %10, %11"
      "}, {%12, %13, %14, %15}, %16, p, 1, 1, 1;\n}\n"
    : "+f"(d[0]), "+f"(d[1]), "+f"(d[2]), "+f"(d[3]), "+f"(d[4]), "+f"(d[5]), "+f"(d[6]), "+f"(d[7]),
      "+f"(d[8]), "+f"(d[9]), "+f"(d[10]), "+f"(d[11])
    : "r"(a0), "r"(a1), "r"(a2), "r"(a3), "l"(db), "r"(sd));
}

#define KST 4
#define K1_EC 6
#define K1S 4
constexpr int K1_ST = K1S, K1_STAGE = 45056;
constexpr int K1_SMEM = K1_ST * K1_STAGE + 640   + 1536   + 2560   + 128;

__device__ __forceinline__ float2 row_stats(uint4 v0, uint4 v1, uint4 v2) {
  const uint32_t wd[12] = {v0.x, v0.y, v0.z, v0.w, v1.x, v1.y, v1.z, v1.w, v2.x, v2.y, v2.z, v2.w};
  float sx = 0.f, sq = 0.f;
#pragma unroll
  for (int e = 0; e < 12; e++) {
    const float lo = bf_lo(wd[e]), hi = bf_hi(wd[e]);
    sx += lo + hi; sq = fmaf(lo, lo, fmaf(hi, hi, sq));
  }
#pragma unroll
  for (int o = 16; o; o >>= 1) { sx += __shfl_xor_sync(~0u, sx, o); sq += __shfl_xor_sync(~0u, sq, o); }
  const float mean = sx * (1.f / D_);
  return make_float2(rsqrtf(fmaxf(sq * (1.f / D_) - mean * mean, 0.f) + 1e-5f), mean);
}

__global__ void __cluster_dims__(2, 1, 1) __launch_bounds__(512, 1)
k1_qkv(const __grid_constant__ CUtensorMap tmx, const __grid_constant__ CUtensorMap tmw,
       const bf16* __restrict__ x, const bf16* __restrict__ w, const bf16* __restrict__ wo) {
  extern __shared__ __align__(1024) uint8_t sm[];
  float* cs = (float*)(sm + K1_ST * K1_STAGE);
  float2* rowab = (float2*)(sm + K1_ST * K1_STAGE + 640);
  float* red = (float*)(sm + K1_ST * K1_STAGE + 2176);
  const uint32_t sbase = smem_u32(sm);
  const uint32_t fullb = sbase + K1_ST * K1_STAGE + 4736, emptyb = fullb + 8 * K1_ST;
  const int tid = threadIdx.x, lane = tid & 31;
  const int warp = __shfl_sync(~0u, tid >> 5, 0);
  const int rank = blockIdx.x & 1, cl = blockIdx.x >> 1;
  const int m = cl / 6, n = (cl - m * 6) * 2 + rank;
  if (tid == 0) STAMP(0, 0);

  if (warp == 12) {
    if (lane == 0) {
      prefetch_map(&tmx); prefetch_map(&tmw);
      for (int i = 0; i < K1_ST; i++) { mbar_init(fullb + 8 * i, 1); mbar_init(emptyb + 8 * i, K1_EC); }
      asm volatile("fence.mbarrier_init.release.cluster;" ::: "memory");
    }
    __syncwarp();
    cluster_arrive();
    bar_arrive(4, 512);
    if (lane == 0) {
      for (int kt = 0; kt < K1_ST; kt++) mbar_expect(fullb + 8 * kt, K1_STAGE);
#pragma unroll
      for (int j = 0; j < 5; j++) tma2d(sbase + 24576 + j * 4096, &tmw, n * 160 + j * 32, 0, fullb);
    }
    __syncwarp();
    cluster_wait();
    if (lane == 0) {
#pragma unroll 1
      for (int kt = 0; kt < 10; kt++) {
        const int s = kt % K1_ST;
        const uint32_t sa = sbase + s * K1_STAGE;
        if (kt >= K1_ST) {
          mbar_wait(emptyb + 8 * s, ((kt / K1_ST) - 1) & 1);
          mbar_expect(fullb + 8 * s, K1_STAGE);
        }
        tma2d_mc(sa + rank * 12288, &tmx, kt * 64, m * 192 + rank * 96, fullb + 8 * s);
        if (kt > 0) {
#pragma unroll
          for (int j = 0; j < 5; j++) tma2d(sa + 24576 + j * 4096, &tmw, n * 160 + j * 32, kt * 64, fullb + 8 * s);
        }
        if (kt == K1_ST - 1) {
          if (m * 192 + n * 16 < S_)
            asm volatile("cp.async.bulk.prefetch.L2.global [%0], %1;" ::"l"(x + (size_t)(m * 192 + n * 16) * D_), "r"(16 * D_ * 2) : "memory");
          if (m >= K1_ST && m < 10) {
#pragma unroll
            for (int j = 0; j < 5; j++)
              asm volatile("cp.async.bulk.prefetch.tensor.2d.L2.global [%0, {%1, %2}];" ::"l"(&tmw), "r"(n * 160 + j * 32), "r"(m * 64) : "memory");
          }
          pdl_trigger();
        }
      }
    }
    __syncwarp();
    cluster_arrive();
  } else if (warp > 12) {
    cluster_arrive();
    const int t96 = tid - 416;
    const uint32_t tag = __ldcg(&g_epoch) + 1;
    bar_sync(4, 512);
    mbar_wait(fullb, 0);
    if (m < 10) {
      const int ck = t96 % 20, rg = min(t96 / 20, 3);
      uint4 wv[16];
#pragma unroll
      for (int i = 0; i < 16; i++) wv[i] = ldg_nc(w + (size_t)(m * 64 + rg * 16 + i) * 1920 + n * 160 + ck * 8);
      float acc8[8];
#pragma unroll
      for (int i = 0; i < 8; i++) acc8[i] = 0.f;
#pragma unroll
      for (int i = 0; i < 16; i++) ACC8(acc8, wv[i]);
      *(float4*)&red[rg * 160 + ck * 8] = make_float4(acc8[0], acc8[1], acc8[2], acc8[3]);
      *(float4*)&red[rg * 160 + ck * 8 + 4] = make_float4(acc8[4], acc8[5], acc8[6], acc8[7]);
      bar_sync(1, 96);
      if (t96 < 80) {
        const float2 p0 = *(const float2*)&red[t96 * 2], p1 = *(const float2*)&red[160 + t96 * 2];
        const float2 p2 = *(const float2*)&red[320 + t96 * 2], p3 = *(const float2*)&red[480 + t96 * 2];
        st_relaxed(&g_cpart[(m * 12 + n) * 80 + t96], (p0.x + p1.x) + (p2.x + p3.x), (p0.y + p1.y) + (p2.y + p3.y), tag);
      }
    }
    if (tid == 416) STAMP(5, 7);
    bool ok = false;
    for (int it = 0; it < 64 && !ok; it++) {
      uint4 p[10], st[2];
#pragma unroll
      for (int k = 0; k < 10; k++) p[k] = ld_relaxed(&g_cpart[(k * 12 + n) * 80 + min(t96, 79)]);
#pragma unroll
      for (int k = 0; k < 2; k++) st[k] = ld_relaxed(&g_rowstat[min(m * 192 + k * 96 + t96, S_ - 1)]);
      ok = true;
      float s0 = 0.f, s1 = 0.f;
#pragma unroll
      for (int k = 0; k < 10; k++) {
        ok = ok && p[k].y == tag && p[k].w == tag;
        s0 += __uint_as_float(p[k].x); s1 += __uint_as_float(p[k].z);
      }
      if (t96 < 80) *(float2*)&cs[t96 * 2] = make_float2(s0, s1);
#pragma unroll
      for (int k = 0; k < 2; k++) {
        ok = ok && st[k].y == tag && st[k].w == tag;
        rowab[k * 96 + t96] = make_float2(__uint_as_float(st[k].x), -__uint_as_float(st[k].x) * __uint_as_float(st[k].z));
      }
      ok = __all_sync(~0u, ok);
      if (!ok) __nanosleep(300);
    }
    if (!ok) {
      const int c2 = min(t96, 79);
      float s0 = 0.f, s1 = 0.f;
#pragma unroll 1
      for (int k = 0; k < D_; k++) {
        const uint32_t v = *(const uint32_t*)(w + (size_t)k * 1920 + n * 160 + c2 * 2);
        s0 += bf_lo(v); s1 += bf_hi(v);
      }
      if (t96 < 80) *(float2*)&cs[t96 * 2] = make_float2(s0, s1);
#pragma unroll 1
      for (int i = 0; i < 64; i++) {
        const int r = (i >> 5) * 96 + (t96 & ~31) + (i & 31);
        const bf16* xr = x + (size_t)min(m * 192 + r, S_ - 1) * D_ + lane * 8;
        const float2 st = row_stats(ldg_nc(xr), ldg_nc(xr + 256), lane < 16 ? ldg_nc(xr + 512) : make_uint4(0u, 0u, 0u, 0u));
        if (lane == 0) rowab[r] = make_float2(st.x, -st.x * st.y);
      }
    }
    __syncwarp();
    bar_arrive(2, 96 + 384);
    bar_sync(1, 96);
    if (tid == 416) STAMP(0, 5);
    if (blockIdx.x < 128) {
      uint4 v[5];
      const int ck = min(t96, 79), nt = ck / 10;
#pragma unroll
      for (int i = 0; i < 5; i++) {
        const int k = blockIdx.x * 5 + i, pr = k / 40, r = k - pr * 40;
        v[i] = ldg_nc(wo + (size_t)(pr * 40 + (r < 16 ? r : (r < 32 ? r + 4 : (r < 36 ? r - 16 : r)))) * D_ + ck * 8);
      }
#pragma unroll
      for (int i = 0; i < 5; i++) {
        const int k = blockIdx.x * 5 + i;
        g_wo[((nt * 10 + (k >> 6)) * 10 + ck - nt * 10) * 64 + (k & 63)] = v[i];
        float t = ((bf_lo(v[i].x) + bf_hi(v[i].x)) + (bf_lo(v[i].y) + bf_hi(v[i].y))) +
                  ((bf_lo(v[i].z) + bf_hi(v[i].z)) + (bf_lo(v[i].w) + bf_hi(v[i].w)));
        if (t96 >= 80) t = 0.f;
#pragma unroll
        for (int o = 16; o; o >>= 1) t += __shfl_xor_sync(~0u, t, o);
        if (lane == 0) red[(t96 >> 5) * 8 + i] = t;
      }
      bar_sync(1, 96);
      if (t96 < 5) {
        const float mu = (red[t96] + red[8 + t96] + red[16 + t96]) * (1.f / D_);
        const float hi = bf_lo(pack_bf16(mu, 0.f));
        g_wm[blockIdx.x * 5 + t96] = make_uint4(pack_bf16(hi, mu - hi), 0u, 0u, 0u);
      }
    }
    if (tid == 416) STAMP(0, 7);
    __syncwarp();
    cluster_wait();
    cluster_arrive();
  } else {
    cluster_arrive();
    float acc[80];
    const uint64_t da0 = mkdesc(sbase + (warp >> 2) * 8192, 16, 1024, 1);
    const uint64_t db0 = mkdesc(sbase + 24576, 4096, 512, 2);
    const uint32_t tag = __ldcg(&g_epoch) + 1;
    const int srow = m * 192 + n * 16 + warp * 2;
    const bool dostat = warp < 8 && srow < S_;
    uint4 xv[2][3];
    bar_sync(4, 512);
    cluster_wait();
#pragma unroll
    for (int kt = 0; kt < 10; kt++) {
      const int s = kt % K1_ST;
      mbar_wait(fullb + 8 * s, (kt / K1_ST) & 1);
      if (kt == 0 && tid == 0) STAMP(0, 1);
      if (kt == 2 && tid == 0) STAMP(5, 0);
      if (kt == 4 && tid == 0) STAMP(5, 1);
      if (kt == 7 && tid == 0) STAMP(5, 2);
      const uint64_t da = da0 + s * (K1_STAGE >> 4), db = db0 + s * (K1_STAGE >> 4);
      WG_FENCE();
#pragma unroll
      for (int k = 0; k < 4; k++) wgmma_ss_n160(acc, da + k * 2, db + k * 64, (kt | k) != 0);
      WG_COMMIT();
      if (kt > 0) {
        WG_WAIT(1);
        if (kt - 1 + K1_ST < 10 && (tid & 127) < 2) mbar_arrive_cta(emptyb + 8 * ((kt - 1) % K1_ST), tid & 1);
      }
      if (kt == 0) {
#pragma unroll
        for (int i = 0; i < 2; i++) {
          const bf16* xr = x + (size_t)min(srow + i, S_ - 1) * D_ + lane * 8;
          xv[i][0] = xv[i][1] = xv[i][2] = make_uint4(0u, 0u, 0u, 0u);
          if (dostat) { xv[i][0] = ldg_nc(xr); xv[i][1] = ldg_nc(xr + 256); }
          if (dostat && lane < 16) xv[i][2] = ldg_nc(xr + 512);
        }
      }
      if ((kt == KST || kt == KST + 1) && dostat) {
        const float2 st = row_stats(xv[kt - KST][0], xv[kt - KST][1], xv[kt - KST][2]);
        if (lane == 0) st_relaxed(&g_rowstat[srow + kt - KST], st.x, st.y, tag);
      }
      __syncwarp();
    }
    cluster_arrive();
    WG_WAIT(0);
    fence_regs(acc);
    if (tid == 0) STAMP(0, 2);
    bar_sync(2, 96 + 384);
    if (tid == 0) STAMP(0, 3);
    const int row0 = m * 192 + warp * 16;
    if (row0 < S_) {
      const int g = lane >> 2, c = lane & 3, sec = n >> 2, grp = (row0 & 127) >> 3;
      const bool lo = c < 2;
      const float2 ab0 = rowab[warp * 16 + g], ab1 = rowab[warp * 16 + g + 8];
      const bool p0 = sec == 1 && ((POLY_MASK >> grp) & 1), p1 = sec == 1 && ((POLY_MASK >> (grp + 1)) & 1);
      const uint32_t padqv = sec == 0 ? (c == 2 ? 0x3F803F80u : 0x00003F80u) : (sec == 2 && c == 2 ? 0x00003F80u : 0u);
      const uint32_t padk = c == 2 ? 0x4A7A4B00u : 0x00004653u;
      const uint32_t pad0 = p0 ? padk : padqv, pad1 = p1 ? padk : padqv;
      const float f0 = sec == 0 ? QSCALE : (p0 ? 32768.f : 1.f), f1 = sec == 0 ? QSCALE : (p1 ? 32768.f : 1.f);
      const float a0 = ab0.x * f0, b0 = ab0.y * f0, a1 = ab1.x * f1, b1 = ab1.y * f1;
      const float r0 = p0 ? 9.313225746154785e-10f : 1.f, r1 = p1 ? 9.313225746154785e-10f : 1.f;
      const int cst = sec == 1 ? 2048 : 128, gst = sec == 1 ? 128 : 384;
      uint8_t* pe = (uint8_t*)g_qkv + (size_t)(n * 8) * HEAD_IMG + (row0 >> 7) * 6144 + grp * gst + lane * 4;
      uint8_t* pe1 = pe + cst;
      uint8_t* pe2 = pe1 + cst;
      uint8_t* pf = pe + gst;
      uint8_t* pf1 = pf + cst;
      uint8_t* pf2 = pf1 + cst;
#pragma unroll
      for (int hp = 0; hp < 4; hp++) {
        uint32_t u[5], v[5];
        float su[5], sv[5];
#pragma unroll
        for (int i = 0; i < 5; i++) {
          const int j = hp * 5 + i;
          const float2 t = *(const float2*)&cs[j * 8 + c * 2];
          const float x0 = fmaf(acc[4 * j], a0, b0 * t.x), x1 = fmaf(acc[4 * j + 1], a0, b0 * t.y);
          const float y0 = fmaf(acc[4 * j + 2], a1, b1 * t.x), y1 = fmaf(acc[4 * j + 3], a1, b1 * t.y);
          u[i] = pack_bf16(x0, x1); v[i] = pack_bf16(y0, y1);
          su[i] = fmaf(x0, x0, x1 * x1); sv[i] = fmaf(y0, y0, y1 * y1);
        }
        constexpr int HE = HEAD_IMG;
        const int oe = hp * 2 * HE, oo = oe + HE;
        *(uint32_t*)(pe + oe) = u[0];  *(uint32_t*)(pf + oe) = v[0];
        *(uint32_t*)(pe1 + oe) = u[1]; *(uint32_t*)(pf1 + oe) = v[1];
        *(uint32_t*)(pe2 + oe) = lo ? u[2] : pad0; *(uint32_t*)(pf2 + oe) = lo ? v[2] : pad1;
        *(uint32_t*)(pe + oo) = __shfl_xor_sync(~0u, lo ? u[3] : u[2], 2);
        *(uint32_t*)(pf + oo) = __shfl_xor_sync(~0u, lo ? v[3] : v[2], 2);
        *(uint32_t*)(pe1 + oo) = __shfl_xor_sync(~0u, lo ? u[4] : u[3], 2);
        *(uint32_t*)(pf1 + oo) = __shfl_xor_sync(~0u, lo ? v[4] : v[3], 2);
        const uint32_t tu = __shfl_xor_sync(~0u, u[4], 2), tv = __shfl_xor_sync(~0u, v[4], 2);
        *(uint32_t*)(pe2 + oo) = lo ? tu : pad0; *(uint32_t*)(pf2 + oo) = lo ? tv : pad1;
        if (sec < 2) {
          float e0 = (su[0] + su[1] + (lo ? su[2] : 0.f)) * r0, e1 = (sv[0] + sv[1] + (lo ? sv[2] : 0.f)) * r1;
          float o0 = (su[3] + su[4] + (lo ? 0.f : su[2])) * r0, o1 = (sv[3] + sv[4] + (lo ? 0.f : sv[2])) * r1;
          e0 += __shfl_xor_sync(~0u, e0, 1); e1 += __shfl_xor_sync(~0u, e1, 1);
          o0 += __shfl_xor_sync(~0u, o0, 1); o1 += __shfl_xor_sync(~0u, o1, 1);
          e0 += __shfl_xor_sync(~0u, e0, 2); e1 += __shfl_xor_sync(~0u, e1, 2);
          o0 += __shfl_xor_sync(~0u, o0, 2); o1 += __shfl_xor_sync(~0u, o1, 2);
          const uint32_t em = __reduce_max_sync(~0u, max(__float_as_uint(e0), __float_as_uint(e1)));
          const uint32_t om = __reduce_max_sync(~0u, max(__float_as_uint(o0), __float_as_uint(o1)));
          if (lane < 2) g_nrm[(n * 8 + hp * 2 + lane) * 128 + (row0 >> 4)] = __uint_as_float(lane ? om : em);
        }
      }
    }
    if (tid == 0) STAMP(0, 4);
  }
  cluster_wait();
  if (tid == 0) STAMP(0, 6);
}

constexpr int K2_SMEM = 2 * HEAD_IMG + 2 * 6144 + 2 * 10240 + 256;

__device__ __forceinline__ uint64_t desc64(uint32_t lo, uint32_t hi) {
  uint64_t d;
  asm("mov.b64 %0, {%1, %2};" : "=l"(d) : "r"(lo), "r"(hi));
  return d;
}
__device__ __forceinline__ uint32_t exp_pair(bool poly, float a, float b, uint32_t mk) {
  if (poly) {
    const uint32_t pk = __byte_perm(__float_as_uint(a), __float_as_uint(b), 0x6521);
    uint32_t m, q;
    asm("lop3.b32 %0, %1, %2, 0x3f803f80, 0xEA;" : "=r"(m) : "r"(pk), "r"(mk));
    asm("fma.rn.bf16x2 %0, %1, %1, %2;" : "=r"(q) : "r"(m), "r"(0x40014001u));
    return pk - m + q;
  }
  return pack_bf16(ex2(a), ex2(b));
}
#define PV_GR 4
__device__ __forceinline__ void exp_pv(const float (&s)[64], float (&o)[12], uint64_t dv, uint32_t mk) {
#pragma unroll
  for (int k0 = 0; k0 < 8; k0 += PV_GR) {
    uint32_t p[4 * PV_GR];
#pragma unroll
    for (int i = 0; i < 4 * PV_GR; i++)
      p[i] = exp_pair((POLY_MASK >> (k0 * 2 + i / 2)) & 1, s[k0 * 8 + 2 * i], s[k0 * 8 + 2 * i + 1], mk);
    WG_FENCE();
#pragma unroll
    for (int k = 0; k < PV_GR; k++)
      wgmma_rs_n24(o, p[4 * k], p[4 * k + 1], p[4 * k + 2], p[4 * k + 3], dv + (k0 + k) * 48, 1);
  }
}
__device__ __forceinline__ void load_q(uint32_t (&q)[6], const uint8_t* p) {
  q[0] = __ldcg((const uint32_t*)p);         q[1] = __ldcg((const uint32_t*)(p + 384));
  q[2] = __ldcg((const uint32_t*)(p + 128)); q[3] = __ldcg((const uint32_t*)(p + 512));
  q[4] = __ldcg((const uint32_t*)(p + 256)); q[5] = __ldcg((const uint32_t*)(p + 640));
}
__device__ __forceinline__ float rcp(float x) {
  float y;
  asm("rcp.approx.ftz.f32 %0, %1;" : "=f"(y) : "f"(x));
  return y;
}
__device__ __forceinline__ int img_off(int chunk) { return (chunk >> 3) * 16384 + (chunk & 7) * 128; }
__device__ __forceinline__ void store_o(const float (&o)[12], int tile) {
  int tid, bid;
  asm volatile("mov.u32 %0, %%tid.x;" : "=r"(tid));
  asm volatile("mov.u32 %0, %%ctaid.x;" : "=r"(bid));
  const int head = bid >> 2;
  uint8_t* dst = (uint8_t*)g_o + ((bid & 3) * 4 + (tile >> 1)) * 163840 + (tile & 1) * 8192 + ((tid >> 5) & 3) * 2048 + (tid & 31) * 4;
  const int oc = (head >> 1) * 5 + (head & 1) * 2;
  const int o0 = img_off(oc), o1 = img_off(oc + 1), o2 = img_off((head >> 1) * 5 + 4) + (head & 1) * 8;
  const float i0 = rcp(__shfl_sync(~0u, o[8], 2, 4)), i1 = rcp(__shfl_sync(~0u, o[10], 2, 4));
  *(uint32_t*)(dst + o0) = pack_bf16(o[0] * i0, o[1] * i0); *(uint32_t*)(dst + o0 + 1024) = pack_bf16(o[2] * i1, o[3] * i1);
  *(uint32_t*)(dst + o1) = pack_bf16(o[4] * i0, o[5] * i0); *(uint32_t*)(dst + o1 + 1024) = pack_bf16(o[6] * i1, o[7] * i1);
  if ((tid & 3) < 2) {
    *(uint32_t*)(dst + o2) = pack_bf16(o[8] * i0, o[9] * i0);
    *(uint32_t*)(dst + o2 + 1024) = pack_bf16(o[10] * i1, o[11] * i1);
  }
}

struct Maps5 { CUtensorMap m[5]; };

__global__ void __launch_bounds__(512, 1)
k2_attn(const __grid_constant__ Maps5 maps, uint32_t mk) {
  const CUtensorMap* tmw = maps.m;
  extern __shared__ __align__(1024) uint8_t sm[];
  const uint32_t sbase = smem_u32(sm);
  float* part = (float*)(sm + 2 * HEAD_IMG);
  const uint32_t rbuf = sbase + 2 * HEAD_IMG + 2 * 6144;
  const uint32_t kvb = rbuf + 2 * 10240;
  const uint32_t partb = kvb + 128, rbar = kvb + 144;
  const int tid = threadIdx.x, lane = tid & 31;
  const int warp = __shfl_sync(~0u, tid >> 5, 0);
  const int head = blockIdx.x >> 2, qb = blockIdx.x & 3;

  if (tid == 0) STAMP(1, 0);
  if (tid == 0) {
    for (int i = 0; i < 16; i++) mbar_init(kvb + 8 * i, 1);
    mbar_init(partb, 128); mbar_init(partb + 8, 128); mbar_init(rbar, 1); mbar_init(rbar + 8, 1);
    asm volatile("fence.mbarrier_init.release.cluster;" ::: "memory");
  }
  __syncthreads();

  if (warp >= 12) {
    asm volatile("setmaxnreg.dec.sync.aligned.u32 32;");
    if (tid == 384) {
      pdl_wait();
      pdl_trigger();
      const uint8_t* kimg = (const uint8_t*)g_qkv + (size_t)(32 + head) * HEAD_IMG;
#pragma unroll 1
      for (int b = 0; b < 16; b++) {
        mbar_expect(kvb + 8 * b, 12288);
        bulk_ld(sbase + b * 6144, kimg + b * 6144, 6144, kvb + 8 * b);
        bulk_ld(sbase + HEAD_IMG + b * 6144, kimg + 32 * HEAD_IMG + b * 6144, 6144, kvb + 8 * b);
        if (b >= 2) mbar_wait(kvb + 8 * (b - 1), 0);

      }
      if (blockIdx.x == 0) g_epoch = g_epoch + 1;
      mbar_wait(kvb + 8 * 15, 0);
      STAMP(1, 2);
      uint8_t* pdst = nullptr;
      uint32_t pbytes = 0;
#pragma unroll 1
      for (int i = 0; i < 8; i++) {
        const int p = blockIdx.x + 128 * i;
        uint8_t* dst = nullptr;
        uint32_t bytes = 0;
        if (i < 7 && p < 856) {
          asm volatile("cp.async.bulk.wait_group.read 0;" ::: "memory");
          const CUtensorMap* tm;
          int c1, c2;
          if (p < 640) {
            const int nt = p / 80, r = p - nt * 80, ph = r / 40, st = (r - ph * 40) >> 1, up = r & 1;
            bytes = ph ? 6656 : 7168;
            dst = (uint8_t*)g_wgu + nt * 552960 + ph * 286720 + (up * 20 + st) * bytes;
            tm = &tmw[ph * 2 + up]; c1 = ph ? 112 + nt * 13 : nt * 14; c2 = st * 2;
          } else {
            const int nk = p - 640, nt = nk / 27;
            bytes = 10240;
            dst = (uint8_t*)g_wd + (size_t)nk * 10240;
            tm = &tmw[4]; c1 = nt * 10; c2 = nk - nt * 27;
          }
          mbar_expect(rbar + 8 * (i & 1), bytes);
          tma4d(rbuf + (i & 1) * 10240, tm, c1, c2, rbar + 8 * (i & 1));
        }
        if (pbytes) {
          mbar_wait(rbar + 8 * ((i - 1) & 1), ((i - 1) >> 1) & 1);
          bulk_st(pdst, rbuf + ((i - 1) & 1) * 10240, pbytes);
          asm volatile("cp.async.bulk.commit_group;" ::: "memory");
        }
        pdst = dst; pbytes = bytes;
      }
      asm volatile("cp.async.bulk.wait_group.read 0;" ::: "memory");
      STAMP(1, 6);
    }
  } else {
    asm volatile("setmaxnreg.inc.sync.aligned.u32 160;");
    const int wg = warp >> 2;
    const uint8_t* qthr = (const uint8_t*)g_qkv + (size_t)head * HEAD_IMG + qb * 64 * 384 + (warp & 3) * 768 + lane * 4;
    const uint32_t klo0 = ((sbase & 0x3FFFF) >> 4) | (128u << 16), vlo0 = (((sbase + HEAD_IMG) & 0x3FFFF) >> 4) | (24u << 16);
    constexpr uint64_t KSTEP2 = (uint64_t)(int64_t)(256 - (128 << 16));
    constexpr uint64_t KV2K = 384 - (HEAD_IMG >> 4) + (104 << 16);
    const int nun = wg == 1 ? 4 : 3;
    uint32_t utile = wg == 0 ? 0x210u : (wg == 1 ? 0x4235u : 0x576u);
    uint32_t ubeg = wg == 0 ? 0u : (wg == 1 ? 0x0b00u : 0x600u);
    uint32_t ulen = wg == 0 ? 0x0b1010u : (wg == 1 ? 0x10051006u : 0x0a1010u);
    pdl_wait();
    if (tid == 0) STAMP(1, 1);
    uint32_t q[6];
    load_q(q, qthr + (utile & 15) * 3072);
    bool fast;
    {
      const float4 kn = __ldcg((const float4*)&g_nrm[(32 + head) * 128 + lane * 4]);
      const float qv = __ldcg(&g_nrm[head * 128 + qb * 32 + lane]);
      const uint32_t km = max(max(__float_as_uint(kn.x), __float_as_uint(kn.y)), max(__float_as_uint(kn.z), __float_as_uint(kn.w)));
      const float k2 = __uint_as_float(__reduce_max_sync(~0u, km)), q2 = __uint_as_float(__reduce_max_sync(~0u, __float_as_uint(qv)));
      fast = q2 * k2 <= 3400.f;
    }
    if (fast) {
#pragma unroll 1
      for (int u = 0; u < nun; u++) {
        const uint32_t b0 = ubeg & 15;
        const bool wt = u == 0 || (wg == 1 && u == 1);
        float s[64], o[12];
#pragma unroll
        for (int i = 0; i < 12; i++) o[i] = 0.f;
        uint32_t vlo = vlo0 + b0 * 384, kb = kvb + b0 * 8;
        const uint32_t vend = vlo + ((ulen & 255) - 1) * 384;
        if (wt) mbar_wait(kb, 0);
        if (tid == 0) STAMP(5, 4 + u);
        fence_regs(o);
        WG_FENCE();
        wgmma_rs_n128(s, q[0], q[1], q[2], q[3], desc64(klo0 + b0 * 384, 8), 0);
        wgmma_rs_n128(s, q[4], q[5], 0, 0, desc64(klo0 + b0 * 384, 8) + KSTEP2, 1);
        WG_COMMIT();
#define K2UNR 1
        constexpr int kUnr = K2UNR;
#pragma unroll kUnr
        for (; vlo != vend; vlo += 384) {
          if (wt) { kb += 8; mbar_wait(kb, 0); }
          WG_WAIT(0);
          fence_regs(s); fence_regs(o);
          const uint64_t dv = desc64(vlo, 8);
          exp_pv(s, o, dv, mk);
          wgmma_rs_n128(s, q[0], q[1], q[2], q[3], dv + KV2K, 0);
          wgmma_rs_n128(s, q[4], q[5], 0, 0, dv + (KV2K + KSTEP2), 1);
          WG_COMMIT();
        }
        WG_WAIT(0);
        fence_regs(s); fence_regs(o);
        if (u + 1 < nun) load_q(q, qthr + ((utile >> 4) & 15) * 3072);
        exp_pv(s, o, desc64(vlo, 8), mk);
        WG_COMMIT();
        WG_WAIT(0);
        fence_regs(o);
        if (wg == 1 && !(u & 1)) {
          float4* pp = (float4*)(part + u * 768) + (tid & 127);
          pp[0] = make_float4(o[0], o[1], o[2], o[3]);
          pp[128] = make_float4(o[4], o[5], o[6], o[7]);
          pp[256] = make_float4(o[8], o[9], o[10], o[11]);
          mbar_arrive(partb + 4 * u);
        } else {
          if (wg != 1 && u == 2) {
            const int pi = wg == 0 ? 1 : 0;
            mbar_wait(partb + 8 * pi, 0);
            const float4* pp = (const float4*)(part + pi * 1536) + (tid & 127);
            const float4 x0 = pp[0], x1 = pp[128], x2 = pp[256];
            o[0] += x0.x; o[1] += x0.y; o[2] += x0.z; o[3] += x0.w; o[4] += x1.x; o[5] += x1.y;
            o[6] += x1.z; o[7] += x1.w; o[8] += x2.x; o[9] += x2.y; o[10] += x2.z; o[11] += x2.w;
          }
          store_o(o, utile & 15);
        }
        utile >>= 4; ubeg >>= 4; ulen >>= 8;
      }
      if ((tid & 127) == 0) STAMP(1, 3 + wg);
    } else {
#pragma unroll 1
      for (int tile = wg; tile < 8; tile += 3) {
        load_q(q, qthr + tile * 3072);
        if ((lane & 3) >= 2) { q[4] = 0; q[5] = 0; }
        float o[12], m0 = -INFINITY, m1 = -INFINITY;
#pragma unroll
        for (int i = 0; i < 12; i++) o[i] = 0.f;
#pragma unroll 1
        for (int b = 0; b < 16; b++) {
          float s[64];
          mbar_wait(kvb + 8 * b, 0);
          WG_FENCE();
          wgmma_rs_n128(s, q[0], q[1], q[2], q[3], desc64(klo0 + b * 384, 8), 0);
          wgmma_rs_n128(s, q[4], q[5], 0, 0, desc64(klo0 + b * 384, 8) + KSTEP2, 1);
          WG_COMMIT();
          WG_WAIT(0);
          fence_regs(s);
          float x0 = m0, x1 = m1;
#pragma unroll
          for (int j = 0; j < 16; j++) {
            if ((POLY_MASK >> j) & 1) {
#pragma unroll
              for (int i = 0; i < 4; i++) s[4 * j + i] *= (1.f / 32768.f);
            }
            x0 = fmaxf(x0, fmaxf(s[4 * j], s[4 * j + 1]));
            x1 = fmaxf(x1, fmaxf(s[4 * j + 2], s[4 * j + 3]));
          }
          x0 = fmaxf(x0, __shfl_xor_sync(~0u, x0, 1)); x0 = fmaxf(x0, __shfl_xor_sync(~0u, x0, 2));
          x1 = fmaxf(x1, __shfl_xor_sync(~0u, x1, 1)); x1 = fmaxf(x1, __shfl_xor_sync(~0u, x1, 2));
          const float al0 = ex2(m0 - x0), al1 = ex2(m1 - x1);
          m0 = x0; m1 = x1;
#pragma unroll
          for (int i = 0; i < 12; i++) o[i] *= (i & 2) ? al1 : al0;
          uint32_t p[32];
#pragma unroll
          for (int i = 0; i < 32; i++) {
            const float mm = (i & 1) ? m1 : m0;
            p[i] = pack_bf16(ex2(s[2 * i] - mm), ex2(s[2 * i + 1] - mm));
          }
          fence_regs(o);
          WG_FENCE();
#pragma unroll
          for (int k = 0; k < 8; k++)
            wgmma_rs_n24(o, p[4 * k], p[4 * k + 1], p[4 * k + 2], p[4 * k + 3], desc64(vlo0 + b * 384 + k * 48, 8), 1);
          WG_COMMIT();
          WG_WAIT(0);
          fence_regs(o);
        }
        store_o(o, tile);
      }
    }
  }
}

#define K3P 2
constexpr int K3_ST = 4, K3_STAGE = 37888, K3_PRE = K3P;
constexpr int K3_SMEM = K3_ST * K3_STAGE + 45056 + 20480 + 256;

template <int N> struct Acc { float v[N]; };

template <int NB, int NK, bool FIRST>
__global__ void __cluster_dims__(2, 1, 1) __launch_bounds__(384, 1)
k3_proj(const __grid_constant__ CUtensorMap tmr, const uint4* __restrict__ aimg, const uint4* __restrict__ wimg) {
  constexpr int KT = 2 * NB + NK, EX = FIRST ? 1 : 0;
  extern __shared__ __align__(1024) uint8_t sm[];
  const uint32_t sbase = smem_u32(sm);
  uint8_t* xch = sm + K3_ST * K3_STAGE;
  uint8_t* stg = sm + K3_ST * K3_STAGE + 45056;
  const uint32_t fullb = smem_u32(stg) + 20480, emptyb = fullb + 8 * K3_ST, resb = emptyb + 8 * K3_ST, xchb = resb + 8;
  const int tid = threadIdx.x, lane = tid & 31;
  const int warp = __shfl_sync(~0u, tid >> 5, 0);
  const int rank = blockIdx.x & 1;
  const int n = blockIdx.x & 7, m = blockIdx.x >> 3;
  if (tid == 0) STAMP(FIRST ? 2 : 4, 0);
  if (warp == 0) {
    if (lane == 0) {
      prefetch_map(&tmr);
      for (int i = 0; i < K3_ST; i++) { mbar_init(fullb + 8 * i, 1); mbar_init(emptyb + 8 * i, 4); }
      mbar_init(resb, 1); mbar_init(xchb, 1);
      mbar_expect(xchb, 4096 * (10 + EX));
      asm volatile("fence.mbarrier_init.release.cluster;" ::: "memory");
    }
    __syncwarp();
    cluster_arrive();
    bar_arrive(4, 256 + 32);
    if (lane == 0) {
      const uint8_t* wk = (const uint8_t*)wimg + (size_t)n * KT * 10240;
      const uint8_t* ws = (const uint8_t*)wimg + (size_t)(n ^ 1) * KT * 10240;
      const uint8_t* ab = (const uint8_t*)aimg + (size_t)m * KT * 16384;
      auto load_w = [&](int i) {
        const int s = i % K3_ST, kt = i < NB ? i + rank * (NB + NK) : i;
        const uint32_t sa = sbase + s * K3_STAGE;
        mbar_expect(fullb + 8 * s, 26624 + EX * 1024 + (i < NB ? 10240 : 0));
        bulk_ld(sa + 16384, wk + kt * 10240, 10240, fullb + 8 * s);
        if (FIRST) bulk_ld(sa + 26624, (const uint8_t*)g_wm + kt * 1024, 1024, fullb + 8 * s);
        if (i < NB) bulk_ld(sa + 26624 + EX * 1024, ws + kt * 10240, 10240, fullb + 8 * s);
      };
#pragma unroll 1
      for (int i = 0; i < K3_PRE; i++) load_w(i);
      if (FIRST) {
        mbar_expect(resb, 20480);
        tma2d(smem_u32(stg), &tmr, n * 80, m * 128, resb);
        tma2d(smem_u32(stg) + 10240, &tmr, n * 80, m * 128 + 64, resb);
      }
      asm volatile("barrier.cluster.wait;" ::: "memory");
      pdl_wait();
      pdl_trigger();
#pragma unroll 1
      for (int i = 0; i < NB + NK; i++) {
        const int s = i % K3_ST;
        const uint32_t sa = sbase + s * K3_STAGE;
        if (i >= K3_ST) mbar_wait(emptyb + 8 * s, ((i / K3_ST) - 1) & 1);
        if (i < NB) bulk_ld(sa, ab + (i + rank * (NB + NK)) * 16384, 16384, fullb + 8 * s);
        else bulk_ld_mc(sa + rank * 8192, ab + i * 16384 + rank * 8192, 8192, fullb + 8 * s);
        if (i >= K3_PRE) load_w(i);
      }
    } else {
      asm volatile("barrier.cluster.wait;" ::: "memory");
    }
    __syncwarp();
    cluster_arrive();
  } else if (warp >= 4) {
    cluster_arrive();
    const int cw = warp - 4, wg = cw >> 2;
    const int g = lane >> 2, c = lane & 3;
    const int row = m * 128 + cw * 16 + g;
    uint8_t* himg = (uint8_t*)g_h + (size_t)m * 163840 + cw * 2048 + lane * 4;
    uint32_t rv[20];
    float mu0, mu1;
    if (FIRST) {
      mu0 = __uint_as_float(__ldcg(&g_rowstat[row].z)); mu1 = __uint_as_float(__ldcg(&g_rowstat[row + 8].z));
    } else {
      mu0 = __ldcg(&g_hmean[row]); mu1 = __ldcg(&g_hmean[row + 8]);
#pragma unroll
      for (int j = 0; j < 10; j++) {
        rv[2 * j] = __ldcg((const uint32_t*)(himg + img_off(n * 10 + j)));
        rv[2 * j + 1] = __ldcg((const uint32_t*)(himg + img_off(n * 10 + j) + 1024));
      }
    }
    float acc[80 + 4 * EX];
    float (&keep)[40 + 4 * EX] = ((Acc<40 + 4 * EX>*)acc)->v;
    const uint64_t da0 = mkdesc(sbase + wg * 8192, 128, 1024, 0);
    const uint64_t db0 = mkdesc(sbase + 16384, 128, 1024, 0);
    bar_sync(4, 256 + 32);
    cluster_wait();
#pragma unroll 1
    for (int i = 0; i < NB; i++) {
      const int s = i % K3_ST;
      mbar_wait(fullb + 8 * s, (i / K3_ST) & 1);
      if (i == 0 && tid == 128) STAMP(FIRST ? 2 : 4, 2);
      const uint64_t da = da0 + s * (K3_STAGE >> 4), db = db0 + s * (K3_STAGE >> 4);
      WG_FENCE();
#pragma unroll
      for (int k = 0; k < 4; k++) {
        if constexpr (FIRST) wgmma_ss_n168(acc, da + k * 16, db + k * 16, (i | k) != 0);
        else wgmma_ss_n160(acc, da + k * 16, db + k * 16, (i | k) != 0);
      }
      WG_COMMIT();
      if (i > 0) {
        WG_WAIT(1);
        if ((tid & 127) < 2) mbar_arrive_cta(emptyb + 8 * ((i - 1) % K3_ST), tid & 1);
      }
    }
    const uint32_t rx = mapa(smem_u32(xch) + (tid - 128) * 16, rank ^ 1), rb = mapa(xchb, rank ^ 1);
    WG_WAIT(0);
    fence_regs(acc);
    if ((tid & 127) < 2) mbar_arrive_cta(emptyb + 8 * ((NB - 1) % K3_ST), tid & 1);
    if (FIRST) st_async4(rx, acc[40], acc[41], acc[42], acc[43], rb);
    if (tid == 128) STAMP(FIRST ? 2 : 4, 1);
#pragma unroll
    for (int i = NB; i < NB + NK; i++) {
      const int s = i % K3_ST;
      mbar_wait(fullb + 8 * s, (i / K3_ST) & 1);
      const uint64_t da = da0 + s * (K3_STAGE >> 4), db = db0 + s * (K3_STAGE >> 4);
      WG_FENCE();
#pragma unroll
      for (int k = 0; k < 4; k++) {
        if constexpr (FIRST) wgmma_ss_n88(keep, da + k * 16, db + k * 16, 1);
        else wgmma_ss_n80(keep, da + k * 16, db + k * 16, 1);
      }
      WG_COMMIT();
      if (i > NB && i - 1 + K3_ST < NB + NK) {
        WG_WAIT(1);
        if ((tid & 127) < 2) mbar_arrive_cta(emptyb + 8 * ((i - 1) % K3_ST), tid & 1);
      }
#pragma unroll
      for (int j = (i - NB) * 3 + EX; j < (i - NB) * 3 + 3 + EX; j++)
        if (j < 10 + EX) st_async4(rx + j * 4096, acc[40 + 4 * j], acc[41 + 4 * j], acc[42 + 4 * j], acc[43 + 4 * j], rb);
    }
    cluster_arrive();
    uint8_t* sp = stg + (cw * 16 + g) * 160 + c * 4;
    if (FIRST) {
      mbar_wait(resb, 0);
#pragma unroll
      for (int j = 0; j < 10; j++) {
        rv[2 * j] = *(const uint32_t*)(sp + j * 16);
        rv[2 * j + 1] = *(const uint32_t*)(sp + 1280 + j * 16);
      }
    }
    WG_WAIT(0);
    fence_regs(keep);
    if (tid == 128) STAMP(FIRST ? 2 : 4, 3);
    mbar_wait(xchb, 0);
    if (tid == 128) STAMP(FIRST ? 2 : 4, 5);
    const uint8_t* xp = xch + (tid - 128) * 16;
    if (FIRST) {
      const float4 p = *(const float4*)xp;
      mu0 += __shfl_sync(~0u, (keep[40] + p.x) + (keep[41] + p.y), 0, 4);
      mu1 += __shfl_sync(~0u, (keep[42] + p.z) + (keep[43] + p.w), 0, 4);
      if (n == 0 && c == 0) { g_hmean[row] = mu0; g_hmean[row + 8] = mu1; }
      mu0 = -mu0; mu1 = -mu1;
    }
    float q0 = 0.f, q1 = 0.f;
#pragma unroll
    for (int j = 0; j < 10; j++) {
      const float4 p = *(const float4*)(xp + (j + EX) * 4096);
      const float x0 = (keep[4 * j] + p.x) + (bf_lo(rv[2 * j]) + mu0), x1 = (keep[4 * j + 1] + p.y) + (bf_hi(rv[2 * j]) + mu0);
      const float y0 = (keep[4 * j + 2] + p.z) + (bf_lo(rv[2 * j + 1]) + mu1), y1 = (keep[4 * j + 3] + p.w) + (bf_hi(rv[2 * j + 1]) + mu1);
      if (FIRST) {
        *(uint32_t*)(himg + img_off(n * 10 + j)) = pack_bf16(x0, x1);
        *(uint32_t*)(himg + img_off(n * 10 + j) + 1024) = pack_bf16(y0, y1);
        q0 = fmaf(x0, x0, fmaf(x1, x1, q0)); q1 = fmaf(y0, y0, fmaf(y1, y1, q1));
      } else {
        *(uint32_t*)(sp + j * 16) = pack_bf16(x0, x1);
        *(uint32_t*)(sp + 1280 + j * 16) = pack_bf16(y0, y1);
      }
    }
    if (FIRST) {
      q0 += __shfl_xor_sync(~0u, q0, 1); q0 += __shfl_xor_sync(~0u, q0, 2);
      q1 += __shfl_xor_sync(~0u, q1, 1); q1 += __shfl_xor_sync(~0u, q1, 2);
      if (c < 2) g_hpart[n * S_ + row + c * 8] = c ? q1 : q0;
    } else {
      fence_async();
      bar_sync(1 + wg, 128);
      if ((tid & 127) == 0) {
        tma2d_st(&tmr, n * 80, m * 128 + wg * 64, smem_u32(stg) + wg * 10240);
        bulk_commit_wait();
      }
      __syncwarp();
    }
    if (tid == 128) STAMP(FIRST ? 2 : 4, 4);
  } else {
    cluster_arrive();
    cluster_wait();
    cluster_arrive();
  }
  cluster_wait();
}

constexpr int K4_NS = 9;
constexpr int K4_RB = 163840, K4_BST = 7168, K4_XCH = 147456, K4_STG = K4_XCH + 40960, K4_BAR = K4_RB + K4_NS * K4_BST;
constexpr int K4_SMEM = K4_BAR + 384;

__device__ __forceinline__ void wait_flags(const uint4* f, uint32_t tag) {
  for (uint32_t it = 0;; it++) {
    uint4 a, b;
    asm volatile("ld.acquire.gpu.global.v4.u32 {%0, %1, %2, %3}, [%4];" : "=r"(a.x), "=r"(a.y), "=r"(a.z), "=r"(a.w) : "l"(f) : "memory");
    asm volatile("ld.acquire.gpu.global.v4.u32 {%0, %1, %2, %3}, [%4];" : "=r"(b.x), "=r"(b.y), "=r"(b.z), "=r"(b.w) : "l"(f + 1) : "memory");
    if (a.x == tag && a.y == tag && a.z == tag && a.w == tag && b.x == tag && b.y == tag && b.z == tag && b.w == tag) break;
    if (it > (1u << 20)) wait_timeout();
    __nanosleep(50);
  }
  asm volatile("fence.proxy.async.global;" ::: "memory");
}

__global__ void __cluster_dims__(2, 1, 1) __launch_bounds__(384, 1)
k45_ffn(const __grid_constant__ CUtensorMap tmo) {
  extern __shared__ __align__(1024) uint8_t sm[];
  const uint32_t sbase = smem_u32(sm);
  const uint32_t afull = sbase + K4_BAR, bfull = afull + 80, bempty = bfull + 8 * K4_NS, full3 = bempty + 8 * K4_NS;
  const uint32_t empty3 = full3 + 32, afree = empty3 + 32, xchb = afree + 32;
  const int tid = threadIdx.x, lane = tid & 31;
  const int warp = __shfl_sync(~0u, tid >> 5, 0);
  const int rank = blockIdx.x & 1;
  const int n1 = (blockIdx.x >> 1) & 7, m1 = (blockIdx.x >> 4) * 2 + rank;
  const int n3 = blockIdx.x & 7, m3 = blockIdx.x >> 3;
  if (tid == 0) STAMP(3, 0);
  if (warp == 8) {
    if (lane < 10) mbar_init(afull + 8 * lane, 1);
    if (lane < K4_NS) { mbar_init(bfull + 8 * lane, 1); mbar_init(bempty + 8 * lane, 4); }
    if (lane < 4) { mbar_init(full3 + 8 * lane, 1); mbar_init(empty3 + 8 * lane, 4); mbar_init(afree + 8 * lane, 2); }
    if (lane == 0) { mbar_init(xchb, 1); mbar_expect(xchb, 40960); prefetch_map(&tmo); }
    asm volatile("fence.mbarrier_init.release.cluster;" ::: "memory");
    __syncwarp();
  }
  cluster_arrive();
  if (warp >= 8) {
    cluster_wait();
    if (warp == 8) {
      if (lane == 0) {
        const uint8_t* wb = (const uint8_t*)g_wgu + n1 * 552960;
        const uint8_t* hb = (const uint8_t*)g_h + (size_t)m1 * 163840;
        int s = 0, ph = 1;
#pragma unroll 1
        for (int j = 0; j < 80; j++) {
          if (j == K4_NS) {
            pdl_wait();
            STAMP(3, 1);
#pragma unroll 1
            for (int kt = 0; kt < 3; kt++) { mbar_expect(afull + 8 * kt, 16384); bulk_ld(sbase + kt * 16384, hb + kt * 16384, 16384, afull + 8 * kt); }
          }
          if (j >= K4_NS) mbar_wait(bempty + 8 * s, ph);
          if (j >= 12 && j < 40 && !(j & 3)) {
            const int kt = j >> 2;
            mbar_expect(afull + 8 * kt, 16384);
            bulk_ld(sbase + kt * 16384, hb + kt * 16384, 16384, afull + 8 * kt);
          }
          const uint32_t half = j < 40 ? 3584 : 3328;
          mbar_expect(bfull + 8 * s, 2 * half);
          bulk_ld_mc(sbase + K4_RB + s * K4_BST + rank * half, wb + (j < 40 ? j * 3584 : 286720 + (j - 40) * 3328) + rank * 40 * half,
                     half, bfull + 8 * s);
          if (++s == K4_NS) { s = 0; ph ^= 1; }
        }
      }
    } else if (warp == 9) {
      const uint32_t tag = __ldcg(&g_epoch);
#pragma unroll 1
      for (int ph = 0; ph < 2; ph++) {
        bar_sync(5 + ph, 256 + 32);
        if (lane == 0) {
          asm volatile("st.release.gpu.global.u32 [%0], %1;" ::"l"((uint32_t*)&g_flag[ph * 32 + m1 * 2] + n1), "r"(tag) : "memory");
          STAMP(3, 5 + ph);
        }
        __syncwarp();
      }
    } else if (lane == 0) {
      const uint8_t* wk = (const uint8_t*)g_wd + n3 * 276480;
      const uint8_t* ws = (const uint8_t*)g_wd + (n3 ^ 1) * 276480;
      const uint8_t* ab = (const uint8_t*)g_hh + (size_t)m3 * 442368;
      const uint32_t tag = __ldcg(&g_epoch);
#pragma unroll 1
      for (int i = 0; i < 16; i++) {
        const int kt = i < 7 ? rank * 7 + i : (i < 11 ? rank * 4 + 7 + i : 11 + i);
        const uint32_t sa = sbase + (i & 3) * 36864, fb = full3 + 8 * (i & 3);
        if (i < 4) mbar_wait(afree + 8 * i, 0);
        else mbar_wait(empty3 + 8 * (i & 3), ((i >> 2) - 1) & 1);
        if (warp == 10) {
          mbar_expect(fb, i < 11 ? 36864 : 26624);
          bulk_ld(sa + 16384, wk + kt * 10240, 10240, fb);
          if (i < 11) bulk_ld(sa + 26624, ws + kt * 10240, 10240, fb);
        } else {
          if (i == 0 || i == 7) {
            wait_flags(&g_flag[(i ? 32 : 0) + m3 * 2], tag);
            STAMP(4, i ? 7 : 6);
          }
          if (i < 11) bulk_ld(sa, ab + kt * 16384, 16384, fb);
          else bulk_ld_mc(sa + rank * 8192, ab + kt * 16384 + rank * 8192, 8192, fb);
        }
      }
    }
    __syncwarp();
    cluster_arrive();
    asm volatile("barrier.cluster.wait.aligned; // producers" ::: "memory");
  } else {
    const int wg = warp >> 2;
    const uint64_t da0 = mkdesc(sbase + wg * 8192, 128, 1024, 0);
    const uint64_t db0 = mkdesc(sbase + K4_RB, 128, 256, 0);
    cluster_wait();
    float a1[112], a2[104];
    int s = 0, ph = 0, sprev = 0;
#pragma unroll 1
    for (int j = 0; j < 40; j++) {
      if (!(j & 3)) mbar_wait(afull + 2 * j, 0);
      mbar_wait(bfull + 8 * s, ph);
      if (j == 0 && tid == 0) STAMP(3, 2);
      WG_FENCE();
      wgmma_ss_n224(a1, da0 + (j >> 2) * 1024 + (j & 3) * 16, db0 + s * (K4_BST >> 4), j != 0);
      WG_COMMIT();
      if (j > 0) {
        WG_WAIT(1);
        if ((tid & 127) < 2) mbar_arrive_cta(bempty + 8 * sprev, tid & 1);
      }
      sprev = s;
      if (++s == K4_NS) { s = 0; ph ^= 1; }
    }
    float r0, r1;
    {
      const float* hp = &g_hpart[(lane & 3) * 2 * S_ + m1 * 128 + warp * 16 + (lane >> 2)];
      r0 = __ldcg(hp) + __ldcg(hp + S_);
      r1 = __ldcg(hp + 8) + __ldcg(hp + S_ + 8);
    }
    float acc[80];
    uint8_t* hd = (uint8_t*)g_hh + (size_t)m1 * 442368 + warp * 2048 + lane * 4;
    {
      r0 += __shfl_xor_sync(~0u, r0, 1); r1 += __shfl_xor_sync(~0u, r1, 1);
      r0 += __shfl_xor_sync(~0u, r0, 2); r1 += __shfl_xor_sync(~0u, r1, 2);
      r0 = __frcp_rn(r0 * (1.f / D_) + 1e-5f); r1 = __frcp_rn(r1 * (1.f / D_) + 1e-5f);
    }
    WG_WAIT(0);
    fence_regs(a1);
    if ((tid & 127) < 2) mbar_arrive_cta(bempty + 8 * ((39) % K4_NS), tid & 1);
    if (tid == 0) STAMP(3, 3);
#define STORE_H(a, off, q, c) do { uint8_t* p_ = hd + img_off(q); \
      *(uint32_t*)p_ = pack_bf16(a[4 * (c)] * r0 * a[off + 4 * (c)], a[4 * (c) + 1] * r0 * a[off + 1 + 4 * (c)]); \
      *(uint32_t*)(p_ + 1024) = pack_bf16(a[4 * (c) + 2] * r1 * a[off + 2 + 4 * (c)], a[4 * (c) + 3] * r1 * a[off + 3 + 4 * (c)]); } while (0)
#pragma unroll
    for (int c = 0; c < 14; c++) STORE_H(a1, 56, n1 * 14 + c, c);
    bar_arrive(5, 256 + 32);
#pragma unroll 1
    for (int j = 0; j < 40; j++) {
      mbar_wait(bfull + 8 * s, ph);
      WG_FENCE();
      wgmma_ss_n208(a2, da0 + (j >> 2) * 1024 + (j & 3) * 16, db0 + s * (K4_BST >> 4), j != 0);
      WG_COMMIT();
      if (j > 0) {
        WG_WAIT(1);
        if (j <= 40 - K4_NS && (tid & 127) < 2) mbar_arrive_cta(bempty + 8 * sprev, tid & 1);
        if (j >= 12 && (j & 7) == 4 && (tid & 127) == 0) mbar_arrive(afree + (j - 12));
      }
      sprev = s;
      if (++s == K4_NS) { s = 0; ph ^= 1; }
    }
    WG_WAIT(0);
    fence_regs(a2);
    if (tid == 0) STAMP(3, 4);
#pragma unroll
    for (int c = 0; c < 13; c++) STORE_H(a2, 52, 112 + n1 * 13 + c, c);
    bar_arrive(6, 256 + 32);
    float (&keep)[40] = ((Acc<40>*)acc)->v;
    const uint64_t db3 = mkdesc(sbase + 16384, 128, 1024, 0);
#pragma unroll 1
    for (int i = 0; i < 11; i++) {
      mbar_wait(full3 + 8 * (i & 3), (i >> 2) & 1);
      if (i == 0 && tid == 0) STAMP(4, 2);
      const uint64_t da = da0 + (i & 3) * 2304, db = db3 + (i & 3) * 2304;
      WG_FENCE();
#pragma unroll
      for (int k = 0; k < 4; k++) wgmma_ss_n160(acc, da + k * 16, db + k * 16, (i | k) != 0);
      WG_COMMIT();
      if (i > 0) {
        WG_WAIT(1);
        if ((tid & 127) < 2) mbar_arrive_cta(empty3 + 8 * ((i - 1) & 3), tid & 1);
      }
    }
    const int g = lane >> 2, c = lane & 3, row = m3 * 128 + warp * 16 + g;
    const uint8_t* himg = (const uint8_t*)g_h + (size_t)m3 * 163840 + warp * 2048 + lane * 4;
    uint32_t rv[20];
    const float mu0 = __ldcg(&g_hmean[row]), mu1 = __ldcg(&g_hmean[row + 8]);
#pragma unroll
    for (int j = 0; j < 10; j++) {
      rv[2 * j] = __ldcg((const uint32_t*)(himg + img_off(n3 * 10 + j)));
      rv[2 * j + 1] = __ldcg((const uint32_t*)(himg + img_off(n3 * 10 + j) + 1024));
    }
    const uint32_t rx = mapa(sbase + K4_XCH + tid * 16, rank ^ 1), rb = mapa(xchb, rank ^ 1);
    WG_WAIT(0);
    fence_regs(acc);
    if ((tid & 127) < 2) mbar_arrive_cta(empty3 + 16, tid & 1);
    if (tid == 0) STAMP(4, 1);
#pragma unroll
    for (int i = 11; i < 16; i++) {
      mbar_wait(full3 + 8 * (i & 3), (i >> 2) & 1);
      const uint64_t da = da0 + (i & 3) * 2304, db = db3 + (i & 3) * 2304;
      WG_FENCE();
#pragma unroll
      for (int k = 0; k < 4; k++) wgmma_ss_n80(keep, da + k * 16, db + k * 16, 1);
      WG_COMMIT();
      if (i == 12) {
        WG_WAIT(1);
        if ((tid & 127) < 2) mbar_arrive_cta(empty3 + 24, tid & 1);
      }
#pragma unroll
      for (int j = (i - 11) * 3; j < (i - 11) * 3 + 3; j++)
        if (j < 10) st_async4(rx + j * 4096, acc[40 + 4 * j], acc[41 + 4 * j], acc[42 + 4 * j], acc[43 + 4 * j], rb);
    }
    cluster_arrive();
    WG_WAIT(0);
    fence_regs(keep);
    if (tid == 0) STAMP(4, 3);
    mbar_wait(xchb, 0);
    if (tid == 0) STAMP(4, 5);
    uint8_t* sp = sm + K4_STG + (warp * 16 + g) * 160 + c * 4;
#pragma unroll
    for (int j = 0; j < 10; j++) {
      const float4 p = *(const float4*)(sm + K4_XCH + tid * 16 + j * 4096);
      *(uint32_t*)(sp + j * 16) = pack_bf16((keep[4 * j] + p.x) + (bf_lo(rv[2 * j]) + mu0), (keep[4 * j + 1] + p.y) + (bf_hi(rv[2 * j]) + mu0));
      *(uint32_t*)(sp + 1280 + j * 16) = pack_bf16((keep[4 * j + 2] + p.z) + (bf_lo(rv[2 * j + 1]) + mu1), (keep[4 * j + 3] + p.w) + (bf_hi(rv[2 * j + 1]) + mu1));
    }
    fence_async();
    bar_sync(1 + wg, 128);
    if ((tid & 127) == 0) {
      tma2d_st(&tmo, n3 * 80, m3 * 128 + wg * 64, sbase + K4_STG + wg * 10240);
      bulk_commit_wait();
    }
    __syncwarp();
    if (tid == 0) STAMP(4, 4);
    asm volatile("barrier.cluster.wait.aligned; // consumers" ::: "memory");
  }
}

typedef CUresult (*EncodeFn)(CUtensorMap*, CUtensorMapDataType, cuuint32_t, void*, const cuuint64_t*, const cuuint64_t*,
                             const cuuint32_t*, const cuuint32_t*, CUtensorMapInterleave, CUtensorMapSwizzle,
                             CUtensorMapL2promotion, CUtensorMapFloatOOBfill);

static CUtensorMap make_map(EncodeFn enc, const void* p, uint64_t inner, uint64_t outer, uint32_t box_inner,
                            uint32_t box_outer, CUtensorMapSwizzle swz) {
  CUtensorMap m;
  cuuint64_t gd[2] = {inner, outer};
  cuuint64_t gs[1] = {inner * 2};
  cuuint32_t bd[2] = {box_inner, box_outer};
  cuuint32_t es[2] = {1, 1};
  enc(&m, CU_TENSOR_MAP_DATA_TYPE_BFLOAT16, 2, (void*)p, gd, gs, bd, es, CU_TENSOR_MAP_INTERLEAVE_NONE, swz,
      CU_TENSOR_MAP_L2_PROMOTION_L2_256B, CU_TENSOR_MAP_FLOAT_OOB_FILL_NONE);
  return m;
}

static CUtensorMap make_map_img(EncodeFn enc, const void* p, uint64_t k, uint64_t n, uint32_t rows, uint32_t chunks,
                                uint32_t groups) {
  CUtensorMap m;
  cuuint64_t gd[4] = {8, rows, n / 8, k / rows};
  cuuint64_t gs[3] = {n * 2, 16, n * 2 * rows};
  cuuint32_t bd[4] = {8, rows, chunks, groups};
  cuuint32_t es[4] = {1, 1, 1, 1};
  enc(&m, CU_TENSOR_MAP_DATA_TYPE_BFLOAT16, 4, (void*)p, gd, gs, bd, es, CU_TENSOR_MAP_INTERLEAVE_NONE,
      CU_TENSOR_MAP_SWIZZLE_NONE, CU_TENSOR_MAP_L2_PROMOTION_L2_128B, CU_TENSOR_MAP_FLOAT_OOB_FILL_NONE);
  return m;
}

template <typename... KArgs, typename... Args>
static void launch(void (*k)(KArgs...), int grid, int threads, int smem, bool pdl, Args... args) {
  cudaLaunchConfig_t cfg = {};
  cfg.gridDim = dim3(grid);
  cfg.blockDim = dim3(threads);
  cfg.dynamicSmemBytes = smem;
  cfg.stream = cudaStreamPerThread;
  cudaLaunchAttribute at[1];
  at[0].id = cudaLaunchAttributeProgrammaticStreamSerialization;
  at[0].val.programmaticStreamSerializationAllowed = 1;
  cfg.attrs = at;
  cfg.numAttrs = pdl ? 1 : 0;
  cudaLaunchKernelEx(&cfg, k, KArgs(args)...);
}

extern "C" void kernel_launch(void* const* d_in, const int* in_sizes, int n_in, void* d_out, int out_size) {
  const bf16* x = (const bf16*)d_in[0];
  const bf16* wqkv = (const bf16*)d_in[1];
  const bf16* wo = (const bf16*)d_in[2];
  const bf16* wg = (const bf16*)d_in[4];
  const bf16* wu = (const bf16*)d_in[5];
  const bf16* wd = (const bf16*)d_in[6];

  static EncodeFn enc = nullptr;
  static void *p_o, *p_wo;
  if (!enc) {
    void* fn = nullptr;
    cudaDriverEntryPointQueryResult qr;
    cudaGetDriverEntryPoint("cuTensorMapEncodeTiled", &fn, cudaEnableDefault, &qr);
    enc = (EncodeFn)fn;
    cudaGetSymbolAddress(&p_o, g_o);
    cudaGetSymbolAddress(&p_wo, g_wo);
    cudaFuncSetAttribute(k1_qkv, cudaFuncAttributeMaxDynamicSharedMemorySize, K1_SMEM);
    cudaFuncSetAttribute(k2_attn, cudaFuncAttributeMaxDynamicSharedMemorySize, K2_SMEM);
    cudaFuncSetAttribute(k3_proj<3, 4, true>, cudaFuncAttributeMaxDynamicSharedMemorySize, K3_SMEM);
    cudaFuncSetAttribute(k45_ffn, cudaFuncAttributeMaxDynamicSharedMemorySize, K4_SMEM);
  }
  const CUtensorMap tmx = make_map(enc, x, D_, S_, 64, 96, CU_TENSOR_MAP_SWIZZLE_128B);
  const CUtensorMap tmw = make_map(enc, wqkv, 3 * D_, D_, 32, 64, CU_TENSOR_MAP_SWIZZLE_64B);
  const CUtensorMap tmxr = make_map(enc, x, D_, S_, 80, 64, CU_TENSOR_MAP_SWIZZLE_NONE);
  Maps5 maps;
  maps.m[0] = make_map_img(enc, wg, D_, F_, 16, 14, 2); maps.m[1] = make_map_img(enc, wu, D_, F_, 16, 14, 2);
  maps.m[2] = make_map_img(enc, wg, D_, F_, 16, 13, 2); maps.m[3] = make_map_img(enc, wu, D_, F_, 16, 13, 2);
  maps.m[4] = make_map_img(enc, wd, F_, D_, 64, 10, 1);
  const CUtensorMap tmout = make_map(enc, d_out, D_, S_, 80, 64, CU_TENSOR_MAP_SWIZZLE_NONE);

  launch(k1_qkv, 132, 512, K1_SMEM, false, tmx, tmw, x, wqkv, wo);
  launch(k2_attn, 128, 512, K2_SMEM, true, maps, 0x007f007fu);
  launch(k3_proj<3, 4, true>, 128, 384, K3_SMEM, true, tmxr, (const uint4*)p_o, (const uint4*)p_wo);
  launch(k45_ffn, 128, 384, K4_SMEM, true, tmout);
}
```

```cpp
#include <cuda_runtime.h>
#include <cuda_bf16.h>
#include <cuda.h>
#include <stdint.h>

typedef __nv_bfloat16 bf16;

constexpr int S_ = 2048, D_ = 640, F_ = 1728;
constexpr int HEAD_IMG = 98304;
#define PMASK 0xDB6D
constexpr uint32_t POLY_MASK = PMASK;
constexpr float QSCALE = 0.22360679774997896f * 1.4426950408889634f;

__device__ __align__(1024) uint4 g_qkv[96 * HEAD_IMG / 16];
__device__ __align__(1024) uint4 g_o[S_ * D_ / 8];
__device__ __align__(1024) uint4 g_h[S_ * D_ / 8];
__device__ __align__(1024) uint4 g_hh[S_ * F_ / 8];
__device__ __align__(1024) uint4 g_wo[D_ * D_ / 8];
__device__ __align__(1024) uint4 g_wgu[2 * D_ * F_ / 8];
__device__ __align__(1024) uint4 g_wd[F_ * D_ / 8];
__device__ uint4 g_rowstat[S_];
__device__ uint4 g_cpart[10 * 12 * 80];
__device__ float g_nrm[64 * 128];
__device__ uint4 g_wm[D_];
__device__ float g_hmean[S_];
__device__ float g_hpart[8 * S_];
__device__ uint4 g_flag[2 * 16 * 2];
__device__ unsigned g_epoch;

#define STAMP(k, i)
__device__ __forceinline__ uint32_t smem_u32(const void* p) { return (uint32_t)__cvta_generic_to_shared(p); }
__device__ __forceinline__ void mbar_init(uint32_t a, uint32_t c) {
  asm volatile("mbarrier.init.shared::cta.b64 [%0], %1;" ::"r"(a), "r"(c) : "memory");
}
__device__ __forceinline__ void mbar_expect(uint32_t a, uint32_t bytes) {
  asm volatile("mbarrier.arrive.expect_tx.shared::cta.b64 _, [%0], %1;" ::"r"(a), "r"(bytes) : "memory");
}
__device__ __forceinline__ void mbar_arrive(uint32_t a) {
  asm volatile("mbarrier.arrive.shared::cta.b64 _, [%0];" ::"r"(a) : "memory");
}
__device__ __forceinline__ void mbar_arrive_cta(uint32_t a, uint32_t cta) {
  asm volatile("{\n.reg .b32 r;\nmapa.shared::cluster.u32 r, %0, %1;\n"
               "mbarrier.arrive.shared::cluster.b64 _, [r];\n}" ::"r"(a), "r"(cta) : "memory");
}
__device__ __forceinline__ bool mbar_try(uint32_t a, uint32_t ph) {
  uint32_t ok;
  asm volatile("{\n.reg .pred p;\nmbarrier.try_wait.parity.shared::cta.b64 p, [%1], %2;\nselp.u32 %0, 1, 0, p;\n}"
               : "=r"(ok) : "r"(a), "r"(ph) : "memory");
  return ok;
}
__device__ __noinline__ void wait_timeout() { __trap(); }
__device__ __forceinline__ void mbar_wait(uint32_t a, uint32_t ph) {
  if (mbar_try(a, ph)) return;
  uint32_t it = 0;
  while (!mbar_try(a, ph)) if (++it > (1u << 22)) wait_timeout();
}
__device__ __forceinline__ void tma2d(uint32_t dst, const CUtensorMap* m, int c0, int c1, uint32_t bar) {
  asm volatile("cp.async.bulk.tensor.2d.shared::cluster.global.mbarrier::complete_tx::bytes [%0], [%1, {%3, %4}], [%2];"
               ::"r"(dst), "l"(m), "r"(bar), "r"(c0), "r"(c1) : "memory");
}
__device__ __forceinline__ void tma2d_mc(uint32_t dst, const CUtensorMap* m, int c0, int c1, uint32_t bar) {
  asm volatile("cp.async.bulk.tensor.2d.shared::cluster.global.mbarrier::complete_tx::bytes.multicast::cluster "
               "[%0], [%1, {%3, %4}], [%2], %5;"
               ::"r"(dst), "l"(m), "r"(bar), "r"(c0), "r"(c1), "h"((uint16_t)3) : "memory");
}
__device__ __forceinline__ void bulk_ld(uint32_t dst, const void* src, uint32_t bytes, uint32_t bar) {
  asm volatile("cp.async.bulk.shared::cluster.global.mbarrier::complete_tx::bytes [%0], [%1], %2, [%3];"
               ::"r"(dst), "l"(src), "r"(bytes), "r"(bar) : "memory");
}
__device__ __forceinline__ void bulk_ld_mc(uint32_t dst, const void* src, uint32_t bytes, uint32_t bar) {
  asm volatile("cp.async.bulk.shared::cluster.global.mbarrier::complete_tx::bytes.multicast::cluster "
               "[%0], [%1], %2, [%3], %4;"
               ::"r"(dst), "l"(src), "r"(bytes), "r"(bar), "h"((uint16_t)3) : "memory");
}
__device__ __forceinline__ void cluster_arrive() { asm volatile("barrier.cluster.arrive.relaxed.aligned;" ::: "memory"); }
__device__ __forceinline__ void cluster_wait() { asm volatile("barrier.cluster.wait.aligned;" ::: "memory"); }
__device__ __forceinline__ void bulk_st(void* dst, uint32_t src, uint32_t bytes) {
  asm volatile("cp.async.bulk.global.shared::cta.bulk_group [%0], [%1], %2;" ::"l"(dst), "r"(src), "r"(bytes) : "memory");
}
__device__ __forceinline__ void tma2d_st(const CUtensorMap* m, int c0, int c1, uint32_t src) {
  asm volatile("cp.async.bulk.tensor.2d.global.shared::cta.bulk_group [%0, {%2, %3}], [%1];"
               ::"l"(m), "r"(src), "r"(c0), "r"(c1) : "memory");
}
__device__ __forceinline__ void bulk_commit_wait() {
  asm volatile("cp.async.bulk.commit_group;\ncp.async.bulk.wait_group.read 0;" ::: "memory");
}
__device__ __forceinline__ uint32_t mapa(uint32_t a, uint32_t cta) {
  uint32_t r;
  asm("mapa.shared::cluster.u32 %0, %1, %2;" : "=r"(r) : "r"(a), "r"(cta));
  return r;
}
__device__ __forceinline__ void st_async4(uint32_t dst, float a, float b, float c, float d, uint32_t bar) {
  asm volatile("st.async.shared::cluster.mbarrier::complete_tx::bytes.v4.f32 [%0], {%1, %2, %3, %4}, [%5];"
               ::"r"(dst), "f"(a), "f"(b), "f"(c), "f"(d), "r"(bar) : "memory");
}
__device__ __forceinline__ void fence_async() { asm volatile("fence.proxy.async.shared::cta;" ::: "memory"); }
__device__ __forceinline__ void prefetch_map(const CUtensorMap* m) {
  asm volatile("prefetch.tensormap [%0];" ::"l"(m) : "memory");
}
__device__ __forceinline__ void pdl_wait() { asm volatile("griddepcontrol.wait;" ::: "memory"); }
__device__ __forceinline__ void pdl_trigger() { asm volatile("griddepcontrol.launch_dependents;" ::: "memory"); }
__device__ __forceinline__ void bar_sync(int id, int n) { asm volatile("bar.sync %0, %1;" ::"r"(id), "r"(n) : "memory"); }
__device__ __forceinline__ void bar_arrive(int id, int n) { asm volatile("bar.arrive %0, %1;" ::"r"(id), "r"(n) : "memory"); }
#define WG_FENCE() asm volatile("wgmma.fence.sync.aligned;" ::: "memory")
#define WG_COMMIT() asm volatile("wgmma.commit_group.sync.aligned;" ::: "memory")
#define WG_WAIT(n) asm volatile("wgmma.wait_group.sync.aligned %0;" ::"n"(n) : "memory")
__device__ __forceinline__ uint64_t mkdesc(uint32_t addr, uint32_t lbo, uint32_t sbo, uint32_t sw) {
  return (uint64_t)((addr & 0x3FFFF) >> 4) | ((uint64_t)(lbo >> 4) << 16) | ((uint64_t)(sbo >> 4) << 32) |
         ((uint64_t)sw << 62);
}
template <int N> __device__ __forceinline__ void fence_regs(float (&r)[N]) {
#pragma unroll
  for (int i = 0; i < N; i++) asm volatile("" : "+f"(r[i])::"memory");
}
__device__ __forceinline__ uint32_t pack_bf16(float lo, float hi) {
  uint32_t r;
  asm("cvt.rn.bf16x2.f32 %0, %1, %2;" : "=r"(r) : "f"(hi), "f"(lo));
  return r;
}
__device__ __forceinline__ float bf_lo(uint32_t v) { return __uint_as_float(v << 16); }
__device__ __forceinline__ float bf_hi(uint32_t v) { return __uint_as_float(v & 0xffff0000u); }
__device__ __forceinline__ float ex2(float x) {
  float y;
  asm("ex2.approx.ftz.f32 %0, %1;" : "=f"(y) : "f"(x));
  return y;
}
__device__ __forceinline__ uint4 ldg_nc(const void* p) {
  uint4 v;
  asm volatile("ld.global.nc.L1::no_allocate.v4.u32 {%0, %1, %2, %3}, [%4];"
               : "=r"(v.x), "=r"(v.y), "=r"(v.z), "=r"(v.w) : "l"(p));
  return v;
}

__device__ __forceinline__ uint4 ld_relaxed(const uint4* p) {
  uint64_t a, b;
  asm volatile("ld.relaxed.gpu.global.v2.u64 {%0, %1}, [%2];" : "=l"(a), "=l"(b) : "l"(p) : "memory");
  return make_uint4((uint32_t)a, (uint32_t)(a >> 32), (uint32_t)b, (uint32_t)(b >> 32));
}
__device__ __forceinline__ void st_relaxed(uint4* p, float x, float y, uint32_t tag) {
  const uint64_t a = ((uint64_t)tag << 32) | __float_as_uint(x), b = ((uint64_t)tag << 32) | __float_as_uint(y);
  asm volatile("st.relaxed.gpu.global.v2.u64 [%0], {%1, %2};" ::"l"(p), "l"(a), "l"(b) : "memory");
}
__device__ __forceinline__ void tma4d(uint32_t dst, const CUtensorMap* m, int c2, int c3, uint32_t bar) {
  asm volatile("cp.async.bulk.tensor.4d.shared::cluster.global.mbarrier::complete_tx::bytes [%0], [%1, {%3, %3, %4, %5}], [%2];"
               ::"r"(dst), "l"(m), "r"(bar), "r"(0), "r"(c2), "r"(c3) : "memory");
}
#define ACC8(a, v) do { a[0] += bf_lo(v.x); a[1] += bf_hi(v.x); a[2] += bf_lo(v.y); a[3] += bf_hi(v.y); \
                        a[4] += bf_lo(v.z); a[5] += bf_hi(v.z); a[6] += bf_lo(v.w); a[7] += bf_hi(v.w); } while (0)

__device__ __forceinline__ void wgmma_ss_n224(float (&d)[112], uint64_t da, uint64_t db, int sd) {
  asm volatile("{\n.reg .pred p;\nsetp.ne.b32 p, %114, 0;\n"
      "wgmma.mma_async.sync.aligned.m64n224k16.f32.bf16.bf16 {"
      "%0, %1, %2, %3, %4, %5, %6, %7, %8, %9, %10, %11, %12, %13, %14, %15, "
      "%16, %17, %18, %19, %20, %21, %22, %23, %24, %25, %26, %27, %28, %29, %30, %31, "
      "%32, %33, %34, %35, %36, %37, %38, %39, %40, %41, %42, %43, %44, %45, %46, %47, "
      "%48, %49, %50, %51, %52, %53, %54, %55, %56, %57, %58, %59, %60, %61, %62, %63, "
      "%64, %65, %66, %67, %68, %69, %70, %71, %72, %73, %74, %75, %76, %77, %78, %79, "
      "%80, %81, %82, %83, %84, %85, %86, %87, %88, %89, %90, %91, %92, %93, %94, %95, "
      "%96, %97, %98, %99, %100, %101, %102, %103, %104, %105, %106, %107, %108, %109, %110, %111"
      "}, %112, %113, p, 1, 1, 0, 1;\n}\n"
    : "+f"(d[0]), "+f"(d[1]), "+f"(d[2]), "+f"(d[3]), "+f"(d[4]), "+f"(d[5]), "+f"(d[6]), "+f"(d[7]),
      "+f"(d[8]), "+f"(d[9]), "+f"(d[10]), "+f"(d[11]), "+f"(d[12]), "+f"(d[13]), "+f"(d[14]), "+f"(d[15]),
      "+f"(d[16]), "+f"(d[17]), "+f"(d[18]), "+f"(d[19]), "+f"(d[20]), "+f"(d[21]), "+f"(d[22]), "+f"(d[23]),
      "+f"(d[24]), "+f"(d[25]), "+f"(d[26]), "+f"(d[27]), "+f"(d[28]), "+f"(d[29]), "+f"(d[30]), "+f"(d[31]),
      "+f"(d[32]), "+f"(d[33]), "+f"(d[34]), "+f"(d[35]), "+f"(d[36]), "+f"(d[37]), "+f"(d[38]), "+f"(d[39]),
      "+f"(d[40]), "+f"(d[41]), "+f"(d[42]), "+f"(d[43]), "+f"(d[44]), "+f"(d[45]), "+f"(d[46]), "+f"(d[47]),
      "+f"(d[48]), "+f"(d[49]), "+f"(d[50]), "+f"(d[51]), "+f"(d[52]), "+f"(d[53]), "+f"(d[54]), "+f"(d[55]),
      "+f"(d[56]), "+f"(d[57]), "+f"(d[58]), "+f"(d[59]), "+f"(d[60]), "+f"(d[61]), "+f"(d[62]), "+f"(d[63]),
      "+f"(d[64]), "+f"(d[65]), "+f"(d[66]), "+f"(d[67]), "+f"(d[68]), "+f"(d[69]), "+f"(d[70]), "+f"(d[71]),
      "+f"(d[72]), "+f"(d[73]), "+f"(d[74]), "+f"(d[75]), "+f"(d[76]), "+f"(d[77]), "+f"(d[78]), "+f"(d[79]),
      "+f"(d[80]), "+f"(d[81]), "+f"(d[82]), "+f"(d[83]), "+f"(d[84]), "+f"(d[85]), "+f"(d[86]), "+f"(d[87]),
      "+f"(d[88]), "+f"(d[89]), "+f"(d[90]), "+f"(d[91]), "+f"(d[92]), "+f"(d[93]), "+f"(d[94]), "+f"(d[95]),
      "+f"(d[96]), "+f"(d[97]), "+f"(d[98]), "+f"(d[99]), "+f"(d[100]), "+f"(d[101]), "+f"(d[102]), "+f"(d[103]),
      "+f"(d[104]), "+f"(d[105]), "+f"(d[106]), "+f"(d[107]), "+f"(d[108]), "+f"(d[109]), "+f"(d[110]), "+f"(d[111])
    : "l"(da), "l"(db), "r"(sd));
}
__device__ __forceinline__ void wgmma_ss_n208(float (&d)[104], uint64_t da, uint64_t db, int sd) {
  asm volatile("{\n.reg .pred p;\nsetp.ne.b32 p, %106, 0;\n"
      "wgmma.mma_async.sync.aligned.m64n208k16.f32.bf16.bf16 {"
      "%0, %1, %2, %3, %4, %5, %6, %7, %8, %9, %10, %11, %12, %13, %14, %15, "
      "%16, %17, %18, %19, %20, %21, %22, %23, %24, %25, %26, %27, %28, %29, %30, %31, "
      "%32, %33, %34, %35, %36, %37, %38, %39, %40, %41, %42, %43, %44, %45, %46, %47, "
      "%48, %49, %50, %51, %52, %53, %54, %55, %56, %57, %58, %59, %60, %61, %62, %63, "
      "%64, %65, %66, %67, %68, %69, %70, %71, %72, %73, %74, %75, %76, %77, %78, %79, "
      "%80, %81, %82, %83, %84, %85, %86, %87, %88, %89, %90, %91, %92, %93, %94, %95, "
      "%96, %97, %98, %99, %100, %101, %102, %103"
      "}, %104, %105, p, 1, 1, 0, 1;\n}\n"
    : "+f"(d[0]), "+f"(d[1]), "+f"(d[2]), "+f"(d[3]), "+f"(d[4]), "+f"(d[5]), "+f"(d[6]), "+f"(d[7]),
      "+f"(d[8]), "+f"(d[9]), "+f"(d[10]), "+f"(d[11]), "+f"(d[12]), "+f"(d[13]), "+f"(d[14]), "+f"(d[15]),
      "+f"(d[16]), "+f"(d[17]), "+f"(d[18]), "+f"(d[19]), "+f"(d[20]), "+f"(d[21]), "+f"(d[22]), "+f"(d[23]),
      "+f"(d[24]), "+f"(d[25]), "+f"(d[26]), "+f"(d[27]), "+f"(d[28]), "+f"(d[29]), "+f"(d[30]), "+f"(d[31]),
      "+f"(d[32]), "+f"(d[33]), "+f"(d[34]), "+f"(d[35]), "+f"(d[36]), "+f"(d[37]), "+f"(d[38]), "+f"(d[39]),
      "+f"(d[40]), "+f"(d[41]), "+f"(d[42]), "+f"(d[43]), "+f"(d[44]), "+f"(d[45]), "+f"(d[46]), "+f"(d[47]),
      "+f"(d[48]), "+f"(d[49]), "+f"(d[50]), "+f"(d[51]), "+f"(d[52]), "+f"(d[53]), "+f"(d[54]), "+f"(d[55]),
      "+f"(d[56]), "+f"(d[57]), "+f"(d[58]), "+f"(d[59]), "+f"(d[60]), "+f"(d[61]), "+f"(d[62]), "+f"(d[63]),
      "+f"(d[64]), "+f"(d[65]), "+f"(d[66]), "+f"(d[67]), "+f"(d[68]), "+f"(d[69]), "+f"(d[70]), "+f"(d[71]),
      "+f"(d[72]), "+f"(d[73]), "+f"(d[74]), "+f"(d[75]), "+f"(d[76]), "+f"(d[77]), "+f"(d[78]), "+f"(d[79]),
      "+f"(d[80]), "+f"(d[81]), "+f"(d[82]), "+f"(d[83]), "+f"(d[84]), "+f"(d[85]), "+f"(d[86]), "+f"(d[87]),
      "+f"(d[88]), "+f"(d[89]), "+f"(d[90]), "+f"(d[91]), "+f"(d[92]), "+f"(d[93]), "+f"(d[94]), "+f"(d[95]),
      "+f"(d[96]), "+f"(d[97]), "+f"(d[98]), "+f"(d[99]), "+f"(d[100]), "+f"(d[101]), "+f"(d[102]), "+f"(d[103])
    : "l"(da), "l"(db), "r"(sd));
}
__device__ __forceinline__ void wgmma_ss_n168(float (&d)[84], uint64_t da, uint64_t db, int sd) {
  asm volatile("{\n.reg .pred p;\nsetp.ne.b32 p, %86, 0;\n"
      "wgmma.mma_async.sync.aligned.m64n168k16.f32.bf16.bf16 {"
      "%0, %1, %2, %3, %4, %5, %6, %7, %8, %9, %10, %11, %12, %13, %14, %15, "
      "%16, %17, %18, %19, %20, %21, %22, %23, %24, %25, %26, %27, %28, %29, %30, %31, "
      "%32, %33, %34, %35, %36, %37, %38, %39, %40, %41, %42, %43, %44, %45, %46, %47, "
      "%48, %49, %50, %51, %52, %53, %54, %55, %56, %57, %58, %59, %60, %61, %62, %63, "
      "%64, %65, %66, %67, %68, %69, %70, %71, %72, %73, %74, %75, %76, %77, %78, %79, "
      "%80, %81, %82, %83"
      "}, %84, %85, p, 1, 1, 0, 1;\n}\n"
    : "+f"(d[0]), "+f"(d[1]), "+f"(d[2]), "+f"(d[3]), "+f"(d[4]), "+f"(d[5]), "+f"(d[6]), "+f"(d[7]),
      "+f"(d[8]), "+f"(d[9]), "+f"(d[10]), "+f"(d[11]), "+f"(d[12]), "+f"(d[13]), "+f"(d[14]), "+f"(d[15]),
      "+f"(d[16]), "+f"(d[17]), "+f"(d[18]), "+f"(d[19]), "+f"(d[20]), "+f"(d[21]), "+f"(d[22]), "+f"(d[23]),
      "+f"(d[24]), "+f"(d[25]), "+f"(d[26]), "+f"(d[27]), "+f"(d[28]), "+f"(d[29]), "+f"(d[30]), "+f"(d[31]),
      "+f"(d[32]), "+f"(d[33]), "+f"(d[34]), "+f"(d[35]), "+f"(d[36]), "+f"(d[37]), "+f"(d[38]), "+f"(d[39]),
      "+f"(d[40]), "+f"(d[41]), "+f"(d[42]), "+f"(d[43]), "+f"(d[44]), "+f"(d[45]), "+f"(d[46]), "+f"(d[47]),
      "+f"(d[48]), "+f"(d[49]), "+f"(d[50]), "+f"(d[51]), "+f"(d[52]), "+f"(d[53]), "+f"(d[54]), "+f"(d[55]),
      "+f"(d[56]), "+f"(d[57]), "+f"(d[58]), "+f"(d[59]), "+f"(d[60]), "+f"(d[61]), "+f"(d[62]), "+f"(d[63]),
      "+f"(d[64]), "+f"(d[65]), "+f"(d[66]), "+f"(d[67]), "+f"(d[68]), "+f"(d[69]), "+f"(d[70]), "+f"(d[71]),
      "+f"(d[72]), "+f"(d[73]), "+f"(d[74]), "+f"(d[75]), "+f"(d[76]), "+f"(d[77]), "+f"(d[78]), "+f"(d[79]),
      "+f"(d[80]), "+f"(d[81]), "+f"(d[82]), "+f"(d[83])
    : "l"(da), "l"(db), "r"(sd));
}
__device__ __forceinline__ void wgmma_ss_n160(float (&d)[80], uint64_t da, uint64_t db, int sd) {
  asm volatile("{\n.reg .pred p;\nsetp.ne.b32 p, %82, 0;\n"
      "wgmma.mma_async.sync.aligned.m64n160k16.f32.bf16.bf16 {"
      "%0, %1, %2, %3, %4, %5, %6, %7, %8, %9, %10, %11, %12, %13, %14, %15, "
      "%16, %17, %18, %19, %20, %21, %22, %23, %24, %25, %26, %27, %28, %29, %30, %31, "
      "%32, %33, %34, %35, %36, %37, %38, %39, %40, %41, %42, %43, %44, %45, %46, %47, "
      "%48, %49, %50, %51, %52, %53, %54, %55, %56, %57, %58, %59, %60, %61, %62, %63, "
      "%64, %65, %66, %67, %68, %69, %70, %71, %72, %73, %74, %75, %76, %77, %78, %79"
      "}, %80, %81, p, 1, 1, 0, 1;\n}\n"
    : "+f"(d[0]), "+f"(d[1]), "+f"(d[2]), "+f"(d[3]), "+f"(d[4]), "+f"(d[5]), "+f"(d[6]), "+f"(d[7]),
      "+f"(d[8]), "+f"(d[9]), "+f"(d[10]), "+f"(d[11]), "+f"(d[12]), "+f"(d[13]), "+f"(d[14]), "+f"(d[15]),
      "+f"(d[16]), "+f"(d[17]), "+f"(d[18]), "+f"(d[19]), "+f"(d[20]), "+f"(d[21]), "+f"(d[22]), "+f"(d[23]),
      "+f"(d[24]), "+f"(d[25]), "+f"(d[26]), "+f"(d[27]), "+f"(d[28]), "+f"(d[29]), "+f"(d[30]), "+f"(d[31]),
      "+f"(d[32]), "+f"(d[33]), "+f"(d[34]), "+f"(d[35]), "+f"(d[36]), "+f"(d[37]), "+f"(d[38]), "+f"(d[39]),
      "+f"(d[40]), "+f"(d[41]), "+f"(d[42]), "+f"(d[43]), "+f"(d[44]), "+f"(d[45]), "+f"(d[46]), "+f"(d[47]),
      "+f"(d[48]), "+f"(d[49]), "+f"(d[50]), "+f"(d[51]), "+f"(d[52]), "+f"(d[53]), "+f"(d[54]), "+f"(d[55]),
      "+f"(d[56]), "+f"(d[57]), "+f"(d[58]), "+f"(d[59]), "+f"(d[60]), "+f"(d[61]), "+f"(d[62]), "+f"(d[63]),
      "+f"(d[64]), "+f"(d[65]), "+f"(d[66]), "+f"(d[67]), "+f"(d[68]), "+f"(d[69]), "+f"(d[70]), "+f"(d[71]),
      "+f"(d[72]), "+f"(d[73]), "+f"(d[74]), "+f"(d[75]), "+f"(d[76]), "+f"(d[77]), "+f"(d[78]), "+f"(d[79])
    : "l"(da), "l"(db), "r"(sd));
}
__device__ __forceinline__ void wgmma_ss_n88(float (&d)[44], uint64_t da, uint64_t db, int sd) {
  asm volatile("{\n.reg .pred p;\nsetp.ne.b32 p, %46, 0;\n"
      "wgmma.mma_async.sync.aligned.m64n88k16.f32.bf16.bf16 {"
      "%0, %1, %2, %3, %4, %5, %6, %7, %8, %9, %10, %11, %12, %13, %14, %15, "
      "%16, %17, %18, %19, %20, %21, %22, %23, %24, %25, %26, %27, %28, %29, %30, %31, "
      "%32, %33, %34, %35, %36, %37, %38, %39, %40, %41, %42, %43"
      "}, %44, %45, p, 1, 1, 0, 1;\n}\n"
    : "+f"(d[0]), "+f"(d[1]), "+f"(d[2]), "+f"(d[3]), "+f"(d[4]), "+f"(d[5]), "+f"(d[6]), "+f"(d[7]),
      "+f"(d[8]), "+f"(d[9]), "+f"(d[10]), "+f"(d[11]), "+f"(d[12]), "+f"(d[13]), "+f"(d[14]), "+f"(d[15]),
      "+f"(d[16]), "+f"(d[17]), "+f"(d[18]), "+f"(d[19]), "+f"(d[20]), "+f"(d[21]), "+f"(d[22]), "+f"(d[23]),
      "+f"(d[24]), "+f"(d[25]), "+f"(d[26]), "+f"(d[27]), "+f"(d[28]), "+f"(d[29]), "+f"(d[30]), "+f"(d[31]),
      "+f"(d[32]), "+f"(d[33]), "+f"(d[34]), "+f"(d[35]), "+f"(d[36]), "+f"(d[37]), "+f"(d[38]), "+f"(d[39]),
      "+f"(d[40]), "+f"(d[41]), "+f"(d[42]), "+f"(d[43])
    : "l"(da), "l"(db), "r"(sd));
}
__device__ __forceinline__ void wgmma_ss_n80(float (&d)[40], uint64_t da, uint64_t db, int sd) {
  asm volatile("{\n.reg .pred p;\nsetp.ne.b32 p, %42, 0;\n"
      "wgmma.mma_async.sync.aligned.m64n80k16.f32.bf16.bf16 {"
      "%0, %1, %2, %3, %4, %5, %6, %7, %8, %9, %10, %11, %12, %13, %14, %15, "
      "%16, %17, %18, %19, %20, %21, %22, %23, %24, %25, %26, %27, %28, %29, %30, %31, "
      "%32, %33, %34, %35, %36, %37, %38, %39"
      "}, %40, %41, p, 1, 1, 0, 1;\n}\n"
    : "+f"(d[0]), "+f"(d[1]), "+f"(d[2]), "+f"(d[3]), "+f"(d[4]), "+f"(d[5]), "+f"(d[6]), "+f"(d[7]),
      "+f"(d[8]), "+f"(d[9]), "+f"(d[10]), "+f"(d[11]), "+f"(d[12]), "+f"(d[13]), "+f"(d[14]), "+f"(d[15]),
      "+f"(d[16]), "+f"(d[17]), "+f"(d[18]), "+f"(d[19]), "+f"(d[20]), "+f"(d[21]), "+f"(d[22]), "+f"(d[23]),
      "+f"(d[24]), "+f"(d[25]), "+f"(d[26]), "+f"(d[27]), "+f"(d[28]), "+f"(d[29]), "+f"(d[30]), "+f"(d[31]),
      "+f"(d[32]), "+f"(d[33]), "+f"(d[34]), "+f"(d[35]), "+f"(d[36]), "+f"(d[37]), "+f"(d[38]), "+f"(d[39])
    : "l"(da), "l"(db), "r"(sd));
}
__device__ __forceinline__ void wgmma_rs_n128(float (&d)[64], uint32_t a0, uint32_t a1, uint32_t a2, uint32_t a3,
                                  uint64_t db, int sd) {
  asm volatile("{\n.reg .pred p;\nsetp.ne.b32 p, %69, 0;\n"
      "wgmma.mma_async.sync.aligned.m64n128k16.f32.bf16.bf16 {"
      "%0, %1, %2, %3, %4, %5, %6, %7, %8, %9, %10, %11, %12, %13, %14, %15, "
      "%16, %17, %18, %19, %20, %21, %22, %23, %24, %25, %26, %27, %28, %29, %30, %31, "
      "%32, %33, %34, %35, %36, %37, %38, %39, %40, %41, %42, %43, %44, %45, %46, %47, "
      "%48, %49, %50, %51, %52, %53, %54, %55, %56, %57, %58, %59, %60, %61, %62, %63"
      "}, {%64, %65, %66, %67}, %68, p, 1, 1, 0;\n}\n"
    : "+f"(d[0]), "+f"(d[1]), "+f"(d[2]), "+f"(d[3]), "+f"(d[4]), "+f"(d[5]), "+f"(d[6]), "+f"(d[7]),
      "+f"(d[8]), "+f"(d[9]), "+f"(d[10]), "+f"(d[11]), "+f"(d[12]), "+f"(d[13]), "+f"(d[14]), "+f"(d[15]),
      "+f"(d[16]), "+f"(d[17]), "+f"(d[18]), "+f"(d[19]), "+f"(d[20]), "+f"(d[21]), "+f"(d[22]), "+f"(d[23]),
      "+f"(d[24]), "+f"(d[25]), "+f"(d[26]), "+f"(d[27]), "+f"(d[28]), "+f"(d[29]), "+f"(d[30]), "+f"(d[31]),
      "+f"(d[32]), "+f"(d[33]), "+f"(d[34]), "+f"(d[35]), "+f"(d[36]), "+f"(d[37]), "+f"(d[38]), "+f"(d[39]),
      "+f"(d[40]), "+f"(d[41]), "+f"(d[42]), "+f"(d[43]), "+f"(d[44]), "+f"(d[45]), "+f"(d[46]), "+f"(d[47]),
      "+f"(d[48]), "+f"(d[49]), "+f"(d[50]), "+f"(d[51]), "+f"(d[52]), "+f"(d[53]), "+f"(d[54]), "+f"(d[55]),
      "+f"(d[56]), "+f"(d[57]), "+f"(d[58]), "+f"(d[59]), "+f"(d[60]), "+f"(d[61]), "+f"(d[62]), "+f"(d[63])
    : "r"(a0), "r"(a1), "r"(a2), "r"(a3), "l"(db), "r"(sd));
}
__device__ __forceinline__ void wgmma_rs_n24(float (&d)[12], uint32_t a0, uint32_t a1, uint32_t a2, uint32_t a3,
                                  uint64_t db, int sd) {
  asm volatile("{\n.reg .pred p;\nsetp.ne.b32 p, %17, 0;\n"
      "wgmma.mma_async.sync.aligned.m64n24k16.f32.bf16.bf16 {"
      "%0, %1, %2, %3, %4, %5, %6, %7, %8, %9, %10, %11"
      "}, {%12, %13, %14, %15}, %16, p, 1, 1, 1;\n}\n"
    : "+f"(d[0]), "+f"(d[1]), "+f"(d[2]), "+f"(d[3]), "+f"(d[4]), "+f"(d[5]), "+f"(d[6]), "+f"(d[7]),
      "+f"(d[8]), "+f"(d[9]), "+f"(d[10]), "+f"(d[11])
    : "r"(a0), "r"(a1), "r"(a2), "r"(a3), "l"(db), "r"(sd));
}

#define KST 4
#define K1_EC 6
#define K1S 4
constexpr int K1_ST = K1S, K1_STAGE = 45056;
constexpr int K1_SMEM = K1_ST * K1_STAGE + 640   + 1536   + 2560   + 128;

__device__ __forceinline__ float2 row_stats(uint4 v0, uint4 v1, uint4 v2) {
  const uint32_t wd[12] = {v0.x, v0.y, v0.z, v0.w, v1.x, v1.y, v1.z, v1.w, v2.x, v2.y, v2.z, v2.w};
  float sx = 0.f, sq = 0.f;
#pragma unroll
  for (int e = 0; e < 12; e++) {
    const float lo = bf_lo(wd[e]), hi = bf_hi(wd[e]);
    sx += lo + hi; sq = fmaf(lo, lo, fmaf(hi, hi, sq));
  }
#pragma unroll
  for (int o = 16; o; o >>= 1) { sx += __shfl_xor_sync(~0u, sx, o); sq += __shfl_xor_sync(~0u, sq, o); }
  const float mean = sx * (1.f / D_);
  return make_float2(rsqrtf(fmaxf(sq * (1.f / D_) - mean * mean, 0.f) + 1e-5f), mean);
}

__global__ void __cluster_dims__(2, 1, 1) __launch_bounds__(512, 1)
k1_qkv(const __grid_constant__ CUtensorMap tmx, const __grid_constant__ CUtensorMap tmw,
       const bf16* __restrict__ x, const bf16* __restrict__ w, const bf16* __restrict__ wo) {
  extern __shared__ __align__(1024) uint8_t sm[];
  float* cs = (float*)(sm + K1_ST * K1_STAGE);
  float2* rowab = (float2*)(sm + K1_ST * K1_STAGE + 640);
  float* red = (float*)(sm + K1_ST * K1_STAGE + 2176);
  const uint32_t sbase = smem_u32(sm);
  const uint32_t fullb = sbase + K1_ST * K1_STAGE + 4736, emptyb = fullb + 8 * K1_ST;
  const int tid = threadIdx.x, lane = tid & 31;
  const int warp = __shfl_sync(~0u, tid >> 5, 0);
  const int rank = blockIdx.x & 1, cl = blockIdx.x >> 1;
  const int m = cl / 6, n = (cl - m * 6) * 2 + rank;
  if (tid == 0) STAMP(0, 0);

  if (warp == 12) {
    if (lane == 0) {
      prefetch_map(&tmx); prefetch_map(&tmw);
      for (int i = 0; i < K1_ST; i++) { mbar_init(fullb + 8 * i, 1); mbar_init(emptyb + 8 * i, K1_EC); }
      asm volatile("fence.mbarrier_init.release.cluster;" ::: "memory");
    }
    __syncwarp();
    cluster_arrive();
    bar_arrive(4, 512);
    if (lane == 0) {
      for (int kt = 0; kt < K1_ST; kt++) mbar_expect(fullb + 8 * kt, K1_STAGE);
#pragma unroll
      for (int j = 0; j < 5; j++) tma2d(sbase + 24576 + j * 4096, &tmw, n * 160 + j * 32, 0, fullb);
    }
    __syncwarp();
    cluster_wait();
    if (lane == 0) {
#pragma unroll 1
      for (int kt = 0; kt < 10; kt++) {
        const int s = kt % K1_ST;
        const uint32_t sa = sbase + s * K1_STAGE;
        if (kt >= K1_ST) {
          mbar_wait(emptyb + 8 * s, ((kt / K1_ST) - 1) & 1);
          mbar_expect(fullb + 8 * s, K1_STAGE);
        }
        tma2d_mc(sa + rank * 12288, &tmx, kt * 64, m * 192 + rank * 96, fullb + 8 * s);
        if (kt > 0) {
#pragma unroll
          for (int j = 0; j < 5; j++) tma2d(sa + 24576 + j * 4096, &tmw, n * 160 + j * 32, kt * 64, fullb + 8 * s);
        }
        if (kt == K1_ST - 1) {
          if (m * 192 + n * 16 < S_)
            asm volatile("cp.async.bulk.prefetch.L2.global [%0], %1;" ::"l"(x + (size_t)(m * 192 + n * 16) * D_), "r"(16 * D_ * 2) : "memory");
          if (m >= K1_ST && m < 10) {
#pragma unroll
            for (int j = 0; j < 5; j++)
              asm volatile("cp.async.bulk.prefetch.tensor.2d.L2.global [%0, {%1, %2}];" ::"l"(&tmw), "r"(n * 160 + j * 32), "r"(m * 64) : "memory");
          }
          pdl_trigger();
        }
      }
    }
    __syncwarp();
    cluster_arrive();
  } else if (warp > 12) {
    cluster_arrive();
    const int t96 = tid - 416;
    const uint32_t tag = __ldcg(&g_epoch) + 1;
    bar_sync(4, 512);
    mbar_wait(fullb, 0);
    if (m < 10) {
      const int ck = t96 % 20, rg = min(t96 / 20, 3);
      uint4 wv[16];
#pragma unroll
      for (int i = 0; i < 16; i++) wv[i] = ldg_nc(w + (size_t)(m * 64 + rg * 16 + i) * 1920 + n * 160 + ck * 8);
      float acc8[8];
#pragma unroll
      for (int i = 0; i < 8; i++) acc8[i] = 0.f;
#pragma unroll
      for (int i = 0; i < 16; i++) ACC8(acc8, wv[i]);
      *(float4*)&red[rg * 160 + ck * 8] = make_float4(acc8[0], acc8[1], acc8[2], acc8[3]);
      *(float4*)&red[rg * 160 + ck * 8 + 4] = make_float4(acc8[4], acc8[5], acc8[6], acc8[7]);
      bar_sync(1, 96);
      if (t96 < 80) {
        const float2 p0 = *(const float2*)&red[t96 * 2], p1 = *(const float2*)&red[160 + t96 * 2];
        const float2 p2 = *(const float2*)&red[320 + t96 * 2], p3 = *(const float2*)&red[480 + t96 * 2];
        st_relaxed(&g_cpart[(m * 12 + n) * 80 + t96], (p0.x + p1.x) + (p2.x + p3.x), (p0.y + p1.y) + (p2.y + p3.y), tag);
      }
    }
    if (tid == 416) STAMP(5, 7);
    bool ok = false;
    for (int it = 0; it < 64 && !ok; it++) {
      uint4 p[10], st[2];
#pragma unroll
      for (int k = 0; k < 10; k++) p[k] = ld_relaxed(&g_cpart[(k * 12 + n) * 80 + min(t96, 79)]);
#pragma unroll
      for (int k = 0; k < 2; k++) st[k] = ld_relaxed(&g_rowstat[min(m * 192 + k * 96 + t96, S_ - 1)]);
      ok = true;
      float s0 = 0.f, s1 = 0.f;
#pragma unroll
      for (int k = 0; k < 10; k++) {
        ok = ok && p[k].y == tag && p[k].w == tag;
        s0 += __uint_as_float(p[k].x); s1 += __uint_as_float(p[k].z);
      }
      if (t96 < 80) *(float2*)&cs[t96 * 2] = make_float2(s0, s1);
#pragma unroll
      for (int k = 0; k < 2; k++) {
        ok = ok && st[k].y == tag && st[k].w == tag;
        rowab[k * 96 + t96] = make_float2(__uint_as_float(st[k].x), -__uint_as_float(st[k].x) * __uint_as_float(st[k].z));
      }
      ok = __all_sync(~0u, ok);
      if (!ok) __nanosleep(300);
    }
    if (!ok) {
      const int c2 = min(t96, 79);
      float s0 = 0.f, s1 = 0.f;
#pragma unroll 1
      for (int k = 0; k < D_; k++) {
        const uint32_t v = *(const uint32_t*)(w + (size_t)k * 1920 + n * 160 + c2 * 2);
        s0 += bf_lo(v); s1 += bf_hi(v);
      }
      if (t96 < 80) *(float2*)&cs[t96 * 2] = make_float2(s0, s1);
#pragma unroll 1
      for (int i = 0; i < 64; i++) {
        const int r = (i >> 5) * 96 + (t96 & ~31) + (i & 31);
        const bf16* xr = x + (size_t)min(m * 192 + r, S_ - 1) * D_ + lane * 8;
        const float2 st = row_stats(ldg_nc(xr), ldg_nc(xr + 256), lane < 16 ? ldg_nc(xr + 512) : make_uint4(0u, 0u, 0u, 0u));
        if (lane == 0) rowab[r] = make_float2(st.x, -st.x * st.y);
      }
    }
    __syncwarp();
    bar_arrive(2, 96 + 384);
    bar_sync(1, 96);
    if (tid == 416) STAMP(0, 5);
    if (blockIdx.x < 128) {
      uint4 v[5];
      const int ck = min(t96, 79), nt = ck / 10;
#pragma unroll
      for (int i = 0; i < 5; i++) {
        const int k = blockIdx.x * 5 + i, pr = k / 40, r = k - pr * 40;
        v[i] = ldg_nc(wo + (size_t)(pr * 40 + (r < 16 ? r : (r < 32 ? r + 4 : (r < 36 ? r - 16 : r)))) * D_ + ck * 8);
      }
#pragma unroll
      for (int i = 0; i < 5; i++) {
        const int k = blockIdx.x * 5 + i;
        g_wo[((nt * 10 + (k >> 6)) * 10 + ck - nt * 10) * 64 + (k & 63)] = v[i];
        float t = ((bf_lo(v[i].x) + bf_hi(v[i].x)) + (bf_lo(v[i].y) + bf_hi(v[i].y))) +
                  ((bf_lo(v[i].z) + bf_hi(v[i].z)) + (bf_lo(v[i].w) + bf_hi(v[i].w)));
        if (t96 >= 80) t = 0.f;
#pragma unroll
        for (int o = 16; o; o >>= 1) t += __shfl_xor_sync(~0u, t, o);
        if (lane == 0) red[(t96 >> 5) * 8 + i] = t;
      }
      bar_sync(1, 96);
      if (t96 < 5) {
        const float mu = (red[t96] + red[8 + t96] + red[16 + t96]) * (1.f / D_);
        const float hi = bf_lo(pack_bf16(mu, 0.f));
        g_wm[blockIdx.x * 5 + t96] = make_uint4(pack_bf16(hi, mu - hi), 0u, 0u, 0u);
      }
    }
    if (tid == 416) STAMP(0, 7);
    __syncwarp();
    cluster_wait();
    cluster_arrive();
  } else {
    cluster_arrive();
    float acc[80];
    const uint64_t da0 = mkdesc(sbase + (warp >> 2) * 8192, 16, 1024, 1);
    const uint64_t db0 = mkdesc(sbase + 24576, 4096, 512, 2);
    const uint32_t tag = __ldcg(&g_epoch) + 1;
    const int srow = m * 192 + n * 16 + warp * 2;
    const bool dostat = warp < 8 && srow < S_;
    uint4 xv[2][3];
    bar_sync(4, 512);
    cluster_wait();
#pragma unroll
    for (int kt = 0; kt < 10; kt++) {
      const int s = kt % K1_ST;
      mbar_wait(fullb + 8 * s, (kt / K1_ST) & 1);
      if (kt == 0 && tid == 0) STAMP(0, 1);
      if (kt == 2 && tid == 0) STAMP(5, 0);
      if (kt == 4 && tid == 0) STAMP(5, 1);
      if (kt == 7 && tid == 0) STAMP(5, 2);
      const uint64_t da = da0 + s * (K1_STAGE >> 4), db = db0 + s * (K1_STAGE >> 4);
      WG_FENCE();
#pragma unroll
      for (int k = 0; k < 4; k++) wgmma_ss_n160(acc, da + k * 2, db + k * 64, (kt | k) != 0);
      WG_COMMIT();
      if (kt > 0) {
        WG_WAIT(1);
        if (kt - 1 + K1_ST < 10 && (tid & 127) < 2) mbar_arrive_cta(emptyb + 8 * ((kt - 1) % K1_ST), tid & 1);
      }
      if (kt == 0) {
#pragma unroll
        for (int i = 0; i < 2; i++) {
          const bf16* xr = x + (size_t)min(srow + i, S_ - 1) * D_ + lane * 8;
          xv[i][0] = xv[i][1] = xv[i][2] = make_uint4(0u, 0u, 0u, 0u);
          if (dostat) { xv[i][0] = ldg_nc(xr); xv[i][1] = ldg_nc(xr + 256); }
          if (dostat && lane < 16) xv[i][2] = ldg_nc(xr + 512);
        }
      }
      if ((kt == KST || kt == KST + 1) && dostat) {
        const float2 st = row_stats(xv[kt - KST][0], xv[kt - KST][1], xv[kt - KST][2]);
        if (lane == 0) st_relaxed(&g_rowstat[srow + kt - KST], st.x, st.y, tag);
      }
      __syncwarp();
    }
    cluster_arrive();
    WG_WAIT(0);
    fence_regs(acc);
    if (tid == 0) STAMP(0, 2);
    bar_sync(2, 96 + 384);
    if (tid == 0) STAMP(0, 3);
    const int row0 = m * 192 + warp * 16;
    if (row0 < S_) {
      const int g = lane >> 2, c = lane & 3, sec = n >> 2, grp = (row0 & 127) >> 3;
      const bool lo = c < 2;
      const float2 ab0 = rowab[warp * 16 + g], ab1 = rowab[warp * 16 + g + 8];
      const bool p0 = sec == 1 && ((POLY_MASK >> grp) & 1), p1 = sec == 1 && ((POLY_MASK >> (grp + 1)) & 1);
      const uint32_t padqv = sec == 0 ? (c == 2 ? 0x3F803F80u : 0x00003F80u) : (sec == 2 && c == 2 ? 0x00003F80u : 0u);
      const uint32_t padk = c == 2 ? 0x4A7A4B00u : 0x00004653u;
      const uint32_t pad0 = p0 ? padk : padqv, pad1 = p1 ? padk : padqv;
      const float f0 = sec == 0 ? QSCALE : (p0 ? 32768.f : 1.f), f1 = sec == 0 ? QSCALE : (p1 ? 32768.f : 1.f);
      const float a0 = ab0.x * f0, b0 = ab0.y * f0, a1 = ab1.x * f1, b1 = ab1.y * f1;
      const float r0 = p0 ? 9.313225746154785e-10f : 1.f, r1 = p1 ? 9.313225746154785e-10f : 1.f;
      const int cst = sec == 1 ? 2048 : 128, gst = sec == 1 ? 128 : 384;
      uint8_t* pe = (uint8_t*)g_qkv + (size_t)(n * 8) * HEAD_IMG + (row0 >> 7) * 6144 + grp * gst + lane * 4;
      uint8_t* pe1 = pe + cst;
      uint8_t* pe2 = pe1 + cst;
      uint8_t* pf = pe + gst;
      uint8_t* pf1 = pf + cst;
      uint8_t* pf2 = pf1 + cst;
#pragma unroll
      for (int hp = 0; hp < 4; hp++) {
        uint32_t u[5], v[5];
        float su[5], sv[5];
#pragma unroll
        for (int i = 0; i < 5; i++) {
          const int j = hp * 5 + i;
          const float2 t = *(const float2*)&cs[j * 8 + c * 2];
          const float x0 = fmaf(acc[4 * j], a0, b0 * t.x), x1 = fmaf(acc[4 * j + 1], a0, b0 * t.y);
          const float y0 = fmaf(acc[4 * j + 2], a1, b1 * t.x), y1 = fmaf(acc[4 * j + 3], a1, b1 * t.y);
          u[i] = pack_bf16(x0, x1); v[i] = pack_bf16(y0, y1);
          su[i] = fmaf(x0, x0, x1 * x1); sv[i] = fmaf(y0, y0, y1 * y1);
        }
        constexpr int HE = HEAD_IMG;
        const int oe = hp * 2 * HE, oo = oe + HE;
        *(uint32_t*)(pe + oe) = u[0];  *(uint32_t*)(pf + oe) = v[0];
        *(uint32_t*)(pe1 + oe) = u[1]; *(uint32_t*)(pf1 + oe) = v[1];
        *(uint32_t*)(pe2 + oe) = lo ? u[2] : pad0; *(uint32_t*)(pf2 + oe) = lo ? v[2] : pad1;
        *(uint32_t*)(pe + oo) = __shfl_xor_sync(~0u, lo ? u[3] : u[2], 2);
        *(uint32_t*)(pf + oo) = __shfl_xor_sync(~0u, lo ? v[3] : v[2], 2);
        *(uint32_t*)(pe1 + oo) = __shfl_xor_sync(~0u, lo ? u[4] : u[3], 2);
        *(uint32_t*)(pf1 + oo) = __shfl_xor_sync(~0u, lo ? v[4] : v[3], 2);
        const uint32_t tu = __shfl_xor_sync(~0u, u[4], 2), tv = __shfl_xor_sync(~0u, v[4], 2);
        *(uint32_t*)(pe2 + oo) = lo ? tu : pad0; *(uint32_t*)(pf2 + oo) = lo ? tv : pad1;
        if (sec < 2) {
          float e0 = (su[0] + su[1] + (lo ? su[2] : 0.f)) * r0, e1 = (sv[0] + sv[1] + (lo ? sv[2] : 0.f)) * r1;
          float o0 = (su[3] + su[4] + (lo ? 0.f : su[2])) * r0, o1 = (sv[3] + sv[4] + (lo ? 0.f : sv[2])) * r1;
          e0 += __shfl_xor_sync(~0u, e0, 1); e1 += __shfl_xor_sync(~0u, e1, 1);
          o0 += __shfl_xor_sync(~0u, o0, 1); o1 += __shfl_xor_sync(~0u, o1, 1);
          e0 += __shfl_xor_sync(~0u, e0, 2); e1 += __shfl_xor_sync(~0u, e1, 2);
          o0 += __shfl_xor_sync(~0u, o0, 2); o1 += __shfl_xor_sync(~0u, o1, 2);
          const uint32_t em = __reduce_max_sync(~0u, max(__float_as_uint(e0), __float_as_uint(e1)));
          const uint32_t om = __reduce_max_sync(~0u, max(__float_as_uint(o0), __float_as_uint(o1)));
          if (lane < 2) g_nrm[(n * 8 + hp * 2 + lane) * 128 + (row0 >> 4)] = __uint_as_float(lane ? om : em);
        }
      }
    }
    if (tid == 0) STAMP(0, 4);
  }
  cluster_wait();
  if (tid == 0) STAMP(0, 6);
}

constexpr int K2_SMEM = 2 * HEAD_IMG + 2 * 6144 + 2 * 10240 + 256;

__device__ __forceinline__ uint64_t desc64(uint32_t lo, uint32_t hi) {
  uint64_t d;
  asm("mov.b64 %0, {%1, %2};" : "=l"(d) : "r"(lo), "r"(hi));
  return d;
}
__device__ __forceinline__ uint32_t exp_pair(bool poly, float a, float b, uint32_t mk) {
  if (poly) {
    const uint32_t pk = __byte_perm(__float_as_uint(a), __float_as_uint(b), 0x6521);
    uint32_t m, q;
    asm("lop3.b32 %0, %1, %2, 0x3f803f80, 0xEA;" : "=r"(m) : "r"(pk), "r"(mk));
    asm("fma.rn.bf16x2 %0, %1, %1, %2;" : "=r"(q) : "r"(m), "r"(0x40014001u));
    return pk - m + q;
  }
  return pack_bf16(ex2(a), ex2(b));
}
#define PV_GR 4
__device__ __forceinline__ void exp_pv(const float (&s)[64], float (&o)[12], uint64_t dv, uint32_t mk) {
#pragma unroll
  for (int k0 = 0; k0 < 8; k0 += PV_GR) {
    uint32_t p[4 * PV_GR];
#pragma unroll
    for (int i = 0; i < 4 * PV_GR; i++)
      p[i] = exp_pair((POLY_MASK >> (k0 * 2 + i / 2)) & 1, s[k0 * 8 + 2 * i], s[k0 * 8 + 2 * i + 1], mk);
    WG_FENCE();
#pragma unroll
    for (int k = 0; k < PV_GR; k++)
      wgmma_rs_n24(o, p[4 * k], p[4 * k + 1], p[4 * k + 2], p[4 * k + 3], dv + (k0 + k) * 48, 1);
  }
}
__device__ __forceinline__ void load_q(uint32_t (&q)[6], const uint8_t* p) {
  q[0] = __ldcg((const uint32_t*)p);         q[1] = __ldcg((const uint32_t*)(p + 384));
  q[2] = __ldcg((const uint32_t*)(p + 128)); q[3] = __ldcg((const uint32_t*)(p + 512));
  q[4] = __ldcg((const uint32_t*)(p + 256)); q[5] = __ldcg((const uint32_t*)(p + 640));
}
__device__ __forceinline__ float rcp(float x) {
  float y;
  asm("rcp.approx.ftz.f32 %0, %1;" : "=f"(y) : "f"(x));
  return y;
}
__device__ __forceinline__ int img_off(int chunk) { return (chunk >> 3) * 16384 + (chunk & 7) * 128; }
__device__ __forceinline__ void store_o(const float (&o)[12], int tile) {
  int tid, bid;
  asm volatile("mov.u32 %0, %%tid.x;" : "=r"(tid));
  asm volatile("mov.u32 %0, %%ctaid.x;" : "=r"(bid));
  const int head = bid >> 2;
  uint8_t* dst = (uint8_t*)g_o + ((bid & 3) * 4 + (tile >> 1)) * 163840 + (tile & 1) * 8192 + ((tid >> 5) & 3) * 2048 + (tid & 31) * 4;
  const int oc = (head >> 1) * 5 + (head & 1) * 2;
  const int o0 = img_off(oc), o1 = img_off(oc + 1), o2 = img_off((head >> 1) * 5 + 4) + (head & 1) * 8;
  const float i0 = rcp(__shfl_sync(~0u, o[8], 2, 4)), i1 = rcp(__shfl_sync(~0u, o[10], 2, 4));
  *(uint32_t*)(dst + o0) = pack_bf16(o[0] * i0, o[1] * i0); *(uint32_t*)(dst + o0 + 1024) = pack_bf16(o[2] * i1, o[3] * i1);
  *(uint32_t*)(dst + o1) = pack_bf16(o[4] * i0, o[5] * i0); *(uint32_t*)(dst + o1 + 1024) = pack_bf16(o[6] * i1, o[7] * i1);
  if ((tid & 3) < 2) {
    *(uint32_t*)(dst + o2) = pack_bf16(o[8] * i0, o[9] * i0);
    *(uint32_t*)(dst + o2 + 1024) = pack_bf16(o[10] * i1, o[11] * i1);
  }
}

struct Maps5 { CUtensorMap m[5]; };

__global__ void __launch_bounds__(512, 1)
k2_attn(const __grid_constant__ Maps5 maps, uint32_t mk) {
  const CUtensorMap* tmw = maps.m;
  extern __shared__ __align__(1024) uint8_t sm[];
  const uint32_t sbase = smem_u32(sm);
  float* part = (float*)(sm + 2 * HEAD_IMG);
  const uint32_t rbuf = sbase + 2 * HEAD_IMG + 2 * 6144;
  const uint32_t kvb = rbuf + 2 * 10240;
  const uint32_t partb = kvb + 128, rbar = kvb + 144;
  const int tid = threadIdx.x, lane = tid & 31;
  const int warp = __shfl_sync(~0u, tid >> 5, 0);
  const int head = blockIdx.x >> 2, qb = blockIdx.x & 3;

  if (tid == 0) STAMP(1, 0);
  if (tid == 0) {
    for (int i = 0; i < 16; i++) mbar_init(kvb + 8 * i, 1);
    mbar_init(partb, 128); mbar_init(partb + 8, 128); mbar_init(rbar, 1); mbar_init(rbar + 8, 1);
    asm volatile("fence.mbarrier_init.release.cluster;" ::: "memory");
  }
  __syncthreads();

  if (warp >= 12) {
    asm volatile("setmaxnreg.dec.sync.aligned.u32 32;");
    if (tid == 384) {
      pdl_wait();
      pdl_trigger();
      const uint8_t* kimg = (const uint8_t*)g_qkv + (size_t)(32 + head) * HEAD_IMG;
#pragma unroll 1
      for (int b = 0; b < 16; b++) {
        mbar_expect(kvb + 8 * b, 12288);
        bulk_ld(sbase + b * 6144, kimg + b * 6144, 6144, kvb + 8 * b);
        bulk_ld(sbase + HEAD_IMG + b * 6144, kimg + 32 * HEAD_IMG + b * 6144, 6144, kvb + 8 * b);
        if (b >= 2) mbar_wait(kvb + 8 * (b - 1), 0);

      }
      if (blockIdx.x == 0) g_epoch = g_epoch + 1;
      mbar_wait(kvb + 8 * 15, 0);
      STAMP(1, 2);
      uint8_t* pdst = nullptr;
      uint32_t pbytes = 0;
#pragma unroll 1
      for (int i = 0; i < 8; i++) {
        const int p = blockIdx.x + 128 * i;
        uint8_t* dst = nullptr;
        uint32_t bytes = 0;
        if (i < 7 && p < 856) {
          asm volatile("cp.async.bulk.wait_group.read 0;" ::: "memory");
          const CUtensorMap* tm;
          int c1, c2;
          if (p < 640) {
            const int nt = p / 80, r = p - nt * 80, ph = r / 40, st = (r - ph * 40) >> 1, up = r & 1;
            bytes = ph ? 6656 : 7168;
            dst = (uint8_t*)g_wgu + nt * 552960 + ph * 286720 + st * 2 * bytes + up * (bytes >> 1);
            tm = &tmw[ph * 2 + up]; c1 = ph ? 112 + nt * 13 : nt * 14; c2 = st * 2;
          } else {
            const int nk = p - 640, nt = nk / 27;
            bytes = 10240;
            dst = (uint8_t*)g_wd + (size_t)nk * 10240;
            tm = &tmw[4]; c1 = nt * 10; c2 = nk - nt * 27;
          }
          mbar_expect(rbar + 8 * (i & 1), bytes);
          tma4d(rbuf + (i & 1) * 10240, tm, c1, c2, rbar + 8 * (i & 1));
        }
        if (pbytes) {
          mbar_wait(rbar + 8 * ((i - 1) & 1), ((i - 1) >> 1) & 1);
          if (pbytes == 10240) {
            bulk_st(pdst, rbuf + ((i - 1) & 1) * 10240, pbytes);
          } else {
            bulk_st(pdst, rbuf + ((i - 1) & 1) * 10240, pbytes >> 1);
            bulk_st(pdst + pbytes, rbuf + ((i - 1) & 1) * 10240 + (pbytes >> 1), pbytes >> 1);
          }
          asm volatile("cp.async.bulk.commit_group;" ::: "memory");
        }
        pdst = dst; pbytes = bytes;
      }
      asm volatile("cp.async.bulk.wait_group.read 0;" ::: "memory");
      STAMP(1, 6);
    }
  } else {
    asm volatile("setmaxnreg.inc.sync.aligned.u32 160;");
    const int wg = warp >> 2;
    const uint8_t* qthr = (const uint8_t*)g_qkv + (size_t)head * HEAD_IMG + qb * 64 * 384 + (warp & 3) * 768 + lane * 4;
    const uint32_t klo0 = ((sbase & 0x3FFFF) >> 4) | (128u << 16), vlo0 = (((sbase + HEAD_IMG) & 0x3FFFF) >> 4) | (24u << 16);
    constexpr uint64_t KSTEP2 = (uint64_t)(int64_t)(256 - (128 << 16));
    constexpr uint64_t KV2K = 384 - (HEAD_IMG >> 4) + (104 << 16);
    const int nun = wg == 1 ? 4 : 3;
    uint32_t utile = wg == 0 ? 0x210u : (wg == 1 ? 0x4235u : 0x576u);
    uint32_t ubeg = wg == 0 ? 0u : (wg == 1 ? 0x0b00u : 0x600u);
    uint32_t ulen = wg == 0 ? 0x0b1010u : (wg == 1 ? 0x10051006u : 0x0a1010u);
    pdl_wait();
    if (tid == 0) STAMP(1, 1);
    uint32_t q[6];
    load_q(q, qthr + (utile & 15) * 3072);
    bool fast;
    {
      const float4 kn = __ldcg((const float4*)&g_nrm[(32 + head) * 128 + lane * 4]);
      const float qv = __ldcg(&g_nrm[head * 128 + qb * 32 + lane]);
      const uint32_t km = max(max(__float_as_uint(kn.x), __float_as_uint(kn.y)), max(__float_as_uint(kn.z), __float_as_uint(kn.w)));
      const float k2 = __uint_as_float(__reduce_max_sync(~0u, km)), q2 = __uint_as_float(__reduce_max_sync(~0u, __float_as_uint(qv)));
      fast = q2 * k2 <= 3400.f;
    }
    if (fast) {
#pragma unroll 1
      for (int u = 0; u < nun; u++) {
        const uint32_t b0 = ubeg & 15;
        const bool wt = u == 0 || (wg == 1 && u == 1);
        float s[64], o[12];
#pragma unroll
        for (int i = 0; i < 12; i++) o[i] = 0.f;
        uint32_t vlo = vlo0 + b0 * 384, kb = kvb + b0 * 8;
        const uint32_t vend = vlo + ((ulen & 255) - 1) * 384;
        if (wt) mbar_wait(kb, 0);
        if (tid == 0) STAMP(5, 4 + u);
        fence_regs(o);
        WG_FENCE();
        wgmma_rs_n128(s, q[0], q[1], q[2], q[3], desc64(klo0 + b0 * 384, 8), 0);
        wgmma_rs_n128(s, q[4], q[5], 0, 0, desc64(klo0 + b0 * 384, 8) + KSTEP2, 1);
        WG_COMMIT();
#define K2UNR 1
        constexpr int kUnr = K2UNR;
#pragma unroll kUnr
        for (; vlo != vend; vlo += 384) {
          if (wt) { kb += 8; mbar_wait(kb, 0); }
          WG_WAIT(0);
          fence_regs(s); fence_regs(o);
          const uint64_t dv = desc64(vlo, 8);
          exp_pv(s, o, dv, mk);
          wgmma_rs_n128(s, q[0], q[1], q[2], q[3], dv + KV2K, 0);
          wgmma_rs_n128(s, q[4], q[5], 0, 0, dv + (KV2K + KSTEP2), 1);
          WG_COMMIT();
        }
        WG_WAIT(0);
        fence_regs(s); fence_regs(o);
        if (u + 1 < nun) load_q(q, qthr + ((utile >> 4) & 15) * 3072);
        exp_pv(s, o, desc64(vlo, 8), mk);
        WG_COMMIT();
        WG_WAIT(0);
        fence_regs(o);
        if (wg == 1 && !(u & 1)) {
          float4* pp = (float4*)(part + u * 768) + (tid & 127);
          pp[0] = make_float4(o[0], o[1], o[2], o[3]);
          pp[128] = make_float4(o[4], o[5], o[6], o[7]);
          pp[256] = make_float4(o[8], o[9], o[10], o[11]);
          mbar_arrive(partb + 4 * u);
        } else {
          if (wg != 1 && u == 2) {
            const int pi = wg == 0 ? 1 : 0;
            mbar_wait(partb + 8 * pi, 0);
            const float4* pp = (const float4*)(part + pi * 1536) + (tid & 127);
            const float4 x0 = pp[0], x1 = pp[128], x2 = pp[256];
            o[0] += x0.x; o[1] += x0.y; o[2] += x0.z; o[3] += x0.w; o[4] += x1.x; o[5] += x1.y;
            o[6] += x1.z; o[7] += x1.w; o[8] += x2.x; o[9] += x2.y; o[10] += x2.z; o[11] += x2.w;
          }
          store_o(o, utile & 15);
        }
        utile >>= 4; ubeg >>= 4; ulen >>= 8;
      }
      if ((tid & 127) == 0) STAMP(1, 3 + wg);
    } else {
#pragma unroll 1
      for (int tile = wg; tile < 8; tile += 3) {
        load_q(q, qthr + tile * 3072);
        if ((lane & 3) >= 2) { q[4] = 0; q[5] = 0; }
        float o[12], m0 = -INFINITY, m1 = -INFINITY;
#pragma unroll
        for (int i = 0; i < 12; i++) o[i] = 0.f;
#pragma unroll 1
        for (int b = 0; b < 16; b++) {
          float s[64];
          mbar_wait(kvb + 8 * b, 0);
          WG_FENCE();
          wgmma_rs_n128(s, q[0], q[1], q[2], q[3], desc64(klo0 + b * 384, 8), 0);
          wgmma_rs_n128(s, q[4], q[5], 0, 0, desc64(klo0 + b * 384, 8) + KSTEP2, 1);
          WG_COMMIT();
          WG_WAIT(0);
          fence_regs(s);
          float x0 = m0, x1 = m1;
#pragma unroll
          for (int j = 0; j < 16; j++) {
            if ((POLY_MASK >> j) & 1) {
#pragma unroll
              for (int i = 0; i < 4; i++) s[4 * j + i] *= (1.f / 32768.f);
            }
            x0 = fmaxf(x0, fmaxf(s[4 * j], s[4 * j + 1]));
            x1 = fmaxf(x1, fmaxf(s[4 * j + 2], s[4 * j + 3]));
          }
          x0 = fmaxf(x0, __shfl_xor_sync(~0u, x0, 1)); x0 = fmaxf(x0, __shfl_xor_sync(~0u, x0, 2));
          x1 = fmaxf(x1, __shfl_xor_sync(~0u, x1, 1)); x1 = fmaxf(x1, __shfl_xor_sync(~0u, x1, 2));
          const float al0 = ex2(m0 - x0), al1 = ex2(m1 - x1);
          m0 = x0; m1 = x1;
#pragma unroll
          for (int i = 0; i < 12; i++) o[i] *= (i & 2) ? al1 : al0;
          uint32_t p[32];
#pragma unroll
          for (int i = 0; i < 32; i++) {
            const float mm = (i & 1) ? m1 : m0;
            p[i] = pack_bf16(ex2(s[2 * i] - mm), ex2(s[2 * i + 1] - mm));
          }
          fence_regs(o);
          WG_FENCE();
#pragma unroll
          for (int k = 0; k < 8; k++)
            wgmma_rs_n24(o, p[4 * k], p[4 * k + 1], p[4 * k + 2], p[4 * k + 3], desc64(vlo0 + b * 384 + k * 48, 8), 1);
          WG_COMMIT();
          WG_WAIT(0);
          fence_regs(o);
        }
        store_o(o, tile);
      }
    }
  }
}

#define K3P 2
constexpr int K3_ST = 4, K3_STAGE = 37888, K3_PRE = K3P;
constexpr int K3_SMEM = K3_ST * K3_STAGE + 45056 + 20480 + 256;

template <int N> struct Acc { float v[N]; };

template <int NB, int NK, bool FIRST>
__global__ void __cluster_dims__(2, 1, 1) __launch_bounds__(384, 1)
k3_proj(const __grid_constant__ CUtensorMap tmr, const uint4* __restrict__ aimg, const uint4* __restrict__ wimg) {
  constexpr int KT = 2 * NB + NK, EX = FIRST ? 1 : 0;
  extern __shared__ __align__(1024) uint8_t sm[];
  const uint32_t sbase = smem_u32(sm);
  uint8_t* xch = sm + K3_ST * K3_STAGE;
  uint8_t* stg = sm + K3_ST * K3_STAGE + 45056;
  const uint32_t fullb = smem_u32(stg) + 20480, emptyb = fullb + 8 * K3_ST, resb = emptyb + 8 * K3_ST, xchb = resb + 8;
  const int tid = threadIdx.x, lane = tid & 31;
  const int warp = __shfl_sync(~0u, tid >> 5, 0);
  const int rank = blockIdx.x & 1;
  const int n = blockIdx.x & 7, m = blockIdx.x >> 3;
  if (tid == 0) STAMP(FIRST ? 2 : 4, 0);
  if (warp == 0) {
    if (lane == 0) {
      prefetch_map(&tmr);
      for (int i = 0; i < K3_ST; i++) { mbar_init(fullb + 8 * i, 1); mbar_init(emptyb + 8 * i, 4); }
      mbar_init(resb, 1); mbar_init(xchb, 1);
      mbar_expect(xchb, 4096 * (10 + EX));
      asm volatile("fence.mbarrier_init.release.cluster;" ::: "memory");
    }
    __syncwarp();
    cluster_arrive();
    bar_arrive(4, 256 + 32);
    if (lane == 0) {
      const uint8_t* wk = (const uint8_t*)wimg + (size_t)n * KT * 10240;
      const uint8_t* ws = (const uint8_t*)wimg + (size_t)(n ^ 1) * KT * 10240;
      const uint8_t* ab = (const uint8_t*)aimg + (size_t)m * KT * 16384;
      auto load_w = [&](int i) {
        const int s = i % K3_ST, kt = i < NB ? i + rank * (NB + NK) : i;
        const uint32_t sa = sbase + s * K3_STAGE;
        mbar_expect(fullb + 8 * s, 26624 + EX * 1024 + (i < NB ? 10240 : 0));
        bulk_ld(sa + 16384, wk + kt * 10240, 10240, fullb + 8 * s);
        if (FIRST) bulk_ld(sa + 26624, (const uint8_t*)g_wm + kt * 1024, 1024, fullb + 8 * s);
        if (i < NB) bulk_ld(sa + 26624 + EX * 1024, ws + kt * 10240, 10240, fullb + 8 * s);
      };
#pragma unroll 1
      for (int i = 0; i < K3_PRE; i++) load_w(i);
      if (FIRST) {
        mbar_expect(resb, 20480);
        tma2d(smem_u32(stg), &tmr, n * 80, m * 128, resb);
        tma2d(smem_u32(stg) + 10240, &tmr, n * 80, m * 128 + 64, resb);
      }
      asm volatile("barrier.cluster.wait;" ::: "memory");
      pdl_wait();
      pdl_trigger();
#pragma unroll 1
      for (int i = 0; i < NB + NK; i++) {
        const int s = i % K3_ST;
        const uint32_t sa = sbase + s * K3_STAGE;
        if (i >= K3_ST) mbar_wait(emptyb + 8 * s, ((i / K3_ST) - 1) & 1);
        if (i < NB) bulk_ld(sa, ab + (i + rank * (NB + NK)) * 16384, 16384, fullb + 8 * s);
        else bulk_ld_mc(sa + rank * 8192, ab + i * 16384 + rank * 8192, 8192, fullb + 8 * s);
        if (i >= K3_PRE) load_w(i);
      }
    } else {
      asm volatile("barrier.cluster.wait;" ::: "memory");
    }
    __syncwarp();
    cluster_arrive();
  } else if (warp >= 4) {
    cluster_arrive();
    const int cw = warp - 4, wg = cw >> 2;
    const int g = lane >> 2, c = lane & 3;
    const int row = m * 128 + cw * 16 + g;
    uint8_t* himg = (uint8_t*)g_h + (size_t)m * 163840 + cw * 2048 + lane * 4;
    uint32_t rv[20];
    float mu0, mu1;
    if (FIRST) {
      mu0 = __uint_as_float(__ldcg(&g_rowstat[row].z)); mu1 = __uint_as_float(__ldcg(&g_rowstat[row + 8].z));
    } else {
      mu0 = __ldcg(&g_hmean[row]); mu1 = __ldcg(&g_hmean[row + 8]);
#pragma unroll
      for (int j = 0; j < 10; j++) {
        rv[2 * j] = __ldcg((const uint32_t*)(himg + img_off(n * 10 + j)));
        rv[2 * j + 1] = __ldcg((const uint32_t*)(himg + img_off(n * 10 + j) + 1024));
      }
    }
    float acc[80 + 4 * EX];
    float (&keep)[40 + 4 * EX] = ((Acc<40 + 4 * EX>*)acc)->v;
    const uint64_t da0 = mkdesc(sbase + wg * 8192, 128, 1024, 0);
    const uint64_t db0 = mkdesc(sbase + 16384, 128, 1024, 0);
    bar_sync(4, 256 + 32);
    cluster_wait();
#pragma unroll 1
    for (int i = 0; i < NB; i++) {
      const int s = i % K3_ST;
      mbar_wait(fullb + 8 * s, (i / K3_ST) & 1);
      if (i == 0 && tid == 128) STAMP(FIRST ? 2 : 4, 2);
      const uint64_t da = da0 + s * (K3_STAGE >> 4), db = db0 + s * (K3_STAGE >> 4);
      WG_FENCE();
#pragma unroll
      for (int k = 0; k < 4; k++) {
        if constexpr (FIRST) wgmma_ss_n168(acc, da + k * 16, db + k * 16, (i | k) != 0);
        else wgmma_ss_n160(acc, da + k * 16, db + k * 16, (i | k) != 0);
      }
      WG_COMMIT();
      if (i > 0) {
        WG_WAIT(1);
        if ((tid & 127) < 2) mbar_arrive_cta(emptyb + 8 * ((i - 1) % K3_ST), tid & 1);
      }
    }
    const uint32_t rx = mapa(smem_u32(xch) + (tid - 128) * 16, rank ^ 1), rb = mapa(xchb, rank ^ 1);
    WG_WAIT(0);
    fence_regs(acc);
    if ((tid & 127) < 2) mbar_arrive_cta(emptyb + 8 * ((NB - 1) % K3_ST), tid & 1);
    if (FIRST) st_async4(rx, acc[40], acc[41], acc[42], acc[43], rb);
    if (tid == 128) STAMP(FIRST ? 2 : 4, 1);
#pragma unroll
    for (int i = NB; i < NB + NK; i++) {
      const int s = i % K3_ST;
      mbar_wait(fullb + 8 * s, (i / K3_ST) & 1);
      const uint64_t da = da0 + s * (K3_STAGE >> 4), db = db0 + s * (K3_STAGE >> 4);
      WG_FENCE();
#pragma unroll
      for (int k = 0; k < 4; k++) {
        if constexpr (FIRST) wgmma_ss_n88(keep, da + k * 16, db + k * 16, 1);
        else wgmma_ss_n80(keep, da + k * 16, db + k * 16, 1);
      }
      WG_COMMIT();
      if (i > NB && i - 1 + K3_ST < NB + NK) {
        WG_WAIT(1);
        if ((tid & 127) < 2) mbar_arrive_cta(emptyb + 8 * ((i - 1) % K3_ST), tid & 1);
      }
#pragma unroll
      for (int j = (i - NB) * 3 + EX; j < (i - NB) * 3 + 3 + EX; j++)
        if (j < 10 + EX) st_async4(rx + j * 4096, acc[40 + 4 * j], acc[41 + 4 * j], acc[42 + 4 * j], acc[43 + 4 * j], rb);
    }
    cluster_arrive();
    uint8_t* sp = stg + (cw * 16 + g) * 160 + c * 4;
    if (FIRST) {
      mbar_wait(resb, 0);
#pragma unroll
      for (int j = 0; j < 10; j++) {
        rv[2 * j] = *(const uint32_t*)(sp + j * 16);
        rv[2 * j + 1] = *(const uint32_t*)(sp + 1280 + j * 16);
      }
    }
    WG_WAIT(0);
    fence_regs(keep);
    if (tid == 128) STAMP(FIRST ? 2 : 4, 3);
    mbar_wait(xchb, 0);
    if (tid == 128) STAMP(FIRST ? 2 : 4, 5);
    const uint8_t* xp = xch + (tid - 128) * 16;
    if (FIRST) {
      const float4 p = *(const float4*)xp;
      mu0 += __shfl_sync(~0u, (keep[40] + p.x) + (keep[41] + p.y), 0, 4);
      mu1 += __shfl_sync(~0u, (keep[42] + p.z) + (keep[43] + p.w), 0, 4);
      if (n == 0 && c == 0) { g_hmean[row] = mu0; g_hmean[row + 8] = mu1; }
      mu0 = -mu0; mu1 = -mu1;
    }
    float q0 = 0.f, q1 = 0.f;
#pragma unroll
    for (int j = 0; j < 10; j++) {
      const float4 p = *(const float4*)(xp + (j + EX) * 4096);
      const float x0 = (keep[4 * j] + p.x) + (bf_lo(rv[2 * j]) + mu0), x1 = (keep[4 * j + 1] + p.y) + (bf_hi(rv[2 * j]) + mu0);
      const float y0 = (keep[4 * j + 2] + p.z) + (bf_lo(rv[2 * j + 1]) + mu1), y1 = (keep[4 * j + 3] + p.w) + (bf_hi(rv[2 * j + 1]) + mu1);
      if (FIRST) {
        *(uint32_t*)(himg + img_off(n * 10 + j)) = pack_bf16(x0, x1);
        *(uint32_t*)(himg + img_off(n * 10 + j) + 1024) = pack_bf16(y0, y1);
        q0 = fmaf(x0, x0, fmaf(x1, x1, q0)); q1 = fmaf(y0, y0, fmaf(y1, y1, q1));
      } else {
        *(uint32_t*)(sp + j * 16) = pack_bf16(x0, x1);
        *(uint32_t*)(sp + 1280 + j * 16) = pack_bf16(y0, y1);
      }
    }
    if (FIRST) {
      q0 += __shfl_xor_sync(~0u, q0, 1); q0 += __shfl_xor_sync(~0u, q0, 2);
      q1 += __shfl_xor_sync(~0u, q1, 1); q1 += __shfl_xor_sync(~0u, q1, 2);
      if (c < 2) g_hpart[n * S_ + row + c * 8] = c ? q1 : q0;
    } else {
      fence_async();
      bar_sync(1 + wg, 128);
      if ((tid & 127) == 0) {
        tma2d_st(&tmr, n * 80, m * 128 + wg * 64, smem_u32(stg) + wg * 10240);
        bulk_commit_wait();
      }
      __syncwarp();
    }
    if (tid == 128) STAMP(FIRST ? 2 : 4, 4);
  } else {
    cluster_arrive();
    cluster_wait();
    cluster_arrive();
  }
  cluster_wait();
}

#define K4G 2
#define K4MC 2
constexpr int K4_G = K4G, K4_NS = K4_G == 1 ? 9 : (K4_G == 2 ? 4 : 2), K4_NJ = 40 / K4_G;
constexpr int K4_RB = 163840, K4_BST = 7168 * K4_G, K4_XCH = 147456, K4_STG = K4_XCH + 40960, K4_BAR = K4_RB + K4_NS * K4_BST;
constexpr int K4_SMEM = K4_BAR + 384;

__device__ __forceinline__ void wait_flags(const uint4* f, uint32_t tag) {
  for (uint32_t it = 0;; it++) {
    uint4 a, b;
    asm volatile("ld.acquire.gpu.global.v4.u32 {%0, %1, %2, %3}, [%4];" : "=r"(a.x), "=r"(a.y), "=r"(a.z), "=r"(a.w) : "l"(f) : "memory");
    asm volatile("ld.acquire.gpu.global.v4.u32 {%0, %1, %2, %3}, [%4];" : "=r"(b.x), "=r"(b.y), "=r"(b.z), "=r"(b.w) : "l"(f + 1) : "memory");
    if (a.x == tag && a.y == tag && a.z == tag && a.w == tag && b.x == tag && b.y == tag && b.z == tag && b.w == tag) break;
    if (it > (1u << 20)) wait_timeout();
    __nanosleep(50);
  }
  asm volatile("fence.proxy.async.global;" ::: "memory");
}

__global__ void __cluster_dims__(2, 1, 1) __launch_bounds__(384, 1)
k45_ffn(const __grid_constant__ CUtensorMap tmo) {
  extern __shared__ __align__(1024) uint8_t sm[];
  const uint32_t sbase = smem_u32(sm);
  const uint32_t afull = sbase + K4_BAR, bfull = afull + 80, bempty = bfull + 8 * K4_NS, full3 = bempty + 8 * K4_NS;
  const uint32_t empty3 = full3 + 32, afree = empty3 + 32, xchb = afree + 32;
  const int tid = threadIdx.x, lane = tid & 31;
  const int warp = __shfl_sync(~0u, tid >> 5, 0);
  const int rank = blockIdx.x & 1;
  const int n1 = (blockIdx.x >> 1) & 7, m1 = (blockIdx.x >> 4) * 2 + rank;
  const int n3 = blockIdx.x & 7, m3 = blockIdx.x >> 3;
  if (tid == 0) STAMP(3, 0);
  if (warp == 8) {
    if (lane < 10) mbar_init(afull + 8 * lane, 1);
    if (lane < K4_NS) { mbar_init(bfull + 8 * lane, 1); mbar_init(bempty + 8 * lane, 4); }
    if (lane < 4) { mbar_init(full3 + 8 * lane, 1); mbar_init(empty3 + 8 * lane, 4); mbar_init(afree + 8 * lane, 2); }
    if (lane == 0) { mbar_init(xchb, 1); mbar_expect(xchb, 40960); prefetch_map(&tmo); }
    asm volatile("fence.mbarrier_init.release.cluster;" ::: "memory");
    __syncwarp();
  }
  cluster_arrive();
  if (warp >= 8) {
    cluster_wait();
    if (warp == 8) {
      if (lane == 0) {
        const uint8_t* wb = (const uint8_t*)g_wgu + n1 * 552960;
        const uint8_t* hb = (const uint8_t*)g_h + (size_t)m1 * 163840;
        int s = 0, ph = 1;
#pragma unroll 1
        for (int j = 0; j < 2 * K4_NJ; j++) {
          if (j == K4_NS) {
            pdl_wait();
            STAMP(3, 1);
#pragma unroll 1
            for (int kt = 0; kt < 3; kt++) { mbar_expect(afull + 8 * kt, 16384); bulk_ld(sbase + kt * 16384, hb + kt * 16384, 16384, afull + 8 * kt); }
          }
          if (j >= K4_NS) mbar_wait(bempty + 8 * s, ph);
          if (j >= K4_NS && ((j - K4_NS) * K4_G) % 4 == 0 && 3 + (j - K4_NS) * K4_G / 4 < 10) {
            const int kt = 3 + (j - K4_NS) * K4_G / 4;
            mbar_expect(afull + 8 * kt, 16384);
            bulk_ld(sbase + kt * 16384, hb + kt * 16384, 16384, afull + 8 * kt);
          }
          const uint32_t sz = (j < K4_NJ ? 7168 : 6656) * K4_G;
          const uint8_t* src = wb + (j < K4_NJ ? j * sz : 286720 + (j - K4_NJ) * sz);
          mbar_expect(bfull + 8 * s, sz);
          if (K4MC == 0) bulk_ld(sbase + K4_RB + s * K4_BST, src, sz, bfull + 8 * s);
          if (K4MC == 1) bulk_ld_mc(sbase + K4_RB + s * K4_BST + rank * (sz >> 1), src + rank * (sz >> 1), sz >> 1, bfull + 8 * s);
          if (K4MC == 2 && (j & 1) == rank) bulk_ld_mc(sbase + K4_RB + s * K4_BST, src, sz, bfull + 8 * s);
          if (++s == K4_NS) { s = 0; ph ^= 1; }
        }
      }
    } else if (warp == 9) {
      const uint32_t tag = __ldcg(&g_epoch);
#pragma unroll 1
      for (int ph = 0; ph < 2; ph++) {
        bar_sync(5 + ph, 256 + 32);
        if (lane == 0) {
          asm volatile("st.release.gpu.global.u32 [%0], %1;" ::"l"((uint32_t*)&g_flag[ph * 32 + m1 * 2] + n1), "r"(tag) : "memory");
          STAMP(3, 5 + ph);
        }
        __syncwarp();
      }
    } else if (lane == 0) {
      const uint8_t* wk = (const uint8_t*)g_wd + n3 * 276480;
      const uint8_t* ws = (const uint8_t*)g_wd + (n3 ^ 1) * 276480;
      const uint8_t* ab = (const uint8_t*)g_hh + (size_t)m3 * 442368;
      const uint32_t tag = __ldcg(&g_epoch);
#pragma unroll 1
      for (int i = 0; i < 16; i++) {
        const int kt = i < 7 ? rank * 7 + i : (i < 11 ? rank * 4 + 7 + i : 11 + i);
        const uint32_t sa = sbase + (i & 3) * 36864, fb = full3 + 8 * (i & 3);
        if (i < 4) mbar_wait(afree + 8 * i, 0);
        else mbar_wait(empty3 + 8 * (i & 3), ((i >> 2) - 1) & 1);
        if (warp == 10) {
          mbar_expect(fb, i < 11 ? 36864 : 26624);
          bulk_ld(sa + 16384, wk + kt * 10240, 10240, fb);
          if (i < 11) bulk_ld(sa + 26624, ws + kt * 10240, 10240, fb);
        } else {
          if (i == 0 || i == 7) {
            wait_flags(&g_flag[(i ? 32 : 0) + m3 * 2], tag);
            STAMP(4, i ? 7 : 6);
          }
          if (i < 11) bulk_ld(sa, ab + kt * 16384, 16384, fb);
          else bulk_ld_mc(sa + rank * 8192, ab + kt * 16384 + rank * 8192, 8192, fb);
        }
      }
    }
    __syncwarp();
    cluster_arrive();
    asm volatile("barrier.cluster.wait.aligned; // producers" ::: "memory");
  } else {
    const int wg = warp >> 2;
    const uint64_t da0 = mkdesc(sbase + wg * 8192, 128, 1024, 0);
    const uint64_t db0 = mkdesc(sbase + K4_RB, 128, 256, 0);
    cluster_wait();
    float a1[112], a2[104];
    int s = 0, ph = 0, sprev = 0;
#pragma unroll 1
    for (int j = 0; j < K4_NJ; j++) {
      if ((j * K4_G) % 4 == 0) mbar_wait(afull + 2 * K4_G * j, 0);
      mbar_wait(bfull + 8 * s, ph);
      if (j == 0 && tid == 0) STAMP(3, 2);
      const uint64_t da = da0 + ((j * K4_G) >> 2) * 1024 + ((j * K4_G) & 3) * 16, db = db0 + s * (K4_BST >> 4);
      WG_FENCE();
#pragma unroll
      for (int k = 0; k < K4_G; k++) wgmma_ss_n224(a1, da + k * 16, db + k * 448, (j | k) != 0);
      WG_COMMIT();
      if (j > 0) {
        WG_WAIT(1);
        if ((tid & 127) < 2) mbar_arrive_cta(bempty + 8 * sprev, tid & 1);
      }
      sprev = s;
      if (++s == K4_NS) { s = 0; ph ^= 1; }
    }
    float r0, r1;
    {
      const float* hp = &g_hpart[(lane & 3) * 2 * S_ + m1 * 128 + warp * 16 + (lane >> 2)];
      r0 = __ldcg(hp) + __ldcg(hp + S_);
      r1 = __ldcg(hp + 8) + __ldcg(hp + S_ + 8);
    }
    float acc[80];
    uint8_t* hd = (uint8_t*)g_hh + (size_t)m1 * 442368 + warp * 2048 + lane * 4;
    {
      r0 += __shfl_xor_sync(~0u, r0, 1); r1 += __shfl_xor_sync(~0u, r1, 1);
      r0 += __shfl_xor_sync(~0u, r0, 2); r1 += __shfl_xor_sync(~0u, r1, 2);
      r0 = __frcp_rn(r0 * (1.f / D_) + 1e-5f); r1 = __frcp_rn(r1 * (1.f / D_) + 1e-5f);
    }
    WG_WAIT(0);
    fence_regs(a1);
    if ((tid & 127) < 2) mbar_arrive_cta(bempty + 8 * ((K4_NJ - 1) % K4_NS), tid & 1);
    if (tid == 0) STAMP(3, 3);
#define STORE_H(a, off, q, c) do { uint8_t* p_ = hd + img_off(q); \
      *(uint32_t*)p_ = pack_bf16(a[4 * (c)] * r0 * a[off + 4 * (c)], a[4 * (c) + 1] * r0 * a[off + 1 + 4 * (c)]); \
      *(uint32_t*)(p_ + 1024) = pack_bf16(a[4 * (c) + 2] * r1 * a[off + 2 + 4 * (c)], a[4 * (c) + 3] * r1 * a[off + 3 + 4 * (c)]); } while (0)
#pragma unroll
    for (int c = 0; c < 14; c++) STORE_H(a1, 56, n1 * 14 + c, c);
    bar_arrive(5, 256 + 32);
#pragma unroll 1
    for (int j = 0; j < K4_NJ; j++) {
      mbar_wait(bfull + 8 * s, ph);
      const uint64_t da = da0 + ((j * K4_G) >> 2) * 1024 + ((j * K4_G) & 3) * 16, db = db0 + s * (K4_BST >> 4);
      WG_FENCE();
#pragma unroll
      for (int k = 0; k < K4_G; k++) wgmma_ss_n208(a2, da + k * 16, db + k * 416, (j | k) != 0);
      WG_COMMIT();
      if (j > 0) {
        WG_WAIT(1);
        if (j <= K4_NJ - K4_NS && (tid & 127) < 2) mbar_arrive_cta(bempty + 8 * sprev, tid & 1);
        if (j * K4_G >= 12 && ((j * K4_G) & 7) == 4 && (tid & 127) == 0) mbar_arrive(afree + (j * K4_G - 12));
      }
      sprev = s;
      if (++s == K4_NS) { s = 0; ph ^= 1; }
    }
    WG_WAIT(0);
    fence_regs(a2);
    if (tid == 0) STAMP(3, 4);
#pragma unroll
    for (int c = 0; c < 13; c++) STORE_H(a2, 52, 112 + n1 * 13 + c, c);
    bar_arrive(6, 256 + 32);
    float (&keep)[40] = ((Acc<40>*)acc)->v;
    const uint64_t db3 = mkdesc(sbase + 16384, 128, 1024, 0);
#pragma unroll 1
    for (int i = 0; i < 11; i++) {
      mbar_wait(full3 + 8 * (i & 3), (i >> 2) & 1);
      if (i == 0 && tid == 0) STAMP(4, 2);
      const uint64_t da = da0 + (i & 3) * 2304, db = db3 + (i & 3) * 2304;
      WG_FENCE();
#pragma unroll
      for (int k = 0; k < 4; k++) wgmma_ss_n160(acc, da + k * 16, db + k * 16, (i | k) != 0);
      WG_COMMIT();
      if (i > 0) {
        WG_WAIT(1);
        if ((tid & 127) < 2) mbar_arrive_cta(empty3 + 8 * ((i - 1) & 3), tid & 1);
      }
    }
    const int g = lane >> 2, c = lane & 3, row = m3 * 128 + warp * 16 + g;
    const uint8_t* himg = (const uint8_t*)g_h + (size_t)m3 * 163840 + warp * 2048 + lane * 4;
    uint32_t rv[20];
    const float mu0 = __ldcg(&g_hmean[row]), mu1 = __ldcg(&g_hmean[row + 8]);
#pragma unroll
    for (int j = 0; j < 10; j++) {
      rv[2 * j] = __ldcg((const uint32_t*)(himg + img_off(n3 * 10 + j)));
      rv[2 * j + 1] = __ldcg((const uint32_t*)(himg + img_off(n3 * 10 + j) + 1024));
    }
    const uint32_t rx = mapa(sbase + K4_XCH + tid * 16, rank ^ 1), rb = mapa(xchb, rank ^ 1);
    WG_WAIT(0);
    fence_regs(acc);
    if ((tid & 127) < 2) mbar_arrive_cta(empty3 + 16, tid & 1);
    if (tid == 0) STAMP(4, 1);
#pragma unroll
    for (int i = 11; i < 16; i++) {
      mbar_wait(full3 + 8 * (i & 3), (i >> 2) & 1);
      const uint64_t da = da0 + (i & 3) * 2304, db = db3 + (i & 3) * 2304;
      WG_FENCE();
#pragma unroll
      for (int k = 0; k < 4; k++) wgmma_ss_n80(keep, da + k * 16, db + k * 16, 1);
      WG_COMMIT();
      if (i == 12) {
        WG_WAIT(1);
        if ((tid & 127) < 2) mbar_arrive_cta(empty3 + 24, tid & 1);
      }
#pragma unroll
      for (int j = (i - 11) * 3; j < (i - 11) * 3 + 3; j++)
        if (j < 10) st_async4(rx + j * 4096, acc[40 + 4 * j], acc[41 + 4 * j], acc[42 + 4 * j], acc[43 + 4 * j], rb);
    }
    cluster_arrive();
    WG_WAIT(0);
    fence_regs(keep);
    if (tid == 0) STAMP(4, 3);
    mbar_wait(xchb, 0);
    if (tid == 0) STAMP(4, 5);
    uint8_t* sp = sm + K4_STG + (warp * 16 + g) * 160 + c * 4;
#pragma unroll
    for (int j = 0; j < 10; j++) {
      const float4 p = *(const float4*)(sm + K4_XCH + tid * 16 + j * 4096);
      *(uint32_t*)(sp + j * 16) = pack_bf16((keep[4 * j] + p.x) + (bf_lo(rv[2 * j]) + mu0), (keep[4 * j + 1] + p.y) + (bf_hi(rv[2 * j]) + mu0));
      *(uint32_t*)(sp + 1280 + j * 16) = pack_bf16((keep[4 * j + 2] + p.z) + (bf_lo(rv[2 * j + 1]) + mu1), (keep[4 * j + 3] + p.w) + (bf_hi(rv[2 * j + 1]) + mu1));
    }
    fence_async();
    bar_sync(1 + wg, 128);
    if ((tid & 127) == 0) {
      tma2d_st(&tmo, n3 * 80, m3 * 128 + wg * 64, sbase + K4_STG + wg * 10240);
      bulk_commit_wait();
    }
    __syncwarp();
    if (tid == 0) STAMP(4, 4);
    asm volatile("barrier.cluster.wait.aligned; // consumers" ::: "memory");
  }
}

typedef CUresult (*EncodeFn)(CUtensorMap*, CUtensorMapDataType, cuuint32_t, void*, const cuuint64_t*, const cuuint64_t*,
                             const cuuint32_t*, const cuuint32_t*, CUtensorMapInterleave, CUtensorMapSwizzle,
                             CUtensorMapL2promotion, CUtensorMapFloatOOBfill);

static CUtensorMap make_map(EncodeFn enc, const void* p, uint64_t inner, uint64_t outer, uint32_t box_inner,
                            uint32_t box_outer, CUtensorMapSwizzle swz) {
  CUtensorMap m;
  cuuint64_t gd[2] = {inner, outer};
  cuuint64_t gs[1] = {inner * 2};
  cuuint32_t bd[2] = {box_inner, box_outer};
  cuuint32_t es[2] = {1, 1};
  enc(&m, CU_TENSOR_MAP_DATA_TYPE_BFLOAT16, 2, (void*)p, gd, gs, bd, es, CU_TENSOR_MAP_INTERLEAVE_NONE, swz,
      CU_TENSOR_MAP_L2_PROMOTION_L2_256B, CU_TENSOR_MAP_FLOAT_OOB_FILL_NONE);
  return m;
}

static CUtensorMap make_map_img(EncodeFn enc, const void* p, uint64_t k, uint64_t n, uint32_t rows, uint32_t chunks,
                                uint32_t groups) {
  CUtensorMap m;
  cuuint64_t gd[4] = {8, rows, n / 8, k / rows};
  cuuint64_t gs[3] = {n * 2, 16, n * 2 * rows};
  cuuint32_t bd[4] = {8, rows, chunks, groups};
  cuuint32_t es[4] = {1, 1, 1, 1};
  enc(&m, CU_TENSOR_MAP_DATA_TYPE_BFLOAT16, 4, (void*)p, gd, gs, bd, es, CU_TENSOR_MAP_INTERLEAVE_NONE,
      CU_TENSOR_MAP_SWIZZLE_NONE, CU_TENSOR_MAP_L2_PROMOTION_L2_128B, CU_TENSOR_MAP_FLOAT_OOB_FILL_NONE);
  return m;
}

template <typename... KArgs, typename... Args>
static void launch(void (*k)(KArgs...), int grid, int threads, int smem, bool pdl, Args... args) {
  cudaLaunchConfig_t cfg = {};
  cfg.gridDim = dim3(grid);
  cfg.blockDim = dim3(threads);
  cfg.dynamicSmemBytes = smem;
  cfg.stream = cudaStreamPerThread;
  cudaLaunchAttribute at[1];
  at[0].id = cudaLaunchAttributeProgrammaticStreamSerialization;
  at[0].val.programmaticStreamSerializationAllowed = 1;
  cfg.attrs = at;
  cfg.numAttrs = pdl ? 1 : 0;
  cudaLaunchKernelEx(&cfg, k, KArgs(args)...);
}

extern "C" void kernel_launch(void* const* d_in, const int* in_sizes, int n_in, void* d_out, int out_size) {
  const bf16* x = (const bf16*)d_in[0];
  const bf16* wqkv = (const bf16*)d_in[1];
  const bf16* wo = (const bf16*)d_in[2];
  const bf16* wg = (const bf16*)d_in[4];
  const bf16* wu = (const bf16*)d_in[5];
  const bf16* wd = (const bf16*)d_in[6];

  static EncodeFn enc = nullptr;
  static void *p_o, *p_wo;
  if (!enc) {
    void* fn = nullptr;
    cudaDriverEntryPointQueryResult qr;
    cudaGetDriverEntryPoint("cuTensorMapEncodeTiled", &fn, cudaEnableDefault, &qr);
    enc = (EncodeFn)fn;
    cudaGetSymbolAddress(&p_o, g_o);
    cudaGetSymbolAddress(&p_wo, g_wo);
    cudaFuncSetAttribute(k1_qkv, cudaFuncAttributeMaxDynamicSharedMemorySize, K1_SMEM);
    cudaFuncSetAttribute(k2_attn, cudaFuncAttributeMaxDynamicSharedMemorySize, K2_SMEM);
    cudaFuncSetAttribute(k3_proj<3, 4, true>, cudaFuncAttributeMaxDynamicSharedMemorySize, K3_SMEM);
    cudaFuncSetAttribute(k45_ffn, cudaFuncAttributeMaxDynamicSharedMemorySize, K4_SMEM);
  }
  const CUtensorMap tmx = make_map(enc, x, D_, S_, 64, 96, CU_TENSOR_MAP_SWIZZLE_128B);
  const CUtensorMap tmw = make_map(enc, wqkv, 3 * D_, D_, 32, 64, CU_TENSOR_MAP_SWIZZLE_64B);
  const CUtensorMap tmxr = make_map(enc, x, D_, S_, 80, 64, CU_TENSOR_MAP_SWIZZLE_NONE);
  Maps5 maps;
  maps.m[0] = make_map_img(enc, wg, D_, F_, 16, 14, 2); maps.m[1] = make_map_img(enc, wu, D_, F_, 16, 14, 2);
  maps.m[2] = make_map_img(enc, wg, D_, F_, 16, 13, 2); maps.m[3] = make_map_img(enc, wu, D_, F_, 16, 13, 2);
  maps.m[4] = make_map_img(enc, wd, F_, D_, 64, 10, 1);
  const CUtensorMap tmout = make_map(enc, d_out, D_, S_, 80, 64, CU_TENSOR_MAP_SWIZZLE_NONE);

  launch(k1_qkv, 132, 512, K1_SMEM, false, tmx, tmw, x, wqkv, wo);
  launch(k2_attn, 128, 512, K2_SMEM, true, maps, 0x007f007fu);
  launch(k3_proj<3, 4, true>, 128, 384, K3_SMEM, true, tmxr, (const uint4*)p_o, (const uint4*)p_wo);
  launch(k45_ffn, 128, 384, K4_SMEM, true, tmout);
}
```

```cpp
#include <cuda_runtime.h>
#include <cuda_bf16.h>
#include <cuda.h>
#include <stdint.h>

typedef __nv_bfloat16 bf16;

constexpr int S_ = 2048, D_ = 640, F_ = 1728;
constexpr int HEAD_IMG = 98304;
#define PMASK 0xDB6D
constexpr uint32_t POLY_MASK = PMASK;
constexpr float QSCALE = 0.22360679774997896f * 1.4426950408889634f;

__device__ __align__(1024) uint4 g_qkv[96 * HEAD_IMG / 16];
__device__ __align__(1024) uint4 g_o[S_ * D_ / 8];
__device__ __align__(1024) uint4 g_h[S_ * D_ / 8];
__device__ __align__(1024) uint4 g_hh[S_ * F_ / 8];
__device__ __align__(1024) uint4 g_wo[D_ * D_ / 8];
__device__ __align__(1024) uint4 g_wgu[2 * D_ * F_ / 8];
__device__ __align__(1024) uint4 g_wd[F_ * D_ / 8];
__device__ uint4 g_rowstat[S_];
__device__ uint4 g_cpart[10 * 12 * 80];
__device__ float g_nrm[64 * 128];
__device__ uint4 g_wm[D_];
__device__ float g_hmean[S_];
__device__ float g_hpart[8 * S_];
__device__ uint4 g_flag[2 * 16 * 2];
__device__ unsigned g_epoch;

#define STAMP(k, i)
__device__ __forceinline__ uint32_t smem_u32(const void* p) { return (uint32_t)__cvta_generic_to_shared(p); }
__device__ __forceinline__ void mbar_init(uint32_t a, uint32_t c) {
  asm volatile("mbarrier.init.shared::cta.b64 [%0], %1;" ::"r"(a), "r"(c) : "memory");
}
__device__ __forceinline__ void mbar_expect(uint32_t a, uint32_t bytes) {
  asm volatile("mbarrier.arrive.expect_tx.shared::cta.b64 _, [%0], %1;" ::"r"(a), "r"(bytes) : "memory");
}
__device__ __forceinline__ void mbar_arrive(uint32_t a) {
  asm volatile("mbarrier.arrive.shared::cta.b64 _, [%0];" ::"r"(a) : "memory");
}
__device__ __forceinline__ void mbar_arrive_cta(uint32_t a, uint32_t cta) {
  asm volatile("{\n.reg .b32 r;\nmapa.shared::cluster.u32 r, %0, %1;\n"
               "mbarrier.arrive.shared::cluster.b64 _, [r];\n}" ::"r"(a), "r"(cta) : "memory");
}
__device__ __forceinline__ bool mbar_try(uint32_t a, uint32_t ph) {
  uint32_t ok;
  asm volatile("{\n.reg .pred p;\nmbarrier.try_wait.parity.shared::cta.b64 p, [%1], %2;\nselp.u32 %0, 1, 0, p;\n}"
               : "=r"(ok) : "r"(a), "r"(ph) : "memory");
  return ok;
}
__device__ __noinline__ void wait_timeout() { __trap(); }
__device__ __forceinline__ void mbar_wait(uint32_t a, uint32_t ph) {
  if (mbar_try(a, ph)) return;
  uint32_t it = 0;
  while (!mbar_try(a, ph)) if (++it > (1u << 22)) wait_timeout();
}
__device__ __forceinline__ void tma2d(uint32_t dst, const CUtensorMap* m, int c0, int c1, uint32_t bar) {
  asm volatile("cp.async.bulk.tensor.2d.shared::cluster.global.mbarrier::complete_tx::bytes [%0], [%1, {%3, %4}], [%2];"
               ::"r"(dst), "l"(m), "r"(bar), "r"(c0), "r"(c1) : "memory");
}
__device__ __forceinline__ void tma2d_mc(uint32_t dst, const CUtensorMap* m, int c0, int c1, uint32_t bar) {
  asm volatile("cp.async.bulk.tensor.2d.shared::cluster.global.mbarrier::complete_tx::bytes.multicast::cluster "
               "[%0], [%1, {%3, %4}], [%2], %5;"
               ::"r"(dst), "l"(m), "r"(bar), "r"(c0), "r"(c1), "h"((uint16_t)3) : "memory");
}
__device__ __forceinline__ void bulk_ld(uint32_t dst, const void* src, uint32_t bytes, uint32_t bar) {
  asm volatile("cp.async.bulk.shared::cluster.global.mbarrier::complete_tx::bytes [%0], [%1], %2, [%3];"
               ::"r"(dst), "l"(src), "r"(bytes), "r"(bar) : "memory");
}
__device__ __forceinline__ void bulk_ld_mc(uint32_t dst, const void* src, uint32_t bytes, uint32_t bar) {
  asm volatile("cp.async.bulk.shared::cluster.global.mbarrier::complete_tx::bytes.multicast::cluster "
               "[%0], [%1], %2, [%3], %4;"
               ::"r"(dst), "l"(src), "r"(bytes), "r"(bar), "h"((uint16_t)3) : "memory");
}
__device__ __forceinline__ void cluster_arrive() { asm volatile("barrier.cluster.arrive.relaxed.aligned;" ::: "memory"); }
__device__ __forceinline__ void cluster_wait() { asm volatile("barrier.cluster.wait.aligned;" ::: "memory"); }
__device__ __forceinline__ void bulk_st(void* dst, uint32_t src, uint32_t bytes) {
  asm volatile("cp.async.bulk.global.shared::cta.bulk_group [%0], [%1], %2;" ::"l"(dst), "r"(src), "r"(bytes) : "memory");
}
__device__ __forceinline__ void tma2d_st(const CUtensorMap* m, int c0, int c1, uint32_t src) {
  asm volatile("cp.async.bulk.tensor.2d.global.shared::cta.bulk_group [%0, {%2, %3}], [%1];"
               ::"l"(m), "r"(src), "r"(c0), "r"(c1) : "memory");
}
__device__ __forceinline__ void bulk_commit_wait() {
  asm volatile("cp.async.bulk.commit_group;\ncp.async.bulk.wait_group.read 0;" ::: "memory");
}
__device__ __forceinline__ uint32_t mapa(uint32_t a, uint32_t cta) {
  uint32_t r;
  asm("mapa.shared::cluster.u32 %0, %1, %2;" : "=r"(r) : "r"(a), "r"(cta));
  return r;
}
__device__ __forceinline__ void st_async4(uint32_t dst, float a, float b, float c, float d, uint32_t bar) {
  asm volatile("st.async.shared::cluster.mbarrier::complete_tx::bytes.v4.f32 [%0], {%1, %2, %3, %4}, [%5];"
               ::"r"(dst), "f"(a), "f"(b), "f"(c), "f"(d), "r"(bar) : "memory");
}
__device__ __forceinline__ void fence_async() { asm volatile("fence.proxy.async.shared::cta;" ::: "memory"); }
__device__ __forceinline__ void prefetch_map(const CUtensorMap* m) {
  asm volatile("prefetch.tensormap [%0];" ::"l"(m) : "memory");
}
__device__ __forceinline__ bool elect_one() {
  uint32_t p;
  asm volatile("{\n.reg .pred q;\nelect.sync _|q, 0xffffffff;\nselp.u32 %0, 1, 0, q;\n}" : "=r"(p));
  return p;
}
__device__ __forceinline__ void pdl_wait() { asm volatile("griddepcontrol.wait;" ::: "memory"); }
__device__ __forceinline__ void pdl_trigger() { asm volatile("griddepcontrol.launch_dependents;" ::: "memory"); }
__device__ __forceinline__ void bar_sync(int id, int n) { asm volatile("bar.sync %0, %1;" ::"r"(id), "r"(n) : "memory"); }
__device__ __forceinline__ void bar_arrive(int id, int n) { asm volatile("bar.arrive %0, %1;" ::"r"(id), "r"(n) : "memory"); }
#define WG_FENCE() asm volatile("wgmma.fence.sync.aligned;" ::: "memory")
#define WG_COMMIT() asm volatile("wgmma.commit_group.sync.aligned;" ::: "memory")
#define WG_WAIT(n) asm volatile("wgmma.wait_group.sync.aligned %0;" ::"n"(n) : "memory")
__device__ __forceinline__ uint64_t mkdesc(uint32_t addr, uint32_t lbo, uint32_t sbo, uint32_t sw) {
  return (uint64_t)((addr & 0x3FFFF) >> 4) | ((uint64_t)(lbo >> 4) << 16) | ((uint64_t)(sbo >> 4) << 32) |
         ((uint64_t)sw << 62);
}
template <int N> __device__ __forceinline__ void fence_regs(float (&r)[N]) {
#pragma unroll
  for (int i = 0; i < N; i++) asm volatile("" : "+f"(r[i])::"memory");
}
__device__ __forceinline__ uint32_t pack_bf16(float lo, float hi) {
  uint32_t r;
  asm("cvt.rn.bf16x2.f32 %0, %1, %2;" : "=r"(r) : "f"(hi), "f"(lo));
  return r;
}
__device__ __forceinline__ float bf_lo(uint32_t v) { return __uint_as_float(v << 16); }
__device__ __forceinline__ float bf_hi(uint32_t v) { return __uint_as_float(v & 0xffff0000u); }
__device__ __forceinline__ float ex2(float x) {
  float y;
  asm("ex2.approx.ftz.f32 %0, %1;" : "=f"(y) : "f"(x));
  return y;
}
__device__ __forceinline__ uint4 ldg_nc(const void* p) {
  uint4 v;
  asm volatile("ld.global.nc.L1::no_allocate.v4.u32 {%0, %1, %2, %3}, [%4];"
               : "=r"(v.x), "=r"(v.y), "=r"(v.z), "=r"(v.w) : "l"(p));
  return v;
}

__device__ __forceinline__ uint4 ld_relaxed(const uint4* p) {
  uint64_t a, b;
  asm volatile("ld.relaxed.gpu.global.v2.u64 {%0, %1}, [%2];" : "=l"(a), "=l"(b) : "l"(p) : "memory");
  return make_uint4((uint32_t)a, (uint32_t)(a >> 32), (uint32_t)b, (uint32_t)(b >> 32));
}
__device__ __forceinline__ void st_relaxed(uint4* p, float x, float y, uint32_t tag) {
  const uint64_t a = ((uint64_t)tag << 32) | __float_as_uint(x), b = ((uint64_t)tag << 32) | __float_as_uint(y);
  asm volatile("st.relaxed.gpu.global.v2.u64 [%0], {%1, %2};" ::"l"(p), "l"(a), "l"(b) : "memory");
}
__device__ __forceinline__ void tma4d(uint32_t dst, const CUtensorMap* m, int c2, int c3, uint32_t bar) {
  asm volatile("cp.async.bulk.tensor.4d.shared::cluster.global.mbarrier::complete_tx::bytes [%0], [%1, {%3, %3, %4, %5}], [%2];"
               ::"r"(dst), "l"(m), "r"(bar), "r"(0), "r"(c2), "r"(c3) : "memory");
}
#define ACC8(a, v) do { a[0] += bf_lo(v.x); a[1] += bf_hi(v.x); a[2] += bf_lo(v.y); a[3] += bf_hi(v.y); \
                        a[4] += bf_lo(v.z); a[5] += bf_hi(v.z); a[6] += bf_lo(v.w); a[7] += bf_hi(v.w); } while (0)

__device__ __forceinline__ void wgmma_ss_n224(float (&d)[112], uint64_t da, uint64_t db, int sd) {
  asm volatile("{\n.reg .pred p;\nsetp.ne.b32 p, %114, 0;\n"
      "wgmma.mma_async.sync.aligned.m64n224k16.f32.bf16.bf16 {"
      "%0, %1, %2, %3, %4, %5, %6, %7, %8, %9, %10, %11, %12, %13, %14, %15, "
      "%16, %17, %18, %19, %20, %21, %22, %23, %24, %25, %26, %27, %28, %29, %30, %31, "
      "%32, %33, %34, %35, %36, %37, %38, %39, %40, %41, %42, %43, %44, %45, %46, %47, "
      "%48, %49, %50, %51, %52, %53, %54, %55, %56, %57, %58, %59, %60, %61, %62, %63, "
      "%64, %65, %66, %67, %68, %69, %70, %71, %72, %73, %74, %75, %76, %77, %78, %79, "
      "%80, %81, %82, %83, %84, %85, %86, %87, %88, %89, %90, %91, %92, %93, %94, %95, "
      "%96, %97, %98, %99, %100, %101, %102, %103, %104, %105, %106, %107, %108, %109, %110, %111"
      "}, %112, %113, p, 1, 1, 0, 1;\n}\n"
    : "+f"(d[0]), "+f"(d[1]), "+f"(d[2]), "+f"(d[3]), "+f"(d[4]), "+f"(d[5]), "+f"(d[6]), "+f"(d[7]),
      "+f"(d[8]), "+f"(d[9]), "+f"(d[10]), "+f"(d[11]), "+f"(d[12]), "+f"(d[13]), "+f"(d[14]), "+f"(d[15]),
      "+f"(d[16]), "+f"(d[17]), "+f"(d[18]), "+f"(d[19]), "+f"(d[20]), "+f"(d[21]), "+f"(d[22]), "+f"(d[23]),
      "+f"(d[24]), "+f"(d[25]), "+f"(d[26]), "+f"(d[27]), "+f"(d[28]), "+f"(d[29]), "+f"(d[30]), "+f"(d[31]),
      "+f"(d[32]), "+f"(d[33]), "+f"(d[34]), "+f"(d[35]), "+f"(d[36]), "+f"(d[37]), "+f"(d[38]), "+f"(d[39]),
      "+f"(d[40]), "+f"(d[41]), "+f"(d[42]), "+f"(d[43]), "+f"(d[44]), "+f"(d[45]), "+f"(d[46]), "+f"(d[47]),
      "+f"(d[48]), "+f"(d[49]), "+f"(d[50]), "+f"(d[51]), "+f"(d[52]), "+f"(d[53]), "+f"(d[54]), "+f"(d[55]),
      "+f"(d[56]), "+f"(d[57]), "+f"(d[58]), "+f"(d[59]), "+f"(d[60]), "+f"(d[61]), "+f"(d[62]), "+f"(d[63]),
      "+f"(d[64]), "+f"(d[65]), "+f"(d[66]), "+f"(d[67]), "+f"(d[68]), "+f"(d[69]), "+f"(d[70]), "+f"(d[71]),
      "+f"(d[72]), "+f"(d[73]), "+f"(d[74]), "+f"(d[75]), "+f"(d[76]), "+f"(d[77]), "+f"(d[78]), "+f"(d[79]),
      "+f"(d[80]), "+f"(d[81]), "+f"(d[82]), "+f"(d[83]), "+f"(d[84]), "+f"(d[85]), "+f"(d[86]), "+f"(d[87]),
      "+f"(d[88]), "+f"(d[89]), "+f"(d[90]), "+f"(d[91]), "+f"(d[92]), "+f"(d[93]), "+f"(d[94]), "+f"(d[95]),
      "+f"(d[96]), "+f"(d[97]), "+f"(d[98]), "+f"(d[99]), "+f"(d[100]), "+f"(d[101]), "+f"(d[102]), "+f"(d[103]),
      "+f"(d[104]), "+f"(d[105]), "+f"(d[106]), "+f"(d[107]), "+f"(d[108]), "+f"(d[109]), "+f"(d[110]), "+f"(d[111])
    : "l"(da), "l"(db), "r"(sd));
}
__device__ __forceinline__ void wgmma_ss_n208(float (&d)[104], uint64_t da, uint64_t db, int sd) {
  asm volatile("{\n.reg .pred p;\nsetp.ne.b32 p, %106, 0;\n"
      "wgmma.mma_async.sync.aligned.m64n208k16.f32.bf16.bf16 {"
      "%0, %1, %2, %3, %4, %5, %6, %7, %8, %9, %10, %11, %12, %13, %14, %15, "
      "%16, %17, %18, %19, %20, %21, %22, %23, %24, %25, %26, %27, %28, %29, %30, %31, "
      "%32, %33, %34, %35, %36, %37, %38, %39, %40, %41, %42, %43, %44, %45, %46, %47, "
      "%48, %49, %50, %51, %52, %53, %54, %55, %56, %57, %58, %59, %60, %61, %62, %63, "
      "%64, %65, %66, %67, %68, %69, %70, %71, %72, %73, %74, %75, %76, %77, %78, %79, "
      "%80, %81, %82, %83, %84, %85, %86, %87, %88, %89, %90, %91, %92, %93, %94, %95, "
      "%96, %97, %98, %99, %100, %101, %102, %103"
      "}, %104, %105, p, 1, 1, 0, 1;\n}\n"
    : "+f"(d[0]), "+f"(d[1]), "+f"(d[2]), "+f"(d[3]), "+f"(d[4]), "+f"(d[5]), "+f"(d[6]), "+f"(d[7]),
      "+f"(d[8]), "+f"(d[9]), "+f"(d[10]), "+f"(d[11]), "+f"(d[12]), "+f"(d[13]), "+f"(d[14]), "+f"(d[15]),
      "+f"(d[16]), "+f"(d[17]), "+f"(d[18]), "+f"(d[19]), "+f"(d[20]), "+f"(d[21]), "+f"(d[22]), "+f"(d[23]),
      "+f"(d[24]), "+f"(d[25]), "+f"(d[26]), "+f"(d[27]), "+f"(d[28]), "+f"(d[29]), "+f"(d[30]), "+f"(d[31]),
      "+f"(d[32]), "+f"(d[33]), "+f"(d[34]), "+f"(d[35]), "+f"(d[36]), "+f"(d[37]), "+f"(d[38]), "+f"(d[39]),
      "+f"(d[40]), "+f"(d[41]), "+f"(d[42]), "+f"(d[43]), "+f"(d[44]), "+f"(d[45]), "+f"(d[46]), "+f"(d[47]),
      "+f"(d[48]), "+f"(d[49]), "+f"(d[50]), "+f"(d[51]), "+f"(d[52]), "+f"(d[53]), "+f"(d[54]), "+f"(d[55]),
      "+f"(d[56]), "+f"(d[57]), "+f"(d[58]), "+f"(d[59]), "+f"(d[60]), "+f"(d[61]), "+f"(d[62]), "+f"(d[63]),
      "+f"(d[64]), "+f"(d[65]), "+f"(d[66]), "+f"(d[67]), "+f"(d[68]), "+f"(d[69]), "+f"(d[70]), "+f"(d[71]),
      "+f"(d[72]), "+f"(d[73]), "+f"(d[74]), "+f"(d[75]), "+f"(d[76]), "+f"(d[77]), "+f"(d[78]), "+f"(d[79]),
      "+f"(d[80]), "+f"(d[81]), "+f"(d[82]), "+f"(d[83]), "+f"(d[84]), "+f"(d[85]), "+f"(d[86]), "+f"(d[87]),
      "+f"(d[88]), "+f"(d[89]), "+f"(d[90]), "+f"(d[91]), "+f"(d[92]), "+f"(d[93]), "+f"(d[94]), "+f"(d[95]),
      "+f"(d[96]), "+f"(d[97]), "+f"(d[98]), "+f"(d[99]), "+f"(d[100]), "+f"(d[101]), "+f"(d[102]), "+f"(d[103])
    : "l"(da), "l"(db), "r"(sd));
}
__device__ __forceinline__ void wgmma_ss_n168(float (&d)[84], uint64_t da, uint64_t db, int sd) {
  asm volatile("{\n.reg .pred p;\nsetp.ne.b32 p, %86, 0;\n"
      "wgmma.mma_async.sync.aligned.m64n168k16.f32.bf16.bf16 {"
      "%0, %1, %2, %3, %4, %5, %6, %7, %8, %9, %10, %11, %12, %13, %14, %15, "
      "%16, %17, %18, %19, %20, %21, %22, %23, %24, %25, %26, %27, %28, %29, %30, %31, "
      "%32, %33, %34, %35, %36, %37, %38, %39, %40, %41, %42, %43, %44, %45, %46, %47, "
      "%48, %49, %50, %51, %52, %53, %54, %55, %56, %57, %58, %59, %60, %61, %62, %63, "
      "%64, %65, %66, %67, %68, %69, %70, %71, %72, %73, %74, %75, %76, %77, %78, %79, "
      "%80, %81, %82, %83"
      "}, %84, %85, p, 1, 1, 0, 1;\n}\n"
    : "+f"(d[0]), "+f"(d[1]), "+f"(d[2]), "+f"(d[3]), "+f"(d[4]), "+f"(d[5]), "+f"(d[6]), "+f"(d[7]),
      "+f"(d[8]), "+f"(d[9]), "+f"(d[10]), "+f"(d[11]), "+f"(d[12]), "+f"(d[13]), "+f"(d[14]), "+f"(d[15]),
      "+f"(d[16]), "+f"(d[17]), "+f"(d[18]), "+f"(d[19]), "+f"(d[20]), "+f"(d[21]), "+f"(d[22]), "+f"(d[23]),
      "+f"(d[24]), "+f"(d[25]), "+f"(d[26]), "+f"(d[27]), "+f"(d[28]), "+f"(d[29]), "+f"(d[30]), "+f"(d[31]),
      "+f"(d[32]), "+f"(d[33]), "+f"(d[34]), "+f"(d[35]), "+f"(d[36]), "+f"(d[37]), "+f"(d[38]), "+f"(d[39]),
      "+f"(d[40]), "+f"(d[41]), "+f"(d[42]), "+f"(d[43]), "+f"(d[44]), "+f"(d[45]), "+f"(d[46]), "+f"(d[47]),
      "+f"(d[48]), "+f"(d[49]), "+f"(d[50]), "+f"(d[51]), "+f"(d[52]), "+f"(d[53]), "+f"(d[54]), "+f"(d[55]),
      "+f"(d[56]), "+f"(d[57]), "+f"(d[58]), "+f"(d[59]), "+f"(d[60]), "+f"(d[61]), "+f"(d[62]), "+f"(d[63]),
      "+f"(d[64]), "+f"(d[65]), "+f"(d[66]), "+f"(d[67]), "+f"(d[68]), "+f"(d[69]), "+f"(d[70]), "+f"(d[71]),
      "+f"(d[72]), "+f"(d[73]), "+f"(d[74]), "+f"(d[75]), "+f"(d[76]), "+f"(d[77]), "+f"(d[78]), "+f"(d[79]),
      "+f"(d[80]), "+f"(d[81]), "+f"(d[82]), "+f"(d[83])
    : "l"(da), "l"(db), "r"(sd));
}
__device__ __forceinline__ void wgmma_ss_n160(float (&d)[80], uint64_t da, uint64_t db, int sd) {
  asm volatile("{\n.reg .pred p;\nsetp.ne.b32 p, %82, 0;\n"
      "wgmma.mma_async.sync.aligned.m64n160k16.f32.bf16.bf16 {"
      "%0, %1, %2, %3, %4, %5, %6, %7, %8, %9, %10, %11, %12, %13, %14, %15, "
      "%16, %17, %18, %19, %20, %21, %22, %23, %24, %25, %26, %27, %28, %29, %30, %31, "
      "%32, %33, %34, %35, %36, %37, %38, %39, %40, %41, %42, %43, %44, %45, %46, %47, "
      "%48, %49, %50, %51, %52, %53, %54, %55, %56, %57, %58, %59, %60, %61, %62, %63, "
      "%64, %65, %66, %67, %68, %69, %70, %71, %72, %73, %74, %75, %76, %77, %78, %79"
      "}, %80, %81, p, 1, 1, 0, 1;\n}\n"
    : "+f"(d[0]), "+f"(d[1]), "+f"(d[2]), "+f"(d[3]), "+f"(d[4]), "+f"(d[5]), "+f"(d[6]), "+f"(d[7]),
      "+f"(d[8]), "+f"(d[9]), "+f"(d[10]), "+f"(d[11]), "+f"(d[12]), "+f"(d[13]), "+f"(d[14]), "+f"(d[15]),
      "+f"(d[16]), "+f"(d[17]), "+f"(d[18]), "+f"(d[19]), "+f"(d[20]), "+f"(d[21]), "+f"(d[22]), "+f"(d[23]),
      "+f"(d[24]), "+f"(d[25]), "+f"(d[26]), "+f"(d[27]), "+f"(d[28]), "+f"(d[29]), "+f"(d[30]), "+f"(d[31]),
      "+f"(d[32]), "+f"(d[33]), "+f"(d[34]), "+f"(d[35]), "+f"(d[36]), "+f"(d[37]), "+f"(d[38]), "+f"(d[39]),
      "+f"(d[40]), "+f"(d[41]), "+f"(d[42]), "+f"(d[43]), "+f"(d[44]), "+f"(d[45]), "+f"(d[46]), "+f"(d[47]),
      "+f"(d[48]), "+f"(d[49]), "+f"(d[50]), "+f"(d[51]), "+f"(d[52]), "+f"(d[53]), "+f"(d[54]), "+f"(d[55]),
      "+f"(d[56]), "+f"(d[57]), "+f"(d[58]), "+f"(d[59]), "+f"(d[60]), "+f"(d[61]), "+f"(d[62]), "+f"(d[63]),
      "+f"(d[64]), "+f"(d[65]), "+f"(d[66]), "+f"(d[67]), "+f"(d[68]), "+f"(d[69]), "+f"(d[70]), "+f"(d[71]),
      "+f"(d[72]), "+f"(d[73]), "+f"(d[74]), "+f"(d[75]), "+f"(d[76]), "+f"(d[77]), "+f"(d[78]), "+f"(d[79])
    : "l"(da), "l"(db), "r"(sd));
}
__device__ __forceinline__ void wgmma_ss_n88(float (&d)[44], uint64_t da, uint64_t db, int sd) {
  asm volatile("{\n.reg .pred p;\nsetp.ne.b32 p, %46, 0;\n"
      "wgmma.mma_async.sync.aligned.m64n88k16.f32.bf16.bf16 {"
      "%0, %1, %2, %3, %4, %5, %6, %7, %8, %9, %10, %11, %12, %13, %14, %15, "
      "%16, %17, %18, %19, %20, %21, %22, %23, %24, %25, %26, %27, %28, %29, %30, %31, "
      "%32, %33, %34, %35, %36, %37, %38, %39, %40, %41, %42, %43"
      "}, %44, %45, p, 1, 1, 0, 1;\n}\n"
    : "+f"(d[0]), "+f"(d[1]), "+f"(d[2]), "+f"(d[3]), "+f"(d[4]), "+f"(d[5]), "+f"(d[6]), "+f"(d[7]),
      "+f"(d[8]), "+f"(d[9]), "+f"(d[10]), "+f"(d[11]), "+f"(d[12]), "+f"(d[13]), "+f"(d[14]), "+f"(d[15]),
      "+f"(d[16]), "+f"(d[17]), "+f"(d[18]), "+f"(d[19]), "+f"(d[20]), "+f"(d[21]), "+f"(d[22]), "+f"(d[23]),
      "+f"(d[24]), "+f"(d[25]), "+f"(d[26]), "+f"(d[27]), "+f"(d[28]), "+f"(d[29]), "+f"(d[30]), "+f"(d[31]),
      "+f"(d[32]), "+f"(d[33]), "+f"(d[34]), "+f"(d[35]), "+f"(d[36]), "+f"(d[37]), "+f"(d[38]), "+f"(d[39]),
      "+f"(d[40]), "+f"(d[41]), "+f"(d[42]), "+f"(d[43])
    : "l"(da), "l"(db), "r"(sd));
}
__device__ __forceinline__ void wgmma_ss_n80(float (&d)[40], uint64_t da, uint64_t db, int sd) {
  asm volatile("{\n.reg .pred p;\nsetp.ne.b32 p, %42, 0;\n"
      "wgmma.mma_async.sync.aligned.m64n80k16.f32.bf16.bf16 {"
      "%0, %1, %2, %3, %4, %5, %6, %7, %8, %9, %10, %11, %12, %13, %14, %15, "
      "%16, %17, %18, %19, %20, %21, %22, %23, %24, %25, %26, %27, %28, %29, %30, %31, "
      "%32, %33, %34, %35, %36, %37, %38, %39"
      "}, %40, %41, p, 1, 1, 0, 1;\n}\n"
    : "+f"(d[0]), "+f"(d[1]), "+f"(d[2]), "+f"(d[3]), "+f"(d[4]), "+f"(d[5]), "+f"(d[6]), "+f"(d[7]),
      "+f"(d[8]), "+f"(d[9]), "+f"(d[10]), "+f"(d[11]), "+f"(d[12]), "+f"(d[13]), "+f"(d[14]), "+f"(d[15]),
      "+f"(d[16]), "+f"(d[17]), "+f"(d[18]), "+f"(d[19]), "+f"(d[20]), "+f"(d[21]), "+f"(d[22]), "+f"(d[23]),
      "+f"(d[24]), "+f"(d[25]), "+f"(d[26]), "+f"(d[27]), "+f"(d[28]), "+f"(d[29]), "+f"(d[30]), "+f"(d[31]),
      "+f"(d[32]), "+f"(d[33]), "+f"(d[34]), "+f"(d[35]), "+f"(d[36]), "+f"(d[37]), "+f"(d[38]), "+f"(d[39])
    : "l"(da), "l"(db), "r"(sd));
}
__device__ __forceinline__ void wgmma_rs_n128(float (&d)[64], uint32_t a0, uint32_t a1, uint32_t a2, uint32_t a3,
                                  uint64_t db, int sd) {
  asm volatile("{\n.reg .pred p;\nsetp.ne.b32 p, %69, 0;\n"
      "wgmma.mma_async.sync.aligned.m64n128k16.f32.bf16.bf16 {"
      "%0, %1, %2, %3, %4, %5, %6, %7, %8, %9, %10, %11, %12, %13, %14, %15, "
      "%16, %17, %18, %19, %20, %21, %22, %23, %24, %25, %26, %27, %28, %29, %30, %31, "
      "%32, %33, %34, %35, %36, %37, %38, %39, %40, %41, %42, %43, %44, %45, %46, %47, "
      "%48, %49, %50, %51, %52, %53, %54, %55, %56, %57, %58, %59, %60, %61, %62, %63"
      "}, {%64, %65, %66, %67}, %68, p, 1, 1, 0;\n}\n"
    : "+f"(d[0]), "+f"(d[1]), "+f"(d[2]), "+f"(d[3]), "+f"(d[4]), "+f"(d[5]), "+f"(d[6]), "+f"(d[7]),
      "+f"(d[8]), "+f"(d[9]), "+f"(d[10]), "+f"(d[11]), "+f"(d[12]), "+f"(d[13]), "+f"(d[14]), "+f"(d[15]),
      "+f"(d[16]), "+f"(d[17]), "+f"(d[18]), "+f"(d[19]), "+f"(d[20]), "+f"(d[21]), "+f"(d[22]), "+f"(d[23]),
      "+f"(d[24]), "+f"(d[25]), "+f"(d[26]), "+f"(d[27]), "+f"(d[28]), "+f"(d[29]), "+f"(d[30]), "+f"(d[31]),
      "+f"(d[32]), "+f"(d[33]), "+f"(d[34]), "+f"(d[35]), "+f"(d[36]), "+f"(d[37]), "+f"(d[38]), "+f"(d[39]),
      "+f"(d[40]), "+f"(d[41]), "+f"(d[42]), "+f"(d[43]), "+f"(d[44]), "+f"(d[45]), "+f"(d[46]), "+f"(d[47]),
      "+f"(d[48]), "+f"(d[49]), "+f"(d[50]), "+f"(d[51]), "+f"(d[52]), "+f"(d[53]), "+f"(d[54]), "+f"(d[55]),
      "+f"(d[56]), "+f"(d[57]), "+f"(d[58]), "+f"(d[59]), "+f"(d[60]), "+f"(d[61]), "+f"(d[62]), "+f"(d[63])
    : "r"(a0), "r"(a1), "r"(a2), "r"(a3), "l"(db), "r"(sd));
}
__device__ __forceinline__ void wgmma_rs_n24(float (&d)[12], uint32_t a0, uint32_t a1, uint32_t a2, uint32_t a3,
                                  uint64_t db, int sd) {
  asm volatile("{\n.reg .pred p;\nsetp.ne.b32 p, %17, 0;\n"
      "wgmma.mma_async.sync.aligned.m64n24k16.f32.bf16.bf16 {"
      "%0, %1, %2, %3, %4, %5, %6, %7, %8, %9, %10, %11"
      "}, {%12, %13, %14, %15}, %16, p, 1, 1, 1;\n}\n"
    : "+f"(d[0]), "+f"(d[1]), "+f"(d[2]), "+f"(d[3]), "+f"(d[4]), "+f"(d[5]), "+f"(d[6]), "+f"(d[7]),
      "+f"(d[8]), "+f"(d[9]), "+f"(d[10]), "+f"(d[11])
    : "r"(a0), "r"(a1), "r"(a2), "r"(a3), "l"(db), "r"(sd));
}

#define KST 4
#define K1S 4
constexpr int K1_ST = K1S, K1_STAGE = 45056;
constexpr int K1_SMEM = K1_ST * K1_STAGE + 640   + 1536   + 2560   + 128;

__device__ __forceinline__ float2 row_stats(uint4 v0, uint4 v1, uint4 v2) {
  const uint32_t wd[12] = {v0.x, v0.y, v0.z, v0.w, v1.x, v1.y, v1.z, v1.w, v2.x, v2.y, v2.z, v2.w};
  float sx = 0.f, sq = 0.f;
#pragma unroll
  for (int e = 0; e < 12; e++) {
    const float lo = bf_lo(wd[e]), hi = bf_hi(wd[e]);
    sx += lo + hi; sq = fmaf(lo, lo, fmaf(hi, hi, sq));
  }
#pragma unroll
  for (int o = 16; o; o >>= 1) { sx += __shfl_xor_sync(~0u, sx, o); sq += __shfl_xor_sync(~0u, sq, o); }
  const float mean = sx * (1.f / D_);
  return make_float2(rsqrtf(fmaxf(sq * (1.f / D_) - mean * mean, 0.f) + 1e-5f), mean);
}

__global__ void __cluster_dims__(2, 1, 1) __launch_bounds__(512, 1)
k1_qkv(const __grid_constant__ CUtensorMap tmx, const __grid_constant__ CUtensorMap tmw,
       const bf16* __restrict__ x, const bf16* __restrict__ w, const bf16* __restrict__ wo) {
  extern __shared__ __align__(1024) uint8_t sm[];
  float* cs = (float*)(sm + K1_ST * K1_STAGE);
  float2* rowab = (float2*)(sm + K1_ST * K1_STAGE + 640);
  float* red = (float*)(sm + K1_ST * K1_STAGE + 2176);
  const uint32_t sbase = smem_u32(sm);
  const uint32_t fullb = sbase + K1_ST * K1_STAGE + 4736, emptyb = fullb + 8 * K1_ST;
  const int tid = threadIdx.x, lane = tid & 31;
  const int warp = __shfl_sync(~0u, tid >> 5, 0);
  const int rank = blockIdx.x & 1, cl = blockIdx.x >> 1;
  const int m = cl / 6, n = (cl - m * 6) * 2 + rank;
  if (tid == 0) STAMP(0, 0);

  if (warp == 12) {
    if (lane == 0) {
      prefetch_map(&tmx); prefetch_map(&tmw);
      for (int i = 0; i < K1_ST; i++) { mbar_init(fullb + 8 * i, 1); mbar_init(emptyb + 8 * i, 6); }
      asm volatile("fence.mbarrier_init.release.cluster;" ::: "memory");
    }
    __syncwarp();
    cluster_arrive();
    bar_arrive(4, 512);
    if (elect_one()) {
#pragma unroll
      for (int kt = 0; kt < K1_ST; kt++) mbar_expect(fullb + 8 * kt, K1_STAGE);
#pragma unroll
      for (int j = 0; j < 5; j++) tma2d(sbase + 24576 + j * 4096, &tmw, n * 160 + j * 32, 0, fullb);
    }
    cluster_wait();
#pragma unroll
    for (int kt = 0; kt < 10; kt++) {
      const int s = kt % K1_ST;
      const uint32_t sa = sbase + s * K1_STAGE;
      if (kt >= K1_ST) mbar_wait(emptyb + 8 * s, ((kt / K1_ST) - 1) & 1);
      if (elect_one()) {
        if (kt >= K1_ST) mbar_expect(fullb + 8 * s, K1_STAGE);
        tma2d_mc(sa + rank * 12288, &tmx, kt * 64, m * 192 + rank * 96, fullb + 8 * s);
        if (kt > 0) {
#pragma unroll
          for (int j = 0; j < 5; j++) tma2d(sa + 24576 + j * 4096, &tmw, n * 160 + j * 32, kt * 64, fullb + 8 * s);
        }
      }
      if (kt == K1_ST - 1) pdl_trigger();
    }
    __syncwarp();
    cluster_arrive();
  } else if (warp > 12) {
    cluster_arrive();
    const int t96 = tid - 416;
    const uint32_t tag = __ldcg(&g_epoch) + 1;
    bar_sync(4, 512);
    mbar_wait(fullb, 0);
    if (m < 10) {
      const int ck = t96 % 20, rg = min(t96 / 20, 3);
      uint4 wv[16];
#pragma unroll
      for (int i = 0; i < 16; i++) wv[i] = ldg_nc(w + (size_t)(m * 64 + rg * 16 + i) * 1920 + n * 160 + ck * 8);
      float acc8[8];
#pragma unroll
      for (int i = 0; i < 8; i++) acc8[i] = 0.f;
#pragma unroll
      for (int i = 0; i < 16; i++) ACC8(acc8, wv[i]);
      *(float4*)&red[rg * 160 + ck * 8] = make_float4(acc8[0], acc8[1], acc8[2], acc8[3]);
      *(float4*)&red[rg * 160 + ck * 8 + 4] = make_float4(acc8[4], acc8[5], acc8[6], acc8[7]);
      bar_sync(1, 96);
      if (t96 < 80) {
        const float2 p0 = *(const float2*)&red[t96 * 2], p1 = *(const float2*)&red[160 + t96 * 2];
        const float2 p2 = *(const float2*)&red[320 + t96 * 2], p3 = *(const float2*)&red[480 + t96 * 2];
        st_relaxed(&g_cpart[(m * 12 + n) * 80 + t96], (p0.x + p1.x) + (p2.x + p3.x), (p0.y + p1.y) + (p2.y + p3.y), tag);
      }
    }
    if (tid == 416) STAMP(5, 7);
    bool ok = false;
    for (int it = 0; it < 64 && !ok; it++) {
      uint4 p[10], st[2];
#pragma unroll
      for (int k = 0; k < 10; k++) p[k] = ld_relaxed(&g_cpart[(k * 12 + n) * 80 + min(t96, 79)]);
#pragma unroll
      for (int k = 0; k < 2; k++) st[k] = ld_relaxed(&g_rowstat[min(m * 192 + k * 96 + t96, S_ - 1)]);
      ok = true;
      float s0 = 0.f, s1 = 0.f;
#pragma unroll
      for (int k = 0; k < 10; k++) {
        ok = ok && p[k].y == tag && p[k].w == tag;
        s0 += __uint_as_float(p[k].x); s1 += __uint_as_float(p[k].z);
      }
      if (t96 < 80) *(float2*)&cs[t96 * 2] = make_float2(s0, s1);
#pragma unroll
      for (int k = 0; k < 2; k++) {
        ok = ok && st[k].y == tag && st[k].w == tag;
        rowab[k * 96 + t96] = make_float2(__uint_as_float(st[k].x), -__uint_as_float(st[k].x) * __uint_as_float(st[k].z));
      }
      ok = __all_sync(~0u, ok);
      if (!ok) __nanosleep(300);
    }
    if (!ok) {
      const int c2 = min(t96, 79);
      float s0 = 0.f, s1 = 0.f;
#pragma unroll 1
      for (int k = 0; k < D_; k++) {
        const uint32_t v = *(const uint32_t*)(w + (size_t)k * 1920 + n * 160 + c2 * 2);
        s0 += bf_lo(v); s1 += bf_hi(v);
      }
      if (t96 < 80) *(float2*)&cs[t96 * 2] = make_float2(s0, s1);
#pragma unroll 1
      for (int i = 0; i < 64; i++) {
        const int r = (i >> 5) * 96 + (t96 & ~31) + (i & 31);
        const bf16* xr = x + (size_t)min(m * 192 + r, S_ - 1) * D_ + lane * 8;
        const float2 st = row_stats(ldg_nc(xr), ldg_nc(xr + 256), lane < 16 ? ldg_nc(xr + 512) : make_uint4(0u, 0u, 0u, 0u));
        if (lane == 0) rowab[r] = make_float2(st.x, -st.x * st.y);
      }
    }
    __syncwarp();
    bar_arrive(2, 96 + 384);
    bar_sync(1, 96);
    if (tid == 416) STAMP(0, 5);
    if (blockIdx.x < 128) {
      uint4 v[5];
      const int ck = min(t96, 79), nt = ck / 10;
#pragma unroll
      for (int i = 0; i < 5; i++) {
        const int k = blockIdx.x * 5 + i, pr = k / 40, r = k - pr * 40;
        v[i] = ldg_nc(wo + (size_t)(pr * 40 + (r < 16 ? r : (r < 32 ? r + 4 : (r < 36 ? r - 16 : r)))) * D_ + ck * 8);
      }
#pragma unroll
      for (int i = 0; i < 5; i++) {
        const int k = blockIdx.x * 5 + i;
        g_wo[((nt * 10 + (k >> 6)) * 10 + ck - nt * 10) * 64 + (k & 63)] = v[i];
        float t = ((bf_lo(v[i].x) + bf_hi(v[i].x)) + (bf_lo(v[i].y) + bf_hi(v[i].y))) +
                  ((bf_lo(v[i].z) + bf_hi(v[i].z)) + (bf_lo(v[i].w) + bf_hi(v[i].w)));
        if (t96 >= 80) t = 0.f;
#pragma unroll
        for (int o = 16; o; o >>= 1) t += __shfl_xor_sync(~0u, t, o);
        if (lane == 0) red[(t96 >> 5) * 8 + i] = t;
      }
      bar_sync(1, 96);
      if (t96 < 5) {
        const float mu = (red[t96] + red[8 + t96] + red[16 + t96]) * (1.f / D_);
        const float hi = bf_lo(pack_bf16(mu, 0.f));
        g_wm[blockIdx.x * 5 + t96] = make_uint4(pack_bf16(hi, mu - hi), 0u, 0u, 0u);
      }
    }
    if (tid == 416) STAMP(0, 7);
    __syncwarp();
    cluster_wait();
    cluster_arrive();
  } else {
    cluster_arrive();
    float acc[80];
    const uint64_t da0 = mkdesc(sbase + (warp >> 2) * 8192, 16, 1024, 1);
    const uint64_t db0 = mkdesc(sbase + 24576, 4096, 512, 2);
    const uint32_t tag = __ldcg(&g_epoch) + 1;
    const int srow = m * 192 + n * 16 + warp * 2;
    const bool dostat = warp < 8 && srow < S_;
    uint4 xv[2][3];
    bar_sync(4, 512);
    cluster_wait();
#pragma unroll
    for (int kt = 0; kt < 10; kt++) {
      const int s = kt % K1_ST;
      mbar_wait(fullb + 8 * s, (kt / K1_ST) & 1);
      if (kt == 0 && tid == 0) STAMP(0, 1);
      if (kt == 2 && tid == 0) STAMP(5, 0);
      if (kt == 4 && tid == 0) STAMP(5, 1);
      if (kt == 7 && tid == 0) STAMP(5, 2);
      const uint64_t da = da0 + s * (K1_STAGE >> 4), db = db0 + s * (K1_STAGE >> 4);
      WG_FENCE();
#pragma unroll
      for (int k = 0; k < 4; k++) wgmma_ss_n160(acc, da + k * 2, db + k * 64, (kt | k) != 0);
      WG_COMMIT();
      if (kt > 0) {
        WG_WAIT(1);
        if (kt - 1 + K1_ST < 10 && (tid & 127) < 2) mbar_arrive_cta(emptyb + 8 * ((kt - 1) % K1_ST), tid & 1);
      }
      if (kt == 0) {
#pragma unroll
        for (int i = 0; i < 2; i++) {
          const bf16* xr = x + (size_t)min(srow + i, S_ - 1) * D_ + lane * 8;
          xv[i][0] = xv[i][1] = xv[i][2] = make_uint4(0u, 0u, 0u, 0u);
          if (dostat) { xv[i][0] = ldg_nc(xr); xv[i][1] = ldg_nc(xr + 256); }
          if (dostat && lane < 16) xv[i][2] = ldg_nc(xr + 512);
        }
      }
      if ((kt == KST || kt == KST + 1) && dostat) {
        const float2 st = row_stats(xv[kt - KST][0], xv[kt - KST][1], xv[kt - KST][2]);
        if (lane == 0) st_relaxed(&g_rowstat[srow + kt - KST], st.x, st.y, tag);
      }
      __syncwarp();
    }
    cluster_arrive();
    WG_WAIT(0);
    fence_regs(acc);
    if (tid == 0) STAMP(0, 2);
    bar_sync(2, 96 + 384);
    if (tid == 0) STAMP(0, 3);
    const int row0 = m * 192 + warp * 16;
    if (row0 < S_) {
      const int g = lane >> 2, c = lane & 3, sec = n >> 2, grp = (row0 & 127) >> 3;
      const bool lo = c < 2;
      const float2 ab0 = rowab[warp * 16 + g], ab1 = rowab[warp * 16 + g + 8];
      const bool p0 = sec == 1 && ((POLY_MASK >> grp) & 1), p1 = sec == 1 && ((POLY_MASK >> (grp + 1)) & 1);
      const uint32_t padqv = sec == 0 ? (c == 2 ? 0x3F803F80u : 0x00003F80u) : (sec == 2 && c == 2 ? 0x00003F80u : 0u);
      const uint32_t padk = c == 2 ? 0x4A7A4B00u : 0x00004653u;
      const uint32_t pad0 = p0 ? padk : padqv, pad1 = p1 ? padk : padqv;
      const float f0 = sec == 0 ? QSCALE : (p0 ? 32768.f : 1.f), f1 = sec == 0 ? QSCALE : (p1 ? 32768.f : 1.f);
      const float a0 = ab0.x * f0, b0 = ab0.y * f0, a1 = ab1.x * f1, b1 = ab1.y * f1;
      const float r0 = p0 ? 9.313225746154785e-10f : 1.f, r1 = p1 ? 9.313225746154785e-10f : 1.f;
      const int cst = sec == 1 ? 2048 : 128, gst = sec == 1 ? 128 : 384;
      uint8_t* pe = (uint8_t*)g_qkv + (size_t)(n * 8) * HEAD_IMG + (row0 >> 7) * 6144 + grp * gst + lane * 4;
      uint8_t* pe1 = pe + cst;
      uint8_t* pe2 = pe1 + cst;
      uint8_t* pf = pe + gst;
      uint8_t* pf1 = pf + cst;
      uint8_t* pf2 = pf1 + cst;
#pragma unroll
      for (int hp = 0; hp < 4; hp++) {
        uint32_t u[5], v[5];
        float su[5], sv[5];
#pragma unroll
        for (int i = 0; i < 5; i++) {
          const int j = hp * 5 + i;
          const float2 t = *(const float2*)&cs[j * 8 + c * 2];
          const float x0 = fmaf(acc[4 * j], a0, b0 * t.x), x1 = fmaf(acc[4 * j + 1], a0, b0 * t.y);
          const float y0 = fmaf(acc[4 * j + 2], a1, b1 * t.x), y1 = fmaf(acc[4 * j + 3], a1, b1 * t.y);
          u[i] = pack_bf16(x0, x1); v[i] = pack_bf16(y0, y1);
          su[i] = fmaf(x0, x0, x1 * x1); sv[i] = fmaf(y0, y0, y1 * y1);
        }
        constexpr int HE = HEAD_IMG;
        const int oe = hp * 2 * HE, oo = oe + HE;
        *(uint32_t*)(pe + oe) = u[0];  *(uint32_t*)(pf + oe) = v[0];
        *(uint32_t*)(pe1 + oe) = u[1]; *(uint32_t*)(pf1 + oe) = v[1];
        *(uint32_t*)(pe2 + oe) = lo ? u[2] : pad0; *(uint32_t*)(pf2 + oe) = lo ? v[2] : pad1;
        *(uint32_t*)(pe + oo) = __shfl_xor_sync(~0u, lo ? u[3] : u[2], 2);
        *(uint32_t*)(pf + oo) = __shfl_xor_sync(~0u, lo ? v[3] : v[2], 2);
        *(uint32_t*)(pe1 + oo) = __shfl_xor_sync(~0u, lo ? u[4] : u[3], 2);
        *(uint32_t*)(pf1 + oo) = __shfl_xor_sync(~0u, lo ? v[4] : v[3], 2);
        const uint32_t tu = __shfl_xor_sync(~0u, u[4], 2), tv = __shfl_xor_sync(~0u, v[4], 2);
        *(uint32_t*)(pe2 + oo) = lo ? tu : pad0; *(uint32_t*)(pf2 + oo) = lo ? tv : pad1;
        if (sec < 2) {
          float e0 = (su[0] + su[1] + (lo ? su[2] : 0.f)) * r0, e1 = (sv[0] + sv[1] + (lo ? sv[2] : 0.f)) * r1;
          float o0 = (su[3] + su[4] + (lo ? 0.f : su[2])) * r0, o1 = (sv[3] + sv[4] + (lo ? 0.f : sv[2])) * r1;
          e0 += __shfl_xor_sync(~0u, e0, 1); e1 += __shfl_xor_sync(~0u, e1, 1);
          o0 += __shfl_xor_sync(~0u, o0, 1); o1 += __shfl_xor_sync(~0u, o1, 1);
          e0 += __shfl_xor_sync(~0u, e0, 2); e1 += __shfl_xor_sync(~0u, e1, 2);
          o0 += __shfl_xor_sync(~0u, o0, 2); o1 += __shfl_xor_sync(~0u, o1, 2);
          const uint32_t em = __reduce_max_sync(~0u, max(__float_as_uint(e0), __float_as_uint(e1)));
          const uint32_t om = __reduce_max_sync(~0u, max(__float_as_uint(o0), __float_as_uint(o1)));
          if (lane < 2) g_nrm[(n * 8 + hp * 2 + lane) * 128 + (row0 >> 4)] = __uint_as_float(lane ? om : em);
        }
      }
    }
    if (tid == 0) STAMP(0, 4);
  }
  cluster_wait();
  if (tid == 0) STAMP(0, 6);
}

constexpr int K2_SMEM = 2 * HEAD_IMG + 2 * 6144 + 2 * 10240 + 256;

__device__ __forceinline__ uint64_t desc64(uint32_t lo, uint32_t hi) {
  uint64_t d;
  asm("mov.b64 %0, {%1, %2};" : "=l"(d) : "r"(lo), "r"(hi));
  return d;
}
__device__ __forceinline__ uint32_t exp_pair(bool poly, float a, float b, uint32_t mk) {
  if (poly) {
    const uint32_t pk = __byte_perm(__float_as_uint(a), __float_as_uint(b), 0x6521);
    uint32_t m, q;
    asm("lop3.b32 %0, %1, %2, 0x3f803f80, 0xEA;" : "=r"(m) : "r"(pk), "r"(mk));
    asm("fma.rn.bf16x2 %0, %1, %1, %2;" : "=r"(q) : "r"(m), "r"(0x40014001u));
    return pk - m + q;
  }
  return pack_bf16(ex2(a), ex2(b));
}
#define PV_GR 4
__device__ __forceinline__ void exp_pv(const float (&s)[64], float (&o)[12], uint64_t dv, uint32_t mk) {
#pragma unroll
  for (int k0 = 0; k0 < 8; k0 += PV_GR) {
    uint32_t p[4 * PV_GR];
#pragma unroll
    for (int i = 0; i < 4 * PV_GR; i++)
      p[i] = exp_pair((POLY_MASK >> (k0 * 2 + i / 2)) & 1, s[k0 * 8 + 2 * i], s[k0 * 8 + 2 * i + 1], mk);
    WG_FENCE();
#pragma unroll
    for (int k = 0; k < PV_GR; k++)
      wgmma_rs_n24(o, p[4 * k], p[4 * k + 1], p[4 * k + 2], p[4 * k + 3], dv + (k0 + k) * 48, 1);
  }
}
__device__ __forceinline__ void load_q(uint32_t (&q)[6], const uint8_t* p) {
  q[0] = __ldcg((const uint32_t*)p);         q[1] = __ldcg((const uint32_t*)(p + 384));
  q[2] = __ldcg((const uint32_t*)(p + 128)); q[3] = __ldcg((const uint32_t*)(p + 512));
  q[4] = __ldcg((const uint32_t*)(p + 256)); q[5] = __ldcg((const uint32_t*)(p + 640));
}
__device__ __forceinline__ float rcp(float x) {
  float y;
  asm("rcp.approx.ftz.f32 %0, %1;" : "=f"(y) : "f"(x));
  return y;
}
__device__ __forceinline__ int img_off(int chunk) { return (chunk >> 3) * 16384 + (chunk & 7) * 128; }
__device__ __forceinline__ void store_o(const float (&o)[12], int tile) {
  int tid, bid;
  asm volatile("mov.u32 %0, %%tid.x;" : "=r"(tid));
  asm volatile("mov.u32 %0, %%ctaid.x;" : "=r"(bid));
  const int head = bid >> 2;
  uint8_t* dst = (uint8_t*)g_o + ((bid & 3) * 4 + (tile >> 1)) * 163840 + (tile & 1) * 8192 + ((tid >> 5) & 3) * 2048 + (tid & 31) * 4;
  const int oc = (head >> 1) * 5 + (head & 1) * 2;
  const int o0 = img_off(oc), o1 = img_off(oc + 1), o2 = img_off((head >> 1) * 5 + 4) + (head & 1) * 8;
  const float i0 = rcp(__shfl_sync(~0u, o[8], 2, 4)), i1 = rcp(__shfl_sync(~0u, o[10], 2, 4));
  *(uint32_t*)(dst + o0) = pack_bf16(o[0] * i0, o[1] * i0); *(uint32_t*)(dst + o0 + 1024) = pack_bf16(o[2] * i1, o[3] * i1);
  *(uint32_t*)(dst + o1) = pack_bf16(o[4] * i0, o[5] * i0); *(uint32_t*)(dst + o1 + 1024) = pack_bf16(o[6] * i1, o[7] * i1);
  if ((tid & 3) < 2) {
    *(uint32_t*)(dst + o2) = pack_bf16(o[8] * i0, o[9] * i0);
    *(uint32_t*)(dst + o2 + 1024) = pack_bf16(o[10] * i1, o[11] * i1);
  }
}

struct Maps5 { CUtensorMap m[5]; };

__global__ void __launch_bounds__(512, 1)
k2_attn(const __grid_constant__ Maps5 maps, uint32_t mk) {
  const CUtensorMap* tmw = maps.m;
  extern __shared__ __align__(1024) uint8_t sm[];
  const uint32_t sbase = smem_u32(sm);
  float* part = (float*)(sm + 2 * HEAD_IMG);
  const uint32_t rbuf = sbase + 2 * HEAD_IMG + 2 * 6144;
  const uint32_t kvb = rbuf + 2 * 10240;
  const uint32_t partb = kvb + 128, rbar = kvb + 144;
  const int tid = threadIdx.x, lane = tid & 31;
  const int warp = __shfl_sync(~0u, tid >> 5, 0);
  const int head = blockIdx.x >> 2, qb = blockIdx.x & 3;

  if (tid == 0) STAMP(1, 0);
  if (tid == 0) {
    for (int i = 0; i < 16; i++) mbar_init(kvb + 8 * i, 1);
    mbar_init(partb, 128); mbar_init(partb + 8, 128); mbar_init(rbar, 1); mbar_init(rbar + 8, 1);
    asm volatile("fence.mbarrier_init.release.cluster;" ::: "memory");
  }
  __syncthreads();

  if (warp >= 12) {
    asm volatile("setmaxnreg.dec.sync.aligned.u32 32;");
    if (tid == 384) {
      pdl_wait();
      pdl_trigger();
      const uint8_t* kimg = (const uint8_t*)g_qkv + (size_t)(32 + head) * HEAD_IMG;
#pragma unroll 1
      for (int b = 0; b < 16; b++) {
        mbar_expect(kvb + 8 * b, 12288);
        bulk_ld(sbase + b * 6144, kimg + b * 6144, 6144, kvb + 8 * b);
        bulk_ld(sbase + HEAD_IMG + b * 6144, kimg + 32 * HEAD_IMG + b * 6144, 6144, kvb + 8 * b);
        if (b >= 2) mbar_wait(kvb + 8 * (b - 1), 0);

      }
      if (blockIdx.x == 0) g_epoch = g_epoch + 1;
      mbar_wait(kvb + 8 * 15, 0);
      STAMP(1, 2);
      uint8_t* pdst = nullptr;
      uint32_t pbytes = 0;
#pragma unroll 1
      for (int i = 0; i < 8; i++) {
        const int p = blockIdx.x + 128 * i;
        uint8_t* dst = nullptr;
        uint32_t bytes = 0;
        if (i < 7 && p < 856) {
          asm volatile("cp.async.bulk.wait_group.read 0;" ::: "memory");
          const CUtensorMap* tm;
          int c1, c2;
          if (p < 640) {
            const int nt = p / 80, r = p - nt * 80, ph = r / 40, st = (r - ph * 40) >> 1, up = r & 1;
            bytes = ph ? 6656 : 7168;
            dst = (uint8_t*)g_wgu + nt * 552960 + ph * 286720 + st * 2 * bytes + up * (bytes >> 1);
            tm = &tmw[ph * 2 + up]; c1 = ph ? 112 + nt * 13 : nt * 14; c2 = st * 2;
          } else {
            const int nk = p - 640, nt = nk / 27;
            bytes = 10240;
            dst = (uint8_t*)g_wd + (size_t)nk * 10240;
            tm = &tmw[4]; c1 = nt * 10; c2 = nk - nt * 27;
          }
          mbar_expect(rbar + 8 * (i & 1), bytes);
          tma4d(rbuf + (i & 1) * 10240, tm, c1, c2, rbar + 8 * (i & 1));
        }
        if (pbytes) {
          mbar_wait(rbar + 8 * ((i - 1) & 1), ((i - 1) >> 1) & 1);
          if (pbytes == 10240) {
            bulk_st(pdst, rbuf + ((i - 1) & 1) * 10240, pbytes);
          } else {
            bulk_st(pdst, rbuf + ((i - 1) & 1) * 10240, pbytes >> 1);
            bulk_st(pdst + pbytes, rbuf + ((i - 1) & 1) * 10240 + (pbytes >> 1), pbytes >> 1);
          }
          asm volatile("cp.async.bulk.commit_group;" ::: "memory");
        }
        pdst = dst; pbytes = bytes;
      }
      asm volatile("cp.async.bulk.wait_group.read 0;" ::: "memory");
      STAMP(1, 6);
    }
  } else {
    asm volatile("setmaxnreg.inc.sync.aligned.u32 160;");
    const int wg = warp >> 2;
    const uint8_t* qthr = (const uint8_t*)g_qkv + (size_t)head * HEAD_IMG + qb * 64 * 384 + (warp & 3) * 768 + lane * 4;
    const uint32_t klo0 = ((sbase & 0x3FFFF) >> 4) | (128u << 16), vlo0 = (((sbase + HEAD_IMG) & 0x3FFFF) >> 4) | (24u << 16);
    constexpr uint64_t KSTEP2 = (uint64_t)(int64_t)(256 - (128 << 16));
    constexpr uint64_t KV2K = 384 - (HEAD_IMG >> 4) + (104 << 16);
    const int nun = wg == 1 ? 4 : 3;
    uint32_t utile = wg == 0 ? 0x210u : (wg == 1 ? 0x4235u : 0x576u);
    uint32_t ubeg = wg == 0 ? 0u : (wg == 1 ? 0x0b00u : 0x600u);
    uint32_t ulen = wg == 0 ? 0x0b1010u : (wg == 1 ? 0x10051006u : 0x0a1010u);
    pdl_wait();
    if (tid == 0) STAMP(1, 1);
    uint32_t q[6];
    load_q(q, qthr + (utile & 15) * 3072);
    bool fast;
    {
      const float4 kn = __ldcg((const float4*)&g_nrm[(32 + head) * 128 + lane * 4]);
      const float qv = __ldcg(&g_nrm[head * 128 + qb * 32 + lane]);
      const uint32_t km = max(max(__float_as_uint(kn.x), __float_as_uint(kn.y)), max(__float_as_uint(kn.z), __float_as_uint(kn.w)));
      const float k2 = __uint_as_float(__reduce_max_sync(~0u, km)), q2 = __uint_as_float(__reduce_max_sync(~0u, __float_as_uint(qv)));
      fast = q2 * k2 <= 3400.f;
    }
    if (fast) {
#pragma unroll 1
      for (int u = 0; u < nun; u++) {
        const uint32_t b0 = ubeg & 15;
        const bool wt = u == 0 || (wg == 1 && u == 1);
        float s[64], o[12];
#pragma unroll
        for (int i = 0; i < 12; i++) o[i] = 0.f;
        uint32_t vlo = vlo0 + b0 * 384, kb = kvb + b0 * 8;
        const uint32_t vend = vlo + ((ulen & 255) - 1) * 384;
        if (wt) mbar_wait(kb, 0);
        if (tid == 0) STAMP(5, 4 + u);
        fence_regs(o);
        WG_FENCE();
        wgmma_rs_n128(s, q[0], q[1], q[2], q[3], desc64(klo0 + b0 * 384, 8), 0);
        wgmma_rs_n128(s, q[4], q[5], 0, 0, desc64(klo0 + b0 * 384, 8) + KSTEP2, 1);
        WG_COMMIT();
#define K2UNR 1
        constexpr int kUnr = K2UNR;
#pragma unroll kUnr
        for (; vlo != vend; vlo += 384) {
          if (wt) { kb += 8; mbar_wait(kb, 0); }
          WG_WAIT(0);
          fence_regs(s); fence_regs(o);
          const uint64_t dv = desc64(vlo, 8);
          exp_pv(s, o, dv, mk);
          wgmma_rs_n128(s, q[0], q[1], q[2], q[3], dv + KV2K, 0);
          wgmma_rs_n128(s, q[4], q[5], 0, 0, dv + (KV2K + KSTEP2), 1);
          WG_COMMIT();
        }
        WG_WAIT(0);
        fence_regs(s); fence_regs(o);
        if (u + 1 < nun) load_q(q, qthr + ((utile >> 4) & 15) * 3072);
        exp_pv(s, o, desc64(vlo, 8), mk);
        WG_COMMIT();
        WG_WAIT(0);
        fence_regs(o);
        if (wg == 1 && !(u & 1)) {
          float4* pp = (float4*)(part + u * 768) + (tid & 127);
          pp[0] = make_float4(o[0], o[1], o[2], o[3]);
          pp[128] = make_float4(o[4], o[5], o[6], o[7]);
          pp[256] = make_float4(o[8], o[9], o[10], o[11]);
          mbar_arrive(partb + 4 * u);
        } else {
          if (wg != 1 && u == 2) {
            const int pi = wg == 0 ? 1 : 0;
            mbar_wait(partb + 8 * pi, 0);
            const float4* pp = (const float4*)(part + pi * 1536) + (tid & 127);
            const float4 x0 = pp[0], x1 = pp[128], x2 = pp[256];
            o[0] += x0.x; o[1] += x0.y; o[2] += x0.z; o[3] += x0.w; o[4] += x1.x; o[5] += x1.y;
            o[6] += x1.z; o[7] += x1.w; o[8] += x2.x; o[9] += x2.y; o[10] += x2.z; o[11] += x2.w;
          }
          store_o(o, utile & 15);
        }
        utile >>= 4; ubeg >>= 4; ulen >>= 8;
      }
      if ((tid & 127) == 0) STAMP(1, 3 + wg);
    } else {
#pragma unroll 1
      for (int tile = wg; tile < 8; tile += 3) {
        load_q(q, qthr + tile * 3072);
        if ((lane & 3) >= 2) { q[4] = 0; q[5] = 0; }
        float o[12], m0 = -INFINITY, m1 = -INFINITY;
#pragma unroll
        for (int i = 0; i < 12; i++) o[i] = 0.f;
#pragma unroll 1
        for (int b = 0; b < 16; b++) {
          float s[64];
          mbar_wait(kvb + 8 * b, 0);
          WG_FENCE();
          wgmma_rs_n128(s, q[0], q[1], q[2], q[3], desc64(klo0 + b * 384, 8), 0);
          wgmma_rs_n128(s, q[4], q[5], 0, 0, desc64(klo0 + b * 384, 8) + KSTEP2, 1);
          WG_COMMIT();
          WG_WAIT(0);
          fence_regs(s);
          float x0 = m0, x1 = m1;
#pragma unroll
          for (int j = 0; j < 16; j++) {
            if ((POLY_MASK >> j) & 1) {
#pragma unroll
              for (int i = 0; i < 4; i++) s[4 * j + i] *= (1.f / 32768.f);
            }
            x0 = fmaxf(x0, fmaxf(s[4 * j], s[4 * j + 1]));
            x1 = fmaxf(x1, fmaxf(s[4 * j + 2], s[4 * j + 3]));
          }
          x0 = fmaxf(x0, __shfl_xor_sync(~0u, x0, 1)); x0 = fmaxf(x0, __shfl_xor_sync(~0u, x0, 2));
          x1 = fmaxf(x1, __shfl_xor_sync(~0u, x1, 1)); x1 = fmaxf(x1, __shfl_xor_sync(~0u, x1, 2));
          const float al0 = ex2(m0 - x0), al1 = ex2(m1 - x1);
          m0 = x0; m1 = x1;
#pragma unroll
          for (int i = 0; i < 12; i++) o[i] *= (i & 2) ? al1 : al0;
          uint32_t p[32];
#pragma unroll
          for (int i = 0; i < 32; i++) {
            const float mm = (i & 1) ? m1 : m0;
            p[i] = pack_bf16(ex2(s[2 * i] - mm), ex2(s[2 * i + 1] - mm));
          }
          fence_regs(o);
          WG_FENCE();
#pragma unroll
          for (int k = 0; k < 8; k++)
            wgmma_rs_n24(o, p[4 * k], p[4 * k + 1], p[4 * k + 2], p[4 * k + 3], desc64(vlo0 + b * 384 + k * 48, 8), 1);
          WG_COMMIT();
          WG_WAIT(0);
          fence_regs(o);
        }
        store_o(o, tile);
      }
    }
  }
}

#define K3P 2
constexpr int K3_ST = 4, K3_STAGE = 37888, K3_PRE = K3P;
constexpr int K3_SMEM = K3_ST * K3_STAGE + 45056 + 20480 + 256;

template <int N> struct Acc { float v[N]; };

template <int NB, int NK, bool FIRST>
__global__ void __cluster_dims__(2, 1, 1) __launch_bounds__(384, 1)
k3_proj(const __grid_constant__ CUtensorMap tmr, const uint4* __restrict__ aimg, const uint4* __restrict__ wimg) {
  constexpr int KT = 2 * NB + NK, EX = FIRST ? 1 : 0;
  extern __shared__ __align__(1024) uint8_t sm[];
  const uint32_t sbase = smem_u32(sm);
  uint8_t* xch = sm + K3_ST * K3_STAGE;
  uint8_t* stg = sm + K3_ST * K3_STAGE + 45056;
  const uint32_t fullb = smem_u32(stg) + 20480, emptyb = fullb + 8 * K3_ST, resb = emptyb + 8 * K3_ST, xchb = resb + 8;
  const int tid = threadIdx.x, lane = tid & 31;
  const int warp = __shfl_sync(~0u, tid >> 5, 0);
  const int rank = blockIdx.x & 1;
  const int n = blockIdx.x & 7, m = blockIdx.x >> 3;
  if (tid == 0) STAMP(FIRST ? 2 : 4, 0);
  if (warp == 0) {
    if (lane == 0) {
      prefetch_map(&tmr);
      for (int i = 0; i < K3_ST; i++) { mbar_init(fullb + 8 * i, 1); mbar_init(emptyb + 8 * i, 4); }
      mbar_init(resb, 1); mbar_init(xchb, 1);
      mbar_expect(xchb, 4096 * (10 + EX));
      asm volatile("fence.mbarrier_init.release.cluster;" ::: "memory");
    }
    __syncwarp();
    cluster_arrive();
    bar_arrive(4, 256 + 32);
    const uint8_t* wk = (const uint8_t*)wimg + (size_t)n * KT * 10240;
    const uint8_t* ws = (const uint8_t*)wimg + (size_t)(n ^ 1) * KT * 10240;
    const uint8_t* ab = (const uint8_t*)aimg + (size_t)m * KT * 16384;
    auto load_w = [&](int i) {
      const int s = i % K3_ST, kt = i < NB ? i + rank * (NB + NK) : i;
      const uint32_t sa = sbase + s * K3_STAGE;
      mbar_expect(fullb + 8 * s, 26624 + EX * 1024 + (i < NB ? 10240 : 0));
      bulk_ld(sa + 16384, wk + kt * 10240, 10240, fullb + 8 * s);
      if (FIRST) bulk_ld(sa + 26624, (const uint8_t*)g_wm + kt * 1024, 1024, fullb + 8 * s);
      if (i < NB) bulk_ld(sa + 26624 + EX * 1024, ws + kt * 10240, 10240, fullb + 8 * s);
    };
    if (elect_one()) {
#pragma unroll
      for (int i = 0; i < K3_PRE; i++) load_w(i);
      if (FIRST) {
        mbar_expect(resb, 20480);
        tma2d(smem_u32(stg), &tmr, n * 80, m * 128, resb);
        tma2d(smem_u32(stg) + 10240, &tmr, n * 80, m * 128 + 64, resb);
      }
    }
    cluster_wait();
    pdl_wait();
    pdl_trigger();
#pragma unroll
    for (int i = 0; i < NB + NK; i++) {
      const int s = i % K3_ST;
      const uint32_t sa = sbase + s * K3_STAGE;
      if (i >= K3_ST) mbar_wait(emptyb + 8 * s, ((i / K3_ST) - 1) & 1);
      if (elect_one()) {
        if (i < NB) bulk_ld(sa, ab + (i + rank * (NB + NK)) * 16384, 16384, fullb + 8 * s);
        else bulk_ld_mc(sa + rank * 8192, ab + i * 16384 + rank * 8192, 8192, fullb + 8 * s);
        if (i >= K3_PRE) load_w(i);
      }
    }
    __syncwarp();
    cluster_arrive();
  } else if (warp >= 4) {
    cluster_arrive();
    const int cw = warp - 4, wg = cw >> 2;
    const int g = lane >> 2, c = lane & 3;
    const int row = m * 128 + cw * 16 + g;
    uint8_t* himg = (uint8_t*)g_h + (size_t)m * 163840 + cw * 2048 + lane * 4;
    uint32_t rv[20];
    float mu0, mu1;
    if (FIRST) {
      mu0 = __uint_as_float(__ldcg(&g_rowstat[row].z)); mu1 = __uint_as_float(__ldcg(&g_rowstat[row + 8].z));
    } else {
      mu0 = __ldcg(&g_hmean[row]); mu1 = __ldcg(&g_hmean[row + 8]);
#pragma unroll
      for (int j = 0; j < 10; j++) {
        rv[2 * j] = __ldcg((const uint32_t*)(himg + img_off(n * 10 + j)));
        rv[2 * j + 1] = __ldcg((const uint32_t*)(himg + img_off(n * 10 + j) + 1024));
      }
    }
    float acc[80 + 4 * EX];
    float (&keep)[40 + 4 * EX] = ((Acc<40 + 4 * EX>*)acc)->v;
    const uint64_t da0 = mkdesc(sbase + wg * 8192, 128, 1024, 0);
    const uint64_t db0 = mkdesc(sbase + 16384, 128, 1024, 0);
    bar_sync(4, 256 + 32);
    cluster_wait();
#pragma unroll 1
    for (int i = 0; i < NB; i++) {
      const int s = i % K3_ST;
      mbar_wait(fullb + 8 * s, (i / K3_ST) & 1);
      if (i == 0 && tid == 128) STAMP(FIRST ? 2 : 4, 2);
      const uint64_t da = da0 + s * (K3_STAGE >> 4), db = db0 + s * (K3_STAGE >> 4);
      WG_FENCE();
#pragma unroll
      for (int k = 0; k < 4; k++) {
        if constexpr (FIRST) wgmma_ss_n168(acc, da + k * 16, db + k * 16, (i | k) != 0);
        else wgmma_ss_n160(acc, da + k * 16, db + k * 16, (i | k) != 0);
      }
      WG_COMMIT();
      if (i > 0) {
        WG_WAIT(1);
        if ((tid & 127) < 2) mbar_arrive_cta(emptyb + 8 * ((i - 1) % K3_ST), tid & 1);
      }
    }
    const uint32_t rx = mapa(smem_u32(xch) + (tid - 128) * 16, rank ^ 1), rb = mapa(xchb, rank ^ 1);
    WG_WAIT(0);
    fence_regs(acc);
    if ((tid & 127) < 2) mbar_arrive_cta(emptyb + 8 * ((NB - 1) % K3_ST), tid & 1);
    if (FIRST) st_async4(rx, acc[40], acc[41], acc[42], acc[43], rb);
    if (tid == 128) STAMP(FIRST ? 2 : 4, 1);
#pragma unroll
    for (int i = NB; i < NB + NK; i++) {
      const int s = i % K3_ST;
      mbar_wait(fullb + 8 * s, (i / K3_ST) & 1);
      const uint64_t da = da0 + s * (K3_STAGE >> 4), db = db0 + s * (K3_STAGE >> 4);
      WG_FENCE();
#pragma unroll
      for (int k = 0; k < 4; k++) {
        if constexpr (FIRST) wgmma_ss_n88(keep, da + k * 16, db + k * 16, 1);
        else wgmma_ss_n80(keep, da + k * 16, db + k * 16, 1);
      }
      WG_COMMIT();
      if (i > NB && i - 1 + K3_ST < NB + NK) {
        WG_WAIT(1);
        if ((tid & 127) < 2) mbar_arrive_cta(emptyb + 8 * ((i - 1) % K3_ST), tid & 1);
      }
#pragma unroll
      for (int j = (i - NB) * 3 + EX; j < (i - NB) * 3 + 3 + EX; j++)
        if (j < 10 + EX) st_async4(rx + j * 4096, acc[40 + 4 * j], acc[41 + 4 * j], acc[42 + 4 * j], acc[43 + 4 * j], rb);
    }
    cluster_arrive();
    uint8_t* sp = stg + (cw * 16 + g) * 160 + c * 4;
    if (FIRST) {
      mbar_wait(resb, 0);
#pragma unroll
      for (int j = 0; j < 10; j++) {
        rv[2 * j] = *(const uint32_t*)(sp + j * 16);
        rv[2 * j + 1] = *(const uint32_t*)(sp + 1280 + j * 16);
      }
    }
    WG_WAIT(0);
    fence_regs(keep);
    if (tid == 128) STAMP(FIRST ? 2 : 4, 3);
    mbar_wait(xchb, 0);
    if (tid == 128) STAMP(FIRST ? 2 : 4, 5);
    const uint8_t* xp = xch + (tid - 128) * 16;
    if (FIRST) {
      const float4 p = *(const float4*)xp;
      mu0 += __shfl_sync(~0u, (keep[40] + p.x) + (keep[41] + p.y), 0, 4);
      mu1 += __shfl_sync(~0u, (keep[42] + p.z) + (keep[43] + p.w), 0, 4);
      if (n == 0 && c == 0) { g_hmean[row] = mu0; g_hmean[row + 8] = mu1; }
      mu0 = -mu0; mu1 = -mu1;
    }
    float q0 = 0.f, q1 = 0.f;
#pragma unroll
    for (int j = 0; j < 10; j++) {
      const float4 p = *(const float4*)(xp + (j + EX) * 4096);
      const float x0 = (keep[4 * j] + p.x) + (bf_lo(rv[2 * j]) + mu0), x1 = (keep[4 * j + 1] + p.y) + (bf_hi(rv[2 * j]) + mu0);
      const float y0 = (keep[4 * j + 2] + p.z) + (bf_lo(rv[2 * j + 1]) + mu1), y1 = (keep[4 * j + 3] + p.w) + (bf_hi(rv[2 * j + 1]) + mu1);
      if (FIRST) {
        *(uint32_t*)(himg + img_off(n * 10 + j)) = pack_bf16(x0, x1);
        *(uint32_t*)(himg + img_off(n * 10 + j) + 1024) = pack_bf16(y0, y1);
        q0 = fmaf(x0, x0, fmaf(x1, x1, q0)); q1 = fmaf(y0, y0, fmaf(y1, y1, q1));
      } else {
        *(uint32_t*)(sp + j * 16) = pack_bf16(x0, x1);
        *(uint32_t*)(sp + 1280 + j * 16) = pack_bf16(y0, y1);
      }
    }
    if (FIRST) {
      q0 += __shfl_xor_sync(~0u, q0, 1); q0 += __shfl_xor_sync(~0u, q0, 2);
      q1 += __shfl_xor_sync(~0u, q1, 1); q1 += __shfl_xor_sync(~0u, q1, 2);
      if (c < 2) g_hpart[n * S_ + row + c * 8] = c ? q1 : q0;
    } else {
      fence_async();
      bar_sync(1 + wg, 128);
      if ((tid & 127) == 0) {
        tma2d_st(&tmr, n * 80, m * 128 + wg * 64, smem_u32(stg) + wg * 10240);
        bulk_commit_wait();
      }
      __syncwarp();
    }
    if (tid == 128) STAMP(FIRST ? 2 : 4, 4);
  } else {
    cluster_arrive();
    cluster_wait();
    cluster_arrive();
  }
  cluster_wait();
}

#define K4G 2
#define K4MC 2
constexpr int K4_G = K4G, K4_NS = K4_G == 1 ? 9 : (K4_G == 2 ? 4 : 2), K4_NJ = 40 / K4_G;
constexpr int K4_RB = 163840, K4_BST = 7168 * K4_G, K4_XCH = 147456, K4_STG = K4_XCH + 40960, K4_BAR = K4_RB + K4_NS * K4_BST;
constexpr int K4_SMEM = K4_BAR + 384;

__device__ __forceinline__ void wait_flags(const uint4* f, uint32_t tag) {
  for (uint32_t it = 0;; it++) {
    uint4 a, b;
    asm volatile("ld.acquire.gpu.global.v4.u32 {%0, %1, %2, %3}, [%4];" : "=r"(a.x), "=r"(a.y), "=r"(a.z), "=r"(a.w) : "l"(f) : "memory");
    asm volatile("ld.acquire.gpu.global.v4.u32 {%0, %1, %2, %3}, [%4];" : "=r"(b.x), "=r"(b.y), "=r"(b.z), "=r"(b.w) : "l"(f + 1) : "memory");
    if (a.x == tag && a.y == tag && a.z == tag && a.w == tag && b.x == tag && b.y == tag && b.z == tag && b.w == tag) break;
    if (it > (1u << 20)) wait_timeout();
    __nanosleep(50);
  }
  asm volatile("fence.proxy.async.global;" ::: "memory");
}

__global__ void __cluster_dims__(2, 1, 1) __launch_bounds__(384, 1)
k45_ffn(const __grid_constant__ CUtensorMap tmo) {
  extern __shared__ __align__(1024) uint8_t sm[];
  const uint32_t sbase = smem_u32(sm);
  const uint32_t afull = sbase + K4_BAR, bfull = afull + 80, bempty = bfull + 8 * K4_NS, full3 = bempty + 8 * K4_NS;
  const uint32_t empty3 = full3 + 32, afree = empty3 + 32, xchb = afree + 32;
  const int tid = threadIdx.x, lane = tid & 31;
  const int warp = __shfl_sync(~0u, tid >> 5, 0);
  const int rank = blockIdx.x & 1;
  const int n1 = (blockIdx.x >> 1) & 7, m1 = (blockIdx.x >> 4) * 2 + rank;
  const int n3 = blockIdx.x & 7, m3 = blockIdx.x >> 3;
  if (tid == 0) STAMP(3, 0);
  if (warp == 8) {
    if (lane < 10) mbar_init(afull + 8 * lane, 1);
    if (lane < K4_NS) { mbar_init(bfull + 8 * lane, 1); mbar_init(bempty + 8 * lane, 4); }
    if (lane < 4) { mbar_init(full3 + 8 * lane, 1); mbar_init(empty3 + 8 * lane, 4); mbar_init(afree + 8 * lane, 2); }
    if (lane == 0) { mbar_init(xchb, 1); mbar_expect(xchb, 40960); prefetch_map(&tmo); }
    asm volatile("fence.mbarrier_init.release.cluster;" ::: "memory");
    __syncwarp();
  }
  cluster_arrive();
  if (warp >= 8) {
    cluster_wait();
    if (warp == 8) {
      const uint8_t* src = (const uint8_t*)g_wgu + n1 * 552960 + (K4MC == 1 ? rank * 3584 * K4_G : 0);
      const uint8_t* hb = (const uint8_t*)g_h + (size_t)m1 * 163840;
      const uint32_t rb = sbase + K4_RB + (K4MC == 1 ? rank * 3584 * K4_G : 0);
#pragma unroll
      for (int j = 0; j < 2 * K4_NJ; j++) {
        constexpr int G = K4_G;
        const int s = j % K4_NS, ka = 3 + (j - K4_NS) * G / 4;
        if (j == K4_NS) {
          pdl_wait();
          if (lane == 0) STAMP(3, 1);
          if (elect_one()) {
#pragma unroll
            for (int kt = 0; kt < 3; kt++) { mbar_expect(afull + 8 * kt, 16384); bulk_ld(sbase + kt * 16384, hb + kt * 16384, 16384, afull + 8 * kt); }
          }
        }
        if (j >= K4_NS) mbar_wait(bempty + 8 * s, (j / K4_NS - 1) & 1);
        const int sz = (j < K4_NJ ? 7168 : 6656) * G;
        const int off = j < K4_NJ ? j * sz : 286720 + (j - K4_NJ) * sz, adj = (K4MC == 1 && j >= K4_NJ) ? rank * 256 * G : 0;
        if (elect_one()) {
          mbar_expect(bfull + 8 * s, sz);
          if (K4MC == 0) bulk_ld(rb + s * K4_BST, src + off, sz, bfull + 8 * s);
          if (K4MC == 1) bulk_ld_mc(rb + s * K4_BST - adj, src + off - adj, sz >> 1, bfull + 8 * s);
          if (K4MC == 2 && (j & 1) == rank) bulk_ld_mc(rb + s * K4_BST, src + off, sz, bfull + 8 * s);
          if (j >= K4_NS && ((j - K4_NS) * G) % 4 == 0 && ka < 10) {
            mbar_expect(afull + 8 * ka, 16384);
            bulk_ld(sbase + ka * 16384, hb + ka * 16384, 16384, afull + 8 * ka);
          }
        }
      }
    } else if (warp == 9) {
      const uint32_t tag = __ldcg(&g_epoch);
#pragma unroll 1
      for (int ph = 0; ph < 2; ph++) {
        bar_sync(5 + ph, 256 + 32);
        if (lane == 0) {
          asm volatile("st.release.gpu.global.u32 [%0], %1;" ::"l"((uint32_t*)&g_flag[ph * 32 + m1 * 2] + n1), "r"(tag) : "memory");
          STAMP(3, 5 + ph);
        }
        __syncwarp();
      }
    } else {
      const uint8_t* wk = (const uint8_t*)g_wd + n3 * 276480;
      const uint8_t* ws = (const uint8_t*)g_wd + (n3 ^ 1) * 276480;
      const uint8_t* ab = (const uint8_t*)g_hh + (size_t)m3 * 442368;
      const uint32_t tag = __ldcg(&g_epoch);
#pragma unroll
      for (int i = 0; i < 16; i++) {
        const int kt = i < 7 ? rank * 7 + i : (i < 11 ? rank * 4 + 7 + i : 11 + i);
        const uint32_t sa = sbase + (i & 3) * 36864, fb = full3 + 8 * (i & 3);
        if (i < 4) mbar_wait(afree + 8 * i, 0);
        else mbar_wait(empty3 + 8 * (i & 3), ((i >> 2) - 1) & 1);
        if (warp == 10) {
          if (elect_one()) {
            mbar_expect(fb, i < 11 ? 36864 : 26624);
            bulk_ld(sa + 16384, wk + kt * 10240, 10240, fb);
            if (i < 11) bulk_ld(sa + 26624, ws + kt * 10240, 10240, fb);
          }
        } else {
          if (i == 0 || i == 7) {
            wait_flags(&g_flag[(i ? 32 : 0) + m3 * 2], tag);
            if (lane == 0) STAMP(4, i ? 7 : 6);
          }
          if (elect_one()) {
            if (i < 11) bulk_ld(sa, ab + kt * 16384, 16384, fb);
            else bulk_ld_mc(sa + rank * 8192, ab + kt * 16384 + rank * 8192, 8192, fb);
          }
        }
      }
    }
    __syncwarp();
    cluster_arrive();
    asm volatile("barrier.cluster.wait.aligned; // producers" ::: "memory");
  } else {
    const int wg = warp >> 2;
    const uint64_t da0 = mkdesc(sbase + wg * 8192, 128, 1024, 0);
    const uint64_t db0 = mkdesc(sbase + K4_RB, 128, 256, 0);
    cluster_wait();
    float a1[112], a2[104];
    int s = 0, ph = 0, sprev = 0;
#pragma unroll 1
    for (int j = 0; j < K4_NJ; j++) {
      if ((j * K4_G) % 4 == 0) mbar_wait(afull + 2 * K4_G * j, 0);
      mbar_wait(bfull + 8 * s, ph);
      if (j == 0 && tid == 0) STAMP(3, 2);
      const uint64_t da = da0 + ((j * K4_G) >> 2) * 1024 + ((j * K4_G) & 3) * 16, db = db0 + s * (K4_BST >> 4);
      WG_FENCE();
#pragma unroll
      for (int k = 0; k < K4_G; k++) wgmma_ss_n224(a1, da + k * 16, db + k * 448, (j | k) != 0);
      WG_COMMIT();
      if (j > 0) {
        WG_WAIT(1);
        if ((tid & 127) < 2) mbar_arrive_cta(bempty + 8 * sprev, tid & 1);
      }
      sprev = s;
      if (++s == K4_NS) { s = 0; ph ^= 1; }
    }
    float r0, r1;
    {
      const float* hp = &g_hpart[(lane & 3) * 2 * S_ + m1 * 128 + warp * 16 + (lane >> 2)];
      r0 = __ldcg(hp) + __ldcg(hp + S_);
      r1 = __ldcg(hp + 8) + __ldcg(hp + S_ + 8);
    }
    float acc[80];
    uint8_t* hd = (uint8_t*)g_hh + (size_t)m1 * 442368 + warp * 2048 + lane * 4;
    {
      r0 += __shfl_xor_sync(~0u, r0, 1); r1 += __shfl_xor_sync(~0u, r1, 1);
      r0 += __shfl_xor_sync(~0u, r0, 2); r1 += __shfl_xor_sync(~0u, r1, 2);
      r0 = __frcp_rn(r0 * (1.f / D_) + 1e-5f); r1 = __frcp_rn(r1 * (1.f / D_) + 1e-5f);
    }
    WG_WAIT(0);
    fence_regs(a1);
    if ((tid & 127) < 2) mbar_arrive_cta(bempty + 8 * ((K4_NJ - 1) % K4_NS), tid & 1);
    if (tid == 0) STAMP(3, 3);
#define STORE_H(a, off, q, c) do { uint8_t* p_ = hd + img_off(q); \
      *(uint32_t*)p_ = pack_bf16(a[4 * (c)] * r0 * a[off + 4 * (c)], a[4 * (c) + 1] * r0 * a[off + 1 + 4 * (c)]); \
      *(uint32_t*)(p_ + 1024) = pack_bf16(a[4 * (c) + 2] * r1 * a[off + 2 + 4 * (c)], a[4 * (c) + 3] * r1 * a[off + 3 + 4 * (c)]); } while (0)
#pragma unroll
    for (int c = 0; c < 14; c++) STORE_H(a1, 56, n1 * 14 + c, c);
    bar_arrive(5, 256 + 32);
#pragma unroll 1
    for (int j = 0; j < K4_NJ; j++) {
      mbar_wait(bfull + 8 * s, ph);
      const uint64_t da = da0 + ((j * K4_G) >> 2) * 1024 + ((j * K4_G) & 3) * 16, db = db0 + s * (K4_BST >> 4);
      WG_FENCE();
#pragma unroll
      for (int k = 0; k < K4_G; k++) wgmma_ss_n208(a2, da + k * 16, db + k * 416, (j | k) != 0);
      WG_COMMIT();
      if (j > 0) {
        WG_WAIT(1);
        if (j <= K4_NJ - K4_NS && (tid & 127) < 2) mbar_arrive_cta(bempty + 8 * sprev, tid & 1);
        if (j * K4_G >= 12 && ((j * K4_G) & 7) == 4 && (tid & 127) == 0) mbar_arrive(afree + (j * K4_G - 12));
      }
      sprev = s;
      if (++s == K4_NS) { s = 0; ph ^= 1; }
    }
    WG_WAIT(0);
    fence_regs(a2);
    if (tid == 0) STAMP(3, 4);
#pragma unroll
    for (int c = 0; c < 13; c++) STORE_H(a2, 52, 112 + n1 * 13 + c, c);
    bar_arrive(6, 256 + 32);
    float (&keep)[40] = ((Acc<40>*)acc)->v;
    const uint64_t db3 = mkdesc(sbase + 16384, 128, 1024, 0);
#pragma unroll 1
    for (int i = 0; i < 11; i++) {
      mbar_wait(full3 + 8 * (i & 3), (i >> 2) & 1);
      if (i == 0 && tid == 0) STAMP(4, 2);
      const uint64_t da = da0 + (i & 3) * 2304, db = db3 + (i & 3) * 2304;
      WG_FENCE();
#pragma unroll
      for (int k = 0; k < 4; k++) wgmma_ss_n160(acc, da + k * 16, db + k * 16, (i | k) != 0);
      WG_COMMIT();
      if (i > 0) {
        WG_WAIT(1);
        if ((tid & 127) < 2) mbar_arrive_cta(empty3 + 8 * ((i - 1) & 3), tid & 1);
      }
    }
    const int g = lane >> 2, c = lane & 3, row = m3 * 128 + warp * 16 + g;
    const uint8_t* himg = (const uint8_t*)g_h + (size_t)m3 * 163840 + warp * 2048 + lane * 4;
    uint32_t rv[20];
    const float mu0 = __ldcg(&g_hmean[row]), mu1 = __ldcg(&g_hmean[row + 8]);
#pragma unroll
    for (int j = 0; j < 10; j++) {
      rv[2 * j] = __ldcg((const uint32_t*)(himg + img_off(n3 * 10 + j)));
      rv[2 * j + 1] = __ldcg((const uint32_t*)(himg + img_off(n3 * 10 + j) + 1024));
    }
    const uint32_t rx = mapa(sbase + K4_XCH + tid * 16, rank ^ 1), rb = mapa(xchb, rank ^ 1);
    WG_WAIT(0);
    fence_regs(acc);
    if ((tid & 127) < 2) mbar_arrive_cta(empty3 + 16, tid & 1);
    if (tid == 0) STAMP(4, 1);
#pragma unroll
    for (int i = 11; i < 16; i++) {
      mbar_wait(full3 + 8 * (i & 3), (i >> 2) & 1);
      const uint64_t da = da0 + (i & 3) * 2304, db = db3 + (i & 3) * 2304;
      WG_FENCE();
#pragma unroll
      for (int k = 0; k < 4; k++) wgmma_ss_n80(keep, da + k * 16, db + k * 16, 1);
      WG_COMMIT();
      if (i == 12) {
        WG_WAIT(1);
        if ((tid & 127) < 2) mbar_arrive_cta(empty3 + 24, tid & 1);
      }
#pragma unroll
      for (int j = (i - 11) * 3; j < (i - 11) * 3 + 3; j++)
        if (j < 10) st_async4(rx + j * 4096, acc[40 + 4 * j], acc[41 + 4 * j], acc[42 + 4 * j], acc[43 + 4 * j], rb);
    }
    cluster_arrive();
    WG_WAIT(0);
    fence_regs(keep);
    if (tid == 0) STAMP(4, 3);
    mbar_wait(xchb, 0);
    if (tid == 0) STAMP(4, 5);
    uint8_t* sp = sm + K4_STG + (warp * 16 + g) * 160 + c * 4;
#pragma unroll
    for (int j = 0; j < 10; j++) {
      const float4 p = *(const float4*)(sm + K4_XCH + tid * 16 + j * 4096);
      *(uint32_t*)(sp + j * 16) = pack_bf16((keep[4 * j] + p.x) + (bf_lo(rv[2 * j]) + mu0), (keep[4 * j + 1] + p.y) + (bf_hi(rv[2 * j]) + mu0));
      *(uint32_t*)(sp + 1280 + j * 16) = pack_bf16((keep[4 * j + 2] + p.z) + (bf_lo(rv[2 * j + 1]) + mu1), (keep[4 * j + 3] + p.w) + (bf_hi(rv[2 * j + 1]) + mu1));
    }
    fence_async();
    bar_sync(1 + wg, 128);
    if ((tid & 127) == 0) {
      tma2d_st(&tmo, n3 * 80, m3 * 128 + wg * 64, sbase + K4_STG + wg * 10240);
      bulk_commit_wait();
    }
    __syncwarp();
    if (tid == 0) STAMP(4, 4);
    asm volatile("barrier.cluster.wait.aligned; // consumers" ::: "memory");
  }
}

typedef CUresult (*EncodeFn)(CUtensorMap*, CUtensorMapDataType, cuuint32_t, void*, const cuuint64_t*, const cuuint64_t*,
                             const cuuint32_t*, const cuuint32_t*, CUtensorMapInterleave, CUtensorMapSwizzle,
                             CUtensorMapL2promotion, CUtensorMapFloatOOBfill);

static CUtensorMap make_map(EncodeFn enc, const void* p, uint64_t inner, uint64_t outer, uint32_t box_inner,
                            uint32_t box_outer, CUtensorMapSwizzle swz) {
  CUtensorMap m;
  cuuint64_t gd[2] = {inner, outer};
  cuuint64_t gs[1] = {inner * 2};
  cuuint32_t bd[2] = {box_inner, box_outer};
  cuuint32_t es[2] = {1, 1};
  enc(&m, CU_TENSOR_MAP_DATA_TYPE_BFLOAT16, 2, (void*)p, gd, gs, bd, es, CU_TENSOR_MAP_INTERLEAVE_NONE, swz,
      CU_TENSOR_MAP_L2_PROMOTION_L2_256B, CU_TENSOR_MAP_FLOAT_OOB_FILL_NONE);
  return m;
}

static CUtensorMap make_map_img(EncodeFn enc, const void* p, uint64_t k, uint64_t n, uint32_t rows, uint32_t chunks,
                                uint32_t groups) {
  CUtensorMap m;
  cuuint64_t gd[4] = {8, rows, n / 8, k / rows};
  cuuint64_t gs[3] = {n * 2, 16, n * 2 * rows};
  cuuint32_t bd[4] = {8, rows, chunks, groups};
  cuuint32_t es[4] = {1, 1, 1, 1};
  enc(&m, CU_TENSOR_MAP_DATA_TYPE_BFLOAT16, 4, (void*)p, gd, gs, bd, es, CU_TENSOR_MAP_INTERLEAVE_NONE,
      CU_TENSOR_MAP_SWIZZLE_NONE, CU_TENSOR_MAP_L2_PROMOTION_L2_128B, CU_TENSOR_MAP_FLOAT_OOB_FILL_NONE);
  return m;
}

template <typename... KArgs, typename... Args>
static void launch(void (*k)(KArgs...), int grid, int threads, int smem, bool pdl, Args... args) {
  cudaLaunchConfig_t cfg = {};
  cfg.gridDim = dim3(grid);
  cfg.blockDim = dim3(threads);
  cfg.dynamicSmemBytes = smem;
  cfg.stream = cudaStreamPerThread;
  cudaLaunchAttribute at[1];
  at[0].id = cudaLaunchAttributeProgrammaticStreamSerialization;
  at[0].val.programmaticStreamSerializationAllowed = 1;
  cfg.attrs = at;
  cfg.numAttrs = pdl ? 1 : 0;
  cudaLaunchKernelEx(&cfg, k, KArgs(args)...);
}

extern "C" void kernel_launch(void* const* d_in, const int* in_sizes, int n_in, void* d_out, int out_size) {
  const bf16* x = (const bf16*)d_in[0];
  const bf16* wqkv = (const bf16*)d_in[1];
  const bf16* wo = (const bf16*)d_in[2];
  const bf16* wg = (const bf16*)d_in[4];
  const bf16* wu = (const bf16*)d_in[5];
  const bf16* wd = (const bf16*)d_in[6];

  static EncodeFn enc = nullptr;
  static void *p_o, *p_wo;
  if (!enc) {
    void* fn = nullptr;
    cudaDriverEntryPointQueryResult qr;
    cudaGetDriverEntryPoint("cuTensorMapEncodeTiled", &fn, cudaEnableDefault, &qr);
    enc = (EncodeFn)fn;
    cudaGetSymbolAddress(&p_o, g_o);
    cudaGetSymbolAddress(&p_wo, g_wo);
    cudaFuncSetAttribute(k1_qkv, cudaFuncAttributeMaxDynamicSharedMemorySize, K1_SMEM);
    cudaFuncSetAttribute(k2_attn, cudaFuncAttributeMaxDynamicSharedMemorySize, K2_SMEM);
    cudaFuncSetAttribute(k3_proj<3, 4, true>, cudaFuncAttributeMaxDynamicSharedMemorySize, K3_SMEM);
    cudaFuncSetAttribute(k45_ffn, cudaFuncAttributeMaxDynamicSharedMemorySize, K4_SMEM);
  }
  const CUtensorMap tmx = make_map(enc, x, D_, S_, 64, 96, CU_TENSOR_MAP_SWIZZLE_128B);
  const CUtensorMap tmw = make_map(enc, wqkv, 3 * D_, D_, 32, 64, CU_TENSOR_MAP_SWIZZLE_64B);
  const CUtensorMap tmxr = make_map(enc, x, D_, S_, 80, 64, CU_TENSOR_MAP_SWIZZLE_NONE);
  Maps5 maps;
  maps.m[0] = make_map_img(enc, wg, D_, F_, 16, 14, 2); maps.m[1] = make_map_img(enc, wu, D_, F_, 16, 14, 2);
  maps.m[2] = make_map_img(enc, wg, D_, F_, 16, 13, 2); maps.m[3] = make_map_img(enc, wu, D_, F_, 16, 13, 2);
  maps.m[4] = make_map_img(enc, wd, F_, D_, 64, 10, 1);
  const CUtensorMap tmout = make_map(enc, d_out, D_, S_, 80, 64, CU_TENSOR_MAP_SWIZZLE_NONE);

  launch(k1_qkv, 132, 512, K1_SMEM, false, tmx, tmw, x, wqkv, wo);
  launch(k2_attn, 128, 512, K2_SMEM, true, maps, 0x007f007fu);
  launch(k3_proj<3, 4, true>, 128, 384, K3_SMEM, true, tmxr, (const uint4*)p_o, (const uint4*)p_wo);
  launch(k45_ffn, 128, 384, K4_SMEM, true, tmout);
}
```

```cpp
#include <cuda_runtime.h>
#include <cuda_bf16.h>
#include <cuda.h>
#include <stdint.h>

typedef __nv_bfloat16 bf16;

constexpr int S_ = 2048, D_ = 640, F_ = 1728;
constexpr int HEAD_IMG = 98304;
#define PMASK 0xDB6D
constexpr uint32_t POLY_MASK = PMASK;
constexpr float QSCALE = 0.22360679774997896f * 1.4426950408889634f;

__device__ __align__(1024) uint4 g_qkv[96 * HEAD_IMG / 16];
__device__ __align__(1024) uint4 g_o[S_ * D_ / 8];
__device__ __align__(1024) uint4 g_h[S_ * D_ / 8];
__device__ __align__(1024) uint4 g_hh[S_ * F_ / 8];
__device__ __align__(1024) uint4 g_wo[D_ * D_ / 8];
__device__ __align__(1024) uint4 g_wgu[2 * D_ * F_ / 8];
__device__ __align__(1024) uint4 g_wd[F_ * D_ / 8];
__device__ uint4 g_rowstat[S_];
__device__ uint4 g_cpart[10 * 12 * 80];
__device__ float g_nrm[64 * 128];
__device__ uint4 g_wm[D_];
__device__ float g_hmean[S_];
__device__ float g_hpart[8 * S_];
__device__ uint4 g_flag[2 * 16 * 2];
__device__ unsigned g_epoch;

#define STAMP(k, i)
__device__ __forceinline__ uint32_t smem_u32(const void* p) { return (uint32_t)__cvta_generic_to_shared(p); }
__device__ __forceinline__ void mbar_init(uint32_t a, uint32_t c) {
  asm volatile("mbarrier.init.shared::cta.b64 [%0], %1;" ::"r"(a), "r"(c) : "memory");
}
__device__ __forceinline__ void mbar_expect(uint32_t a, uint32_t bytes) {
  asm volatile("mbarrier.arrive.expect_tx.shared::cta.b64 _, [%0], %1;" ::"r"(a), "r"(bytes) : "memory");
}
__device__ __forceinline__ void mbar_arrive(uint32_t a) {
  asm volatile("mbarrier.arrive.shared::cta.b64 _, [%0];" ::"r"(a) : "memory");
}
__device__ __forceinline__ void mbar_arrive_cta(uint32_t a, uint32_t cta) {
  asm volatile("{\n.reg .b32 r;\nmapa.shared::cluster.u32 r, %0, %1;\n"
               "mbarrier.arrive.shared::cluster.b64 _, [r];\n}" ::"r"(a), "r"(cta) : "memory");
}
__device__ __forceinline__ bool mbar_try(uint32_t a, uint32_t ph) {
  uint32_t ok;
  asm volatile("{\n.reg .pred p;\nmbarrier.try_wait.parity.shared::cta.b64 p, [%1], %2;\nselp.u32 %0, 1, 0, p;\n}"
               : "=r"(ok) : "r"(a), "r"(ph) : "memory");
  return ok;
}
__device__ __noinline__ void wait_timeout() { __trap(); }
__device__ __forceinline__ void mbar_wait(uint32_t a, uint32_t ph) {
  if (mbar_try(a, ph)) return;
  uint32_t it = 0;
  while (!mbar_try(a, ph)) if (++it > (1u << 22)) wait_timeout();
}
__device__ __forceinline__ void tma2d(uint32_t dst, const CUtensorMap* m, int c0, int c1, uint32_t bar) {
  asm volatile("cp.async.bulk.tensor.2d.shared::cluster.global.mbarrier::complete_tx::bytes [%0], [%1, {%3, %4}], [%2];"
               ::"r"(dst), "l"(m), "r"(bar), "r"(c0), "r"(c1) : "memory");
}
__device__ __forceinline__ void tma2d_mc(uint32_t dst, const CUtensorMap* m, int c0, int c1, uint32_t bar) {
  asm volatile("cp.async.bulk.tensor.2d.shared::cluster.global.mbarrier::complete_tx::bytes.multicast::cluster "
               "[%0], [%1, {%3, %4}], [%2], %5;"
               ::"r"(dst), "l"(m), "r"(bar), "r"(c0), "r"(c1), "h"((uint16_t)3) : "memory");
}
__device__ __forceinline__ void bulk_ld(uint32_t dst, const void* src, uint32_t bytes, uint32_t bar) {
  asm volatile("cp.async.bulk.shared::cluster.global.mbarrier::complete_tx::bytes [%0], [%1], %2, [%3];"
               ::"r"(dst), "l"(src), "r"(bytes), "r"(bar) : "memory");
}
__device__ __forceinline__ void bulk_ld_mc(uint32_t dst, const void* src, uint32_t bytes, uint32_t bar) {
  asm volatile("cp.async.bulk.shared::cluster.global.mbarrier::complete_tx::bytes.multicast::cluster "
               "[%0], [%1], %2, [%3], %4;"
               ::"r"(dst), "l"(src), "r"(bytes), "r"(bar), "h"((uint16_t)3) : "memory");
}
__device__ __forceinline__ void cluster_arrive() { asm volatile("barrier.cluster.arrive.relaxed.aligned;" ::: "memory"); }
__device__ __forceinline__ void cluster_wait() { asm volatile("barrier.cluster.wait.aligned;" ::: "memory"); }
__device__ __forceinline__ void bulk_st(void* dst, uint32_t src, uint32_t bytes) {
  asm volatile("cp.async.bulk.global.shared::cta.bulk_group [%0], [%1], %2;" ::"l"(dst), "r"(src), "r"(bytes) : "memory");
}
__device__ __forceinline__ void tma2d_st(const CUtensorMap* m, int c0, int c1, uint32_t src) {
  asm volatile("cp.async.bulk.tensor.2d.global.shared::cta.bulk_group [%0, {%2, %3}], [%1];"
               ::"l"(m), "r"(src), "r"(c0), "r"(c1) : "memory");
}
__device__ __forceinline__ void bulk_commit_wait() {
  asm volatile("cp.async.bulk.commit_group;\ncp.async.bulk.wait_group.read 0;" ::: "memory");
}
__device__ __forceinline__ uint32_t mapa(uint32_t a, uint32_t cta) {
  uint32_t r;
  asm("mapa.shared::cluster.u32 %0, %1, %2;" : "=r"(r) : "r"(a), "r"(cta));
  return r;
}
__device__ __forceinline__ void st_async4(uint32_t dst, float a, float b, float c, float d, uint32_t bar) {
  asm volatile("st.async.shared::cluster.mbarrier::complete_tx::bytes.v4.f32 [%0], {%1, %2, %3, %4}, [%5];"
               ::"r"(dst), "f"(a), "f"(b), "f"(c), "f"(d), "r"(bar) : "memory");
}
__device__ __forceinline__ void fence_async() { asm volatile("fence.proxy.async.shared::cta;" ::: "memory"); }
__device__ __forceinline__ void prefetch_map(const CUtensorMap* m) {
  asm volatile("prefetch.tensormap [%0];" ::"l"(m) : "memory");
}
__device__ __forceinline__ bool elect_one() {
  uint32_t p;
  asm volatile("{\n.reg .pred q;\nelect.sync _|q, 0xffffffff;\nselp.u32 %0, 1, 0, q;\n}" : "=r"(p));
  return p;
}
__device__ __forceinline__ void pdl_wait() { asm volatile("griddepcontrol.wait;" ::: "memory"); }
__device__ __forceinline__ void pdl_trigger() { asm volatile("griddepcontrol.launch_dependents;" ::: "memory"); }
__device__ __forceinline__ void bar_sync(int id, int n) { asm volatile("bar.sync %0, %1;" ::"r"(id), "r"(n) : "memory"); }
__device__ __forceinline__ void bar_arrive(int id, int n) { asm volatile("bar.arrive %0, %1;" ::"r"(id), "r"(n) : "memory"); }
#define WG_FENCE() asm volatile("wgmma.fence.sync.aligned;" ::: "memory")
#define WG_COMMIT() asm volatile("wgmma.commit_group.sync.aligned;" ::: "memory")
#define WG_WAIT(n) asm volatile("wgmma.wait_group.sync.aligned %0;" ::"n"(n) : "memory")
__device__ __forceinline__ uint64_t mkdesc(uint32_t addr, uint32_t lbo, uint32_t sbo, uint32_t sw) {
  return (uint64_t)((addr & 0x3FFFF) >> 4) | ((uint64_t)(lbo >> 4) << 16) | ((uint64_t)(sbo >> 4) << 32) |
         ((uint64_t)sw << 62);
}
template <int N> __device__ __forceinline__ void fence_regs(float (&r)[N]) {
#pragma unroll
  for (int i = 0; i < N; i++) asm volatile("" : "+f"(r[i])::"memory");
}
__device__ __forceinline__ uint32_t pack_bf16(float lo, float hi) {
  uint32_t r;
  asm("cvt.rn.bf16x2.f32 %0, %1, %2;" : "=r"(r) : "f"(hi), "f"(lo));
  return r;
}
__device__ __forceinline__ float bf_lo(uint32_t v) { return __uint_as_float(v << 16); }
__device__ __forceinline__ float bf_hi(uint32_t v) { return __uint_as_float(v & 0xffff0000u); }
__device__ __forceinline__ float ex2(float x) {
  float y;
  asm("ex2.approx.ftz.f32 %0, %1;" : "=f"(y) : "f"(x));
  return y;
}
__device__ __forceinline__ uint4 ldg_nc(const void* p) {
  uint4 v;
  asm volatile("ld.global.nc.L1::no_allocate.v4.u32 {%0, %1, %2, %3}, [%4];"
               : "=r"(v.x), "=r"(v.y), "=r"(v.z), "=r"(v.w) : "l"(p));
  return v;
}

__device__ __forceinline__ uint4 ld_relaxed(const uint4* p) {
  uint64_t a, b;
  asm volatile("ld.relaxed.gpu.global.v2.u64 {%0, %1}, [%2];" : "=l"(a), "=l"(b) : "l"(p) : "memory");
  return make_uint4((uint32_t)a, (uint32_t)(a >> 32), (uint32_t)b, (uint32_t)(b >> 32));
}
__device__ __forceinline__ void st_relaxed(uint4* p, float x, float y, uint32_t tag) {
  const uint64_t a = ((uint64_t)tag << 32) | __float_as_uint(x), b = ((uint64_t)tag << 32) | __float_as_uint(y);
  asm volatile("st.relaxed.gpu.global.v2.u64 [%0], {%1, %2};" ::"l"(p), "l"(a), "l"(b) : "memory");
}
__device__ __forceinline__ void tma4d(uint32_t dst, const CUtensorMap* m, int c2, int c3, uint32_t bar) {
  asm volatile("cp.async.bulk.tensor.4d.shared::cluster.global.mbarrier::complete_tx::bytes [%0], [%1, {%3, %3, %4, %5}], [%2];"
               ::"r"(dst), "l"(m), "r"(bar), "r"(0), "r"(c2), "r"(c3) : "memory");
}
#define ACC8(a, v) do { a[0] += bf_lo(v.x); a[1] += bf_hi(v.x); a[2] += bf_lo(v.y); a[3] += bf_hi(v.y); \
                        a[4] += bf_lo(v.z); a[5] += bf_hi(v.z); a[6] += bf_lo(v.w); a[7] += bf_hi(v.w); } while (0)

__device__ __forceinline__ void wgmma_ss_n224(float (&d)[112], uint64_t da, uint64_t db, int sd) {
  asm volatile("{\n.reg .pred p;\nsetp.ne.b32 p, %114, 0;\n"
      "wgmma.mma_async.sync.aligned.m64n224k16.f32.bf16.bf16 {"
      "%0, %1, %2, %3, %4, %5, %6, %7, %8, %9, %10, %11, %12, %13, %14, %15, "
      "%16, %17, %18, %19, %20, %21, %22, %23, %24, %25, %26, %27, %28, %29, %30, %31, "
      "%32, %33, %34, %35, %36, %37, %38, %39, %40, %41, %42, %43, %44, %45, %46, %47, "
      "%48, %49, %50, %51, %52, %53, %54, %55, %56, %57, %58, %59, %60, %61, %62, %63, "
      "%64, %65, %66, %67, %68, %69, %70, %71, %72, %73, %74, %75, %76, %77, %78, %79, "
      "%80, %81, %82, %83, %84, %85, %86, %87, %88, %89, %90, %91, %92, %93, %94, %95, "
      "%96, %97, %98, %99, %100, %101, %102, %103, %104, %105, %106, %107, %108, %109, %110, %111"
      "}, %112, %113, p, 1, 1, 0, 1;\n}\n"
    : "+f"(d[0]), "+f"(d[1]), "+f"(d[2]), "+f"(d[3]), "+f"(d[4]), "+f"(d[5]), "+f"(d[6]), "+f"(d[7]),
      "+f"(d[8]), "+f"(d[9]), "+f"(d[10]), "+f"(d[11]), "+f"(d[12]), "+f"(d[13]), "+f"(d[14]), "+f"(d[15]),
      "+f"(d[16]), "+f"(d[17]), "+f"(d[18]), "+f"(d[19]), "+f"(d[20]), "+f"(d[21]), "+f"(d[22]), "+f"(d[23]),
      "+f"(d[24]), "+f"(d[25]), "+f"(d[26]), "+f"(d[27]), "+f"(d[28]), "+f"(d[29]), "+f"(d[30]), "+f"(d[31]),
      "+f"(d[32]), "+f"(d[33]), "+f"(d[34]), "+f"(d[35]), "+f"(d[36]), "+f"(d[37]), "+f"(d[38]), "+f"(d[39]),
      "+f"(d[40]), "+f"(d[41]), "+f"(d[42]), "+f"(d[43]), "+f"(d[44]), "+f"(d[45]), "+f"(d[46]), "+f"(d[47]),
      "+f"(d[48]), "+f"(d[49]), "+f"(d[50]), "+f"(d[51]), "+f"(d[52]), "+f"(d[53]), "+f"(d[54]), "+f"(d[55]),
      "+f"(d[56]), "+f"(d[57]), "+f"(d[58]), "+f"(d[59]), "+f"(d[60]), "+f"(d[61]), "+f"(d[62]), "+f"(d[63]),
      "+f"(d[64]), "+f"(d[65]), "+f"(d[66]), "+f"(d[67]), "+f"(d[68]), "+f"(d[69]), "+f"(d[70]), "+f"(d[71]),
      "+f"(d[72]), "+f"(d[73]), "+f"(d[74]), "+f"(d[75]), "+f"(d[76]), "+f"(d[77]), "+f"(d[78]), "+f"(d[79]),
      "+f"(d[80]), "+f"(d[81]), "+f"(d[82]), "+f"(d[83]), "+f"(d[84]), "+f"(d[85]), "+f"(d[86]), "+f"(d[87]),
      "+f"(d[88]), "+f"(d[89]), "+f"(d[90]), "+f"(d[91]), "+f"(d[92]), "+f"(d[93]), "+f"(d[94]), "+f"(d[95]),
      "+f"(d[96]), "+f"(d[97]), "+f"(d[98]), "+f"(d[99]), "+f"(d[100]), "+f"(d[101]), "+f"(d[102]), "+f"(d[103]),
      "+f"(d[104]), "+f"(d[105]), "+f"(d[106]), "+f"(d[107]), "+f"(d[108]), "+f"(d[109]), "+f"(d[110]), "+f"(d[111])
    : "l"(da), "l"(db), "r"(sd));
}
__device__ __forceinline__ void wgmma_ss_n208(float (&d)[104], uint64_t da, uint64_t db, int sd) {
  asm volatile("{\n.reg .pred p;\nsetp.ne.b32 p, %106, 0;\n"
      "wgmma.mma_async.sync.aligned.m64n208k16.f32.bf16.bf16 {"
      "%0, %1, %2, %3, %4, %5, %6, %7, %8, %9, %10, %11, %12, %13, %14, %15, "
      "%16, %17, %18, %19, %20, %21, %22, %23, %24, %25, %26, %27, %28, %29, %30, %31, "
      "%32, %33, %34, %35, %36, %37, %38, %39, %40, %41, %42, %43, %44, %45, %46, %47, "
      "%48, %49, %50, %51, %52, %53, %54, %55, %56, %57, %58, %59, %60, %61, %62, %63, "
      "%64, %65, %66, %67, %68, %69, %70, %71, %72, %73, %74, %75, %76, %77, %78, %79, "
      "%80, %81, %82, %83, %84, %85, %86, %87, %88, %89, %90, %91, %92, %93, %94, %95, "
      "%96, %97, %98, %99, %100, %101, %102, %103"
      "}, %104, %105, p, 1, 1, 0, 1;\n}\n"
    : "+f"(d[0]), "+f"(d[1]), "+f"(d[2]), "+f"(d[3]), "+f"(d[4]), "+f"(d[5]), "+f"(d[6]), "+f"(d[7]),
      "+f"(d[8]), "+f"(d[9]), "+f"(d[10]), "+f"(d[11]), "+f"(d[12]), "+f"(d[13]), "+f"(d[14]), "+f"(d[15]),
      "+f"(d[16]), "+f"(d[17]), "+f"(d[18]), "+f"(d[19]), "+f"(d[20]), "+f"(d[21]), "+f"(d[22]), "+f"(d[23]),
      "+f"(d[24]), "+f"(d[25]), "+f"(d[26]), "+f"(d[27]), "+f"(d[28]), "+f"(d[29]), "+f"(d[30]), "+f"(d[31]),
      "+f"(d[32]), "+f"(d[33]), "+f"(d[34]), "+f"(d[35]), "+f"(d[36]), "+f"(d[37]), "+f"(d[38]), "+f"(d[39]),
      "+f"(d[40]), "+f"(d[41]), "+f"(d[42]), "+f"(d[43]), "+f"(d[44]), "+f"(d[45]), "+f"(d[46]), "+f"(d[47]),
      "+f"(d[48]), "+f"(d[49]), "+f"(d[50]), "+f"(d[51]), "+f"(d[52]), "+f"(d[53]), "+f"(d[54]), "+f"(d[55]),
      "+f"(d[56]), "+f"(d[57]), "+f"(d[58]), "+f"(d[59]), "+f"(d[60]), "+f"(d[61]), "+f"(d[62]), "+f"(d[63]),
      "+f"(d[64]), "+f"(d[65]), "+f"(d[66]), "+f"(d[67]), "+f"(d[68]), "+f"(d[69]), "+f"(d[70]), "+f"(d[71]),
      "+f"(d[72]), "+f"(d[73]), "+f"(d[74]), "+f"(d[75]), "+f"(d[76]), "+f"(d[77]), "+f"(d[78]), "+f"(d[79]),
      "+f"(d[80]), "+f"(d[81]), "+f"(d[82]), "+f"(d[83]), "+f"(d[84]), "+f"(d[85]), "+f"(d[86]), "+f"(d[87]),
      "+f"(d[88]), "+f"(d[89]), "+f"(d[90]), "+f"(d[91]), "+f"(d[92]), "+f"(d[93]), "+f"(d[94]), "+f"(d[95]),
      "+f"(d[96]), "+f"(d[97]), "+f"(d[98]), "+f"(d[99]), "+f"(d[100]), "+f"(d[101]), "+f"(d[102]), "+f"(d[103])
    : "l"(da), "l"(db), "r"(sd));
}
__device__ __forceinline__ void wgmma_ss_n168(float (&d)[84], uint64_t da, uint64_t db, int sd) {
  asm volatile("{\n.reg .pred p;\nsetp.ne.b32 p, %86, 0;\n"
      "wgmma.mma_async.sync.aligned.m64n168k16.f32.bf16.bf16 {"
      "%0, %1, %2, %3, %4, %5, %6, %7, %8, %9, %10, %11, %12, %13, %14, %15, "
      "%16, %17, %18, %19, %20, %21, %22, %23, %24, %25, %26, %27, %28, %29, %30, %31, "
      "%32, %33, %34, %35, %36, %37, %38, %39, %40, %41, %42, %43, %44, %45, %46, %47, "
      "%48, %49, %50, %51, %52, %53, %54, %55, %56, %57, %58, %59, %60, %61, %62, %63, "
      "%64, %65, %66, %67, %68, %69, %70, %71, %72, %73, %74, %75, %76, %77, %78, %79, "
      "%80, %81, %82, %83"
      "}, %84, %85, p, 1, 1, 0, 1;\n}\n"
    : "+f"(d[0]), "+f"(d[1]), "+f"(d[2]), "+f"(d[3]), "+f"(d[4]), "+f"(d[5]), "+f"(d[6]), "+f"(d[7]),
      "+f"(d[8]), "+f"(d[9]), "+f"(d[10]), "+f"(d[11]), "+f"(d[12]), "+f"(d[13]), "+f"(d[14]), "+f"(d[15]),
      "+f"(d[16]), "+f"(d[17]), "+f"(d[18]), "+f"(d[19]), "+f"(d[20]), "+f"(d[21]), "+f"(d[22]), "+f"(d[23]),
      "+f"(d[24]), "+f"(d[25]), "+f"(d[26]), "+f"(d[27]), "+f"(d[28]), "+f"(d[29]), "+f"(d[30]), "+f"(d[31]),
      "+f"(d[32]), "+f"(d[33]), "+f"(d[34]), "+f"(d[35]), "+f"(d[36]), "+f"(d[37]), "+f"(d[38]), "+f"(d[39]),
      "+f"(d[40]), "+f"(d[41]), "+f"(d[42]), "+f"(d[43]), "+f"(d[44]), "+f"(d[45]), "+f"(d[46]), "+f"(d[47]),
      "+f"(d[48]), "+f"(d[49]), "+f"(d[50]), "+f"(d[51]), "+f"(d[52]), "+f"(d[53]), "+f"(d[54]), "+f"(d[55]),
      "+f"(d[56]), "+f"(d[57]), "+f"(d[58]), "+f"(d[59]), "+f"(d[60]), "+f"(d[61]), "+f"(d[62]), "+f"(d[63]),
      "+f"(d[64]), "+f"(d[65]), "+f"(d[66]), "+f"(d[67]), "+f"(d[68]), "+f"(d[69]), "+f"(d[70]), "+f"(d[71]),
      "+f"(d[72]), "+f"(d[73]), "+f"(d[74]), "+f"(d[75]), "+f"(d[76]), "+f"(d[77]), "+f"(d[78]), "+f"(d[79]),
      "+f"(d[80]), "+f"(d[81]), "+f"(d[82]), "+f"(d[83])
    : "l"(da), "l"(db), "r"(sd));
}
__device__ __forceinline__ void wgmma_ss_n160(float (&d)[80], uint64_t da, uint64_t db, int sd) {
  asm volatile("{\n.reg .pred p;\nsetp.ne.b32 p, %82, 0;\n"
      "wgmma.mma_async.sync.aligned.m64n160k16.f32.bf16.bf16 {"
      "%0, %1, %2, %3, %4, %5, %6, %7, %8, %9, %10, %11, %12, %13, %14, %15, "
      "%16, %17, %18, %19, %20, %21, %22, %23, %24, %25, %26, %27, %28, %29, %30, %31, "
      "%32, %33, %34, %35, %36, %37, %38, %39, %40, %41, %42, %43, %44, %45, %46, %47, "
      "%48, %49, %50, %51, %52, %53, %54, %55, %56, %57, %58, %59, %60, %61, %62, %63, "
      "%64, %65, %66, %67, %68, %69, %70, %71, %72, %73, %74, %75, %76, %77, %78, %79"
      "}, %80, %81, p, 1, 1, 0, 1;\n}\n"
    : "+f"(d[0]), "+f"(d[1]), "+f"(d[2]), "+f"(d[3]), "+f"(d[4]), "+f"(d[5]), "+f"(d[6]), "+f"(d[7]),
      "+f"(d[8]), "+f"(d[9]), "+f"(d[10]), "+f"(d[11]), "+f"(d[12]), "+f"(d[13]), "+f"(d[14]), "+f"(d[15]),
      "+f"(d[16]), "+f"(d[17]), "+f"(d[18]), "+f"(d[19]), "+f"(d[20]), "+f"(d[21]), "+f"(d[22]), "+f"(d[23]),
      "+f"(d[24]), "+f"(d[25]), "+f"(d[26]), "+f"(d[27]), "+f"(d[28]), "+f"(d[29]), "+f"(d[30]), "+f"(d[31]),
      "+f"(d[32]), "+f"(d[33]), "+f"(d[34]), "+f"(d[35]), "+f"(d[36]), "+f"(d[37]), "+f"(d[38]), "+f"(d[39]),
      "+f"(d[40]), "+f"(d[41]), "+f"(d[42]), "+f"(d[43]), "+f"(d[44]), "+f"(d[45]), "+f"(d[46]), "+f"(d[47]),
      "+f"(d[48]), "+f"(d[49]), "+f"(d[50]), "+f"(d[51]), "+f"(d[52]), "+f"(d[53]), "+f"(d[54]), "+f"(d[55]),
      "+f"(d[56]), "+f"(d[57]), "+f"(d[58]), "+f"(d[59]), "+f"(d[60]), "+f"(d[61]), "+f"(d[62]), "+f"(d[63]),
      "+f"(d[64]), "+f"(d[65]), "+f"(d[66]), "+f"(d[67]), "+f"(d[68]), "+f"(d[69]), "+f"(d[70]), "+f"(d[71]),
      "+f"(d[72]), "+f"(d[73]), "+f"(d[74]), "+f"(d[75]), "+f"(d[76]), "+f"(d[77]), "+f"(d[78]), "+f"(d[79])
    : "l"(da), "l"(db), "r"(sd));
}
__device__ __forceinline__ void wgmma_ss_n88(float (&d)[44], uint64_t da, uint64_t db, int sd) {
  asm volatile("{\n.reg .pred p;\nsetp.ne.b32 p, %46, 0;\n"
      "wgmma.mma_async.sync.aligned.m64n88k16.f32.bf16.bf16 {"
      "%0, %1, %2, %3, %4, %5, %6, %7, %8, %9, %10, %11, %12, %13, %14, %15, "
      "%16, %17, %18, %19, %20, %21, %22, %23, %24, %25, %26, %27, %28, %29, %30, %31, "
      "%32, %33, %34, %35, %36, %37, %38, %39, %40, %41, %42, %43"
      "}, %44, %45, p, 1, 1, 0, 1;\n}\n"
    : "+f"(d[0]), "+f"(d[1]), "+f"(d[2]), "+f"(d[3]), "+f"(d[4]), "+f"(d[5]), "+f"(d[6]), "+f"(d[7]),
      "+f"(d[8]), "+f"(d[9]), "+f"(d[10]), "+f"(d[11]), "+f"(d[12]), "+f"(d[13]), "+f"(d[14]), "+f"(d[15]),
      "+f"(d[16]), "+f"(d[17]), "+f"(d[18]), "+f"(d[19]), "+f"(d[20]), "+f"(d[21]), "+f"(d[22]), "+f"(d[23]),
      "+f"(d[24]), "+f"(d[25]), "+f"(d[26]), "+f"(d[27]), "+f"(d[28]), "+f"(d[29]), "+f"(d[30]), "+f"(d[31]),
      "+f"(d[32]), "+f"(d[33]), "+f"(d[34]), "+f"(d[35]), "+f"(d[36]), "+f"(d[37]), "+f"(d[38]), "+f"(d[39]),
      "+f"(d[40]), "+f"(d[41]), "+f"(d[42]), "+f"(d[43])
    : "l"(da), "l"(db), "r"(sd));
}
__device__ __forceinline__ void wgmma_ss_n80(float (&d)[40], uint64_t da, uint64_t db, int sd) {
  asm volatile("{\n.reg .pred p;\nsetp.ne.b32 p, %42, 0;\n"
      "wgmma.mma_async.sync.aligned.m64n80k16.f32.bf16.bf16 {"
      "%0, %1, %2, %3, %4, %5, %6, %7, %8, %9, %10, %11, %12, %13, %14, %15, "
      "%16, %17, %18, %19, %20, %21, %22, %23, %24, %25, %26, %27, %28, %29, %30, %31, "
      "%32, %33, %34, %35, %36, %37, %38, %39"
      "}, %40, %41, p, 1, 1, 0, 1;\n}\n"
    : "+f"(d[0]), "+f"(d[1]), "+f"(d[2]), "+f"(d[3]), "+f"(d[4]), "+f"(d[5]), "+f"(d[6]), "+f"(d[7]),
      "+f"(d[8]), "+f"(d[9]), "+f"(d[10]), "+f"(d[11]), "+f"(d[12]), "+f"(d[13]), "+f"(d[14]), "+f"(d[15]),
      "+f"(d[16]), "+f"(d[17]), "+f"(d[18]), "+f"(d[19]), "+f"(d[20]), "+f"(d[21]), "+f"(d[22]), "+f"(d[23]),
      "+f"(d[24]), "+f"(d[25]), "+f"(d[26]), "+f"(d[27]), "+f"(d[28]), "+f"(d[29]), "+f"(d[30]), "+f"(d[31]),
      "+f"(d[32]), "+f"(d[33]), "+f"(d[34]), "+f"(d[35]), "+f"(d[36]), "+f"(d[37]), "+f"(d[38]), "+f"(d[39])
    : "l"(da), "l"(db), "r"(sd));
}
__device__ __forceinline__ void wgmma_rs_n128(float (&d)[64], uint32_t a0, uint32_t a1, uint32_t a2, uint32_t a3,
                                  uint64_t db, int sd) {
  asm volatile("{\n.reg .pred p;\nsetp.ne.b32 p, %69, 0;\n"
      "wgmma.mma_async.sync.aligned.m64n128k16.f32.bf16.bf16 {"
      "%0, %1, %2, %3, %4, %5, %6, %7, %8, %9, %10, %11, %12, %13, %14, %15, "
      "%16, %17, %18, %19, %20, %21, %22, %23, %24, %25, %26, %27, %28, %29, %30, %31, "
      "%32, %33, %34, %35, %36, %37, %38, %39, %40, %41, %42, %43, %44, %45, %46, %47, "
      "%48, %49, %50, %51, %52, %53, %54, %55, %56, %57, %58, %59, %60, %61, %62, %63"
      "}, {%64, %65, %66, %67}, %68, p, 1, 1, 0;\n}\n"
    : "+f"(d[0]), "+f"(d[1]), "+f"(d[2]), "+f"(d[3]), "+f"(d[4]), "+f"(d[5]), "+f"(d[6]), "+f"(d[7]),
      "+f"(d[8]), "+f"(d[9]), "+f"(d[10]), "+f"(d[11]), "+f"(d[12]), "+f"(d[13]), "+f"(d[14]), "+f"(d[15]),
      "+f"(d[16]), "+f"(d[17]), "+f"(d[18]), "+f"(d[19]), "+f"(d[20]), "+f"(d[21]), "+f"(d[22]), "+f"(d[23]),
      "+f"(d[24]), "+f"(d[25]), "+f"(d[26]), "+f"(d[27]), "+f"(d[28]), "+f"(d[29]), "+f"(d[30]), "+f"(d[31]),
      "+f"(d[32]), "+f"(d[33]), "+f"(d[34]), "+f"(d[35]), "+f"(d[36]), "+f"(d[37]), "+f"(d[38]), "+f"(d[39]),
      "+f"(d[40]), "+f"(d[41]), "+f"(d[42]), "+f"(d[43]), "+f"(d[44]), "+f"(d[45]), "+f"(d[46]), "+f"(d[47]),
      "+f"(d[48]), "+f"(d[49]), "+f"(d[50]), "+f"(d[51]), "+f"(d[52]), "+f"(d[53]), "+f"(d[54]), "+f"(d[55]),
      "+f"(d[56]), "+f"(d[57]), "+f"(d[58]), "+f"(d[59]), "+f"(d[60]), "+f"(d[61]), "+f"(d[62]), "+f"(d[63])
    : "r"(a0), "r"(a1), "r"(a2), "r"(a3), "l"(db), "r"(sd));
}
__device__ __forceinline__ void wgmma_rs_n24(float (&d)[12], uint32_t a0, uint32_t a1, uint32_t a2, uint32_t a3,
                                  uint64_t db, int sd) {
  asm volatile("{\n.reg .pred p;\nsetp.ne.b32 p, %17, 0;\n"
      "wgmma.mma_async.sync.aligned.m64n24k16.f32.bf16.bf16 {"
      "%0, %1, %2, %3, %4, %5, %6, %7, %8, %9, %10, %11"
      "}, {%12, %13, %14, %15}, %16, p, 1, 1, 1;\n}\n"
    : "+f"(d[0]), "+f"(d[1]), "+f"(d[2]), "+f"(d[3]), "+f"(d[4]), "+f"(d[5]), "+f"(d[6]), "+f"(d[7]),
      "+f"(d[8]), "+f"(d[9]), "+f"(d[10]), "+f"(d[11])
    : "r"(a0), "r"(a1), "r"(a2), "r"(a3), "l"(db), "r"(sd));
}

#define KST 4
#define K1S 4
constexpr int K1_ST = K1S, K1_STAGE = 45056;
constexpr int K1_SMEM = K1_ST * K1_STAGE + 640   + 1536   + 2560   + 128;

__device__ __forceinline__ float2 row_stats(uint4 v0, uint4 v1, uint4 v2) {
  const uint32_t wd[12] = {v0.x, v0.y, v0.z, v0.w, v1.x, v1.y, v1.z, v1.w, v2.x, v2.y, v2.z, v2.w};
  float sx = 0.f, sq = 0.f;
#pragma unroll
  for (int e = 0; e < 12; e++) {
    const float lo = bf_lo(wd[e]), hi = bf_hi(wd[e]);
    sx += lo + hi; sq = fmaf(lo, lo, fmaf(hi, hi, sq));
  }
#pragma unroll
  for (int o = 16; o; o >>= 1) { sx += __shfl_xor_sync(~0u, sx, o); sq += __shfl_xor_sync(~0u, sq, o); }
  const float mean = sx * (1.f / D_);
  return make_float2(rsqrtf(fmaxf(sq * (1.f / D_) - mean * mean, 0.f) + 1e-5f), mean);
}

__global__ void __cluster_dims__(2, 1, 1) __launch_bounds__(512, 1)
k1_qkv(const __grid_constant__ CUtensorMap tmx, const __grid_constant__ CUtensorMap tmw,
       const bf16* __restrict__ x, const bf16* __restrict__ w, const bf16* __restrict__ wo) {
  extern __shared__ __align__(1024) uint8_t sm[];
  float* cs = (float*)(sm + K1_ST * K1_STAGE);
  float2* rowab = (float2*)(sm + K1_ST * K1_STAGE + 640);
  float* red = (float*)(sm + K1_ST * K1_STAGE + 2176);
  const uint32_t sbase = smem_u32(sm);
  const uint32_t fullb = sbase + K1_ST * K1_STAGE + 4736, emptyb = fullb + 8 * K1_ST;
  const int tid = threadIdx.x, lane = tid & 31;
  const int warp = __shfl_sync(~0u, tid >> 5, 0);
  const int rank = blockIdx.x & 1, cl = blockIdx.x >> 1;
  const int m = cl / 6, n = (cl - m * 6) * 2 + rank;
  if (tid == 0) STAMP(0, 0);

  if (warp == 12) {
    if (lane == 0) {
      prefetch_map(&tmx); prefetch_map(&tmw);
      for (int i = 0; i < K1_ST; i++) { mbar_init(fullb + 8 * i, 1); mbar_init(emptyb + 8 * i, 6); }
      asm volatile("fence.mbarrier_init.release.cluster;" ::: "memory");
    }
    __syncwarp();
    cluster_arrive();
    bar_arrive(4, 512);
    if (elect_one()) {
#pragma unroll
      for (int kt = 0; kt < K1_ST; kt++) mbar_expect(fullb + 8 * kt, K1_STAGE);
#pragma unroll
      for (int j = 0; j < 5; j++) tma2d(sbase + 24576 + j * 4096, &tmw, n * 160 + j * 32, 0, fullb);
    }
    cluster_wait();
#pragma unroll 1
    for (int kt = 0; kt < 10; kt++) {
      const int s = kt % K1_ST;
      const uint32_t sa = sbase + s * K1_STAGE;
      if (kt >= K1_ST) mbar_wait(emptyb + 8 * s, ((kt / K1_ST) - 1) & 1);
      if (elect_one()) {
        if (kt >= K1_ST) mbar_expect(fullb + 8 * s, K1_STAGE);
        tma2d_mc(sa + rank * 12288, &tmx, kt * 64, m * 192 + rank * 96, fullb + 8 * s);
        if (kt > 0) {
#pragma unroll
          for (int j = 0; j < 5; j++) tma2d(sa + 24576 + j * 4096, &tmw, n * 160 + j * 32, kt * 64, fullb + 8 * s);
        }
      }
      if (kt == K1_ST - 1) pdl_trigger();
    }
    __syncwarp();
    cluster_arrive();
  } else if (warp > 12) {
    cluster_arrive();
    const int t96 = tid - 416;
    const uint32_t tag = __ldcg(&g_epoch) + 1;
    bar_sync(4, 512);
    mbar_wait(fullb, 0);
    if (m < 10) {
      const int ck = t96 % 20, rg = min(t96 / 20, 3);
      uint4 wv[16];
#pragma unroll
      for (int i = 0; i < 16; i++) wv[i] = ldg_nc(w + (size_t)(m * 64 + rg * 16 + i) * 1920 + n * 160 + ck * 8);
      float acc8[8];
#pragma unroll
      for (int i = 0; i < 8; i++) acc8[i] = 0.f;
#pragma unroll
      for (int i = 0; i < 16; i++) ACC8(acc8, wv[i]);
      *(float4*)&red[rg * 160 + ck * 8] = make_float4(acc8[0], acc8[1], acc8[2], acc8[3]);
      *(float4*)&red[rg * 160 + ck * 8 + 4] = make_float4(acc8[4], acc8[5], acc8[6], acc8[7]);
      bar_sync(1, 96);
      if (t96 < 80) {
        const float2 p0 = *(const float2*)&red[t96 * 2], p1 = *(const float2*)&red[160 + t96 * 2];
        const float2 p2 = *(const float2*)&red[320 + t96 * 2], p3 = *(const float2*)&red[480 + t96 * 2];
        st_relaxed(&g_cpart[(m * 12 + n) * 80 + t96], (p0.x + p1.x) + (p2.x + p3.x), (p0.y + p1.y) + (p2.y + p3.y), tag);
      }
    }
    if (tid == 416) STAMP(5, 7);
    bool ok = false;
    for (int it = 0; it < 64 && !ok; it++) {
      uint4 p[10], st[2];
#pragma unroll
      for (int k = 0; k < 10; k++) p[k] = ld_relaxed(&g_cpart[(k * 12 + n) * 80 + min(t96, 79)]);
#pragma unroll
      for (int k = 0; k < 2; k++) st[k] = ld_relaxed(&g_rowstat[min(m * 192 + k * 96 + t96, S_ - 1)]);
      ok = true;
      float s0 = 0.f, s1 = 0.f;
#pragma unroll
      for (int k = 0; k < 10; k++) {
        ok = ok && p[k].y == tag && p[k].w == tag;
        s0 += __uint_as_float(p[k].x); s1 += __uint_as_float(p[k].z);
      }
      if (t96 < 80) *(float2*)&cs[t96 * 2] = make_float2(s0, s1);
#pragma unroll
      for (int k = 0; k < 2; k++) {
        ok = ok && st[k].y == tag && st[k].w == tag;
        rowab[k * 96 + t96] = make_float2(__uint_as_float(st[k].x), -__uint_as_float(st[k].x) * __uint_as_float(st[k].z));
      }
      ok = __all_sync(~0u, ok);
      if (!ok) __nanosleep(300);
    }
    if (!ok) {
      const int c2 = min(t96, 79);
      float s0 = 0.f, s1 = 0.f;
#pragma unroll 1
      for (int k = 0; k < D_; k++) {
        const uint32_t v = *(const uint32_t*)(w + (size_t)k * 1920 + n * 160 + c2 * 2);
        s0 += bf_lo(v); s1 += bf_hi(v);
      }
      if (t96 < 80) *(float2*)&cs[t96 * 2] = make_float2(s0, s1);
#pragma unroll 1
      for (int i = 0; i < 64; i++) {
        const int r = (i >> 5) * 96 + (t96 & ~31) + (i & 31);
        const bf16* xr = x + (size_t)min(m * 192 + r, S_ - 1) * D_ + lane * 8;
        const float2 st = row_stats(ldg_nc(xr), ldg_nc(xr + 256), lane < 16 ? ldg_nc(xr + 512) : make_uint4(0u, 0u, 0u, 0u));
        if (lane == 0) rowab[r] = make_float2(st.x, -st.x * st.y);
      }
    }
    __syncwarp();
    bar_arrive(2, 96 + 384);
    bar_sync(1, 96);
    if (tid == 416) STAMP(0, 5);
    if (blockIdx.x < 128) {
      uint4 v[5];
      const int ck = min(t96, 79), nt = ck / 10;
#pragma unroll
      for (int i = 0; i < 5; i++) {
        const int k = blockIdx.x * 5 + i, pr = k / 40, r = k - pr * 40;
        v[i] = ldg_nc(wo + (size_t)(pr * 40 + (r < 16 ? r : (r < 32 ? r + 4 : (r < 36 ? r - 16 : r)))) * D_ + ck * 8);
      }
#pragma unroll
      for (int i = 0; i < 5; i++) {
        const int k = blockIdx.x * 5 + i;
        g_wo[((nt * 10 + (k >> 6)) * 10 + ck - nt * 10) * 64 + (k & 63)] = v[i];
        float t = ((bf_lo(v[i].x) + bf_hi(v[i].x)) + (bf_lo(v[i].y) + bf_hi(v[i].y))) +
                  ((bf_lo(v[i].z) + bf_hi(v[i].z)) + (bf_lo(v[i].w) + bf_hi(v[i].w)));
        if (t96 >= 80) t = 0.f;
#pragma unroll
        for (int o = 16; o; o >>= 1) t += __shfl_xor_sync(~0u, t, o);
        if (lane == 0) red[(t96 >> 5) * 8 + i] = t;
      }
      bar_sync(1, 96);
      if (t96 < 5) {
        const float mu = (red[t96] + red[8 + t96] + red[16 + t96]) * (1.f / D_);
        const float hi = bf_lo(pack_bf16(mu, 0.f));
        g_wm[blockIdx.x * 5 + t96] = make_uint4(pack_bf16(hi, mu - hi), 0u, 0u, 0u);
      }
    }
    if (tid == 416) STAMP(0, 7);
    __syncwarp();
    cluster_wait();
    cluster_arrive();
  } else {
    cluster_arrive();
    float acc[80];
    const uint64_t da0 = mkdesc(sbase + (warp >> 2) * 8192, 16, 1024, 1);
    const uint64_t db0 = mkdesc(sbase + 24576, 4096, 512, 2);
    const uint32_t tag = __ldcg(&g_epoch) + 1;
    const int srow = m * 192 + n * 16 + warp * 2;
    const bool dostat = warp < 8 && srow < S_;
    uint4 xv[2][3];
    bar_sync(4, 512);
    cluster_wait();
#pragma unroll
    for (int kt = 0; kt < 10; kt++) {
      const int s = kt % K1_ST;
      mbar_wait(fullb + 8 * s, (kt / K1_ST) & 1);
      if (kt == 0 && tid == 0) STAMP(0, 1);
      if (kt == 2 && tid == 0) STAMP(5, 0);
      if (kt == 4 && tid == 0) STAMP(5, 1);
      if (kt == 7 && tid == 0) STAMP(5, 2);
      const uint64_t da = da0 + s * (K1_STAGE >> 4), db = db0 + s * (K1_STAGE >> 4);
      WG_FENCE();
#pragma unroll
      for (int k = 0; k < 4; k++) wgmma_ss_n160(acc, da + k * 2, db + k * 64, (kt | k) != 0);
      WG_COMMIT();
      if (kt > 0) {
        WG_WAIT(1);
        if (kt - 1 + K1_ST < 10 && (tid & 127) < 2) mbar_arrive_cta(emptyb + 8 * ((kt - 1) % K1_ST), tid & 1);
      }
      if (kt == 0) {
#pragma unroll
        for (int i = 0; i < 2; i++) {
          const bf16* xr = x + (size_t)min(srow + i, S_ - 1) * D_ + lane * 8;
          xv[i][0] = xv[i][1] = xv[i][2] = make_uint4(0u, 0u, 0u, 0u);
          if (dostat) { xv[i][0] = ldg_nc(xr); xv[i][1] = ldg_nc(xr + 256); }
          if (dostat && lane < 16) xv[i][2] = ldg_nc(xr + 512);
        }
      }
      if ((kt == KST || kt == KST + 1) && dostat) {
        const float2 st = row_stats(xv[kt - KST][0], xv[kt - KST][1], xv[kt - KST][2]);
        if (lane == 0) st_relaxed(&g_rowstat[srow + kt - KST], st.x, st.y, tag);
      }
      __syncwarp();
    }
    cluster_arrive();
    WG_WAIT(0);
    fence_regs(acc);
    if (tid == 0) STAMP(0, 2);
    bar_sync(2, 96 + 384);
    if (tid == 0) STAMP(0, 3);
    const int row0 = m * 192 + warp * 16;
    if (row0 < S_) {
      const int g = lane >> 2, c = lane & 3, sec = n >> 2, grp = (row0 & 127) >> 3;
      const bool lo = c < 2;
      const float2 ab0 = rowab[warp * 16 + g], ab1 = rowab[warp * 16 + g + 8];
      const bool p0 = sec == 1 && ((POLY_MASK >> grp) & 1), p1 = sec == 1 && ((POLY_MASK >> (grp + 1)) & 1);
      const uint32_t padqv = sec == 0 ? (c == 2 ? 0x3F803F80u : 0x00003F80u) : (sec == 2 && c == 2 ? 0x00003F80u : 0u);
      const uint32_t padk = c == 2 ? 0x4A7A4B00u : 0x00004653u;
      const uint32_t pad0 = p0 ? padk : padqv, pad1 = p1 ? padk : padqv;
      const float f0 = sec == 0 ? QSCALE : (p0 ? 32768.f : 1.f), f1 = sec == 0 ? QSCALE : (p1 ? 32768.f : 1.f);
      const float a0 = ab0.x * f0, b0 = ab0.y * f0, a1 = ab1.x * f1, b1 = ab1.y * f1;
      const float r0 = p0 ? 9.313225746154785e-10f : 1.f, r1 = p1 ? 9.313225746154785e-10f : 1.f;
      const int cst = sec == 1 ? 2048 : 128, gst = sec == 1 ? 128 : 384;
      uint8_t* pe = (uint8_t*)g_qkv + (size_t)(n * 8) * HEAD_IMG + (row0 >> 7) * 6144 + grp * gst + lane * 4;
      uint8_t* pe1 = pe + cst;
      uint8_t* pe2 = pe1 + cst;
      uint8_t* pf = pe + gst;
      uint8_t* pf1 = pf + cst;
      uint8_t* pf2 = pf1 + cst;
#pragma unroll
      for (int hp = 0; hp < 4; hp++) {
        uint32_t u[5], v[5];
        float su[5], sv[5];
#pragma unroll
        for (int i = 0; i < 5; i++) {
          const int j = hp * 5 + i;
          const float2 t = *(const float2*)&cs[j * 8 + c * 2];
          const float x0 = fmaf(acc[4 * j], a0, b0 * t.x), x1 = fmaf(acc[4 * j + 1], a0, b0 * t.y);
          const float y0 = fmaf(acc[4 * j + 2], a1, b1 * t.x), y1 = fmaf(acc[4 * j + 3], a1, b1 * t.y);
          u[i] = pack_bf16(x0, x1); v[i] = pack_bf16(y0, y1);
          su[i] = fmaf(x0, x0, x1 * x1); sv[i] = fmaf(y0, y0, y1 * y1);
        }
        constexpr int HE = HEAD_IMG;
        const int oe = hp * 2 * HE, oo = oe + HE;
        *(uint32_t*)(pe + oe) = u[0];  *(uint32_t*)(pf + oe) = v[0];
        *(uint32_t*)(pe1 + oe) = u[1]; *(uint32_t*)(pf1 + oe) = v[1];
        *(uint32_t*)(pe2 + oe) = lo ? u[2] : pad0; *(uint32_t*)(pf2 + oe) = lo ? v[2] : pad1;
        *(uint32_t*)(pe + oo) = __shfl_xor_sync(~0u, lo ? u[3] : u[2], 2);
        *(uint32_t*)(pf + oo) = __shfl_xor_sync(~0u, lo ? v[3] : v[2], 2);
        *(uint32_t*)(pe1 + oo) = __shfl_xor_sync(~0u, lo ? u[4] : u[3], 2);
        *(uint32_t*)(pf1 + oo) = __shfl_xor_sync(~0u, lo ? v[4] : v[3], 2);
        const uint32_t tu = __shfl_xor_sync(~0u, u[4], 2), tv = __shfl_xor_sync(~0u, v[4], 2);
        *(uint32_t*)(pe2 + oo) = lo ? tu : pad0; *(uint32_t*)(pf2 + oo) = lo ? tv : pad1;
        if (sec < 2) {
          float e0 = (su[0] + su[1] + (lo ? su[2] : 0.f)) * r0, e1 = (sv[0] + sv[1] + (lo ? sv[2] : 0.f)) * r1;
          float o0 = (su[3] + su[4] + (lo ? 0.f : su[2])) * r0, o1 = (sv[3] + sv[4] + (lo ? 0.f : sv[2])) * r1;
          e0 += __shfl_xor_sync(~0u, e0, 1); e1 += __shfl_xor_sync(~0u, e1, 1);
          o0 += __shfl_xor_sync(~0u, o0, 1); o1 += __shfl_xor_sync(~0u, o1, 1);
          e0 += __shfl_xor_sync(~0u, e0, 2); e1 += __shfl_xor_sync(~0u, e1, 2);
          o0 += __shfl_xor_sync(~0u, o0, 2); o1 += __shfl_xor_sync(~0u, o1, 2);
          const uint32_t em = __reduce_max_sync(~0u, max(__float_as_uint(e0), __float_as_uint(e1)));
          const uint32_t om = __reduce_max_sync(~0u, max(__float_as_uint(o0), __float_as_uint(o1)));
          if (lane < 2) g_nrm[(n * 8 + hp * 2 + lane) * 128 + (row0 >> 4)] = __uint_as_float(lane ? om : em);
        }
      }
    }
    if (tid == 0) STAMP(0, 4);
  }
  cluster_wait();
  if (tid == 0) STAMP(0, 6);
}

constexpr int K2_SMEM = 2 * HEAD_IMG + 2 * 6144 + 2 * 10240 + 256;

__device__ __forceinline__ uint64_t desc64(uint32_t lo, uint32_t hi) {
  uint64_t d;
  asm("mov.b64 %0, {%1, %2};" : "=l"(d) : "r"(lo), "r"(hi));
  return d;
}
__device__ __forceinline__ uint32_t exp_pair(bool poly, float a, float b, uint32_t mk) {
  if (poly) {
    const uint32_t pk = __byte_perm(__float_as_uint(a), __float_as_uint(b), 0x6521);
    uint32_t m, q;
    asm("lop3.b32 %0, %1, %2, 0x3f803f80, 0xEA;" : "=r"(m) : "r"(pk), "r"(mk));
    asm("fma.rn.bf16x2 %0, %1, %1, %2;" : "=r"(q) : "r"(m), "r"(0x40014001u));
    return pk - m + q;
  }
  return pack_bf16(ex2(a), ex2(b));
}
#define PV_GR 4
__device__ __forceinline__ void exp_pv(const float (&s)[64], float (&o)[12], uint64_t dv, uint32_t mk) {
#pragma unroll
  for (int k0 = 0; k0 < 8; k0 += PV_GR) {
    uint32_t p[4 * PV_GR];
#pragma unroll
    for (int i = 0; i < 4 * PV_GR; i++)
      p[i] = exp_pair((POLY_MASK >> (k0 * 2 + i / 2)) & 1, s[k0 * 8 + 2 * i], s[k0 * 8 + 2 * i + 1], mk);
    WG_FENCE();
#pragma unroll
    for (int k = 0; k < PV_GR; k++)
      wgmma_rs_n24(o, p[4 * k], p[4 * k + 1], p[4 * k + 2], p[4 * k + 3], dv + (k0 + k) * 48, 1);
  }
}
__device__ __forceinline__ void load_q(uint32_t (&q)[6], const uint8_t* p) {
  q[0] = __ldcg((const uint32_t*)p);         q[1] = __ldcg((const uint32_t*)(p + 384));
  q[2] = __ldcg((const uint32_t*)(p + 128)); q[3] = __ldcg((const uint32_t*)(p + 512));
  q[4] = __ldcg((const uint32_t*)(p + 256)); q[5] = __ldcg((const uint32_t*)(p + 640));
}
__device__ __forceinline__ float rcp(float x) {
  float y;
  asm("rcp.approx.ftz.f32 %0, %1;" : "=f"(y) : "f"(x));
  return y;
}
__device__ __forceinline__ int img_off(int chunk) { return (chunk >> 3) * 16384 + (chunk & 7) * 128; }
__device__ __forceinline__ void store_o(const float (&o)[12], int tile) {
  int tid, bid;
  asm volatile("mov.u32 %0, %%tid.x;" : "=r"(tid));
  asm volatile("mov.u32 %0, %%ctaid.x;" : "=r"(bid));
  const int head = bid >> 2;
  uint8_t* dst = (uint8_t*)g_o + ((bid & 3) * 4 + (tile >> 1)) * 163840 + (tile & 1) * 8192 + ((tid >> 5) & 3) * 2048 + (tid & 31) * 4;
  const int oc = (head >> 1) * 5 + (head & 1) * 2;
  const int o0 = img_off(oc), o1 = img_off(oc + 1), o2 = img_off((head >> 1) * 5 + 4) + (head & 1) * 8;
  const float i0 = rcp(__shfl_sync(~0u, o[8], 2, 4)), i1 = rcp(__shfl_sync(~0u, o[10], 2, 4));
  *(uint32_t*)(dst + o0) = pack_bf16(o[0] * i0, o[1] * i0); *(uint32_t*)(dst + o0 + 1024) = pack_bf16(o[2] * i1, o[3] * i1);
  *(uint32_t*)(dst + o1) = pack_bf16(o[4] * i0, o[5] * i0); *(uint32_t*)(dst + o1 + 1024) = pack_bf16(o[6] * i1, o[7] * i1);
  if ((tid & 3) < 2) {
    *(uint32_t*)(dst + o2) = pack_bf16(o[8] * i0, o[9] * i0);
    *(uint32_t*)(dst + o2 + 1024) = pack_bf16(o[10] * i1, o[11] * i1);
  }
}

struct Maps5 { CUtensorMap m[5]; };

__global__ void __launch_bounds__(512, 1)
k2_attn(const __grid_constant__ Maps5 maps, uint32_t mk) {
  const CUtensorMap* tmw = maps.m;
  extern __shared__ __align__(1024) uint8_t sm[];
  const uint32_t sbase = smem_u32(sm);
  float* part = (float*)(sm + 2 * HEAD_IMG);
  const uint32_t rbuf = sbase + 2 * HEAD_IMG + 2 * 6144;
  const uint32_t kvb = rbuf + 2 * 10240;
  const uint32_t partb = kvb + 128, rbar = kvb + 144;
  const int tid = threadIdx.x, lane = tid & 31;
  const int warp = __shfl_sync(~0u, tid >> 5, 0);
  const int head = blockIdx.x >> 2, qb = blockIdx.x & 3;

  if (tid == 0) STAMP(1, 0);
  if (tid == 0) {
    for (int i = 0; i < 16; i++) mbar_init(kvb + 8 * i, 1);
    mbar_init(partb, 128); mbar_init(partb + 8, 128); mbar_init(rbar, 1); mbar_init(rbar + 8, 1);
    asm volatile("fence.mbarrier_init.release.cluster;" ::: "memory");
  }
  __syncthreads();

  if (warp >= 12) {
    asm volatile("setmaxnreg.dec.sync.aligned.u32 32;");
    if (tid == 384) {
      pdl_wait();
      pdl_trigger();
      const uint8_t* kimg = (const uint8_t*)g_qkv + (size_t)(32 + head) * HEAD_IMG;
#pragma unroll 1
      for (int b = 0; b < 16; b++) {
        mbar_expect(kvb + 8 * b, 12288);
        bulk_ld(sbase + b * 6144, kimg + b * 6144, 6144, kvb + 8 * b);
        bulk_ld(sbase + HEAD_IMG + b * 6144, kimg + 32 * HEAD_IMG + b * 6144, 6144, kvb + 8 * b);
        if (b >= 2) mbar_wait(kvb + 8 * (b - 1), 0);

      }
      if (blockIdx.x == 0) g_epoch = g_epoch + 1;
      mbar_wait(kvb + 8 * 15, 0);
      STAMP(1, 2);
      uint8_t* pdst = nullptr;
      uint32_t pbytes = 0;
#pragma unroll 1
      for (int i = 0; i < 8; i++) {
        const int p = blockIdx.x + 128 * i;
        uint8_t* dst = nullptr;
        uint32_t bytes = 0;
        if (i < 7 && p < 856) {
          asm volatile("cp.async.bulk.wait_group.read 0;" ::: "memory");
          const CUtensorMap* tm;
          int c1, c2;
          if (p < 640) {
            const int nt = p / 80, r = p - nt * 80, ph = r / 40, st = (r - ph * 40) >> 1, up = r & 1;
            bytes = ph ? 6656 : 7168;
            dst = (uint8_t*)g_wgu + nt * 552960 + ph * 286720 + st * 2 * bytes + up * (bytes >> 1);
            tm = &tmw[ph * 2 + up]; c1 = ph ? 112 + nt * 13 : nt * 14; c2 = st * 2;
          } else {
            const int nk = p - 640, nt = nk / 27;
            bytes = 10240;
            dst = (uint8_t*)g_wd + (size_t)nk * 10240;
            tm = &tmw[4]; c1 = nt * 10; c2 = nk - nt * 27;
          }
          mbar_expect(rbar + 8 * (i & 1), bytes);
          tma4d(rbuf + (i & 1) * 10240, tm, c1, c2, rbar + 8 * (i & 1));
        }
        if (pbytes) {
          mbar_wait(rbar + 8 * ((i - 1) & 1), ((i - 1) >> 1) & 1);
          if (pbytes == 10240) {
            bulk_st(pdst, rbuf + ((i - 1) & 1) * 10240, pbytes);
          } else {
            bulk_st(pdst, rbuf + ((i - 1) & 1) * 10240, pbytes >> 1);
            bulk_st(pdst + pbytes, rbuf + ((i - 1) & 1) * 10240 + (pbytes >> 1), pbytes >> 1);
          }
          asm volatile("cp.async.bulk.commit_group;" ::: "memory");
        }
        pdst = dst; pbytes = bytes;
      }
      asm volatile("cp.async.bulk.wait_group.read 0;" ::: "memory");
      STAMP(1, 6);
    }
  } else {
    asm volatile("setmaxnreg.inc.sync.aligned.u32 160;");
    const int wg = warp >> 2;
    const uint8_t* qthr = (const uint8_t*)g_qkv + (size_t)head * HEAD_IMG + qb * 64 * 384 + (warp & 3) * 768 + lane * 4;
    const uint32_t klo0 = ((sbase & 0x3FFFF) >> 4) | (128u << 16), vlo0 = (((sbase + HEAD_IMG) & 0x3FFFF) >> 4) | (24u << 16);
    constexpr uint64_t KSTEP2 = (uint64_t)(int64_t)(256 - (128 << 16));
    constexpr uint64_t KV2K = 384 - (HEAD_IMG >> 4) + (104 << 16);
    const int nun = wg == 1 ? 4 : 3;
    uint32_t utile = wg == 0 ? 0x210u : (wg == 1 ? 0x4235u : 0x576u);
    uint32_t ubeg = wg == 0 ? 0u : (wg == 1 ? 0x0b00u : 0x600u);
    uint32_t ulen = wg == 0 ? 0x0b1010u : (wg == 1 ? 0x10051006u : 0x0a1010u);
    pdl_wait();
    if (tid == 0) STAMP(1, 1);
    uint32_t q[6];
    load_q(q, qthr + (utile & 15) * 3072);
    bool fast;
    {
      const float4 kn = __ldcg((const float4*)&g_nrm[(32 + head) * 128 + lane * 4]);
      const float qv = __ldcg(&g_nrm[head * 128 + qb * 32 + lane]);
      const uint32_t km = max(max(__float_as_uint(kn.x), __float_as_uint(kn.y)), max(__float_as_uint(kn.z), __float_as_uint(kn.w)));
      const float k2 = __uint_as_float(__reduce_max_sync(~0u, km)), q2 = __uint_as_float(__reduce_max_sync(~0u, __float_as_uint(qv)));
      fast = q2 * k2 <= 3400.f;
    }
    if (fast) {
#pragma unroll 1
      for (int u = 0; u < nun; u++) {
        const uint32_t b0 = ubeg & 15;
        const bool wt = u == 0 || (wg == 1 && u == 1);
        float s[64], o[12];
#pragma unroll
        for (int i = 0; i < 12; i++) o[i] = 0.f;
        uint32_t vlo = vlo0 + b0 * 384, kb = kvb + b0 * 8;
        const uint32_t vend = vlo + ((ulen & 255) - 1) * 384;
        if (wt) mbar_wait(kb, 0);
        if (tid == 0) STAMP(5, 4 + u);
        fence_regs(o);
        WG_FENCE();
        wgmma_rs_n128(s, q[0], q[1], q[2], q[3], desc64(klo0 + b0 * 384, 8), 0);
        wgmma_rs_n128(s, q[4], q[5], 0, 0, desc64(klo0 + b0 * 384, 8) + KSTEP2, 1);
        WG_COMMIT();
#define K2UNR 1
        constexpr int kUnr = K2UNR;
#pragma unroll kUnr
        for (; vlo != vend; vlo += 384) {
          if (wt) { kb += 8; mbar_wait(kb, 0); }
          WG_WAIT(0);
          fence_regs(s); fence_regs(o);
          const uint64_t dv = desc64(vlo, 8);
          exp_pv(s, o, dv, mk);
          wgmma_rs_n128(s, q[0], q[1], q[2], q[3], dv + KV2K, 0);
          wgmma_rs_n128(s, q[4], q[5], 0, 0, dv + (KV2K + KSTEP2), 1);
          WG_COMMIT();
        }
        WG_WAIT(0);
        fence_regs(s); fence_regs(o);
        if (u + 1 < nun) load_q(q, qthr + ((utile >> 4) & 15) * 3072);
        exp_pv(s, o, desc64(vlo, 8), mk);
        WG_COMMIT();
        WG_WAIT(0);
        fence_regs(o);
        if (wg == 1 && !(u & 1)) {
          float4* pp = (float4*)(part + u * 768) + (tid & 127);
          pp[0] = make_float4(o[0], o[1], o[2], o[3]);
          pp[128] = make_float4(o[4], o[5], o[6], o[7]);
          pp[256] = make_float4(o[8], o[9], o[10], o[11]);
          mbar_arrive(partb + 4 * u);
        } else {
          if (wg != 1 && u == 2) {
            const int pi = wg == 0 ? 1 : 0;
            mbar_wait(partb + 8 * pi, 0);
            const float4* pp = (const float4*)(part + pi * 1536) + (tid & 127);
            const float4 x0 = pp[0], x1 = pp[128], x2 = pp[256];
            o[0] += x0.x; o[1] += x0.y; o[2] += x0.z; o[3] += x0.w; o[4] += x1.x; o[5] += x1.y;
            o[6] += x1.z; o[7] += x1.w; o[8] += x2.x; o[9] += x2.y; o[10] += x2.z; o[11] += x2.w;
          }
          store_o(o, utile & 15);
        }
        utile >>= 4; ubeg >>= 4; ulen >>= 8;
      }
      if ((tid & 127) == 0) STAMP(1, 3 + wg);
    } else {
#pragma unroll 1
      for (int tile = wg; tile < 8; tile += 3) {
        load_q(q, qthr + tile * 3072);
        if ((lane & 3) >= 2) { q[4] = 0; q[5] = 0; }
        float o[12], m0 = -INFINITY, m1 = -INFINITY;
#pragma unroll
        for (int i = 0; i < 12; i++) o[i] = 0.f;
#pragma unroll 1
        for (int b = 0; b < 16; b++) {
          float s[64];
          mbar_wait(kvb + 8 * b, 0);
          WG_FENCE();
          wgmma_rs_n128(s, q[0], q[1], q[2], q[3], desc64(klo0 + b * 384, 8), 0);
          wgmma_rs_n128(s, q[4], q[5], 0, 0, desc64(klo0 + b * 384, 8) + KSTEP2, 1);
          WG_COMMIT();
          WG_WAIT(0);
          fence_regs(s);
          float x0 = m0, x1 = m1;
#pragma unroll
          for (int j = 0; j < 16; j++) {
            if ((POLY_MASK >> j) & 1) {
#pragma unroll
              for (int i = 0; i < 4; i++) s[4 * j + i] *= (1.f / 32768.f);
            }
            x0 = fmaxf(x0, fmaxf(s[4 * j], s[4 * j + 1]));
            x1 = fmaxf(x1, fmaxf(s[4 * j + 2], s[4 * j + 3]));
          }
          x0 = fmaxf(x0, __shfl_xor_sync(~0u, x0, 1)); x0 = fmaxf(x0, __shfl_xor_sync(~0u, x0, 2));
          x1 = fmaxf(x1, __shfl_xor_sync(~0u, x1, 1)); x1 = fmaxf(x1, __shfl_xor_sync(~0u, x1, 2));
          const float al0 = ex2(m0 - x0), al1 = ex2(m1 - x1);
          m0 = x0; m1 = x1;
#pragma unroll
          for (int i = 0; i < 12; i++) o[i] *= (i & 2) ? al1 : al0;
          uint32_t p[32];
#pragma unroll
          for (int i = 0; i < 32; i++) {
            const float mm = (i & 1) ? m1 : m0;
            p[i] = pack_bf16(ex2(s[2 * i] - mm), ex2(s[2 * i + 1] - mm));
          }
          fence_regs(o);
          WG_FENCE();
#pragma unroll
          for (int k = 0; k < 8; k++)
            wgmma_rs_n24(o, p[4 * k], p[4 * k + 1], p[4 * k + 2], p[4 * k + 3], desc64(vlo0 + b * 384 + k * 48, 8), 1);
          WG_COMMIT();
          WG_WAIT(0);
          fence_regs(o);
        }
        store_o(o, tile);
      }
    }
  }
}

#define K3P 1
constexpr int K3_ST = 4, K3_STAGE = 37888, K3_PRE = K3P;
constexpr int K3_SMEM = K3_ST * K3_STAGE + 45056 + 20480 + 256;

template <int N> struct Acc { float v[N]; };

template <int NB, int NK, bool FIRST>
__global__ void __cluster_dims__(2, 1, 1) __launch_bounds__(384, 1)
k3_proj(const __grid_constant__ CUtensorMap tmr, const uint4* __restrict__ aimg, const uint4* __restrict__ wimg) {
  constexpr int KT = 2 * NB + NK, EX = FIRST ? 1 : 0;
  extern __shared__ __align__(1024) uint8_t sm[];
  const uint32_t sbase = smem_u32(sm);
  uint8_t* xch = sm + K3_ST * K3_STAGE;
  uint8_t* stg = sm + K3_ST * K3_STAGE + 45056;
  const uint32_t fullb = smem_u32(stg) + 20480, emptyb = fullb + 8 * K3_ST, resb = emptyb + 8 * K3_ST, xchb = resb + 8;
  const int tid = threadIdx.x, lane = tid & 31;
  const int warp = __shfl_sync(~0u, tid >> 5, 0);
  const int rank = blockIdx.x & 1;
  const int n = blockIdx.x & 7, m = blockIdx.x >> 3;
  if (tid == 0) STAMP(FIRST ? 2 : 4, 0);
  if (warp == 0) {
    if (lane == 0) {
      prefetch_map(&tmr);
      for (int i = 0; i < K3_ST; i++) { mbar_init(fullb + 8 * i, 1); mbar_init(emptyb + 8 * i, 4); }
      mbar_init(resb, 1); mbar_init(xchb, 1);
      mbar_expect(xchb, 4096 * (10 + EX));
      asm volatile("fence.mbarrier_init.release.cluster;" ::: "memory");
    }
    __syncwarp();
    cluster_arrive();
    bar_arrive(4, 256 + 32);
    const uint8_t* wk = (const uint8_t*)wimg + (size_t)n * KT * 10240;
    const uint8_t* ws = (const uint8_t*)wimg + (size_t)(n ^ 1) * KT * 10240;
    const uint8_t* ab = (const uint8_t*)aimg + (size_t)m * KT * 16384;
    auto load_w = [&](int i) {
      const int s = i % K3_ST, kt = i < NB ? i + rank * (NB + NK) : i;
      const uint32_t sa = sbase + s * K3_STAGE;
      mbar_expect(fullb + 8 * s, 26624 + EX * 1024 + (i < NB ? 10240 : 0));
      bulk_ld(sa + 16384, wk + kt * 10240, 10240, fullb + 8 * s);
      if (FIRST) bulk_ld(sa + 26624, (const uint8_t*)g_wm + kt * 1024, 1024, fullb + 8 * s);
      if (i < NB) bulk_ld(sa + 26624 + EX * 1024, ws + kt * 10240, 10240, fullb + 8 * s);
    };
    if (elect_one()) {
#pragma unroll 1
      for (int i = 0; i < K3_PRE; i++) load_w(i);
    }
    cluster_wait();
    pdl_wait();
    pdl_trigger();
    if (lane == 0) STAMP(2, 6);
#pragma unroll 1
    for (int i = 0; i < NB + NK; i++) {
      const int s = i % K3_ST;
      const uint32_t sa = sbase + s * K3_STAGE;
      if (i >= K3_ST) mbar_wait(emptyb + 8 * s, ((i / K3_ST) - 1) & 1);
      if (elect_one()) {
        if (i < NB) bulk_ld(sa, ab + (i + rank * (NB + NK)) * 16384, 16384, fullb + 8 * s);
        else bulk_ld_mc(sa + rank * 8192, ab + i * 16384 + rank * 8192, 8192, fullb + 8 * s);
        if (i >= K3_PRE) load_w(i);
        if (FIRST && i == K3_ST - 1) {
          mbar_expect(resb, 20480);
          tma2d(smem_u32(stg), &tmr, n * 80, m * 128, resb);
          tma2d(smem_u32(stg) + 10240, &tmr, n * 80, m * 128 + 64, resb);
        }
      }
    }
    __syncwarp();
    cluster_arrive();
  } else if (warp >= 4) {
    cluster_arrive();
    const int cw = warp - 4, wg = cw >> 2;
    const int g = lane >> 2, c = lane & 3;
    const int row = m * 128 + cw * 16 + g;
    uint8_t* himg = (uint8_t*)g_h + (size_t)m * 163840 + cw * 2048 + lane * 4;
    uint32_t rv[20];
    float mu0, mu1;
    if (FIRST) {
      mu0 = __uint_as_float(__ldcg(&g_rowstat[row].z)); mu1 = __uint_as_float(__ldcg(&g_rowstat[row + 8].z));
    } else {
      mu0 = __ldcg(&g_hmean[row]); mu1 = __ldcg(&g_hmean[row + 8]);
#pragma unroll
      for (int j = 0; j < 10; j++) {
        rv[2 * j] = __ldcg((const uint32_t*)(himg + img_off(n * 10 + j)));
        rv[2 * j + 1] = __ldcg((const uint32_t*)(himg + img_off(n * 10 + j) + 1024));
      }
    }
    float acc[80 + 4 * EX];
    float (&keep)[40 + 4 * EX] = ((Acc<40 + 4 * EX>*)acc)->v;
    const uint64_t da0 = mkdesc(sbase + wg * 8192, 128, 1024, 0);
    const uint64_t db0 = mkdesc(sbase + 16384, 128, 1024, 0);
    bar_sync(4, 256 + 32);
    cluster_wait();
#pragma unroll 1
    for (int i = 0; i < NB; i++) {
      const int s = i % K3_ST;
      mbar_wait(fullb + 8 * s, (i / K3_ST) & 1);
      if (i == 0 && tid == 128) STAMP(FIRST ? 2 : 4, 2);
      const uint64_t da = da0 + s * (K3_STAGE >> 4), db = db0 + s * (K3_STAGE >> 4);
      WG_FENCE();
#pragma unroll
      for (int k = 0; k < 4; k++) {
        if constexpr (FIRST) wgmma_ss_n168(acc, da + k * 16, db + k * 16, (i | k) != 0);
        else wgmma_ss_n160(acc, da + k * 16, db + k * 16, (i | k) != 0);
      }
      WG_COMMIT();
      if (i > 0) {
        WG_WAIT(1);
        if ((tid & 127) < 2) mbar_arrive_cta(emptyb + 8 * ((i - 1) % K3_ST), tid & 1);
      }
    }
    const uint32_t rx = mapa(smem_u32(xch) + (tid - 128) * 16, rank ^ 1), rb = mapa(xchb, rank ^ 1);
    WG_WAIT(0);
    fence_regs(acc);
    if ((tid & 127) < 2) mbar_arrive_cta(emptyb + 8 * ((NB - 1) % K3_ST), tid & 1);
    if (FIRST) st_async4(rx, acc[40], acc[41], acc[42], acc[43], rb);
    if (tid == 128) STAMP(FIRST ? 2 : 4, 1);
#pragma unroll
    for (int i = NB; i < NB + NK; i++) {
      const int s = i % K3_ST;
      mbar_wait(fullb + 8 * s, (i / K3_ST) & 1);
      const uint64_t da = da0 + s * (K3_STAGE >> 4), db = db0 + s * (K3_STAGE >> 4);
      WG_FENCE();
#pragma unroll
      for (int k = 0; k < 4; k++) {
        if constexpr (FIRST) wgmma_ss_n88(keep, da + k * 16, db + k * 16, 1);
        else wgmma_ss_n80(keep, da + k * 16, db + k * 16, 1);
      }
      WG_COMMIT();
      if (i > NB && i - 1 + K3_ST < NB + NK) {
        WG_WAIT(1);
        if ((tid & 127) < 2) mbar_arrive_cta(emptyb + 8 * ((i - 1) % K3_ST), tid & 1);
      }
#pragma unroll
      for (int j = (i - NB) * 3 + EX; j < (i - NB) * 3 + 3 + EX; j++)
        if (j < 10 + EX) st_async4(rx + j * 4096, acc[40 + 4 * j], acc[41 + 4 * j], acc[42 + 4 * j], acc[43 + 4 * j], rb);
    }
    cluster_arrive();
    uint8_t* sp = stg + (cw * 16 + g) * 160 + c * 4;
    if (FIRST) {
      mbar_wait(resb, 0);
#pragma unroll
      for (int j = 0; j < 10; j++) {
        rv[2 * j] = *(const uint32_t*)(sp + j * 16);
        rv[2 * j + 1] = *(const uint32_t*)(sp + 1280 + j * 16);
      }
    }
    WG_WAIT(0);
    fence_regs(keep);
    if (tid == 128) STAMP(FIRST ? 2 : 4, 3);
    mbar_wait(xchb, 0);
    if (tid == 128) STAMP(FIRST ? 2 : 4, 5);
    const uint8_t* xp = xch + (tid - 128) * 16;
    if (FIRST) {
      const float4 p = *(const float4*)xp;
      mu0 += __shfl_sync(~0u, (keep[40] + p.x) + (keep[41] + p.y), 0, 4);
      mu1 += __shfl_sync(~0u, (keep[42] + p.z) + (keep[43] + p.w), 0, 4);
      if (n == 0 && c == 0) { g_hmean[row] = mu0; g_hmean[row + 8] = mu1; }
      mu0 = -mu0; mu1 = -mu1;
    }
    float q0 = 0.f, q1 = 0.f;
#pragma unroll
    for (int j = 0; j < 10; j++) {
      const float4 p = *(const float4*)(xp + (j + EX) * 4096);
      const float x0 = (keep[4 * j] + p.x) + (bf_lo(rv[2 * j]) + mu0), x1 = (keep[4 * j + 1] + p.y) + (bf_hi(rv[2 * j]) + mu0);
      const float y0 = (keep[4 * j + 2] + p.z) + (bf_lo(rv[2 * j + 1]) + mu1), y1 = (keep[4 * j + 3] + p.w) + (bf_hi(rv[2 * j + 1]) + mu1);
      if (FIRST) {
        *(uint32_t*)(himg + img_off(n * 10 + j)) = pack_bf16(x0, x1);
        *(uint32_t*)(himg + img_off(n * 10 + j) + 1024) = pack_bf16(y0, y1);
        q0 = fmaf(x0, x0, fmaf(x1, x1, q0)); q1 = fmaf(y0, y0, fmaf(y1, y1, q1));
      } else {
        *(uint32_t*)(sp + j * 16) = pack_bf16(x0, x1);
        *(uint32_t*)(sp + 1280 + j * 16) = pack_bf16(y0, y1);
      }
    }
    if (FIRST) {
      q0 += __shfl_xor_sync(~0u, q0, 1); q0 += __shfl_xor_sync(~0u, q0, 2);
      q1 += __shfl_xor_sync(~0u, q1, 1); q1 += __shfl_xor_sync(~0u, q1, 2);
      if (c < 2) g_hpart[n * S_ + row + c * 8] = c ? q1 : q0;
    } else {
      fence_async();
      bar_sync(1 + wg, 128);
      if ((tid & 127) == 0) {
        tma2d_st(&tmr, n * 80, m * 128 + wg * 64, smem_u32(stg) + wg * 10240);
        bulk_commit_wait();
      }
      __syncwarp();
    }
    if (tid == 128) STAMP(FIRST ? 2 : 4, 4);
  } else {
    cluster_arrive();
    cluster_wait();
    cluster_arrive();
  }
  cluster_wait();
}

constexpr int K4_G = 2, K4_NS = 4, K4_NJ = 20;
constexpr int K4_RB = 163840, K4_BST = 7168 * K4_G, K4_XCH = 147456, K4_STG = K4_XCH + 40960, K4_BAR = K4_RB + K4_NS * K4_BST;
constexpr int K4_SMEM = K4_BAR + 384;

__device__ __forceinline__ void wait_flags(const uint4* f, uint32_t tag) {
  for (uint32_t it = 0;; it++) {
    uint4 a, b;
    asm volatile("ld.acquire.gpu.global.v4.u32 {%0, %1, %2, %3}, [%4];" : "=r"(a.x), "=r"(a.y), "=r"(a.z), "=r"(a.w) : "l"(f) : "memory");
    asm volatile("ld.acquire.gpu.global.v4.u32 {%0, %1, %2, %3}, [%4];" : "=r"(b.x), "=r"(b.y), "=r"(b.z), "=r"(b.w) : "l"(f + 1) : "memory");
    if (a.x == tag && a.y == tag && a.z == tag && a.w == tag && b.x == tag && b.y == tag && b.z == tag && b.w == tag) break;
    if (it > (1u << 20)) wait_timeout();
    __nanosleep(50);
  }
  asm volatile("fence.proxy.async.global;" ::: "memory");
}

__global__ void __cluster_dims__(2, 1, 1) __launch_bounds__(384, 1)
k45_ffn(const __grid_constant__ CUtensorMap tmo) {
  extern __shared__ __align__(1024) uint8_t sm[];
  const uint32_t sbase = smem_u32(sm);
  const uint32_t afull = sbase + K4_BAR, bfull = afull + 80, bempty = bfull + 8 * K4_NS, full3 = bempty + 8 * K4_NS;
  const uint32_t empty3 = full3 + 32, afree = empty3 + 32, xchb = afree + 32;
  const int tid = threadIdx.x, lane = tid & 31;
  const int warp = __shfl_sync(~0u, tid >> 5, 0);
  const int rank = blockIdx.x & 1;
  const int n1 = (blockIdx.x >> 1) & 7, m1 = (blockIdx.x >> 4) * 2 + rank;
  const int n3 = blockIdx.x & 7, m3 = blockIdx.x >> 3;
  if (tid == 0) STAMP(3, 0);
  if (warp == 8) {
    if (elect_one()) {
#pragma unroll
      for (int i = 0; i < 10; i++) mbar_init(afull + 8 * i, 1);
#pragma unroll
      for (int i = 0; i < 4; i++) {
        mbar_init(bfull + 8 * i, 1); mbar_init(bempty + 8 * i, 4); mbar_init(full3 + 8 * i, 1); mbar_init(empty3 + 8 * i, 4);
        mbar_init(afree + 8 * i, 2);
      }
      mbar_init(xchb, 1);
      mbar_expect(xchb, 40960);
      asm volatile("fence.mbarrier_init.release.cluster;" ::: "memory");
    }
    __syncwarp();
  }
  cluster_arrive();
  if (warp >= 8) {
    cluster_wait();
    if (warp == 8) {
      if (lane == 0) STAMP(3, 7);
      const uint8_t* src = (const uint8_t*)g_wgu + n1 * 552960;
      const uint8_t* hb = (const uint8_t*)g_h + (size_t)m1 * 163840;
#pragma unroll 1
      for (int j = 0; j < 40; j++) {
        const uint32_t s8 = (j & 3) * 8, sz = j < 20 ? 14336 : 13312;
#define K4PRE 2
        if (j == K4PRE) {
          pdl_wait();
          if (lane == 0) STAMP(3, 1);
          if (elect_one()) {
#pragma unroll
            for (int kt = 0; kt < K4PRE / 2 + 1; kt++) { mbar_expect(afull + 8 * kt, 16384); bulk_ld(sbase + kt * 16384, hb + kt * 16384, 16384, afull + 8 * kt); }
          }
        }
        if (j >= 4) mbar_wait(bempty + s8, ((j >> 2) - 1) & 1);
        if (elect_one()) {
          mbar_expect(bfull + s8, sz);
          if ((j & 1) == rank) bulk_ld_mc(sbase + K4_RB + s8 * (K4_BST / 8), src, sz, bfull + s8);
          if (j > K4PRE && j < 18 && (j & 1)) {
            mbar_expect(afull + 4 + j * 4, 16384);
            bulk_ld(sbase + 8192 + j * 8192, hb + 8192 + j * 8192, 16384, afull + 4 + j * 4);
          }
        }
        src += sz;
      }
    } else if (warp == 9) {
      prefetch_map(&tmo);
      const uint32_t tag = __ldcg(&g_epoch);
#pragma unroll 1
      for (int ph = 0; ph < 2; ph++) {
        bar_sync(5 + ph, 256 + 32);
        if (lane == 0) {
          asm volatile("st.release.gpu.global.u32 [%0], %1;" ::"l"((uint32_t*)&g_flag[ph * 32 + m1 * 2] + n1), "r"(tag) : "memory");
          STAMP(3, 5 + ph);
        }
        __syncwarp();
      }
    } else {
      const uint8_t* wk = (const uint8_t*)g_wd + n3 * 276480;
      const uint8_t* ws = (const uint8_t*)g_wd + (n3 ^ 1) * 276480;
      const uint8_t* ab = (const uint8_t*)g_hh + (size_t)m3 * 442368;
      const uint32_t tag = __ldcg(&g_epoch);
#pragma unroll 1
      for (int i = 0; i < 16; i++) {
        const int kt = i < 7 ? rank * 7 + i : (i < 11 ? rank * 4 + 7 + i : 11 + i);
        const uint32_t sa = sbase + (i & 3) * 36864, fb = full3 + 8 * (i & 3);
        if (i < 4) mbar_wait(afree + 8 * i, 0);
        else mbar_wait(empty3 + 8 * (i & 3), ((i >> 2) - 1) & 1);
        if (warp == 10) {
          if (elect_one()) {
            mbar_expect(fb, i < 11 ? 36864 : 26624);
            bulk_ld(sa + 16384, wk + kt * 10240, 10240, fb);
            if (i < 11) bulk_ld(sa + 26624, ws + kt * 10240, 10240, fb);
          }
        } else {
          if (i == 0 || i == 7) {
            wait_flags(&g_flag[(i ? 32 : 0) + m3 * 2], tag);
            if (lane == 0) STAMP(4, i ? 7 : 6);
          }
          if (elect_one()) {
            if (i < 11) bulk_ld(sa, ab + kt * 16384, 16384, fb);
            else bulk_ld_mc(sa + rank * 8192, ab + kt * 16384 + rank * 8192, 8192, fb);
          }
        }
      }
    }
    __syncwarp();
    cluster_arrive();
    asm volatile("barrier.cluster.wait.aligned; // producers" ::: "memory");
  } else {
    const int wg = warp >> 2;
    const uint64_t da0 = mkdesc(sbase + wg * 8192, 128, 1024, 0);
    const uint64_t db0 = mkdesc(sbase + K4_RB, 128, 256, 0);
    cluster_wait();
    float a1[112], a2[104];
    int s = 0, ph = 0, sprev = 0;
#pragma unroll 1
    for (int j = 0; j < K4_NJ; j++) {
      if ((j * K4_G) % 4 == 0) mbar_wait(afull + 2 * K4_G * j, 0);
      mbar_wait(bfull + 8 * s, ph);
      if (j == 0 && tid == 0) STAMP(3, 2);
      const uint64_t da = da0 + ((j * K4_G) >> 2) * 1024 + ((j * K4_G) & 3) * 16, db = db0 + s * (K4_BST >> 4);
      WG_FENCE();
#pragma unroll
      for (int k = 0; k < K4_G; k++) wgmma_ss_n224(a1, da + k * 16, db + k * 448, (j | k) != 0);
      WG_COMMIT();
      if (j > 0) {
        WG_WAIT(1);
        if ((tid & 127) < 2) mbar_arrive_cta(bempty + 8 * sprev, tid & 1);
      }
      sprev = s;
      if (++s == K4_NS) { s = 0; ph ^= 1; }
    }
    float r0, r1;
    {
      const float* hp = &g_hpart[(lane & 3) * 2 * S_ + m1 * 128 + warp * 16 + (lane >> 2)];
      r0 = __ldcg(hp) + __ldcg(hp + S_);
      r1 = __ldcg(hp + 8) + __ldcg(hp + S_ + 8);
    }
    float acc[80];
    uint8_t* hd = (uint8_t*)g_hh + (size_t)m1 * 442368 + warp * 2048 + lane * 4;
    {
      r0 += __shfl_xor_sync(~0u, r0, 1); r1 += __shfl_xor_sync(~0u, r1, 1);
      r0 += __shfl_xor_sync(~0u, r0, 2); r1 += __shfl_xor_sync(~0u, r1, 2);
      r0 = __frcp_rn(r0 * (1.f / D_) + 1e-5f); r1 = __frcp_rn(r1 * (1.f / D_) + 1e-5f);
    }
    WG_WAIT(0);
    fence_regs(a1);
    if ((tid & 127) < 2) mbar_arrive_cta(bempty + 8 * ((K4_NJ - 1) % K4_NS), tid & 1);
    if (tid == 0) STAMP(3, 3);
    uint32_t pk[28];
#define PACK_H(a, off, c) do { \
      pk[2 * (c)] = pack_bf16(a[4 * (c)] * r0 * a[off + 4 * (c)], a[4 * (c) + 1] * r0 * a[off + 1 + 4 * (c)]); \
      pk[2 * (c) + 1] = pack_bf16(a[4 * (c) + 2] * r1 * a[off + 2 + 4 * (c)], a[4 * (c) + 3] * r1 * a[off + 3 + 4 * (c)]); \
      asm volatile("" : "+r"(pk[2 * (c)]), "+r"(pk[2 * (c) + 1])::"memory"); } while (0)
#define STORE_H(q, c) do { uint8_t* p_ = hd + img_off(q); *(uint32_t*)p_ = pk[2 * (c)]; *(uint32_t*)(p_ + 1024) = pk[2 * (c) + 1]; } while (0)
#pragma unroll
    for (int c = 0; c < 14; c++) PACK_H(a1, 56, c);
#pragma unroll 1
    for (int j = 0; j < K4_NJ; j++) {
      mbar_wait(bfull + 8 * s, ph);
      const uint64_t da = da0 + ((j * K4_G) >> 2) * 1024 + ((j * K4_G) & 3) * 16, db = db0 + s * (K4_BST >> 4);
      WG_FENCE();
#pragma unroll
      for (int k = 0; k < K4_G; k++) wgmma_ss_n208(a2, da + k * 16, db + k * 416, (j | k) != 0);
      WG_COMMIT();
      if (j > 0) {
        WG_WAIT(1);
        if (j <= K4_NJ - K4_NS && (tid & 127) < 2) mbar_arrive_cta(bempty + 8 * sprev, tid & 1);
        if (j * K4_G >= 12 && ((j * K4_G) & 7) == 4 && (tid & 127) == 0) mbar_arrive(afree + (j * K4_G - 12));
      } else {
#pragma unroll
        for (int c = 0; c < 14; c++) STORE_H(n1 * 14 + c, c);
        bar_arrive(5, 256 + 32);
      }
      sprev = s;
      if (++s == K4_NS) { s = 0; ph ^= 1; }
    }
    WG_WAIT(0);
    fence_regs(a2);
    if (tid == 0) STAMP(3, 4);
#pragma unroll
    for (int c = 0; c < 13; c++) PACK_H(a2, 52, c);
    float (&keep)[40] = ((Acc<40>*)acc)->v;
    const uint64_t db3 = mkdesc(sbase + 16384, 128, 1024, 0);
#pragma unroll 1
    for (int i = 0; i < 11; i++) {
      mbar_wait(full3 + 8 * (i & 3), (i >> 2) & 1);
      if (i == 0 && tid == 0) STAMP(4, 2);
      const uint64_t da = da0 + (i & 3) * 2304, db = db3 + (i & 3) * 2304;
      WG_FENCE();
#pragma unroll
      for (int k = 0; k < 4; k++) wgmma_ss_n160(acc, da + k * 16, db + k * 16, (i | k) != 0);
      WG_COMMIT();
      if (i > 0) {
        WG_WAIT(1);
        if ((tid & 127) < 2) mbar_arrive_cta(empty3 + 8 * ((i - 1) & 3), tid & 1);
      } else {
#pragma unroll
        for (int c = 0; c < 13; c++) STORE_H(112 + n1 * 13 + c, c);
        bar_arrive(6, 256 + 32);
      }
    }
    const int g = lane >> 2, c = lane & 3, row = m3 * 128 + warp * 16 + g;
    const uint8_t* himg = (const uint8_t*)g_h + (size_t)m3 * 163840 + warp * 2048 + lane * 4;
    uint32_t rv[20];
    const float mu0 = __ldcg(&g_hmean[row]), mu1 = __ldcg(&g_hmean[row + 8]);
#pragma unroll
    for (int j = 0; j < 10; j++) {
      rv[2 * j] = __ldcg((const uint32_t*)(himg + img_off(n3 * 10 + j)));
      rv[2 * j + 1] = __ldcg((const uint32_t*)(himg + img_off(n3 * 10 + j) + 1024));
    }
    const uint32_t rx = mapa(sbase + K4_XCH + tid * 16, rank ^ 1), rb = mapa(xchb, rank ^ 1);
    WG_WAIT(0);
    fence_regs(acc);
    if ((tid & 127) < 2) mbar_arrive_cta(empty3 + 16, tid & 1);
    if (tid == 0) STAMP(4, 1);
#pragma unroll
    for (int i = 11; i < 16; i++) {
      mbar_wait(full3 + 8 * (i & 3), (i >> 2) & 1);
      const uint64_t da = da0 + (i & 3) * 2304, db = db3 + (i & 3) * 2304;
      WG_FENCE();
#pragma unroll
      for (int k = 0; k < 4; k++) wgmma_ss_n80(keep, da + k * 16, db + k * 16, 1);
      WG_COMMIT();
      if (i == 12) {
        WG_WAIT(1);
        if ((tid & 127) < 2) mbar_arrive_cta(empty3 + 24, tid & 1);
      }
#pragma unroll
      for (int j = (i - 11) * 3; j < (i - 11) * 3 + 3; j++)
        if (j < 10) st_async4(rx + j * 4096, acc[40 + 4 * j], acc[41 + 4 * j], acc[42 + 4 * j], acc[43 + 4 * j], rb);
    }
    cluster_arrive();
    WG_WAIT(0);
    fence_regs(keep);
    if (tid == 0) STAMP(4, 3);
    mbar_wait(xchb, 0);
    if (tid == 0) STAMP(4, 5);
    uint8_t* sp = sm + K4_STG + (warp * 16 + g) * 160 + c * 4;
#pragma unroll
    for (int j = 0; j < 10; j++) {
      const float4 p = *(const float4*)(sm + K4_XCH + tid * 16 + j * 4096);
      *(uint32_t*)(sp + j * 16) = pack_bf16((keep[4 * j] + p.x) + (bf_lo(rv[2 * j]) + mu0), (keep[4 * j + 1] + p.y) + (bf_hi(rv[2 * j]) + mu0));
      *(uint32_t*)(sp + 1280 + j * 16) = pack_bf16((keep[4 * j + 2] + p.z) + (bf_lo(rv[2 * j + 1]) + mu1), (keep[4 * j + 3] + p.w) + (bf_hi(rv[2 * j + 1]) + mu1));
    }
    fence_async();
    bar_sync(1 + wg, 128);
    if ((tid & 127) == 0) {
      tma2d_st(&tmo, n3 * 80, m3 * 128 + wg * 64, sbase + K4_STG + wg * 10240);
      bulk_commit_wait();
    }
    __syncwarp();
    if (tid == 0) STAMP(4, 4);
    asm volatile("barrier.cluster.wait.aligned; // consumers" ::: "memory");
  }
}

typedef CUresult (*EncodeFn)(CUtensorMap*, CUtensorMapDataType, cuuint32_t, void*, const cuuint64_t*, const cuuint64_t*,
                             const cuuint32_t*, const cuuint32_t*, CUtensorMapInterleave, CUtensorMapSwizzle,
                             CUtensorMapL2promotion, CUtensorMapFloatOOBfill);

static CUtensorMap make_map(EncodeFn enc, const void* p, uint64_t inner, uint64_t outer, uint32_t box_inner,
                            uint32_t box_outer, CUtensorMapSwizzle swz) {
  CUtensorMap m;
  cuuint64_t gd[2] = {inner, outer};
  cuuint64_t gs[1] = {inner * 2};
  cuuint32_t bd[2] = {box_inner, box_outer};
  cuuint32_t es[2] = {1, 1};
  enc(&m, CU_TENSOR_MAP_DATA_TYPE_BFLOAT16, 2, (void*)p, gd, gs, bd, es, CU_TENSOR_MAP_INTERLEAVE_NONE, swz,
      CU_TENSOR_MAP_L2_PROMOTION_L2_256B, CU_TENSOR_MAP_FLOAT_OOB_FILL_NONE);
  return m;
}

static CUtensorMap make_map_img(EncodeFn enc, const void* p, uint64_t k, uint64_t n, uint32_t rows, uint32_t chunks,
                                uint32_t groups) {
  CUtensorMap m;
  cuuint64_t gd[4] = {8, rows, n / 8, k / rows};
  cuuint64_t gs[3] = {n * 2, 16, n * 2 * rows};
  cuuint32_t bd[4] = {8, rows, chunks, groups};
  cuuint32_t es[4] = {1, 1, 1, 1};
  enc(&m, CU_TENSOR_MAP_DATA_TYPE_BFLOAT16, 4, (void*)p, gd, gs, bd, es, CU_TENSOR_MAP_INTERLEAVE_NONE,
      CU_TENSOR_MAP_SWIZZLE_NONE, CU_TENSOR_MAP_L2_PROMOTION_L2_128B, CU_TENSOR_MAP_FLOAT_OOB_FILL_NONE);
  return m;
}

template <typename... KArgs, typename... Args>
static void launch(void (*k)(KArgs...), int grid, int threads, int smem, bool pdl, Args... args) {
  cudaLaunchConfig_t cfg = {};
  cfg.gridDim = dim3(grid);
  cfg.blockDim = dim3(threads);
  cfg.dynamicSmemBytes = smem;
  cfg.stream = cudaStreamPerThread;
  cudaLaunchAttribute at[1];
  at[0].id = cudaLaunchAttributeProgrammaticStreamSerialization;
  at[0].val.programmaticStreamSerializationAllowed = 1;
  cfg.attrs = at;
  cfg.numAttrs = pdl ? 1 : 0;
  cudaLaunchKernelEx(&cfg, k, KArgs(args)...);
}

extern "C" void kernel_launch(void* const* d_in, const int* in_sizes, int n_in, void* d_out, int out_size) {
  const bf16* x = (const bf16*)d_in[0];
  const bf16* wqkv = (const bf16*)d_in[1];
  const bf16* wo = (const bf16*)d_in[2];
  const bf16* wg = (const bf16*)d_in[4];
  const bf16* wu = (const bf16*)d_in[5];
  const bf16* wd = (const bf16*)d_in[6];

  static EncodeFn enc = nullptr;
  static void *p_o, *p_wo;
  if (!enc) {
    void* fn = nullptr;
    cudaDriverEntryPointQueryResult qr;
    cudaGetDriverEntryPoint("cuTensorMapEncodeTiled", &fn, cudaEnableDefault, &qr);
    enc = (EncodeFn)fn;
    cudaGetSymbolAddress(&p_o, g_o);
    cudaGetSymbolAddress(&p_wo, g_wo);
    cudaFuncSetAttribute(k1_qkv, cudaFuncAttributeMaxDynamicSharedMemorySize, K1_SMEM);
    cudaFuncSetAttribute(k2_attn, cudaFuncAttributeMaxDynamicSharedMemorySize, K2_SMEM);
    cudaFuncSetAttribute(k3_proj<3, 4, true>, cudaFuncAttributeMaxDynamicSharedMemorySize, K3_SMEM);
    cudaFuncSetAttribute(k45_ffn, cudaFuncAttributeMaxDynamicSharedMemorySize, K4_SMEM);
  }
  const CUtensorMap tmx = make_map(enc, x, D_, S_, 64, 96, CU_TENSOR_MAP_SWIZZLE_128B);
  const CUtensorMap tmw = make_map(enc, wqkv, 3 * D_, D_, 32, 64, CU_TENSOR_MAP_SWIZZLE_64B);
  const CUtensorMap tmxr = make_map(enc, x, D_, S_, 80, 64, CU_TENSOR_MAP_SWIZZLE_NONE);
  Maps5 maps;
  maps.m[0] = make_map_img(enc, wg, D_, F_, 16, 14, 2); maps.m[1] = make_map_img(enc, wu, D_, F_, 16, 14, 2);
  maps.m[2] = make_map_img(enc, wg, D_, F_, 16, 13, 2); maps.m[3] = make_map_img(enc, wu, D_, F_, 16, 13, 2);
  maps.m[4] = make_map_img(enc, wd, F_, D_, 64, 10, 1);
  const CUtensorMap tmout = make_map(enc, d_out, D_, S_, 80, 64, CU_TENSOR_MAP_SWIZZLE_NONE);

  launch(k1_qkv, 132, 512, K1_SMEM, false, tmx, tmw, x, wqkv, wo);
  launch(k2_attn, 128, 512, K2_SMEM, true, maps, 0x007f007fu);
  launch(k3_proj<3, 4, true>, 128, 384, K3_SMEM, true, tmxr, (const uint4*)p_o, (const uint4*)p_wo);
  launch(k45_ffn, 128, 384, K4_SMEM, true, tmout);
}
```

```cpp
#include <cuda_runtime.h>
#include <cuda_bf16.h>
#include <cuda.h>
#include <stdint.h>

typedef __nv_bfloat16 bf16;

constexpr int S_ = 2048, D_ = 640, F_ = 1728;
constexpr int HEAD_IMG = 98304;
#define PMASK 0xDB6D
constexpr uint32_t POLY_MASK = PMASK;
constexpr float QSCALE = 0.22360679774997896f * 1.4426950408889634f;

__device__ __align__(1024) uint4 g_qkv[96 * HEAD_IMG / 16];
__device__ __align__(1024) uint4 g_o[S_ * D_ / 8];
__device__ __align__(1024) uint4 g_h[S_ * D_ / 8];
__device__ __align__(1024) uint4 g_hh[S_ * F_ / 8];
__device__ __align__(1024) uint4 g_wo[D_ * D_ / 8];
__device__ __align__(1024) uint4 g_wgu[2 * D_ * F_ / 8];
__device__ __align__(1024) uint4 g_wd[F_ * D_ / 8];
__device__ uint4 g_rowstat[S_];
__device__ uint4 g_cpart[10 * 12 * 80];
__device__ float g_nrm[64 * 128];
__device__ uint4 g_wm[D_];
__device__ float g_hmean[S_];
__device__ float g_hpart[8 * S_];
__device__ uint4 g_flag[2 * 16 * 2];
__device__ unsigned g_epoch;

#define STAMP(k, i)
__device__ __forceinline__ uint32_t smem_u32(const void* p) { return (uint32_t)__cvta_generic_to_shared(p); }
__device__ __forceinline__ void mbar_init(uint32_t a, uint32_t c) {
  asm volatile("mbarrier.init.shared::cta.b64 [%0], %1;" ::"r"(a), "r"(c) : "memory");
}
__device__ __forceinline__ void mbar_expect(uint32_t a, uint32_t bytes) {
  asm volatile("mbarrier.arrive.expect_tx.shared::cta.b64 _, [%0], %1;" ::"r"(a), "r"(bytes) : "memory");
}
__device__ __forceinline__ void mbar_arrive(uint32_t a) {
  asm volatile("mbarrier.arrive.shared::cta.b64 _, [%0];" ::"r"(a) : "memory");
}
__device__ __forceinline__ void mbar_arrive_cta(uint32_t a, uint32_t cta) {
  asm volatile("{\n.reg .b32 r;\nmapa.shared::cluster.u32 r, %0, %1;\n"
               "mbarrier.arrive.shared::cluster.b64 _, [r];\n}" ::"r"(a), "r"(cta) : "memory");
}
__device__ __forceinline__ bool mbar_try(uint32_t a, uint32_t ph) {
  uint32_t ok;
  asm volatile("{\n.reg .pred p;\nmbarrier.try_wait.parity.shared::cta.b64 p, [%1], %2;\nselp.u32 %0, 1, 0, p;\n}"
               : "=r"(ok) : "r"(a), "r"(ph) : "memory");
  return ok;
}
__device__ __noinline__ void wait_timeout() { __trap(); }
__device__ __forceinline__ void mbar_wait(uint32_t a, uint32_t ph) {
  if (mbar_try(a, ph)) return;
  uint32_t it = 0;
  while (!mbar_try(a, ph)) if (++it > (1u << 22)) wait_timeout();
}
__device__ __forceinline__ void tma2d(uint32_t dst, const CUtensorMap* m, int c0, int c1, uint32_t bar) {
  asm volatile("cp.async.bulk.tensor.2d.shared::cluster.global.mbarrier::complete_tx::bytes [%0], [%1, {%3, %4}], [%2];"
               ::"r"(dst), "l"(m), "r"(bar), "r"(c0), "r"(c1) : "memory");
}
__device__ __forceinline__ void tma2d_mc(uint32_t dst, const CUtensorMap* m, int c0, int c1, uint32_t bar) {
  asm volatile("cp.async.bulk.tensor.2d.shared::cluster.global.mbarrier::complete_tx::bytes.multicast::cluster "
               "[%0], [%1, {%3, %4}], [%2], %5;"
               ::"r"(dst), "l"(m), "r"(bar), "r"(c0), "r"(c1), "h"((uint16_t)3) : "memory");
}
__device__ __forceinline__ void bulk_ld(uint32_t dst, const void* src, uint32_t bytes, uint32_t bar) {
  asm volatile("cp.async.bulk.shared::cluster.global.mbarrier::complete_tx::bytes [%0], [%1], %2, [%3];"
               ::"r"(dst), "l"(src), "r"(bytes), "r"(bar) : "memory");
}
__device__ __forceinline__ void bulk_ld_mc(uint32_t dst, const void* src, uint32_t bytes, uint32_t bar) {
  asm volatile("cp.async.bulk.shared::cluster.global.mbarrier::complete_tx::bytes.multicast::cluster "
               "[%0], [%1], %2, [%3], %4;"
               ::"r"(dst), "l"(src), "r"(bytes), "r"(bar), "h"((uint16_t)3) : "memory");
}
__device__ __forceinline__ void cluster_arrive() { asm volatile("barrier.cluster.arrive.relaxed.aligned;" ::: "memory"); }
__device__ __forceinline__ void cluster_wait() { asm volatile("barrier.cluster.wait.aligned;" ::: "memory"); }
__device__ __forceinline__ void bulk_st(void* dst, uint32_t src, uint32_t bytes) {
  asm volatile("cp.async.bulk.global.shared::cta.bulk_group [%0], [%1], %2;" ::"l"(dst), "r"(src), "r"(bytes) : "memory");
}
__device__ __forceinline__ void tma2d_st(const CUtensorMap* m, int c0, int c1, uint32_t src) {
  asm volatile("cp.async.bulk.tensor.2d.global.shared::cta.bulk_group [%0, {%2, %3}], [%1];"
               ::"l"(m), "r"(src), "r"(c0), "r"(c1) : "memory");
}
__device__ __forceinline__ void bulk_commit_wait() {
  asm volatile("cp.async.bulk.commit_group;\ncp.async.bulk.wait_group.read 0;" ::: "memory");
}
__device__ __forceinline__ uint32_t mapa(uint32_t a, uint32_t cta) {
  uint32_t r;
  asm("mapa.shared::cluster.u32 %0, %1, %2;" : "=r"(r) : "r"(a), "r"(cta));
  return r;
}
__device__ __forceinline__ void st_async4(uint32_t dst, float a, float b, float c, float d, uint32_t bar) {
  asm volatile("st.async.shared::cluster.mbarrier::complete_tx::bytes.v4.f32 [%0], {%1, %2, %3, %4}, [%5];"
               ::"r"(dst), "f"(a), "f"(b), "f"(c), "f"(d), "r"(bar) : "memory");
}
__device__ __forceinline__ void fence_async() { asm volatile("fence.proxy.async.shared::cta;" ::: "memory"); }
__device__ __forceinline__ void prefetch_map(const CUtensorMap* m) {
  asm volatile("prefetch.tensormap [%0];" ::"l"(m) : "memory");
}
__device__ __forceinline__ bool elect_one() {
  uint32_t p;
  asm volatile("{\n.reg .pred q;\nelect.sync _|q, 0xffffffff;\nselp.u32 %0, 1, 0, q;\n}" : "=r"(p));
  return p;
}
__device__ __forceinline__ void pdl_wait() { asm volatile("griddepcontrol.wait;" ::: "memory"); }
__device__ __forceinline__ void pdl_trigger() { asm volatile("griddepcontrol.launch_dependents;" ::: "memory"); }
__device__ __forceinline__ void bar_sync(int id, int n) { asm volatile("bar.sync %0, %1;" ::"r"(id), "r"(n) : "memory"); }
__device__ __forceinline__ void bar_arrive(int id, int n) { asm volatile("bar.arrive %0, %1;" ::"r"(id), "r"(n) : "memory"); }
#define WG_FENCE() asm volatile("wgmma.fence.sync.aligned;" ::: "memory")
#define WG_COMMIT() asm volatile("wgmma.commit_group.sync.aligned;" ::: "memory")
#define WG_WAIT(n) asm volatile("wgmma.wait_group.sync.aligned %0;" ::"n"(n) : "memory")
__device__ __forceinline__ uint64_t mkdesc(uint32_t addr, uint32_t lbo, uint32_t sbo, uint32_t sw) {
  return (uint64_t)((addr & 0x3FFFF) >> 4) | ((uint64_t)(lbo >> 4) << 16) | ((uint64_t)(sbo >> 4) << 32) |
         ((uint64_t)sw << 62);
}
template <int N> __device__ __forceinline__ void fence_regs(float (&r)[N]) {
#pragma unroll
  for (int i = 0; i < N; i++) asm volatile("" : "+f"(r[i])::"memory");
}
__device__ __forceinline__ uint32_t pack_bf16(float lo, float hi) {
  uint32_t r;
  asm("cvt.rn.bf16x2.f32 %0, %1, %2;" : "=r"(r) : "f"(hi), "f"(lo));
  return r;
}
__device__ __forceinline__ float bf_lo(uint32_t v) { return __uint_as_float(v << 16); }
__device__ __forceinline__ float bf_hi(uint32_t v) { return __uint_as_float(v & 0xffff0000u); }
__device__ __forceinline__ float ex2(float x) {
  float y;
  asm("ex2.approx.ftz.f32 %0, %1;" : "=f"(y) : "f"(x));
  return y;
}
__device__ __forceinline__ uint4 ldg_nc(const void* p) {
  uint4 v;
  asm volatile("ld.global.nc.L1::no_allocate.v4.u32 {%0, %1, %2, %3}, [%4];"
               : "=r"(v.x), "=r"(v.y), "=r"(v.z), "=r"(v.w) : "l"(p));
  return v;
}

__device__ __forceinline__ uint4 ld_relaxed(const uint4* p) {
  uint64_t a, b;
  asm volatile("ld.relaxed.gpu.global.v2.u64 {%0, %1}, [%2];" : "=l"(a), "=l"(b) : "l"(p) : "memory");
  return make_uint4((uint32_t)a, (uint32_t)(a >> 32), (uint32_t)b, (uint32_t)(b >> 32));
}
__device__ __forceinline__ void st_relaxed(uint4* p, float x, float y, uint32_t tag) {
  const uint64_t a = ((uint64_t)tag << 32) | __float_as_uint(x), b = ((uint64_t)tag << 32) | __float_as_uint(y);
  asm volatile("st.relaxed.gpu.global.v2.u64 [%0], {%1, %2};" ::"l"(p), "l"(a), "l"(b) : "memory");
}
__device__ __forceinline__ void tma4d(uint32_t dst, const CUtensorMap* m, int c2, int c3, uint32_t bar) {
  asm volatile("cp.async.bulk.tensor.4d.shared::cluster.global.mbarrier::complete_tx::bytes [%0], [%1, {%3, %3, %4, %5}], [%2];"
               ::"r"(dst), "l"(m), "r"(bar), "r"(0), "r"(c2), "r"(c3) : "memory");
}
#define ACC8(a, v) do { a[0] += bf_lo(v.x); a[1] += bf_hi(v.x); a[2] += bf_lo(v.y); a[3] += bf_hi(v.y); \
                        a[4] += bf_lo(v.z); a[5] += bf_hi(v.z); a[6] += bf_lo(v.w); a[7] += bf_hi(v.w); } while (0)

__device__ __forceinline__ void wgmma_ss_n224(float (&d)[112], uint64_t da, uint64_t db, int sd) {
  asm volatile("{\n.reg .pred p;\nsetp.ne.b32 p, %114, 0;\n"
      "wgmma.mma_async.sync.aligned.m64n224k16.f32.bf16.bf16 {"
      "%0, %1, %2, %3, %4, %5, %6, %7, %8, %9, %10, %11, %12, %13, %14, %15, "
      "%16, %17, %18, %19, %20, %21, %22, %23, %24, %25, %26, %27, %28, %29, %30, %31, "
      "%32, %33, %34, %35, %36, %37, %38, %39, %40, %41, %42, %43, %44, %45, %46, %47, "
      "%48, %49, %50, %51, %52, %53, %54, %55, %56, %57, %58, %59, %60, %61, %62, %63, "
      "%64, %65, %66, %67, %68, %69, %70, %71, %72, %73, %74, %75, %76, %77, %78, %79, "
      "%80, %81, %82, %83, %84, %85, %86, %87, %88, %89, %90, %91, %92, %93, %94, %95, "
      "%96, %97, %98, %99, %100, %101, %102, %103, %104, %105, %106, %107, %108, %109, %110, %111"
      "}, %112, %113, p, 1, 1, 0, 1;\n}\n"
    : "+f"(d[0]), "+f"(d[1]), "+f"(d[2]), "+f"(d[3]), "+f"(d[4]), "+f"(d[5]), "+f"(d[6]), "+f"(d[7]),
      "+f"(d[8]), "+f"(d[9]), "+f"(d[10]), "+f"(d[11]), "+f"(d[12]), "+f"(d[13]), "+f"(d[14]), "+f"(d[15]),
      "+f"(d[16]), "+f"(d[17]), "+f"(d[18]), "+f"(d[19]), "+f"(d[20]), "+f"(d[21]), "+f"(d[22]), "+f"(d[23]),
      "+f"(d[24]), "+f"(d[25]), "+f"(d[26]), "+f"(d[27]), "+f"(d[28]), "+f"(d[29]), "+f"(d[30]), "+f"(d[31]),
      "+f"(d[32]), "+f"(d[33]), "+f"(d[34]), "+f"(d[35]), "+f"(d[36]), "+f"(d[37]), "+f"(d[38]), "+f"(d[39]),
      "+f"(d[40]), "+f"(d[41]), "+f"(d[42]), "+f"(d[43]), "+f"(d[44]), "+f"(d[45]), "+f"(d[46]), "+f"(d[47]),
      "+f"(d[48]), "+f"(d[49]), "+f"(d[50]), "+f"(d[51]), "+f"(d[52]), "+f"(d[53]), "+f"(d[54]), "+f"(d[55]),
      "+f"(d[56]), "+f"(d[57]), "+f"(d[58]), "+f"(d[59]), "+f"(d[60]), "+f"(d[61]), "+f"(d[62]), "+f"(d[63]),
      "+f"(d[64]), "+f"(d[65]), "+f"(d[66]), "+f"(d[67]), "+f"(d[68]), "+f"(d[69]), "+f"(d[70]), "+f"(d[71]),
      "+f"(d[72]), "+f"(d[73]), "+f"(d[74]), "+f"(d[75]), "+f"(d[76]), "+f"(d[77]), "+f"(d[78]), "+f"(d[79]),
      "+f"(d[80]), "+f"(d[81]), "+f"(d[82]), "+f"(d[83]), "+f"(d[84]), "+f"(d[85]), "+f"(d[86]), "+f"(d[87]),
      "+f"(d[88]), "+f"(d[89]), "+f"(d[90]), "+f"(d[91]), "+f"(d[92]), "+f"(d[93]), "+f"(d[94]), "+f"(d[95]),
      "+f"(d[96]), "+f"(d[97]), "+f"(d[98]), "+f"(d[99]), "+f"(d[100]), "+f"(d[101]), "+f"(d[102]), "+f"(d[103]),
      "+f"(d[104]), "+f"(d[105]), "+f"(d[106]), "+f"(d[107]), "+f"(d[108]), "+f"(d[109]), "+f"(d[110]), "+f"(d[111])
    : "l"(da), "l"(db), "r"(sd));
}
__device__ __forceinline__ void wgmma_ss_n208(float (&d)[104], uint64_t da, uint64_t db, int sd) {
  asm volatile("{\n.reg .pred p;\nsetp.ne.b32 p, %106, 0;\n"
      "wgmma.mma_async.sync.aligned.m64n208k16.f32.bf16.bf16 {"
      "%0, %1, %2, %3, %4, %5, %6, %7, %8, %9, %10, %11, %12, %13, %14, %15, "
      "%16, %17, %18, %19, %20, %21, %22, %23, %24, %25, %26, %27, %28, %29, %30, %31, "
      "%32, %33, %34, %35, %36, %37, %38, %39, %40, %41, %42, %43, %44, %45, %46, %47, "
      "%48, %49, %50, %51, %52, %53, %54, %55, %56, %57, %58, %59, %60, %61, %62, %63, "
      "%64, %65, %66, %67, %68, %69, %70, %71, %72, %73, %74, %75, %76, %77, %78, %79, "
      "%80, %81, %82, %83, %84, %85, %86, %87, %88, %89, %90, %91, %92, %93, %94, %95, "
      "%96, %97, %98, %99, %100, %101, %102, %103"
      "}, %104, %105, p, 1, 1, 0, 1;\n}\n"
    : "+f"(d[0]), "+f"(d[1]), "+f"(d[2]), "+f"(d[3]), "+f"(d[4]), "+f"(d[5]), "+f"(d[6]), "+f"(d[7]),
      "+f"(d[8]), "+f"(d[9]), "+f"(d[10]), "+f"(d[11]), "+f"(d[12]), "+f"(d[13]), "+f"(d[14]), "+f"(d[15]),
      "+f"(d[16]), "+f"(d[17]), "+f"(d[18]), "+f"(d[19]), "+f"(d[20]), "+f"(d[21]), "+f"(d[22]), "+f"(d[23]),
      "+f"(d[24]), "+f"(d[25]), "+f"(d[26]), "+f"(d[27]), "+f"(d[28]), "+f"(d[29]), "+f"(d[30]), "+f"(d[31]),
      "+f"(d[32]), "+f"(d[33]), "+f"(d[34]), "+f"(d[35]), "+f"(d[36]), "+f"(d[37]), "+f"(d[38]), "+f"(d[39]),
      "+f"(d[40]), "+f"(d[41]), "+f"(d[42]), "+f"(d[43]), "+f"(d[44]), "+f"(d[45]), "+f"(d[46]), "+f"(d[47]),
      "+f"(d[48]), "+f"(d[49]), "+f"(d[50]), "+f"(d[51]), "+f"(d[52]), "+f"(d[53]), "+f"(d[54]), "+f"(d[55]),
      "+f"(d[56]), "+f"(d[57]), "+f"(d[58]), "+f"(d[59]), "+f"(d[60]), "+f"(d[61]), "+f"(d[62]), "+f"(d[63]),
      "+f"(d[64]), "+f"(d[65]), "+f"(d[66]), "+f"(d[67]), "+f"(d[68]), "+f"(d[69]), "+f"(d[70]), "+f"(d[71]),
      "+f"(d[72]), "+f"(d[73]), "+f"(d[74]), "+f"(d[75]), "+f"(d[76]), "+f"(d[77]), "+f"(d[78]), "+f"(d[79]),
      "+f"(d[80]), "+f"(d[81]), "+f"(d[82]), "+f"(d[83]), "+f"(d[84]), "+f"(d[85]), "+f"(d[86]), "+f"(d[87]),
      "+f"(d[88]), "+f"(d[89]), "+f"(d[90]), "+f"(d[91]), "+f"(d[92]), "+f"(d[93]), "+f"(d[94]), "+f"(d[95]),
      "+f"(d[96]), "+f"(d[97]), "+f"(d[98]), "+f"(d[99]), "+f"(d[100]), "+f"(d[101]), "+f"(d[102]), "+f"(d[103])
    : "l"(da), "l"(db), "r"(sd));
}
__device__ __forceinline__ void wgmma_ss_n168(float (&d)[84], uint64_t da, uint64_t db, int sd) {
  asm volatile("{\n.reg .pred p;\nsetp.ne.b32 p, %86, 0;\n"
      "wgmma.mma_async.sync.aligned.m64n168k16.f32.bf16.bf16 {"
      "%0, %1, %2, %3, %4, %5, %6, %7, %8, %9, %10, %11, %12, %13, %14, %15, "
      "%16, %17, %18, %19, %20, %21, %22, %23, %24, %25, %26, %27, %28, %29, %30, %31, "
      "%32, %33, %34, %35, %36, %37, %38, %39, %40, %41, %42, %43, %44, %45, %46, %47, "
      "%48, %49, %50, %51, %52, %53, %54, %55, %56, %57, %58, %59, %60, %61, %62, %63, "
      "%64, %65, %66, %67, %68, %69, %70, %71, %72, %73, %74, %75, %76, %77, %78, %79, "
      "%80, %81, %82, %83"
      "}, %84, %85, p, 1, 1, 0, 1;\n}\n"
    : "+f"(d[0]), "+f"(d[1]), "+f"(d[2]), "+f"(d[3]), "+f"(d[4]), "+f"(d[5]), "+f"(d[6]), "+f"(d[7]),
      "+f"(d[8]), "+f"(d[9]), "+f"(d[10]), "+f"(d[11]), "+f"(d[12]), "+f"(d[13]), "+f"(d[14]), "+f"(d[15]),
      "+f"(d[16]), "+f"(d[17]), "+f"(d[18]), "+f"(d[19]), "+f"(d[20]), "+f"(d[21]), "+f"(d[22]), "+f"(d[23]),
      "+f"(d[24]), "+f"(d[25]), "+f"(d[26]), "+f"(d[27]), "+f"(d[28]), "+f"(d[29]), "+f"(d[30]), "+f"(d[31]),
      "+f"(d[32]), "+f"(d[33]), "+f"(d[34]), "+f"(d[35]), "+f"(d[36]), "+f"(d[37]), "+f"(d[38]), "+f"(d[39]),
      "+f"(d[40]), "+f"(d[41]), "+f"(d[42]), "+f"(d[43]), "+f"(d[44]), "+f"(d[45]), "+f"(d[46]), "+f"(d[47]),
      "+f"(d[48]), "+f"(d[49]), "+f"(d[50]), "+f"(d[51]), "+f"(d[52]), "+f"(d[53]), "+f"(d[54]), "+f"(d[55]),
      "+f"(d[56]), "+f"(d[57]), "+f"(d[58]), "+f"(d[59]), "+f"(d[60]), "+f"(d[61]), "+f"(d[62]), "+f"(d[63]),
      "+f"(d[64]), "+f"(d[65]), "+f"(d[66]), "+f"(d[67]), "+f"(d[68]), "+f"(d[69]), "+f"(d[70]), "+f"(d[71]),
      "+f"(d[72]), "+f"(d[73]), "+f"(d[74]), "+f"(d[75]), "+f"(d[76]), "+f"(d[77]), "+f"(d[78]), "+f"(d[79]),
      "+f"(d[80]), "+f"(d[81]), "+f"(d[82]), "+f"(d[83])
    : "l"(da), "l"(db), "r"(sd));
}
__device__ __forceinline__ void wgmma_ss_n160(float (&d)[80], uint64_t da, uint64_t db, int sd) {
  asm volatile("{\n.reg .pred p;\nsetp.ne.b32 p, %82, 0;\n"
      "wgmma.mma_async.sync.aligned.m64n160k16.f32.bf16.bf16 {"
      "%0, %1, %2, %3, %4, %5, %6, %7, %8, %9, %10, %11, %12, %13, %14, %15, "
      "%16, %17, %18, %19, %20, %21, %22, %23, %24, %25, %26, %27, %28, %29, %30, %31, "
      "%32, %33, %34, %35, %36, %37, %38, %39, %40, %41, %42, %43, %44, %45, %46, %47, "
      "%48, %49, %50, %51, %52, %53, %54, %55, %56, %57, %58, %59, %60, %61, %62, %63, "
      "%64, %65, %66, %67, %68, %69, %70, %71, %72, %73, %74, %75, %76, %77, %78, %79"
      "}, %80, %81, p, 1, 1, 0, 1;\n}\n"
    : "+f"(d[0]), "+f"(d[1]), "+f"(d[2]), "+f"(d[3]), "+f"(d[4]), "+f"(d[5]), "+f"(d[6]), "+f"(d[7]),
      "+f"(d[8]), "+f"(d[9]), "+f"(d[10]), "+f"(d[11]), "+f"(d[12]), "+f"(d[13]), "+f"(d[14]), "+f"(d[15]),
      "+f"(d[16]), "+f"(d[17]), "+f"(d[18]), "+f"(d[19]), "+f"(d[20]), "+f"(d[21]), "+f"(d[22]), "+f"(d[23]),
      "+f"(d[24]), "+f"(d[25]), "+f"(d[26]), "+f"(d[27]), "+f"(d[28]), "+f"(d[29]), "+f"(d[30]), "+f"(d[31]),
      "+f"(d[32]), "+f"(d[33]), "+f"(d[34]), "+f"(d[35]), "+f"(d[36]), "+f"(d[37]), "+f"(d[38]), "+f"(d[39]),
      "+f"(d[40]), "+f"(d[41]), "+f"(d[42]), "+f"(d[43]), "+f"(d[44]), "+f"(d[45]), "+f"(d[46]), "+f"(d[47]),
      "+f"(d[48]), "+f"(d[49]), "+f"(d[50]), "+f"(d[51]), "+f"(d[52]), "+f"(d[53]), "+f"(d[54]), "+f"(d[55]),
      "+f"(d[56]), "+f"(d[57]), "+f"(d[58]), "+f"(d[59]), "+f"(d[60]), "+f"(d[61]), "+f"(d[62]), "+f"(d[63]),
      "+f"(d[64]), "+f"(d[65]), "+f"(d[66]), "+f"(d[67]), "+f"(d[68]), "+f"(d[69]), "+f"(d[70]), "+f"(d[71]),
      "+f"(d[72]), "+f"(d[73]), "+f"(d[74]), "+f"(d[75]), "+f"(d[76]), "+f"(d[77]), "+f"(d[78]), "+f"(d[79])
    : "l"(da), "l"(db), "r"(sd));
}
__device__ __forceinline__ void wgmma_ss_n88(float (&d)[44], uint64_t da, uint64_t db, int sd) {
  asm volatile("{\n.reg .pred p;\nsetp.ne.b32 p, %46, 0;\n"
      "wgmma.mma_async.sync.aligned.m64n88k16.f32.bf16.bf16 {"
      "%0, %1, %2, %3, %4, %5, %6, %7, %8, %9, %10, %11, %12, %13, %14, %15, "
      "%16, %17, %18, %19, %20, %21, %22, %23, %24, %25, %26, %27, %28, %29, %30, %31, "
      "%32, %33, %34, %35, %36, %37, %38, %39, %40, %41, %42, %43"
      "}, %44, %45, p, 1, 1, 0, 1;\n}\n"
    : "+f"(d[0]), "+f"(d[1]), "+f"(d[2]), "+f"(d[3]), "+f"(d[4]), "+f"(d[5]), "+f"(d[6]), "+f"(d[7]),
      "+f"(d[8]), "+f"(d[9]), "+f"(d[10]), "+f"(d[11]), "+f"(d[12]), "+f"(d[13]), "+f"(d[14]), "+f"(d[15]),
      "+f"(d[16]), "+f"(d[17]), "+f"(d[18]), "+f"(d[19]), "+f"(d[20]), "+f"(d[21]), "+f"(d[22]), "+f"(d[23]),
      "+f"(d[24]), "+f"(d[25]), "+f"(d[26]), "+f"(d[27]), "+f"(d[28]), "+f"(d[29]), "+f"(d[30]), "+f"(d[31]),
      "+f"(d[32]), "+f"(d[33]), "+f"(d[34]), "+f"(d[35]), "+f"(d[36]), "+f"(d[37]), "+f"(d[38]), "+f"(d[39]),
      "+f"(d[40]), "+f"(d[41]), "+f"(d[42]), "+f"(d[43])
    : "l"(da), "l"(db), "r"(sd));
}
__device__ __forceinline__ void wgmma_ss_n80(float (&d)[40], uint64_t da, uint64_t db, int sd) {
  asm volatile("{\n.reg .pred p;\nsetp.ne.b32 p, %42, 0;\n"
      "wgmma.mma_async.sync.aligned.m64n80k16.f32.bf16.bf16 {"
      "%0, %1, %2, %3, %4, %5, %6, %7, %8, %9, %10, %11, %12, %13, %14, %15, "
      "%16, %17, %18, %19, %20, %21, %22, %23, %24, %25, %26, %27, %28, %29, %30, %31, "
      "%32, %33, %34, %35, %36, %37, %38, %39"
      "}, %40, %41, p, 1, 1, 0, 1;\n}\n"
    : "+f"(d[0]), "+f"(d[1]), "+f"(d[2]), "+f"(d[3]), "+f"(d[4]), "+f"(d[5]), "+f"(d[6]), "+f"(d[7]),
      "+f"(d[8]), "+f"(d[9]), "+f"(d[10]), "+f"(d[11]), "+f"(d[12]), "+f"(d[13]), "+f"(d[14]), "+f"(d[15]),
      "+f"(d[16]), "+f"(d[17]), "+f"(d[18]), "+f"(d[19]), "+f"(d[20]), "+f"(d[21]), "+f"(d[22]), "+f"(d[23]),
      "+f"(d[24]), "+f"(d[25]), "+f"(d[26]), "+f"(d[27]), "+f"(d[28]), "+f"(d[29]), "+f"(d[30]), "+f"(d[31]),
      "+f"(d[32]), "+f"(d[33]), "+f"(d[34]), "+f"(d[35]), "+f"(d[36]), "+f"(d[37]), "+f"(d[38]), "+f"(d[39])
    : "l"(da), "l"(db), "r"(sd));
}
__device__ __forceinline__ void wgmma_rs_n128(float (&d)[64], uint32_t a0, uint32_t a1, uint32_t a2, uint32_t a3,
                                  uint64_t db, int sd) {
  asm volatile("{\n.reg .pred p;\nsetp.ne.b32 p, %69, 0;\n"
      "wgmma.mma_async.sync.aligned.m64n128k16.f32.bf16.bf16 {"
      "%0, %1, %2, %3, %4, %5, %6, %7, %8, %9, %10, %11, %12, %13, %14, %15, "
      "%16, %17, %18, %19, %20, %21, %22, %23, %24, %25, %26, %27, %28, %29, %30, %31, "
      "%32, %33, %34, %35, %36, %37, %38, %39, %40, %41, %42, %43, %44, %45, %46, %47, "
      "%48, %49, %50, %51, %52, %53, %54, %55, %56, %57, %58, %59, %60, %61, %62, %63"
      "}, {%64, %65, %66, %67}, %68, p, 1, 1, 0;\n}\n"
    : "+f"(d[0]), "+f"(d[1]), "+f"(d[2]), "+f"(d[3]), "+f"(d[4]), "+f"(d[5]), "+f"(d[6]), "+f"(d[7]),
      "+f"(d[8]), "+f"(d[9]), "+f"(d[10]), "+f"(d[11]), "+f"(d[12]), "+f"(d[13]), "+f"(d[14]), "+f"(d[15]),
      "+f"(d[16]), "+f"(d[17]), "+f"(d[18]), "+f"(d[19]), "+f"(d[20]), "+f"(d[21]), "+f"(d[22]), "+f"(d[23]),
      "+f"(d[24]), "+f"(d[25]), "+f"(d[26]), "+f"(d[27]), "+f"(d[28]), "+f"(d[29]), "+f"(d[30]), "+f"(d[31]),
      "+f"(d[32]), "+f"(d[33]), "+f"(d[34]), "+f"(d[35]), "+f"(d[36]), "+f"(d[37]), "+f"(d[38]), "+f"(d[39]),
      "+f"(d[40]), "+f"(d[41]), "+f"(d[42]), "+f"(d[43]), "+f"(d[44]), "+f"(d[45]), "+f"(d[46]), "+f"(d[47]),
      "+f"(d[48]), "+f"(d[49]), "+f"(d[50]), "+f"(d[51]), "+f"(d[52]), "+f"(d[53]), "+f"(d[54]), "+f"(d[55]),
      "+f"(d[56]), "+f"(d[57]), "+f"(d[58]), "+f"(d[59]), "+f"(d[60]), "+f"(d[61]), "+f"(d[62]), "+f"(d[63])
    : "r"(a0), "r"(a1), "r"(a2), "r"(a3), "l"(db), "r"(sd));
}
__device__ __forceinline__ void wgmma_rs_n24(float (&d)[12], uint32_t a0, uint32_t a1, uint32_t a2, uint32_t a3,
                                  uint64_t db, int sd) {
  asm volatile("{\n.reg .pred p;\nsetp.ne.b32 p, %17, 0;\n"
      "wgmma.mma_async.sync.aligned.m64n24k16.f32.bf16.bf16 {"
      "%0, %1, %2, %3, %4, %5, %6, %7, %8, %9, %10, %11"
      "}, {%12, %13, %14, %15}, %16, p, 1, 1, 1;\n}\n"
    : "+f"(d[0]), "+f"(d[1]), "+f"(d[2]), "+f"(d[3]), "+f"(d[4]), "+f"(d[5]), "+f"(d[6]), "+f"(d[7]),
      "+f"(d[8]), "+f"(d[9]), "+f"(d[10]), "+f"(d[11])
    : "r"(a0), "r"(a1), "r"(a2), "r"(a3), "l"(db), "r"(sd));
}

#define KST 4
#define K1S 4
constexpr int K1_ST = K1S, K1_STAGE = 45056;
constexpr int K1_SMEM = K1_ST * K1_STAGE + 640   + 1536   + 2560   + 128;

__device__ __forceinline__ float2 row_stats(uint4 v0, uint4 v1, uint4 v2) {
  const uint32_t wd[12] = {v0.x, v0.y, v0.z, v0.w, v1.x, v1.y, v1.z, v1.w, v2.x, v2.y, v2.z, v2.w};
  float sx = 0.f, sq = 0.f;
#pragma unroll
  for (int e = 0; e < 12; e++) {
    const float lo = bf_lo(wd[e]), hi = bf_hi(wd[e]);
    sx += lo + hi; sq = fmaf(lo, lo, fmaf(hi, hi, sq));
  }
#pragma unroll
  for (int o = 16; o; o >>= 1) { sx += __shfl_xor_sync(~0u, sx, o); sq += __shfl_xor_sync(~0u, sq, o); }
  const float mean = sx * (1.f / D_);
  return make_float2(rsqrtf(fmaxf(sq * (1.f / D_) - mean * mean, 0.f) + 1e-5f), mean);
}

__global__ void __cluster_dims__(2, 1, 1) __launch_bounds__(512, 1)
k1_qkv(const __grid_constant__ CUtensorMap tmx, const __grid_constant__ CUtensorMap tmw,
       const bf16* __restrict__ x, const bf16* __restrict__ w, const bf16* __restrict__ wo) {
  extern __shared__ __align__(1024) uint8_t sm[];
  float* cs = (float*)(sm + K1_ST * K1_STAGE);
  float2* rowab = (float2*)(sm + K1_ST * K1_STAGE + 640);
  float* red = (float*)(sm + K1_ST * K1_STAGE + 2176);
  const uint32_t sbase = smem_u32(sm);
  const uint32_t fullb = sbase + K1_ST * K1_STAGE + 4736, emptyb = fullb + 8 * K1_ST;
  const int tid = threadIdx.x, lane = tid & 31;
  const int warp = __shfl_sync(~0u, tid >> 5, 0);
  const int rank = blockIdx.x & 1, cl = blockIdx.x >> 1;
  const int m = cl / 6, n = (cl - m * 6) * 2 + rank;
  if (tid == 0) STAMP(0, 0);

  if (warp == 12) {
    if (lane == 0) {
      prefetch_map(&tmx); prefetch_map(&tmw);
      for (int i = 0; i < K1_ST; i++) { mbar_init(fullb + 8 * i, 1); mbar_init(emptyb + 8 * i, 6); }
      asm volatile("fence.mbarrier_init.release.cluster;" ::: "memory");
    }
    __syncwarp();
    cluster_arrive();
    bar_arrive(4, 512);
    if (elect_one()) {
#pragma unroll
      for (int kt = 0; kt < K1_ST; kt++) mbar_expect(fullb + 8 * kt, K1_STAGE);
#pragma unroll
      for (int j = 0; j < 5; j++) tma2d(sbase + 24576 + j * 4096, &tmw, n * 160 + j * 32, 0, fullb);
    }
    cluster_wait();
#pragma unroll 1
    for (int kt = 0; kt < 10; kt++) {
      const int s = kt % K1_ST;
      const uint32_t sa = sbase + s * K1_STAGE;
      if (kt >= K1_ST) mbar_wait(emptyb + 8 * s, ((kt / K1_ST) - 1) & 1);
      if (elect_one()) {
        if (kt >= K1_ST) mbar_expect(fullb + 8 * s, K1_STAGE);
        tma2d_mc(sa + rank * 12288, &tmx, kt * 64, m * 192 + rank * 96, fullb + 8 * s);
        if (kt > 0) {
#pragma unroll
          for (int j = 0; j < 5; j++) tma2d(sa + 24576 + j * 4096, &tmw, n * 160 + j * 32, kt * 64, fullb + 8 * s);
        }
      }
      if (kt == K1_ST - 1) pdl_trigger();
    }
    __syncwarp();
    cluster_arrive();
  } else if (warp > 12) {
    cluster_arrive();
    const int t96 = tid - 416;
    const uint32_t tag = __ldcg(&g_epoch) + 1;
    bar_sync(4, 512);
    mbar_wait(fullb, 0);
    if (m < 10) {
      const int ck = t96 % 20, rg = min(t96 / 20, 3);
      uint4 wv[16];
#pragma unroll
      for (int i = 0; i < 16; i++) wv[i] = ldg_nc(w + (size_t)(m * 64 + rg * 16 + i) * 1920 + n * 160 + ck * 8);
      float acc8[8];
#pragma unroll
      for (int i = 0; i < 8; i++) acc8[i] = 0.f;
#pragma unroll
      for (int i = 0; i < 16; i++) ACC8(acc8, wv[i]);
      *(float4*)&red[rg * 160 + ck * 8] = make_float4(acc8[0], acc8[1], acc8[2], acc8[3]);
      *(float4*)&red[rg * 160 + ck * 8 + 4] = make_float4(acc8[4], acc8[5], acc8[6], acc8[7]);
      bar_sync(1, 96);
      if (t96 < 80) {
        const float2 p0 = *(const float2*)&red[t96 * 2], p1 = *(const float2*)&red[160 + t96 * 2];
        const float2 p2 = *(const float2*)&red[320 + t96 * 2], p3 = *(const float2*)&red[480 + t96 * 2];
        st_relaxed(&g_cpart[(m * 12 + n) * 80 + t96], (p0.x + p1.x) + (p2.x + p3.x), (p0.y + p1.y) + (p2.y + p3.y), tag);
      }
    }
    if (tid == 416) STAMP(5, 7);
    bool ok = false;
    for (int it = 0; it < 64 && !ok; it++) {
      uint4 p[10], st[2];
#pragma unroll
      for (int k = 0; k < 10; k++) p[k] = ld_relaxed(&g_cpart[(k * 12 + n) * 80 + min(t96, 79)]);
#pragma unroll
      for (int k = 0; k < 2; k++) st[k] = ld_relaxed(&g_rowstat[min(m * 192 + k * 96 + t96, S_ - 1)]);
      ok = true;
      float s0 = 0.f, s1 = 0.f;
#pragma unroll
      for (int k = 0; k < 10; k++) {
        ok = ok && p[k].y == tag && p[k].w == tag;
        s0 += __uint_as_float(p[k].x); s1 += __uint_as_float(p[k].z);
      }
      if (t96 < 80) *(float2*)&cs[t96 * 2] = make_float2(s0, s1);
#pragma unroll
      for (int k = 0; k < 2; k++) {
        ok = ok && st[k].y == tag && st[k].w == tag;
        rowab[k * 96 + t96] = make_float2(__uint_as_float(st[k].x), -__uint_as_float(st[k].x) * __uint_as_float(st[k].z));
      }
      ok = __all_sync(~0u, ok);
      if (!ok) __nanosleep(300);
    }
    if (!ok) {
      const int c2 = min(t96, 79);
      float s0 = 0.f, s1 = 0.f;
#pragma unroll 1
      for (int k = 0; k < D_; k++) {
        const uint32_t v = *(const uint32_t*)(w + (size_t)k * 1920 + n * 160 + c2 * 2);
        s0 += bf_lo(v); s1 += bf_hi(v);
      }
      if (t96 < 80) *(float2*)&cs[t96 * 2] = make_float2(s0, s1);
#pragma unroll 1
      for (int i = 0; i < 64; i++) {
        const int r = (i >> 5) * 96 + (t96 & ~31) + (i & 31);
        const bf16* xr = x + (size_t)min(m * 192 + r, S_ - 1) * D_ + lane * 8;
        const float2 st = row_stats(ldg_nc(xr), ldg_nc(xr + 256), lane < 16 ? ldg_nc(xr + 512) : make_uint4(0u, 0u, 0u, 0u));
        if (lane == 0) rowab[r] = make_float2(st.x, -st.x * st.y);
      }
    }
    __syncwarp();
    bar_arrive(2, 96 + 384);
    bar_sync(1, 96);
    if (tid == 416) STAMP(0, 5);
    if (blockIdx.x < 128) {
      uint4 v[5];
      const int ck = min(t96, 79), nt = ck / 10;
#pragma unroll
      for (int i = 0; i < 5; i++) {
        const int k = blockIdx.x * 5 + i, pr = k / 40, r = k - pr * 40;
        v[i] = ldg_nc(wo + (size_t)(pr * 40 + (r < 16 ? r : (r < 32 ? r + 4 : (r < 36 ? r - 16 : r)))) * D_ + ck * 8);
      }
#pragma unroll
      for (int i = 0; i < 5; i++) {
        const int k = blockIdx.x * 5 + i;
        g_wo[((nt * 10 + (k >> 6)) * 10 + ck - nt * 10) * 64 + (k & 63)] = v[i];
        float t = ((bf_lo(v[i].x) + bf_hi(v[i].x)) + (bf_lo(v[i].y) + bf_hi(v[i].y))) +
                  ((bf_lo(v[i].z) + bf_hi(v[i].z)) + (bf_lo(v[i].w) + bf_hi(v[i].w)));
        if (t96 >= 80) t = 0.f;
#pragma unroll
        for (int o = 16; o; o >>= 1) t += __shfl_xor_sync(~0u, t, o);
        if (lane == 0) red[(t96 >> 5) * 8 + i] = t;
      }
      bar_sync(1, 96);
      if (t96 < 5) {
        const float mu = (red[t96] + red[8 + t96] + red[16 + t96]) * (1.f / D_);
        const float hi = bf_lo(pack_bf16(mu, 0.f));
        g_wm[blockIdx.x * 5 + t96] = make_uint4(pack_bf16(hi, mu - hi), 0u, 0u, 0u);
      }
    }
    if (tid == 416) STAMP(0, 7);
    __syncwarp();
    cluster_wait();
    cluster_arrive();
  } else {
    cluster_arrive();
    float acc[80];
    const uint64_t da0 = mkdesc(sbase + (warp >> 2) * 8192, 16, 1024, 1);
    const uint64_t db0 = mkdesc(sbase + 24576, 4096, 512, 2);
    const uint32_t tag = __ldcg(&g_epoch) + 1;
    const int srow = m * 192 + n * 16 + warp * 2;
    const bool dostat = warp < 8 && srow < S_;
    uint4 xv[2][3];
    bar_sync(4, 512);
    cluster_wait();
#pragma unroll
    for (int kt = 0; kt < 10; kt++) {
      const int s = kt % K1_ST;
      mbar_wait(fullb + 8 * s, (kt / K1_ST) & 1);
      if (kt == 0 && tid == 0) STAMP(0, 1);
      if (kt == 2 && tid == 0) STAMP(5, 0);
      if (kt == 4 && tid == 0) STAMP(5, 1);
      if (kt == 7 && tid == 0) STAMP(5, 2);
      const uint64_t da = da0 + s * (K1_STAGE >> 4), db = db0 + s * (K1_STAGE >> 4);
      WG_FENCE();
#pragma unroll
      for (int k = 0; k < 4; k++) wgmma_ss_n160(acc, da + k * 2, db + k * 64, (kt | k) != 0);
      WG_COMMIT();
      if (kt > 0) {
        WG_WAIT(1);
        if (kt - 1 + K1_ST < 10 && (tid & 127) < 2) mbar_arrive_cta(emptyb + 8 * ((kt - 1) % K1_ST), tid & 1);
      }
      if (kt == 0) {
#pragma unroll
        for (int i = 0; i < 2; i++) {
          const bf16* xr = x + (size_t)min(srow + i, S_ - 1) * D_ + lane * 8;
          xv[i][0] = xv[i][1] = xv[i][2] = make_uint4(0u, 0u, 0u, 0u);
          if (dostat) { xv[i][0] = ldg_nc(xr); xv[i][1] = ldg_nc(xr + 256); }
          if (dostat && lane < 16) xv[i][2] = ldg_nc(xr + 512);
        }
      }
      if ((kt == KST || kt == KST + 1) && dostat) {
        const float2 st = row_stats(xv[kt - KST][0], xv[kt - KST][1], xv[kt - KST][2]);
        if (lane == 0) st_relaxed(&g_rowstat[srow + kt - KST], st.x, st.y, tag);
      }
      __syncwarp();
    }
    cluster_arrive();
    WG_WAIT(0);
    fence_regs(acc);
    if (tid == 0) STAMP(0, 2);
    bar_sync(2, 96 + 384);
    if (tid == 0) STAMP(0, 3);
    const int row0 = m * 192 + warp * 16;
    if (row0 < S_) {
      const int g = lane >> 2, c = lane & 3, sec = n >> 2, grp = (row0 & 127) >> 3;
      const bool lo = c < 2;
      const float2 ab0 = rowab[warp * 16 + g], ab1 = rowab[warp * 16 + g + 8];
      const bool p0 = sec == 1 && ((POLY_MASK >> grp) & 1), p1 = sec == 1 && ((POLY_MASK >> (grp + 1)) & 1);
      const uint32_t padqv = sec == 0 ? (c == 2 ? 0x3F803F80u : 0x00003F80u) : (sec == 2 && c == 2 ? 0x00003F80u : 0u);
      const uint32_t padk = c == 2 ? 0x4A7A4B00u : 0x00004653u;
      const uint32_t pad0 = p0 ? padk : padqv, pad1 = p1 ? padk : padqv;
      const float f0 = sec == 0 ? QSCALE : (p0 ? 32768.f : 1.f), f1 = sec == 0 ? QSCALE : (p1 ? 32768.f : 1.f);
      const float a0 = ab0.x * f0, b0 = ab0.y * f0, a1 = ab1.x * f1, b1 = ab1.y * f1;
      const float r0 = p0 ? 9.313225746154785e-10f : 1.f, r1 = p1 ? 9.313225746154785e-10f : 1.f;
      const int cst = sec == 1 ? 2048 : 128, gst = sec == 1 ? 128 : 384;
      uint8_t* pe = (uint8_t*)g_qkv + (size_t)(n * 8) * HEAD_IMG + (row0 >> 7) * 6144 + grp * gst + lane * 4;
      uint8_t* pe1 = pe + cst;
      uint8_t* pe2 = pe1 + cst;
      uint8_t* pf = pe + gst;
      uint8_t* pf1 = pf + cst;
      uint8_t* pf2 = pf1 + cst;
#pragma unroll
      for (int hp = 0; hp < 4; hp++) {
        uint32_t u[5], v[5];
        float su[5], sv[5];
#pragma unroll
        for (int i = 0; i < 5; i++) {
          const int j = hp * 5 + i;
          const float2 t = *(const float2*)&cs[j * 8 + c * 2];
          const float x0 = fmaf(acc[4 * j], a0, b0 * t.x), x1 = fmaf(acc[4 * j + 1], a0, b0 * t.y);
          const float y0 = fmaf(acc[4 * j + 2], a1, b1 * t.x), y1 = fmaf(acc[4 * j + 3], a1, b1 * t.y);
          u[i] = pack_bf16(x0, x1); v[i] = pack_bf16(y0, y1);
          su[i] = fmaf(x0, x0, x1 * x1); sv[i] = fmaf(y0, y0, y1 * y1);
        }
        constexpr int HE = HEAD_IMG;
        const int oe = hp * 2 * HE, oo = oe + HE;
        *(uint32_t*)(pe + oe) = u[0];  *(uint32_t*)(pf + oe) = v[0];
        *(uint32_t*)(pe1 + oe) = u[1]; *(uint32_t*)(pf1 + oe) = v[1];
        *(uint32_t*)(pe2 + oe) = lo ? u[2] : pad0; *(uint32_t*)(pf2 + oe) = lo ? v[2] : pad1;
        *(uint32_t*)(pe + oo) = __shfl_xor_sync(~0u, lo ? u[3] : u[2], 2);
        *(uint32_t*)(pf + oo) = __shfl_xor_sync(~0u, lo ? v[3] : v[2], 2);
        *(uint32_t*)(pe1 + oo) = __shfl_xor_sync(~0u, lo ? u[4] : u[3], 2);
        *(uint32_t*)(pf1 + oo) = __shfl_xor_sync(~0u, lo ? v[4] : v[3], 2);
        const uint32_t tu = __shfl_xor_sync(~0u, u[4], 2), tv = __shfl_xor_sync(~0u, v[4], 2);
        *(uint32_t*)(pe2 + oo) = lo ? tu : pad0; *(uint32_t*)(pf2 + oo) = lo ? tv : pad1;
        if (sec < 2) {
          float e0 = (su[0] + su[1] + (lo ? su[2] : 0.f)) * r0, e1 = (sv[0] + sv[1] + (lo ? sv[2] : 0.f)) * r1;
          float o0 = (su[3] + su[4] + (lo ? 0.f : su[2])) * r0, o1 = (sv[3] + sv[4] + (lo ? 0.f : sv[2])) * r1;
          e0 += __shfl_xor_sync(~0u, e0, 1); e1 += __shfl_xor_sync(~0u, e1, 1);
          o0 += __shfl_xor_sync(~0u, o0, 1); o1 += __shfl_xor_sync(~0u, o1, 1);
          e0 += __shfl_xor_sync(~0u, e0, 2); e1 += __shfl_xor_sync(~0u, e1, 2);
          o0 += __shfl_xor_sync(~0u, o0, 2); o1 += __shfl_xor_sync(~0u, o1, 2);
          const uint32_t em = __reduce_max_sync(~0u, max(__float_as_uint(e0), __float_as_uint(e1)));
          const uint32_t om = __reduce_max_sync(~0u, max(__float_as_uint(o0), __float_as_uint(o1)));
          if (lane < 2) g_nrm[(n * 8 + hp * 2 + lane) * 128 + (row0 >> 4)] = __uint_as_float(lane ? om : em);
        }
      }
    }
    if (tid == 0) STAMP(0, 4);
  }
  cluster_wait();
  if (tid == 0) STAMP(0, 6);
}

constexpr int K2_SMEM = 2 * HEAD_IMG + 2 * 6144 + 2 * 10240 + 256;

__device__ __forceinline__ uint64_t desc64(uint32_t lo, uint32_t hi) {
  uint64_t d;
  asm("mov.b64 %0, {%1, %2};" : "=l"(d) : "r"(lo), "r"(hi));
  return d;
}
__device__ __forceinline__ uint32_t exp_pair(bool poly, float a, float b, uint32_t mk) {
  if (poly) {
    const uint32_t pk = __byte_perm(__float_as_uint(a), __float_as_uint(b), 0x6521);
    uint32_t m, q;
    asm("lop3.b32 %0, %1, %2, 0x3f803f80, 0xEA;" : "=r"(m) : "r"(pk), "r"(mk));
    asm("fma.rn.bf16x2 %0, %1, %1, %2;" : "=r"(q) : "r"(m), "r"(0x40014001u));
    return pk - m + q;
  }
  return pack_bf16(ex2(a), ex2(b));
}
#define PV_GR 4
__device__ __forceinline__ void exp_pv(const float (&s)[64], float (&o)[12], uint64_t dv, uint32_t mk) {
#pragma unroll
  for (int k0 = 0; k0 < 8; k0 += PV_GR) {
    uint32_t p[4 * PV_GR];
#pragma unroll
    for (int i = 0; i < 4 * PV_GR; i++)
      p[i] = exp_pair((POLY_MASK >> (k0 * 2 + i / 2)) & 1, s[k0 * 8 + 2 * i], s[k0 * 8 + 2 * i + 1], mk);
    WG_FENCE();
#pragma unroll
    for (int k = 0; k < PV_GR; k++)
      wgmma_rs_n24(o, p[4 * k], p[4 * k + 1], p[4 * k + 2], p[4 * k + 3], dv + (k0 + k) * 48, 1);
  }
}
__device__ __forceinline__ void load_q(uint32_t (&q)[6], const uint8_t* p) {
  q[0] = __ldcg((const uint32_t*)p);         q[1] = __ldcg((const uint32_t*)(p + 384));
  q[2] = __ldcg((const uint32_t*)(p + 128)); q[3] = __ldcg((const uint32_t*)(p + 512));
  q[4] = __ldcg((const uint32_t*)(p + 256)); q[5] = __ldcg((const uint32_t*)(p + 640));
}
__device__ __forceinline__ float rcp(float x) {
  float y;
  asm("rcp.approx.ftz.f32 %0, %1;" : "=f"(y) : "f"(x));
  return y;
}
__device__ __forceinline__ int img_off(int chunk) { return (chunk >> 3) * 16384 + (chunk & 7) * 128; }
__device__ __forceinline__ void store_o(const float (&o)[12], int tile) {
  int tid, bid;
  asm volatile("mov.u32 %0, %%tid.x;" : "=r"(tid));
  asm volatile("mov.u32 %0, %%ctaid.x;" : "=r"(bid));
  const int head = bid >> 2;
  uint8_t* dst = (uint8_t*)g_o + ((bid & 3) * 4 + (tile >> 1)) * 163840 + (tile & 1) * 8192 + ((tid >> 5) & 3) * 2048 + (tid & 31) * 4;
  const int oc = (head >> 1) * 5 + (head & 1) * 2;
  const int o0 = img_off(oc), o1 = img_off(oc + 1), o2 = img_off((head >> 1) * 5 + 4) + (head & 1) * 8;
  const float i0 = rcp(__shfl_sync(~0u, o[8], 2, 4)), i1 = rcp(__shfl_sync(~0u, o[10], 2, 4));
  *(uint32_t*)(dst + o0) = pack_bf16(o[0] * i0, o[1] * i0); *(uint32_t*)(dst + o0 + 1024) = pack_bf16(o[2] * i1, o[3] * i1);
  *(uint32_t*)(dst + o1) = pack_bf16(o[4] * i0, o[5] * i0); *(uint32_t*)(dst + o1 + 1024) = pack_bf16(o[6] * i1, o[7] * i1);
  if ((tid & 3) < 2) {
    *(uint32_t*)(dst + o2) = pack_bf16(o[8] * i0, o[9] * i0);
    *(uint32_t*)(dst + o2 + 1024) = pack_bf16(o[10] * i1, o[11] * i1);
  }
}

struct Maps5 { CUtensorMap m[5]; };

__global__ void __launch_bounds__(512, 1)
k2_attn(const __grid_constant__ Maps5 maps, uint32_t mk) {
  const CUtensorMap* tmw = maps.m;
  extern __shared__ __align__(1024) uint8_t sm[];
  const uint32_t sbase = smem_u32(sm);
  float* part = (float*)(sm + 2 * HEAD_IMG);
  const uint32_t rbuf = sbase + 2 * HEAD_IMG + 2 * 6144;
  const uint32_t kvb = rbuf + 2 * 10240;
  const uint32_t partb = kvb + 128, rbar = kvb + 144;
  const int tid = threadIdx.x, lane = tid & 31;
  const int warp = __shfl_sync(~0u, tid >> 5, 0);
  const int head = blockIdx.x >> 2, qb = blockIdx.x & 3;

  if (tid == 0) STAMP(1, 0);
  if (tid == 0) {
    for (int i = 0; i < 16; i++) mbar_init(kvb + 8 * i, 1);
    mbar_init(partb, 128); mbar_init(partb + 8, 128); mbar_init(rbar, 1); mbar_init(rbar + 8, 1);
    asm volatile("fence.mbarrier_init.release.cluster;" ::: "memory");
  }
  __syncthreads();

  if (warp >= 12) {
    asm volatile("setmaxnreg.dec.sync.aligned.u32 32;");
    if (tid == 384) {
      pdl_wait();
      pdl_trigger();
      const uint8_t* kimg = (const uint8_t*)g_qkv + (size_t)(32 + head) * HEAD_IMG;
#pragma unroll 1
      for (int b = 0; b < 16; b++) {
        mbar_expect(kvb + 8 * b, 12288);
        bulk_ld(sbase + b * 6144, kimg + b * 6144, 6144, kvb + 8 * b);
        bulk_ld(sbase + HEAD_IMG + b * 6144, kimg + 32 * HEAD_IMG + b * 6144, 6144, kvb + 8 * b);
        if (b >= 2) mbar_wait(kvb + 8 * (b - 1), 0);

      }
      if (blockIdx.x == 0) g_epoch = g_epoch + 1;
      mbar_wait(kvb + 8 * 15, 0);
      STAMP(1, 2);
      uint8_t* pdst = nullptr;
      uint32_t pbytes = 0;
#pragma unroll 1
      for (int i = 0; i < 8; i++) {
        const int p = blockIdx.x + 128 * i;
        uint8_t* dst = nullptr;
        uint32_t bytes = 0;
        if (i < 7 && p < 856) {
          asm volatile("cp.async.bulk.wait_group.read 0;" ::: "memory");
          const CUtensorMap* tm;
          int c1, c2;
          if (p < 640) {
            const int nt = p / 80, r = p - nt * 80, ph = r / 40, st = (r - ph * 40) >> 1, up = r & 1;
            bytes = ph ? 6656 : 7168;
            dst = (uint8_t*)g_wgu + nt * 552960 + ph * 286720 + st * 2 * bytes + up * (bytes >> 1);
            tm = &tmw[ph * 2 + up]; c1 = ph ? 112 + nt * 13 : nt * 14; c2 = st * 2;
          } else {
            const int nk = p - 640, nt = nk / 27;
            bytes = 10240;
            dst = (uint8_t*)g_wd + (size_t)nk * 10240;
            tm = &tmw[4]; c1 = nt * 10; c2 = nk - nt * 27;
          }
          mbar_expect(rbar + 8 * (i & 1), bytes);
          tma4d(rbuf + (i & 1) * 10240, tm, c1, c2, rbar + 8 * (i & 1));
        }
        if (pbytes) {
          mbar_wait(rbar + 8 * ((i - 1) & 1), ((i - 1) >> 1) & 1);
          if (pbytes == 10240) {
            bulk_st(pdst, rbuf + ((i - 1) & 1) * 10240, pbytes);
          } else {
            bulk_st(pdst, rbuf + ((i - 1) & 1) * 10240, pbytes >> 1);
            bulk_st(pdst + pbytes, rbuf + ((i - 1) & 1) * 10240 + (pbytes >> 1), pbytes >> 1);
          }
          asm volatile("cp.async.bulk.commit_group;" ::: "memory");
        }
        pdst = dst; pbytes = bytes;
      }
      asm volatile("cp.async.bulk.wait_group.read 0;" ::: "memory");
      STAMP(1, 6);
    }
  } else {
    asm volatile("setmaxnreg.inc.sync.aligned.u32 160;");
    const int wg = warp >> 2;
    const uint8_t* qthr = (const uint8_t*)g_qkv + (size_t)head * HEAD_IMG + qb * 64 * 384 + (warp & 3) * 768 + lane * 4;
    const uint32_t klo0 = ((sbase & 0x3FFFF) >> 4) | (128u << 16), vlo0 = (((sbase + HEAD_IMG) & 0x3FFFF) >> 4) | (24u << 16);
    constexpr uint64_t KSTEP2 = (uint64_t)(int64_t)(256 - (128 << 16));
    constexpr uint64_t KV2K = 384 - (HEAD_IMG >> 4) + (104 << 16);
    const int nun = wg == 1 ? 4 : 3;
    uint32_t utile = wg == 0 ? 0x210u : (wg == 1 ? 0x4235u : 0x576u);
    uint32_t ubeg = wg == 0 ? 0u : (wg == 1 ? 0x0b00u : 0x600u);
    uint32_t ulen = wg == 0 ? 0x0b1010u : (wg == 1 ? 0x10051006u : 0x0a1010u);
    pdl_wait();
    if (tid == 0) STAMP(1, 1);
    uint32_t q[6];
    load_q(q, qthr + (utile & 15) * 3072);
    bool fast;
    {
      const float4 kn = __ldcg((const float4*)&g_nrm[(32 + head) * 128 + lane * 4]);
      const float qv = __ldcg(&g_nrm[head * 128 + qb * 32 + lane]);
      const uint32_t km = max(max(__float_as_uint(kn.x), __float_as_uint(kn.y)), max(__float_as_uint(kn.z), __float_as_uint(kn.w)));
      const float k2 = __uint_as_float(__reduce_max_sync(~0u, km)), q2 = __uint_as_float(__reduce_max_sync(~0u, __float_as_uint(qv)));
      fast = q2 * k2 <= 3400.f;
    }
    if (fast) {
#pragma unroll 1
      for (int u = 0; u < nun; u++) {
        const uint32_t b0 = ubeg & 15;
        const bool wt = u == 0 || (wg == 1 && u == 1);
        float s[64], o[12];
#pragma unroll
        for (int i = 0; i < 12; i++) o[i] = 0.f;
        uint32_t vlo = vlo0 + b0 * 384, kb = kvb + b0 * 8;
        const uint32_t vend = vlo + ((ulen & 255) - 1) * 384;
        if (wt) mbar_wait(kb, 0);
        if (tid == 0) STAMP(5, 4 + u);
        fence_regs(o);
        WG_FENCE();
        wgmma_rs_n128(s, q[0], q[1], q[2], q[3], desc64(klo0 + b0 * 384, 8), 0);
        wgmma_rs_n128(s, q[4], q[5], 0, 0, desc64(klo0 + b0 * 384, 8) + KSTEP2, 1);
        WG_COMMIT();
#define K2UNR 1
        constexpr int kUnr = K2UNR;
#pragma unroll kUnr
        for (; vlo != vend; vlo += 384) {
          if (wt) { kb += 8; mbar_wait(kb, 0); }
          WG_WAIT(0);
          fence_regs(s); fence_regs(o);
          const uint64_t dv = desc64(vlo, 8);
          exp_pv(s, o, dv, mk);
          wgmma_rs_n128(s, q[0], q[1], q[2], q[3], dv + KV2K, 0);
          wgmma_rs_n128(s, q[4], q[5], 0, 0, dv + (KV2K + KSTEP2), 1);
          WG_COMMIT();
        }
        WG_WAIT(0);
        fence_regs(s); fence_regs(o);
        if (u + 1 < nun) load_q(q, qthr + ((utile >> 4) & 15) * 3072);
        exp_pv(s, o, desc64(vlo, 8), mk);
        WG_COMMIT();
        WG_WAIT(0);
        fence_regs(o);
        if (wg == 1 && !(u & 1)) {
          float4* pp = (float4*)(part + u * 768) + (tid & 127);
          pp[0] = make_float4(o[0], o[1], o[2], o[3]);
          pp[128] = make_float4(o[4], o[5], o[6], o[7]);
          pp[256] = make_float4(o[8], o[9], o[10], o[11]);
          mbar_arrive(partb + 4 * u);
        } else {
          if (wg != 1 && u == 2) {
            const int pi = wg == 0 ? 1 : 0;
            mbar_wait(partb + 8 * pi, 0);
            const float4* pp = (const float4*)(part + pi * 1536) + (tid & 127);
            const float4 x0 = pp[0], x1 = pp[128], x2 = pp[256];
            o[0] += x0.x; o[1] += x0.y; o[2] += x0.z; o[3] += x0.w; o[4] += x1.x; o[5] += x1.y;
            o[6] += x1.z; o[7] += x1.w; o[8] += x2.x; o[9] += x2.y; o[10] += x2.z; o[11] += x2.w;
          }
          store_o(o, utile & 15);
        }
        utile >>= 4; ubeg >>= 4; ulen >>= 8;
      }
      if ((tid & 127) == 0) STAMP(1, 3 + wg);
    } else {
#pragma unroll 1
      for (int tile = wg; tile < 8; tile += 3) {
        load_q(q, qthr + tile * 3072);
        if ((lane & 3) >= 2) { q[4] = 0; q[5] = 0; }
        float o[12], m0 = -INFINITY, m1 = -INFINITY;
#pragma unroll
        for (int i = 0; i < 12; i++) o[i] = 0.f;
#pragma unroll 1
        for (int b = 0; b < 16; b++) {
          float s[64];
          mbar_wait(kvb + 8 * b, 0);
          WG_FENCE();
          wgmma_rs_n128(s, q[0], q[1], q[2], q[3], desc64(klo0 + b * 384, 8), 0);
          wgmma_rs_n128(s, q[4], q[5], 0, 0, desc64(klo0 + b * 384, 8) + KSTEP2, 1);
          WG_COMMIT();
          WG_WAIT(0);
          fence_regs(s);
          float x0 = m0, x1 = m1;
#pragma unroll
          for (int j = 0; j < 16; j++) {
            if ((POLY_MASK >> j) & 1) {
#pragma unroll
              for (int i = 0; i < 4; i++) s[4 * j + i] *= (1.f / 32768.f);
            }
            x0 = fmaxf(x0, fmaxf(s[4 * j], s[4 * j + 1]));
            x1 = fmaxf(x1, fmaxf(s[4 * j + 2], s[4 * j + 3]));
          }
          x0 = fmaxf(x0, __shfl_xor_sync(~0u, x0, 1)); x0 = fmaxf(x0, __shfl_xor_sync(~0u, x0, 2));
          x1 = fmaxf(x1, __shfl_xor_sync(~0u, x1, 1)); x1 = fmaxf(x1, __shfl_xor_sync(~0u, x1, 2));
          const float al0 = ex2(m0 - x0), al1 = ex2(m1 - x1);
          m0 = x0; m1 = x1;
#pragma unroll
          for (int i = 0; i < 12; i++) o[i] *= (i & 2) ? al1 : al0;
          uint32_t p[32];
#pragma unroll
          for (int i = 0; i < 32; i++) {
            const float mm = (i & 1) ? m1 : m0;
            p[i] = pack_bf16(ex2(s[2 * i] - mm), ex2(s[2 * i + 1] - mm));
          }
          fence_regs(o);
          WG_FENCE();
#pragma unroll
          for (int k = 0; k < 8; k++)
            wgmma_rs_n24(o, p[4 * k], p[4 * k + 1], p[4 * k + 2], p[4 * k + 3], desc64(vlo0 + b * 384 + k * 48, 8), 1);
          WG_COMMIT();
          WG_WAIT(0);
          fence_regs(o);
        }
        store_o(o, tile);
      }
    }
  }
}

#define K3P 1
constexpr int K3_ST = 4, K3_STAGE = 37888, K3_PRE = K3P;
constexpr int K3_SMEM = K3_ST * K3_STAGE + 45056 + 20480 + 256;

template <int N> struct Acc { float v[N]; };

template <int NB, int NK, bool FIRST>
__global__ void __cluster_dims__(2, 1, 1) __launch_bounds__(384, 1)
k3_proj(const __grid_constant__ CUtensorMap tmr, const uint4* __restrict__ aimg, const uint4* __restrict__ wimg) {
  constexpr int KT = 2 * NB + NK, EX = FIRST ? 1 : 0;
  extern __shared__ __align__(1024) uint8_t sm[];
  const uint32_t sbase = smem_u32(sm);
  uint8_t* xch = sm + K3_ST * K3_STAGE;
  uint8_t* stg = sm + K3_ST * K3_STAGE + 45056;
  const uint32_t fullb = smem_u32(stg) + 20480, emptyb = fullb + 8 * K3_ST, resb = emptyb + 8 * K3_ST, xchb = resb + 8;
  const int tid = threadIdx.x, lane = tid & 31;
  const int warp = __shfl_sync(~0u, tid >> 5, 0);
  const int rank = blockIdx.x & 1;
  const int n = blockIdx.x & 7, m = blockIdx.x >> 3;
  if (tid == 0) STAMP(FIRST ? 2 : 4, 0);
  if (warp == 0) {
    if (lane == 0) {
      prefetch_map(&tmr);
      for (int i = 0; i < K3_ST; i++) { mbar_init(fullb + 8 * i, 1); mbar_init(emptyb + 8 * i, 4); }
      mbar_init(resb, 1); mbar_init(xchb, 1);
      mbar_expect(xchb, 4096 * (10 + EX));
      asm volatile("fence.mbarrier_init.release.cluster;" ::: "memory");
    }
    __syncwarp();
    cluster_arrive();
    bar_arrive(4, 256 + 32);
    const uint8_t* wk = (const uint8_t*)wimg + (size_t)n * KT * 10240;
    const uint8_t* ws = (const uint8_t*)wimg + (size_t)(n ^ 1) * KT * 10240;
    const uint8_t* ab = (const uint8_t*)aimg + (size_t)m * KT * 16384;
    auto load_w = [&](int i) {
      const int s = i % K3_ST, kt = i < NB ? i + rank * (NB + NK) : i;
      const uint32_t sa = sbase + s * K3_STAGE;
      mbar_expect(fullb + 8 * s, 26624 + EX * 1024 + (i < NB ? 10240 : 0));
      bulk_ld(sa + 16384, wk + kt * 10240, 10240, fullb + 8 * s);
      if (FIRST) bulk_ld(sa + 26624, (const uint8_t*)g_wm + kt * 1024, 1024, fullb + 8 * s);
      if (i < NB) bulk_ld(sa + 26624 + EX * 1024, ws + kt * 10240, 10240, fullb + 8 * s);
    };
    if (elect_one()) {
#pragma unroll 1
      for (int i = 0; i < K3_PRE; i++) load_w(i);
    }
    cluster_wait();
    pdl_wait();
    pdl_trigger();
    if (lane == 0) STAMP(2, 6);
#pragma unroll 1
    for (int i = 0; i < NB + NK; i++) {
      const int s = i % K3_ST;
      const uint32_t sa = sbase + s * K3_STAGE;
      if (i >= K3_ST) mbar_wait(emptyb + 8 * s, ((i / K3_ST) - 1) & 1);
      if (elect_one()) {
        if (i < NB) bulk_ld(sa, ab + (i + rank * (NB + NK)) * 16384, 16384, fullb + 8 * s);
        else bulk_ld_mc(sa + rank * 8192, ab + i * 16384 + rank * 8192, 8192, fullb + 8 * s);
        if (i >= K3_PRE) load_w(i);
        if (FIRST && i == K3_ST - 1) {
          mbar_expect(resb, 20480);
          tma2d(smem_u32(stg), &tmr, n * 80, m * 128, resb);
          tma2d(smem_u32(stg) + 10240, &tmr, n * 80, m * 128 + 64, resb);
        }
      }
    }
    __syncwarp();
    cluster_arrive();
  } else if (warp >= 4) {
    cluster_arrive();
    const int cw = warp - 4, wg = cw >> 2;
    const int g = lane >> 2, c = lane & 3;
    const int row = m * 128 + cw * 16 + g;
    uint8_t* himg = (uint8_t*)g_h + (size_t)m * 163840 + cw * 2048 + lane * 4;
    uint32_t rv[20];
    float mu0, mu1;
    if (FIRST) {
      mu0 = __uint_as_float(__ldcg(&g_rowstat[row].z)); mu1 = __uint_as_float(__ldcg(&g_rowstat[row + 8].z));
    } else {
      mu0 = __ldcg(&g_hmean[row]); mu1 = __ldcg(&g_hmean[row + 8]);
#pragma unroll
      for (int j = 0; j < 10; j++) {
        rv[2 * j] = __ldcg((const uint32_t*)(himg + img_off(n * 10 + j)));
        rv[2 * j + 1] = __ldcg((const uint32_t*)(himg + img_off(n * 10 + j) + 1024));
      }
    }
    float acc[80 + 4 * EX];
    float (&keep)[40 + 4 * EX] = ((Acc<40 + 4 * EX>*)acc)->v;
    const uint64_t da0 = mkdesc(sbase + wg * 8192, 128, 1024, 0);
    const uint64_t db0 = mkdesc(sbase + 16384, 128, 1024, 0);
    bar_sync(4, 256 + 32);
    cluster_wait();
#pragma unroll 1
    for (int i = 0; i < NB; i++) {
      const int s = i % K3_ST;
      mbar_wait(fullb + 8 * s, (i / K3_ST) & 1);
      if (i == 0 && tid == 128) STAMP(FIRST ? 2 : 4, 2);
      const uint64_t da = da0 + s * (K3_STAGE >> 4), db = db0 + s * (K3_STAGE >> 4);
      WG_FENCE();
#pragma unroll
      for (int k = 0; k < 4; k++) {
        if constexpr (FIRST) wgmma_ss_n168(acc, da + k * 16, db + k * 16, (i | k) != 0);
        else wgmma_ss_n160(acc, da + k * 16, db + k * 16, (i | k) != 0);
      }
      WG_COMMIT();
      if (i > 0) {
        WG_WAIT(1);
        if ((tid & 127) < 2) mbar_arrive_cta(emptyb + 8 * ((i - 1) % K3_ST), tid & 1);
      }
    }
    const uint32_t rx = mapa(smem_u32(xch) + (tid - 128) * 16, rank ^ 1), rb = mapa(xchb, rank ^ 1);
    WG_WAIT(0);
    fence_regs(acc);
    if ((tid & 127) < 2) mbar_arrive_cta(emptyb + 8 * ((NB - 1) % K3_ST), tid & 1);
    if (FIRST) st_async4(rx, acc[40], acc[41], acc[42], acc[43], rb);
    if (tid == 128) STAMP(FIRST ? 2 : 4, 1);
#pragma unroll
    for (int i = NB; i < NB + NK; i++) {
      const int s = i % K3_ST;
      mbar_wait(fullb + 8 * s, (i / K3_ST) & 1);
      const uint64_t da = da0 + s * (K3_STAGE >> 4), db = db0 + s * (K3_STAGE >> 4);
      WG_FENCE();
#pragma unroll
      for (int k = 0; k < 4; k++) {
        if constexpr (FIRST) wgmma_ss_n88(keep, da + k * 16, db + k * 16, 1);
        else wgmma_ss_n80(keep, da + k * 16, db + k * 16, 1);
      }
      WG_COMMIT();
      if (i > NB && i - 1 + K3_ST < NB + NK) {
        WG_WAIT(1);
        if ((tid & 127) < 2) mbar_arrive_cta(emptyb + 8 * ((i - 1) % K3_ST), tid & 1);
      }
#pragma unroll
      for (int j = (i - NB) * 3 + EX; j < (i - NB) * 3 + 3 + EX; j++)
        if (j < 10 + EX) st_async4(rx + j * 4096, acc[40 + 4 * j], acc[41 + 4 * j], acc[42 + 4 * j], acc[43 + 4 * j], rb);
    }
    cluster_arrive();
    uint8_t* sp = stg + (cw * 16 + g) * 160 + c * 4;
    if (FIRST) {
      mbar_wait(resb, 0);
#pragma unroll
      for (int j = 0; j < 10; j++) {
        rv[2 * j] = *(const uint32_t*)(sp + j * 16);
        rv[2 * j + 1] = *(const uint32_t*)(sp + 1280 + j * 16);
      }
    }
    WG_WAIT(0);
    fence_regs(keep);
    if (tid == 128) STAMP(FIRST ? 2 : 4, 3);
    mbar_wait(xchb, 0);
    if (tid == 128) STAMP(FIRST ? 2 : 4, 5);
    const uint8_t* xp = xch + (tid - 128) * 16;
    if (FIRST) {
      const float4 p = *(const float4*)xp;
      mu0 += __shfl_sync(~0u, (keep[40] + p.x) + (keep[41] + p.y), 0, 4);
      mu1 += __shfl_sync(~0u, (keep[42] + p.z) + (keep[43] + p.w), 0, 4);
      if (n == 0 && c == 0) { g_hmean[row] = mu0; g_hmean[row + 8] = mu1; }
      mu0 = -mu0; mu1 = -mu1;
    }
    float q0 = 0.f, q1 = 0.f;
#pragma unroll
    for (int j = 0; j < 10; j++) {
      const float4 p = *(const float4*)(xp + (j + EX) * 4096);
      const float x0 = (keep[4 * j] + p.x) + (bf_lo(rv[2 * j]) + mu0), x1 = (keep[4 * j + 1] + p.y) + (bf_hi(rv[2 * j]) + mu0);
      const float y0 = (keep[4 * j + 2] + p.z) + (bf_lo(rv[2 * j + 1]) + mu1), y1 = (keep[4 * j + 3] + p.w) + (bf_hi(rv[2 * j + 1]) + mu1);
      if (FIRST) {
        *(uint32_t*)(himg + img_off(n * 10 + j)) = pack_bf16(x0, x1);
        *(uint32_t*)(himg + img_off(n * 10 + j) + 1024) = pack_bf16(y0, y1);
        q0 = fmaf(x0, x0, fmaf(x1, x1, q0)); q1 = fmaf(y0, y0, fmaf(y1, y1, q1));
      } else {
        *(uint32_t*)(sp + j * 16) = pack_bf16(x0, x1);
        *(uint32_t*)(sp + 1280 + j * 16) = pack_bf16(y0, y1);
      }
    }
    if (FIRST) {
      q0 += __shfl_xor_sync(~0u, q0, 1); q0 += __shfl_xor_sync(~0u, q0, 2);
      q1 += __shfl_xor_sync(~0u, q1, 1); q1 += __shfl_xor_sync(~0u, q1, 2);
      if (c < 2) g_hpart[n * S_ + row + c * 8] = c ? q1 : q0;
    } else {
      fence_async();
      bar_sync(1 + wg, 128);
      if ((tid & 127) == 0) {
        tma2d_st(&tmr, n * 80, m * 128 + wg * 64, smem_u32(stg) + wg * 10240);
        bulk_commit_wait();
      }
      __syncwarp();
    }
    if (tid == 128) STAMP(FIRST ? 2 : 4, 4);
  } else {
    cluster_arrive();
    cluster_wait();
    cluster_arrive();
  }
  cluster_wait();
}

constexpr int K4_G = 2, K4_NS = 4, K4_NJ = 20;
constexpr int K4_RB = 163840, K4_BST = 7168 * K4_G, K4_XCH = 147456, K4_STG = K4_XCH + 40960, K4_BAR = K4_RB + K4_NS * K4_BST;
constexpr int K4_SMEM = K4_BAR + 384;

__device__ __forceinline__ void wait_flags(const uint4* f, uint32_t tag) {
  for (uint32_t it = 0;; it++) {
    uint4 a, b;
    asm volatile("ld.acquire.gpu.global.v4.u32 {%0, %1, %2, %3}, [%4];" : "=r"(a.x), "=r"(a.y), "=r"(a.z), "=r"(a.w) : "l"(f) : "memory");
    asm volatile("ld.acquire.gpu.global.v4.u32 {%0, %1, %2, %3}, [%4];" : "=r"(b.x), "=r"(b.y), "=r"(b.z), "=r"(b.w) : "l"(f + 1) : "memory");
    if (a.x == tag && a.y == tag && a.z == tag && a.w == tag && b.x == tag && b.y == tag && b.z == tag && b.w == tag) break;
    if (it > (1u << 20)) wait_timeout();
    __nanosleep(50);
  }
  asm volatile("fence.proxy.async.global;" ::: "memory");
}

__global__ void __cluster_dims__(2, 1, 1) __launch_bounds__(384, 1)
k45_ffn(const __grid_constant__ CUtensorMap tmo) {
  extern __shared__ __align__(1024) uint8_t sm[];
  const uint32_t sbase = smem_u32(sm);
  const uint32_t afull = sbase + K4_BAR, bfull = afull + 80, bempty = bfull + 8 * K4_NS, full3 = bempty + 8 * K4_NS;
  const uint32_t empty3 = full3 + 32, afree = empty3 + 32, xchb = afree + 32;
  const int tid = threadIdx.x, lane = tid & 31;
  const int warp = __shfl_sync(~0u, tid >> 5, 0);
  const int rank = blockIdx.x & 1;
  const int n1 = (blockIdx.x >> 1) & 7, m1 = (blockIdx.x >> 4) * 2 + rank;
  const int n3 = blockIdx.x & 7, m3 = blockIdx.x >> 3;
  if (tid == 0) STAMP(3, 0);
  if (warp == 8) {
    if (elect_one()) {
#pragma unroll
      for (int i = 0; i < 10; i++) mbar_init(afull + 8 * i, 1);
#pragma unroll
      for (int i = 0; i < 4; i++) {
        mbar_init(bfull + 8 * i, 1); mbar_init(bempty + 8 * i, 4); mbar_init(full3 + 8 * i, 1); mbar_init(empty3 + 8 * i, 4);
        mbar_init(afree + 8 * i, 2);
      }
      mbar_init(xchb, 1);
      mbar_expect(xchb, 40960);
      asm volatile("fence.mbarrier_init.release.cluster;" ::: "memory");
    }
    __syncwarp();
  }
  cluster_arrive();
  if (warp >= 8) {
    cluster_wait();
    if (warp == 8) {
      if (lane == 0) STAMP(3, 7);
      const uint8_t* src = (const uint8_t*)g_wgu + n1 * 552960;
      const uint8_t* hb = (const uint8_t*)g_h + (size_t)m1 * 163840;
#pragma unroll 1
      for (int j = 0; j < 40; j++) {
        const uint32_t s8 = (j & 3) * 8, sz = j < 20 ? 14336 : 13312;
#define K4PRE 2
        if (j == K4PRE) {
          pdl_wait();
          if (lane == 0) STAMP(3, 1);
          if (elect_one()) {
#pragma unroll
            for (int kt = 0; kt < K4PRE / 2 + 1; kt++) { mbar_expect(afull + 8 * kt, 16384); bulk_ld(sbase + kt * 16384, hb + kt * 16384, 16384, afull + 8 * kt); }
          }
        }
        if (j >= 4) mbar_wait(bempty + s8, ((j >> 2) - 1) & 1);
        if (elect_one()) {
          mbar_expect(bfull + s8, sz);
          if ((j & 1) == rank) bulk_ld_mc(sbase + K4_RB + s8 * (K4_BST / 8), src, sz, bfull + s8);
          if (j > K4PRE && j < 18 && (j & 1)) {
            mbar_expect(afull + 4 + j * 4, 16384);
            bulk_ld(sbase + 8192 + j * 8192, hb + 8192 + j * 8192, 16384, afull + 4 + j * 4);
          }
        }
        src += sz;
      }
    } else if (warp == 9) {
      prefetch_map(&tmo);
      const uint32_t tag = __ldcg(&g_epoch);
#pragma unroll 1
      for (int ph = 0; ph < 2; ph++) {
        bar_sync(5 + ph, 256 + 32);
        if (lane == 0) {
          asm volatile("st.release.gpu.global.u32 [%0], %1;" ::"l"((uint32_t*)&g_flag[ph * 32 + m1 * 2] + n1), "r"(tag) : "memory");
          STAMP(3, 5 + ph);
        }
        __syncwarp();
      }
    } else {
      const uint8_t* wk = (const uint8_t*)g_wd + n3 * 276480;
      const uint8_t* ws = (const uint8_t*)g_wd + (n3 ^ 1) * 276480;
      const uint8_t* ab = (const uint8_t*)g_hh + (size_t)m3 * 442368;
      const uint32_t tag = __ldcg(&g_epoch);
#pragma unroll 1
      for (int i = 0; i < 16; i++) {
        const int kt = i < 7 ? rank * 7 + i : (i < 11 ? rank * 4 + 7 + i : 11 + i);
        const uint32_t sa = sbase + (i & 3) * 36864, fb = full3 + 8 * (i & 3);
        if (i < 4) mbar_wait(afree + 8 * i, 0);
        else mbar_wait(empty3 + 8 * (i & 3), ((i >> 2) - 1) & 1);
        if (warp == 10) {
          if (elect_one()) {
            mbar_expect(fb, i < 11 ? 36864 : 26624);
            bulk_ld(sa + 16384, wk + kt * 10240, 10240, fb);
            if (i < 11) bulk_ld(sa + 26624, ws + kt * 10240, 10240, fb);
          }
        } else {
          if (i == 0 || i == 7) {
            wait_flags(&g_flag[(i ? 32 : 0) + m3 * 2], tag);
            if (lane == 0) STAMP(4, i ? 7 : 6);
          }
          if (elect_one()) {
            if (i < 11) bulk_ld(sa, ab + kt * 16384, 16384, fb);
            else bulk_ld_mc(sa + rank * 8192, ab + kt * 16384 + rank * 8192, 8192, fb);
          }
        }
      }
    }
    __syncwarp();
    cluster_arrive();
    asm volatile("barrier.cluster.wait.aligned; // producers" ::: "memory");
  } else {
    const int wg = warp >> 2;
    const uint64_t da0 = mkdesc(sbase + wg * 8192, 128, 1024, 0);
    const uint64_t db0 = mkdesc(sbase + K4_RB, 128, 256, 0);
    cluster_wait();
    float a1[112], a2[104];
    int s = 0, ph = 0, sprev = 0;
#pragma unroll 1
    for (int j = 0; j < K4_NJ; j++) {
      if ((j * K4_G) % 4 == 0) mbar_wait(afull + 2 * K4_G * j, 0);
      mbar_wait(bfull + 8 * s, ph);
      if (j == 0 && tid == 0) STAMP(3, 2);
      const uint64_t da = da0 + ((j * K4_G) >> 2) * 1024 + ((j * K4_G) & 3) * 16, db = db0 + s * (K4_BST >> 4);
      WG_FENCE();
#pragma unroll
      for (int k = 0; k < K4_G; k++) wgmma_ss_n224(a1, da + k * 16, db + k * 448, (j | k) != 0);
      WG_COMMIT();
      if (j > 0) {
        WG_WAIT(1);
        if ((tid & 127) < 2) mbar_arrive_cta(bempty + 8 * sprev, tid & 1);
      }
      sprev = s;
      if (++s == K4_NS) { s = 0; ph ^= 1; }
    }
    float acc[80];
    uint8_t* hd = (uint8_t*)g_hh + (size_t)m1 * 442368 + warp * 2048 + lane * 4;
    WG_WAIT(0);
    fence_regs(a1);
    if ((tid & 127) < 2) mbar_arrive_cta(bempty + 8 * ((K4_NJ - 1) % K4_NS), tid & 1);
    if (tid == 0) STAMP(3, 3);
#define STORE_H(a, off, q, c) do { uint8_t* p_ = hd + img_off(q); \
      *(uint32_t*)p_ = pack_bf16(a[4 * (c)] * a[off + 4 * (c)], a[4 * (c) + 1] * a[off + 1 + 4 * (c)]); \
      *(uint32_t*)(p_ + 1024) = pack_bf16(a[4 * (c) + 2] * a[off + 2 + 4 * (c)], a[4 * (c) + 3] * a[off + 3 + 4 * (c)]); } while (0)
#pragma unroll
    for (int c = 0; c < 14; c++) STORE_H(a1, 56, n1 * 14 + c, c);
    bar_arrive(5, 256 + 32);
#pragma unroll 1
    for (int j = 0; j < K4_NJ; j++) {
      mbar_wait(bfull + 8 * s, ph);
      const uint64_t da = da0 + ((j * K4_G) >> 2) * 1024 + ((j * K4_G) & 3) * 16, db = db0 + s * (K4_BST >> 4);
      WG_FENCE();
#pragma unroll
      for (int k = 0; k < K4_G; k++) wgmma_ss_n208(a2, da + k * 16, db + k * 416, (j | k) != 0);
      WG_COMMIT();
      if (j > 0) {
        WG_WAIT(1);
        if (j <= K4_NJ - K4_NS && (tid & 127) < 2) mbar_arrive_cta(bempty + 8 * sprev, tid & 1);
        if (j * K4_G >= 12 && ((j * K4_G) & 7) == 4 && (tid & 127) == 0) mbar_arrive(afree + (j * K4_G - 12));
      }
      sprev = s;
      if (++s == K4_NS) { s = 0; ph ^= 1; }
    }
    WG_WAIT(0);
    fence_regs(a2);
    if (tid == 0) STAMP(3, 4);
#pragma unroll
    for (int c = 0; c < 13; c++) STORE_H(a2, 52, 112 + n1 * 13 + c, c);
    bar_arrive(6, 256 + 32);
    float (&keep)[40] = ((Acc<40>*)acc)->v;
    const uint64_t db3 = mkdesc(sbase + 16384, 128, 1024, 0);
#pragma unroll 1
    for (int i = 0; i < 11; i++) {
      mbar_wait(full3 + 8 * (i & 3), (i >> 2) & 1);
      if (i == 0 && tid == 0) STAMP(4, 2);
      const uint64_t da = da0 + (i & 3) * 2304, db = db3 + (i & 3) * 2304;
      WG_FENCE();
#pragma unroll
      for (int k = 0; k < 4; k++) wgmma_ss_n160(acc, da + k * 16, db + k * 16, (i | k) != 0);
      WG_COMMIT();
      if (i > 0) {
        WG_WAIT(1);
        if ((tid & 127) < 2) mbar_arrive_cta(empty3 + 8 * ((i - 1) & 3), tid & 1);
      }
    }
    const int g = lane >> 2, c = lane & 3, row = m3 * 128 + warp * 16 + g;
    const uint8_t* himg = (const uint8_t*)g_h + (size_t)m3 * 163840 + warp * 2048 + lane * 4;
    uint32_t rv[20];
    const float mu0 = __ldcg(&g_hmean[row]), mu1 = __ldcg(&g_hmean[row + 8]);
    float r0 = __ldcg(&g_hpart[c * 2 * S_ + row]) + __ldcg(&g_hpart[(c * 2 + 1) * S_ + row]);
    float r1 = __ldcg(&g_hpart[c * 2 * S_ + row + 8]) + __ldcg(&g_hpart[(c * 2 + 1) * S_ + row + 8]);
#pragma unroll
    for (int j = 0; j < 10; j++) {
      rv[2 * j] = __ldcg((const uint32_t*)(himg + img_off(n3 * 10 + j)));
      rv[2 * j + 1] = __ldcg((const uint32_t*)(himg + img_off(n3 * 10 + j) + 1024));
    }
    const uint32_t rx = mapa(sbase + K4_XCH + tid * 16, rank ^ 1), rb = mapa(xchb, rank ^ 1);
    WG_WAIT(0);
    fence_regs(acc);
    if ((tid & 127) < 2) mbar_arrive_cta(empty3 + 16, tid & 1);
    if (tid == 0) STAMP(4, 1);
#pragma unroll
    for (int i = 11; i < 16; i++) {
      mbar_wait(full3 + 8 * (i & 3), (i >> 2) & 1);
      const uint64_t da = da0 + (i & 3) * 2304, db = db3 + (i & 3) * 2304;
      WG_FENCE();
#pragma unroll
      for (int k = 0; k < 4; k++) wgmma_ss_n80(keep, da + k * 16, db + k * 16, 1);
      WG_COMMIT();
      if (i == 12) {
        WG_WAIT(1);
        if ((tid & 127) < 2) mbar_arrive_cta(empty3 + 24, tid & 1);
      }
#pragma unroll
      for (int j = (i - 11) * 3; j < (i - 11) * 3 + 3; j++)
        if (j < 10) st_async4(rx + j * 4096, acc[40 + 4 * j], acc[41 + 4 * j], acc[42 + 4 * j], acc[43 + 4 * j], rb);
    }
    cluster_arrive();
    r0 += __shfl_xor_sync(~0u, r0, 1); r1 += __shfl_xor_sync(~0u, r1, 1);
    r0 += __shfl_xor_sync(~0u, r0, 2); r1 += __shfl_xor_sync(~0u, r1, 2);
    r0 = rcp(r0 * (1.f / D_) + 1e-5f); r1 = rcp(r1 * (1.f / D_) + 1e-5f);
    asm volatile("" : "+f"(r0), "+f"(r1)::"memory");
    WG_WAIT(0);
    fence_regs(keep);
    if (tid == 0) STAMP(4, 3);
    mbar_wait(xchb, 0);
    if (tid == 0) STAMP(4, 5);
    uint8_t* sp = sm + K4_STG + (warp * 16 + g) * 160 + c * 4;
#pragma unroll
    for (int j = 0; j < 10; j++) {
      const float4 p = *(const float4*)(sm + K4_XCH + tid * 16 + j * 4096);
      *(uint32_t*)(sp + j * 16) = pack_bf16(fmaf(keep[4 * j] + p.x, r0, bf_lo(rv[2 * j]) + mu0), fmaf(keep[4 * j + 1] + p.y, r0, bf_hi(rv[2 * j]) + mu0));
      *(uint32_t*)(sp + 1280 + j * 16) = pack_bf16(fmaf(keep[4 * j + 2] + p.z, r1, bf_lo(rv[2 * j + 1]) + mu1), fmaf(keep[4 * j + 3] + p.w, r1, bf_hi(rv[2 * j + 1]) + mu1));
    }
    fence_async();
    bar_sync(1 + wg, 128);
    if ((tid & 127) == 0) {
      tma2d_st(&tmo, n3 * 80, m3 * 128 + wg * 64, sbase + K4_STG + wg * 10240);
      bulk_commit_wait();
    }
    __syncwarp();
    if (tid == 0) STAMP(4, 4);
    asm volatile("barrier.cluster.wait.aligned; // consumers" ::: "memory");
  }
}

typedef CUresult (*EncodeFn)(CUtensorMap*, CUtensorMapDataType, cuuint32_t, void*, const cuuint64_t*, const cuuint64_t*,
                             const cuuint32_t*, const cuuint32_t*, CUtensorMapInterleave, CUtensorMapSwizzle,
                             CUtensorMapL2promotion, CUtensorMapFloatOOBfill);

static CUtensorMap make_map(EncodeFn enc, const void* p, uint64_t inner, uint64_t outer, uint32_t box_inner,
                            uint32_t box_outer, CUtensorMapSwizzle swz) {
  CUtensorMap m;
  cuuint64_t gd[2] = {inner, outer};
  cuuint64_t gs[1] = {inner * 2};
  cuuint32_t bd[2] = {box_inner, box_outer};
  cuuint32_t es[2] = {1, 1};
  enc(&m, CU_TENSOR_MAP_DATA_TYPE_BFLOAT16, 2, (void*)p, gd, gs, bd, es, CU_TENSOR_MAP_INTERLEAVE_NONE, swz,
      CU_TENSOR_MAP_L2_PROMOTION_L2_256B, CU_TENSOR_MAP_FLOAT_OOB_FILL_NONE);
  return m;
}

static CUtensorMap make_map_img(EncodeFn enc, const void* p, uint64_t k, uint64_t n, uint32_t rows, uint32_t chunks,
                                uint32_t groups) {
  CUtensorMap m;
  cuuint64_t gd[4] = {8, rows, n / 8, k / rows};
  cuuint64_t gs[3] = {n * 2, 16, n * 2 * rows};
  cuuint32_t bd[4] = {8, rows, chunks, groups};
  cuuint32_t es[4] = {1, 1, 1, 1};
  enc(&m, CU_TENSOR_MAP_DATA_TYPE_BFLOAT16, 4, (void*)p, gd, gs, bd, es, CU_TENSOR_MAP_INTERLEAVE_NONE,
      CU_TENSOR_MAP_SWIZZLE_NONE, CU_TENSOR_MAP_L2_PROMOTION_L2_128B, CU_TENSOR_MAP_FLOAT_OOB_FILL_NONE);
  return m;
}

template <typename... KArgs, typename... Args>
static void launch(void (*k)(KArgs...), int grid, int threads, int smem, bool pdl, Args... args) {
  cudaLaunchConfig_t cfg = {};
  cfg.gridDim = dim3(grid);
  cfg.blockDim = dim3(threads);
  cfg.dynamicSmemBytes = smem;
  cfg.stream = cudaStreamPerThread;
  cudaLaunchAttribute at[1];
  at[0].id = cudaLaunchAttributeProgrammaticStreamSerialization;
  at[0].val.programmaticStreamSerializationAllowed = 1;
  cfg.attrs = at;
  cfg.numAttrs = pdl ? 1 : 0;
  cudaLaunchKernelEx(&cfg, k, KArgs(args)...);
}

extern "C" void kernel_launch(void* const* d_in, const int* in_sizes, int n_in, void* d_out, int out_size) {
  const bf16* x = (const bf16*)d_in[0];
  const bf16* wqkv = (const bf16*)d_in[1];
  const bf16* wo = (const bf16*)d_in[2];
  const bf16* wg = (const bf16*)d_in[4];
  const bf16* wu = (const bf16*)d_in[5];
  const bf16* wd = (const bf16*)d_in[6];

  static EncodeFn enc = nullptr;
  static void *p_o, *p_wo;
  if (!enc) {
    void* fn = nullptr;
    cudaDriverEntryPointQueryResult qr;
    cudaGetDriverEntryPoint("cuTensorMapEncodeTiled", &fn, cudaEnableDefault, &qr);
    enc = (EncodeFn)fn;
    cudaGetSymbolAddress(&p_o, g_o);
    cudaGetSymbolAddress(&p_wo, g_wo);
    cudaFuncSetAttribute(k1_qkv, cudaFuncAttributeMaxDynamicSharedMemorySize, K1_SMEM);
    cudaFuncSetAttribute(k2_attn, cudaFuncAttributeMaxDynamicSharedMemorySize, K2_SMEM);
    cudaFuncSetAttribute(k3_proj<3, 4, true>, cudaFuncAttributeMaxDynamicSharedMemorySize, K3_SMEM);
    cudaFuncSetAttribute(k45_ffn, cudaFuncAttributeMaxDynamicSharedMemorySize, K4_SMEM);
  }
  const CUtensorMap tmx = make_map(enc, x, D_, S_, 64, 96, CU_TENSOR_MAP_SWIZZLE_128B);
  const CUtensorMap tmw = make_map(enc, wqkv, 3 * D_, D_, 32, 64, CU_TENSOR_MAP_SWIZZLE_64B);
  const CUtensorMap tmxr = make_map(enc, x, D_, S_, 80, 64, CU_TENSOR_MAP_SWIZZLE_NONE);
  Maps5 maps;
  maps.m[0] = make_map_img(enc, wg, D_, F_, 16, 14, 2); maps.m[1] = make_map_img(enc, wu, D_, F_, 16, 14, 2);
  maps.m[2] = make_map_img(enc, wg, D_, F_, 16, 13, 2); maps.m[3] = make_map_img(enc, wu, D_, F_, 16, 13, 2);
  maps.m[4] = make_map_img(enc, wd, F_, D_, 64, 10, 1);
  const CUtensorMap tmout = make_map(enc, d_out, D_, S_, 80, 64, CU_TENSOR_MAP_SWIZZLE_NONE);

  launch(k1_qkv, 132, 512, K1_SMEM, false, tmx, tmw, x, wqkv, wo);
  launch(k2_attn, 128, 512, K2_SMEM, true, maps, 0x007f007fu);
  launch(k3_proj<3, 4, true>, 128, 384, K3_SMEM, true, tmxr, (const uint4*)p_o, (const uint4*)p_wo);
  launch(k45_ffn, 128, 384, K4_SMEM, true, tmout);
}
```

```cpp
#include <cuda_runtime.h>
#include <cuda_bf16.h>
#include <cuda.h>
#include <stdint.h>

typedef __nv_bfloat16 bf16;

constexpr int S_ = 2048, D_ = 640, F_ = 1728;
constexpr int HEAD_IMG = 98304;
#define PMASK 0xDB6D
constexpr uint32_t POLY_MASK = PMASK;
constexpr float QSCALE = 0.22360679774997896f * 1.4426950408889634f;

__device__ __align__(1024) uint4 g_qkv[96 * HEAD_IMG / 16];
__device__ __align__(1024) uint4 g_o[S_ * D_ / 8];
__device__ __align__(1024) uint4 g_h[S_ * D_ / 8];
__device__ __align__(1024) uint4 g_hh[S_ * F_ / 8];
__device__ __align__(1024) uint4 g_wo[D_ * D_ / 8];
__device__ __align__(1024) uint4 g_wgu[2 * D_ * F_ / 8];
__device__ __align__(1024) uint4 g_wd[F_ * D_ / 8];
__device__ uint4 g_rowstat[S_];
__device__ uint4 g_cpart[10 * 12 * 80];
__device__ float g_nrm[64 * 128];
__device__ uint4 g_wm[D_];
__device__ float g_hmean[S_];
__device__ float g_hpart[8 * S_];
__device__ uint4 g_flag[2 * 16 * 2];
__device__ unsigned g_epoch;

#define STAMP(k, i)
__device__ __forceinline__ uint32_t smem_u32(const void* p) { return (uint32_t)__cvta_generic_to_shared(p); }
__device__ __forceinline__ void mbar_init(uint32_t a, uint32_t c) {
  asm volatile("mbarrier.init.shared::cta.b64 [%0], %1;" ::"r"(a), "r"(c) : "memory");
}
__device__ __forceinline__ void mbar_expect(uint32_t a, uint32_t bytes) {
  asm volatile("mbarrier.arrive.expect_tx.shared::cta.b64 _, [%0], %1;" ::"r"(a), "r"(bytes) : "memory");
}
__device__ __forceinline__ void mbar_arrive(uint32_t a) {
  asm volatile("mbarrier.arrive.shared::cta.b64 _, [%0];" ::"r"(a) : "memory");
}
__device__ __forceinline__ void mbar_arrive_cta(uint32_t a, uint32_t cta) {
  asm volatile("{\n.reg .b32 r;\nmapa.shared::cluster.u32 r, %0, %1;\n"
               "mbarrier.arrive.shared::cluster.b64 _, [r];\n}" ::"r"(a), "r"(cta) : "memory");
}
__device__ __forceinline__ bool mbar_try(uint32_t a, uint32_t ph) {
  uint32_t ok;
  asm volatile("{\n.reg .pred p;\nmbarrier.try_wait.parity.shared::cta.b64 p, [%1], %2;\nselp.u32 %0, 1, 0, p;\n}"
               : "=r"(ok) : "r"(a), "r"(ph) : "memory");
  return ok;
}
__device__ __noinline__ void wait_timeout() { __trap(); }
__device__ __forceinline__ void mbar_wait(uint32_t a, uint32_t ph) {
  if (mbar_try(a, ph)) return;
  uint32_t it = 0;
  while (!mbar_try(a, ph)) if (++it > (1u << 22)) wait_timeout();
}
__device__ __forceinline__ void tma2d(uint32_t dst, const CUtensorMap* m, int c0, int c1, uint32_t bar) {
  asm volatile("cp.async.bulk.tensor.2d.shared::cluster.global.mbarrier::complete_tx::bytes [%0], [%1, {%3, %4}], [%2];"
               ::"r"(dst), "l"(m), "r"(bar), "r"(c0), "r"(c1) : "memory");
}
__device__ __forceinline__ void tma2d_mc(uint32_t dst, const CUtensorMap* m, int c0, int c1, uint32_t bar) {
  asm volatile("cp.async.bulk.tensor.2d.shared::cluster.global.mbarrier::complete_tx::bytes.multicast::cluster "
               "[%0], [%1, {%3, %4}], [%2], %5;"
               ::"r"(dst), "l"(m), "r"(bar), "r"(c0), "r"(c1), "h"((uint16_t)3) : "memory");
}
__device__ __forceinline__ void bulk_ld(uint32_t dst, const void* src, uint32_t bytes, uint32_t bar) {
  asm volatile("cp.async.bulk.shared::cluster.global.mbarrier::complete_tx::bytes [%0], [%1], %2, [%3];"
               ::"r"(dst), "l"(src), "r"(bytes), "r"(bar) : "memory");
}
__device__ __forceinline__ void bulk_ld_mc(uint32_t dst, const void* src, uint32_t bytes, uint32_t bar) {
  asm volatile("cp.async.bulk.shared::cluster.global.mbarrier::complete_tx::bytes.multicast::cluster "
               "[%0], [%1], %2, [%3], %4;"
               ::"r"(dst), "l"(src), "r"(bytes), "r"(bar), "h"((uint16_t)3) : "memory");
}
__device__ __forceinline__ void cluster_arrive() { asm volatile("barrier.cluster.arrive.relaxed.aligned;" ::: "memory"); }
__device__ __forceinline__ void cluster_wait() { asm volatile("barrier.cluster.wait.aligned;" ::: "memory"); }
__device__ __forceinline__ void bulk_st(void* dst, uint32_t src, uint32_t bytes) {
  asm volatile("cp.async.bulk.global.shared::cta.bulk_group [%0], [%1], %2;" ::"l"(dst), "r"(src), "r"(bytes) : "memory");
}
__device__ __forceinline__ void tma2d_st(const CUtensorMap* m, int c0, int c1, uint32_t src) {
  asm volatile("cp.async.bulk.tensor.2d.global.shared::cta.bulk_group [%0, {%2, %3}], [%1];"
               ::"l"(m), "r"(src), "r"(c0), "r"(c1) : "memory");
}
__device__ __forceinline__ void bulk_commit_wait() {
  asm volatile("cp.async.bulk.commit_group;\ncp.async.bulk.wait_group.read 0;" ::: "memory");
}
__device__ __forceinline__ uint32_t mapa(uint32_t a, uint32_t cta) {
  uint32_t r;
  asm("mapa.shared::cluster.u32 %0, %1, %2;" : "=r"(r) : "r"(a), "r"(cta));
  return r;
}
__device__ __forceinline__ void st_async4(uint32_t dst, float a, float b, float c, float d, uint32_t bar) {
  asm volatile("st.async.shared::cluster.mbarrier::complete_tx::bytes.v4.f32 [%0], {%1, %2, %3, %4}, [%5];"
               ::"r"(dst), "f"(a), "f"(b), "f"(c), "f"(d), "r"(bar) : "memory");
}
__device__ __forceinline__ void fence_async() { asm volatile("fence.proxy.async.shared::cta;" ::: "memory"); }
__device__ __forceinline__ void prefetch_map(const CUtensorMap* m) {
  asm volatile("prefetch.tensormap [%0];" ::"l"(m) : "memory");
}
__device__ __forceinline__ bool elect_one() {
  uint32_t p;
  asm volatile("{\n.reg .pred q;\nelect.sync _|q, 0xffffffff;\nselp.u32 %0, 1, 0, q;\n}" : "=r"(p));
  return p;
}
__device__ __forceinline__ void pdl_wait() { asm volatile("griddepcontrol.wait;" ::: "memory"); }
__device__ __forceinline__ void pdl_trigger() { asm volatile("griddepcontrol.launch_dependents;" ::: "memory"); }
__device__ __forceinline__ void bar_sync(int id, int n) { asm volatile("bar.sync %0, %1;" ::"r"(id), "r"(n) : "memory"); }
__device__ __forceinline__ void bar_arrive(int id, int n) { asm volatile("bar.arrive %0, %1;" ::"r"(id), "r"(n) : "memory"); }
#define WG_FENCE() asm volatile("wgmma.fence.sync.aligned;" ::: "memory")
#define WG_COMMIT() asm volatile("wgmma.commit_group.sync.aligned;" ::: "memory")
#define WG_WAIT(n) asm volatile("wgmma.wait_group.sync.aligned %0;" ::"n"(n) : "memory")
__device__ __forceinline__ uint64_t mkdesc(uint32_t addr, uint32_t lbo, uint32_t sbo, uint32_t sw) {
  return (uint64_t)((addr & 0x3FFFF) >> 4) | ((uint64_t)(lbo >> 4) << 16) | ((uint64_t)(sbo >> 4) << 32) |
         ((uint64_t)sw << 62);
}
template <int N> __device__ __forceinline__ void fence_regs(float (&r)[N]) {
#pragma unroll
  for (int i = 0; i < N; i++) asm volatile("" : "+f"(r[i])::"memory");
}
__device__ __forceinline__ uint32_t pack_bf16(float lo, float hi) {
  uint32_t r;
  asm("cvt.rn.bf16x2.f32 %0, %1, %2;" : "=r"(r) : "f"(hi), "f"(lo));
  return r;
}
__device__ __forceinline__ float bf_lo(uint32_t v) { return __uint_as_float(v << 16); }
__device__ __forceinline__ float bf_hi(uint32_t v) { return __uint_as_float(v & 0xffff0000u); }
__device__ __forceinline__ float ex2(float x) {
  float y;
  asm("ex2.approx.ftz.f32 %0, %1;" : "=f"(y) : "f"(x));
  return y;
}
__device__ __forceinline__ uint4 ldg_nc(const void* p) {
  uint4 v;
  asm volatile("ld.global.nc.L1::no_allocate.v4.u32 {%0, %1, %2, %3}, [%4];"
               : "=r"(v.x), "=r"(v.y), "=r"(v.z), "=r"(v.w) : "l"(p));
  return v;
}

__device__ __forceinline__ uint4 ld_relaxed(const uint4* p) {
  uint64_t a, b;
  asm volatile("ld.relaxed.gpu.global.v2.u64 {%0, %1}, [%2];" : "=l"(a), "=l"(b) : "l"(p) : "memory");
  return make_uint4((uint32_t)a, (uint32_t)(a >> 32), (uint32_t)b, (uint32_t)(b >> 32));
}
__device__ __forceinline__ void st_relaxed(uint4* p, float x, float y, uint32_t tag) {
  const uint64_t a = ((uint64_t)tag << 32) | __float_as_uint(x), b = ((uint64_t)tag << 32) | __float_as_uint(y);
  asm volatile("st.relaxed.gpu.global.v2.u64 [%0], {%1, %2};" ::"l"(p), "l"(a), "l"(b) : "memory");
}
__device__ __forceinline__ void tma4d(uint32_t dst, const CUtensorMap* m, int c2, int c3, uint32_t bar) {
  asm volatile("cp.async.bulk.tensor.4d.shared::cluster.global.mbarrier::complete_tx::bytes [%0], [%1, {%3, %3, %4, %5}], [%2];"
               ::"r"(dst), "l"(m), "r"(bar), "r"(0), "r"(c2), "r"(c3) : "memory");
}
#define ACC8(a, v) do { a[0] += bf_lo(v.x); a[1] += bf_hi(v.x); a[2] += bf_lo(v.y); a[3] += bf_hi(v.y); \
                        a[4] += bf_lo(v.z); a[5] += bf_hi(v.z); a[6] += bf_lo(v.w); a[7] += bf_hi(v.w); } while (0)

__device__ __forceinline__ void wgmma_ss_n256(float (&d)[128], uint64_t da, uint64_t db, int sd) {
  asm volatile("{\n.reg .pred p;\nsetp.ne.b32 p, %130, 0;\n"
      "wgmma.mma_async.sync.aligned.m64n256k16.f32.bf16.bf16 {"
      "%0, %1, %2, %3, %4, %5, %6, %7, %8, %9, %10, %11, %12, %13, %14, %15, "
      "%16, %17, %18, %19, %20, %21, %22, %23, %24, %25, %26, %27, %28, %29, %30, %31, "
      "%32, %33, %34, %35, %36, %37, %38, %39, %40, %41, %42, %43, %44, %45, %46, %47, "
      "%48, %49, %50, %51, %52, %53, %54, %55, %56, %57, %58, %59, %60, %61, %62, %63, "
      "%64, %65, %66, %67, %68, %69, %70, %71, %72, %73, %74, %75, %76, %77, %78, %79, "
      "%80, %81, %82, %83, %84, %85, %86, %87, %88, %89, %90, %91, %92, %93, %94, %95, "
      "%96, %97, %98, %99, %100, %101, %102, %103, %104, %105, %106, %107, %108, %109, %110, %111, "
      "%112, %113, %114, %115, %116, %117, %118, %119, %120, %121, %122, %123, %124, %125, %126, %127"
      "}, %128, %129, p, 1, 1, 0, 1;\n}\n"
    : "+f"(d[0]), "+f"(d[1]), "+f"(d[2]), "+f"(d[3]), "+f"(d[4]), "+f"(d[5]), "+f"(d[6]), "+f"(d[7]),
      "+f"(d[8]), "+f"(d[9]), "+f"(d[10]), "+f"(d[11]), "+f"(d[12]), "+f"(d[13]), "+f"(d[14]), "+f"(d[15]),
      "+f"(d[16]), "+f"(d[17]), "+f"(d[18]), "+f"(d[19]), "+f"(d[20]), "+f"(d[21]), "+f"(d[22]), "+f"(d[23]),
      "+f"(d[24]), "+f"(d[25]), "+f"(d[26]), "+f"(d[27]), "+f"(d[28]), "+f"(d[29]), "+f"(d[30]), "+f"(d[31]),
      "+f"(d[32]), "+f"(d[33]), "+f"(d[34]), "+f"(d[35]), "+f"(d[36]), "+f"(d[37]), "+f"(d[38]), "+f"(d[39]),
      "+f"(d[40]), "+f"(d[41]), "+f"(d[42]), "+f"(d[43]), "+f"(d[44]), "+f"(d[45]), "+f"(d[46]), "+f"(d[47]),
      "+f"(d[48]), "+f"(d[49]), "+f"(d[50]), "+f"(d[51]), "+f"(d[52]), "+f"(d[53]), "+f"(d[54]), "+f"(d[55]),
      "+f"(d[56]), "+f"(d[57]), "+f"(d[58]), "+f"(d[59]), "+f"(d[60]), "+f"(d[61]), "+f"(d[62]), "+f"(d[63]),
      "+f"(d[64]), "+f"(d[65]), "+f"(d[66]), "+f"(d[67]), "+f"(d[68]), "+f"(d[69]), "+f"(d[70]), "+f"(d[71]),
      "+f"(d[72]), "+f"(d[73]), "+f"(d[74]), "+f"(d[75]), "+f"(d[76]), "+f"(d[77]), "+f"(d[78]), "+f"(d[79]),
      "+f"(d[80]), "+f"(d[81]), "+f"(d[82]), "+f"(d[83]), "+f"(d[84]), "+f"(d[85]), "+f"(d[86]), "+f"(d[87]),
      "+f"(d[88]), "+f"(d[89]), "+f"(d[90]), "+f"(d[91]), "+f"(d[92]), "+f"(d[93]), "+f"(d[94]), "+f"(d[95]),
      "+f"(d[96]), "+f"(d[97]), "+f"(d[98]), "+f"(d[99]), "+f"(d[100]), "+f"(d[101]), "+f"(d[102]), "+f"(d[103]),
      "+f"(d[104]), "+f"(d[105]), "+f"(d[106]), "+f"(d[107]), "+f"(d[108]), "+f"(d[109]), "+f"(d[110]), "+f"(d[111]),
      "+f"(d[112]), "+f"(d[113]), "+f"(d[114]), "+f"(d[115]), "+f"(d[116]), "+f"(d[117]), "+f"(d[118]), "+f"(d[119]),
      "+f"(d[120]), "+f"(d[121]), "+f"(d[122]), "+f"(d[123]), "+f"(d[124]), "+f"(d[125]), "+f"(d[126]), "+f"(d[127])
    : "l"(da), "l"(db), "r"(sd));
}
__device__ __forceinline__ void wgmma_ss_n176(float (&d)[88], uint64_t da, uint64_t db, int sd) {
  asm volatile("{\n.reg .pred p;\nsetp.ne.b32 p, %90, 0;\n"
      "wgmma.mma_async.sync.aligned.m64n176k16.f32.bf16.bf16 {"
      "%0, %1, %2, %3, %4, %5, %6, %7, %8, %9, %10, %11, %12, %13, %14, %15, "
      "%16, %17, %18, %19, %20, %21, %22, %23, %24, %25, %26, %27, %28, %29, %30, %31, "
      "%32, %33, %34, %35, %36, %37, %38, %39, %40, %41, %42, %43, %44, %45, %46, %47, "
      "%48, %49, %50, %51, %52, %53, %54, %55, %56, %57, %58, %59, %60, %61, %62, %63, "
      "%64, %65, %66, %67, %68, %69, %70, %71, %72, %73, %74, %75, %76, %77, %78, %79, "
      "%80, %81, %82, %83, %84, %85, %86, %87"
      "}, %88, %89, p, 1, 1, 0, 1;\n}\n"
    : "+f"(d[0]), "+f"(d[1]), "+f"(d[2]), "+f"(d[3]), "+f"(d[4]), "+f"(d[5]), "+f"(d[6]), "+f"(d[7]),
      "+f"(d[8]), "+f"(d[9]), "+f"(d[10]), "+f"(d[11]), "+f"(d[12]), "+f"(d[13]), "+f"(d[14]), "+f"(d[15]),
      "+f"(d[16]), "+f"(d[17]), "+f"(d[18]), "+f"(d[19]), "+f"(d[20]), "+f"(d[21]), "+f"(d[22]), "+f"(d[23]),
      "+f"(d[24]), "+f"(d[25]), "+f"(d[26]), "+f"(d[27]), "+f"(d[28]), "+f"(d[29]), "+f"(d[30]), "+f"(d[31]),
      "+f"(d[32]), "+f"(d[33]), "+f"(d[34]), "+f"(d[35]), "+f"(d[36]), "+f"(d[37]), "+f"(d[38]), "+f"(d[39]),
      "+f"(d[40]), "+f"(d[41]), "+f"(d[42]), "+f"(d[43]), "+f"(d[44]), "+f"(d[45]), "+f"(d[46]), "+f"(d[47]),
      "+f"(d[48]), "+f"(d[49]), "+f"(d[50]), "+f"(d[51]), "+f"(d[52]), "+f"(d[53]), "+f"(d[54]), "+f"(d[55]),
      "+f"(d[56]), "+f"(d[57]), "+f"(d[58]), "+f"(d[59]), "+f"(d[60]), "+f"(d[61]), "+f"(d[62]), "+f"(d[63]),
      "+f"(d[64]), "+f"(d[65]), "+f"(d[66]), "+f"(d[67]), "+f"(d[68]), "+f"(d[69]), "+f"(d[70]), "+f"(d[71]),
      "+f"(d[72]), "+f"(d[73]), "+f"(d[74]), "+f"(d[75]), "+f"(d[76]), "+f"(d[77]), "+f"(d[78]), "+f"(d[79]),
      "+f"(d[80]), "+f"(d[81]), "+f"(d[82]), "+f"(d[83]), "+f"(d[84]), "+f"(d[85]), "+f"(d[86]), "+f"(d[87])
    : "l"(da), "l"(db), "r"(sd));
}
__device__ __forceinline__ void wgmma_ss_n168(float (&d)[84], uint64_t da, uint64_t db, int sd) {
  asm volatile("{\n.reg .pred p;\nsetp.ne.b32 p, %86, 0;\n"
      "wgmma.mma_async.sync.aligned.m64n168k16.f32.bf16.bf16 {"
      "%0, %1, %2, %3, %4, %5, %6, %7, %8, %9, %10, %11, %12, %13, %14, %15, "
      "%16, %17, %18, %19, %20, %21, %22, %23, %24, %25, %26, %27, %28, %29, %30, %31, "
      "%32, %33, %34, %35, %36, %37, %38, %39, %40, %41, %42, %43, %44, %45, %46, %47, "
      "%48, %49, %50, %51, %52, %53, %54, %55, %56, %57, %58, %59, %60, %61, %62, %63, "
      "%64, %65, %66, %67, %68, %69, %70, %71, %72, %73, %74, %75, %76, %77, %78, %79, "
      "%80, %81, %82, %83"
      "}, %84, %85, p, 1, 1, 0, 1;\n}\n"
    : "+f"(d[0]), "+f"(d[1]), "+f"(d[2]), "+f"(d[3]), "+f"(d[4]), "+f"(d[5]), "+f"(d[6]), "+f"(d[7]),
      "+f"(d[8]), "+f"(d[9]), "+f"(d[10]), "+f"(d[11]), "+f"(d[12]), "+f"(d[13]), "+f"(d[14]), "+f"(d[15]),
      "+f"(d[16]), "+f"(d[17]), "+f"(d[18]), "+f"(d[19]), "+f"(d[20]), "+f"(d[21]), "+f"(d[22]), "+f"(d[23]),
      "+f"(d[24]), "+f"(d[25]), "+f"(d[26]), "+f"(d[27]), "+f"(d[28]), "+f"(d[29]), "+f"(d[30]), "+f"(d[31]),
      "+f"(d[32]), "+f"(d[33]), "+f"(d[34]), "+f"(d[35]), "+f"(d[36]), "+f"(d[37]), "+f"(d[38]), "+f"(d[39]),
      "+f"(d[40]), "+f"(d[41]), "+f"(d[42]), "+f"(d[43]), "+f"(d[44]), "+f"(d[45]), "+f"(d[46]), "+f"(d[47]),
      "+f"(d[48]), "+f"(d[49]), "+f"(d[50]), "+f"(d[51]), "+f"(d[52]), "+f"(d[53]), "+f"(d[54]), "+f"(d[55]),
      "+f"(d[56]), "+f"(d[57]), "+f"(d[58]), "+f"(d[59]), "+f"(d[60]), "+f"(d[61]), "+f"(d[62]), "+f"(d[63]),
      "+f"(d[64]), "+f"(d[65]), "+f"(d[66]), "+f"(d[67]), "+f"(d[68]), "+f"(d[69]), "+f"(d[70]), "+f"(d[71]),
      "+f"(d[72]), "+f"(d[73]), "+f"(d[74]), "+f"(d[75]), "+f"(d[76]), "+f"(d[77]), "+f"(d[78]), "+f"(d[79]),
      "+f"(d[80]), "+f"(d[81]), "+f"(d[82]), "+f"(d[83])
    : "l"(da), "l"(db), "r"(sd));
}
__device__ __forceinline__ void wgmma_ss_n160(float (&d)[80], uint64_t da, uint64_t db, int sd) {
  asm volatile("{\n.reg .pred p;\nsetp.ne.b32 p, %82, 0;\n"
      "wgmma.mma_async.sync.aligned.m64n160k16.f32.bf16.bf16 {"
      "%0, %1, %2, %3, %4, %5, %6, %7, %8, %9, %10, %11, %12, %13, %14, %15, "
      "%16, %17, %18, %19, %20, %21, %22, %23, %24, %25, %26, %27, %28, %29, %30, %31, "
      "%32, %33, %34, %35, %36, %37, %38, %39, %40, %41, %42, %43, %44, %45, %46, %47, "
      "%48, %49, %50, %51, %52, %53, %54, %55, %56, %57, %58, %59, %60, %61, %62, %63, "
      "%64, %65, %66, %67, %68, %69, %70, %71, %72, %73, %74, %75, %76, %77, %78, %79"
      "}, %80, %81, p, 1, 1, 0, 1;\n}\n"
    : "+f"(d[0]), "+f"(d[1]), "+f"(d[2]), "+f"(d[3]), "+f"(d[4]), "+f"(d[5]), "+f"(d[6]), "+f"(d[7]),
      "+f"(d[8]), "+f"(d[9]), "+f"(d[10]), "+f"(d[11]), "+f"(d[12]), "+f"(d[13]), "+f"(d[14]), "+f"(d[15]),
      "+f"(d[16]), "+f"(d[17]), "+f"(d[18]), "+f"(d[19]), "+f"(d[20]), "+f"(d[21]), "+f"(d[22]), "+f"(d[23]),
      "+f"(d[24]), "+f"(d[25]), "+f"(d[26]), "+f"(d[27]), "+f"(d[28]), "+f"(d[29]), "+f"(d[30]), "+f"(d[31]),
      "+f"(d[32]), "+f"(d[33]), "+f"(d[34]), "+f"(d[35]), "+f"(d[36]), "+f"(d[37]), "+f"(d[38]), "+f"(d[39]),
      "+f"(d[40]), "+f"(d[41]), "+f"(d[42]), "+f"(d[43]), "+f"(d[44]), "+f"(d[45]), "+f"(d[46]), "+f"(d[47]),
      "+f"(d[48]), "+f"(d[49]), "+f"(d[50]), "+f"(d[51]), "+f"(d[52]), "+f"(d[53]), "+f"(d[54]), "+f"(d[55]),
      "+f"(d[56]), "+f"(d[57]), "+f"(d[58]), "+f"(d[59]), "+f"(d[60]), "+f"(d[61]), "+f"(d[62]), "+f"(d[63]),
      "+f"(d[64]), "+f"(d[65]), "+f"(d[66]), "+f"(d[67]), "+f"(d[68]), "+f"(d[69]), "+f"(d[70]), "+f"(d[71]),
      "+f"(d[72]), "+f"(d[73]), "+f"(d[74]), "+f"(d[75]), "+f"(d[76]), "+f"(d[77]), "+f"(d[78]), "+f"(d[79])
    : "l"(da), "l"(db), "r"(sd));
}
__device__ __forceinline__ void wgmma_ss_n88(float (&d)[44], uint64_t da, uint64_t db, int sd) {
  asm volatile("{\n.reg .pred p;\nsetp.ne.b32 p, %46, 0;\n"
      "wgmma.mma_async.sync.aligned.m64n88k16.f32.bf16.bf16 {"
      "%0, %1, %2, %3, %4, %5, %6, %7, %8, %9, %10, %11, %12, %13, %14, %15, "
      "%16, %17, %18, %19, %20, %21, %22, %23, %24, %25, %26, %27, %28, %29, %30, %31, "
      "%32, %33, %34, %35, %36, %37, %38, %39, %40, %41, %42, %43"
      "}, %44, %45, p, 1, 1, 0, 1;\n}\n"
    : "+f"(d[0]), "+f"(d[1]), "+f"(d[2]), "+f"(d[3]), "+f"(d[4]), "+f"(d[5]), "+f"(d[6]), "+f"(d[7]),
      "+f"(d[8]), "+f"(d[9]), "+f"(d[10]), "+f"(d[11]), "+f"(d[12]), "+f"(d[13]), "+f"(d[14]), "+f"(d[15]),
      "+f"(d[16]), "+f"(d[17]), "+f"(d[18]), "+f"(d[19]), "+f"(d[20]), "+f"(d[21]), "+f"(d[22]), "+f"(d[23]),
      "+f"(d[24]), "+f"(d[25]), "+f"(d[26]), "+f"(d[27]), "+f"(d[28]), "+f"(d[29]), "+f"(d[30]), "+f"(d[31]),
      "+f"(d[32]), "+f"(d[33]), "+f"(d[34]), "+f"(d[35]), "+f"(d[36]), "+f"(d[37]), "+f"(d[38]), "+f"(d[39]),
      "+f"(d[40]), "+f"(d[41]), "+f"(d[42]), "+f"(d[43])
    : "l"(da), "l"(db), "r"(sd));
}
__device__ __forceinline__ void wgmma_ss_n80(float (&d)[40], uint64_t da, uint64_t db, int sd) {
  asm volatile("{\n.reg .pred p;\nsetp.ne.b32 p, %42, 0;\n"
      "wgmma.mma_async.sync.aligned.m64n80k16.f32.bf16.bf16 {"
      "%0, %1, %2, %3, %4, %5, %6, %7, %8, %9, %10, %11, %12, %13, %14, %15, "
      "%16, %17, %18, %19, %20, %21, %22, %23, %24, %25, %26, %27, %28, %29, %30, %31, "
      "%32, %33, %34, %35, %36, %37, %38, %39"
      "}, %40, %41, p, 1, 1, 0, 1;\n}\n"
    : "+f"(d[0]), "+f"(d[1]), "+f"(d[2]), "+f"(d[3]), "+f"(d[4]), "+f"(d[5]), "+f"(d[6]), "+f"(d[7]),
      "+f"(d[8]), "+f"(d[9]), "+f"(d[10]), "+f"(d[11]), "+f"(d[12]), "+f"(d[13]), "+f"(d[14]), "+f"(d[15]),
      "+f"(d[16]), "+f"(d[17]), "+f"(d[18]), "+f"(d[19]), "+f"(d[20]), "+f"(d[21]), "+f"(d[22]), "+f"(d[23]),
      "+f"(d[24]), "+f"(d[25]), "+f"(d[26]), "+f"(d[27]), "+f"(d[28]), "+f"(d[29]), "+f"(d[30]), "+f"(d[31]),
      "+f"(d[32]), "+f"(d[33]), "+f"(d[34]), "+f"(d[35]), "+f"(d[36]), "+f"(d[37]), "+f"(d[38]), "+f"(d[39])
    : "l"(da), "l"(db), "r"(sd));
}
__device__ __forceinline__ void wgmma_rs_n128(float (&d)[64], uint32_t a0, uint32_t a1, uint32_t a2, uint32_t a3,
                                  uint64_t db, int sd) {
  asm volatile("{\n.reg .pred p;\nsetp.ne.b32 p, %69, 0;\n"
      "wgmma.mma_async.sync.aligned.m64n128k16.f32.bf16.bf16 {"
      "%0, %1, %2, %3, %4, %5, %6, %7, %8, %9, %10, %11, %12, %13, %14, %15, "
      "%16, %17, %18, %19, %20, %21, %22, %23, %24, %25, %26, %27, %28, %29, %30, %31, "
      "%32, %33, %34, %35, %36, %37, %38, %39, %40, %41, %42, %43, %44, %45, %46, %47, "
      "%48, %49, %50, %51, %52, %53, %54, %55, %56, %57, %58, %59, %60, %61, %62, %63"
      "}, {%64, %65, %66, %67}, %68, p, 1, 1, 0;\n}\n"
    : "+f"(d[0]), "+f"(d[1]), "+f"(d[2]), "+f"(d[3]), "+f"(d[4]), "+f"(d[5]), "+f"(d[6]), "+f"(d[7]),
      "+f"(d[8]), "+f"(d[9]), "+f"(d[10]), "+f"(d[11]), "+f"(d[12]), "+f"(d[13]), "+f"(d[14]), "+f"(d[15]),
      "+f"(d[16]), "+f"(d[17]), "+f"(d[18]), "+f"(d[19]), "+f"(d[20]), "+f"(d[21]), "+f"(d[22]), "+f"(d[23]),
      "+f"(d[24]), "+f"(d[25]), "+f"(d[26]), "+f"(d[27]), "+f"(d[28]), "+f"(d[29]), "+f"(d[30]), "+f"(d[31]),
      "+f"(d[32]), "+f"(d[33]), "+f"(d[34]), "+f"(d[35]), "+f"(d[36]), "+f"(d[37]), "+f"(d[38]), "+f"(d[39]),
      "+f"(d[40]), "+f"(d[41]), "+f"(d[42]), "+f"(d[43]), "+f"(d[44]), "+f"(d[45]), "+f"(d[46]), "+f"(d[47]),
      "+f"(d[48]), "+f"(d[49]), "+f"(d[50]), "+f"(d[51]), "+f"(d[52]), "+f"(d[53]), "+f"(d[54]), "+f"(d[55]),
      "+f"(d[56]), "+f"(d[57]), "+f"(d[58]), "+f"(d[59]), "+f"(d[60]), "+f"(d[61]), "+f"(d[62]), "+f"(d[63])
    : "r"(a0), "r"(a1), "r"(a2), "r"(a3), "l"(db), "r"(sd));
}
__device__ __forceinline__ void wgmma_rs_n24(float (&d)[12], uint32_t a0, uint32_t a1, uint32_t a2, uint32_t a3,
                                  uint64_t db, int sd) {
  asm volatile("{\n.reg .pred p;\nsetp.ne.b32 p, %17, 0;\n"
      "wgmma.mma_async.sync.aligned.m64n24k16.f32.bf16.bf16 {"
      "%0, %1, %2, %3, %4, %5, %6, %7, %8, %9, %10, %11"
      "}, {%12, %13, %14, %15}, %16, p, 1, 1, 1;\n}\n"
    : "+f"(d[0]), "+f"(d[1]), "+f"(d[2]), "+f"(d[3]), "+f"(d[4]), "+f"(d[5]), "+f"(d[6]), "+f"(d[7]),
      "+f"(d[8]), "+f"(d[9]), "+f"(d[10]), "+f"(d[11])
    : "r"(a0), "r"(a1), "r"(a2), "r"(a3), "l"(db), "r"(sd));
}

#define KST 4
#define K1S 4
constexpr int K1_ST = K1S, K1_STAGE = 45056;
constexpr int K1_SMEM = K1_ST * K1_STAGE + 640   + 1536   + 2560   + 128;

__device__ __forceinline__ float2 row_stats(uint4 v0, uint4 v1, uint4 v2) {
  const uint32_t wd[12] = {v0.x, v0.y, v0.z, v0.w, v1.x, v1.y, v1.z, v1.w, v2.x, v2.y, v2.z, v2.w};
  float sx = 0.f, sq = 0.f;
#pragma unroll
  for (int e = 0; e < 12; e++) {
    const float lo = bf_lo(wd[e]), hi = bf_hi(wd[e]);
    sx += lo + hi; sq = fmaf(lo, lo, fmaf(hi, hi, sq));
  }
#pragma unroll
  for (int o = 16; o; o >>= 1) { sx += __shfl_xor_sync(~0u, sx, o); sq += __shfl_xor_sync(~0u, sq, o); }
  const float mean = sx * (1.f / D_);
  return make_float2(rsqrtf(fmaxf(sq * (1.f / D_) - mean * mean, 0.f) + 1e-5f), mean);
}

__global__ void __cluster_dims__(2, 1, 1) __launch_bounds__(512, 1)
k1_qkv(const __grid_constant__ CUtensorMap tmx, const __grid_constant__ CUtensorMap tmw,
       const bf16* __restrict__ x, const bf16* __restrict__ w, const bf16* __restrict__ wo) {
  extern __shared__ __align__(1024) uint8_t sm[];
  float* cs = (float*)(sm + K1_ST * K1_STAGE);
  float2* rowab = (float2*)(sm + K1_ST * K1_STAGE + 640);
  float* red = (float*)(sm + K1_ST * K1_STAGE + 2176);
  const uint32_t sbase = smem_u32(sm);
  const uint32_t fullb = sbase + K1_ST * K1_STAGE + 4736, emptyb = fullb + 8 * K1_ST;
  const int tid = threadIdx.x, lane = tid & 31;
  const int warp = __shfl_sync(~0u, tid >> 5, 0);
  const int rank = blockIdx.x & 1, cl = blockIdx.x >> 1;
  const int m = cl / 6, n = (cl - m * 6) * 2 + rank;
  if (tid == 0) STAMP(0, 0);

  if (warp == 12) {
    if (lane == 0) {
      prefetch_map(&tmx); prefetch_map(&tmw);
      for (int i = 0; i < K1_ST; i++) { mbar_init(fullb + 8 * i, 1); mbar_init(emptyb + 8 * i, 6); }
      asm volatile("fence.mbarrier_init.release.cluster;" ::: "memory");
    }
    __syncwarp();
    cluster_arrive();
    bar_arrive(4, 512);
    if (elect_one()) {
#pragma unroll
      for (int kt = 0; kt < K1_ST; kt++) mbar_expect(fullb + 8 * kt, K1_STAGE);
#pragma unroll
      for (int j = 0; j < 5; j++) tma2d(sbase + 24576 + j * 4096, &tmw, n * 160 + j * 32, 0, fullb);
    }
    cluster_wait();
#pragma unroll 1
    for (int kt = 0; kt < 10; kt++) {
      const int s = kt % K1_ST;
      const uint32_t sa = sbase + s * K1_STAGE;
      if (kt >= K1_ST) mbar_wait(emptyb + 8 * s, ((kt / K1_ST) - 1) & 1);
      if (elect_one()) {
        if (kt >= K1_ST) mbar_expect(fullb + 8 * s, K1_STAGE);
        tma2d_mc(sa + rank * 12288, &tmx, kt * 64, m * 192 + rank * 96, fullb + 8 * s);
        if (kt > 0) {
#pragma unroll
          for (int j = 0; j < 5; j++) tma2d(sa + 24576 + j * 4096, &tmw, n * 160 + j * 32, kt * 64, fullb + 8 * s);
        }
      }
      if (kt == K1_ST - 1) pdl_trigger();
    }
    __syncwarp();
    cluster_arrive();
  } else if (warp > 12) {
    cluster_arrive();
    const int t96 = tid - 416;
    const uint32_t tag = __ldcg(&g_epoch) + 1;
    bar_sync(4, 512);
    mbar_wait(fullb, 0);
    if (m < 10) {
      const int ck = t96 % 20, rg = min(t96 / 20, 3);
      uint4 wv[16];
#pragma unroll
      for (int i = 0; i < 16; i++) wv[i] = ldg_nc(w + (size_t)(m * 64 + rg * 16 + i) * 1920 + n * 160 + ck * 8);
      float acc8[8];
#pragma unroll
      for (int i = 0; i < 8; i++) acc8[i] = 0.f;
#pragma unroll
      for (int i = 0; i < 16; i++) ACC8(acc8, wv[i]);
      *(float4*)&red[rg * 160 + ck * 8] = make_float4(acc8[0], acc8[1], acc8[2], acc8[3]);
      *(float4*)&red[rg * 160 + ck * 8 + 4] = make_float4(acc8[4], acc8[5], acc8[6], acc8[7]);
      bar_sync(1, 96);
      if (t96 < 80) {
        const float2 p0 = *(const float2*)&red[t96 * 2], p1 = *(const float2*)&red[160 + t96 * 2];
        const float2 p2 = *(const float2*)&red[320 + t96 * 2], p3 = *(const float2*)&red[480 + t96 * 2];
        st_relaxed(&g_cpart[(m * 12 + n) * 80 + t96], (p0.x + p1.x) + (p2.x + p3.x), (p0.y + p1.y) + (p2.y + p3.y), tag);
      }
    }
    if (tid == 416) STAMP(5, 7);
    bool ok = false;
    for (int it = 0; it < 64 && !ok; it++) {
      uint4 p[10], st[2];
#pragma unroll
      for (int k = 0; k < 10; k++) p[k] = ld_relaxed(&g_cpart[(k * 12 + n) * 80 + min(t96, 79)]);
#pragma unroll
      for (int k = 0; k < 2; k++) st[k] = ld_relaxed(&g_rowstat[min(m * 192 + k * 96 + t96, S_ - 1)]);
      ok = true;
      float s0 = 0.f, s1 = 0.f;
#pragma unroll
      for (int k = 0; k < 10; k++) {
        ok = ok && p[k].y == tag && p[k].w == tag;
        s0 += __uint_as_float(p[k].x); s1 += __uint_as_float(p[k].z);
      }
      if (t96 < 80) *(float2*)&cs[t96 * 2] = make_float2(s0, s1);
#pragma unroll
      for (int k = 0; k < 2; k++) {
        ok = ok && st[k].y == tag && st[k].w == tag;
        rowab[k * 96 + t96] = make_float2(__uint_as_float(st[k].x), -__uint_as_float(st[k].x) * __uint_as_float(st[k].z));
      }
      ok = __all_sync(~0u, ok);
      if (!ok) __nanosleep(300);
    }
    if (!ok) {
      const int c2 = min(t96, 79);
      float s0 = 0.f, s1 = 0.f;
#pragma unroll 1
      for (int k = 0; k < D_; k++) {
        const uint32_t v = *(const uint32_t*)(w + (size_t)k * 1920 + n * 160 + c2 * 2);
        s0 += bf_lo(v); s1 += bf_hi(v);
      }
      if (t96 < 80) *(float2*)&cs[t96 * 2] = make_float2(s0, s1);
#pragma unroll 1
      for (int i = 0; i < 64; i++) {
        const int r = (i >> 5) * 96 + (t96 & ~31) + (i & 31);
        const bf16* xr = x + (size_t)min(m * 192 + r, S_ - 1) * D_ + lane * 8;
        const float2 st = row_stats(ldg_nc(xr), ldg_nc(xr + 256), lane < 16 ? ldg_nc(xr + 512) : make_uint4(0u, 0u, 0u, 0u));
        if (lane == 0) rowab[r] = make_float2(st.x, -st.x * st.y);
      }
    }
    __syncwarp();
    bar_arrive(2, 96 + 384);
    bar_sync(1, 96);
    if (tid == 416) STAMP(0, 5);
    if (blockIdx.x < 128) {
      uint4 v[5];
      const int ck = min(t96, 79), nt = ck / 10;
#pragma unroll
      for (int i = 0; i < 5; i++) {
        const int k = blockIdx.x * 5 + i, pr = k / 40, r = k - pr * 40;
        v[i] = ldg_nc(wo + (size_t)(pr * 40 + (r < 16 ? r : (r < 32 ? r + 4 : (r < 36 ? r - 16 : r)))) * D_ + ck * 8);
      }
#pragma unroll
      for (int i = 0; i < 5; i++) {
        const int k = blockIdx.x * 5 + i;
        g_wo[((nt * 10 + (k >> 6)) * 10 + ck - nt * 10) * 64 + (k & 63)] = v[i];
        float t = ((bf_lo(v[i].x) + bf_hi(v[i].x)) + (bf_lo(v[i].y) + bf_hi(v[i].y))) +
                  ((bf_lo(v[i].z) + bf_hi(v[i].z)) + (bf_lo(v[i].w) + bf_hi(v[i].w)));
        if (t96 >= 80) t = 0.f;
#pragma unroll
        for (int o = 16; o; o >>= 1) t += __shfl_xor_sync(~0u, t, o);
        if (lane == 0) red[(t96 >> 5) * 8 + i] = t;
      }
      bar_sync(1, 96);
      if (t96 < 5) {
        const float mu = (red[t96] + red[8 + t96] + red[16 + t96]) * (1.f / D_);
        const float hi = bf_lo(pack_bf16(mu, 0.f));
        g_wm[blockIdx.x * 5 + t96] = make_uint4(pack_bf16(hi, mu - hi), 0u, 0u, 0u);
      }
    }
    if (tid == 416) STAMP(0, 7);
    __syncwarp();
    cluster_wait();
    cluster_arrive();
  } else {
    cluster_arrive();
    float acc[80];
    const uint64_t da0 = mkdesc(sbase + (warp >> 2) * 8192, 16, 1024, 1);
    const uint64_t db0 = mkdesc(sbase + 24576, 4096, 512, 2);
    const uint32_t tag = __ldcg(&g_epoch) + 1;
    const int srow = m * 192 + n * 16 + warp * 2;
    const bool dostat = warp < 8 && srow < S_;
    uint4 xv[2][3];
    bar_sync(4, 512);
    cluster_wait();
#pragma unroll
    for (int kt = 0; kt < 10; kt++) {
      const int s = kt % K1_ST;
      mbar_wait(fullb + 8 * s, (kt / K1_ST) & 1);
      if (kt == 0 && tid == 0) STAMP(0, 1);
      if (kt == 2 && tid == 0) STAMP(5, 0);
      if (kt == 4 && tid == 0) STAMP(5, 1);
      if (kt == 7 && tid == 0) STAMP(5, 2);
      const uint64_t da = da0 + s * (K1_STAGE >> 4), db = db0 + s * (K1_STAGE >> 4);
      WG_FENCE();
#pragma unroll
      for (int k = 0; k < 4; k++) wgmma_ss_n160(acc, da + k * 2, db + k * 64, (kt | k) != 0);
      WG_COMMIT();
      if (kt > 0) {
        WG_WAIT(1);
        if (kt - 1 + K1_ST < 10 && (tid & 127) < 2) mbar_arrive_cta(emptyb + 8 * ((kt - 1) % K1_ST), tid & 1);
      }
      if (kt == 0) {
#pragma unroll
        for (int i = 0; i < 2; i++) {
          const bf16* xr = x + (size_t)min(srow + i, S_ - 1) * D_ + lane * 8;
          xv[i][0] = xv[i][1] = xv[i][2] = make_uint4(0u, 0u, 0u, 0u);
          if (dostat) { xv[i][0] = ldg_nc(xr); xv[i][1] = ldg_nc(xr + 256); }
          if (dostat && lane < 16) xv[i][2] = ldg_nc(xr + 512);
        }
      }
      if ((kt == KST || kt == KST + 1) && dostat) {
        const float2 st = row_stats(xv[kt - KST][0], xv[kt - KST][1], xv[kt - KST][2]);
        if (lane == 0) st_relaxed(&g_rowstat[srow + kt - KST], st.x, st.y, tag);
      }
      __syncwarp();
    }
    cluster_arrive();
    WG_WAIT(0);
    fence_regs(acc);
    if (tid == 0) STAMP(0, 2);
    bar_sync(2, 96 + 384);
    if (tid == 0) STAMP(0, 3);
    const int row0 = m * 192 + warp * 16;
    if (row0 < S_) {
      const int g = lane >> 2, c = lane & 3, sec = n >> 2, grp = (row0 & 127) >> 3;
      const bool lo = c < 2;
      const float2 ab0 = rowab[warp * 16 + g], ab1 = rowab[warp * 16 + g + 8];
      const bool p0 = sec == 1 && ((POLY_MASK >> grp) & 1), p1 = sec == 1 && ((POLY_MASK >> (grp + 1)) & 1);
      const uint32_t padqv = sec == 0 ? (c == 2 ? 0x3F803F80u : 0x00003F80u) : (sec == 2 && c == 2 ? 0x00003F80u : 0u);
      const uint32_t padk = c == 2 ? 0x4A7A4B00u : 0x00004653u;
      const uint32_t pad0 = p0 ? padk : padqv, pad1 = p1 ? padk : padqv;
      const float f0 = sec == 0 ? QSCALE : (p0 ? 32768.f : 1.f), f1 = sec == 0 ? QSCALE : (p1 ? 32768.f : 1.f);
      const float a0 = ab0.x * f0, b0 = ab0.y * f0, a1 = ab1.x * f1, b1 = ab1.y * f1;
      const float r0 = p0 ? 9.313225746154785e-10f : 1.f, r1 = p1 ? 9.313225746154785e-10f : 1.f;
      const int cst = sec == 1 ? 2048 : 128, gst = sec == 1 ? 128 : 384;
      uint8_t* pe = (uint8_t*)g_qkv + (size_t)(n * 8) * HEAD_IMG + (row0 >> 7) * 6144 + grp * gst + lane * 4;
      uint8_t* pe1 = pe + cst;
      uint8_t* pe2 = pe1 + cst;
      uint8_t* pf = pe + gst;
      uint8_t* pf1 = pf + cst;
      uint8_t* pf2 = pf1 + cst;
#pragma unroll
      for (int hp = 0; hp < 4; hp++) {
        uint32_t u[5], v[5];
        float su[5], sv[5];
#pragma unroll
        for (int i = 0; i < 5; i++) {
          const int j = hp * 5 + i;
          const float2 t = *(const float2*)&cs[j * 8 + c * 2];
          const float x0 = fmaf(acc[4 * j], a0, b0 * t.x), x1 = fmaf(acc[4 * j + 1], a0, b0 * t.y);
          const float y0 = fmaf(acc[4 * j + 2], a1, b1 * t.x), y1 = fmaf(acc[4 * j + 3], a1, b1 * t.y);
          u[i] = pack_bf16(x0, x1); v[i] = pack_bf16(y0, y1);
          su[i] = fmaf(x0, x0, x1 * x1); sv[i] = fmaf(y0, y0, y1 * y1);
        }
        constexpr int HE = HEAD_IMG;
        const int oe = hp * 2 * HE, oo = oe + HE;
        *(uint32_t*)(pe + oe) = u[0];  *(uint32_t*)(pf + oe) = v[0];
        *(uint32_t*)(pe1 + oe) = u[1]; *(uint32_t*)(pf1 + oe) = v[1];
        *(uint32_t*)(pe2 + oe) = lo ? u[2] : pad0; *(uint32_t*)(pf2 + oe) = lo ? v[2] : pad1;
        *(uint32_t*)(pe + oo) = __shfl_xor_sync(~0u, lo ? u[3] : u[2], 2);
        *(uint32_t*)(pf + oo) = __shfl_xor_sync(~0u, lo ? v[3] : v[2], 2);
        *(uint32_t*)(pe1 + oo) = __shfl_xor_sync(~0u, lo ? u[4] : u[3], 2);
        *(uint32_t*)(pf1 + oo) = __shfl_xor_sync(~0u, lo ? v[4] : v[3], 2);
        const uint32_t tu = __shfl_xor_sync(~0u, u[4], 2), tv = __shfl_xor_sync(~0u, v[4], 2);
        *(uint32_t*)(pe2 + oo) = lo ? tu : pad0; *(uint32_t*)(pf2 + oo) = lo ? tv : pad1;
        if (sec < 2) {
          float e0 = (su[0] + su[1] + (lo ? su[2] : 0.f)) * r0, e1 = (sv[0] + sv[1] + (lo ? sv[2] : 0.f)) * r1;
          float o0 = (su[3] + su[4] + (lo ? 0.f : su[2])) * r0, o1 = (sv[3] + sv[4] + (lo ? 0.f : sv[2])) * r1;
          e0 += __shfl_xor_sync(~0u, e0, 1); e1 += __shfl_xor_sync(~0u, e1, 1);
          o0 += __shfl_xor_sync(~0u, o0, 1); o1 += __shfl_xor_sync(~0u, o1, 1);
          e0 += __shfl_xor_sync(~0u, e0, 2); e1 += __shfl_xor_sync(~0u, e1, 2);
          o0 += __shfl_xor_sync(~0u, o0, 2); o1 += __shfl_xor_sync(~0u, o1, 2);
          const uint32_t em = __reduce_max_sync(~0u, max(__float_as_uint(e0), __float_as_uint(e1)));
          const uint32_t om = __reduce_max_sync(~0u, max(__float_as_uint(o0), __float_as_uint(o1)));
          if (lane < 2) g_nrm[(n * 8 + hp * 2 + lane) * 128 + (row0 >> 4)] = __uint_as_float(lane ? om : em);
        }
      }
    }
    if (tid == 0) STAMP(0, 4);
  }
  cluster_wait();
  if (tid == 0) STAMP(0, 6);
}

constexpr int K2_SMEM = 2 * HEAD_IMG + 2 * 6144 + 2 * 10240 + 256;

__device__ __forceinline__ uint64_t desc64(uint32_t lo, uint32_t hi) {
  uint64_t d;
  asm("mov.b64 %0, {%1, %2};" : "=l"(d) : "r"(lo), "r"(hi));
  return d;
}
__device__ __forceinline__ uint32_t exp_pair(bool poly, float a, float b, uint32_t mk) {
  if (poly) {
    const uint32_t pk = __byte_perm(__float_as_uint(a), __float_as_uint(b), 0x6521);
    uint32_t m, q;
    asm("lop3.b32 %0, %1, %2, 0x3f803f80, 0xEA;" : "=r"(m) : "r"(pk), "r"(mk));
    asm("fma.rn.bf16x2 %0, %1, %1, %2;" : "=r"(q) : "r"(m), "r"(0x40014001u));
    return pk - m + q;
  }
  return pack_bf16(ex2(a), ex2(b));
}
#define PV_GR 4
__device__ __forceinline__ void exp_pv(const float (&s)[64], float (&o)[12], uint64_t dv, uint32_t mk) {
#pragma unroll
  for (int k0 = 0; k0 < 8; k0 += PV_GR) {
    uint32_t p[4 * PV_GR];
#pragma unroll
    for (int i = 0; i < 4 * PV_GR; i++)
      p[i] = exp_pair((POLY_MASK >> (k0 * 2 + i / 2)) & 1, s[k0 * 8 + 2 * i], s[k0 * 8 + 2 * i + 1], mk);
    WG_FENCE();
#pragma unroll
    for (int k = 0; k < PV_GR; k++)
      wgmma_rs_n24(o, p[4 * k], p[4 * k + 1], p[4 * k + 2], p[4 * k + 3], dv + (k0 + k) * 48, 1);
  }
}
__device__ __forceinline__ void load_q(uint32_t (&q)[6], const uint8_t* p) {
  q[0] = __ldcg((const uint32_t*)p);         q[1] = __ldcg((const uint32_t*)(p + 384));
  q[2] = __ldcg((const uint32_t*)(p + 128)); q[3] = __ldcg((const uint32_t*)(p + 512));
  q[4] = __ldcg((const uint32_t*)(p + 256)); q[5] = __ldcg((const uint32_t*)(p + 640));
}
__device__ __forceinline__ float rcp(float x) {
  float y;
  asm("rcp.approx.ftz.f32 %0, %1;" : "=f"(y) : "f"(x));
  return y;
}
__device__ __forceinline__ int img_off(int chunk) { return (chunk >> 3) * 16384 + (chunk & 7) * 128; }
__device__ __forceinline__ void store_o(const float (&o)[12], int tile) {
  int tid, bid;
  asm volatile("mov.u32 %0, %%tid.x;" : "=r"(tid));
  asm volatile("mov.u32 %0, %%ctaid.x;" : "=r"(bid));
  const int head = bid >> 2;
  uint8_t* dst = (uint8_t*)g_o + ((bid & 3) * 4 + (tile >> 1)) * 163840 + (tile & 1) * 8192 + ((tid >> 5) & 3) * 2048 + (tid & 31) * 4;
  const int oc = (head >> 1) * 5 + (head & 1) * 2;
  const int o0 = img_off(oc), o1 = img_off(oc + 1), o2 = img_off((head >> 1) * 5 + 4) + (head & 1) * 8;
  const float i0 = rcp(__shfl_sync(~0u, o[8], 2, 4)), i1 = rcp(__shfl_sync(~0u, o[10], 2, 4));
  *(uint32_t*)(dst + o0) = pack_bf16(o[0] * i0, o[1] * i0); *(uint32_t*)(dst + o0 + 1024) = pack_bf16(o[2] * i1, o[3] * i1);
  *(uint32_t*)(dst + o1) = pack_bf16(o[4] * i0, o[5] * i0); *(uint32_t*)(dst + o1 + 1024) = pack_bf16(o[6] * i1, o[7] * i1);
  if ((tid & 3) < 2) {
    *(uint32_t*)(dst + o2) = pack_bf16(o[8] * i0, o[9] * i0);
    *(uint32_t*)(dst + o2 + 1024) = pack_bf16(o[10] * i1, o[11] * i1);
  }
}

struct Maps5 { CUtensorMap m[5]; };

__global__ void __launch_bounds__(512, 1)
k2_attn(const __grid_constant__ Maps5 maps, uint32_t mk) {
  const CUtensorMap* tmw = maps.m;
  extern __shared__ __align__(1024) uint8_t sm[];
  const uint32_t sbase = smem_u32(sm);
  float* part = (float*)(sm + 2 * HEAD_IMG);
  const uint32_t rbuf = sbase + 2 * HEAD_IMG + 2 * 6144;
  const uint32_t kvb = rbuf + 2 * 10240;
  const uint32_t partb = kvb + 128, rbar = kvb + 144;
  const int tid = threadIdx.x, lane = tid & 31;
  const int warp = __shfl_sync(~0u, tid >> 5, 0);
  const int head = blockIdx.x >> 2, qb = blockIdx.x & 3;

  if (tid == 0) STAMP(1, 0);
  if (tid == 0) {
    for (int i = 0; i < 16; i++) mbar_init(kvb + 8 * i, 1);
    mbar_init(partb, 128); mbar_init(partb + 8, 128); mbar_init(rbar, 1); mbar_init(rbar + 8, 1);
    asm volatile("fence.mbarrier_init.release.cluster;" ::: "memory");
  }
  __syncthreads();

  if (warp >= 12) {
    asm volatile("setmaxnreg.dec.sync.aligned.u32 32;");
    if (tid == 384) {
      pdl_wait();
      pdl_trigger();
      const uint8_t* kimg = (const uint8_t*)g_qkv + (size_t)(32 + head) * HEAD_IMG;
#pragma unroll 1
      for (int b = 0; b < 16; b++) {
        mbar_expect(kvb + 8 * b, 12288);
        bulk_ld(sbase + b * 6144, kimg + b * 6144, 6144, kvb + 8 * b);
        bulk_ld(sbase + HEAD_IMG + b * 6144, kimg + 32 * HEAD_IMG + b * 6144, 6144, kvb + 8 * b);
        if (b >= 2) mbar_wait(kvb + 8 * (b - 1), 0);

      }
      if (blockIdx.x == 0) g_epoch = g_epoch + 1;
      mbar_wait(kvb + 8 * 15, 0);
      STAMP(1, 2);
      uint8_t* pdst = nullptr;
      uint32_t pbytes = 0;
#pragma unroll 1
      for (int i = 0; i < 8; i++) {
        const int p = blockIdx.x + 128 * i;
        uint8_t* dst = nullptr;
        uint32_t bytes = 0;
        if (i < 7 && p < 856) {
          asm volatile("cp.async.bulk.wait_group.read 0;" ::: "memory");
          const CUtensorMap* tm;
          int c1, c2;
          if (p < 640) {
            const int nt = p / 80, r = p - nt * 80, ph = r / 40, st = (r - ph * 40) >> 1, up = r & 1;
            bytes = ph ? 5632 : 8192;
            dst = (uint8_t*)g_wgu + nt * 552960 + ph * 327680 + st * 2 * bytes + up * (bytes >> 1);
            tm = &tmw[ph * 2 + up]; c1 = ph ? 128 + nt * 11 : nt * 16; c2 = st * 2;
          } else {
            const int nk = p - 640, nt = nk / 27;
            bytes = 10240;
            dst = (uint8_t*)g_wd + (size_t)nk * 10240;
            tm = &tmw[4]; c1 = nt * 10; c2 = nk - nt * 27;
          }
          mbar_expect(rbar + 8 * (i & 1), bytes);
          tma4d(rbuf + (i & 1) * 10240, tm, c1, c2, rbar + 8 * (i & 1));
        }
        if (pbytes) {
          mbar_wait(rbar + 8 * ((i - 1) & 1), ((i - 1) >> 1) & 1);
          if (pbytes == 10240) {
            bulk_st(pdst, rbuf + ((i - 1) & 1) * 10240, pbytes);
          } else {
            bulk_st(pdst, rbuf + ((i - 1) & 1) * 10240, pbytes >> 1);
            bulk_st(pdst + pbytes, rbuf + ((i - 1) & 1) * 10240 + (pbytes >> 1), pbytes >> 1);
          }
          asm volatile("cp.async.bulk.commit_group;" ::: "memory");
        }
        pdst = dst; pbytes = bytes;
      }
      asm volatile("cp.async.bulk.wait_group.read 0;" ::: "memory");
      STAMP(1, 6);
    }
  } else {
    asm volatile("setmaxnreg.inc.sync.aligned.u32 160;");
    const int wg = warp >> 2;
    const uint8_t* qthr = (const uint8_t*)g_qkv + (size_t)head * HEAD_IMG + qb * 64 * 384 + (warp & 3) * 768 + lane * 4;
    const uint32_t klo0 = ((sbase & 0x3FFFF) >> 4) | (128u << 16), vlo0 = (((sbase + HEAD_IMG) & 0x3FFFF) >> 4) | (24u << 16);
    constexpr uint64_t KSTEP2 = (uint64_t)(int64_t)(256 - (128 << 16));
    constexpr uint64_t KV2K = 384 - (HEAD_IMG >> 4) + (104 << 16);
    const int nun = wg == 1 ? 4 : 3;
    uint32_t utile = wg == 0 ? 0x210u : (wg == 1 ? 0x4235u : 0x576u);
    uint32_t ubeg = wg == 0 ? 0u : (wg == 1 ? 0x0b00u : 0x600u);
    uint32_t ulen = wg == 0 ? 0x0b1010u : (wg == 1 ? 0x10051006u : 0x0a1010u);
    pdl_wait();
    if (tid == 0) STAMP(1, 1);
    uint32_t q[6];
    load_q(q, qthr + (utile & 15) * 3072);
    bool fast;
    {
      const float4 kn = __ldcg((const float4*)&g_nrm[(32 + head) * 128 + lane * 4]);
      const float qv = __ldcg(&g_nrm[head * 128 + qb * 32 + lane]);
      const uint32_t km = max(max(__float_as_uint(kn.x), __float_as_uint(kn.y)), max(__float_as_uint(kn.z), __float_as_uint(kn.w)));
      const float k2 = __uint_as_float(__reduce_max_sync(~0u, km)), q2 = __uint_as_float(__reduce_max_sync(~0u, __float_as_uint(qv)));
      fast = q2 * k2 <= 3400.f;
    }
    if (fast) {
#pragma unroll 1
      for (int u = 0; u < nun; u++) {
        const uint32_t b0 = ubeg & 15;
        const bool wt = u == 0 || (wg == 1 && u == 1);
        float s[64], o[12];
#pragma unroll
        for (int i = 0; i < 12; i++) o[i] = 0.f;
        uint32_t vlo = vlo0 + b0 * 384, kb = kvb + b0 * 8;
        const uint32_t vend = vlo + ((ulen & 255) - 1) * 384;
        if (wt) mbar_wait(kb, 0);
        if (tid == 0) STAMP(5, 4 + u);
        fence_regs(o);
        WG_FENCE();
        wgmma_rs_n128(s, q[0], q[1], q[2], q[3], desc64(klo0 + b0 * 384, 8), 0);
        wgmma_rs_n128(s, q[4], q[5], 0, 0, desc64(klo0 + b0 * 384, 8) + KSTEP2, 1);
        WG_COMMIT();
#define K2UNR 1
        constexpr int kUnr = K2UNR;
#pragma unroll kUnr
        for (; vlo != vend; vlo += 384) {
          if (wt) { kb += 8; mbar_wait(kb, 0); }
          WG_WAIT(0);
          fence_regs(s); fence_regs(o);
          const uint64_t dv = desc64(vlo, 8);
          exp_pv(s, o, dv, mk);
          wgmma_rs_n128(s, q[0], q[1], q[2], q[3], dv + KV2K, 0);
          wgmma_rs_n128(s, q[4], q[5], 0, 0, dv + (KV2K + KSTEP2), 1);
          WG_COMMIT();
        }
        WG_WAIT(0);
        fence_regs(s); fence_regs(o);
        if (u + 1 < nun) load_q(q, qthr + ((utile >> 4) & 15) * 3072);
        exp_pv(s, o, desc64(vlo, 8), mk);
        WG_COMMIT();
        WG_WAIT(0);
        fence_regs(o);
        if (wg == 1 && !(u & 1)) {
          float4* pp = (float4*)(part + u * 768) + (tid & 127);
          pp[0] = make_float4(o[0], o[1], o[2], o[3]);
          pp[128] = make_float4(o[4], o[5], o[6], o[7]);
          pp[256] = make_float4(o[8], o[9], o[10], o[11]);
          mbar_arrive(partb + 4 * u);
        } else {
          if (wg != 1 && u == 2) {
            const int pi = wg == 0 ? 1 : 0;
            mbar_wait(partb + 8 * pi, 0);
            const float4* pp = (const float4*)(part + pi * 1536) + (tid & 127);
            const float4 x0 = pp[0], x1 = pp[128], x2 = pp[256];
            o[0] += x0.x; o[1] += x0.y; o[2] += x0.z; o[3] += x0.w; o[4] += x1.x; o[5] += x1.y;
            o[6] += x1.z; o[7] += x1.w; o[8] += x2.x; o[9] += x2.y; o[10] += x2.z; o[11] += x2.w;
          }
          store_o(o, utile & 15);
        }
        utile >>= 4; ubeg >>= 4; ulen >>= 8;
      }
      if ((tid & 127) == 0) STAMP(1, 3 + wg);
    } else {
#pragma unroll 1
      for (int tile = wg; tile < 8; tile += 3) {
        load_q(q, qthr + tile * 3072);
        if ((lane & 3) >= 2) { q[4] = 0; q[5] = 0; }
        float o[12], m0 = -INFINITY, m1 = -INFINITY;
#pragma unroll
        for (int i = 0; i < 12; i++) o[i] = 0.f;
#pragma unroll 1
        for (int b = 0; b < 16; b++) {
          float s[64];
          mbar_wait(kvb + 8 * b, 0);
          WG_FENCE();
          wgmma_rs_n128(s, q[0], q[1], q[2], q[3], desc64(klo0 + b * 384, 8), 0);
          wgmma_rs_n128(s, q[4], q[5], 0, 0, desc64(klo0 + b * 384, 8) + KSTEP2, 1);
          WG_COMMIT();
          WG_WAIT(0);
          fence_regs(s);
          float x0 = m0, x1 = m1;
#pragma unroll
          for (int j = 0; j < 16; j++) {
            if ((POLY_MASK >> j) & 1) {
#pragma unroll
              for (int i = 0; i < 4; i++) s[4 * j + i] *= (1.f / 32768.f);
            }
            x0 = fmaxf(x0, fmaxf(s[4 * j], s[4 * j + 1]));
            x1 = fmaxf(x1, fmaxf(s[4 * j + 2], s[4 * j + 3]));
          }
          x0 = fmaxf(x0, __shfl_xor_sync(~0u, x0, 1)); x0 = fmaxf(x0, __shfl_xor_sync(~0u, x0, 2));
          x1 = fmaxf(x1, __shfl_xor_sync(~0u, x1, 1)); x1 = fmaxf(x1, __shfl_xor_sync(~0u, x1, 2));
          const float al0 = ex2(m0 - x0), al1 = ex2(m1 - x1);
          m0 = x0; m1 = x1;
#pragma unroll
          for (int i = 0; i < 12; i++) o[i] *= (i & 2) ? al1 : al0;
          uint32_t p[32];
#pragma unroll
          for (int i = 0; i < 32; i++) {
            const float mm = (i & 1) ? m1 : m0;
            p[i] = pack_bf16(ex2(s[2 * i] - mm), ex2(s[2 * i + 1] - mm));
          }
          fence_regs(o);
          WG_FENCE();
#pragma unroll
          for (int k = 0; k < 8; k++)
            wgmma_rs_n24(o, p[4 * k], p[4 * k + 1], p[4 * k + 2], p[4 * k + 3], desc64(vlo0 + b * 384 + k * 48, 8), 1);
          WG_COMMIT();
          WG_WAIT(0);
          fence_regs(o);
        }
        store_o(o, tile);
      }
    }
  }
}

#define K3P 1
constexpr int K3_ST = 4, K3_STAGE = 37888, K3_PRE = K3P;
constexpr int K3_SMEM = K3_ST * K3_STAGE + 45056 + 20480 + 256;

template <int N> struct Acc { float v[N]; };

template <int NB, int NK, bool FIRST>
__global__ void __cluster_dims__(2, 1, 1) __launch_bounds__(384, 1)
k3_proj(const __grid_constant__ CUtensorMap tmr, const uint4* __restrict__ aimg, const uint4* __restrict__ wimg) {
  constexpr int KT = 2 * NB + NK, EX = FIRST ? 1 : 0;
  extern __shared__ __align__(1024) uint8_t sm[];
  const uint32_t sbase = smem_u32(sm);
  uint8_t* xch = sm + K3_ST * K3_STAGE;
  uint8_t* stg = sm + K3_ST * K3_STAGE + 45056;
  const uint32_t fullb = smem_u32(stg) + 20480, emptyb = fullb + 8 * K3_ST, resb = emptyb + 8 * K3_ST, xchb = resb + 8;
  const int tid = threadIdx.x, lane = tid & 31;
  const int warp = __shfl_sync(~0u, tid >> 5, 0);
  const int rank = blockIdx.x & 1;
  const int n = blockIdx.x & 7, m = blockIdx.x >> 3;
  if (tid == 0) STAMP(FIRST ? 2 : 4, 0);
  if (warp == 0) {
    if (lane == 0) {
      prefetch_map(&tmr);
      for (int i = 0; i < K3_ST; i++) { mbar_init(fullb + 8 * i, 1); mbar_init(emptyb + 8 * i, 4); }
      mbar_init(resb, 1); mbar_init(xchb, 1);
      mbar_expect(xchb, 4096 * (10 + EX));
      asm volatile("fence.mbarrier_init.release.cluster;" ::: "memory");
    }
    __syncwarp();
    cluster_arrive();
    bar_arrive(4, 256 + 32);
    const uint8_t* wk = (const uint8_t*)wimg + (size_t)n * KT * 10240;
    const uint8_t* ws = (const uint8_t*)wimg + (size_t)(n ^ 1) * KT * 10240;
    const uint8_t* ab = (const uint8_t*)aimg + (size_t)m * KT * 16384;
    auto load_w = [&](int i) {
      const int s = i % K3_ST, kt = i < NB ? i + rank * (NB + NK) : i;
      const uint32_t sa = sbase + s * K3_STAGE;
      mbar_expect(fullb + 8 * s, 26624 + EX * 1024 + (i < NB ? 10240 : 0));
      bulk_ld(sa + 16384, wk + kt * 10240, 10240, fullb + 8 * s);
      if (FIRST) bulk_ld(sa + 26624, (const uint8_t*)g_wm + kt * 1024, 1024, fullb + 8 * s);
      if (i < NB) bulk_ld(sa + 26624 + EX * 1024, ws + kt * 10240, 10240, fullb + 8 * s);
    };
    if (elect_one()) {
#pragma unroll 1
      for (int i = 0; i < K3_PRE; i++) load_w(i);
    }
    cluster_wait();
    pdl_wait();
    pdl_trigger();
    if (lane == 0) STAMP(2, 6);
#pragma unroll 1
    for (int i = 0; i < NB + NK; i++) {
      const int s = i % K3_ST;
      const uint32_t sa = sbase + s * K3_STAGE;
      if (i >= K3_ST) mbar_wait(emptyb + 8 * s, ((i / K3_ST) - 1) & 1);
      if (elect_one()) {
        if (i < NB) bulk_ld(sa, ab + (i + rank * (NB + NK)) * 16384, 16384, fullb + 8 * s);
        else bulk_ld_mc(sa + rank * 8192, ab + i * 16384 + rank * 8192, 8192, fullb + 8 * s);
        if (i >= K3_PRE) load_w(i);
        if (FIRST && i == K3_ST - 1) {
          mbar_expect(resb, 20480);
          tma2d(smem_u32(stg), &tmr, n * 80, m * 128, resb);
          tma2d(smem_u32(stg) + 10240, &tmr, n * 80, m * 128 + 64, resb);
        }
      }
    }
    __syncwarp();
    cluster_arrive();
  } else if (warp >= 4) {
    cluster_arrive();
    const int cw = warp - 4, wg = cw >> 2;
    const int g = lane >> 2, c = lane & 3;
    const int row = m * 128 + cw * 16 + g;
    uint8_t* himg = (uint8_t*)g_h + (size_t)m * 163840 + cw * 2048 + lane * 4;
    uint32_t rv[20];
    float mu0, mu1;
    if (FIRST) {
      mu0 = __uint_as_float(__ldcg(&g_rowstat[row].z)); mu1 = __uint_as_float(__ldcg(&g_rowstat[row + 8].z));
    } else {
      mu0 = __ldcg(&g_hmean[row]); mu1 = __ldcg(&g_hmean[row + 8]);
#pragma unroll
      for (int j = 0; j < 10; j++) {
        rv[2 * j] = __ldcg((const uint32_t*)(himg + img_off(n * 10 + j)));
        rv[2 * j + 1] = __ldcg((const uint32_t*)(himg + img_off(n * 10 + j) + 1024));
      }
    }
    float acc[80 + 4 * EX];
    float (&keep)[40 + 4 * EX] = ((Acc<40 + 4 * EX>*)acc)->v;
    const uint64_t da0 = mkdesc(sbase + wg * 8192, 128, 1024, 0);
    const uint64_t db0 = mkdesc(sbase + 16384, 128, 1024, 0);
    bar_sync(4, 256 + 32);
    cluster_wait();
#pragma unroll 1
    for (int i = 0; i < NB; i++) {
      const int s = i % K3_ST;
      mbar_wait(fullb + 8 * s, (i / K3_ST) & 1);
      if (i == 0 && tid == 128) STAMP(FIRST ? 2 : 4, 2);
      const uint64_t da = da0 + s * (K3_STAGE >> 4), db = db0 + s * (K3_STAGE >> 4);
      WG_FENCE();
#pragma unroll
      for (int k = 0; k < 4; k++) {
        if constexpr (FIRST) wgmma_ss_n168(acc, da + k * 16, db + k * 16, (i | k) != 0);
        else wgmma_ss_n160(acc, da + k * 16, db + k * 16, (i | k) != 0);
      }
      WG_COMMIT();
      if (i > 0) {
        WG_WAIT(1);
        if ((tid & 127) < 2) mbar_arrive_cta(emptyb + 8 * ((i - 1) % K3_ST), tid & 1);
      }
    }
    const uint32_t rx = mapa(smem_u32(xch) + (tid - 128) * 16, rank ^ 1), rb = mapa(xchb, rank ^ 1);
    WG_WAIT(0);
    fence_regs(acc);
    if ((tid & 127) < 2) mbar_arrive_cta(emptyb + 8 * ((NB - 1) % K3_ST), tid & 1);
    if (FIRST) st_async4(rx, acc[40], acc[41], acc[42], acc[43], rb);
    if (tid == 128) STAMP(FIRST ? 2 : 4, 1);
#pragma unroll
    for (int i = NB; i < NB + NK; i++) {
      const int s = i % K3_ST;
      mbar_wait(fullb + 8 * s, (i / K3_ST) & 1);
      const uint64_t da = da0 + s * (K3_STAGE >> 4), db = db0 + s * (K3_STAGE >> 4);
      WG_FENCE();
#pragma unroll
      for (int k = 0; k < 4; k++) {
        if constexpr (FIRST) wgmma_ss_n88(keep, da + k * 16, db + k * 16, 1);
        else wgmma_ss_n80(keep, da + k * 16, db + k * 16, 1);
      }
      WG_COMMIT();
      if (i > NB && i - 1 + K3_ST < NB + NK) {
        WG_WAIT(1);
        if ((tid & 127) < 2) mbar_arrive_cta(emptyb + 8 * ((i - 1) % K3_ST), tid & 1);
      }
#pragma unroll
      for (int j = (i - NB) * 3 + EX; j < (i - NB) * 3 + 3 + EX; j++)
        if (j < 10 + EX) st_async4(rx + j * 4096, acc[40 + 4 * j], acc[41 + 4 * j], acc[42 + 4 * j], acc[43 + 4 * j], rb);
    }
    cluster_arrive();
    uint8_t* sp = stg + (cw * 16 + g) * 160 + c * 4;
    if (FIRST) {
      mbar_wait(resb, 0);
#pragma unroll
      for (int j = 0; j < 10; j++) {
        rv[2 * j] = *(const uint32_t*)(sp + j * 16);
        rv[2 * j + 1] = *(const uint32_t*)(sp + 1280 + j * 16);
      }
    }
    WG_WAIT(0);
    fence_regs(keep);
    if (tid == 128) STAMP(FIRST ? 2 : 4, 3);
    mbar_wait(xchb, 0);
    if (tid == 128) STAMP(FIRST ? 2 : 4, 5);
    const uint8_t* xp = xch + (tid - 128) * 16;
    if (FIRST) {
      const float4 p = *(const float4*)xp;
      mu0 += __shfl_sync(~0u, (keep[40] + p.x) + (keep[41] + p.y), 0, 4);
      mu1 += __shfl_sync(~0u, (keep[42] + p.z) + (keep[43] + p.w), 0, 4);
      if (n == 0 && c == 0) { g_hmean[row] = mu0; g_hmean[row + 8] = mu1; }
      mu0 = -mu0; mu1 = -mu1;
    }
    float q0 = 0.f, q1 = 0.f;
#pragma unroll
    for (int j = 0; j < 10; j++) {
      const float4 p = *(const float4*)(xp + (j + EX) * 4096);
      const float x0 = (keep[4 * j] + p.x) + (bf_lo(rv[2 * j]) + mu0), x1 = (keep[4 * j + 1] + p.y) + (bf_hi(rv[2 * j]) + mu0);
      const float y0 = (keep[4 * j + 2] + p.z) + (bf_lo(rv[2 * j + 1]) + mu1), y1 = (keep[4 * j + 3] + p.w) + (bf_hi(rv[2 * j + 1]) + mu1);
      if (FIRST) {
        *(uint32_t*)(himg + img_off(n * 10 + j)) = pack_bf16(x0, x1);
        *(uint32_t*)(himg + img_off(n * 10 + j) + 1024) = pack_bf16(y0, y1);
        q0 = fmaf(x0, x0, fmaf(x1, x1, q0)); q1 = fmaf(y0, y0, fmaf(y1, y1, q1));
      } else {
        *(uint32_t*)(sp + j * 16) = pack_bf16(x0, x1);
        *(uint32_t*)(sp + 1280 + j * 16) = pack_bf16(y0, y1);
      }
    }
    if (FIRST) {
      q0 += __shfl_xor_sync(~0u, q0, 1); q0 += __shfl_xor_sync(~0u, q0, 2);
      q1 += __shfl_xor_sync(~0u, q1, 1); q1 += __shfl_xor_sync(~0u, q1, 2);
      if (c < 2) g_hpart[n * S_ + row + c * 8] = c ? q1 : q0;
    } else {
      fence_async();
      bar_sync(1 + wg, 128);
      if ((tid & 127) == 0) {
        tma2d_st(&tmr, n * 80, m * 128 + wg * 64, smem_u32(stg) + wg * 10240);
        bulk_commit_wait();
      }
      __syncwarp();
    }
    if (tid == 128) STAMP(FIRST ? 2 : 4, 4);
  } else {
    cluster_arrive();
    cluster_wait();
    cluster_arrive();
  }
  cluster_wait();
}

constexpr int K4_G = 2, K4_NS = 4, K4_NJ = 20;
constexpr int K4_RB = 163840, K4_BST = 8192 * K4_G, K4_XCH = 147456, K4_STG = K4_XCH + 40960, K4_BAR = K4_RB + K4_NS * K4_BST;
constexpr int K4_SMEM = K4_BAR + 384;

__device__ __forceinline__ void wait_flags(const uint4* f, uint32_t tag) {
  for (uint32_t it = 0;; it++) {
    uint4 a, b;
    asm volatile("ld.acquire.gpu.global.v4.u32 {%0, %1, %2, %3}, [%4];" : "=r"(a.x), "=r"(a.y), "=r"(a.z), "=r"(a.w) : "l"(f) : "memory");
    asm volatile("ld.acquire.gpu.global.v4.u32 {%0, %1, %2, %3}, [%4];" : "=r"(b.x), "=r"(b.y), "=r"(b.z), "=r"(b.w) : "l"(f + 1) : "memory");
    if (a.x == tag && a.y == tag && a.z == tag && a.w == tag && b.x == tag && b.y == tag && b.z == tag && b.w == tag) break;
    if (it > (1u << 20)) wait_timeout();
    __nanosleep(50);
  }
  asm volatile("fence.proxy.async.global;" ::: "memory");
}

__global__ void __cluster_dims__(2, 1, 1) __launch_bounds__(384, 1)
k45_ffn(const __grid_constant__ CUtensorMap tmo) {
  extern __shared__ __align__(1024) uint8_t sm[];
  const uint32_t sbase = smem_u32(sm);
  const uint32_t afull = sbase + K4_BAR, bfull = afull + 80, bempty = bfull + 8 * K4_NS, full3 = bempty + 8 * K4_NS;
  const uint32_t empty3 = full3 + 32, afree = empty3 + 32, xchb = afree + 32;
  const int tid = threadIdx.x, lane = tid & 31;
  const int warp = __shfl_sync(~0u, tid >> 5, 0);
  const int rank = blockIdx.x & 1;
  const int n1 = (blockIdx.x >> 1) & 7, m1 = (blockIdx.x >> 4) * 2 + rank;
  const int n3 = blockIdx.x & 7, m3 = blockIdx.x >> 3;
  if (tid == 0) STAMP(3, 0);
  if (warp == 8) {
    if (elect_one()) {
#pragma unroll
      for (int i = 0; i < 10; i++) mbar_init(afull + 8 * i, 1);
#pragma unroll
      for (int i = 0; i < 4; i++) {
        mbar_init(bfull + 8 * i, 1); mbar_init(bempty + 8 * i, 4); mbar_init(full3 + 8 * i, 1); mbar_init(empty3 + 8 * i, 4);
        mbar_init(afree + 8 * i, 2);
      }
      mbar_init(xchb, 1);
      mbar_expect(xchb, 40960);
      asm volatile("fence.mbarrier_init.release.cluster;" ::: "memory");
    }
    __syncwarp();
  }
  cluster_arrive();
  if (warp >= 8) {
    cluster_wait();
    if (warp == 8) {
      if (lane == 0) STAMP(3, 7);
      const uint8_t* src = (const uint8_t*)g_wgu + n1 * 552960;
      const uint8_t* hb = (const uint8_t*)g_h + (size_t)m1 * 163840;
#pragma unroll 1
      for (int j = 0; j < 40; j++) {
        const uint32_t s8 = (j & 3) * 8, sz = j < 20 ? 16384 : 11264;
#define K4PRE 2
        if (j == K4PRE) {
          pdl_wait();
          if (lane == 0) STAMP(3, 1);
          if (elect_one()) {
#pragma unroll
            for (int kt = 0; kt < K4PRE / 2 + 1; kt++) { mbar_expect(afull + 8 * kt, 16384); bulk_ld(sbase + kt * 16384, hb + kt * 16384, 16384, afull + 8 * kt); }
          }
        }
        if (j >= 4) mbar_wait(bempty + s8, ((j >> 2) - 1) & 1);
        if (elect_one()) {
          mbar_expect(bfull + s8, sz);
          if ((j & 1) == rank) bulk_ld_mc(sbase + K4_RB + s8 * (K4_BST / 8), src, sz, bfull + s8);
          if (j > K4PRE && j < 18 && (j & 1)) {
            mbar_expect(afull + 4 + j * 4, 16384);
            bulk_ld(sbase + 8192 + j * 8192, hb + 8192 + j * 8192, 16384, afull + 4 + j * 4);
          }
        }
        src += sz;
      }
    } else if (warp == 9) {
      prefetch_map(&tmo);
      const uint32_t tag = __ldcg(&g_epoch);
#pragma unroll 1
      for (int ph = 0; ph < 2; ph++) {
        bar_sync(5 + ph, 256 + 32);
        if (lane == 0) {
          asm volatile("st.release.gpu.global.u32 [%0], %1;" ::"l"((uint32_t*)&g_flag[ph * 32 + m1 * 2] + n1), "r"(tag) : "memory");
          STAMP(3, 5 + ph);
        }
        __syncwarp();
      }
    } else {
      const uint8_t* wk = (const uint8_t*)g_wd + n3 * 276480;
      const uint8_t* ws = (const uint8_t*)g_wd + (n3 ^ 1) * 276480;
      const uint8_t* ab = (const uint8_t*)g_hh + (size_t)m3 * 442368;
      const uint32_t tag = __ldcg(&g_epoch);
#pragma unroll 1
      for (int i = 0; i < 16; i++) {
        const int kt = i < 8 ? rank * 8 + i : (i < 11 ? rank * 3 + 8 + i : 11 + i);
        const uint32_t sa = sbase + (i & 3) * 36864, fb = full3 + 8 * (i & 3);
        if (i < 4) mbar_wait(afree + 8 * i, 0);
        else mbar_wait(empty3 + 8 * (i & 3), ((i >> 2) - 1) & 1);
        if (warp == 10) {
          if (elect_one()) {
            mbar_expect(fb, i < 11 ? 36864 : 26624);
            bulk_ld(sa + 16384, wk + kt * 10240, 10240, fb);
            if (i < 11) bulk_ld(sa + 26624, ws + kt * 10240, 10240, fb);
          }
        } else {
          if (i == 0 || i == 8) {
            wait_flags(&g_flag[(i ? 32 : 0) + m3 * 2], tag);
            if (lane == 0) STAMP(4, i ? 7 : 6);
          }
          if (elect_one()) {
            if (i < 11) bulk_ld(sa, ab + kt * 16384, 16384, fb);
            else bulk_ld_mc(sa + rank * 8192, ab + kt * 16384 + rank * 8192, 8192, fb);
          }
        }
      }
    }
    __syncwarp();
    cluster_arrive();
    asm volatile("barrier.cluster.wait.aligned; // producers" ::: "memory");
  } else {
    const int wg = warp >> 2;
    const uint64_t da0 = mkdesc(sbase + wg * 8192, 128, 1024, 0);
    const uint64_t db0 = mkdesc(sbase + K4_RB, 128, 256, 0);
    cluster_wait();
    float a1[128], a2[88];
    int s = 0, ph = 0, sprev = 0;
#pragma unroll 1
    for (int j = 0; j < K4_NJ; j++) {
      if ((j * K4_G) % 4 == 0) mbar_wait(afull + 2 * K4_G * j, 0);
      mbar_wait(bfull + 8 * s, ph);
      if (j == 0 && tid == 0) STAMP(3, 2);
      const uint64_t da = da0 + ((j * K4_G) >> 2) * 1024 + ((j * K4_G) & 3) * 16, db = db0 + s * (K4_BST >> 4);
      WG_FENCE();
#pragma unroll
      for (int k = 0; k < K4_G; k++) wgmma_ss_n256(a1, da + k * 16, db + k * 512, (j | k) != 0);
      WG_COMMIT();
      if (j > 0) {
        WG_WAIT(1);
        if ((tid & 127) < 2) mbar_arrive_cta(bempty + 8 * sprev, tid & 1);
      }
      sprev = s;
      if (++s == K4_NS) { s = 0; ph ^= 1; }
    }
    float acc[80];
    uint8_t* hd = (uint8_t*)g_hh + (size_t)m1 * 442368 + warp * 2048 + lane * 4;
    WG_WAIT(0);
    fence_regs(a1);
    if ((tid & 127) < 2) mbar_arrive_cta(bempty + 8 * ((K4_NJ - 1) % K4_NS), tid & 1);
    if (tid == 0) STAMP(3, 3);
#define STORE_H(a, off, ptr, c) do { uint8_t* p_ = ptr; \
      *(uint32_t*)p_ = pack_bf16(a[4 * (c)] * a[off + 4 * (c)], a[4 * (c) + 1] * a[off + 1 + 4 * (c)]); \
      *(uint32_t*)(p_ + 1024) = pack_bf16(a[4 * (c) + 2] * a[off + 2 + 4 * (c)], a[4 * (c) + 3] * a[off + 3 + 4 * (c)]); } while (0)
#pragma unroll
    for (int c = 0; c < 16; c++) STORE_H(a1, 64, hd + n1 * 32768 + img_off(c), c);
    bar_arrive(5, 256 + 32);
#pragma unroll 1
    for (int j = 0; j < K4_NJ; j++) {
      mbar_wait(bfull + 8 * s, ph);
      const uint64_t da = da0 + ((j * K4_G) >> 2) * 1024 + ((j * K4_G) & 3) * 16, db = db0 + s * (K4_BST >> 4);
      WG_FENCE();
#pragma unroll
      for (int k = 0; k < K4_G; k++) wgmma_ss_n176(a2, da + k * 16, db + k * 352, (j | k) != 0);
      WG_COMMIT();
      if (j > 0) {
        WG_WAIT(1);
        if (j <= K4_NJ - K4_NS && (tid & 127) < 2) mbar_arrive_cta(bempty + 8 * sprev, tid & 1);
        if (j * K4_G >= 12 && ((j * K4_G) & 7) == 4 && (tid & 127) == 0) mbar_arrive(afree + (j * K4_G - 12));
      }
      sprev = s;
      if (++s == K4_NS) { s = 0; ph ^= 1; }
    }
    WG_WAIT(0);
    fence_regs(a2);
    if (tid == 0) STAMP(3, 4);
#pragma unroll
    for (int c = 0; c < 11; c++) STORE_H(a2, 44, hd + img_off(128 + n1 * 11 + c), c);
    bar_arrive(6, 256 + 32);
    float (&keep)[40] = ((Acc<40>*)acc)->v;
    const uint64_t db3 = mkdesc(sbase + 16384, 128, 1024, 0);
#pragma unroll 1
    for (int i = 0; i < 11; i++) {
      mbar_wait(full3 + 8 * (i & 3), (i >> 2) & 1);
      if (i == 0 && tid == 0) STAMP(4, 2);
      const uint64_t da = da0 + (i & 3) * 2304, db = db3 + (i & 3) * 2304;
      WG_FENCE();
#pragma unroll
      for (int k = 0; k < 4; k++) wgmma_ss_n160(acc, da + k * 16, db + k * 16, (i | k) != 0);
      WG_COMMIT();
      if (i > 0) {
        WG_WAIT(1);
        if ((tid & 127) < 2) mbar_arrive_cta(empty3 + 8 * ((i - 1) & 3), tid & 1);
      }
    }
    const int g = lane >> 2, c = lane & 3, row = m3 * 128 + warp * 16 + g;
    const uint8_t* himg = (const uint8_t*)g_h + (size_t)m3 * 163840 + warp * 2048 + lane * 4;
    uint32_t rv[20];
    const float mu0 = __ldcg(&g_hmean[row]), mu1 = __ldcg(&g_hmean[row + 8]);
    float r0 = __ldcg(&g_hpart[c * 2 * S_ + row]) + __ldcg(&g_hpart[(c * 2 + 1) * S_ + row]);
    float r1 = __ldcg(&g_hpart[c * 2 * S_ + row + 8]) + __ldcg(&g_hpart[(c * 2 + 1) * S_ + row + 8]);
#pragma unroll
    for (int j = 0; j < 10; j++) {
      rv[2 * j] = __ldcg((const uint32_t*)(himg + img_off(n3 * 10 + j)));
      rv[2 * j + 1] = __ldcg((const uint32_t*)(himg + img_off(n3 * 10 + j) + 1024));
    }
    const uint32_t rx = mapa(sbase + K4_XCH + tid * 16, rank ^ 1), rb = mapa(xchb, rank ^ 1);
    WG_WAIT(0);
    fence_regs(acc);
    if ((tid & 127) < 2) mbar_arrive_cta(empty3 + 16, tid & 1);
    if (tid == 0) STAMP(4, 1);
#pragma unroll
    for (int i = 11; i < 16; i++) {
      mbar_wait(full3 + 8 * (i & 3), (i >> 2) & 1);
      const uint64_t da = da0 + (i & 3) * 2304, db = db3 + (i & 3) * 2304;
      WG_FENCE();
#pragma unroll
      for (int k = 0; k < 4; k++) wgmma_ss_n80(keep, da + k * 16, db + k * 16, 1);
      WG_COMMIT();
      if (i == 12) {
        WG_WAIT(1);
        if ((tid & 127) < 2) mbar_arrive_cta(empty3 + 24, tid & 1);
      }
#pragma unroll
      for (int j = (i - 11) * 3; j < (i - 11) * 3 + 3; j++)
        if (j < 10) st_async4(rx + j * 4096, acc[40 + 4 * j], acc[41 + 4 * j], acc[42 + 4 * j], acc[43 + 4 * j], rb);
    }
    cluster_arrive();
    r0 += __shfl_xor_sync(~0u, r0, 1); r1 += __shfl_xor_sync(~0u, r1, 1);
    r0 += __shfl_xor_sync(~0u, r0, 2); r1 += __shfl_xor_sync(~0u, r1, 2);
    r0 = rcp(r0 * (1.f / D_) + 1e-5f); r1 = rcp(r1 * (1.f / D_) + 1e-5f);
    asm volatile("" : "+f"(r0), "+f"(r1)::"memory");
    WG_WAIT(0);
    fence_regs(keep);
    if (tid == 0) STAMP(4, 3);
    mbar_wait(xchb, 0);
    if (tid == 0) STAMP(4, 5);
    uint8_t* sp = sm + K4_STG + (warp * 16 + g) * 160 + c * 4;
#pragma unroll
    for (int j = 0; j < 10; j++) {
      const float4 p = *(const float4*)(sm + K4_XCH + tid * 16 + j * 4096);
      *(uint32_t*)(sp + j * 16) = pack_bf16(fmaf(keep[4 * j] + p.x, r0, bf_lo(rv[2 * j]) + mu0), fmaf(keep[4 * j + 1] + p.y, r0, bf_hi(rv[2 * j]) + mu0));
      *(uint32_t*)(sp + 1280 + j * 16) = pack_bf16(fmaf(keep[4 * j + 2] + p.z, r1, bf_lo(rv[2 * j + 1]) + mu1), fmaf(keep[4 * j + 3] + p.w, r1, bf_hi(rv[2 * j + 1]) + mu1));
    }
    fence_async();
    bar_sync(1 + wg, 128);
    if ((tid & 127) == 0) {
      tma2d_st(&tmo, n3 * 80, m3 * 128 + wg * 64, sbase + K4_STG + wg * 10240);
      bulk_commit_wait();
    }
    __syncwarp();
    if (tid == 0) STAMP(4, 4);
    asm volatile("barrier.cluster.wait.aligned; // consumers" ::: "memory");
  }
}

typedef CUresult (*EncodeFn)(CUtensorMap*, CUtensorMapDataType, cuuint32_t, void*, const cuuint64_t*, const cuuint64_t*,
                             const cuuint32_t*, const cuuint32_t*, CUtensorMapInterleave, CUtensorMapSwizzle,
                             CUtensorMapL2promotion, CUtensorMapFloatOOBfill);

static CUtensorMap make_map(EncodeFn enc, const void* p, uint64_t inner, uint64_t outer, uint32_t box_inner,
                            uint32_t box_outer, CUtensorMapSwizzle swz) {
  CUtensorMap m;
  cuuint64_t gd[2] = {inner, outer};
  cuuint64_t gs[1] = {inner * 2};
  cuuint32_t bd[2] = {box_inner, box_outer};
  cuuint32_t es[2] = {1, 1};
  enc(&m, CU_TENSOR_MAP_DATA_TYPE_BFLOAT16, 2, (void*)p, gd, gs, bd, es, CU_TENSOR_MAP_INTERLEAVE_NONE, swz,
      CU_TENSOR_MAP_L2_PROMOTION_L2_256B, CU_TENSOR_MAP_FLOAT_OOB_FILL_NONE);
  return m;
}

static CUtensorMap make_map_img(EncodeFn enc, const void* p, uint64_t k, uint64_t n, uint32_t rows, uint32_t chunks,
                                uint32_t groups) {
  CUtensorMap m;
  cuuint64_t gd[4] = {8, rows, n / 8, k / rows};
  cuuint64_t gs[3] = {n * 2, 16, n * 2 * rows};
  cuuint32_t bd[4] = {8, rows, chunks, groups};
  cuuint32_t es[4] = {1, 1, 1, 1};
  enc(&m, CU_TENSOR_MAP_DATA_TYPE_BFLOAT16, 4, (void*)p, gd, gs, bd, es, CU_TENSOR_MAP_INTERLEAVE_NONE,
      CU_TENSOR_MAP_SWIZZLE_NONE, CU_TENSOR_MAP_L2_PROMOTION_L2_128B, CU_TENSOR_MAP_FLOAT_OOB_FILL_NONE);
  return m;
}

template <typename... KArgs, typename... Args>
static void launch(void (*k)(KArgs...), int grid, int threads, int smem, bool pdl, Args... args) {
  cudaLaunchConfig_t cfg = {};
  cfg.gridDim = dim3(grid);
  cfg.blockDim = dim3(threads);
  cfg.dynamicSmemBytes = smem;
  cfg.stream = cudaStreamPerThread;
  cudaLaunchAttribute at[1];
  at[0].id = cudaLaunchAttributeProgrammaticStreamSerialization;
  at[0].val.programmaticStreamSerializationAllowed = 1;
  cfg.attrs = at;
  cfg.numAttrs = pdl ? 1 : 0;
  cudaLaunchKernelEx(&cfg, k, KArgs(args)...);
}

extern "C" void kernel_launch(void* const* d_in, const int* in_sizes, int n_in, void* d_out, int out_size) {
  const bf16* x = (const bf16*)d_in[0];
  const bf16* wqkv = (const bf16*)d_in[1];
  const bf16* wo = (const bf16*)d_in[2];
  const bf16* wg = (const bf16*)d_in[4];
  const bf16* wu = (const bf16*)d_in[5];
  const bf16* wd = (const bf16*)d_in[6];

  static EncodeFn enc = nullptr;
  static void *p_o, *p_wo;
  if (!enc) {
    void* fn = nullptr;
    cudaDriverEntryPointQueryResult qr;
    cudaGetDriverEntryPoint("cuTensorMapEncodeTiled", &fn, cudaEnableDefault, &qr);
    enc = (EncodeFn)fn;
    cudaGetSymbolAddress(&p_o, g_o);
    cudaGetSymbolAddress(&p_wo, g_wo);
    cudaFuncSetAttribute(k1_qkv, cudaFuncAttributeMaxDynamicSharedMemorySize, K1_SMEM);
    cudaFuncSetAttribute(k2_attn, cudaFuncAttributeMaxDynamicSharedMemorySize, K2_SMEM);
    cudaFuncSetAttribute(k3_proj<3, 4, true>, cudaFuncAttributeMaxDynamicSharedMemorySize, K3_SMEM);
    cudaFuncSetAttribute(k45_ffn, cudaFuncAttributeMaxDynamicSharedMemorySize, K4_SMEM);
  }
  const CUtensorMap tmx = make_map(enc, x, D_, S_, 64, 96, CU_TENSOR_MAP_SWIZZLE_128B);
  const CUtensorMap tmw = make_map(enc, wqkv, 3 * D_, D_, 32, 64, CU_TENSOR_MAP_SWIZZLE_64B);
  const CUtensorMap tmxr = make_map(enc, x, D_, S_, 80, 64, CU_TENSOR_MAP_SWIZZLE_NONE);
  Maps5 maps;
  maps.m[0] = make_map_img(enc, wg, D_, F_, 16, 16, 2); maps.m[1] = make_map_img(enc, wu, D_, F_, 16, 16, 2);
  maps.m[2] = make_map_img(enc, wg, D_, F_, 16, 11, 2); maps.m[3] = make_map_img(enc, wu, D_, F_, 16, 11, 2);
  maps.m[4] = make_map_img(enc, wd, F_, D_, 64, 10, 1);
  const CUtensorMap tmout = make_map(enc, d_out, D_, S_, 80, 64, CU_TENSOR_MAP_SWIZZLE_NONE);

  launch(k1_qkv, 132, 512, K1_SMEM, false, tmx, tmw, x, wqkv, wo);
  launch(k2_attn, 128, 512, K2_SMEM, true, maps, 0x007f007fu);
  launch(k3_proj<3, 4, true>, 128, 384, K3_SMEM, true, tmxr, (const uint4*)p_o, (const uint4*)p_wo);
  launch(k45_ffn, 128, 384, K4_SMEM, true, tmout);
}
```

```cpp
#include <cuda_runtime.h>
#include <cuda_bf16.h>
#include <cuda.h>
#include <stdint.h>

typedef __nv_bfloat16 bf16;

constexpr int S_ = 2048, D_ = 640, F_ = 1728;
constexpr int HEAD_IMG = 98304;
#define PMASK 0xDB6D
constexpr uint32_t POLY_MASK = PMASK;
constexpr float QSCALE = 0.22360679774997896f * 1.4426950408889634f;

__device__ __align__(1024) uint4 g_qkv[96 * HEAD_IMG / 16];
__device__ __align__(1024) uint4 g_o[S_ * D_ / 8];
__device__ __align__(1024) uint4 g_h[S_ * D_ / 8];
__device__ __align__(1024) uint4 g_hh[S_ * F_ / 8];
__device__ __align__(1024) uint4 g_wo[D_ * D_ / 8];
__device__ __align__(1024) uint4 g_wgu[2 * D_ * F_ / 8];
__device__ __align__(1024) uint4 g_wd[F_ * D_ / 8];
__device__ uint4 g_rowstat[S_];
__device__ uint4 g_cpart[10 * 12 * 80];
__device__ float g_nrm[64 * 128];
__device__ uint4 g_wm[D_];
__device__ float g_hmean[S_];
__device__ float g_hpart[8 * S_];
__device__ uint4 g_flag[2 * 16 * 2];
__device__ unsigned g_epoch;

#define STAMP(k, i)
__device__ __forceinline__ uint32_t smem_u32(const void* p) { return (uint32_t)__cvta_generic_to_shared(p); }
__device__ __forceinline__ void mbar_init(uint32_t a, uint32_t c) {
  asm volatile("mbarrier.init.shared::cta.b64 [%0], %1;" ::"r"(a), "r"(c) : "memory");
}
__device__ __forceinline__ void mbar_expect(uint32_t a, uint32_t bytes) {
  asm volatile("mbarrier.arrive.expect_tx.shared::cta.b64 _, [%0], %1;" ::"r"(a), "r"(bytes) : "memory");
}
__device__ __forceinline__ void mbar_arrive(uint32_t a) {
  asm volatile("mbarrier.arrive.shared::cta.b64 _, [%0];" ::"r"(a) : "memory");
}
__device__ __forceinline__ void mbar_arrive_cta(uint32_t a, uint32_t cta) {
  asm volatile("{\n.reg .b32 r;\nmapa.shared::cluster.u32 r, %0, %1;\n"
               "mbarrier.arrive.shared::cluster.b64 _, [r];\n}" ::"r"(a), "r"(cta) : "memory");
}
__device__ __forceinline__ bool mbar_try(uint32_t a, uint32_t ph) {
  uint32_t ok;
  asm volatile("{\n.reg .pred p;\nmbarrier.try_wait.parity.shared::cta.b64 p, [%1], %2;\nselp.u32 %0, 1, 0, p;\n}"
               : "=r"(ok) : "r"(a), "r"(ph) : "memory");
  return ok;
}
__device__ __noinline__ void wait_timeout() { __trap(); }
__device__ __forceinline__ void mbar_wait(uint32_t a, uint32_t ph) {
  if (mbar_try(a, ph)) return;
  uint32_t it = 0;
  while (!mbar_try(a, ph)) if (++it > (1u << 22)) wait_timeout();
}
__device__ __forceinline__ void tma2d(uint32_t dst, const CUtensorMap* m, int c0, int c1, uint32_t bar) {
  asm volatile("cp.async.bulk.tensor.2d.shared::cluster.global.mbarrier::complete_tx::bytes [%0], [%1, {%3, %4}], [%2];"
               ::"r"(dst), "l"(m), "r"(bar), "r"(c0), "r"(c1) : "memory");
}
__device__ __forceinline__ void tma2d_mc(uint32_t dst, const CUtensorMap* m, int c0, int c1, uint32_t bar) {
  asm volatile("cp.async.bulk.tensor.2d.shared::cluster.global.mbarrier::complete_tx::bytes.multicast::cluster "
               "[%0], [%1, {%3, %4}], [%2], %5;"
               ::"r"(dst), "l"(m), "r"(bar), "r"(c0), "r"(c1), "h"((uint16_t)3) : "memory");
}
__device__ __forceinline__ void bulk_ld(uint32_t dst, const void* src, uint32_t bytes, uint32_t bar) {
  asm volatile("cp.async.bulk.shared::cluster.global.mbarrier::complete_tx::bytes [%0], [%1], %2, [%3];"
               ::"r"(dst), "l"(src), "r"(bytes), "r"(bar) : "memory");
}
__device__ __forceinline__ void bulk_ld_mc(uint32_t dst, const void* src, uint32_t bytes, uint32_t bar) {
  asm volatile("cp.async.bulk.shared::cluster.global.mbarrier::complete_tx::bytes.multicast::cluster "
               "[%0], [%1], %2, [%3], %4;"
               ::"r"(dst), "l"(src), "r"(bytes), "r"(bar), "h"((uint16_t)3) : "memory");
}
__device__ __forceinline__ void cluster_arrive() { asm volatile("barrier.cluster.arrive.relaxed.aligned;" ::: "memory"); }
__device__ __forceinline__ void cluster_wait() { asm volatile("barrier.cluster.wait.aligned;" ::: "memory"); }
__device__ __forceinline__ void bulk_st(void* dst, uint32_t src, uint32_t bytes) {
  asm volatile("cp.async.bulk.global.shared::cta.bulk_group [%0], [%1], %2;" ::"l"(dst), "r"(src), "r"(bytes) : "memory");
}
__device__ __forceinline__ void tma2d_st(const CUtensorMap* m, int c0, int c1, uint32_t src) {
  asm volatile("cp.async.bulk.tensor.2d.global.shared::cta.bulk_group [%0, {%2, %3}], [%1];"
               ::"l"(m), "r"(src), "r"(c0), "r"(c1) : "memory");
}
__device__ __forceinline__ void bulk_commit_wait() {
  asm volatile("cp.async.bulk.commit_group;\ncp.async.bulk.wait_group.read 0;" ::: "memory");
}
__device__ __forceinline__ uint32_t mapa(uint32_t a, uint32_t cta) {
  uint32_t r;
  asm("mapa.shared::cluster.u32 %0, %1, %2;" : "=r"(r) : "r"(a), "r"(cta));
  return r;
}
__device__ __forceinline__ void st_async4(uint32_t dst, float a, float b, float c, float d, uint32_t bar) {
  asm volatile("st.async.shared::cluster.mbarrier::complete_tx::bytes.v4.f32 [%0], {%1, %2, %3, %4}, [%5];"
               ::"r"(dst), "f"(a), "f"(b), "f"(c), "f"(d), "r"(bar) : "memory");
}
__device__ __forceinline__ void fence_async() { asm volatile("fence.proxy.async.shared::cta;" ::: "memory"); }
__device__ __forceinline__ void prefetch_map(const CUtensorMap* m) {
  asm volatile("prefetch.tensormap [%0];" ::"l"(m) : "memory");
}
__device__ __forceinline__ bool elect_one() {
  uint32_t p;
  asm volatile("{\n.reg .pred q;\nelect.sync _|q, 0xffffffff;\nselp.u32 %0, 1, 0, q;\n}" : "=r"(p));
  return p;
}
__device__ __forceinline__ void pdl_wait() { asm volatile("griddepcontrol.wait;" ::: "memory"); }
__device__ __forceinline__ void pdl_trigger() { asm volatile("griddepcontrol.launch_dependents;" ::: "memory"); }
__device__ __forceinline__ void bar_sync(int id, int n) { asm volatile("bar.sync %0, %1;" ::"r"(id), "r"(n) : "memory"); }
__device__ __forceinline__ void bar_arrive(int id, int n) { asm volatile("bar.arrive %0, %1;" ::"r"(id), "r"(n) : "memory"); }
#define WG_FENCE() asm volatile("wgmma.fence.sync.aligned;" ::: "memory")
#define WG_COMMIT() asm volatile("wgmma.commit_group.sync.aligned;" ::: "memory")
#define WG_WAIT(n) asm volatile("wgmma.wait_group.sync.aligned %0;" ::"n"(n) : "memory")
__device__ __forceinline__ uint64_t mkdesc(uint32_t addr, uint32_t lbo, uint32_t sbo, uint32_t sw) {
  return (uint64_t)((addr & 0x3FFFF) >> 4) | ((uint64_t)(lbo >> 4) << 16) | ((uint64_t)(sbo >> 4) << 32) |
         ((uint64_t)sw << 62);
}
template <int N> __device__ __forceinline__ void fence_regs(float (&r)[N]) {
#pragma unroll
  for (int i = 0; i < N; i++) asm volatile("" : "+f"(r[i])::"memory");
}
__device__ __forceinline__ uint32_t pack_bf16(float lo, float hi) {
  uint32_t r;
  asm("cvt.rn.bf16x2.f32 %0, %1, %2;" : "=r"(r) : "f"(hi), "f"(lo));
  return r;
}
__device__ __forceinline__ float bf_lo(uint32_t v) { return __uint_as_float(v << 16); }
__device__ __forceinline__ float bf_hi(uint32_t v) { return __uint_as_float(v & 0xffff0000u); }
__device__ __forceinline__ float ex2(float x) {
  float y;
  asm("ex2.approx.ftz.f32 %0, %1;" : "=f"(y) : "f"(x));
  return y;
}
__device__ __forceinline__ uint4 ldg_nc(const void* p) {
  uint4 v;
  asm volatile("ld.global.nc.L1::no_allocate.v4.u32 {%0, %1, %2, %3}, [%4];"
               : "=r"(v.x), "=r"(v.y), "=r"(v.z), "=r"(v.w) : "l"(p));
  return v;
}

__device__ __forceinline__ uint4 ld_relaxed(const uint4* p) {
  uint64_t a, b;
  asm volatile("ld.relaxed.gpu.global.v2.u64 {%0, %1}, [%2];" : "=l"(a), "=l"(b) : "l"(p) : "memory");
  return make_uint4((uint32_t)a, (uint32_t)(a >> 32), (uint32_t)b, (uint32_t)(b >> 32));
}
__device__ __forceinline__ void st_relaxed(uint4* p, float x, float y, uint32_t tag) {
  const uint64_t a = ((uint64_t)tag << 32) | __float_as_uint(x), b = ((uint64_t)tag << 32) | __float_as_uint(y);
  asm volatile("st.relaxed.gpu.global.v2.u64 [%0], {%1, %2};" ::"l"(p), "l"(a), "l"(b) : "memory");
}
__device__ __forceinline__ void tma4d(uint32_t dst, const CUtensorMap* m, int c2, int c3, uint32_t bar) {
  asm volatile("cp.async.bulk.tensor.4d.shared::cluster.global.mbarrier::complete_tx::bytes [%0], [%1, {%3, %3, %4, %5}], [%2];"
               ::"r"(dst), "l"(m), "r"(bar), "r"(0), "r"(c2), "r"(c3) : "memory");
}
#define ACC8(a, v) do { a[0] += bf_lo(v.x); a[1] += bf_hi(v.x); a[2] += bf_lo(v.y); a[3] += bf_hi(v.y); \
                        a[4] += bf_lo(v.z); a[5] += bf_hi(v.z); a[6] += bf_lo(v.w); a[7] += bf_hi(v.w); } while (0)

__device__ __forceinline__ void wgmma_ss_n224(float (&d)[112], uint64_t da, uint64_t db, int sd) {
  asm volatile("{\n.reg .pred p;\nsetp.ne.b32 p, %114, 0;\n"
      "wgmma.mma_async.sync.aligned.m64n224k16.f32.bf16.bf16 {"
      "%0, %1, %2, %3, %4, %5, %6, %7, %8, %9, %10, %11, %12, %13, %14, %15, "
      "%16, %17, %18, %19, %20, %21, %22, %23, %24, %25, %26, %27, %28, %29, %30, %31, "
      "%32, %33, %34, %35, %36, %37, %38, %39, %40, %41, %42, %43, %44, %45, %46, %47, "
      "%48, %49, %50, %51, %52, %53, %54, %55, %56, %57, %58, %59, %60, %61, %62, %63, "
      "%64, %65, %66, %67, %68, %69, %70, %71, %72, %73, %74, %75, %76, %77, %78, %79, "
      "%80, %81, %82, %83, %84, %85, %86, %87, %88, %89, %90, %91, %92, %93, %94, %95, "
      "%96, %97, %98, %99, %100, %101, %102, %103, %104, %105, %106, %107, %108, %109, %110, %111"
      "}, %112, %113, p, 1, 1, 0, 1;\n}\n"
    : "+f"(d[0]), "+f"(d[1]), "+f"(d[2]), "+f"(d[3]), "+f"(d[4]), "+f"(d[5]), "+f"(d[6]), "+f"(d[7]),
      "+f"(d[8]), "+f"(d[9]), "+f"(d[10]), "+f"(d[11]), "+f"(d[12]), "+f"(d[13]), "+f"(d[14]), "+f"(d[15]),
      "+f"(d[16]), "+f"(d[17]), "+f"(d[18]), "+f"(d[19]), "+f"(d[20]), "+f"(d[21]), "+f"(d[22]), "+f"(d[23]),
      "+f"(d[24]), "+f"(d[25]), "+f"(d[26]), "+f"(d[27]), "+f"(d[28]), "+f"(d[29]), "+f"(d[30]), "+f"(d[31]),
      "+f"(d[32]), "+f"(d[33]), "+f"(d[34]), "+f"(d[35]), "+f"(d[36]), "+f"(d[37]), "+f"(d[38]), "+f"(d[39]),
      "+f"(d[40]), "+f"(d[41]), "+f"(d[42]), "+f"(d[43]), "+f"(d[44]), "+f"(d[45]), "+f"(d[46]), "+f"(d[47]),
      "+f"(d[48]), "+f"(d[49]), "+f"(d[50]), "+f"(d[51]), "+f"(d[52]), "+f"(d[53]), "+f"(d[54]), "+f"(d[55]),
      "+f"(d[56]), "+f"(d[57]), "+f"(d[58]), "+f"(d[59]), "+f"(d[60]), "+f"(d[61]), "+f"(d[62]), "+f"(d[63]),
      "+f"(d[64]), "+f"(d[65]), "+f"(d[66]), "+f"(d[67]), "+f"(d[68]), "+f"(d[69]), "+f"(d[70]), "+f"(d[71]),
      "+f"(d[72]), "+f"(d[73]), "+f"(d[74]), "+f"(d[75]), "+f"(d[76]), "+f"(d[77]), "+f"(d[78]), "+f"(d[79]),
      "+f"(d[80]), "+f"(d[81]), "+f"(d[82]), "+f"(d[83]), "+f"(d[84]), "+f"(d[85]), "+f"(d[86]), "+f"(d[87]),
      "+f"(d[88]), "+f"(d[89]), "+f"(d[90]), "+f"(d[91]), "+f"(d[92]), "+f"(d[93]), "+f"(d[94]), "+f"(d[95]),
      "+f"(d[96]), "+f"(d[97]), "+f"(d[98]), "+f"(d[99]), "+f"(d[100]), "+f"(d[101]), "+f"(d[102]), "+f"(d[103]),
      "+f"(d[104]), "+f"(d[105]), "+f"(d[106]), "+f"(d[107]), "+f"(d[108]), "+f"(d[109]), "+f"(d[110]), "+f"(d[111])
    : "l"(da), "l"(db), "r"(sd));
}
__device__ __forceinline__ void wgmma_ss_n208(float (&d)[104], uint64_t da, uint64_t db, int sd) {
  asm volatile("{\n.reg .pred p;\nsetp.ne.b32 p, %106, 0;\n"
      "wgmma.mma_async.sync.aligned.m64n208k16.f32.bf16.bf16 {"
      "%0, %1, %2, %3, %4, %5, %6, %7, %8, %9, %10, %11, %12, %13, %14, %15, "
      "%16, %17, %18, %19, %20, %21, %22, %23, %24, %25, %26, %27, %28, %29, %30, %31, "
      "%32, %33, %34, %35, %36, %37, %38, %39, %40, %41, %42, %43, %44, %45, %46, %47, "
      "%48, %49, %50, %51, %52, %53, %54, %55, %56, %57, %58, %59, %60, %61, %62, %63, "
      "%64, %65, %66, %67, %68, %69, %70, %71, %72, %73, %74, %75, %76, %77, %78, %79, "
      "%80, %81, %82, %83, %84, %85, %86, %87, %88, %89, %90, %91, %92, %93, %94, %95, "
      "%96, %97, %98, %99, %100, %101, %102, %103"
      "}, %104, %105, p, 1, 1, 0, 1;\n}\n"
    : "+f"(d[0]), "+f"(d[1]), "+f"(d[2]), "+f"(d[3]), "+f"(d[4]), "+f"(d[5]), "+f"(d[6]), "+f"(d[7]),
      "+f"(d[8]), "+f"(d[9]), "+f"(d[10]), "+f"(d[11]), "+f"(d[12]), "+f"(d[13]), "+f"(d[14]), "+f"(d[15]),
      "+f"(d[16]), "+f"(d[17]), "+f"(d[18]), "+f"(d[19]), "+f"(d[20]), "+f"(d[21]), "+f"(d[22]), "+f"(d[23]),
      "+f"(d[24]), "+f"(d[25]), "+f"(d[26]), "+f"(d[27]), "+f"(d[28]), "+f"(d[29]), "+f"(d[30]), "+f"(d[31]),
      "+f"(d[32]), "+f"(d[33]), "+f"(d[34]), "+f"(d[35]), "+f"(d[36]), "+f"(d[37]), "+f"(d[38]), "+f"(d[39]),
      "+f"(d[40]), "+f"(d[41]), "+f"(d[42]), "+f"(d[43]), "+f"(d[44]), "+f"(d[45]), "+f"(d[46]), "+f"(d[47]),
      "+f"(d[48]), "+f"(d[49]), "+f"(d[50]), "+f"(d[51]), "+f"(d[52]), "+f"(d[53]), "+f"(d[54]), "+f"(d[55]),
      "+f"(d[56]), "+f"(d[57]), "+f"(d[58]), "+f"(d[59]), "+f"(d[60]), "+f"(d[61]), "+f"(d[62]), "+f"(d[63]),
      "+f"(d[64]), "+f"(d[65]), "+f"(d[66]), "+f"(d[67]), "+f"(d[68]), "+f"(d[69]), "+f"(d[70]), "+f"(d[71]),
      "+f"(d[72]), "+f"(d[73]), "+f"(d[74]), "+f"(d[75]), "+f"(d[76]), "+f"(d[77]), "+f"(d[78]), "+f"(d[79]),
      "+f"(d[80]), "+f"(d[81]), "+f"(d[82]), "+f"(d[83]), "+f"(d[84]), "+f"(d[85]), "+f"(d[86]), "+f"(d[87]),
      "+f"(d[88]), "+f"(d[89]), "+f"(d[90]), "+f"(d[91]), "+f"(d[92]), "+f"(d[93]), "+f"(d[94]), "+f"(d[95]),
      "+f"(d[96]), "+f"(d[97]), "+f"(d[98]), "+f"(d[99]), "+f"(d[100]), "+f"(d[101]), "+f"(d[102]), "+f"(d[103])
    : "l"(da), "l"(db), "r"(sd));
}
__device__ __forceinline__ void wgmma_ss_n168(float (&d)[84], uint64_t da, uint64_t db, int sd) {
  asm volatile("{\n.reg .pred p;\nsetp.ne.b32 p, %86, 0;\n"
      "wgmma.mma_async.sync.aligned.m64n168k16.f32.bf16.bf16 {"
      "%0, %1, %2, %3, %4, %5, %6, %7, %8, %9, %10, %11, %12, %13, %14, %15, "
      "%16, %17, %18, %19, %20, %21, %22, %23, %24, %25, %26, %27, %28, %29, %30, %31, "
      "%32, %33, %34, %35, %36, %37, %38, %39, %40, %41, %42, %43, %44, %45, %46, %47, "
      "%48, %49, %50, %51, %52, %53, %54, %55, %56, %57, %58, %59, %60, %61, %62, %63, "
      "%64, %65, %66, %67, %68, %69, %70, %71, %72, %73, %74, %75, %76, %77, %78, %79, "
      "%80, %81, %82, %83"
      "}, %84, %85, p, 1, 1, 0, 1;\n}\n"
    : "+f"(d[0]), "+f"(d[1]), "+f"(d[2]), "+f"(d[3]), "+f"(d[4]), "+f"(d[5]), "+f"(d[6]), "+f"(d[7]),
      "+f"(d[8]), "+f"(d[9]), "+f"(d[10]), "+f"(d[11]), "+f"(d[12]), "+f"(d[13]), "+f"(d[14]), "+f"(d[15]),
      "+f"(d[16]), "+f"(d[17]), "+f"(d[18]), "+f"(d[19]), "+f"(d[20]), "+f"(d[21]), "+f"(d[22]), "+f"(d[23]),
      "+f"(d[24]), "+f"(d[25]), "+f"(d[26]), "+f"(d[27]), "+f"(d[28]), "+f"(d[29]), "+f"(d[30]), "+f"(d[31]),
      "+f"(d[32]), "+f"(d[33]), "+f"(d[34]), "+f"(d[35]), "+f"(d[36]), "+f"(d[37]), "+f"(d[38]), "+f"(d[39]),
      "+f"(d[40]), "+f"(d[41]), "+f"(d[42]), "+f"(d[43]), "+f"(d[44]), "+f"(d[45]), "+f"(d[46]), "+f"(d[47]),
      "+f"(d[48]), "+f"(d[49]), "+f"(d[50]), "+f"(d[51]), "+f"(d[52]), "+f"(d[53]), "+f"(d[54]), "+f"(d[55]),
      "+f"(d[56]), "+f"(d[57]), "+f"(d[58]), "+f"(d[59]), "+f"(d[60]), "+f"(d[61]), "+f"(d[62]), "+f"(d[63]),
      "+f"(d[64]), "+f"(d[65]), "+f"(d[66]), "+f"(d[67]), "+f"(d[68]), "+f"(d[69]), "+f"(d[70]), "+f"(d[71]),
      "+f"(d[72]), "+f"(d[73]), "+f"(d[74]), "+f"(d[75]), "+f"(d[76]), "+f"(d[77]), "+f"(d[78]), "+f"(d[79]),
      "+f"(d[80]), "+f"(d[81]), "+f"(d[82]), "+f"(d[83])
    : "l"(da), "l"(db), "r"(sd));
}
__device__ __forceinline__ void wgmma_ss_n160(float (&d)[80], uint64_t da, uint64_t db, int sd) {
  asm volatile("{\n.reg .pred p;\nsetp.ne.b32 p, %82, 0;\n"
      "wgmma.mma_async.sync.aligned.m64n160k16.f32.bf16.bf16 {"
      "%0, %1, %2, %3, %4, %5, %6, %7, %8, %9, %10, %11, %12, %13, %14, %15, "
      "%16, %17, %18, %19, %20, %21, %22, %23, %24, %25, %26, %27, %28, %29, %30, %31, "
      "%32, %33, %34, %35, %36, %37, %38, %39, %40, %41, %42, %43, %44, %45, %46, %47, "
      "%48, %49, %50, %51, %52, %53, %54, %55, %56, %57, %58, %59, %60, %61, %62, %63, "
      "%64, %65, %66, %67, %68, %69, %70, %71, %72, %73, %74, %75, %76, %77, %78, %79"
      "}, %80, %81, p, 1, 1, 0, 1;\n}\n"
    : "+f"(d[0]), "+f"(d[1]), "+f"(d[2]), "+f"(d[3]), "+f"(d[4]), "+f"(d[5]), "+f"(d[6]), "+f"(d[7]),
      "+f"(d[8]), "+f"(d[9]), "+f"(d[10]), "+f"(d[11]), "+f"(d[12]), "+f"(d[13]), "+f"(d[14]), "+f"(d[15]),
      "+f"(d[16]), "+f"(d[17]), "+f"(d[18]), "+f"(d[19]), "+f"(d[20]), "+f"(d[21]), "+f"(d[22]), "+f"(d[23]),
      "+f"(d[24]), "+f"(d[25]), "+f"(d[26]), "+f"(d[27]), "+f"(d[28]), "+f"(d[29]), "+f"(d[30]), "+f"(d[31]),
      "+f"(d[32]), "+f"(d[33]), "+f"(d[34]), "+f"(d[35]), "+f"(d[36]), "+f"(d[37]), "+f"(d[38]), "+f"(d[39]),
      "+f"(d[40]), "+f"(d[41]), "+f"(d[42]), "+f"(d[43]), "+f"(d[44]), "+f"(d[45]), "+f"(d[46]), "+f"(d[47]),
      "+f"(d[48]), "+f"(d[49]), "+f"(d[50]), "+f"(d[51]), "+f"(d[52]), "+f"(d[53]), "+f"(d[54]), "+f"(d[55]),
      "+f"(d[56]), "+f"(d[57]), "+f"(d[58]), "+f"(d[59]), "+f"(d[60]), "+f"(d[61]), "+f"(d[62]), "+f"(d[63]),
      "+f"(d[64]), "+f"(d[65]), "+f"(d[66]), "+f"(d[67]), "+f"(d[68]), "+f"(d[69]), "+f"(d[70]), "+f"(d[71]),
      "+f"(d[72]), "+f"(d[73]), "+f"(d[74]), "+f"(d[75]), "+f"(d[76]), "+f"(d[77]), "+f"(d[78]), "+f"(d[79])
    : "l"(da), "l"(db), "r"(sd));
}
__device__ __forceinline__ void wgmma_ss_n88(float (&d)[44], uint64_t da, uint64_t db, int sd) {
  asm volatile("{\n.reg .pred p;\nsetp.ne.b32 p, %46, 0;\n"
      "wgmma.mma_async.sync.aligned.m64n88k16.f32.bf16.bf16 {"
      "%0, %1, %2, %3, %4, %5, %6, %7, %8, %9, %10, %11, %12, %13, %14, %15, "
      "%16, %17, %18, %19, %20, %21, %22, %23, %24, %25, %26, %27, %28, %29, %30, %31, "
      "%32, %33, %34, %35, %36, %37, %38, %39, %40, %41, %42, %43"
      "}, %44, %45, p, 1, 1, 0, 1;\n}\n"
    : "+f"(d[0]), "+f"(d[1]), "+f"(d[2]), "+f"(d[3]), "+f"(d[4]), "+f"(d[5]), "+f"(d[6]), "+f"(d[7]),
      "+f"(d[8]), "+f"(d[9]), "+f"(d[10]), "+f"(d[11]), "+f"(d[12]), "+f"(d[13]), "+f"(d[14]), "+f"(d[15]),
      "+f"(d[16]), "+f"(d[17]), "+f"(d[18]), "+f"(d[19]), "+f"(d[20]), "+f"(d[21]), "+f"(d[22]), "+f"(d[23]),
      "+f"(d[24]), "+f"(d[25]), "+f"(d[26]), "+f"(d[27]), "+f"(d[28]), "+f"(d[29]), "+f"(d[30]), "+f"(d[31]),
      "+f"(d[32]), "+f"(d[33]), "+f"(d[34]), "+f"(d[35]), "+f"(d[36]), "+f"(d[37]), "+f"(d[38]), "+f"(d[39]),
      "+f"(d[40]), "+f"(d[41]), "+f"(d[42]), "+f"(d[43])
    : "l"(da), "l"(db), "r"(sd));
}
__device__ __forceinline__ void wgmma_ss_n80(float (&d)[40], uint64_t da, uint64_t db, int sd) {
  asm volatile("{\n.reg .pred p;\nsetp.ne.b32 p, %42, 0;\n"
      "wgmma.mma_async.sync.aligned.m64n80k16.f32.bf16.bf16 {"
      "%0, %1, %2, %3, %4, %5, %6, %7, %8, %9, %10, %11, %12, %13, %14, %15, "
      "%16, %17, %18, %19, %20, %21, %22, %23, %24, %25, %26, %27, %28, %29, %30, %31, "
      "%32, %33, %34, %35, %36, %37, %38, %39"
      "}, %40, %41, p, 1, 1, 0, 1;\n}\n"
    : "+f"(d[0]), "+f"(d[1]), "+f"(d[2]), "+f"(d[3]), "+f"(d[4]), "+f"(d[5]), "+f"(d[6]), "+f"(d[7]),
      "+f"(d[8]), "+f"(d[9]), "+f"(d[10]), "+f"(d[11]), "+f"(d[12]), "+f"(d[13]), "+f"(d[14]), "+f"(d[15]),
      "+f"(d[16]), "+f"(d[17]), "+f"(d[18]), "+f"(d[19]), "+f"(d[20]), "+f"(d[21]), "+f"(d[22]), "+f"(d[23]),
      "+f"(d[24]), "+f"(d[25]), "+f"(d[26]), "+f"(d[27]), "+f"(d[28]), "+f"(d[29]), "+f"(d[30]), "+f"(d[31]),
      "+f"(d[32]), "+f"(d[33]), "+f"(d[34]), "+f"(d[35]), "+f"(d[36]), "+f"(d[37]), "+f"(d[38]), "+f"(d[39])
    : "l"(da), "l"(db), "r"(sd));
}
__device__ __forceinline__ void wgmma_rs_n128(float (&d)[64], uint32_t a0, uint32_t a1, uint32_t a2, uint32_t a3,
                                  uint64_t db, int sd) {
  asm volatile("{\n.reg .pred p;\nsetp.ne.b32 p, %69, 0;\n"
      "wgmma.mma_async.sync.aligned.m64n128k16.f32.bf16.bf16 {"
      "%0, %1, %2, %3, %4, %5, %6, %7, %8, %9, %10, %11, %12, %13, %14, %15, "
      "%16, %17, %18, %19, %20, %21, %22, %23, %24, %25, %26, %27, %28, %29, %30, %31, "
      "%32, %33, %34, %35, %36, %37, %38, %39, %40, %41, %42, %43, %44, %45, %46, %47, "
      "%48, %49, %50, %51, %52, %53, %54, %55, %56, %57, %58, %59, %60, %61, %62, %63"
      "}, {%64, %65, %66, %67}, %68, p, 1, 1, 0;\n}\n"
    : "+f"(d[0]), "+f"(d[1]), "+f"(d[2]), "+f"(d[3]), "+f"(d[4]), "+f"(d[5]), "+f"(d[6]), "+f"(d[7]),
      "+f"(d[8]), "+f"(d[9]), "+f"(d[10]), "+f"(d[11]), "+f"(d[12]), "+f"(d[13]), "+f"(d[14]), "+f"(d[15]),
      "+f"(d[16]), "+f"(d[17]), "+f"(d[18]), "+f"(d[19]), "+f"(d[20]), "+f"(d[21]), "+f"(d[22]), "+f"(d[23]),
      "+f"(d[24]), "+f"(d[25]), "+f"(d[26]), "+f"(d[27]), "+f"(d[28]), "+f"(d[29]), "+f"(d[30]), "+f"(d[31]),
      "+f"(d[32]), "+f"(d[33]), "+f"(d[34]), "+f"(d[35]), "+f"(d[36]), "+f"(d[37]), "+f"(d[38]), "+f"(d[39]),
      "+f"(d[40]), "+f"(d[41]), "+f"(d[42]), "+f"(d[43]), "+f"(d[44]), "+f"(d[45]), "+f"(d[46]), "+f"(d[47]),
      "+f"(d[48]), "+f"(d[49]), "+f"(d[50]), "+f"(d[51]), "+f"(d[52]), "+f"(d[53]), "+f"(d[54]), "+f"(d[55]),
      "+f"(d[56]), "+f"(d[57]), "+f"(d[58]), "+f"(d[59]), "+f"(d[60]), "+f"(d[61]), "+f"(d[62]), "+f"(d[63])
    : "r"(a0), "r"(a1), "r"(a2), "r"(a3), "l"(db), "r"(sd));
}
__device__ __forceinline__ void wgmma_rs_n24(float (&d)[12], uint32_t a0, uint32_t a1, uint32_t a2, uint32_t a3,
                                  uint64_t db, int sd) {
  asm volatile("{\n.reg .pred p;\nsetp.ne.b32 p, %17, 0;\n"
      "wgmma.mma_async.sync.aligned.m64n24k16.f32.bf16.bf16 {"
      "%0, %1, %2, %3, %4, %5, %6, %7, %8, %9, %10, %11"
      "}, {%12, %13, %14, %15}, %16, p, 1, 1, 1;\n}\n"
    : "+f"(d[0]), "+f"(d[1]), "+f"(d[2]), "+f"(d[3]), "+f"(d[4]), "+f"(d[5]), "+f"(d[6]), "+f"(d[7]),
      "+f"(d[8]), "+f"(d[9]), "+f"(d[10]), "+f"(d[11])
    : "r"(a0), "r"(a1), "r"(a2), "r"(a3), "l"(db), "r"(sd));
}

#define KST 4
#define K1S 4
constexpr int K1_ST = K1S, K1_STAGE = 45056;
constexpr int K1_SMEM = K1_ST * K1_STAGE + 640   + 1536   + 2560   + 128;

__device__ __forceinline__ float2 row_stats(uint4 v0, uint4 v1, uint4 v2) {
  const uint32_t wd[12] = {v0.x, v0.y, v0.z, v0.w, v1.x, v1.y, v1.z, v1.w, v2.x, v2.y, v2.z, v2.w};
  float sx = 0.f, sq = 0.f;
#pragma unroll
  for (int e = 0; e < 12; e++) {
    const float lo = bf_lo(wd[e]), hi = bf_hi(wd[e]);
    sx += lo + hi; sq = fmaf(lo, lo, fmaf(hi, hi, sq));
  }
#pragma unroll
  for (int o = 16; o; o >>= 1) { sx += __shfl_xor_sync(~0u, sx, o); sq += __shfl_xor_sync(~0u, sq, o); }
  const float mean = sx * (1.f / D_);
  return make_float2(rsqrtf(fmaxf(sq * (1.f / D_) - mean * mean, 0.f) + 1e-5f), mean);
}

__global__ void __cluster_dims__(2, 1, 1) __launch_bounds__(512, 1)
k1_qkv(const __grid_constant__ CUtensorMap tmx, const __grid_constant__ CUtensorMap tmw,
       const bf16* __restrict__ x, const bf16* __restrict__ w, const bf16* __restrict__ wo) {
  extern __shared__ __align__(1024) uint8_t sm[];
  float* cs = (float*)(sm + K1_ST * K1_STAGE);
  float2* rowab = (float2*)(sm + K1_ST * K1_STAGE + 640);
  float* red = (float*)(sm + K1_ST * K1_STAGE + 2176);
  const uint32_t sbase = smem_u32(sm);
  const uint32_t fullb = sbase + K1_ST * K1_STAGE + 4736, emptyb = fullb + 8 * K1_ST;
  const int tid = threadIdx.x, lane = tid & 31;
  const int warp = __shfl_sync(~0u, tid >> 5, 0);
  const int rank = blockIdx.x & 1, cl = blockIdx.x >> 1;
  const int m = cl / 6, n = (cl - m * 6) * 2 + rank;
  if (tid == 0) STAMP(0, 0);

  if (warp == 12) {
    if (lane == 0) {
      prefetch_map(&tmx); prefetch_map(&tmw);
      for (int i = 0; i < K1_ST; i++) { mbar_init(fullb + 8 * i, 1); mbar_init(emptyb + 8 * i, 6); }
      asm volatile("fence.mbarrier_init.release.cluster;" ::: "memory");
    }
    __syncwarp();
    cluster_arrive();
    bar_arrive(4, 512);
    if (elect_one()) {
#pragma unroll
      for (int kt = 0; kt < K1_ST; kt++) mbar_expect(fullb + 8 * kt, K1_STAGE);
#pragma unroll
      for (int j = 0; j < 5; j++) tma2d(sbase + 24576 + j * 4096, &tmw, n * 160 + j * 32, 0, fullb);
    }
    cluster_wait();
#pragma unroll 1
    for (int kt = 0; kt < 10; kt++) {
      const int s = kt % K1_ST;
      const uint32_t sa = sbase + s * K1_STAGE;
      if (kt >= K1_ST) mbar_wait(emptyb + 8 * s, ((kt / K1_ST) - 1) & 1);
      if (elect_one()) {
        if (kt >= K1_ST) mbar_expect(fullb + 8 * s, K1_STAGE);
        tma2d_mc(sa + rank * 12288, &tmx, kt * 64, m * 192 + rank * 96, fullb + 8 * s);
        if (kt > 0) {
#pragma unroll
          for (int j = 0; j < 5; j++) tma2d(sa + 24576 + j * 4096, &tmw, n * 160 + j * 32, kt * 64, fullb + 8 * s);
        }
      }
      if (kt == K1_ST - 1) pdl_trigger();
    }
    __syncwarp();
    cluster_arrive();
  } else if (warp > 12) {
    cluster_arrive();
    const int t96 = tid - 416;
    const uint32_t tag = __ldcg(&g_epoch) + 1;
    bar_sync(4, 512);
    mbar_wait(fullb, 0);
    if (m < 10) {
      const int ck = t96 % 20, rg = min(t96 / 20, 3);
      uint4 wv[16];
#pragma unroll
      for (int i = 0; i < 16; i++) wv[i] = ldg_nc(w + (size_t)(m * 64 + rg * 16 + i) * 1920 + n * 160 + ck * 8);
      float acc8[8];
#pragma unroll
      for (int i = 0; i < 8; i++) acc8[i] = 0.f;
#pragma unroll
      for (int i = 0; i < 16; i++) ACC8(acc8, wv[i]);
      *(float4*)&red[rg * 160 + ck * 8] = make_float4(acc8[0], acc8[1], acc8[2], acc8[3]);
      *(float4*)&red[rg * 160 + ck * 8 + 4] = make_float4(acc8[4], acc8[5], acc8[6], acc8[7]);
      bar_sync(1, 96);
      if (t96 < 80) {
        const float2 p0 = *(const float2*)&red[t96 * 2], p1 = *(const float2*)&red[160 + t96 * 2];
        const float2 p2 = *(const float2*)&red[320 + t96 * 2], p3 = *(const float2*)&red[480 + t96 * 2];
        st_relaxed(&g_cpart[(m * 12 + n) * 80 + t96], (p0.x + p1.x) + (p2.x + p3.x), (p0.y + p1.y) + (p2.y + p3.y), tag);
      }
    }
    if (tid == 416) STAMP(5, 7);
    bool ok = false;
    for (int it = 0; it < 64 && !ok; it++) {
      uint4 p[10], st[2];
#pragma unroll
      for (int k = 0; k < 10; k++) p[k] = ld_relaxed(&g_cpart[(k * 12 + n) * 80 + min(t96, 79)]);
#pragma unroll
      for (int k = 0; k < 2; k++) st[k] = ld_relaxed(&g_rowstat[min(m * 192 + k * 96 + t96, S_ - 1)]);
      ok = true;
      float s0 = 0.f, s1 = 0.f;
#pragma unroll
      for (int k = 0; k < 10; k++) {
        ok = ok && p[k].y == tag && p[k].w == tag;
        s0 += __uint_as_float(p[k].x); s1 += __uint_as_float(p[k].z);
      }
      if (t96 < 80) *(float2*)&cs[t96 * 2] = make_float2(s0, s1);
#pragma unroll
      for (int k = 0; k < 2; k++) {
        ok = ok && st[k].y == tag && st[k].w == tag;
        rowab[k * 96 + t96] = make_float2(__uint_as_float(st[k].x), -__uint_as_float(st[k].x) * __uint_as_float(st[k].z));
      }
      ok = __all_sync(~0u, ok);
      if (!ok) __nanosleep(300);
    }
    if (!ok) {
      const int c2 = min(t96, 79);
      float s0 = 0.f, s1 = 0.f;
#pragma unroll 1
      for (int k = 0; k < D_; k++) {
        const uint32_t v = *(const uint32_t*)(w + (size_t)k * 1920 + n * 160 + c2 * 2);
        s0 += bf_lo(v); s1 += bf_hi(v);
      }
      if (t96 < 80) *(float2*)&cs[t96 * 2] = make_float2(s0, s1);
#pragma unroll 1
      for (int i = 0; i < 64; i++) {
        const int r = (i >> 5) * 96 + (t96 & ~31) + (i & 31);
        const bf16* xr = x + (size_t)min(m * 192 + r, S_ - 1) * D_ + lane * 8;
        const float2 st = row_stats(ldg_nc(xr), ldg_nc(xr + 256), lane < 16 ? ldg_nc(xr + 512) : make_uint4(0u, 0u, 0u, 0u));
        if (lane == 0) rowab[r] = make_float2(st.x, -st.x * st.y);
      }
    }
    __syncwarp();
    bar_arrive(2, 96 + 384);
    bar_sync(1, 96);
    if (tid == 416) STAMP(0, 5);
    if (blockIdx.x < 128) {
      uint4 v[5];
      const int ck = min(t96, 79), nt = ck / 10;
#pragma unroll
      for (int i = 0; i < 5; i++) {
        const int k = blockIdx.x * 5 + i, pr = k / 40, r = k - pr * 40;
        v[i] = ldg_nc(wo + (size_t)(pr * 40 + (r < 16 ? r : (r < 32 ? r + 4 : (r < 36 ? r - 16 : r)))) * D_ + ck * 8);
      }
#pragma unroll
      for (int i = 0; i < 5; i++) {
        const int k = blockIdx.x * 5 + i;
        g_wo[((nt * 10 + (k >> 6)) * 10 + ck - nt * 10) * 64 + (k & 63)] = v[i];
        float t = ((bf_lo(v[i].x) + bf_hi(v[i].x)) + (bf_lo(v[i].y) + bf_hi(v[i].y))) +
                  ((bf_lo(v[i].z) + bf_hi(v[i].z)) + (bf_lo(v[i].w) + bf_hi(v[i].w)));
        if (t96 >= 80) t = 0.f;
#pragma unroll
        for (int o = 16; o; o >>= 1) t += __shfl_xor_sync(~0u, t, o);
        if (lane == 0) red[(t96 >> 5) * 8 + i] = t;
      }
      bar_sync(1, 96);
      if (t96 < 5) {
        const float mu = (red[t96] + red[8 + t96] + red[16 + t96]) * (1.f / D_);
        const float hi = bf_lo(pack_bf16(mu, 0.f));
        g_wm[blockIdx.x * 5 + t96] = make_uint4(pack_bf16(hi, mu - hi), 0u, 0u, 0u);
      }
    }
    if (tid == 416) STAMP(0, 7);
    __syncwarp();
    cluster_wait();
    cluster_arrive();
  } else {
    cluster_arrive();
    float acc[80];
    const uint64_t da0 = mkdesc(sbase + (warp >> 2) * 8192, 16, 1024, 1);
    const uint64_t db0 = mkdesc(sbase + 24576, 4096, 512, 2);
    const uint32_t tag = __ldcg(&g_epoch) + 1;
    const int srow = m * 192 + n * 16 + warp * 2;
    const bool dostat = warp < 8 && srow < S_;
    uint4 xv[2][3];
    bar_sync(4, 512);
    cluster_wait();
#pragma unroll
    for (int kt = 0; kt < 10; kt++) {
      const int s = kt % K1_ST;
      mbar_wait(fullb + 8 * s, (kt / K1_ST) & 1);
      if (kt == 0 && tid == 0) STAMP(0, 1);
      if (kt == 2 && tid == 0) STAMP(5, 0);
      if (kt == 4 && tid == 0) STAMP(5, 1);
      if (kt == 7 && tid == 0) STAMP(5, 2);
      const uint64_t da = da0 + s * (K1_STAGE >> 4), db = db0 + s * (K1_STAGE >> 4);
      WG_FENCE();
#pragma unroll
      for (int k = 0; k < 4; k++) wgmma_ss_n160(acc, da + k * 2, db + k * 64, (kt | k) != 0);
      WG_COMMIT();
      if (kt > 0) {
        WG_WAIT(1);
        if (kt - 1 + K1_ST < 10 && (tid & 127) < 2) mbar_arrive_cta(emptyb + 8 * ((kt - 1) % K1_ST), tid & 1);
      }
      if (kt == 0) {
#pragma unroll
        for (int i = 0; i < 2; i++) {
          const bf16* xr = x + (size_t)min(srow + i, S_ - 1) * D_ + lane * 8;
          xv[i][0] = xv[i][1] = xv[i][2] = make_uint4(0u, 0u, 0u, 0u);
          if (dostat) { xv[i][0] = ldg_nc(xr); xv[i][1] = ldg_nc(xr + 256); }
          if (dostat && lane < 16) xv[i][2] = ldg_nc(xr + 512);
        }
      }
      if ((kt == KST || kt == KST + 1) && dostat) {
        const float2 st = row_stats(xv[kt - KST][0], xv[kt - KST][1], xv[kt - KST][2]);
        if (lane == 0) st_relaxed(&g_rowstat[srow + kt - KST], st.x, st.y, tag);
      }
      __syncwarp();
    }
    cluster_arrive();
    WG_WAIT(0);
    fence_regs(acc);
    if (tid == 0) STAMP(0, 2);
    bar_sync(2, 96 + 384);
    if (tid == 0) STAMP(0, 3);
    const int row0 = m * 192 + warp * 16;
    if (row0 < S_) {
      const int g = lane >> 2, c = lane & 3, sec = n >> 2, grp = (row0 & 127) >> 3;
      const bool lo = c < 2;
      const float2 ab0 = rowab[warp * 16 + g], ab1 = rowab[warp * 16 + g + 8];
      const bool p0 = sec == 1 && ((POLY_MASK >> grp) & 1), p1 = sec == 1 && ((POLY_MASK >> (grp + 1)) & 1);
      const uint32_t padqv = sec == 0 ? (c == 2 ? 0x3F803F80u : 0x00003F80u) : (sec == 2 && c == 2 ? 0x00003F80u : 0u);
      const uint32_t padk = c == 2 ? 0x4A7A4B00u : 0x00004653u;
      const uint32_t pad0 = p0 ? padk : padqv, pad1 = p1 ? padk : padqv;
      const float f0 = sec == 0 ? QSCALE : (p0 ? 32768.f : 1.f), f1 = sec == 0 ? QSCALE : (p1 ? 32768.f : 1.f);
      const float a0 = ab0.x * f0, b0 = ab0.y * f0, a1 = ab1.x * f1, b1 = ab1.y * f1;
      const float r0 = p0 ? 9.313225746154785e-10f : 1.f, r1 = p1 ? 9.313225746154785e-10f : 1.f;
      const int cst = sec == 1 ? 2048 : 128, gst = sec == 1 ? 128 : 384;
      uint8_t* pe = (uint8_t*)g_qkv + (size_t)(n * 8) * HEAD_IMG + (row0 >> 7) * 6144 + grp * gst + lane * 4;
      uint8_t* pe1 = pe + cst;
      uint8_t* pe2 = pe1 + cst;
      uint8_t* pf = pe + gst;
      uint8_t* pf1 = pf + cst;
      uint8_t* pf2 = pf1 + cst;
#pragma unroll
      for (int hp = 0; hp < 4; hp++) {
        uint32_t u[5], v[5];
        float su[5], sv[5];
#pragma unroll
        for (int i = 0; i < 5; i++) {
          const int j = hp * 5 + i;
          const float2 t = *(const float2*)&cs[j * 8 + c * 2];
          const float x0 = fmaf(acc[4 * j], a0, b0 * t.x), x1 = fmaf(acc[4 * j + 1], a0, b0 * t.y);
          const float y0 = fmaf(acc[4 * j + 2], a1, b1 * t.x), y1 = fmaf(acc[4 * j + 3], a1, b1 * t.y);
          u[i] = pack_bf16(x0, x1); v[i] = pack_bf16(y0, y1);
          su[i] = fmaf(x0, x0, x1 * x1); sv[i] = fmaf(y0, y0, y1 * y1);
        }
        constexpr int HE = HEAD_IMG;
        const int oe = hp * 2 * HE, oo = oe + HE;
        *(uint32_t*)(pe + oe) = u[0];  *(uint32_t*)(pf + oe) = v[0];
        *(uint32_t*)(pe1 + oe) = u[1]; *(uint32_t*)(pf1 + oe) = v[1];
        *(uint32_t*)(pe2 + oe) = lo ? u[2] : pad0; *(uint32_t*)(pf2 + oe) = lo ? v[2] : pad1;
        *(uint32_t*)(pe + oo) = __shfl_xor_sync(~0u, lo ? u[3] : u[2], 2);
        *(uint32_t*)(pf + oo) = __shfl_xor_sync(~0u, lo ? v[3] : v[2], 2);
        *(uint32_t*)(pe1 + oo) = __shfl_xor_sync(~0u, lo ? u[4] : u[3], 2);
        *(uint32_t*)(pf1 + oo) = __shfl_xor_sync(~0u, lo ? v[4] : v[3], 2);
        const uint32_t tu = __shfl_xor_sync(~0u, u[4], 2), tv = __shfl_xor_sync(~0u, v[4], 2);
        *(uint32_t*)(pe2 + oo) = lo ? tu : pad0; *(uint32_t*)(pf2 + oo) = lo ? tv : pad1;
        if (sec < 2) {
          float e0 = (su[0] + su[1] + (lo ? su[2] : 0.f)) * r0, e1 = (sv[0] + sv[1] + (lo ? sv[2] : 0.f)) * r1;
          float o0 = (su[3] + su[4] + (lo ? 0.f : su[2])) * r0, o1 = (sv[3] + sv[4] + (lo ? 0.f : sv[2])) * r1;
          e0 += __shfl_xor_sync(~0u, e0, 1); e1 += __shfl_xor_sync(~0u, e1, 1);
          o0 += __shfl_xor_sync(~0u, o0, 1); o1 += __shfl_xor_sync(~0u, o1, 1);
          e0 += __shfl_xor_sync(~0u, e0, 2); e1 += __shfl_xor_sync(~0u, e1, 2);
          o0 += __shfl_xor_sync(~0u, o0, 2); o1 += __shfl_xor_sync(~0u, o1, 2);
          const uint32_t em = __reduce_max_sync(~0u, max(__float_as_uint(e0), __float_as_uint(e1)));
          const uint32_t om = __reduce_max_sync(~0u, max(__float_as_uint(o0), __float_as_uint(o1)));
          if (lane < 2) g_nrm[(n * 8 + hp * 2 + lane) * 128 + (row0 >> 4)] = __uint_as_float(lane ? om : em);
        }
      }
    }
    if (tid == 0) STAMP(0, 4);
  }
  cluster_wait();
  if (tid == 0) STAMP(0, 6);
}

constexpr int K2_SMEM = 2 * HEAD_IMG + 2 * 6144 + 2 * 10240 + 256;

__device__ __forceinline__ uint64_t desc64(uint32_t lo, uint32_t hi) {
  uint64_t d;
  asm("mov.b64 %0, {%1, %2};" : "=l"(d) : "r"(lo), "r"(hi));
  return d;
}
__device__ __forceinline__ uint32_t exp_pair(bool poly, float a, float b, uint32_t mk) {
  if (poly) {
    const uint32_t pk = __byte_perm(__float_as_uint(a), __float_as_uint(b), 0x6521);
    uint32_t m, q;
    asm("lop3.b32 %0, %1, %2, 0x3f803f80, 0xEA;" : "=r"(m) : "r"(pk), "r"(mk));
    asm("fma.rn.bf16x2 %0, %1, %1, %2;" : "=r"(q) : "r"(m), "r"(0x40014001u));
    return pk - m + q;
  }
  return pack_bf16(ex2(a), ex2(b));
}
#define PV_GR 4
__device__ __forceinline__ void exp_pv(const float (&s)[64], float (&o)[12], uint64_t dv, uint32_t mk) {
#pragma unroll
  for (int k0 = 0; k0 < 8; k0 += PV_GR) {
    uint32_t p[4 * PV_GR];
#pragma unroll
    for (int i = 0; i < 4 * PV_GR; i++)
      p[i] = exp_pair((POLY_MASK >> (k0 * 2 + i / 2)) & 1, s[k0 * 8 + 2 * i], s[k0 * 8 + 2 * i + 1], mk);
    WG_FENCE();
#pragma unroll
    for (int k = 0; k < PV_GR; k++)
      wgmma_rs_n24(o, p[4 * k], p[4 * k + 1], p[4 * k + 2], p[4 * k + 3], dv + (k0 + k) * 48, 1);
  }
}
__device__ __forceinline__ void load_q(uint32_t (&q)[6], const uint8_t* p) {
  q[0] = __ldcg((const uint32_t*)p);         q[1] = __ldcg((const uint32_t*)(p + 384));
  q[2] = __ldcg((const uint32_t*)(p + 128)); q[3] = __ldcg((const uint32_t*)(p + 512));
  q[4] = __ldcg((const uint32_t*)(p + 256)); q[5] = __ldcg((const uint32_t*)(p + 640));
}
__device__ __forceinline__ float rcp(float x) {
  float y;
  asm("rcp.approx.ftz.f32 %0, %1;" : "=f"(y) : "f"(x));
  return y;
}
__device__ __forceinline__ int img_off(int chunk) { return chunk * 2048; }
__device__ __forceinline__ void store_o(const float (&o)[12], int tile) {
  int tid, bid;
  asm volatile("mov.u32 %0, %%tid.x;" : "=r"(tid));
  asm volatile("mov.u32 %0, %%ctaid.x;" : "=r"(bid));
  const int head = bid >> 2;
  uint8_t* dst = (uint8_t*)g_o + ((bid & 3) * 4 + (tile >> 1)) * 163840 + (tile & 1) * 1024 + ((tid >> 5) & 3) * 256 + (tid & 31) * 4;
  const int oc = (head >> 1) * 5 + (head & 1) * 2;
  const int o0 = img_off(oc), o1 = img_off(oc + 1), o2 = img_off((head >> 1) * 5 + 4) + (head & 1) * 8;
  const float i0 = rcp(__shfl_sync(~0u, o[8], 2, 4)), i1 = rcp(__shfl_sync(~0u, o[10], 2, 4));
  *(uint32_t*)(dst + o0) = pack_bf16(o[0] * i0, o[1] * i0); *(uint32_t*)(dst + o0 + 128) = pack_bf16(o[2] * i1, o[3] * i1);
  *(uint32_t*)(dst + o1) = pack_bf16(o[4] * i0, o[5] * i0); *(uint32_t*)(dst + o1 + 128) = pack_bf16(o[6] * i1, o[7] * i1);
  if ((tid & 3) < 2) {
    *(uint32_t*)(dst + o2) = pack_bf16(o[8] * i0, o[9] * i0);
    *(uint32_t*)(dst + o2 + 128) = pack_bf16(o[10] * i1, o[11] * i1);
  }
}

struct Maps5 { CUtensorMap m[5]; };

__global__ void __launch_bounds__(512, 1)
k2_attn(const __grid_constant__ Maps5 maps, uint32_t mk) {
  const CUtensorMap* tmw = maps.m;
  extern __shared__ __align__(1024) uint8_t sm[];
  const uint32_t sbase = smem_u32(sm);
  float* part = (float*)(sm + 2 * HEAD_IMG);
  const uint32_t rbuf = sbase + 2 * HEAD_IMG + 2 * 6144;
  const uint32_t kvb = rbuf + 2 * 10240;
  const uint32_t partb = kvb + 128, rbar = kvb + 144;
  const int tid = threadIdx.x, lane = tid & 31;
  const int warp = __shfl_sync(~0u, tid >> 5, 0);
  const int head = blockIdx.x >> 2, qb = blockIdx.x & 3;

  if (tid == 0) STAMP(1, 0);
  if (tid == 0) {
    for (int i = 0; i < 16; i++) mbar_init(kvb + 8 * i, 1);
    mbar_init(partb, 128); mbar_init(partb + 8, 128); mbar_init(rbar, 1); mbar_init(rbar + 8, 1);
    asm volatile("fence.mbarrier_init.release.cluster;" ::: "memory");
  }
  __syncthreads();

  if (warp >= 12) {
    asm volatile("setmaxnreg.dec.sync.aligned.u32 32;");
    if (tid == 384) {
      pdl_wait();
      pdl_trigger();
      const uint8_t* kimg = (const uint8_t*)g_qkv + (size_t)(32 + head) * HEAD_IMG;
#pragma unroll 1
      for (int b = 0; b < 16; b++) {
        mbar_expect(kvb + 8 * b, 12288);
        bulk_ld(sbase + b * 6144, kimg + b * 6144, 6144, kvb + 8 * b);
        bulk_ld(sbase + HEAD_IMG + b * 6144, kimg + 32 * HEAD_IMG + b * 6144, 6144, kvb + 8 * b);
        if (b >= 2) mbar_wait(kvb + 8 * (b - 1), 0);

      }
      if (blockIdx.x == 0) g_epoch = g_epoch + 1;
      mbar_wait(kvb + 8 * 15, 0);
      STAMP(1, 2);
      uint8_t* pdst = nullptr;
      uint32_t pbytes = 0;
#pragma unroll 1
      for (int i = 0; i < 8; i++) {
        const int p = blockIdx.x + 128 * i;
        uint8_t* dst = nullptr;
        uint32_t bytes = 0;
        if (i < 7 && p < 856) {
          asm volatile("cp.async.bulk.wait_group.read 0;" ::: "memory");
          const CUtensorMap* tm;
          int c1, c2;
          if (p < 640) {
            const int nt = p / 80, r = p - nt * 80, ph = r / 40, st = (r - ph * 40) >> 1, up = r & 1;
            bytes = ph ? 6656 : 7168;
            dst = (uint8_t*)g_wgu + nt * 552960 + ph * 286720 + st * 2 * bytes + up * (bytes >> 1);
            tm = &tmw[ph * 2 + up]; c1 = ph ? 112 + nt * 13 : nt * 14; c2 = st * 2;
          } else {
            const int nk = p - 640, nt = nk / 27;
            bytes = 10240;
            dst = (uint8_t*)g_wd + (size_t)nk * 10240;
            tm = &tmw[4]; c1 = nt * 10; c2 = nk - nt * 27;
          }
          mbar_expect(rbar + 8 * (i & 1), bytes);
          tma4d(rbuf + (i & 1) * 10240, tm, c1, c2, rbar + 8 * (i & 1));
        }
        if (pbytes) {
          mbar_wait(rbar + 8 * ((i - 1) & 1), ((i - 1) >> 1) & 1);
          if (pbytes == 10240) {
            bulk_st(pdst, rbuf + ((i - 1) & 1) * 10240, pbytes);
          } else {
            bulk_st(pdst, rbuf + ((i - 1) & 1) * 10240, pbytes >> 1);
            bulk_st(pdst + pbytes, rbuf + ((i - 1) & 1) * 10240 + (pbytes >> 1), pbytes >> 1);
          }
          asm volatile("cp.async.bulk.commit_group;" ::: "memory");
        }
        pdst = dst; pbytes = bytes;
      }
      asm volatile("cp.async.bulk.wait_group.read 0;" ::: "memory");
      STAMP(1, 6);
    }
  } else {
    asm volatile("setmaxnreg.inc.sync.aligned.u32 160;");
    const int wg = warp >> 2;
    const uint8_t* qthr = (const uint8_t*)g_qkv + (size_t)head * HEAD_IMG + qb * 64 * 384 + (warp & 3) * 768 + lane * 4;
    const uint32_t klo0 = ((sbase & 0x3FFFF) >> 4) | (128u << 16), vlo0 = (((sbase + HEAD_IMG) & 0x3FFFF) >> 4) | (24u << 16);
    constexpr uint64_t KSTEP2 = (uint64_t)(int64_t)(256 - (128 << 16));
    constexpr uint64_t KV2K = 384 - (HEAD_IMG >> 4) + (104 << 16);
    const int nun = wg == 1 ? 4 : 3;
    uint32_t utile = wg == 0 ? 0x210u : (wg == 1 ? 0x4235u : 0x576u);
    uint32_t ubeg = wg == 0 ? 0u : (wg == 1 ? 0x0b00u : 0x600u);
    uint32_t ulen = wg == 0 ? 0x0b1010u : (wg == 1 ? 0x10051006u : 0x0a1010u);
    pdl_wait();
    if (tid == 0) STAMP(1, 1);
    uint32_t q[6];
    load_q(q, qthr + (utile & 15) * 3072);
    bool fast;
    {
      const float4 kn = __ldcg((const float4*)&g_nrm[(32 + head) * 128 + lane * 4]);
      const float qv = __ldcg(&g_nrm[head * 128 + qb * 32 + lane]);
      const uint32_t km = max(max(__float_as_uint(kn.x), __float_as_uint(kn.y)), max(__float_as_uint(kn.z), __float_as_uint(kn.w)));
      const float k2 = __uint_as_float(__reduce_max_sync(~0u, km)), q2 = __uint_as_float(__reduce_max_sync(~0u, __float_as_uint(qv)));
      fast = q2 * k2 <= 3400.f;
    }
    if (fast) {
#pragma unroll 1
      for (int u = 0; u < nun; u++) {
        const uint32_t b0 = ubeg & 15;
        const bool wt = u == 0 || (wg == 1 && u == 1);
        float s[64], o[12];
#pragma unroll
        for (int i = 0; i < 12; i++) o[i] = 0.f;
        uint32_t vlo = vlo0 + b0 * 384, kb = kvb + b0 * 8;
        const uint32_t vend = vlo + ((ulen & 255) - 1) * 384;
        if (wt) mbar_wait(kb, 0);
        if (tid == 0) STAMP(5, 4 + u);
        fence_regs(o);
        WG_FENCE();
        wgmma_rs_n128(s, q[0], q[1], q[2], q[3], desc64(klo0 + b0 * 384, 8), 0);
        wgmma_rs_n128(s, q[4], q[5], 0, 0, desc64(klo0 + b0 * 384, 8) + KSTEP2, 1);
        WG_COMMIT();
#define K2UNR 1
        constexpr int kUnr = K2UNR;
#pragma unroll kUnr
        for (; vlo != vend; vlo += 384) {
          if (wt) { kb += 8; mbar_wait(kb, 0); }
          WG_WAIT(0);
          fence_regs(s); fence_regs(o);
          const uint64_t dv = desc64(vlo, 8);
          exp_pv(s, o, dv, mk);
          wgmma_rs_n128(s, q[0], q[1], q[2], q[3], dv + KV2K, 0);
          wgmma_rs_n128(s, q[4], q[5], 0, 0, dv + (KV2K + KSTEP2), 1);
          WG_COMMIT();
        }
        WG_WAIT(0);
        fence_regs(s); fence_regs(o);
        if (u + 1 < nun) load_q(q, qthr + ((utile >> 4) & 15) * 3072);
        exp_pv(s, o, desc64(vlo, 8), mk);
        WG_COMMIT();
        WG_WAIT(0);
        fence_regs(o);
        if (wg == 1 && !(u & 1)) {
          float4* pp = (float4*)(part + u * 768) + (tid & 127);
          pp[0] = make_float4(o[0], o[1], o[2], o[3]);
          pp[128] = make_float4(o[4], o[5], o[6], o[7]);
          pp[256] = make_float4(o[8], o[9], o[10], o[11]);
          mbar_arrive(partb + 4 * u);
        } else {
          if (wg != 1 && u == 2) {
            const int pi = wg == 0 ? 1 : 0;
            mbar_wait(partb + 8 * pi, 0);
            const float4* pp = (const float4*)(part + pi * 1536) + (tid & 127);
            const float4 x0 = pp[0], x1 = pp[128], x2 = pp[256];
            o[0] += x0.x; o[1] += x0.y; o[2] += x0.z; o[3] += x0.w; o[4] += x1.x; o[5] += x1.y;
            o[6] += x1.z; o[7] += x1.w; o[8] += x2.x; o[9] += x2.y; o[10] += x2.z; o[11] += x2.w;
          }
          store_o(o, utile & 15);
        }
        utile >>= 4; ubeg >>= 4; ulen >>= 8;
      }
      if ((tid & 127) == 0) STAMP(1, 3 + wg);
    } else {
#pragma unroll 1
      for (int tile = wg; tile < 8; tile += 3) {
        load_q(q, qthr + tile * 3072);
        if ((lane & 3) >= 2) { q[4] = 0; q[5] = 0; }
        float o[12], m0 = -INFINITY, m1 = -INFINITY;
#pragma unroll
        for (int i = 0; i < 12; i++) o[i] = 0.f;
#pragma unroll 1
        for (int b = 0; b < 16; b++) {
          float s[64];
          mbar_wait(kvb + 8 * b, 0);
          WG_FENCE();
          wgmma_rs_n128(s, q[0], q[1], q[2], q[3], desc64(klo0 + b * 384, 8), 0);
          wgmma_rs_n128(s, q[4], q[5], 0, 0, desc64(klo0 + b * 384, 8) + KSTEP2, 1);
          WG_COMMIT();
          WG_WAIT(0);
          fence_regs(s);
          float x0 = m0, x1 = m1;
#pragma unroll
          for (int j = 0; j < 16; j++) {
            if ((POLY_MASK >> j) & 1) {
#pragma unroll
              for (int i = 0; i < 4; i++) s[4 * j + i] *= (1.f / 32768.f);
            }
            x0 = fmaxf(x0, fmaxf(s[4 * j], s[4 * j + 1]));
            x1 = fmaxf(x1, fmaxf(s[4 * j + 2], s[4 * j + 3]));
          }
          x0 = fmaxf(x0, __shfl_xor_sync(~0u, x0, 1)); x0 = fmaxf(x0, __shfl_xor_sync(~0u, x0, 2));
          x1 = fmaxf(x1, __shfl_xor_sync(~0u, x1, 1)); x1 = fmaxf(x1, __shfl_xor_sync(~0u, x1, 2));
          const float al0 = ex2(m0 - x0), al1 = ex2(m1 - x1);
          m0 = x0; m1 = x1;
#pragma unroll
          for (int i = 0; i < 12; i++) o[i] *= (i & 2) ? al1 : al0;
          uint32_t p[32];
#pragma unroll
          for (int i = 0; i < 32; i++) {
            const float mm = (i & 1) ? m1 : m0;
            p[i] = pack_bf16(ex2(s[2 * i] - mm), ex2(s[2 * i + 1] - mm));
          }
          fence_regs(o);
          WG_FENCE();
#pragma unroll
          for (int k = 0; k < 8; k++)
            wgmma_rs_n24(o, p[4 * k], p[4 * k + 1], p[4 * k + 2], p[4 * k + 3], desc64(vlo0 + b * 384 + k * 48, 8), 1);
          WG_COMMIT();
          WG_WAIT(0);
          fence_regs(o);
        }
        store_o(o, tile);
      }
    }
  }
}

#define K3P 1
constexpr int K3_ST = 4, K3_STAGE = 37888, K3_PRE = K3P;
constexpr int K3_SMEM = K3_ST * K3_STAGE + 45056 + 20480 + 256;

template <int N> struct Acc { float v[N]; };

template <int NB, int NK, bool FIRST>
__global__ void __cluster_dims__(2, 1, 1) __launch_bounds__(384, 1)
k3_proj(const __grid_constant__ CUtensorMap tmr, const uint4* __restrict__ aimg, const uint4* __restrict__ wimg) {
  constexpr int KT = 2 * NB + NK, EX = FIRST ? 1 : 0;
  extern __shared__ __align__(1024) uint8_t sm[];
  const uint32_t sbase = smem_u32(sm);
  uint8_t* xch = sm + K3_ST * K3_STAGE;
  uint8_t* stg = sm + K3_ST * K3_STAGE + 45056;
  const uint32_t fullb = smem_u32(stg) + 20480, emptyb = fullb + 8 * K3_ST, resb = emptyb + 8 * K3_ST, xchb = resb + 8;
  const int tid = threadIdx.x, lane = tid & 31;
  const int warp = __shfl_sync(~0u, tid >> 5, 0);
  const int rank = blockIdx.x & 1;
  const int n = blockIdx.x & 7, m = blockIdx.x >> 3;
  if (tid == 0) STAMP(FIRST ? 2 : 4, 0);
  if (warp == 0) {
    if (lane == 0) {
      prefetch_map(&tmr);
      for (int i = 0; i < K3_ST; i++) { mbar_init(fullb + 8 * i, 1); mbar_init(emptyb + 8 * i, 4); }
      mbar_init(resb, 1); mbar_init(xchb, 1);
      mbar_expect(xchb, 4096 * (10 + EX));
      asm volatile("fence.mbarrier_init.release.cluster;" ::: "memory");
    }
    __syncwarp();
    cluster_arrive();
    bar_arrive(4, 256 + 32);
    const uint8_t* wk = (const uint8_t*)wimg + (size_t)n * KT * 10240;
    const uint8_t* ws = (const uint8_t*)wimg + (size_t)(n ^ 1) * KT * 10240;
    const uint8_t* ab = (const uint8_t*)aimg + (size_t)m * KT * 16384;
    auto load_w = [&](int i) {
      const int s = i % K3_ST, kt = i < NB ? i + rank * (NB + NK) : i;
      const uint32_t sa = sbase + s * K3_STAGE;
      mbar_expect(fullb + 8 * s, 26624 + EX * 1024 + (i < NB ? 10240 : 0));
      bulk_ld(sa + 16384, wk + kt * 10240, 10240, fullb + 8 * s);
      if (FIRST) bulk_ld(sa + 26624, (const uint8_t*)g_wm + kt * 1024, 1024, fullb + 8 * s);
      if (i < NB) bulk_ld(sa + 26624 + EX * 1024, ws + kt * 10240, 10240, fullb + 8 * s);
    };
    if (elect_one()) {
#pragma unroll 1
      for (int i = 0; i < K3_PRE; i++) load_w(i);
    }
    cluster_wait();
    pdl_wait();
    pdl_trigger();
    if (lane == 0) STAMP(2, 6);
#pragma unroll 1
    for (int i = 0; i < NB + NK; i++) {
      const int s = i % K3_ST;
      const uint32_t sa = sbase + s * K3_STAGE;
      if (i >= K3_ST) mbar_wait(emptyb + 8 * s, ((i / K3_ST) - 1) & 1);
      if (elect_one()) {
        if (i < NB) bulk_ld(sa, ab + (i + rank * (NB + NK)) * 16384, 16384, fullb + 8 * s);
        else bulk_ld_mc(sa + rank * 8192, ab + i * 16384 + rank * 8192, 8192, fullb + 8 * s);
        if (i >= K3_PRE) load_w(i);
        if (FIRST && i == K3_ST - 1) {
          mbar_expect(resb, 20480);
          tma2d(smem_u32(stg), &tmr, n * 80, m * 128, resb);
          tma2d(smem_u32(stg) + 10240, &tmr, n * 80, m * 128 + 64, resb);
        }
      }
    }
    __syncwarp();
    cluster_arrive();
  } else if (warp >= 4) {
    cluster_arrive();
    const int cw = warp - 4, wg = cw >> 2;
    const int g = lane >> 2, c = lane & 3;
    const int row = m * 128 + cw * 16 + g;
    uint8_t* himg = (uint8_t*)g_h + (size_t)m * 163840 + cw * 256 + lane * 4;
    uint32_t rv[20];
    float mu0, mu1;
    if (FIRST) {
      mu0 = __uint_as_float(__ldcg(&g_rowstat[row].z)); mu1 = __uint_as_float(__ldcg(&g_rowstat[row + 8].z));
    } else {
      mu0 = __ldcg(&g_hmean[row]); mu1 = __ldcg(&g_hmean[row + 8]);
#pragma unroll
      for (int j = 0; j < 10; j++) {
        rv[2 * j] = __ldcg((const uint32_t*)(himg + img_off(n * 10 + j)));
        rv[2 * j + 1] = __ldcg((const uint32_t*)(himg + img_off(n * 10 + j) + 128));
      }
    }
    float acc[80 + 4 * EX];
    float (&keep)[40 + 4 * EX] = ((Acc<40 + 4 * EX>*)acc)->v;
    const uint64_t da0 = mkdesc(sbase + wg * 1024, 2048, 128, 0);
    const uint64_t db0 = mkdesc(sbase + 16384, 128, 1024, 0);
    bar_sync(4, 256 + 32);
    cluster_wait();
#pragma unroll 1
    for (int i = 0; i < NB; i++) {
      const int s = i % K3_ST;
      mbar_wait(fullb + 8 * s, (i / K3_ST) & 1);
      if (i == 0 && tid == 128) STAMP(FIRST ? 2 : 4, 2);
      const uint64_t da = da0 + s * (K3_STAGE >> 4), db = db0 + s * (K3_STAGE >> 4);
      WG_FENCE();
#pragma unroll
      for (int k = 0; k < 4; k++) {
        if constexpr (FIRST) wgmma_ss_n168(acc, da + k * 256, db + k * 16, (i | k) != 0);
        else wgmma_ss_n160(acc, da + k * 256, db + k * 16, (i | k) != 0);
      }
      WG_COMMIT();
      if (i > 0) {
        WG_WAIT(1);
        if ((tid & 127) < 2) mbar_arrive_cta(emptyb + 8 * ((i - 1) % K3_ST), tid & 1);
      }
    }
    const uint32_t rx = mapa(smem_u32(xch) + (tid - 128) * 16, rank ^ 1), rb = mapa(xchb, rank ^ 1);
    WG_WAIT(0);
    fence_regs(acc);
    if ((tid & 127) < 2) mbar_arrive_cta(emptyb + 8 * ((NB - 1) % K3_ST), tid & 1);
    if (FIRST) st_async4(rx, acc[40], acc[41], acc[42], acc[43], rb);
    if (tid == 128) STAMP(FIRST ? 2 : 4, 1);
#pragma unroll
    for (int i = NB; i < NB + NK; i++) {
      const int s = i % K3_ST;
      mbar_wait(fullb + 8 * s, (i / K3_ST) & 1);
      const uint64_t da = da0 + s * (K3_STAGE >> 4), db = db0 + s * (K3_STAGE >> 4);
      WG_FENCE();
#pragma unroll
      for (int k = 0; k < 4; k++) {
        if constexpr (FIRST) wgmma_ss_n88(keep, da + k * 256, db + k * 16, 1);
        else wgmma_ss_n80(keep, da + k * 256, db + k * 16, 1);
      }
      WG_COMMIT();
      if (i > NB && i - 1 + K3_ST < NB + NK) {
        WG_WAIT(1);
        if ((tid & 127) < 2) mbar_arrive_cta(emptyb + 8 * ((i - 1) % K3_ST), tid & 1);
      }
#pragma unroll
      for (int j = (i - NB) * 3 + EX; j < (i - NB) * 3 + 3 + EX; j++)
        if (j < 10 + EX) st_async4(rx + j * 4096, acc[40 + 4 * j], acc[41 + 4 * j], acc[42 + 4 * j], acc[43 + 4 * j], rb);
    }
    cluster_arrive();
    uint8_t* sp = stg + (cw * 16 + g) * 160 + c * 4;
    if (FIRST) {
      mbar_wait(resb, 0);
#pragma unroll
      for (int j = 0; j < 10; j++) {
        rv[2 * j] = *(const uint32_t*)(sp + j * 16);
        rv[2 * j + 1] = *(const uint32_t*)(sp + 1280 + j * 16);
      }
    }
    WG_WAIT(0);
    fence_regs(keep);
    if (tid == 128) STAMP(FIRST ? 2 : 4, 3);
    mbar_wait(xchb, 0);
    if (tid == 128) STAMP(FIRST ? 2 : 4, 5);
    const uint8_t* xp = xch + (tid - 128) * 16;
    if (FIRST) {
      const float4 p = *(const float4*)xp;
      mu0 += __shfl_sync(~0u, (keep[40] + p.x) + (keep[41] + p.y), 0, 4);
      mu1 += __shfl_sync(~0u, (keep[42] + p.z) + (keep[43] + p.w), 0, 4);
      if (n == 0 && c == 0) { g_hmean[row] = mu0; g_hmean[row + 8] = mu1; }
      mu0 = -mu0; mu1 = -mu1;
    }
    float q0 = 0.f, q1 = 0.f;
#pragma unroll
    for (int j = 0; j < 10; j++) {
      const float4 p = *(const float4*)(xp + (j + EX) * 4096);
      const float x0 = (keep[4 * j] + p.x) + (bf_lo(rv[2 * j]) + mu0), x1 = (keep[4 * j + 1] + p.y) + (bf_hi(rv[2 * j]) + mu0);
      const float y0 = (keep[4 * j + 2] + p.z) + (bf_lo(rv[2 * j + 1]) + mu1), y1 = (keep[4 * j + 3] + p.w) + (bf_hi(rv[2 * j + 1]) + mu1);
      if (FIRST) {
        *(uint32_t*)(himg + img_off(n * 10 + j)) = pack_bf16(x0, x1);
        *(uint32_t*)(himg + img_off(n * 10 + j) + 128) = pack_bf16(y0, y1);
        q0 = fmaf(x0, x0, fmaf(x1, x1, q0)); q1 = fmaf(y0, y0, fmaf(y1, y1, q1));
      } else {
        *(uint32_t*)(sp + j * 16) = pack_bf16(x0, x1);
        *(uint32_t*)(sp + 1280 + j * 16) = pack_bf16(y0, y1);
      }
    }
    if (FIRST) {
      q0 += __shfl_xor_sync(~0u, q0, 1); q0 += __shfl_xor_sync(~0u, q0, 2);
      q1 += __shfl_xor_sync(~0u, q1, 1); q1 += __shfl_xor_sync(~0u, q1, 2);
      if (c < 2) g_hpart[n * S_ + row + c * 8] = c ? q1 : q0;
    } else {
      fence_async();
      bar_sync(1 + wg, 128);
      if ((tid & 127) == 0) {
        tma2d_st(&tmr, n * 80, m * 128 + wg * 64, smem_u32(stg) + wg * 10240);
        bulk_commit_wait();
      }
      __syncwarp();
    }
    if (tid == 128) STAMP(FIRST ? 2 : 4, 4);
  } else {
    cluster_arrive();
    cluster_wait();
    cluster_arrive();
  }
  cluster_wait();
}

constexpr int K4_G = 2, K4_NS = 4, K4_NJ = 20;
constexpr int K4_RB = 163840, K4_BST = 7168 * K4_G, K4_XCH = 147456, K4_STG = K4_XCH + 40960, K4_BAR = K4_RB + K4_NS * K4_BST;
constexpr int K4_SMEM = K4_BAR + 384;

__device__ __forceinline__ void wait_flags(const uint32_t* f0, const uint32_t* f1, uint32_t tag) {
  for (uint32_t it = 0;; it++) {
    uint32_t a, b;
    asm volatile("ld.acquire.gpu.global.u32 %0, [%1];" : "=r"(a) : "l"(f0) : "memory");
    asm volatile("ld.acquire.gpu.global.u32 %0, [%1];" : "=r"(b) : "l"(f1) : "memory");
    if (a == tag && b == tag) break;
    if (it > (1u << 20)) wait_timeout();
    __nanosleep(40);
  }
  asm volatile("fence.proxy.async.global;" ::: "memory");
}

__global__ void __cluster_dims__(2, 1, 1) __launch_bounds__(384, 1)
k45_ffn(const __grid_constant__ CUtensorMap tmo) {
  extern __shared__ __align__(1024) uint8_t sm[];
  const uint32_t sbase = smem_u32(sm);
  const uint32_t afull = sbase + K4_BAR, bfull = afull + 80, bempty = bfull + 8 * K4_NS, full3 = bempty + 8 * K4_NS;
  const uint32_t empty3 = full3 + 32, afree = empty3 + 32, xchb = afree + 32;
  const int tid = threadIdx.x, lane = tid & 31;
  const int warp = __shfl_sync(~0u, tid >> 5, 0);
  const int rank = blockIdx.x & 1;
  const int n1 = (blockIdx.x >> 1) & 7, m1 = (blockIdx.x >> 4) * 2 + rank;
  const int n3 = blockIdx.x & 7, m3 = blockIdx.x >> 3;
  if (tid == 0) STAMP(3, 0);
  if (warp == 8) {
    if (elect_one()) {
#pragma unroll
      for (int i = 0; i < 10; i++) mbar_init(afull + 8 * i, 1);
#pragma unroll
      for (int i = 0; i < 4; i++) {
        mbar_init(bfull + 8 * i, 1); mbar_init(bempty + 8 * i, 4); mbar_init(full3 + 8 * i, 1); mbar_init(empty3 + 8 * i, 4);
        mbar_init(afree + 8 * i, 2);
      }
      mbar_init(xchb, 1);
      mbar_expect(xchb, 40960);
      asm volatile("fence.mbarrier_init.release.cluster;" ::: "memory");
    }
    __syncwarp();
  }
  cluster_arrive();
  if (warp >= 8) {
    cluster_wait();
    if (warp == 8) {
      if (lane == 0) STAMP(3, 7);
      const uint8_t* src = (const uint8_t*)g_wgu + n1 * 552960;
      const uint8_t* hb = (const uint8_t*)g_h + (size_t)m1 * 163840;
#pragma unroll 1
      for (int j = 0; j < 40; j++) {
        const uint32_t s8 = (j & 3) * 8, sz = j < 20 ? 14336 : 13312;
#define K4PRE 2
        if (j == K4PRE) {
          pdl_wait();
          if (lane == 0) STAMP(3, 1);
          if (elect_one()) {
#pragma unroll
            for (int kt = 0; kt < K4PRE / 2 + 1; kt++) { mbar_expect(afull + 8 * kt, 16384); bulk_ld(sbase + kt * 16384, hb + kt * 16384, 16384, afull + 8 * kt); }
          }
        }
        if (j >= 4) mbar_wait(bempty + s8, ((j >> 2) - 1) & 1);
        if (elect_one()) {
          mbar_expect(bfull + s8, sz);
          if ((j & 1) == rank) bulk_ld_mc(sbase + K4_RB + s8 * (K4_BST / 8), src, sz, bfull + s8);
          if (j > K4PRE && j < 18 && (j & 1)) {
            mbar_expect(afull + 4 + j * 4, 16384);
            bulk_ld(sbase + 8192 + j * 8192, hb + 8192 + j * 8192, 16384, afull + 4 + j * 4);
          }
        }
        src += sz;
      }
    } else if (warp == 9) {
      prefetch_map(&tmo);
      const uint32_t tag = __ldcg(&g_epoch);
#pragma unroll 1
      for (int ph = 0; ph < 2; ph++) {
        bar_sync(5 + ph, 256 + 32);
        if (lane == 0) {
          if (ph) {
            bulk_st((uint8_t*)g_hh + (size_t)m1 * 442368 + img_off(112 + n1 * 13), sbase + K4_STG, 13 * 2048);
            asm volatile("cp.async.bulk.commit_group;\ncp.async.bulk.wait_group 0;\nfence.proxy.async.global;" ::: "memory");
          }
          asm volatile("st.release.gpu.global.u32 [%0], %1;" ::"l"((uint32_t*)&g_flag[ph * 32 + m1 * 2] + n1), "r"(tag) : "memory");
          STAMP(3, 5 + ph);
        }
        __syncwarp();
      }
      bar_arrive(8, 256 + 32);
    } else {
      const uint8_t* wk = (const uint8_t*)g_wd + n3 * 276480;
      const uint8_t* ws = (const uint8_t*)g_wd + (n3 ^ 1) * 276480;
      const uint8_t* ab = (const uint8_t*)g_hh + (size_t)m3 * 442368;
      const uint32_t tag = __ldcg(&g_epoch);
#pragma unroll 1
      for (int i = 0; i < 16; i++) {
        const int kt = i < 7 ? rank * 7 + i : (i < 11 ? rank * 4 + 7 + i : 11 + i);
        const uint32_t sa = sbase + (i & 3) * 36864, fb = full3 + 8 * (i & 3);
        if (i < 4) mbar_wait(afree + 8 * i, 0);
        else mbar_wait(empty3 + 8 * (i & 3), ((i >> 2) - 1) & 1);
        if (warp == 10) {
          if (elect_one()) {
            mbar_expect(fb, i < 11 ? 36864 : 26624);
            bulk_ld(sa + 16384, wk + kt * 10240, 10240, fb);
            if (i < 11) bulk_ld(sa + 26624, ws + kt * 10240, 10240, fb);
          }
        } else {
          {
            const uint32_t* f = (const uint32_t*)&g_flag[(i < 7 ? 0 : 32) + m3 * 2];
            const int q = kt * 8 - (i < 7 ? 0 : 112), w = i < 7 ? 14 : 13;
            wait_flags(f + q / w, f + (q + 7) / w, tag);
            if (lane == 0 && (i == 0 || i == 7)) STAMP(4, i ? 7 : 6);
          }
          if (elect_one()) {
            if (i < 11) bulk_ld(sa, ab + kt * 16384, 16384, fb);
            else bulk_ld_mc(sa + rank * 8192, ab + kt * 16384 + rank * 8192, 8192, fb);
          }
        }
      }
    }
    __syncwarp();
    cluster_arrive();
    asm volatile("barrier.cluster.wait.aligned; // producers" ::: "memory");
  } else {
    const int wg = warp >> 2;
    const uint64_t da0 = mkdesc(sbase + wg * 1024, 2048, 128, 0);
    const uint64_t db0 = mkdesc(sbase + K4_RB, 128, 256, 0);
    cluster_wait();
    float a1[112], a2[104];
    int s = 0, ph = 0, sprev = 0;
#pragma unroll 1
    for (int j = 0; j < K4_NJ; j++) {
      if ((j * K4_G) % 4 == 0) mbar_wait(afull + 2 * K4_G * j, 0);
      mbar_wait(bfull + 8 * s, ph);
      if (j == 0 && tid == 0) STAMP(3, 2);
      const uint64_t da = da0 + j * K4_G * 256, db = db0 + s * (K4_BST >> 4);
      WG_FENCE();
#pragma unroll
      for (int k = 0; k < K4_G; k++) wgmma_ss_n224(a1, da + k * 256, db + k * 448, (j | k) != 0);
      WG_COMMIT();
      if (j > 0) {
        WG_WAIT(1);
        if ((tid & 127) < 2) mbar_arrive_cta(bempty + 8 * sprev, tid & 1);
      }
      sprev = s;
      if (++s == K4_NS) { s = 0; ph ^= 1; }
    }
    float acc[80];
    uint8_t* hd = (uint8_t*)g_hh + (size_t)m1 * 442368 + warp * 256 + lane * 4;
    WG_WAIT(0);
    fence_regs(a1);
    if ((tid & 127) < 2) mbar_arrive_cta(bempty + 8 * ((K4_NJ - 1) % K4_NS), tid & 1);
    if (tid == 0) STAMP(3, 3);
#define STORE_H(a, off, ptr, c) do { uint8_t* p_ = ptr; \
      *(uint32_t*)p_ = pack_bf16(a[4 * (c)] * a[off + 4 * (c)], a[4 * (c) + 1] * a[off + 1 + 4 * (c)]); \
      *(uint32_t*)(p_ + 128) = pack_bf16(a[4 * (c) + 2] * a[off + 2 + 4 * (c)], a[4 * (c) + 3] * a[off + 3 + 4 * (c)]); } while (0)
#pragma unroll
    for (int c = 0; c < 14; c++) STORE_H(a1, 56, hd + img_off(n1 * 14 + c), c);
    bar_arrive(5, 256 + 32);
#pragma unroll 1
    for (int j = 0; j < K4_NJ; j++) {
      mbar_wait(bfull + 8 * s, ph);
      const uint64_t da = da0 + j * K4_G * 256, db = db0 + s * (K4_BST >> 4);
      WG_FENCE();
#pragma unroll
      for (int k = 0; k < K4_G; k++) wgmma_ss_n208(a2, da + k * 256, db + k * 416, (j | k) != 0);
      WG_COMMIT();
      if (j > 0) {
        WG_WAIT(1);
        if (j <= K4_NJ - K4_NS && (tid & 127) < 2) mbar_arrive_cta(bempty + 8 * sprev, tid & 1);
        if (j * K4_G >= 12 && ((j * K4_G) & 7) == 4 && (tid & 127) == 0) mbar_arrive(afree + (j * K4_G - 12));
      }
      sprev = s;
      if (++s == K4_NS) { s = 0; ph ^= 1; }
    }
    WG_WAIT(0);
    fence_regs(a2);
    if (tid == 0) STAMP(3, 4);
    bar_sync(7, 256);
#pragma unroll
    for (int c = 0; c < 13; c++) STORE_H(a2, 52, sm + K4_STG + warp * 256 + lane * 4 + img_off(c), c);
    fence_async();
    bar_arrive(6, 256 + 32);
    float (&keep)[40] = ((Acc<40>*)acc)->v;
    const uint64_t db3 = mkdesc(sbase + 16384, 128, 1024, 0);
#pragma unroll 1
    for (int i = 0; i < 11; i++) {
      mbar_wait(full3 + 8 * (i & 3), (i >> 2) & 1);
      if (i == 0 && tid == 0) STAMP(4, 2);
      const uint64_t da = da0 + (i & 3) * 2304, db = db3 + (i & 3) * 2304;
      WG_FENCE();
#pragma unroll
      for (int k = 0; k < 4; k++) wgmma_ss_n160(acc, da + k * 256, db + k * 16, (i | k) != 0);
      WG_COMMIT();
      if (i > 0) {
        WG_WAIT(1);
        if ((tid & 127) < 2) mbar_arrive_cta(empty3 + 8 * ((i - 1) & 3), tid & 1);
      }
    }
    const int g = lane >> 2, c = lane & 3, row = m3 * 128 + warp * 16 + g;
    const uint8_t* himg = (const uint8_t*)g_h + (size_t)m3 * 163840 + warp * 256 + lane * 4;
    uint32_t rv[20];
    const float mu0 = __ldcg(&g_hmean[row]), mu1 = __ldcg(&g_hmean[row + 8]);
    float r0 = __ldcg(&g_hpart[c * 2 * S_ + row]) + __ldcg(&g_hpart[(c * 2 + 1) * S_ + row]);
    float r1 = __ldcg(&g_hpart[c * 2 * S_ + row + 8]) + __ldcg(&g_hpart[(c * 2 + 1) * S_ + row + 8]);
#pragma unroll
    for (int j = 0; j < 10; j++) {
      rv[2 * j] = __ldcg((const uint32_t*)(himg + img_off(n3 * 10 + j)));
      rv[2 * j + 1] = __ldcg((const uint32_t*)(himg + img_off(n3 * 10 + j) + 128));
    }
    const uint32_t rx = mapa(sbase + K4_XCH + tid * 16, rank ^ 1), rb = mapa(xchb, rank ^ 1);
    WG_WAIT(0);
    fence_regs(acc);
    if ((tid & 127) < 2) mbar_arrive_cta(empty3 + 16, tid & 1);
    if (tid == 0) STAMP(4, 1);
#pragma unroll
    for (int i = 11; i < 16; i++) {
      mbar_wait(full3 + 8 * (i & 3), (i >> 2) & 1);
      const uint64_t da = da0 + (i & 3) * 2304, db = db3 + (i & 3) * 2304;
      WG_FENCE();
#pragma unroll
      for (int k = 0; k < 4; k++) wgmma_ss_n80(keep, da + k * 256, db + k * 16, 1);
      WG_COMMIT();
      if (i == 12) {
        WG_WAIT(1);
        if ((tid & 127) < 2) mbar_arrive_cta(empty3 + 24, tid & 1);
      }
#pragma unroll
      for (int j = (i - 11) * 3; j < (i - 11) * 3 + 3; j++)
        if (j < 10) st_async4(rx + j * 4096, acc[40 + 4 * j], acc[41 + 4 * j], acc[42 + 4 * j], acc[43 + 4 * j], rb);
    }
    cluster_arrive();
    bar_sync(8, 256 + 32);
    r0 += __shfl_xor_sync(~0u, r0, 1); r1 += __shfl_xor_sync(~0u, r1, 1);
    r0 += __shfl_xor_sync(~0u, r0, 2); r1 += __shfl_xor_sync(~0u, r1, 2);
    r0 = rcp(r0 * (1.f / D_) + 1e-5f); r1 = rcp(r1 * (1.f / D_) + 1e-5f);
    asm volatile("" : "+f"(r0), "+f"(r1)::"memory");
    WG_WAIT(0);
    fence_regs(keep);
    if (tid == 0) STAMP(4, 3);
    mbar_wait(xchb, 0);
    if (tid == 0) STAMP(4, 5);
    uint8_t* sp = sm + K4_STG + (warp * 16 + g) * 160 + c * 4;
#pragma unroll
    for (int j = 0; j < 10; j++) {
      const float4 p = *(const float4*)(sm + K4_XCH + tid * 16 + j * 4096);
      *(uint32_t*)(sp + j * 16) = pack_bf16(fmaf(keep[4 * j] + p.x, r0, bf_lo(rv[2 * j]) + mu0), fmaf(keep[4 * j + 1] + p.y, r0, bf_hi(rv[2 * j]) + mu0));
      *(uint32_t*)(sp + 1280 + j * 16) = pack_bf16(fmaf(keep[4 * j + 2] + p.z, r1, bf_lo(rv[2 * j + 1]) + mu1), fmaf(keep[4 * j + 3] + p.w, r1, bf_hi(rv[2 * j + 1]) + mu1));
    }
    fence_async();
    bar_sync(1 + wg, 128);
    if ((tid & 127) == 0) {
      tma2d_st(&tmo, n3 * 80, m3 * 128 + wg * 64, sbase + K4_STG + wg * 10240);
      bulk_commit_wait();
    }
    __syncwarp();
    if (tid == 0) STAMP(4, 4);
    asm volatile("barrier.cluster.wait.aligned; // consumers" ::: "memory");
  }
}

typedef CUresult (*EncodeFn)(CUtensorMap*, CUtensorMapDataType, cuuint32_t, void*, const cuuint64_t*, const cuuint64_t*,
                             const cuuint32_t*, const cuuint32_t*, CUtensorMapInterleave, CUtensorMapSwizzle,
                             CUtensorMapL2promotion, CUtensorMapFloatOOBfill);

static CUtensorMap make_map(EncodeFn enc, const void* p, uint64_t inner, uint64_t outer, uint32_t box_inner,
                            uint32_t box_outer, CUtensorMapSwizzle swz) {
  CUtensorMap m;
  cuuint64_t gd[2] = {inner, outer};
  cuuint64_t gs[1] = {inner * 2};
  cuuint32_t bd[2] = {box_inner, box_outer};
  cuuint32_t es[2] = {1, 1};
  enc(&m, CU_TENSOR_MAP_DATA_TYPE_BFLOAT16, 2, (void*)p, gd, gs, bd, es, CU_TENSOR_MAP_INTERLEAVE_NONE, swz,
      CU_TENSOR_MAP_L2_PROMOTION_L2_256B, CU_TENSOR_MAP_FLOAT_OOB_FILL_NONE);
  return m;
}

static CUtensorMap make_map_img(EncodeFn enc, const void* p, uint64_t k, uint64_t n, uint32_t rows, uint32_t chunks,
                                uint32_t groups) {
  CUtensorMap m;
  cuuint64_t gd[4] = {8, rows, n / 8, k / rows};
  cuuint64_t gs[3] = {n * 2, 16, n * 2 * rows};
  cuuint32_t bd[4] = {8, rows, chunks, groups};
  cuuint32_t es[4] = {1, 1, 1, 1};
  enc(&m, CU_TENSOR_MAP_DATA_TYPE_BFLOAT16, 4, (void*)p, gd, gs, bd, es, CU_TENSOR_MAP_INTERLEAVE_NONE,
      CU_TENSOR_MAP_SWIZZLE_NONE, CU_TENSOR_MAP_L2_PROMOTION_L2_128B, CU_TENSOR_MAP_FLOAT_OOB_FILL_NONE);
  return m;
}

template <typename... KArgs, typename... Args>
static void launch(void (*k)(KArgs...), int grid, int threads, int smem, bool pdl, Args... args) {
  cudaLaunchConfig_t cfg = {};
  cfg.gridDim = dim3(grid);
  cfg.blockDim = dim3(threads);
  cfg.dynamicSmemBytes = smem;
  cfg.stream = cudaStreamPerThread;
  cudaLaunchAttribute at[1];
  at[0].id = cudaLaunchAttributeProgrammaticStreamSerialization;
  at[0].val.programmaticStreamSerializationAllowed = 1;
  cfg.attrs = at;
  cfg.numAttrs = pdl ? 1 : 0;
  cudaLaunchKernelEx(&cfg, k, KArgs(args)...);
}

extern "C" void kernel_launch(void* const* d_in, const int* in_sizes, int n_in, void* d_out, int out_size) {
  const bf16* x = (const bf16*)d_in[0];
  const bf16* wqkv = (const bf16*)d_in[1];
  const bf16* wo = (const bf16*)d_in[2];
  const bf16* wg = (const bf16*)d_in[4];
  const bf16* wu = (const bf16*)d_in[5];
  const bf16* wd = (const bf16*)d_in[6];

  static EncodeFn enc = nullptr;
  static void *p_o, *p_wo;
  if (!enc) {
    void* fn = nullptr;
    cudaDriverEntryPointQueryResult qr;
    cudaGetDriverEntryPoint("cuTensorMapEncodeTiled", &fn, cudaEnableDefault, &qr);
    enc = (EncodeFn)fn;
    cudaGetSymbolAddress(&p_o, g_o);
    cudaGetSymbolAddress(&p_wo, g_wo);
    cudaFuncSetAttribute(k1_qkv, cudaFuncAttributeMaxDynamicSharedMemorySize, K1_SMEM);
    cudaFuncSetAttribute(k2_attn, cudaFuncAttributeMaxDynamicSharedMemorySize, K2_SMEM);
    cudaFuncSetAttribute(k3_proj<3, 4, true>, cudaFuncAttributeMaxDynamicSharedMemorySize, K3_SMEM);
    cudaFuncSetAttribute(k45_ffn, cudaFuncAttributeMaxDynamicSharedMemorySize, K4_SMEM);
  }
  const CUtensorMap tmx = make_map(enc, x, D_, S_, 64, 96, CU_TENSOR_MAP_SWIZZLE_128B);
  const CUtensorMap tmw = make_map(enc, wqkv, 3 * D_, D_, 32, 64, CU_TENSOR_MAP_SWIZZLE_64B);
  const CUtensorMap tmxr = make_map(enc, x, D_, S_, 80, 64, CU_TENSOR_MAP_SWIZZLE_NONE);
  Maps5 maps;
  maps.m[0] = make_map_img(enc, wg, D_, F_, 16, 14, 2); maps.m[1] = make_map_img(enc, wu, D_, F_, 16, 14, 2);
  maps.m[2] = make_map_img(enc, wg, D_, F_, 16, 13, 2); maps.m[3] = make_map_img(enc, wu, D_, F_, 16, 13, 2);
  maps.m[4] = make_map_img(enc, wd, F_, D_, 64, 10, 1);
  const CUtensorMap tmout = make_map(enc, d_out, D_, S_, 80, 64, CU_TENSOR_MAP_SWIZZLE_NONE);

  launch(k1_qkv, 132, 512, K1_SMEM, false, tmx, tmw, x, wqkv, wo);
  launch(k2_attn, 128, 512, K2_SMEM, true, maps, 0x007f007fu);
  launch(k3_proj<3, 4, true>, 128, 384, K3_SMEM, true, tmxr, (const uint4*)p_o, (const uint4*)p_wo);
  launch(k45_ffn, 128, 384, K4_SMEM, true, tmout);
}
```

```cpp
#include <cuda_runtime.h>
#include <cuda_bf16.h>
#include <cuda.h>
#include <stdint.h>

typedef __nv_bfloat16 bf16;

constexpr int S_ = 2048, D_ = 640, F_ = 1728;
constexpr int HEAD_IMG = 98304;
#define PMASK 0xDB6D
constexpr uint32_t POLY_MASK = PMASK;
constexpr float QSCALE = 0.22360679774997896f * 1.4426950408889634f;

__device__ __align__(1024) uint4 g_qkv[96 * HEAD_IMG / 16];
__device__ __align__(1024) uint4 g_o[S_ * D_ / 8];
__device__ __align__(1024) uint4 g_h[S_ * D_ / 8];
__device__ __align__(1024) uint4 g_hh[S_ * F_ / 8];
__device__ __align__(1024) uint4 g_wo[D_ * D_ / 8];
__device__ __align__(1024) uint4 g_wgu[2 * D_ * F_ / 8];
__device__ __align__(1024) uint4 g_wd[F_ * D_ / 8];
__device__ uint4 g_rowstat[S_];
__device__ uint4 g_cpart[10 * 12 * 80];
__device__ float g_nrm[64 * 128];
__device__ uint4 g_wm[D_];
__device__ float g_hmean[S_];
__device__ float g_hpart[8 * S_];
__device__ uint4 g_flag[2 * 16 * 2];
__device__ unsigned g_epoch;

#define STAMP(k, i)
__device__ __forceinline__ uint32_t smem_u32(const void* p) { return (uint32_t)__cvta_generic_to_shared(p); }
__device__ __forceinline__ void mbar_init(uint32_t a, uint32_t c) {
  asm volatile("mbarrier.init.shared::cta.b64 [%0], %1;" ::"r"(a), "r"(c) : "memory");
}
__device__ __forceinline__ void mbar_expect(uint32_t a, uint32_t bytes) {
  asm volatile("mbarrier.arrive.expect_tx.shared::cta.b64 _, [%0], %1;" ::"r"(a), "r"(bytes) : "memory");
}
__device__ __forceinline__ void mbar_arrive(uint32_t a) {
  asm volatile("mbarrier.arrive.shared::cta.b64 _, [%0];" ::"r"(a) : "memory");
}
__device__ __forceinline__ void mbar_arrive_cta(uint32_t a, uint32_t cta) {
  asm volatile("{\n.reg .b32 r;\nmapa.shared::cluster.u32 r, %0, %1;\n"
               "mbarrier.arrive.shared::cluster.b64 _, [r];\n}" ::"r"(a), "r"(cta) : "memory");
}
__device__ __forceinline__ bool mbar_try(uint32_t a, uint32_t ph) {
  uint32_t ok;
  asm volatile("{\n.reg .pred p;\nmbarrier.try_wait.parity.shared::cta.b64 p, [%1], %2;\nselp.u32 %0, 1, 0, p;\n}"
               : "=r"(ok) : "r"(a), "r"(ph) : "memory");
  return ok;
}
__device__ __noinline__ void wait_timeout() { __trap(); }
__device__ __forceinline__ void mbar_wait(uint32_t a, uint32_t ph) {
  if (mbar_try(a, ph)) return;
  uint32_t it = 0;
  while (!mbar_try(a, ph)) if (++it > (1u << 22)) wait_timeout();
}
__device__ __forceinline__ void tma2d(uint32_t dst, const CUtensorMap* m, int c0, int c1, uint32_t bar) {
  asm volatile("cp.async.bulk.tensor.2d.shared::cluster.global.mbarrier::complete_tx::bytes [%0], [%1, {%3, %4}], [%2];"
               ::"r"(dst), "l"(m), "r"(bar), "r"(c0), "r"(c1) : "memory");
}
__device__ __forceinline__ void tma2d_mc(uint32_t dst, const CUtensorMap* m, int c0, int c1, uint32_t bar) {
  asm volatile("cp.async.bulk.tensor.2d.shared::cluster.global.mbarrier::complete_tx::bytes.multicast::cluster "
               "[%0], [%1, {%3, %4}], [%2], %5;"
               ::"r"(dst), "l"(m), "r"(bar), "r"(c0), "r"(c1), "h"((uint16_t)3) : "memory");
}
__device__ __forceinline__ void bulk_ld(uint32_t dst, const void* src, uint32_t bytes, uint32_t bar) {
  asm volatile("cp.async.bulk.shared::cluster.global.mbarrier::complete_tx::bytes [%0], [%1], %2, [%3];"
               ::"r"(dst), "l"(src), "r"(bytes), "r"(bar) : "memory");
}
__device__ __forceinline__ void bulk_ld_mc(uint32_t dst, const void* src, uint32_t bytes, uint32_t bar) {
  asm volatile("cp.async.bulk.shared::cluster.global.mbarrier::complete_tx::bytes.multicast::cluster "
               "[%0], [%1], %2, [%3], %4;"
               ::"r"(dst), "l"(src), "r"(bytes), "r"(bar), "h"((uint16_t)3) : "memory");
}
__device__ __forceinline__ void cluster_arrive() { asm volatile("barrier.cluster.arrive.relaxed.aligned;" ::: "memory"); }
__device__ __forceinline__ void cluster_wait() { asm volatile("barrier.cluster.wait.aligned;" ::: "memory"); }
__device__ __forceinline__ void bulk_st(void* dst, uint32_t src, uint32_t bytes) {
  asm volatile("cp.async.bulk.global.shared::cta.bulk_group [%0], [%1], %2;" ::"l"(dst), "r"(src), "r"(bytes) : "memory");
}
__device__ __forceinline__ void tma2d_st(const CUtensorMap* m, int c0, int c1, uint32_t src) {
  asm volatile("cp.async.bulk.tensor.2d.global.shared::cta.bulk_group [%0, {%2, %3}], [%1];"
               ::"l"(m), "r"(src), "r"(c0), "r"(c1) : "memory");
}
__device__ __forceinline__ void bulk_commit_wait() {
  asm volatile("cp.async.bulk.commit_group;\ncp.async.bulk.wait_group.read 0;" ::: "memory");
}
__device__ __forceinline__ uint32_t mapa(uint32_t a, uint32_t cta) {
  uint32_t r;
  asm("mapa.shared::cluster.u32 %0, %1, %2;" : "=r"(r) : "r"(a), "r"(cta));
  return r;
}
__device__ __forceinline__ void st_async4(uint32_t dst, float a, float b, float c, float d, uint32_t bar) {
  asm volatile("st.async.shared::cluster.mbarrier::complete_tx::bytes.v4.f32 [%0], {%1, %2, %3, %4}, [%5];"
               ::"r"(dst), "f"(a), "f"(b), "f"(c), "f"(d), "r"(bar) : "memory");
}
__device__ __forceinline__ void fence_async() { asm volatile("fence.proxy.async.shared::cta;" ::: "memory"); }
__device__ __forceinline__ void prefetch_map(const CUtensorMap* m) {
  asm volatile("prefetch.tensormap [%0];" ::"l"(m) : "memory");
}
__device__ __forceinline__ bool elect_one() {
  uint32_t p;
  asm volatile("{\n.reg .pred q;\nelect.sync _|q, 0xffffffff;\nselp.u32 %0, 1, 0, q;\n}" : "=r"(p));
  return p;
}
__device__ __forceinline__ void pdl_wait() { asm volatile("griddepcontrol.wait;" ::: "memory"); }
__device__ __forceinline__ void pdl_trigger() { asm volatile("griddepcontrol.launch_dependents;" ::: "memory"); }
__device__ __forceinline__ void bar_sync(int id, int n) { asm volatile("bar.sync %0, %1;" ::"r"(id), "r"(n) : "memory"); }
__device__ __forceinline__ void bar_arrive(int id, int n) { asm volatile("bar.arrive %0, %1;" ::"r"(id), "r"(n) : "memory"); }
#define WG_FENCE() asm volatile("wgmma.fence.sync.aligned;" ::: "memory")
#define WG_COMMIT() asm volatile("wgmma.commit_group.sync.aligned;" ::: "memory")
#define WG_WAIT(n) asm volatile("wgmma.wait_group.sync.aligned %0;" ::"n"(n) : "memory")
__device__ __forceinline__ uint64_t mkdesc(uint32_t addr, uint32_t lbo, uint32_t sbo, uint32_t sw) {
  return (uint64_t)((addr & 0x3FFFF) >> 4) | ((uint64_t)(lbo >> 4) << 16) | ((uint64_t)(sbo >> 4) << 32) |
         ((uint64_t)sw << 62);
}
template <int N> __device__ __forceinline__ void fence_regs(float (&r)[N]) {
#pragma unroll
  for (int i = 0; i < N; i++) asm volatile("" : "+f"(r[i])::"memory");
}
__device__ __forceinline__ uint32_t pack_bf16(float lo, float hi) {
  uint32_t r;
  asm("cvt.rn.bf16x2.f32 %0, %1, %2;" : "=r"(r) : "f"(hi), "f"(lo));
  return r;
}
__device__ __forceinline__ float bf_lo(uint32_t v) { return __uint_as_float(v << 16); }
__device__ __forceinline__ float bf_hi(uint32_t v) { return __uint_as_float(v & 0xffff0000u); }
__device__ __forceinline__ float ex2(float x) {
  float y;
  asm("ex2.approx.ftz.f32 %0, %1;" : "=f"(y) : "f"(x));
  return y;
}
__device__ __forceinline__ uint4 ldg_nc(const void* p) {
  uint4 v;
  asm volatile("ld.global.nc.L1::no_allocate.v4.u32 {%0, %1, %2, %3}, [%4];"
               : "=r"(v.x), "=r"(v.y), "=r"(v.z), "=r"(v.w) : "l"(p));
  return v;
}

__device__ __forceinline__ uint4 ld_relaxed(const uint4* p) {
  uint64_t a, b;
  asm volatile("ld.relaxed.gpu.global.v2.u64 {%0, %1}, [%2];" : "=l"(a), "=l"(b) : "l"(p) : "memory");
  return make_uint4((uint32_t)a, (uint32_t)(a >> 32), (uint32_t)b, (uint32_t)(b >> 32));
}
__device__ __forceinline__ void st_relaxed(uint4* p, float x, float y, uint32_t tag) {
  const uint64_t a = ((uint64_t)tag << 32) | __float_as_uint(x), b = ((uint64_t)tag << 32) | __float_as_uint(y);
  asm volatile("st.relaxed.gpu.global.v2.u64 [%0], {%1, %2};" ::"l"(p), "l"(a), "l"(b) : "memory");
}
__device__ __forceinline__ void tma4d(uint32_t dst, const CUtensorMap* m, int c2, int c3, uint32_t bar) {
  asm volatile("cp.async.bulk.tensor.4d.shared::cluster.global.mbarrier::complete_tx::bytes [%0], [%1, {%3, %3, %4, %5}], [%2];"
               ::"r"(dst), "l"(m), "r"(bar), "r"(0), "r"(c2), "r"(c3) : "memory");
}
#define ACC8(a, v) do { a[0] += bf_lo(v.x); a[1] += bf_hi(v.x); a[2] += bf_lo(v.y); a[3] += bf_hi(v.y); \
                        a[4] += bf_lo(v.z); a[5] += bf_hi(v.z); a[6] += bf_lo(v.w); a[7] += bf_hi(v.w); } while (0)

__device__ __forceinline__ void wgmma_ss_n224(float (&d)[112], uint64_t da, uint64_t db, int sd) {
  asm volatile("{\n.reg .pred p;\nsetp.ne.b32 p, %114, 0;\n"
      "wgmma.mma_async.sync.aligned.m64n224k16.f32.bf16.bf16 {"
      "%0, %1, %2, %3, %4, %5, %6, %7, %8, %9, %10, %11, %12, %13, %14, %15, "
      "%16, %17, %18, %19, %20, %21, %22, %23, %24, %25, %26, %27, %28, %29, %30, %31, "
      "%32, %33, %34, %35, %36, %37, %38, %39, %40, %41, %42, %43, %44, %45, %46, %47, "
      "%48, %49, %50, %51, %52, %53, %54, %55, %56, %57, %58, %59, %60, %61, %62, %63, "
      "%64, %65, %66, %67, %68, %69, %70, %71, %72, %73, %74, %75, %76, %77, %78, %79, "
      "%80, %81, %82, %83, %84, %85, %86, %87, %88, %89, %90, %91, %92, %93, %94, %95, "
      "%96, %97, %98, %99, %100, %101, %102, %103, %104, %105, %106, %107, %108, %109, %110, %111"
      "}, %112, %113, p, 1, 1, 0, 1;\n}\n"
    : "+f"(d[0]), "+f"(d[1]), "+f"(d[2]), "+f"(d[3]), "+f"(d[4]), "+f"(d[5]), "+f"(d[6]), "+f"(d[7]),
      "+f"(d[8]), "+f"(d[9]), "+f"(d[10]), "+f"(d[11]), "+f"(d[12]), "+f"(d[13]), "+f"(d[14]), "+f"(d[15]),
      "+f"(d[16]), "+f"(d[17]), "+f"(d[18]), "+f"(d[19]), "+f"(d[20]), "+f"(d[21]), "+f"(d[22]), "+f"(d[23]),
      "+f"(d[24]), "+f"(d[25]), "+f"(d[26]), "+f"(d[27]), "+f"(d[28]), "+f"(d[29]), "+f"(d[30]), "+f"(d[31]),
      "+f"(d[32]), "+f"(d[33]), "+f"(d[34]), "+f"(d[35]), "+f"(d[36]), "+f"(d[37]), "+f"(d[38]), "+f"(d[39]),
      "+f"(d[40]), "+f"(d[41]), "+f"(d[42]), "+f"(d[43]), "+f"(d[44]), "+f"(d[45]), "+f"(d[46]), "+f"(d[47]),
      "+f"(d[48]), "+f"(d[49]), "+f"(d[50]), "+f"(d[51]), "+f"(d[52]), "+f"(d[53]), "+f"(d[54]), "+f"(d[55]),
      "+f"(d[56]), "+f"(d[57]), "+f"(d[58]), "+f"(d[59]), "+f"(d[60]), "+f"(d[61]), "+f"(d[62]), "+f"(d[63]),
      "+f"(d[64]), "+f"(d[65]), "+f"(d[66]), "+f"(d[67]), "+f"(d[68]), "+f"(d[69]), "+f"(d[70]), "+f"(d[71]),
      "+f"(d[72]), "+f"(d[73]), "+f"(d[74]), "+f"(d[75]), "+f"(d[76]), "+f"(d[77]), "+f"(d[78]), "+f"(d[79]),
      "+f"(d[80]), "+f"(d[81]), "+f"(d[82]), "+f"(d[83]), "+f"(d[84]), "+f"(d[85]), "+f"(d[86]), "+f"(d[87]),
      "+f"(d[88]), "+f"(d[89]), "+f"(d[90]), "+f"(d[91]), "+f"(d[92]), "+f"(d[93]), "+f"(d[94]), "+f"(d[95]),
      "+f"(d[96]), "+f"(d[97]), "+f"(d[98]), "+f"(d[99]), "+f"(d[100]), "+f"(d[101]), "+f"(d[102]), "+f"(d[103]),
      "+f"(d[104]), "+f"(d[105]), "+f"(d[106]), "+f"(d[107]), "+f"(d[108]), "+f"(d[109]), "+f"(d[110]), "+f"(d[111])
    : "l"(da), "l"(db), "r"(sd));
}
__device__ __forceinline__ void wgmma_ss_n208(float (&d)[104], uint64_t da, uint64_t db, int sd) {
  asm volatile("{\n.reg .pred p;\nsetp.ne.b32 p, %106, 0;\n"
      "wgmma.mma_async.sync.aligned.m64n208k16.f32.bf16.bf16 {"
      "%0, %1, %2, %3, %4, %5, %6, %7, %8, %9, %10, %11, %12, %13, %14, %15, "
      "%16, %17, %18, %19, %20, %21, %22, %23, %24, %25, %26, %27, %28, %29, %30, %31, "
      "%32, %33, %34, %35, %36, %37, %38, %39, %40, %41, %42, %43, %44, %45, %46, %47, "
      "%48, %49, %50, %51, %52, %53, %54, %55, %56, %57, %58, %59, %60, %61, %62, %63, "
      "%64, %65, %66, %67, %68, %69, %70, %71, %72, %73, %74, %75, %76, %77, %78, %79, "
      "%80, %81, %82, %83, %84, %85, %86, %87, %88, %89, %90, %91, %92, %93, %94, %95, "
      "%96, %97, %98, %99, %100, %101, %102, %103"
      "}, %104, %105, p, 1, 1, 0, 1;\n}\n"
    : "+f"(d[0]), "+f"(d[1]), "+f"(d[2]), "+f"(d[3]), "+f"(d[4]), "+f"(d[5]), "+f"(d[6]), "+f"(d[7]),
      "+f"(d[8]), "+f"(d[9]), "+f"(d[10]), "+f"(d[11]), "+f"(d[12]), "+f"(d[13]), "+f"(d[14]), "+f"(d[15]),
      "+f"(d[16]), "+f"(d[17]), "+f"(d[18]), "+f"(d[19]), "+f"(d[20]), "+f"(d[21]), "+f"(d[22]), "+f"(d[23]),
      "+f"(d[24]), "+f"(d[25]), "+f"(d[26]), "+f"(d[27]), "+f"(d[28]), "+f"(d[29]), "+f"(d[30]), "+f"(d[31]),
      "+f"(d[32]), "+f"(d[33]), "+f"(d[34]), "+f"(d[35]), "+f"(d[36]), "+f"(d[37]), "+f"(d[38]), "+f"(d[39]),
      "+f"(d[40]), "+f"(d[41]), "+f"(d[42]), "+f"(d[43]), "+f"(d[44]), "+f"(d[45]), "+f"(d[46]), "+f"(d[47]),
      "+f"(d[48]), "+f"(d[49]), "+f"(d[50]), "+f"(d[51]), "+f"(d[52]), "+f"(d[53]), "+f"(d[54]), "+f"(d[55]),
      "+f"(d[56]), "+f"(d[57]), "+f"(d[58]), "+f"(d[59]), "+f"(d[60]), "+f"(d[61]), "+f"(d[62]), "+f"(d[63]),
      "+f"(d[64]), "+f"(d[65]), "+f"(d[66]), "+f"(d[67]), "+f"(d[68]), "+f"(d[69]), "+f"(d[70]), "+f"(d[71]),
      "+f"(d[72]), "+f"(d[73]), "+f"(d[74]), "+f"(d[75]), "+f"(d[76]), "+f"(d[77]), "+f"(d[78]), "+f"(d[79]),
      "+f"(d[80]), "+f"(d[81]), "+f"(d[82]), "+f"(d[83]), "+f"(d[84]), "+f"(d[85]), "+f"(d[86]), "+f"(d[87]),
      "+f"(d[88]), "+f"(d[89]), "+f"(d[90]), "+f"(d[91]), "+f"(d[92]), "+f"(d[93]), "+f"(d[94]), "+f"(d[95]),
      "+f"(d[96]), "+f"(d[97]), "+f"(d[98]), "+f"(d[99]), "+f"(d[100]), "+f"(d[101]), "+f"(d[102]), "+f"(d[103])
    : "l"(da), "l"(db), "r"(sd));
}
__device__ __forceinline__ void wgmma_ss_n168(float (&d)[84], uint64_t da, uint64_t db, int sd) {
  asm volatile("{\n.reg .pred p;\nsetp.ne.b32 p, %86, 0;\n"
      "wgmma.mma_async.sync.aligned.m64n168k16.f32.bf16.bf16 {"
      "%0, %1, %2, %3, %4, %5, %6, %7, %8, %9, %10, %11, %12, %13, %14, %15, "
      "%16, %17, %18, %19, %20, %21, %22, %23, %24, %25, %26, %27, %28, %29, %30, %31, "
      "%32, %33, %34, %35, %36, %37, %38, %39, %40, %41, %42, %43, %44, %45, %46, %47, "
      "%48, %49, %50, %51, %52, %53, %54, %55, %56, %57, %58, %59, %60, %61, %62, %63, "
      "%64, %65, %66, %67, %68, %69, %70, %71, %72, %73, %74, %75, %76, %77, %78, %79, "
      "%80, %81, %82, %83"
      "}, %84, %85, p, 1, 1, 0, 1;\n}\n"
    : "+f"(d[0]), "+f"(d[1]), "+f"(d[2]), "+f"(d[3]), "+f"(d[4]), "+f"(d[5]), "+f"(d[6]), "+f"(d[7]),
      "+f"(d[8]), "+f"(d[9]), "+f"(d[10]), "+f"(d[11]), "+f"(d[12]), "+f"(d[13]), "+f"(d[14]), "+f"(d[15]),
      "+f"(d[16]), "+f"(d[17]), "+f"(d[18]), "+f"(d[19]), "+f"(d[20]), "+f"(d[21]), "+f"(d[22]), "+f"(d[23]),
      "+f"(d[24]), "+f"(d[25]), "+f"(d[26]), "+f"(d[27]), "+f"(d[28]), "+f"(d[29]), "+f"(d[30]), "+f"(d[31]),
      "+f"(d[32]), "+f"(d[33]), "+f"(d[34]), "+f"(d[35]), "+f"(d[36]), "+f"(d[37]), "+f"(d[38]), "+f"(d[39]),
      "+f"(d[40]), "+f"(d[41]), "+f"(d[42]), "+f"(d[43]), "+f"(d[44]), "+f"(d[45]), "+f"(d[46]), "+f"(d[47]),
      "+f"(d[48]), "+f"(d[49]), "+f"(d[50]), "+f"(d[51]), "+f"(d[52]), "+f"(d[53]), "+f"(d[54]), "+f"(d[55]),
      "+f"(d[56]), "+f"(d[57]), "+f"(d[58]), "+f"(d[59]), "+f"(d[60]), "+f"(d[61]), "+f"(d[62]), "+f"(d[63]),
      "+f"(d[64]), "+f"(d[65]), "+f"(d[66]), "+f"(d[67]), "+f"(d[68]), "+f"(d[69]), "+f"(d[70]), "+f"(d[71]),
      "+f"(d[72]), "+f"(d[73]), "+f"(d[74]), "+f"(d[75]), "+f"(d[76]), "+f"(d[77]), "+f"(d[78]), "+f"(d[79]),
      "+f"(d[80]), "+f"(d[81]), "+f"(d[82]), "+f"(d[83])
    : "l"(da), "l"(db), "r"(sd));
}
__device__ __forceinline__ void wgmma_ss_n160(float (&d)[80], uint64_t da, uint64_t db, int sd) {
  asm volatile("{\n.reg .pred p;\nsetp.ne.b32 p, %82, 0;\n"
      "wgmma.mma_async.sync.aligned.m64n160k16.f32.bf16.bf16 {"
      "%0, %1, %2, %3, %4, %5, %6, %7, %8, %9, %10, %11, %12, %13, %14, %15, "
      "%16, %17, %18, %19, %20, %21, %22, %23, %24, %25, %26, %27, %28, %29, %30, %31, "
      "%32, %33, %34, %35, %36, %37, %38, %39, %40, %41, %42, %43, %44, %45, %46, %47, "
      "%48, %49, %50, %51, %52, %53, %54, %55, %56, %57, %58, %59, %60, %61, %62, %63, "
      "%64, %65, %66, %67, %68, %69, %70, %71, %72, %73, %74, %75, %76, %77, %78, %79"
      "}, %80, %81, p, 1, 1, 0, 1;\n}\n"
    : "+f"(d[0]), "+f"(d[1]), "+f"(d[2]), "+f"(d[3]), "+f"(d[4]), "+f"(d[5]), "+f"(d[6]), "+f"(d[7]),
      "+f"(d[8]), "+f"(d[9]), "+f"(d[10]), "+f"(d[11]), "+f"(d[12]), "+f"(d[13]), "+f"(d[14]), "+f"(d[15]),
      "+f"(d[16]), "+f"(d[17]), "+f"(d[18]), "+f"(d[19]), "+f"(d[20]), "+f"(d[21]), "+f"(d[22]), "+f"(d[23]),
      "+f"(d[24]), "+f"(d[25]), "+f"(d[26]), "+f"(d[27]), "+f"(d[28]), "+f"(d[29]), "+f"(d[30]), "+f"(d[31]),
      "+f"(d[32]), "+f"(d[33]), "+f"(d[34]), "+f"(d[35]), "+f"(d[36]), "+f"(d[37]), "+f"(d[38]), "+f"(d[39]),
      "+f"(d[40]), "+f"(d[41]), "+f"(d[42]), "+f"(d[43]), "+f"(d[44]), "+f"(d[45]), "+f"(d[46]), "+f"(d[47]),
      "+f"(d[48]), "+f"(d[49]), "+f"(d[50]), "+f"(d[51]), "+f"(d[52]), "+f"(d[53]), "+f"(d[54]), "+f"(d[55]),
      "+f"(d[56]), "+f"(d[57]), "+f"(d[58]), "+f"(d[59]), "+f"(d[60]), "+f"(d[61]), "+f"(d[62]), "+f"(d[63]),
      "+f"(d[64]), "+f"(d[65]), "+f"(d[66]), "+f"(d[67]), "+f"(d[68]), "+f"(d[69]), "+f"(d[70]), "+f"(d[71]),
      "+f"(d[72]), "+f"(d[73]), "+f"(d[74]), "+f"(d[75]), "+f"(d[76]), "+f"(d[77]), "+f"(d[78]), "+f"(d[79])
    : "l"(da), "l"(db), "r"(sd));
}
__device__ __forceinline__ void wgmma_ss_n88(float (&d)[44], uint64_t da, uint64_t db, int sd) {
  asm volatile("{\n.reg .pred p;\nsetp.ne.b32 p, %46, 0;\n"
      "wgmma.mma_async.sync.aligned.m64n88k16.f32.bf16.bf16 {"
      "%0, %1, %2, %3, %4, %5, %6, %7, %8, %9, %10, %11, %12, %13, %14, %15, "
      "%16, %17, %18, %19, %20, %21, %22, %23, %24, %25, %26, %27, %28, %29, %30, %31, "
      "%32, %33, %34, %35, %36, %37, %38, %39, %40, %41, %42, %43"
      "}, %44, %45, p, 1, 1, 0, 1;\n}\n"
    : "+f"(d[0]), "+f"(d[1]), "+f"(d[2]), "+f"(d[3]), "+f"(d[4]), "+f"(d[5]), "+f"(d[6]), "+f"(d[7]),
      "+f"(d[8]), "+f"(d[9]), "+f"(d[10]), "+f"(d[11]), "+f"(d[12]), "+f"(d[13]), "+f"(d[14]), "+f"(d[15]),
      "+f"(d[16]), "+f"(d[17]), "+f"(d[18]), "+f"(d[19]), "+f"(d[20]), "+f"(d[21]), "+f"(d[22]), "+f"(d[23]),
      "+f"(d[24]), "+f"(d[25]), "+f"(d[26]), "+f"(d[27]), "+f"(d[28]), "+f"(d[29]), "+f"(d[30]), "+f"(d[31]),
      "+f"(d[32]), "+f"(d[33]), "+f"(d[34]), "+f"(d[35]), "+f"(d[36]), "+f"(d[37]), "+f"(d[38]), "+f"(d[39]),
      "+f"(d[40]), "+f"(d[41]), "+f"(d[42]), "+f"(d[43])
    : "l"(da), "l"(db), "r"(sd));
}
__device__ __forceinline__ void wgmma_ss_n80(float (&d)[40], uint64_t da, uint64_t db, int sd) {
  asm volatile("{\n.reg .pred p;\nsetp.ne.b32 p, %42, 0;\n"
      "wgmma.mma_async.sync.aligned.m64n80k16.f32.bf16.bf16 {"
      "%0, %1, %2, %3, %4, %5, %6, %7, %8, %9, %10, %11, %12, %13, %14, %15, "
      "%16, %17, %18, %19, %20, %21, %22, %23, %24, %25, %26, %27, %28, %29, %30, %31, "
      "%32, %33, %34, %35, %36, %37, %38, %39"
      "}, %40, %41, p, 1, 1, 0, 1;\n}\n"
    : "+f"(d[0]), "+f"(d[1]), "+f"(d[2]), "+f"(d[3]), "+f"(d[4]), "+f"(d[5]), "+f"(d[6]), "+f"(d[7]),
      "+f"(d[8]), "+f"(d[9]), "+f"(d[10]), "+f"(d[11]), "+f"(d[12]), "+f"(d[13]), "+f"(d[14]), "+f"(d[15]),
      "+f"(d[16]), "+f"(d[17]), "+f"(d[18]), "+f"(d[19]), "+f"(d[20]), "+f"(d[21]), "+f"(d[22]), "+f"(d[23]),
      "+f"(d[24]), "+f"(d[25]), "+f"(d[26]), "+f"(d[27]), "+f"(d[28]), "+f"(d[29]), "+f"(d[30]), "+f"(d[31]),
      "+f"(d[32]), "+f"(d[33]), "+f"(d[34]), "+f"(d[35]), "+f"(d[36]), "+f"(d[37]), "+f"(d[38]), "+f"(d[39])
    : "l"(da), "l"(db), "r"(sd));
}
__device__ __forceinline__ void wgmma_rs_n128(float (&d)[64], uint32_t a0, uint32_t a1, uint32_t a2, uint32_t a3,
                                  uint64_t db, int sd) {
  asm volatile("{\n.reg .pred p;\nsetp.ne.b32 p, %69, 0;\n"
      "wgmma.mma_async.sync.aligned.m64n128k16.f32.bf16.bf16 {"
      "%0, %1, %2, %3, %4, %5, %6, %7, %8, %9, %10, %11, %12, %13, %14, %15, "
      "%16, %17, %18, %19, %20, %21, %22, %23, %24, %25, %26, %27, %28, %29, %30, %31, "
      "%32, %33, %34, %35, %36, %37, %38, %39, %40, %41, %42, %43, %44, %45, %46, %47, "
      "%48, %49, %50, %51, %52, %53, %54, %55, %56, %57, %58, %59, %60, %61, %62, %63"
      "}, {%64, %65, %66, %67}, %68, p, 1, 1, 0;\n}\n"
    : "+f"(d[0]), "+f"(d[1]), "+f"(d[2]), "+f"(d[3]), "+f"(d[4]), "+f"(d[5]), "+f"(d[6]), "+f"(d[7]),
      "+f"(d[8]), "+f"(d[9]), "+f"(d[10]), "+f"(d[11]), "+f"(d[12]), "+f"(d[13]), "+f"(d[14]), "+f"(d[15]),
      "+f"(d[16]), "+f"(d[17]), "+f"(d[18]), "+f"(d[19]), "+f"(d[20]), "+f"(d[21]), "+f"(d[22]), "+f"(d[23]),
      "+f"(d[24]), "+f"(d[25]), "+f"(d[26]), "+f"(d[27]), "+f"(d[28]), "+f"(d[29]), "+f"(d[30]), "+f"(d[31]),
      "+f"(d[32]), "+f"(d[33]), "+f"(d[34]), "+f"(d[35]), "+f"(d[36]), "+f"(d[37]), "+f"(d[38]), "+f"(d[39]),
      "+f"(d[40]), "+f"(d[41]), "+f"(d[42]), "+f"(d[43]), "+f"(d[44]), "+f"(d[45]), "+f"(d[46]), "+f"(d[47]),
      "+f"(d[48]), "+f"(d[49]), "+f"(d[50]), "+f"(d[51]), "+f"(d[52]), "+f"(d[53]), "+f"(d[54]), "+f"(d[55]),
      "+f"(d[56]), "+f"(d[57]), "+f"(d[58]), "+f"(d[59]), "+f"(d[60]), "+f"(d[61]), "+f"(d[62]), "+f"(d[63])
    : "r"(a0), "r"(a1), "r"(a2), "r"(a3), "l"(db), "r"(sd));
}
__device__ __forceinline__ void wgmma_rs_n24(float (&d)[12], uint32_t a0, uint32_t a1, uint32_t a2, uint32_t a3,
                                  uint64_t db, int sd) {
  asm volatile("{\n.reg .pred p;\nsetp.ne.b32 p, %17, 0;\n"
      "wgmma.mma_async.sync.aligned.m64n24k16.f32.bf16.bf16 {"
      "%0, %1, %2, %3, %4, %5, %6, %7, %8, %9, %10, %11"
      "}, {%12, %13, %14, %15}, %16, p, 1, 1, 1;\n}\n"
    : "+f"(d[0]), "+f"(d[1]), "+f"(d[2]), "+f"(d[3]), "+f"(d[4]), "+f"(d[5]), "+f"(d[6]), "+f"(d[7]),
      "+f"(d[8]), "+f"(d[9]), "+f"(d[10]), "+f"(d[11])
    : "r"(a0), "r"(a1), "r"(a2), "r"(a3), "l"(db), "r"(sd));
}

#define KST 4
#define K1S 4
constexpr int K1_ST = K1S, K1_STAGE = 45056;
constexpr int K1_SMEM = K1_ST * K1_STAGE + 640   + 1536   + 2560   + 128;

__device__ __forceinline__ float2 row_stats(uint4 v0, uint4 v1, uint4 v2) {
  const uint32_t wd[12] = {v0.x, v0.y, v0.z, v0.w, v1.x, v1.y, v1.z, v1.w, v2.x, v2.y, v2.z, v2.w};
  float sx = 0.f, sq = 0.f;
#pragma unroll
  for (int e = 0; e < 12; e++) {
    const float lo = bf_lo(wd[e]), hi = bf_hi(wd[e]);
    sx += lo + hi; sq = fmaf(lo, lo, fmaf(hi, hi, sq));
  }
#pragma unroll
  for (int o = 16; o; o >>= 1) { sx += __shfl_xor_sync(~0u, sx, o); sq += __shfl_xor_sync(~0u, sq, o); }
  const float mean = sx * (1.f / D_);
  return make_float2(rsqrtf(fmaxf(sq * (1.f / D_) - mean * mean, 0.f) + 1e-5f), mean);
}

__global__ void __cluster_dims__(2, 1, 1) __launch_bounds__(512, 1)
k1_qkv(const __grid_constant__ CUtensorMap tmx, const __grid_constant__ CUtensorMap tmw,
       const bf16* __restrict__ x, const bf16* __restrict__ w, const bf16* __restrict__ wo) {
  extern __shared__ __align__(1024) uint8_t sm[];
  float* cs = (float*)(sm + K1_ST * K1_STAGE);
  float2* rowab = (float2*)(sm + K1_ST * K1_STAGE + 640);
  float* red = (float*)(sm + K1_ST * K1_STAGE + 2176);
  const uint32_t sbase = smem_u32(sm);
  const uint32_t fullb = sbase + K1_ST * K1_STAGE + 4736, emptyb = fullb + 8 * K1_ST;
  const int tid = threadIdx.x, lane = tid & 31;
  const int warp = __shfl_sync(~0u, tid >> 5, 0);
  const int rank = blockIdx.x & 1, cl = blockIdx.x >> 1;
  const int m = cl / 6, n = (cl - m * 6) * 2 + rank;
  if (tid == 0) STAMP(0, 0);

  if (warp == 12) {
    if (lane == 0) {
      prefetch_map(&tmx); prefetch_map(&tmw);
      for (int i = 0; i < K1_ST; i++) { mbar_init(fullb + 8 * i, 1); mbar_init(emptyb + 8 * i, 6); }
      asm volatile("fence.mbarrier_init.release.cluster;" ::: "memory");
    }
    __syncwarp();
    cluster_arrive();
    bar_arrive(4, 512);
    if (elect_one()) {
#pragma unroll
      for (int kt = 0; kt < K1_ST; kt++) mbar_expect(fullb + 8 * kt, K1_STAGE);
#pragma unroll
      for (int j = 0; j < 5; j++) tma2d(sbase + 24576 + j * 4096, &tmw, n * 160 + j * 32, 0, fullb);
    }
    cluster_wait();
#pragma unroll 1
    for (int kt = 0; kt < 10; kt++) {
      const int s = kt % K1_ST;
      const uint32_t sa = sbase + s * K1_STAGE;
      if (kt >= K1_ST) mbar_wait(emptyb + 8 * s, ((kt / K1_ST) - 1) & 1);
      if (elect_one()) {
        if (kt >= K1_ST) mbar_expect(fullb + 8 * s, K1_STAGE);
        tma2d_mc(sa + rank * 12288, &tmx, kt * 64, m * 192 + rank * 96, fullb + 8 * s);
        if (kt > 0) {
#pragma unroll
          for (int j = 0; j < 5; j++) tma2d(sa + 24576 + j * 4096, &tmw, n * 160 + j * 32, kt * 64, fullb + 8 * s);
        }
      }
      if (kt == K1_ST - 1) pdl_trigger();
    }
    __syncwarp();
    cluster_arrive();
  } else if (warp > 12) {
    cluster_arrive();
    const int t96 = tid - 416;
    const uint32_t tag = __ldcg(&g_epoch) + 1;
    bar_sync(4, 512);
    mbar_wait(fullb, 0);
    if (m < 10) {
      const int ck = t96 % 20, rg = min(t96 / 20, 3);
      uint4 wv[16];
#pragma unroll
      for (int i = 0; i < 16; i++) wv[i] = ldg_nc(w + (size_t)(m * 64 + rg * 16 + i) * 1920 + n * 160 + ck * 8);
      float acc8[8];
#pragma unroll
      for (int i = 0; i < 8; i++) acc8[i] = 0.f;
#pragma unroll
      for (int i = 0; i < 16; i++) ACC8(acc8, wv[i]);
      *(float4*)&red[rg * 160 + ck * 8] = make_float4(acc8[0], acc8[1], acc8[2], acc8[3]);
      *(float4*)&red[rg * 160 + ck * 8 + 4] = make_float4(acc8[4], acc8[5], acc8[6], acc8[7]);
      bar_sync(1, 96);
      if (t96 < 80) {
        const float2 p0 = *(const float2*)&red[t96 * 2], p1 = *(const float2*)&red[160 + t96 * 2];
        const float2 p2 = *(const float2*)&red[320 + t96 * 2], p3 = *(const float2*)&red[480 + t96 * 2];
        st_relaxed(&g_cpart[(m * 12 + n) * 80 + t96], (p0.x + p1.x) + (p2.x + p3.x), (p0.y + p1.y) + (p2.y + p3.y), tag);
      }
    }
    if (tid == 416) STAMP(5, 7);
    bool ok = false;
    for (int it = 0; it < 64 && !ok; it++) {
      uint4 p[10], st[2];
#pragma unroll
      for (int k = 0; k < 10; k++) p[k] = ld_relaxed(&g_cpart[(k * 12 + n) * 80 + min(t96, 79)]);
#pragma unroll
      for (int k = 0; k < 2; k++) st[k] = ld_relaxed(&g_rowstat[min(m * 192 + k * 96 + t96, S_ - 1)]);
      ok = true;
      float s0 = 0.f, s1 = 0.f;
#pragma unroll
      for (int k = 0; k < 10; k++) {
        ok = ok && p[k].y == tag && p[k].w == tag;
        s0 += __uint_as_float(p[k].x); s1 += __uint_as_float(p[k].z);
      }
      if (t96 < 80) *(float2*)&cs[t96 * 2] = make_float2(s0, s1);
#pragma unroll
      for (int k = 0; k < 2; k++) {
        ok = ok && st[k].y == tag && st[k].w == tag;
        rowab[k * 96 + t96] = make_float2(__uint_as_float(st[k].x), -__uint_as_float(st[k].x) * __uint_as_float(st[k].z));
      }
      ok = __all_sync(~0u, ok);
      if (!ok) __nanosleep(300);
    }
    if (!ok) {
      const int c2 = min(t96, 79);
      float s0 = 0.f, s1 = 0.f;
#pragma unroll 1
      for (int k = 0; k < D_; k++) {
        const uint32_t v = *(const uint32_t*)(w + (size_t)k * 1920 + n * 160 + c2 * 2);
        s0 += bf_lo(v); s1 += bf_hi(v);
      }
      if (t96 < 80) *(float2*)&cs[t96 * 2] = make_float2(s0, s1);
#pragma unroll 1
      for (int i = 0; i < 64; i++) {
        const int r = (i >> 5) * 96 + (t96 & ~31) + (i & 31);
        const bf16* xr = x + (size_t)min(m * 192 + r, S_ - 1) * D_ + lane * 8;
        const float2 st = row_stats(ldg_nc(xr), ldg_nc(xr + 256), lane < 16 ? ldg_nc(xr + 512) : make_uint4(0u, 0u, 0u, 0u));
        if (lane == 0) rowab[r] = make_float2(st.x, -st.x * st.y);
      }
    }
    __syncwarp();
    bar_arrive(2, 96 + 384);
    bar_sync(1, 96);
    if (tid == 416) STAMP(0, 5);
    if (blockIdx.x < 128) {
      uint4 v[5];
      const int ck = min(t96, 79), nt = ck / 10;
#pragma unroll
      for (int i = 0; i < 5; i++) {
        const int k = blockIdx.x * 5 + i, pr = k / 40, r = k - pr * 40;
        v[i] = ldg_nc(wo + (size_t)(pr * 40 + (r < 16 ? r : (r < 32 ? r + 4 : (r < 36 ? r - 16 : r)))) * D_ + ck * 8);
      }
#pragma unroll
      for (int i = 0; i < 5; i++) {
        const int k = blockIdx.x * 5 + i;
        g_wo[((nt * 10 + (k >> 6)) * 10 + ck - nt * 10) * 64 + (k & 63)] = v[i];
        float t = ((bf_lo(v[i].x) + bf_hi(v[i].x)) + (bf_lo(v[i].y) + bf_hi(v[i].y))) +
                  ((bf_lo(v[i].z) + bf_hi(v[i].z)) + (bf_lo(v[i].w) + bf_hi(v[i].w)));
        if (t96 >= 80) t = 0.f;
#pragma unroll
        for (int o = 16; o; o >>= 1) t += __shfl_xor_sync(~0u, t, o);
        if (lane == 0) red[(t96 >> 5) * 8 + i] = t;
      }
      bar_sync(1, 96);
      if (t96 < 5) {
        const float mu = (red[t96] + red[8 + t96] + red[16 + t96]) * (1.f / D_);
        const float hi = bf_lo(pack_bf16(mu, 0.f));
        g_wm[blockIdx.x * 5 + t96] = make_uint4(pack_bf16(hi, mu - hi), 0u, 0u, 0u);
      }
    }
    if (tid == 416) STAMP(0, 7);
    __syncwarp();
    cluster_wait();
    cluster_arrive();
  } else {
    cluster_arrive();
    float acc[80];
    const uint64_t da0 = mkdesc(sbase + (warp >> 2) * 8192, 16, 1024, 1);
    const uint64_t db0 = mkdesc(sbase + 24576, 4096, 512, 2);
    const uint32_t tag = __ldcg(&g_epoch) + 1;
    const int srow = m * 192 + n * 16 + warp * 2;
    const bool dostat = warp < 8 && srow < S_;
    uint4 xv[2][3];
    bar_sync(4, 512);
    cluster_wait();
#pragma unroll
    for (int kt = 0; kt < 10; kt++) {
      const int s = kt % K1_ST;
      mbar_wait(fullb + 8 * s, (kt / K1_ST) & 1);
      if (kt == 0 && tid == 0) STAMP(0, 1);
      if (kt == 2 && tid == 0) STAMP(5, 0);
      if (kt == 4 && tid == 0) STAMP(5, 1);
      if (kt == 7 && tid == 0) STAMP(5, 2);
      const uint64_t da = da0 + s * (K1_STAGE >> 4), db = db0 + s * (K1_STAGE >> 4);
      WG_FENCE();
#pragma unroll
      for (int k = 0; k < 4; k++) wgmma_ss_n160(acc, da + k * 2, db + k * 64, (kt | k) != 0);
      WG_COMMIT();
      if (kt > 0) {
        WG_WAIT(1);
        if (kt - 1 + K1_ST < 10 && (tid & 127) < 2) mbar_arrive_cta(emptyb + 8 * ((kt - 1) % K1_ST), tid & 1);
      }
      if (kt == 0) {
#pragma unroll
        for (int i = 0; i < 2; i++) {
          const bf16* xr = x + (size_t)min(srow + i, S_ - 1) * D_ + lane * 8;
          xv[i][0] = xv[i][1] = xv[i][2] = make_uint4(0u, 0u, 0u, 0u);
          if (dostat) { xv[i][0] = ldg_nc(xr); xv[i][1] = ldg_nc(xr + 256); }
          if (dostat && lane < 16) xv[i][2] = ldg_nc(xr + 512);
        }
      }
      if ((kt == KST || kt == KST + 1) && dostat) {
        const float2 st = row_stats(xv[kt - KST][0], xv[kt - KST][1], xv[kt - KST][2]);
        if (lane == 0) st_relaxed(&g_rowstat[srow + kt - KST], st.x, st.y, tag);
      }
      __syncwarp();
    }
    cluster_arrive();
    WG_WAIT(0);
    fence_regs(acc);
    if (tid == 0) STAMP(0, 2);
    bar_sync(2, 96 + 384);
    if (tid == 0) STAMP(0, 3);
    const int row0 = m * 192 + warp * 16;
    if (row0 < S_) {
      const int g = lane >> 2, c = lane & 3, sec = n >> 2, grp = (row0 & 127) >> 3;
      const bool lo = c < 2;
      const float2 ab0 = rowab[warp * 16 + g], ab1 = rowab[warp * 16 + g + 8];
      const bool p0 = sec == 1 && ((POLY_MASK >> grp) & 1), p1 = sec == 1 && ((POLY_MASK >> (grp + 1)) & 1);
      const uint32_t padqv = sec == 0 ? (c == 2 ? 0x3F803F80u : 0x00003F80u) : (sec == 2 && c == 2 ? 0x00003F80u : 0u);
      const uint32_t padk = c == 2 ? 0x4A7A4B00u : 0x00004653u;
      const uint32_t pad0 = p0 ? padk : padqv, pad1 = p1 ? padk : padqv;
      const float f0 = sec == 0 ? QSCALE : (p0 ? 32768.f : 1.f), f1 = sec == 0 ? QSCALE : (p1 ? 32768.f : 1.f);
      const float a0 = ab0.x * f0, b0 = ab0.y * f0, a1 = ab1.x * f1, b1 = ab1.y * f1;
      const float r0 = p0 ? 9.313225746154785e-10f : 1.f, r1 = p1 ? 9.313225746154785e-10f : 1.f;
      const int cst = sec == 1 ? 2048 : 128, gst = sec == 1 ? 128 : 384;
      uint8_t* pe = (uint8_t*)g_qkv + (size_t)(n * 8) * HEAD_IMG + (row0 >> 7) * 6144 + grp * gst + lane * 4;
      uint8_t* pe1 = pe + cst;
      uint8_t* pe2 = pe1 + cst;
      uint8_t* pf = pe + gst;
      uint8_t* pf1 = pf + cst;
      uint8_t* pf2 = pf1 + cst;
#pragma unroll
      for (int hp = 0; hp < 4; hp++) {
        uint32_t u[5], v[5];
        float su[5], sv[5];
#pragma unroll
        for (int i = 0; i < 5; i++) {
          const int j = hp * 5 + i;
          const float2 t = *(const float2*)&cs[j * 8 + c * 2];
          const float x0 = fmaf(acc[4 * j], a0, b0 * t.x), x1 = fmaf(acc[4 * j + 1], a0, b0 * t.y);
          const float y0 = fmaf(acc[4 * j + 2], a1, b1 * t.x), y1 = fmaf(acc[4 * j + 3], a1, b1 * t.y);
          u[i] = pack_bf16(x0, x1); v[i] = pack_bf16(y0, y1);
          su[i] = fmaf(x0, x0, x1 * x1); sv[i] = fmaf(y0, y0, y1 * y1);
        }
        constexpr int HE = HEAD_IMG;
        const int oe = hp * 2 * HE, oo = oe + HE;
        *(uint32_t*)(pe + oe) = u[0];  *(uint32_t*)(pf + oe) = v[0];
        *(uint32_t*)(pe1 + oe) = u[1]; *(uint32_t*)(pf1 + oe) = v[1];
        *(uint32_t*)(pe2 + oe) = lo ? u[2] : pad0; *(uint32_t*)(pf2 + oe) = lo ? v[2] : pad1;
        *(uint32_t*)(pe + oo) = __shfl_xor_sync(~0u, lo ? u[3] : u[2], 2);
        *(uint32_t*)(pf + oo) = __shfl_xor_sync(~0u, lo ? v[3] : v[2], 2);
        *(uint32_t*)(pe1 + oo) = __shfl_xor_sync(~0u, lo ? u[4] : u[3], 2);
        *(uint32_t*)(pf1 + oo) = __shfl_xor_sync(~0u, lo ? v[4] : v[3], 2);
        const uint32_t tu = __shfl_xor_sync(~0u, u[4], 2), tv = __shfl_xor_sync(~0u, v[4], 2);
        *(uint32_t*)(pe2 + oo) = lo ? tu : pad0; *(uint32_t*)(pf2 + oo) = lo ? tv : pad1;
        if (sec < 2) {
          float e0 = (su[0] + su[1] + (lo ? su[2] : 0.f)) * r0, e1 = (sv[0] + sv[1] + (lo ? sv[2] : 0.f)) * r1;
          float o0 = (su[3] + su[4] + (lo ? 0.f : su[2])) * r0, o1 = (sv[3] + sv[4] + (lo ? 0.f : sv[2])) * r1;
          e0 += __shfl_xor_sync(~0u, e0, 1); e1 += __shfl_xor_sync(~0u, e1, 1);
          o0 += __shfl_xor_sync(~0u, o0, 1); o1 += __shfl_xor_sync(~0u, o1, 1);
          e0 += __shfl_xor_sync(~0u, e0, 2); e1 += __shfl_xor_sync(~0u, e1, 2);
          o0 += __shfl_xor_sync(~0u, o0, 2); o1 += __shfl_xor_sync(~0u, o1, 2);
          const uint32_t em = __reduce_max_sync(~0u, max(__float_as_uint(e0), __float_as_uint(e1)));
          const uint32_t om = __reduce_max_sync(~0u, max(__float_as_uint(o0), __float_as_uint(o1)));
          if (lane < 2) g_nrm[(n * 8 + hp * 2 + lane) * 128 + (row0 >> 4)] = __uint_as_float(lane ? om : em);
        }
      }
    }
    if (tid == 0) STAMP(0, 4);
  }
  cluster_wait();
  if (tid == 0) STAMP(0, 6);
}

constexpr int K2_SMEM = 2 * HEAD_IMG + 2 * 6144 + 2 * 10240 + 256;

__device__ __forceinline__ uint64_t desc64(uint32_t lo, uint32_t hi) {
  uint64_t d;
  asm("mov.b64 %0, {%1, %2};" : "=l"(d) : "r"(lo), "r"(hi));
  return d;
}
__device__ __forceinline__ uint32_t exp_pair(bool poly, float a, float b, uint32_t mk) {
  if (poly) {
    const uint32_t pk = __byte_perm(__float_as_uint(a), __float_as_uint(b), 0x6521);
    uint32_t m, q;
    asm("lop3.b32 %0, %1, %2, 0x3f803f80, 0xEA;" : "=r"(m) : "r"(pk), "r"(mk));
    asm("fma.rn.bf16x2 %0, %1, %1, %2;" : "=r"(q) : "r"(m), "r"(0x40014001u));
    return pk - m + q;
  }
  return pack_bf16(ex2(a), ex2(b));
}
#define PV_GR 4
__device__ __forceinline__ void exp_pv(const float (&s)[64], float (&o)[12], uint64_t dv, uint32_t mk) {
#pragma unroll
  for (int k0 = 0; k0 < 8; k0 += PV_GR) {
    uint32_t p[4 * PV_GR];
#pragma unroll
    for (int i = 0; i < 4 * PV_GR; i++)
      p[i] = exp_pair((POLY_MASK >> (k0 * 2 + i / 2)) & 1, s[k0 * 8 + 2 * i], s[k0 * 8 + 2 * i + 1], mk);
    WG_FENCE();
#pragma unroll
    for (int k = 0; k < PV_GR; k++)
      wgmma_rs_n24(o, p[4 * k], p[4 * k + 1], p[4 * k + 2], p[4 * k + 3], dv + (k0 + k) * 48, 1);
  }
}
__device__ __forceinline__ void load_q(uint32_t (&q)[6], const uint8_t* p) {
  q[0] = __ldcg((const uint32_t*)p);         q[1] = __ldcg((const uint32_t*)(p + 384));
  q[2] = __ldcg((const uint32_t*)(p + 128)); q[3] = __ldcg((const uint32_t*)(p + 512));
  q[4] = __ldcg((const uint32_t*)(p + 256)); q[5] = __ldcg((const uint32_t*)(p + 640));
}
__device__ __forceinline__ float rcp(float x) {
  float y;
  asm("rcp.approx.ftz.f32 %0, %1;" : "=f"(y) : "f"(x));
  return y;
}
__device__ __forceinline__ int img_off(int chunk) { return chunk * 2048; }
__device__ __forceinline__ void store_o(const float (&o)[12], int tile) {
  int tid, bid;
  asm volatile("mov.u32 %0, %%tid.x;" : "=r"(tid));
  asm volatile("mov.u32 %0, %%ctaid.x;" : "=r"(bid));
  const int head = bid >> 2;
  uint8_t* dst = (uint8_t*)g_o + ((bid & 3) * 4 + (tile >> 1)) * 163840 + (tile & 1) * 1024 + ((tid >> 5) & 3) * 256 + (tid & 31) * 4;
  const int oc = (head >> 1) * 5 + (head & 1) * 2;
  const int o0 = img_off(oc), o1 = img_off(oc + 1), o2 = img_off((head >> 1) * 5 + 4) + (head & 1) * 8;
  const float i0 = rcp(__shfl_sync(~0u, o[8], 2, 4)), i1 = rcp(__shfl_sync(~0u, o[10], 2, 4));
  *(uint32_t*)(dst + o0) = pack_bf16(o[0] * i0, o[1] * i0); *(uint32_t*)(dst + o0 + 128) = pack_bf16(o[2] * i1, o[3] * i1);
  *(uint32_t*)(dst + o1) = pack_bf16(o[4] * i0, o[5] * i0); *(uint32_t*)(dst + o1 + 128) = pack_bf16(o[6] * i1, o[7] * i1);
  if ((tid & 3) < 2) {
    *(uint32_t*)(dst + o2) = pack_bf16(o[8] * i0, o[9] * i0);
    *(uint32_t*)(dst + o2 + 128) = pack_bf16(o[10] * i1, o[11] * i1);
  }
}

struct Maps5 { CUtensorMap m[5]; };

__global__ void __launch_bounds__(512, 1)
k2_attn(const __grid_constant__ Maps5 maps, uint32_t mk) {
  const CUtensorMap* tmw = maps.m;
  extern __shared__ __align__(1024) uint8_t sm[];
  const uint32_t sbase = smem_u32(sm);
  float* part = (float*)(sm + 2 * HEAD_IMG);
  const uint32_t rbuf = sbase + 2 * HEAD_IMG + 2 * 6144;
  const uint32_t kvb = rbuf + 2 * 10240;
  const uint32_t partb = kvb + 128, rbar = kvb + 144;
  const int tid = threadIdx.x, lane = tid & 31;
  const int warp = __shfl_sync(~0u, tid >> 5, 0);
  const int head = blockIdx.x >> 2, qb = blockIdx.x & 3;

  if (tid == 0) STAMP(1, 0);
  if (tid == 0) {
    for (int i = 0; i < 16; i++) mbar_init(kvb + 8 * i, 1);
    mbar_init(partb, 128); mbar_init(partb + 8, 128); mbar_init(rbar, 1); mbar_init(rbar + 8, 1);
    asm volatile("fence.mbarrier_init.release.cluster;" ::: "memory");
  }
  __syncthreads();

  if (warp >= 12) {
    asm volatile("setmaxnreg.dec.sync.aligned.u32 32;");
    if (tid == 384) {
      pdl_wait();
      pdl_trigger();
      const uint8_t* kimg = (const uint8_t*)g_qkv + (size_t)(32 + head) * HEAD_IMG;
#pragma unroll 1
      for (int b = 0; b < 16; b++) {
        mbar_expect(kvb + 8 * b, 12288);
        bulk_ld(sbase + b * 6144, kimg + b * 6144, 6144, kvb + 8 * b);
        bulk_ld(sbase + HEAD_IMG + b * 6144, kimg + 32 * HEAD_IMG + b * 6144, 6144, kvb + 8 * b);
        if (b >= 2) mbar_wait(kvb + 8 * (b - 1), 0);

      }
      if (blockIdx.x == 0) g_epoch = g_epoch + 1;
      mbar_wait(kvb + 8 * 15, 0);
      STAMP(1, 2);
      uint8_t* pdst = nullptr;
      uint32_t pbytes = 0;
#pragma unroll 1
      for (int i = 0; i < 8; i++) {
        const int p = blockIdx.x + 128 * i;
        uint8_t* dst = nullptr;
        uint32_t bytes = 0;
        if (i < 7 && p < 856) {
          asm volatile("cp.async.bulk.wait_group.read 0;" ::: "memory");
          const CUtensorMap* tm;
          int c1, c2;
          if (p < 640) {
            const int nt = p / 80, r = p - nt * 80, ph = r / 40, st = (r - ph * 40) >> 1, up = r & 1;
            bytes = ph ? 6656 : 7168;
            dst = (uint8_t*)g_wgu + nt * 552960 + ph * 286720 + st * 2 * bytes + up * (bytes >> 1);
            tm = &tmw[ph * 2 + up]; c1 = ph ? 112 + nt * 13 : nt * 14; c2 = st * 2;
          } else {
            const int nk = p - 640, nt = nk / 27;
            bytes = 10240;
            dst = (uint8_t*)g_wd + (size_t)nk * 10240;
            tm = &tmw[4]; c1 = nt * 10; c2 = nk - nt * 27;
          }
          mbar_expect(rbar + 8 * (i & 1), bytes);
          tma4d(rbuf + (i & 1) * 10240, tm, c1, c2, rbar + 8 * (i & 1));
        }
        if (pbytes) {
          mbar_wait(rbar + 8 * ((i - 1) & 1), ((i - 1) >> 1) & 1);
          if (pbytes == 10240) {
            bulk_st(pdst, rbuf + ((i - 1) & 1) * 10240, pbytes);
          } else {
            bulk_st(pdst, rbuf + ((i - 1) & 1) * 10240, pbytes >> 1);
            bulk_st(pdst + pbytes, rbuf + ((i - 1) & 1) * 10240 + (pbytes >> 1), pbytes >> 1);
          }
          asm volatile("cp.async.bulk.commit_group;" ::: "memory");
        }
        pdst = dst; pbytes = bytes;
      }
      asm volatile("cp.async.bulk.wait_group.read 0;" ::: "memory");
      STAMP(1, 6);
    }
  } else {
    asm volatile("setmaxnreg.inc.sync.aligned.u32 160;");
    const int wg = warp >> 2;
    const uint8_t* qthr = (const uint8_t*)g_qkv + (size_t)head * HEAD_IMG + qb * 64 * 384 + (warp & 3) * 768 + lane * 4;
    const uint32_t klo0 = ((sbase & 0x3FFFF) >> 4) | (128u << 16), vlo0 = (((sbase + HEAD_IMG) & 0x3FFFF) >> 4) | (24u << 16);
    constexpr uint64_t KSTEP2 = (uint64_t)(int64_t)(256 - (128 << 16));
    constexpr uint64_t KV2K = 384 - (HEAD_IMG >> 4) + (104 << 16);
    const int nun = wg == 1 ? 4 : 3;
    uint32_t utile = wg == 0 ? 0x210u : (wg == 1 ? 0x4235u : 0x576u);
    uint32_t ubeg = wg == 0 ? 0u : (wg == 1 ? 0x0b00u : 0x600u);
    uint32_t ulen = wg == 0 ? 0x0b1010u : (wg == 1 ? 0x10051006u : 0x0a1010u);
    pdl_wait();
    if (tid == 0) STAMP(1, 1);
    uint32_t q[6];
    load_q(q, qthr + (utile & 15) * 3072);
    bool fast;
    {
      const float4 kn = __ldcg((const float4*)&g_nrm[(32 + head) * 128 + lane * 4]);
      const float qv = __ldcg(&g_nrm[head * 128 + qb * 32 + lane]);
      const uint32_t km = max(max(__float_as_uint(kn.x), __float_as_uint(kn.y)), max(__float_as_uint(kn.z), __float_as_uint(kn.w)));
      const float k2 = __uint_as_float(__reduce_max_sync(~0u, km)), q2 = __uint_as_float(__reduce_max_sync(~0u, __float_as_uint(qv)));
      fast = q2 * k2 <= 3400.f;
    }
    if (fast) {
#pragma unroll 1
      for (int u = 0; u < nun; u++) {
        const uint32_t b0 = ubeg & 15;
        const bool wt = u == 0 || (wg == 1 && u == 1);
        float s[64], o[12];
#pragma unroll
        for (int i = 0; i < 12; i++) o[i] = 0.f;
        uint32_t vlo = vlo0 + b0 * 384, kb = kvb + b0 * 8;
        const uint32_t vend = vlo + ((ulen & 255) - 1) * 384;
        if (wt) mbar_wait(kb, 0);
        if (tid == 0) STAMP(5, 4 + u);
        fence_regs(o);
        WG_FENCE();
        wgmma_rs_n128(s, q[0], q[1], q[2], q[3], desc64(klo0 + b0 * 384, 8), 0);
        wgmma_rs_n128(s, q[4], q[5], 0, 0, desc64(klo0 + b0 * 384, 8) + KSTEP2, 1);
        WG_COMMIT();
#define K2UNR 1
        constexpr int kUnr = K2UNR;
#pragma unroll kUnr
        for (; vlo != vend; vlo += 384) {
          if (wt) { kb += 8; mbar_wait(kb, 0); }
          WG_WAIT(0);
          fence_regs(s); fence_regs(o);
          const uint64_t dv = desc64(vlo, 8);
          exp_pv(s, o, dv, mk);
          wgmma_rs_n128(s, q[0], q[1], q[2], q[3], dv + KV2K, 0);
          wgmma_rs_n128(s, q[4], q[5], 0, 0, dv + (KV2K + KSTEP2), 1);
          WG_COMMIT();
        }
        WG_WAIT(0);
        fence_regs(s); fence_regs(o);
        if (u + 1 < nun) load_q(q, qthr + ((utile >> 4) & 15) * 3072);
        exp_pv(s, o, desc64(vlo, 8), mk);
        WG_COMMIT();
        WG_WAIT(0);
        fence_regs(o);
        if (wg == 1 && !(u & 1)) {
          float4* pp = (float4*)(part + u * 768) + (tid & 127);
          pp[0] = make_float4(o[0], o[1], o[2], o[3]);
          pp[128] = make_float4(o[4], o[5], o[6], o[7]);
          pp[256] = make_float4(o[8], o[9], o[10], o[11]);
          mbar_arrive(partb + 4 * u);
        } else {
          if (wg != 1 && u == 2) {
            const int pi = wg == 0 ? 1 : 0;
            mbar_wait(partb + 8 * pi, 0);
            const float4* pp = (const float4*)(part + pi * 1536) + (tid & 127);
            const float4 x0 = pp[0], x1 = pp[128], x2 = pp[256];
            o[0] += x0.x; o[1] += x0.y; o[2] += x0.z; o[3] += x0.w; o[4] += x1.x; o[5] += x1.y;
            o[6] += x1.z; o[7] += x1.w; o[8] += x2.x; o[9] += x2.y; o[10] += x2.z; o[11] += x2.w;
          }
          store_o(o, utile & 15);
        }
        utile >>= 4; ubeg >>= 4; ulen >>= 8;
      }
      if ((tid & 127) == 0) STAMP(1, 3 + wg);
    } else {
#pragma unroll 1
      for (int tile = wg; tile < 8; tile += 3) {
        load_q(q, qthr + tile * 3072);
        if ((lane & 3) >= 2) { q[4] = 0; q[5] = 0; }
        float o[12], m0 = -INFINITY, m1 = -INFINITY;
#pragma unroll
        for (int i = 0; i < 12; i++) o[i] = 0.f;
#pragma unroll 1
        for (int b = 0; b < 16; b++) {
          float s[64];
          mbar_wait(kvb + 8 * b, 0);
          WG_FENCE();
          wgmma_rs_n128(s, q[0], q[1], q[2], q[3], desc64(klo0 + b * 384, 8), 0);
          wgmma_rs_n128(s, q[4], q[5], 0, 0, desc64(klo0 + b * 384, 8) + KSTEP2, 1);
          WG_COMMIT();
          WG_WAIT(0);
          fence_regs(s);
          float x0 = m0, x1 = m1;
#pragma unroll
          for (int j = 0; j < 16; j++) {
            if ((POLY_MASK >> j) & 1) {
#pragma unroll
              for (int i = 0; i < 4; i++) s[4 * j + i] *= (1.f / 32768.f);
            }
            x0 = fmaxf(x0, fmaxf(s[4 * j], s[4 * j + 1]));
            x1 = fmaxf(x1, fmaxf(s[4 * j + 2], s[4 * j + 3]));
          }
          x0 = fmaxf(x0, __shfl_xor_sync(~0u, x0, 1)); x0 = fmaxf(x0, __shfl_xor_sync(~0u, x0, 2));
          x1 = fmaxf(x1, __shfl_xor_sync(~0u, x1, 1)); x1 = fmaxf(x1, __shfl_xor_sync(~0u, x1, 2));
          const float al0 = ex2(m0 - x0), al1 = ex2(m1 - x1);
          m0 = x0; m1 = x1;
#pragma unroll
          for (int i = 0; i < 12; i++) o[i] *= (i & 2) ? al1 : al0;
          uint32_t p[32];
#pragma unroll
          for (int i = 0; i < 32; i++) {
            const float mm = (i & 1) ? m1 : m0;
            p[i] = pack_bf16(ex2(s[2 * i] - mm), ex2(s[2 * i + 1] - mm));
          }
          fence_regs(o);
          WG_FENCE();
#pragma unroll
          for (int k = 0; k < 8; k++)
            wgmma_rs_n24(o, p[4 * k], p[4 * k + 1], p[4 * k + 2], p[4 * k + 3], desc64(vlo0 + b * 384 + k * 48, 8), 1);
          WG_COMMIT();
          WG_WAIT(0);
          fence_regs(o);
        }
        store_o(o, tile);
      }
    }
  }
}

#define K3P 1
constexpr int K3_ST = 4, K3_STAGE = 37888, K3_PRE = K3P;
constexpr int K3_SMEM = K3_ST * K3_STAGE + 45056 + 20480 + 256;

template <int N> struct Acc { float v[N]; };

template <int NB, int NK, bool FIRST>
__global__ void __cluster_dims__(2, 1, 1) __launch_bounds__(384, 1)
k3_proj(const __grid_constant__ CUtensorMap tmr, const uint4* __restrict__ aimg, const uint4* __restrict__ wimg) {
  constexpr int KT = 2 * NB + NK, EX = FIRST ? 1 : 0;
  extern __shared__ __align__(1024) uint8_t sm[];
  const uint32_t sbase = smem_u32(sm);
  uint8_t* xch = sm + K3_ST * K3_STAGE;
  uint8_t* stg = sm + K3_ST * K3_STAGE + 45056;
  const uint32_t fullb = smem_u32(stg) + 20480, emptyb = fullb + 8 * K3_ST, resb = emptyb + 8 * K3_ST, xchb = resb + 8;
  const int tid = threadIdx.x, lane = tid & 31;
  const int warp = __shfl_sync(~0u, tid >> 5, 0);
  const int rank = blockIdx.x & 1;
  const int n = blockIdx.x & 7, m = blockIdx.x >> 3;
  if (tid == 0) STAMP(FIRST ? 2 : 4, 0);
  if (warp == 0) {
    if (lane == 0) {
      prefetch_map(&tmr);
      for (int i = 0; i < K3_ST; i++) { mbar_init(fullb + 8 * i, 1); mbar_init(emptyb + 8 * i, 4); }
      mbar_init(resb, 1); mbar_init(xchb, 1);
      mbar_expect(xchb, 4096 * (10 + EX));
      asm volatile("fence.mbarrier_init.release.cluster;" ::: "memory");
    }
    __syncwarp();
    cluster_arrive();
    bar_arrive(4, 256 + 32);
    const uint8_t* wk = (const uint8_t*)wimg + (size_t)n * KT * 10240;
    const uint8_t* ws = (const uint8_t*)wimg + (size_t)(n ^ 1) * KT * 10240;
    const uint8_t* ab = (const uint8_t*)aimg + (size_t)m * KT * 16384;
    auto load_w = [&](int i) {
      const int s = i % K3_ST, kt = i < NB ? i + rank * (NB + NK) : i;
      const uint32_t sa = sbase + s * K3_STAGE;
      mbar_expect(fullb + 8 * s, 26624 + EX * 1024 + (i < NB ? 10240 : 0));
      bulk_ld(sa + 16384, wk + kt * 10240, 10240, fullb + 8 * s);
      if (FIRST) bulk_ld(sa + 26624, (const uint8_t*)g_wm + kt * 1024, 1024, fullb + 8 * s);
      if (i < NB) bulk_ld(sa + 26624 + EX * 1024, ws + kt * 10240, 10240, fullb + 8 * s);
    };
    if (elect_one()) {
#pragma unroll 1
      for (int i = 0; i < K3_PRE; i++) load_w(i);
    }
    cluster_wait();
    pdl_wait();
    pdl_trigger();
    if (lane == 0) STAMP(2, 6);
#pragma unroll 1
    for (int i = 0; i < NB + NK; i++) {
      const int s = i % K3_ST;
      const uint32_t sa = sbase + s * K3_STAGE;
      if (i >= K3_ST) mbar_wait(emptyb + 8 * s, ((i / K3_ST) - 1) & 1);
      if (elect_one()) {
        if (i < NB) bulk_ld(sa, ab + (i + rank * (NB + NK)) * 16384, 16384, fullb + 8 * s);
        else bulk_ld_mc(sa + rank * 8192, ab + i * 16384 + rank * 8192, 8192, fullb + 8 * s);
        if (i >= K3_PRE) load_w(i);
        if (FIRST && i == K3_ST - 1) {
          mbar_expect(resb, 20480);
          tma2d(smem_u32(stg), &tmr, n * 80, m * 128, resb);
          tma2d(smem_u32(stg) + 10240, &tmr, n * 80, m * 128 + 64, resb);
        }
      }
    }
    __syncwarp();
    cluster_arrive();
  } else if (warp >= 4) {
    cluster_arrive();
    const int cw = warp - 4, wg = cw >> 2;
    const int g = lane >> 2, c = lane & 3;
    const int row = m * 128 + cw * 16 + g;
    uint8_t* himg = (uint8_t*)g_h + (size_t)m * 163840 + cw * 256 + lane * 4;
    uint32_t rv[20];
    float mu0, mu1;
    if (FIRST) {
      mu0 = __uint_as_float(__ldcg(&g_rowstat[row].z)); mu1 = __uint_as_float(__ldcg(&g_rowstat[row + 8].z));
    } else {
      mu0 = __ldcg(&g_hmean[row]); mu1 = __ldcg(&g_hmean[row + 8]);
#pragma unroll
      for (int j = 0; j < 10; j++) {
        rv[2 * j] = __ldcg((const uint32_t*)(himg + img_off(n * 10 + j)));
        rv[2 * j + 1] = __ldcg((const uint32_t*)(himg + img_off(n * 10 + j) + 128));
      }
    }
    float acc[80 + 4 * EX];
    float (&keep)[40 + 4 * EX] = ((Acc<40 + 4 * EX>*)acc)->v;
    const uint64_t da0 = mkdesc(sbase + wg * 1024, 2048, 128, 0);
    const uint64_t db0 = mkdesc(sbase + 16384, 128, 1024, 0);
    bar_sync(4, 256 + 32);
    cluster_wait();
#pragma unroll 1
    for (int i = 0; i < NB; i++) {
      const int s = i % K3_ST;
      mbar_wait(fullb + 8 * s, (i / K3_ST) & 1);
      if (i == 0 && tid == 128) STAMP(FIRST ? 2 : 4, 2);
      const uint64_t da = da0 + s * (K3_STAGE >> 4), db = db0 + s * (K3_STAGE >> 4);
      WG_FENCE();
#pragma unroll
      for (int k = 0; k < 4; k++) {
        if constexpr (FIRST) wgmma_ss_n168(acc, da + k * 256, db + k * 16, (i | k) != 0);
        else wgmma_ss_n160(acc, da + k * 256, db + k * 16, (i | k) != 0);
      }
      WG_COMMIT();
      if (i > 0) {
        WG_WAIT(1);
        if ((tid & 127) < 2) mbar_arrive_cta(emptyb + 8 * ((i - 1) % K3_ST), tid & 1);
      }
    }
    const uint32_t rx = mapa(smem_u32(xch) + (tid - 128) * 16, rank ^ 1), rb = mapa(xchb, rank ^ 1);
    WG_WAIT(0);
    fence_regs(acc);
    if ((tid & 127) < 2) mbar_arrive_cta(emptyb + 8 * ((NB - 1) % K3_ST), tid & 1);
    if (FIRST) st_async4(rx, acc[40], acc[41], acc[42], acc[43], rb);
    if (tid == 128) STAMP(FIRST ? 2 : 4, 1);
#pragma unroll
    for (int i = NB; i < NB + NK; i++) {
      const int s = i % K3_ST;
      mbar_wait(fullb + 8 * s, (i / K3_ST) & 1);
      const uint64_t da = da0 + s * (K3_STAGE >> 4), db = db0 + s * (K3_STAGE >> 4);
      WG_FENCE();
#pragma unroll
      for (int k = 0; k < 4; k++) {
        if constexpr (FIRST) wgmma_ss_n88(keep, da + k * 256, db + k * 16, 1);
        else wgmma_ss_n80(keep, da + k * 256, db + k * 16, 1);
      }
      WG_COMMIT();
      if (i > NB && i - 1 + K3_ST < NB + NK) {
        WG_WAIT(1);
        if ((tid & 127) < 2) mbar_arrive_cta(emptyb + 8 * ((i - 1) % K3_ST), tid & 1);
      }
#pragma unroll
      for (int j = (i - NB) * 3 + EX; j < (i - NB) * 3 + 3 + EX; j++)
        if (j < 10 + EX) st_async4(rx + j * 4096, acc[40 + 4 * j], acc[41 + 4 * j], acc[42 + 4 * j], acc[43 + 4 * j], rb);
    }
    cluster_arrive();
    uint8_t* sp = stg + (cw * 16 + g) * 160 + c * 4;
    if (FIRST) {
      mbar_wait(resb, 0);
#pragma unroll
      for (int j = 0; j < 10; j++) {
        rv[2 * j] = *(const uint32_t*)(sp + j * 16);
        rv[2 * j + 1] = *(const uint32_t*)(sp + 1280 + j * 16);
      }
    }
    WG_WAIT(0);
    fence_regs(keep);
    if (tid == 128) STAMP(FIRST ? 2 : 4, 3);
    mbar_wait(xchb, 0);
    if (tid == 128) STAMP(FIRST ? 2 : 4, 5);
    const uint8_t* xp = xch + (tid - 128) * 16;
    if (FIRST) {
      const float4 p = *(const float4*)xp;
      mu0 += __shfl_sync(~0u, (keep[40] + p.x) + (keep[41] + p.y), 0, 4);
      mu1 += __shfl_sync(~0u, (keep[42] + p.z) + (keep[43] + p.w), 0, 4);
      if (n == 0 && c == 0) { g_hmean[row] = mu0; g_hmean[row + 8] = mu1; }
      mu0 = -mu0; mu1 = -mu1;
    }
    float q0 = 0.f, q1 = 0.f;
#pragma unroll
    for (int j = 0; j < 10; j++) {
      const float4 p = *(const float4*)(xp + (j + EX) * 4096);
      const float x0 = (keep[4 * j] + p.x) + (bf_lo(rv[2 * j]) + mu0), x1 = (keep[4 * j + 1] + p.y) + (bf_hi(rv[2 * j]) + mu0);
      const float y0 = (keep[4 * j + 2] + p.z) + (bf_lo(rv[2 * j + 1]) + mu1), y1 = (keep[4 * j + 3] + p.w) + (bf_hi(rv[2 * j + 1]) + mu1);
      if (FIRST) {
        *(uint32_t*)(himg + img_off(n * 10 + j)) = pack_bf16(x0, x1);
        *(uint32_t*)(himg + img_off(n * 10 + j) + 128) = pack_bf16(y0, y1);
        q0 = fmaf(x0, x0, fmaf(x1, x1, q0)); q1 = fmaf(y0, y0, fmaf(y1, y1, q1));
      } else {
        *(uint32_t*)(sp + j * 16) = pack_bf16(x0, x1);
        *(uint32_t*)(sp + 1280 + j * 16) = pack_bf16(y0, y1);
      }
    }
    if (FIRST) {
      q0 += __shfl_xor_sync(~0u, q0, 1); q0 += __shfl_xor_sync(~0u, q0, 2);
      q1 += __shfl_xor_sync(~0u, q1, 1); q1 += __shfl_xor_sync(~0u, q1, 2);
      if (c < 2) g_hpart[n * S_ + row + c * 8] = c ? q1 : q0;
    } else {
      fence_async();
      bar_sync(1 + wg, 128);
      if ((tid & 127) == 0) {
        tma2d_st(&tmr, n * 80, m * 128 + wg * 64, smem_u32(stg) + wg * 10240);
        bulk_commit_wait();
      }
      __syncwarp();
    }
    if (tid == 128) STAMP(FIRST ? 2 : 4, 4);
  } else {
    cluster_arrive();
    cluster_wait();
    cluster_arrive();
  }
  cluster_wait();
}

constexpr int K4_G = 2, K4_NS = 4, K4_NJ = 20;
constexpr int K4_RB = 163840, K4_BST = 7168 * K4_G, K4_XCH = 147456, K4_STG = K4_XCH + 40960, K4_BAR = K4_RB + K4_NS * K4_BST;
constexpr int K4_SMEM = K4_BAR + 384;

__device__ __forceinline__ void wait_flags(const uint4* f, uint32_t tag, uint32_t need, uint32_t& seen) {
  for (uint32_t it = 0; (seen & need) != need; it++) {
    if (it) __nanosleep(40);
    if (it > (1u << 20)) wait_timeout();
    uint4 a, b;
    asm volatile("ld.acquire.gpu.global.v4.u32 {%0, %1, %2, %3}, [%4];" : "=r"(a.x), "=r"(a.y), "=r"(a.z), "=r"(a.w) : "l"(f) : "memory");
    asm volatile("ld.acquire.gpu.global.v4.u32 {%0, %1, %2, %3}, [%4];" : "=r"(b.x), "=r"(b.y), "=r"(b.z), "=r"(b.w) : "l"(f + 1) : "memory");
    seen = (a.x == tag) | (a.y == tag) << 1 | (a.z == tag) << 2 | (a.w == tag) << 3 | (b.x == tag) << 4 | (b.y == tag) << 5 |
           (b.z == tag) << 6 | (b.w == tag) << 7;
    asm volatile("fence.proxy.async.global;" ::: "memory");
  }
}

__global__ void __cluster_dims__(2, 1, 1) __launch_bounds__(384, 1)
k45_ffn(const __grid_constant__ CUtensorMap tmo) {
  extern __shared__ __align__(1024) uint8_t sm[];
  const uint32_t sbase = smem_u32(sm);
  const uint32_t afull = sbase + K4_BAR, bfull = afull + 80, bempty = bfull + 8 * K4_NS, full3 = bempty + 8 * K4_NS;
  const uint32_t empty3 = full3 + 32, afree = empty3 + 32, xchb = afree + 32;
  const int tid = threadIdx.x, lane = tid & 31;
  const int warp = __shfl_sync(~0u, tid >> 5, 0);
  const int rank = blockIdx.x & 1;
  const int n1 = (blockIdx.x >> 1) & 7, m1 = (blockIdx.x >> 4) * 2 + rank;
  const int n3 = blockIdx.x & 7, m3 = blockIdx.x >> 3;
  if (tid == 0) STAMP(3, 0);
  if (warp == 8) {
    if (elect_one()) {
#pragma unroll
      for (int i = 0; i < 10; i++) mbar_init(afull + 8 * i, 1);
#pragma unroll
      for (int i = 0; i < 4; i++) {
        mbar_init(bfull + 8 * i, 1); mbar_init(bempty + 8 * i, 4); mbar_init(full3 + 8 * i, 1); mbar_init(empty3 + 8 * i, 4);
        mbar_init(afree + 8 * i, 2);
      }
      mbar_init(xchb, 1);
      mbar_expect(xchb, 40960);
      asm volatile("fence.mbarrier_init.release.cluster;" ::: "memory");
    }
    __syncwarp();
  }
  cluster_arrive();
  if (warp >= 8) {
    cluster_wait();
    if (warp == 8) {
      if (lane == 0) STAMP(3, 7);
      const uint8_t* src = (const uint8_t*)g_wgu + n1 * 552960;
      const uint8_t* hb = (const uint8_t*)g_h + (size_t)m1 * 163840;
#pragma unroll 1
      for (int j = 0; j < 40; j++) {
        const uint32_t s8 = (j & 3) * 8, sz = j < 20 ? 14336 : 13312;
#define K4PRE 2
        if (j == K4PRE) {
          pdl_wait();
          if (lane == 0) STAMP(3, 1);
          if (elect_one()) {
#pragma unroll
            for (int kt = 0; kt < K4PRE / 2 + 1; kt++) { mbar_expect(afull + 8 * kt, 16384); bulk_ld(sbase + kt * 16384, hb + kt * 16384, 16384, afull + 8 * kt); }
          }
        }
        if (j >= 4) mbar_wait(bempty + s8, ((j >> 2) - 1) & 1);
        if (elect_one()) {
          mbar_expect(bfull + s8, sz);
          if ((j & 1) == rank) bulk_ld_mc(sbase + K4_RB + s8 * (K4_BST / 8), src, sz, bfull + s8);
          if (j > K4PRE && j < 18 && (j & 1)) {
            mbar_expect(afull + 4 + j * 4, 16384);
            bulk_ld(sbase + 8192 + j * 8192, hb + 8192 + j * 8192, 16384, afull + 4 + j * 4);
          }
        }
        src += sz;
      }
    } else if (warp == 9) {
      prefetch_map(&tmo);
      const uint32_t tag = __ldcg(&g_epoch);
#pragma unroll 1
      for (int ph = 0; ph < 2; ph++) {
        bar_sync(5 + ph, 256 + 32);
        if (lane == 0) {
          asm volatile("st.release.gpu.global.u32 [%0], %1;" ::"l"((uint32_t*)&g_flag[ph * 32 + m1 * 2] + n1), "r"(tag) : "memory");
          STAMP(3, 5 + ph);
        }
        __syncwarp();
      }
    } else {
      const uint8_t* wk = (const uint8_t*)g_wd + n3 * 276480;
      const uint8_t* ws = (const uint8_t*)g_wd + (n3 ^ 1) * 276480;
      const uint8_t* ab = (const uint8_t*)g_hh + (size_t)m3 * 442368;
      const uint32_t tag = __ldcg(&g_epoch);
      uint32_t seen = 0;
#pragma unroll 1
      for (int i = 0; i < 16; i++) {
        const int kt = i < 7 ? rank * 7 + i : (i < 11 ? rank * 4 + 7 + i : 11 + i);
        const uint32_t sa = sbase + (i & 3) * 36864, fb = full3 + 8 * (i & 3);
        if (i < 4) mbar_wait(afree + 8 * i, 0);
        else mbar_wait(empty3 + 8 * (i & 3), ((i >> 2) - 1) & 1);
        if (warp == 10) {
          if (elect_one()) {
            mbar_expect(fb, i < 11 ? 36864 : 26624);
            bulk_ld(sa + 16384, wk + kt * 10240, 10240, fb);
            if (i < 11) bulk_ld(sa + 26624, ws + kt * 10240, 10240, fb);
          }
        } else {
          {
            const int q = kt * 8 - (i < 7 ? 0 : 112), w = i < 7 ? 14 : 13;
            if (i == 7) seen = 0;
            wait_flags(&g_flag[(i < 7 ? 0 : 32) + m3 * 2], tag, 1u << (q / w) | 1u << ((q + 7) / w), seen);
            if (lane == 0 && (i == 0 || i == 7)) STAMP(4, i ? 7 : 6);
          }
          if (elect_one()) {
            if (i < 11) bulk_ld(sa, ab + kt * 16384, 16384, fb);
            else bulk_ld_mc(sa + rank * 8192, ab + kt * 16384 + rank * 8192, 8192, fb);
          }
        }
      }
    }
    __syncwarp();
    cluster_arrive();
    asm volatile("barrier.cluster.wait.aligned; // producers" ::: "memory");
  } else {
    const int wg = warp >> 2;
    const uint64_t da0 = mkdesc(sbase + wg * 1024, 2048, 128, 0);
    const uint64_t db0 = mkdesc(sbase + K4_RB, 128, 256, 0);
    cluster_wait();
    float a1[112], a2[104];
    int s = 0, ph = 0, sprev = 0;
#pragma unroll 1
    for (int j = 0; j < K4_NJ; j++) {
      if ((j * K4_G) % 4 == 0) mbar_wait(afull + 2 * K4_G * j, 0);
      mbar_wait(bfull + 8 * s, ph);
      if (j == 0 && tid == 0) STAMP(3, 2);
      const uint64_t da = da0 + j * K4_G * 256, db = db0 + s * (K4_BST >> 4);
      WG_FENCE();
#pragma unroll
      for (int k = 0; k < K4_G; k++) wgmma_ss_n224(a1, da + k * 256, db + k * 448, (j | k) != 0);
      WG_COMMIT();
      if (j > 0) {
        WG_WAIT(1);
        if ((tid & 127) < 2) mbar_arrive_cta(bempty + 8 * sprev, tid & 1);
      }
      sprev = s;
      if (++s == K4_NS) { s = 0; ph ^= 1; }
    }
    float acc[80];
    uint8_t* hd = (uint8_t*)g_hh + (size_t)m1 * 442368 + warp * 256 + lane * 4;
    WG_WAIT(0);
    fence_regs(a1);
    if ((tid & 127) < 2) mbar_arrive_cta(bempty + 8 * ((K4_NJ - 1) % K4_NS), tid & 1);
    if (tid == 0) STAMP(3, 3);
#define STORE_H(a, off, ptr, c) do { uint8_t* p_ = ptr; \
      *(uint32_t*)p_ = pack_bf16(a[4 * (c)] * a[off + 4 * (c)], a[4 * (c) + 1] * a[off + 1 + 4 * (c)]); \
      *(uint32_t*)(p_ + 128) = pack_bf16(a[4 * (c) + 2] * a[off + 2 + 4 * (c)], a[4 * (c) + 3] * a[off + 3 + 4 * (c)]); } while (0)
#pragma unroll
    for (int c = 0; c < 14; c++) STORE_H(a1, 56, hd + img_off(n1 * 14 + c), c);
    bar_arrive(5, 256 + 32);
#pragma unroll 1
    for (int j = 0; j < K4_NJ; j++) {
      mbar_wait(bfull + 8 * s, ph);
      const uint64_t da = da0 + j * K4_G * 256, db = db0 + s * (K4_BST >> 4);
      WG_FENCE();
#pragma unroll
      for (int k = 0; k < K4_G; k++) wgmma_ss_n208(a2, da + k * 256, db + k * 416, (j | k) != 0);
      WG_COMMIT();
      if (j > 0) {
        WG_WAIT(1);
        if (j <= K4_NJ - K4_NS && (tid & 127) < 2) mbar_arrive_cta(bempty + 8 * sprev, tid & 1);
        if (j * K4_G >= 12 && ((j * K4_G) & 7) == 4 && (tid & 127) == 0) mbar_arrive(afree + (j * K4_G - 12));
      }
      sprev = s;
      if (++s == K4_NS) { s = 0; ph ^= 1; }
    }
    WG_WAIT(0);
    fence_regs(a2);
    if (tid == 0) STAMP(3, 4);
#pragma unroll
    for (int c = 0; c < 13; c++) STORE_H(a2, 52, hd + img_off(112 + n1 * 13 + c), c);
    bar_arrive(6, 256 + 32);
    float (&keep)[40] = ((Acc<40>*)acc)->v;
    const uint64_t db3 = mkdesc(sbase + 16384, 128, 1024, 0);
#pragma unroll 1
    for (int i = 0; i < 11; i++) {
      mbar_wait(full3 + 8 * (i & 3), (i >> 2) & 1);
      if (i == 0 && tid == 0) STAMP(4, 2);
      const uint64_t da = da0 + (i & 3) * 2304, db = db3 + (i & 3) * 2304;
      WG_FENCE();
#pragma unroll
      for (int k = 0; k < 4; k++) wgmma_ss_n160(acc, da + k * 256, db + k * 16, (i | k) != 0);
      WG_COMMIT();
      if (i > 0) {
        WG_WAIT(1);
        if ((tid & 127) < 2) mbar_arrive_cta(empty3 + 8 * ((i - 1) & 3), tid & 1);
      }
    }
    const int g = lane >> 2, c = lane & 3, row = m3 * 128 + warp * 16 + g;
    const uint8_t* himg = (const uint8_t*)g_h + (size_t)m3 * 163840 + warp * 256 + lane * 4;
    uint32_t rv[20];
    const float mu0 = __ldcg(&g_hmean[row]), mu1 = __ldcg(&g_hmean[row + 8]);
    float r0 = __ldcg(&g_hpart[c * 2 * S_ + row]) + __ldcg(&g_hpart[(c * 2 + 1) * S_ + row]);
    float r1 = __ldcg(&g_hpart[c * 2 * S_ + row + 8]) + __ldcg(&g_hpart[(c * 2 + 1) * S_ + row + 8]);
#pragma unroll
    for (int j = 0; j < 10; j++) {
      rv[2 * j] = __ldcg((const uint32_t*)(himg + img_off(n3 * 10 + j)));
      rv[2 * j + 1] = __ldcg((const uint32_t*)(himg + img_off(n3 * 10 + j) + 128));
    }
    const uint32_t rx = mapa(sbase + K4_XCH + tid * 16, rank ^ 1), rb = mapa(xchb, rank ^ 1);
    WG_WAIT(0);
    fence_regs(acc);
    if ((tid & 127) < 2) mbar_arrive_cta(empty3 + 16, tid & 1);
    if (tid == 0) STAMP(4, 1);
#pragma unroll
    for (int i = 11; i < 16; i++) {
      mbar_wait(full3 + 8 * (i & 3), (i >> 2) & 1);
      const uint64_t da = da0 + (i & 3) * 2304, db = db3 + (i & 3) * 2304;
      WG_FENCE();
#pragma unroll
      for (int k = 0; k < 4; k++) wgmma_ss_n80(keep, da + k * 256, db + k * 16, 1);
      WG_COMMIT();
      if (i == 12) {
        WG_WAIT(1);
        if ((tid & 127) < 2) mbar_arrive_cta(empty3 + 24, tid & 1);
      }
#pragma unroll
      for (int j = (i - 11) * 3; j < (i - 11) * 3 + 3; j++)
        if (j < 10) st_async4(rx + j * 4096, acc[40 + 4 * j], acc[41 + 4 * j], acc[42 + 4 * j], acc[43 + 4 * j], rb);
    }
    cluster_arrive();
    r0 += __shfl_xor_sync(~0u, r0, 1); r1 += __shfl_xor_sync(~0u, r1, 1);
    r0 += __shfl_xor_sync(~0u, r0, 2); r1 += __shfl_xor_sync(~0u, r1, 2);
    r0 = rcp(r0 * (1.f / D_) + 1e-5f); r1 = rcp(r1 * (1.f / D_) + 1e-5f);
    asm volatile("" : "+f"(r0), "+f"(r1)::"memory");
    WG_WAIT(0);
    fence_regs(keep);
    if (tid == 0) STAMP(4, 3);
    mbar_wait(xchb, 0);
    if (tid == 0) STAMP(4, 5);
    uint8_t* sp = sm + K4_STG + (warp * 16 + g) * 160 + c * 4;
#pragma unroll
    for (int j = 0; j < 10; j++) {
      const float4 p = *(const float4*)(sm + K4_XCH + tid * 16 + j * 4096);
      *(uint32_t*)(sp + j * 16) = pack_bf16(fmaf(keep[4 * j] + p.x, r0, bf_lo(rv[2 * j]) + mu0), fmaf(keep[4 * j + 1] + p.y, r0, bf_hi(rv[2 * j]) + mu0));
      *(uint32_t*)(sp + 1280 + j * 16) = pack_bf16(fmaf(keep[4 * j + 2] + p.z, r1, bf_lo(rv[2 * j + 1]) + mu1), fmaf(keep[4 * j + 3] + p.w, r1, bf_hi(rv[2 * j + 1]) + mu1));
    }
    fence_async();
    bar_sync(1 + wg, 128);
    if ((tid & 127) == 0) {
      tma2d_st(&tmo, n3 * 80, m3 * 128 + wg * 64, sbase + K4_STG + wg * 10240);
      bulk_commit_wait();
    }
    __syncwarp();
    if (tid == 0) STAMP(4, 4);
    asm volatile("barrier.cluster.wait.aligned; // consumers" ::: "memory");
  }
}

typedef CUresult (*EncodeFn)(CUtensorMap*, CUtensorMapDataType, cuuint32_t, void*, const cuuint64_t*, const cuuint64_t*,
                             const cuuint32_t*, const cuuint32_t*, CUtensorMapInterleave, CUtensorMapSwizzle,
                             CUtensorMapL2promotion, CUtensorMapFloatOOBfill);

static CUtensorMap make_map(EncodeFn enc, const void* p, uint64_t inner, uint64_t outer, uint32_t box_inner,
                            uint32_t box_outer, CUtensorMapSwizzle swz) {
  CUtensorMap m;
  cuuint64_t gd[2] = {inner, outer};
  cuuint64_t gs[1] = {inner * 2};
  cuuint32_t bd[2] = {box_inner, box_outer};
  cuuint32_t es[2] = {1, 1};
  enc(&m, CU_TENSOR_MAP_DATA_TYPE_BFLOAT16, 2, (void*)p, gd, gs, bd, es, CU_TENSOR_MAP_INTERLEAVE_NONE, swz,
      CU_TENSOR_MAP_L2_PROMOTION_L2_256B, CU_TENSOR_MAP_FLOAT_OOB_FILL_NONE);
  return m;
}

static CUtensorMap make_map_img(EncodeFn enc, const void* p, uint64_t k, uint64_t n, uint32_t rows, uint32_t chunks,
                                uint32_t groups) {
  CUtensorMap m;
  cuuint64_t gd[4] = {8, rows, n / 8, k / rows};
  cuuint64_t gs[3] = {n * 2, 16, n * 2 * rows};
  cuuint32_t bd[4] = {8, rows, chunks, groups};
  cuuint32_t es[4] = {1, 1, 1, 1};
  enc(&m, CU_TENSOR_MAP_DATA_TYPE_BFLOAT16, 4, (void*)p, gd, gs, bd, es, CU_TENSOR_MAP_INTERLEAVE_NONE,
      CU_TENSOR_MAP_SWIZZLE_NONE, CU_TENSOR_MAP_L2_PROMOTION_L2_128B, CU_TENSOR_MAP_FLOAT_OOB_FILL_NONE);
  return m;
}

template <typename... KArgs, typename... Args>
static void launch(void (*k)(KArgs...), int grid, int threads, int smem, bool pdl, Args... args) {
  cudaLaunchConfig_t cfg = {};
  cfg.gridDim = dim3(grid);
  cfg.blockDim = dim3(threads);
  cfg.dynamicSmemBytes = smem;
  cfg.stream = cudaStreamPerThread;
  cudaLaunchAttribute at[1];
  at[0].id = cudaLaunchAttributeProgrammaticStreamSerialization;
  at[0].val.programmaticStreamSerializationAllowed = 1;
  cfg.attrs = at;
  cfg.numAttrs = pdl ? 1 : 0;
  cudaLaunchKernelEx(&cfg, k, KArgs(args)...);
}

extern "C" void kernel_launch(void* const* d_in, const int* in_sizes, int n_in, void* d_out, int out_size) {
  const bf16* x = (const bf16*)d_in[0];
  const bf16* wqkv = (const bf16*)d_in[1];
  const bf16* wo = (const bf16*)d_in[2];
  const bf16* wg = (const bf16*)d_in[4];
  const bf16* wu = (const bf16*)d_in[5];
  const bf16* wd = (const bf16*)d_in[6];

  static EncodeFn enc = nullptr;
  static void *p_o, *p_wo;
  if (!enc) {
    void* fn = nullptr;
    cudaDriverEntryPointQueryResult qr;
    cudaGetDriverEntryPoint("cuTensorMapEncodeTiled", &fn, cudaEnableDefault, &qr);
    enc = (EncodeFn)fn;
    cudaGetSymbolAddress(&p_o, g_o);
    cudaGetSymbolAddress(&p_wo, g_wo);
    cudaFuncSetAttribute(k1_qkv, cudaFuncAttributeMaxDynamicSharedMemorySize, K1_SMEM);
    cudaFuncSetAttribute(k2_attn, cudaFuncAttributeMaxDynamicSharedMemorySize, K2_SMEM);
    cudaFuncSetAttribute(k3_proj<3, 4, true>, cudaFuncAttributeMaxDynamicSharedMemorySize, K3_SMEM);
    cudaFuncSetAttribute(k45_ffn, cudaFuncAttributeMaxDynamicSharedMemorySize, K4_SMEM);
  }
  const CUtensorMap tmx = make_map(enc, x, D_, S_, 64, 96, CU_TENSOR_MAP_SWIZZLE_128B);
  const CUtensorMap tmw = make_map(enc, wqkv, 3 * D_, D_, 32, 64, CU_TENSOR_MAP_SWIZZLE_64B);
  const CUtensorMap tmxr = make_map(enc, x, D_, S_, 80, 64, CU_TENSOR_MAP_SWIZZLE_NONE);
  Maps5 maps;
  maps.m[0] = make_map_img(enc, wg, D_, F_, 16, 14, 2); maps.m[1] = make_map_img(enc, wu, D_, F_, 16, 14, 2);
  maps.m[2] = make_map_img(enc, wg, D_, F_, 16, 13, 2); maps.m[3] = make_map_img(enc, wu, D_, F_, 16, 13, 2);
  maps.m[4] = make_map_img(enc, wd, F_, D_, 64, 10, 1);
  const CUtensorMap tmout = make_map(enc, d_out, D_, S_, 80, 64, CU_TENSOR_MAP_SWIZZLE_NONE);

  launch(k1_qkv, 132, 512, K1_SMEM, false, tmx, tmw, x, wqkv, wo);
  launch(k2_attn, 128, 512, K2_SMEM, true, maps, 0x007f007fu);
  launch(k3_proj<3, 4, true>, 128, 384, K3_SMEM, true, tmxr, (const uint4*)p_o, (const uint4*)p_wo);
  launch(k45_ffn, 128, 384, K4_SMEM, true, tmout);
}
```

```cpp
#include <cuda_runtime.h>
#include <cuda_bf16.h>
#include <cuda.h>
#include <stdint.h>

typedef __nv_bfloat16 bf16;

constexpr int S_ = 2048, D_ = 640, F_ = 1728;
constexpr int HEAD_IMG = 98304;
#define PMASK 0xDB6D
constexpr uint32_t POLY_MASK = PMASK;
constexpr float QSCALE = 0.22360679774997896f * 1.4426950408889634f;

__device__ __align__(1024) uint4 g_qkv[96 * HEAD_IMG / 16];
__device__ __align__(1024) uint4 g_o[S_ * D_ / 8];
__device__ __align__(1024) uint4 g_h[S_ * D_ / 8];
__device__ __align__(1024) uint4 g_hh[S_ * F_ / 8];
__device__ __align__(1024) uint4 g_wo[D_ * D_ / 8];
__device__ __align__(1024) uint4 g_wgu[2 * D_ * F_ / 8];
__device__ __align__(1024) uint4 g_wd[F_ * D_ / 8];
__device__ uint4 g_rowstat[S_];
__device__ uint4 g_cpart[10 * 12 * 80];
__device__ float g_nrm[64 * 128];
__device__ uint4 g_wm[D_];
__device__ float g_hmean[S_];
__device__ float g_hpart[8 * S_];
__device__ uint4 g_flag[2 * 16 * 2];
__device__ unsigned g_epoch;

#define STAMP(k, i)
__device__ __forceinline__ uint32_t smem_u32(const void* p) { return (uint32_t)__cvta_generic_to_shared(p); }
__device__ __forceinline__ void mbar_init(uint32_t a, uint32_t c) {
  asm volatile("mbarrier.init.shared::cta.b64 [%0], %1;" ::"r"(a), "r"(c) : "memory");
}
__device__ __forceinline__ void mbar_expect(uint32_t a, uint32_t bytes) {
  asm volatile("mbarrier.arrive.expect_tx.shared::cta.b64 _, [%0], %1;" ::"r"(a), "r"(bytes) : "memory");
}
__device__ __forceinline__ void mbar_arrive(uint32_t a) {
  asm volatile("mbarrier.arrive.shared::cta.b64 _, [%0];" ::"r"(a) : "memory");
}
__device__ __forceinline__ void mbar_arrive_cta(uint32_t a, uint32_t cta) {
  asm volatile("{\n.reg .b32 r;\nmapa.shared::cluster.u32 r, %0, %1;\n"
               "mbarrier.arrive.shared::cluster.b64 _, [r];\n}" ::"r"(a), "r"(cta) : "memory");
}
__device__ __forceinline__ bool mbar_try(uint32_t a, uint32_t ph) {
  uint32_t ok;
  asm volatile("{\n.reg .pred p;\nmbarrier.try_wait.parity.shared::cta.b64 p, [%1], %2;\nselp.u32 %0, 1, 0, p;\n}"
               : "=r"(ok) : "r"(a), "r"(ph) : "memory");
  return ok;
}
__device__ __noinline__ void wait_timeout() { __trap(); }
__device__ __forceinline__ void mbar_wait(uint32_t a, uint32_t ph) {
  if (mbar_try(a, ph)) return;
  uint32_t it = 0;
  while (!mbar_try(a, ph)) if (++it > (1u << 22)) wait_timeout();
}
__device__ __forceinline__ void tma2d(uint32_t dst, const CUtensorMap* m, int c0, int c1, uint32_t bar) {
  asm volatile("cp.async.bulk.tensor.2d.shared::cluster.global.mbarrier::complete_tx::bytes [%0], [%1, {%3, %4}], [%2];"
               ::"r"(dst), "l"(m), "r"(bar), "r"(c0), "r"(c1) : "memory");
}
__device__ __forceinline__ void tma2d_mc(uint32_t dst, const CUtensorMap* m, int c0, int c1, uint32_t bar) {
  asm volatile("cp.async.bulk.tensor.2d.shared::cluster.global.mbarrier::complete_tx::bytes.multicast::cluster "
               "[%0], [%1, {%3, %4}], [%2], %5;"
               ::"r"(dst), "l"(m), "r"(bar), "r"(c0), "r"(c1), "h"((uint16_t)3) : "memory");
}
__device__ __forceinline__ void bulk_ld(uint32_t dst, const void* src, uint32_t bytes, uint32_t bar) {
  asm volatile("cp.async.bulk.shared::cluster.global.mbarrier::complete_tx::bytes [%0], [%1], %2, [%3];"
               ::"r"(dst), "l"(src), "r"(bytes), "r"(bar) : "memory");
}
__device__ __forceinline__ void bulk_ld_mc(uint32_t dst, const void* src, uint32_t bytes, uint32_t bar) {
  asm volatile("cp.async.bulk.shared::cluster.global.mbarrier::complete_tx::bytes.multicast::cluster "
               "[%0], [%1], %2, [%3], %4;"
               ::"r"(dst), "l"(src), "r"(bytes), "r"(bar), "h"((uint16_t)3) : "memory");
}
__device__ __forceinline__ void cluster_arrive() { asm volatile("barrier.cluster.arrive.relaxed.aligned;" ::: "memory"); }
__device__ __forceinline__ void cluster_wait() { asm volatile("barrier.cluster.wait.aligned;" ::: "memory"); }
__device__ __forceinline__ void bulk_st(void* dst, uint32_t src, uint32_t bytes) {
  asm volatile("cp.async.bulk.global.shared::cta.bulk_group [%0], [%1], %2;" ::"l"(dst), "r"(src), "r"(bytes) : "memory");
}
__device__ __forceinline__ void tma2d_st(const CUtensorMap* m, int c0, int c1, uint32_t src) {
  asm volatile("cp.async.bulk.tensor.2d.global.shared::cta.bulk_group [%0, {%2, %3}], [%1];"
               ::"l"(m), "r"(src), "r"(c0), "r"(c1) : "memory");
}
__device__ __forceinline__ void bulk_commit_wait() {
  asm volatile("cp.async.bulk.commit_group;\ncp.async.bulk.wait_group.read 0;" ::: "memory");
}
__device__ __forceinline__ uint32_t mapa(uint32_t a, uint32_t cta) {
  uint32_t r;
  asm("mapa.shared::cluster.u32 %0, %1, %2;" : "=r"(r) : "r"(a), "r"(cta));
  return r;
}
__device__ __forceinline__ void st_async4(uint32_t dst, float a, float b, float c, float d, uint32_t bar) {
  asm volatile("st.async.shared::cluster.mbarrier::complete_tx::bytes.v4.f32 [%0], {%1, %2, %3, %4}, [%5];"
               ::"r"(dst), "f"(a), "f"(b), "f"(c), "f"(d), "r"(bar) : "memory");
}
__device__ __forceinline__ void st_async4u(uint32_t dst, uint32_t a, uint32_t b, uint32_t c, uint32_t d, uint32_t bar) {
  asm volatile("st.async.shared::cluster.mbarrier::complete_tx::bytes.v4.b32 [%0], {%1, %2, %3, %4}, [%5];"
               ::"r"(dst), "r"(a), "r"(b), "r"(c), "r"(d), "r"(bar) : "memory");
}
#define SEND8(dst, a, o, bar) st_async4u(dst, pack_bf16(a[o], a[(o) + 1]), pack_bf16(a[(o) + 2], a[(o) + 3]), \
                                         pack_bf16(a[(o) + 4], a[(o) + 5]), pack_bf16(a[(o) + 6], a[(o) + 7]), bar)
__device__ __forceinline__ void fence_async() { asm volatile("fence.proxy.async.shared::cta;" ::: "memory"); }
__device__ __forceinline__ void prefetch_map(const CUtensorMap* m) {
  asm volatile("prefetch.tensormap [%0];" ::"l"(m) : "memory");
}
__device__ __forceinline__ bool elect_one() {
  uint32_t p;
  asm volatile("{\n.reg .pred q;\nelect.sync _|q, 0xffffffff;\nselp.u32 %0, 1, 0, q;\n}" : "=r"(p));
  return p;
}
__device__ __forceinline__ void pdl_wait() { asm volatile("griddepcontrol.wait;" ::: "memory"); }
__device__ __forceinline__ void pdl_trigger() { asm volatile("griddepcontrol.launch_dependents;" ::: "memory"); }
__device__ __forceinline__ void bar_sync(int id, int n) { asm volatile("bar.sync %0, %1;" ::"r"(id), "r"(n) : "memory"); }
__device__ __forceinline__ void bar_arrive(int id, int n) { asm volatile("bar.arrive %0, %1;" ::"r"(id), "r"(n) : "memory"); }
#define WG_FENCE() asm volatile("wgmma.fence.sync.aligned;" ::: "memory")
#define WG_COMMIT() asm volatile("wgmma.commit_group.sync.aligned;" ::: "memory")
#define WG_WAIT(n) asm volatile("wgmma.wait_group.sync.aligned %0;" ::"n"(n) : "memory")
__device__ __forceinline__ uint64_t mkdesc(uint32_t addr, uint32_t lbo, uint32_t sbo, uint32_t sw) {
  return (uint64_t)((addr & 0x3FFFF) >> 4) | ((uint64_t)(lbo >> 4) << 16) | ((uint64_t)(sbo >> 4) << 32) |
         ((uint64_t)sw << 62);
}
template <int N> __device__ __forceinline__ void fence_regs(float (&r)[N]) {
#pragma unroll
  for (int i = 0; i < N; i++) asm volatile("" : "+f"(r[i])::"memory");
}
__device__ __forceinline__ uint32_t pack_bf16(float lo, float hi) {
  uint32_t r;
  asm("cvt.rn.bf16x2.f32 %0, %1, %2;" : "=r"(r) : "f"(hi), "f"(lo));
  return r;
}
__device__ __forceinline__ float bf_lo(uint32_t v) { return __uint_as_float(v << 16); }
__device__ __forceinline__ float bf_hi(uint32_t v) { return __uint_as_float(v & 0xffff0000u); }
__device__ __forceinline__ float ex2(float x) {
  float y;
  asm("ex2.approx.ftz.f32 %0, %1;" : "=f"(y) : "f"(x));
  return y;
}
__device__ __forceinline__ uint4 ldg_nc(const void* p) {
  uint4 v;
  asm volatile("ld.global.nc.L1::no_allocate.v4.u32 {%0, %1, %2, %3}, [%4];"
               : "=r"(v.x), "=r"(v.y), "=r"(v.z), "=r"(v.w) : "l"(p));
  return v;
}

__device__ __forceinline__ uint4 ld_relaxed(const uint4* p) {
  uint64_t a, b;
  asm volatile("ld.relaxed.gpu.global.v2.u64 {%0, %1}, [%2];" : "=l"(a), "=l"(b) : "l"(p) : "memory");
  return make_uint4((uint32_t)a, (uint32_t)(a >> 32), (uint32_t)b, (uint32_t)(b >> 32));
}
__device__ __forceinline__ void st_relaxed(uint4* p, float x, float y, uint32_t tag) {
  const uint64_t a = ((uint64_t)tag << 32) | __float_as_uint(x), b = ((uint64_t)tag << 32) | __float_as_uint(y);
  asm volatile("st.relaxed.gpu.global.v2.u64 [%0], {%1, %2};" ::"l"(p), "l"(a), "l"(b) : "memory");
}
__device__ __forceinline__ void tma4d(uint32_t dst, const CUtensorMap* m, int c2, int c3, uint32_t bar) {
  asm volatile("cp.async.bulk.tensor.4d.shared::cluster.global.mbarrier::complete_tx::bytes [%0], [%1, {%3, %3, %4, %5}], [%2];"
               ::"r"(dst), "l"(m), "r"(bar), "r"(0), "r"(c2), "r"(c3) : "memory");
}
#define ACC8(a, v) do { a[0] += bf_lo(v.x); a[1] += bf_hi(v.x); a[2] += bf_lo(v.y); a[3] += bf_hi(v.y); \
                        a[4] += bf_lo(v.z); a[5] += bf_hi(v.z); a[6] += bf_lo(v.w); a[7] += bf_hi(v.w); } while (0)

__device__ __forceinline__ void wgmma_ss_n224(float (&d)[112], uint64_t da, uint64_t db, int sd) {
  asm volatile("{\n.reg .pred p;\nsetp.ne.b32 p, %114, 0;\n"
      "wgmma.mma_async.sync.aligned.m64n224k16.f32.bf16.bf16 {"
      "%0, %1, %2, %3, %4, %5, %6, %7, %8, %9, %10, %11, %12, %13, %14, %15, "
      "%16, %17, %18, %19, %20, %21, %22, %23, %24, %25, %26, %27, %28, %29, %30, %31, "
      "%32, %33, %34, %35, %36, %37, %38, %39, %40, %41, %42, %43, %44, %45, %46, %47, "
      "%48, %49, %50, %51, %52, %53, %54, %55, %56, %57, %58, %59, %60, %61, %62, %63, "
      "%64, %65, %66, %67, %68, %69, %70, %71, %72, %73, %74, %75, %76, %77, %78, %79, "
      "%80, %81, %82, %83, %84, %85, %86, %87, %88, %89, %90, %91, %92, %93, %94, %95, "
      "%96, %97, %98, %99, %100, %101, %102, %103, %104, %105, %106, %107, %108, %109, %110, %111"
      "}, %112, %113, p, 1, 1, 0, 1;\n}\n"
    : "+f"(d[0]), "+f"(d[1]), "+f"(d[2]), "+f"(d[3]), "+f"(d[4]), "+f"(d[5]), "+f"(d[6]), "+f"(d[7]),
      "+f"(d[8]), "+f"(d[9]), "+f"(d[10]), "+f"(d[11]), "+f"(d[12]), "+f"(d[13]), "+f"(d[14]), "+f"(d[15]),
      "+f"(d[16]), "+f"(d[17]), "+f"(d[18]), "+f"(d[19]), "+f"(d[20]), "+f"(d[21]), "+f"(d[22]), "+f"(d[23]),
      "+f"(d[24]), "+f"(d[25]), "+f"(d[26]), "+f"(d[27]), "+f"(d[28]), "+f"(d[29]), "+f"(d[30]), "+f"(d[31]),
      "+f"(d[32]), "+f"(d[33]), "+f"(d[34]), "+f"(d[35]), "+f"(d[36]), "+f"(d[37]), "+f"(d[38]), "+f"(d[39]),
      "+f"(d[40]), "+f"(d[41]), "+f"(d[42]), "+f"(d[43]), "+f"(d[44]), "+f"(d[45]), "+f"(d[46]), "+f"(d[47]),
      "+f"(d[48]), "+f"(d[49]), "+f"(d[50]), "+f"(d[51]), "+f"(d[52]), "+f"(d[53]), "+f"(d[54]), "+f"(d[55]),
      "+f"(d[56]), "+f"(d[57]), "+f"(d[58]), "+f"(d[59]), "+f"(d[60]), "+f"(d[61]), "+f"(d[62]), "+f"(d[63]),
      "+f"(d[64]), "+f"(d[65]), "+f"(d[66]), "+f"(d[67]), "+f"(d[68]), "+f"(d[69]), "+f"(d[70]), "+f"(d[71]),
      "+f"(d[72]), "+f"(d[73]), "+f"(d[74]), "+f"(d[75]), "+f"(d[76]), "+f"(d[77]), "+f"(d[78]), "+f"(d[79]),
      "+f"(d[80]), "+f"(d[81]), "+f"(d[82]), "+f"(d[83]), "+f"(d[84]), "+f"(d[85]), "+f"(d[86]), "+f"(d[87]),
      "+f"(d[88]), "+f"(d[89]), "+f"(d[90]), "+f"(d[91]), "+f"(d[92]), "+f"(d[93]), "+f"(d[94]), "+f"(d[95]),
      "+f"(d[96]), "+f"(d[97]), "+f"(d[98]), "+f"(d[99]), "+f"(d[100]), "+f"(d[101]), "+f"(d[102]), "+f"(d[103]),
      "+f"(d[104]), "+f"(d[105]), "+f"(d[106]), "+f"(d[107]), "+f"(d[108]), "+f"(d[109]), "+f"(d[110]), "+f"(d[111])
    : "l"(da), "l"(db), "r"(sd));
}
__device__ __forceinline__ void wgmma_ss_n208(float (&d)[104], uint64_t da, uint64_t db, int sd) {
  asm volatile("{\n.reg .pred p;\nsetp.ne.b32 p, %106, 0;\n"
      "wgmma.mma_async.sync.aligned.m64n208k16.f32.bf16.bf16 {"
      "%0, %1, %2, %3, %4, %5, %6, %7, %8, %9, %10, %11, %12, %13, %14, %15, "
      "%16, %17, %18, %19, %20, %21, %22, %23, %24, %25, %26, %27, %28, %29, %30, %31, "
      "%32, %33, %34, %35, %36, %37, %38, %39, %40, %41, %42, %43, %44, %45, %46, %47, "
      "%48, %49, %50, %51, %52, %53, %54, %55, %56, %57, %58, %59, %60, %61, %62, %63, "
      "%64, %65, %66, %67, %68, %69, %70, %71, %72, %73, %74, %75, %76, %77, %78, %79, "
      "%80, %81, %82, %83, %84, %85, %86, %87, %88, %89, %90, %91, %92, %93, %94, %95, "
      "%96, %97, %98, %99, %100, %101, %102, %103"
      "}, %104, %105, p, 1, 1, 0, 1;\n}\n"
    : "+f"(d[0]), "+f"(d[1]), "+f"(d[2]), "+f"(d[3]), "+f"(d[4]), "+f"(d[5]), "+f"(d[6]), "+f"(d[7]),
      "+f"(d[8]), "+f"(d[9]), "+f"(d[10]), "+f"(d[11]), "+f"(d[12]), "+f"(d[13]), "+f"(d[14]), "+f"(d[15]),
      "+f"(d[16]), "+f"(d[17]), "+f"(d[18]), "+f"(d[19]), "+f"(d[20]), "+f"(d[21]), "+f"(d[22]), "+f"(d[23]),
      "+f"(d[24]), "+f"(d[25]), "+f"(d[26]), "+f"(d[27]), "+f"(d[28]), "+f"(d[29]), "+f"(d[30]), "+f"(d[31]),
      "+f"(d[32]), "+f"(d[33]), "+f"(d[34]), "+f"(d[35]), "+f"(d[36]), "+f"(d[37]), "+f"(d[38]), "+f"(d[39]),
      "+f"(d[40]), "+f"(d[41]), "+f"(d[42]), "+f"(d[43]), "+f"(d[44]), "+f"(d[45]), "+f"(d[46]), "+f"(d[47]),
      "+f"(d[48]), "+f"(d[49]), "+f"(d[50]), "+f"(d[51]), "+f"(d[52]), "+f"(d[53]), "+f"(d[54]), "+f"(d[55]),
      "+f"(d[56]), "+f"(d[57]), "+f"(d[58]), "+f"(d[59]), "+f"(d[60]), "+f"(d[61]), "+f"(d[62]), "+f"(d[63]),
      "+f"(d[64]), "+f"(d[65]), "+f"(d[66]), "+f"(d[67]), "+f"(d[68]), "+f"(d[69]), "+f"(d[70]), "+f"(d[71]),
      "+f"(d[72]), "+f"(d[73]), "+f"(d[74]), "+f"(d[75]), "+f"(d[76]), "+f"(d[77]), "+f"(d[78]), "+f"(d[79]),
      "+f"(d[80]), "+f"(d[81]), "+f"(d[82]), "+f"(d[83]), "+f"(d[84]), "+f"(d[85]), "+f"(d[86]), "+f"(d[87]),
      "+f"(d[88]), "+f"(d[89]), "+f"(d[90]), "+f"(d[91]), "+f"(d[92]), "+f"(d[93]), "+f"(d[94]), "+f"(d[95]),
      "+f"(d[96]), "+f"(d[97]), "+f"(d[98]), "+f"(d[99]), "+f"(d[100]), "+f"(d[101]), "+f"(d[102]), "+f"(d[103])
    : "l"(da), "l"(db), "r"(sd));
}
__device__ __forceinline__ void wgmma_ss_n168(float (&d)[84], uint64_t da, uint64_t db, int sd) {
  asm volatile("{\n.reg .pred p;\nsetp.ne.b32 p, %86, 0;\n"
      "wgmma.mma_async.sync.aligned.m64n168k16.f32.bf16.bf16 {"
      "%0, %1, %2, %3, %4, %5, %6, %7, %8, %9, %10, %11, %12, %13, %14, %15, "
      "%16, %17, %18, %19, %20, %21, %22, %23, %24, %25, %26, %27, %28, %29, %30, %31, "
      "%32, %33, %34, %35, %36, %37, %38, %39, %40, %41, %42, %43, %44, %45, %46, %47, "
      "%48, %49, %50, %51, %52, %53, %54, %55, %56, %57, %58, %59, %60, %61, %62, %63, "
      "%64, %65, %66, %67, %68, %69, %70, %71, %72, %73, %74, %75, %76, %77, %78, %79, "
      "%80, %81, %82, %83"
      "}, %84, %85, p, 1, 1, 0, 1;\n}\n"
    : "+f"(d[0]), "+f"(d[1]), "+f"(d[2]), "+f"(d[3]), "+f"(d[4]), "+f"(d[5]), "+f"(d[6]), "+f"(d[7]),
      "+f"(d[8]), "+f"(d[9]), "+f"(d[10]), "+f"(d[11]), "+f"(d[12]), "+f"(d[13]), "+f"(d[14]), "+f"(d[15]),
      "+f"(d[16]), "+f"(d[17]), "+f"(d[18]), "+f"(d[19]), "+f"(d[20]), "+f"(d[21]), "+f"(d[22]), "+f"(d[23]),
      "+f"(d[24]), "+f"(d[25]), "+f"(d[26]), "+f"(d[27]), "+f"(d[28]), "+f"(d[29]), "+f"(d[30]), "+f"(d[31]),
      "+f"(d[32]), "+f"(d[33]), "+f"(d[34]), "+f"(d[35]), "+f"(d[36]), "+f"(d[37]), "+f"(d[38]), "+f"(d[39]),
      "+f"(d[40]), "+f"(d[41]), "+f"(d[42]), "+f"(d[43]), "+f"(d[44]), "+f"(d[45]), "+f"(d[46]), "+f"(d[47]),
      "+f"(d[48]), "+f"(d[49]), "+f"(d[50]), "+f"(d[51]), "+f"(d[52]), "+f"(d[53]), "+f"(d[54]), "+f"(d[55]),
      "+f"(d[56]), "+f"(d[57]), "+f"(d[58]), "+f"(d[59]), "+f"(d[60]), "+f"(d[61]), "+f"(d[62]), "+f"(d[63]),
      "+f"(d[64]), "+f"(d[65]), "+f"(d[66]), "+f"(d[67]), "+f"(d[68]), "+f"(d[69]), "+f"(d[70]), "+f"(d[71]),
      "+f"(d[72]), "+f"(d[73]), "+f"(d[74]), "+f"(d[75]), "+f"(d[76]), "+f"(d[77]), "+f"(d[78]), "+f"(d[79]),
      "+f"(d[80]), "+f"(d[81]), "+f"(d[82]), "+f"(d[83])
    : "l"(da), "l"(db), "r"(sd));
}
__device__ __forceinline__ void wgmma_ss_n160(float (&d)[80], uint64_t da, uint64_t db, int sd) {
  asm volatile("{\n.reg .pred p;\nsetp.ne.b32 p, %82, 0;\n"
      "wgmma.mma_async.sync.aligned.m64n160k16.f32.bf16.bf16 {"
      "%0, %1, %2, %3, %4, %5, %6, %7, %8, %9, %10, %11, %12, %13, %14, %15, "
      "%16, %17, %18, %19, %20, %21, %22, %23, %24, %25, %26, %27, %28, %29, %30, %31, "
      "%32, %33, %34, %35, %36, %37, %38, %39, %40, %41, %42, %43, %44, %45, %46, %47, "
      "%48, %49, %50, %51, %52, %53, %54, %55, %56, %57, %58, %59, %60, %61, %62, %63, "
      "%64, %65, %66, %67, %68, %69, %70, %71, %72, %73, %74, %75, %76, %77, %78, %79"
      "}, %80, %81, p, 1, 1, 0, 1;\n}\n"
    : "+f"(d[0]), "+f"(d[1]), "+f"(d[2]), "+f"(d[3]), "+f"(d[4]), "+f"(d[5]), "+f"(d[6]), "+f"(d[7]),
      "+f"(d[8]), "+f"(d[9]), "+f"(d[10]), "+f"(d[11]), "+f"(d[12]), "+f"(d[13]), "+f"(d[14]), "+f"(d[15]),
      "+f"(d[16]), "+f"(d[17]), "+f"(d[18]), "+f"(d[19]), "+f"(d[20]), "+f"(d[21]), "+f"(d[22]), "+f"(d[23]),
      "+f"(d[24]), "+f"(d[25]), "+f"(d[26]), "+f"(d[27]), "+f"(d[28]), "+f"(d[29]), "+f"(d[30]), "+f"(d[31]),
      "+f"(d[32]), "+f"(d[33]), "+f"(d[34]), "+f"(d[35]), "+f"(d[36]), "+f"(d[37]), "+f"(d[38]), "+f"(d[39]),
      "+f"(d[40]), "+f"(d[41]), "+f"(d[42]), "+f"(d[43]), "+f"(d[44]), "+f"(d[45]), "+f"(d[46]), "+f"(d[47]),
      "+f"(d[48]), "+f"(d[49]), "+f"(d[50]), "+f"(d[51]), "+f"(d[52]), "+f"(d[53]), "+f"(d[54]), "+f"(d[55]),
      "+f"(d[56]), "+f"(d[57]), "+f"(d[58]), "+f"(d[59]), "+f"(d[60]), "+f"(d[61]), "+f"(d[62]), "+f"(d[63]),
      "+f"(d[64]), "+f"(d[65]), "+f"(d[66]), "+f"(d[67]), "+f"(d[68]), "+f"(d[69]), "+f"(d[70]), "+f"(d[71]),
      "+f"(d[72]), "+f"(d[73]), "+f"(d[74]), "+f"(d[75]), "+f"(d[76]), "+f"(d[77]), "+f"(d[78]), "+f"(d[79])
    : "l"(da), "l"(db), "r"(sd));
}
__device__ __forceinline__ void wgmma_ss_n88(float (&d)[44], uint64_t da, uint64_t db, int sd) {
  asm volatile("{\n.reg .pred p;\nsetp.ne.b32 p, %46, 0;\n"
      "wgmma.mma_async.sync.aligned.m64n88k16.f32.bf16.bf16 {"
      "%0, %1, %2, %3, %4, %5, %6, %7, %8, %9, %10, %11, %12, %13, %14, %15, "
      "%16, %17, %18, %19, %20, %21, %22, %23, %24, %25, %26, %27, %28, %29, %30, %31, "
      "%32, %33, %34, %35, %36, %37, %38, %39, %40, %41, %42, %43"
      "}, %44, %45, p, 1, 1, 0, 1;\n}\n"
    : "+f"(d[0]), "+f"(d[1]), "+f"(d[2]), "+f"(d[3]), "+f"(d[4]), "+f"(d[5]), "+f"(d[6]), "+f"(d[7]),
      "+f"(d[8]), "+f"(d[9]), "+f"(d[10]), "+f"(d[11]), "+f"(d[12]), "+f"(d[13]), "+f"(d[14]), "+f"(d[15]),
      "+f"(d[16]), "+f"(d[17]), "+f"(d[18]), "+f"(d[19]), "+f"(d[20]), "+f"(d[21]), "+f"(d[22]), "+f"(d[23]),
      "+f"(d[24]), "+f"(d[25]), "+f"(d[26]), "+f"(d[27]), "+f"(d[28]), "+f"(d[29]), "+f"(d[30]), "+f"(d[31]),
      "+f"(d[32]), "+f"(d[33]), "+f"(d[34]), "+f"(d[35]), "+f"(d[36]), "+f"(d[37]), "+f"(d[38]), "+f"(d[39]),
      "+f"(d[40]), "+f"(d[41]), "+f"(d[42]), "+f"(d[43])
    : "l"(da), "l"(db), "r"(sd));
}
__device__ __forceinline__ void wgmma_ss_n80(float (&d)[40], uint64_t da, uint64_t db, int sd) {
  asm volatile("{\n.reg .pred p;\nsetp.ne.b32 p, %42, 0;\n"
      "wgmma.mma_async.sync.aligned.m64n80k16.f32.bf16.bf16 {"
      "%0, %1, %2, %3, %4, %5, %6, %7, %8, %9, %10, %11, %12, %13, %14, %15, "
      "%16, %17, %18, %19, %20, %21, %22, %23, %24, %25, %26, %27, %28, %29, %30, %31, "
      "%32, %33, %34, %35, %36, %37, %38, %39"
      "}, %40, %41, p, 1, 1, 0, 1;\n}\n"
    : "+f"(d[0]), "+f"(d[1]), "+f"(d[2]), "+f"(d[3]), "+f"(d[4]), "+f"(d[5]), "+f"(d[6]), "+f"(d[7]),
      "+f"(d[8]), "+f"(d[9]), "+f"(d[10]), "+f"(d[11]), "+f"(d[12]), "+f"(d[13]), "+f"(d[14]), "+f"(d[15]),
      "+f"(d[16]), "+f"(d[17]), "+f"(d[18]), "+f"(d[19]), "+f"(d[20]), "+f"(d[21]), "+f"(d[22]), "+f"(d[23]),
      "+f"(d[24]), "+f"(d[25]), "+f"(d[26]), "+f"(d[27]), "+f"(d[28]), "+f"(d[29]), "+f"(d[30]), "+f"(d[31]),
      "+f"(d[32]), "+f"(d[33]), "+f"(d[34]), "+f"(d[35]), "+f"(d[36]), "+f"(d[37]), "+f"(d[38]), "+f"(d[39])
    : "l"(da), "l"(db), "r"(sd));
}
__device__ __forceinline__ void wgmma_rs_n128(float (&d)[64], uint32_t a0, uint32_t a1, uint32_t a2, uint32_t a3,
                                  uint64_t db, int sd) {
  asm volatile("{\n.reg .pred p;\nsetp.ne.b32 p, %69, 0;\n"
      "wgmma.mma_async.sync.aligned.m64n128k16.f32.bf16.bf16 {"
      "%0, %1, %2, %3, %4, %5, %6, %7, %8, %9, %10, %11, %12, %13, %14, %15, "
      "%16, %17, %18, %19, %20, %21, %22, %23, %24, %25, %26, %27, %28, %29, %30, %31, "
      "%32, %33, %34, %35, %36, %37, %38, %39, %40, %41, %42, %43, %44, %45, %46, %47, "
      "%48, %49, %50, %51, %52, %53, %54, %55, %56, %57, %58, %59, %60, %61, %62, %63"
      "}, {%64, %65, %66, %67}, %68, p, 1, 1, 0;\n}\n"
    : "+f"(d[0]), "+f"(d[1]), "+f"(d[2]), "+f"(d[3]), "+f"(d[4]), "+f"(d[5]), "+f"(d[6]), "+f"(d[7]),
      "+f"(d[8]), "+f"(d[9]), "+f"(d[10]), "+f"(d[11]), "+f"(d[12]), "+f"(d[13]), "+f"(d[14]), "+f"(d[15]),
      "+f"(d[16]), "+f"(d[17]), "+f"(d[18]), "+f"(d[19]), "+f"(d[20]), "+f"(d[21]), "+f"(d[22]), "+f"(d[23]),
      "+f"(d[24]), "+f"(d[25]), "+f"(d[26]), "+f"(d[27]), "+f"(d[28]), "+f"(d[29]), "+f"(d[30]), "+f"(d[31]),
      "+f"(d[32]), "+f"(d[33]), "+f"(d[34]), "+f"(d[35]), "+f"(d[36]), "+f"(d[37]), "+f"(d[38]), "+f"(d[39]),
      "+f"(d[40]), "+f"(d[41]), "+f"(d[42]), "+f"(d[43]), "+f"(d[44]), "+f"(d[45]), "+f"(d[46]), "+f"(d[47]),
      "+f"(d[48]), "+f"(d[49]), "+f"(d[50]), "+f"(d[51]), "+f"(d[52]), "+f"(d[53]), "+f"(d[54]), "+f"(d[55]),
      "+f"(d[56]), "+f"(d[57]), "+f"(d[58]), "+f"(d[59]), "+f"(d[60]), "+f"(d[61]), "+f"(d[62]), "+f"(d[63])
    : "r"(a0), "r"(a1), "r"(a2), "r"(a3), "l"(db), "r"(sd));
}
__device__ __forceinline__ void wgmma_rs_n24(float (&d)[12], uint32_t a0, uint32_t a1, uint32_t a2, uint32_t a3,
                                  uint64_t db, int sd) {
  asm volatile("{\n.reg .pred p;\nsetp.ne.b32 p, %17, 0;\n"
      "wgmma.mma_async.sync.aligned.m64n24k16.f32.bf16.bf16 {"
      "%0, %1, %2, %3, %4, %5, %6, %7, %8, %9, %10, %11"
      "}, {%12, %13, %14, %15}, %16, p, 1, 1, 1;\n}\n"
    : "+f"(d[0]), "+f"(d[1]), "+f"(d[2]), "+f"(d[3]), "+f"(d[4]), "+f"(d[5]), "+f"(d[6]), "+f"(d[7]),
      "+f"(d[8]), "+f"(d[9]), "+f"(d[10]), "+f"(d[11])
    : "r"(a0), "r"(a1), "r"(a2), "r"(a3), "l"(db), "r"(sd));
}

#define KST 4
#define K1S 4
constexpr int K1_ST = K1S, K1_STAGE = 45056;
constexpr int K1_SMEM = K1_ST * K1_STAGE + 640   + 1536   + 2560   + 128;

__device__ __forceinline__ float2 row_stats(uint4 v0, uint4 v1, uint4 v2) {
  const uint32_t wd[12] = {v0.x, v0.y, v0.z, v0.w, v1.x, v1.y, v1.z, v1.w, v2.x, v2.y, v2.z, v2.w};
  float sx = 0.f, sq = 0.f;
#pragma unroll
  for (int e = 0; e < 12; e++) {
    const float lo = bf_lo(wd[e]), hi = bf_hi(wd[e]);
    sx += lo + hi; sq = fmaf(lo, lo, fmaf(hi, hi, sq));
  }
#pragma unroll
  for (int o = 16; o; o >>= 1) { sx += __shfl_xor_sync(~0u, sx, o); sq += __shfl_xor_sync(~0u, sq, o); }
  const float mean = sx * (1.f / D_);
  return make_float2(rsqrtf(fmaxf(sq * (1.f / D_) - mean * mean, 0.f) + 1e-5f), mean);
}

__global__ void __cluster_dims__(2, 1, 1) __launch_bounds__(512, 1)
k1_qkv(const __grid_constant__ CUtensorMap tmx, const __grid_constant__ CUtensorMap tmw,
       const bf16* __restrict__ x, const bf16* __restrict__ w, const bf16* __restrict__ wo) {
  extern __shared__ __align__(1024) uint8_t sm[];
  float* cs = (float*)(sm + K1_ST * K1_STAGE);
  float2* rowab = (float2*)(sm + K1_ST * K1_STAGE + 640);
  float* red = (float*)(sm + K1_ST * K1_STAGE + 2176);
  const uint32_t sbase = smem_u32(sm);
  const uint32_t fullb = sbase + K1_ST * K1_STAGE + 4736, emptyb = fullb + 8 * K1_ST;
  const int tid = threadIdx.x, lane = tid & 31;
  const int warp = __shfl_sync(~0u, tid >> 5, 0);
  const int rank = blockIdx.x & 1, cl = blockIdx.x >> 1;
  const int m = cl / 6, n = (cl - m * 6) * 2 + rank;
  if (tid == 0) STAMP(0, 0);

  if (warp == 12) {
    if (lane == 0) {
      prefetch_map(&tmx); prefetch_map(&tmw);
      for (int i = 0; i < K1_ST; i++) { mbar_init(fullb + 8 * i, 1); mbar_init(emptyb + 8 * i, 6); }
      asm volatile("fence.mbarrier_init.release.cluster;" ::: "memory");
    }
    __syncwarp();
    cluster_arrive();
    bar_arrive(4, 512);
    if (elect_one()) {
#pragma unroll
      for (int kt = 0; kt < K1_ST; kt++) mbar_expect(fullb + 8 * kt, K1_STAGE);
#pragma unroll
      for (int j = 0; j < 5; j++) tma2d(sbase + 24576 + j * 4096, &tmw, n * 160 + j * 32, 0, fullb);
    }
    cluster_wait();
#pragma unroll 1
    for (int kt = 0; kt < 10; kt++) {
      const int s = kt % K1_ST;
      const uint32_t sa = sbase + s * K1_STAGE;
      if (kt >= K1_ST) mbar_wait(emptyb + 8 * s, ((kt / K1_ST) - 1) & 1);
      if (elect_one()) {
        if (kt >= K1_ST) mbar_expect(fullb + 8 * s, K1_STAGE);
        tma2d_mc(sa + rank * 12288, &tmx, kt * 64, m * 192 + rank * 96, fullb + 8 * s);
        if (kt > 0) {
#pragma unroll
          for (int j = 0; j < 5; j++) tma2d(sa + 24576 + j * 4096, &tmw, n * 160 + j * 32, kt * 64, fullb + 8 * s);
        }
      }
      if (kt == K1_ST - 1) pdl_trigger();
    }
    __syncwarp();
    cluster_arrive();
  } else if (warp > 12) {
    cluster_arrive();
    const int t96 = tid - 416;
    const uint32_t tag = __ldcg(&g_epoch) + 1;
    bar_sync(4, 512);
    mbar_wait(fullb, 0);
    if (m < 10) {
      const int ck = t96 % 20, rg = min(t96 / 20, 3);
      uint4 wv[16];
#pragma unroll
      for (int i = 0; i < 16; i++) wv[i] = ldg_nc(w + (size_t)(m * 64 + rg * 16 + i) * 1920 + n * 160 + ck * 8);
      float acc8[8];
#pragma unroll
      for (int i = 0; i < 8; i++) acc8[i] = 0.f;
#pragma unroll
      for (int i = 0; i < 16; i++) ACC8(acc8, wv[i]);
      *(float4*)&red[rg * 160 + ck * 8] = make_float4(acc8[0], acc8[1], acc8[2], acc8[3]);
      *(float4*)&red[rg * 160 + ck * 8 + 4] = make_float4(acc8[4], acc8[5], acc8[6], acc8[7]);
      bar_sync(1, 96);
      if (t96 < 80) {
        const float2 p0 = *(const float2*)&red[t96 * 2], p1 = *(const float2*)&red[160 + t96 * 2];
        const float2 p2 = *(const float2*)&red[320 + t96 * 2], p3 = *(const float2*)&red[480 + t96 * 2];
        st_relaxed(&g_cpart[(m * 12 + n) * 80 + t96], (p0.x + p1.x) + (p2.x + p3.x), (p0.y + p1.y) + (p2.y + p3.y), tag);
      }
    }
    if (tid == 416) STAMP(5, 7);
    bool ok = false;
    for (int it = 0; it < 64 && !ok; it++) {
      uint4 p[10], st[2];
#pragma unroll
      for (int k = 0; k < 10; k++) p[k] = ld_relaxed(&g_cpart[(k * 12 + n) * 80 + min(t96, 79)]);
#pragma unroll
      for (int k = 0; k < 2; k++) st[k] = ld_relaxed(&g_rowstat[min(m * 192 + k * 96 + t96, S_ - 1)]);
      ok = true;
      float s0 = 0.f, s1 = 0.f;
#pragma unroll
      for (int k = 0; k < 10; k++) {
        ok = ok && p[k].y == tag && p[k].w == tag;
        s0 += __uint_as_float(p[k].x); s1 += __uint_as_float(p[k].z);
      }
      if (t96 < 80) *(float2*)&cs[t96 * 2] = make_float2(s0, s1);
#pragma unroll
      for (int k = 0; k < 2; k++) {
        ok = ok && st[k].y == tag && st[k].w == tag;
        rowab[k * 96 + t96] = make_float2(__uint_as_float(st[k].x), -__uint_as_float(st[k].x) * __uint_as_float(st[k].z));
      }
      ok = __all_sync(~0u, ok);
      if (!ok) __nanosleep(300);
    }
    if (!ok) {
      const int c2 = min(t96, 79);
      float s0 = 0.f, s1 = 0.f;
#pragma unroll 1
      for (int k = 0; k < D_; k++) {
        const uint32_t v = *(const uint32_t*)(w + (size_t)k * 1920 + n * 160 + c2 * 2);
        s0 += bf_lo(v); s1 += bf_hi(v);
      }
      if (t96 < 80) *(float2*)&cs[t96 * 2] = make_float2(s0, s1);
#pragma unroll 1
      for (int i = 0; i < 64; i++) {
        const int r = (i >> 5) * 96 + (t96 & ~31) + (i & 31);
        const bf16* xr = x + (size_t)min(m * 192 + r, S_ - 1) * D_ + lane * 8;
        const float2 st = row_stats(ldg_nc(xr), ldg_nc(xr + 256), lane < 16 ? ldg_nc(xr + 512) : make_uint4(0u, 0u, 0u, 0u));
        if (lane == 0) rowab[r] = make_float2(st.x, -st.x * st.y);
      }
    }
    __syncwarp();
    bar_arrive(2, 96 + 384);
    bar_sync(1, 96);
    if (tid == 416) STAMP(0, 5);
    if (blockIdx.x < 128) {
      uint4 v[5];
      const int ck = min(t96, 79), nt = ck / 10;
#pragma unroll
      for (int i = 0; i < 5; i++) {
        const int k = blockIdx.x * 5 + i, pr = k / 40, r = k - pr * 40;
        v[i] = ldg_nc(wo + (size_t)(pr * 40 + (r < 16 ? r : (r < 32 ? r + 4 : (r < 36 ? r - 16 : r)))) * D_ + ck * 8);
      }
#pragma unroll
      for (int i = 0; i < 5; i++) {
        const int k = blockIdx.x * 5 + i;
        g_wo[((nt * 10 + (k >> 6)) * 10 + ck - nt * 10) * 64 + (k & 63)] = v[i];
        float t = ((bf_lo(v[i].x) + bf_hi(v[i].x)) + (bf_lo(v[i].y) + bf_hi(v[i].y))) +
                  ((bf_lo(v[i].z) + bf_hi(v[i].z)) + (bf_lo(v[i].w) + bf_hi(v[i].w)));
        if (t96 >= 80) t = 0.f;
#pragma unroll
        for (int o = 16; o; o >>= 1) t += __shfl_xor_sync(~0u, t, o);
        if (lane == 0) red[(t96 >> 5) * 8 + i] = t;
      }
      bar_sync(1, 96);
      if (t96 < 5) {
        const float mu = (red[t96] + red[8 + t96] + red[16 + t96]) * (1.f / D_);
        const float hi = bf_lo(pack_bf16(mu, 0.f));
        g_wm[blockIdx.x * 5 + t96] = make_uint4(pack_bf16(hi, mu - hi), 0u, 0u, 0u);
      }
    }
    if (tid == 416) STAMP(0, 7);
    __syncwarp();
    cluster_wait();
    cluster_arrive();
  } else {
    cluster_arrive();
    float acc[80];
    const uint64_t da0 = mkdesc(sbase + (warp >> 2) * 8192, 16, 1024, 1);
    const uint64_t db0 = mkdesc(sbase + 24576, 4096, 512, 2);
    const uint32_t tag = __ldcg(&g_epoch) + 1;
    const int srow = m * 192 + n * 16 + warp * 2;
    const bool dostat = warp < 8 && srow < S_;
    uint4 xv[2][3];
    bar_sync(4, 512);
    cluster_wait();
#pragma unroll
    for (int kt = 0; kt < 10; kt++) {
      const int s = kt % K1_ST;
      mbar_wait(fullb + 8 * s, (kt / K1_ST) & 1);
      if (kt == 0 && tid == 0) STAMP(0, 1);
      if (kt == 2 && tid == 0) STAMP(5, 0);
      if (kt == 4 && tid == 0) STAMP(5, 1);
      if (kt == 7 && tid == 0) STAMP(5, 2);
      const uint64_t da = da0 + s * (K1_STAGE >> 4), db = db0 + s * (K1_STAGE >> 4);
      WG_FENCE();
#pragma unroll
      for (int k = 0; k < 4; k++) wgmma_ss_n160(acc, da + k * 2, db + k * 64, (kt | k) != 0);
      WG_COMMIT();
      if (kt > 0) {
        WG_WAIT(1);
        if (kt - 1 + K1_ST < 10 && (tid & 127) < 2) mbar_arrive_cta(emptyb + 8 * ((kt - 1) % K1_ST), tid & 1);
      }
      if (kt == 0) {
#pragma unroll
        for (int i = 0; i < 2; i++) {
          const bf16* xr = x + (size_t)min(srow + i, S_ - 1) * D_ + lane * 8;
          xv[i][0] = xv[i][1] = xv[i][2] = make_uint4(0u, 0u, 0u, 0u);
          if (dostat) { xv[i][0] = ldg_nc(xr); xv[i][1] = ldg_nc(xr + 256); }
          if (dostat && lane < 16) xv[i][2] = ldg_nc(xr + 512);
        }
      }
      if ((kt == KST || kt == KST + 1) && dostat) {
        const float2 st = row_stats(xv[kt - KST][0], xv[kt - KST][1], xv[kt - KST][2]);
        if (lane == 0) st_relaxed(&g_rowstat[srow + kt - KST], st.x, st.y, tag);
      }
      __syncwarp();
    }
    cluster_arrive();
    WG_WAIT(0);
    fence_regs(acc);
    if (tid == 0) STAMP(0, 2);
    bar_sync(2, 96 + 384);
    if (tid == 0) STAMP(0, 3);
    const int row0 = m * 192 + warp * 16;
    if (row0 < S_) {
      const int g = lane >> 2, c = lane & 3, sec = n >> 2, grp = (row0 & 127) >> 3;
      const bool lo = c < 2;
      const float2 ab0 = rowab[warp * 16 + g], ab1 = rowab[warp * 16 + g + 8];
      const bool p0 = sec == 1 && ((POLY_MASK >> grp) & 1), p1 = sec == 1 && ((POLY_MASK >> (grp + 1)) & 1);
      const uint32_t padqv = sec == 0 ? (c == 2 ? 0x3F803F80u : 0x00003F80u) : (sec == 2 && c == 2 ? 0x00003F80u : 0u);
      const uint32_t padk = c == 2 ? 0x4A7A4B00u : 0x00004653u;
      const uint32_t pad0 = p0 ? padk : padqv, pad1 = p1 ? padk : padqv;
      const float f0 = sec == 0 ? QSCALE : (p0 ? 32768.f : 1.f), f1 = sec == 0 ? QSCALE : (p1 ? 32768.f : 1.f);
      const float a0 = ab0.x * f0, b0 = ab0.y * f0, a1 = ab1.x * f1, b1 = ab1.y * f1;
      const float r0 = p0 ? 9.313225746154785e-10f : 1.f, r1 = p1 ? 9.313225746154785e-10f : 1.f;
      const int cst = sec == 1 ? 2048 : 128, gst = sec == 1 ? 128 : 384;
      uint8_t* pe = (uint8_t*)g_qkv + (size_t)(n * 8) * HEAD_IMG + (row0 >> 7) * 6144 + grp * gst + lane * 4;
      uint8_t* pe1 = pe + cst;
      uint8_t* pe2 = pe1 + cst;
      uint8_t* pf = pe + gst;
      uint8_t* pf1 = pf + cst;
      uint8_t* pf2 = pf1 + cst;
      uint32_t u[20], v[20];
#pragma unroll
      for (int hp = 0; hp < 4; hp++) {
#pragma unroll
        for (int j = hp * 5; j < hp * 5 + 5; j++) {
          const float2 t = *(const float2*)&cs[j * 8 + c * 2];
          u[j] = pack_bf16(fmaf(acc[4 * j], a0, b0 * t.x), fmaf(acc[4 * j + 1], a0, b0 * t.y));
          v[j] = pack_bf16(fmaf(acc[4 * j + 2], a1, b1 * t.x), fmaf(acc[4 * j + 3], a1, b1 * t.y));
        }
        constexpr int HE = HEAD_IMG;
        const int oe = hp * 2 * HE, oo = oe + HE, j = hp * 5;
        *(uint32_t*)(pe + oe) = u[j];      *(uint32_t*)(pf + oe) = v[j];
        *(uint32_t*)(pe1 + oe) = u[j + 1]; *(uint32_t*)(pf1 + oe) = v[j + 1];
        *(uint32_t*)(pe2 + oe) = lo ? u[j + 2] : pad0; *(uint32_t*)(pf2 + oe) = lo ? v[j + 2] : pad1;
        *(uint32_t*)(pe + oo) = __shfl_xor_sync(~0u, lo ? u[j + 3] : u[j + 2], 2);
        *(uint32_t*)(pf + oo) = __shfl_xor_sync(~0u, lo ? v[j + 3] : v[j + 2], 2);
        *(uint32_t*)(pe1 + oo) = __shfl_xor_sync(~0u, lo ? u[j + 4] : u[j + 3], 2);
        *(uint32_t*)(pf1 + oo) = __shfl_xor_sync(~0u, lo ? v[j + 4] : v[j + 3], 2);
        const uint32_t tu = __shfl_xor_sync(~0u, u[j + 4], 2), tv = __shfl_xor_sync(~0u, v[j + 4], 2);
        *(uint32_t*)(pe2 + oo) = lo ? tu : pad0; *(uint32_t*)(pf2 + oo) = lo ? tv : pad1;
      }
      if (tid == 0) STAMP(5, 3);
      if (sec < 2) {
        float nm = 0.f;
#pragma unroll
        for (int hp = 0; hp < 4; hp++) {
          float sq[2][5];
#pragma unroll
          for (int i = 0; i < 5; i++) {
            const uint32_t x = u[hp * 5 + i], y = v[hp * 5 + i];
            sq[0][i] = fmaf(bf_lo(x), bf_lo(x), bf_hi(x) * bf_hi(x));
            sq[1][i] = fmaf(bf_lo(y), bf_lo(y), bf_hi(y) * bf_hi(y));
          }
          const float e0 = (sq[0][0] + sq[0][1] + (lo ? sq[0][2] : 0.f)) * r0, e1 = (sq[1][0] + sq[1][1] + (lo ? sq[1][2] : 0.f)) * r1;
          const float o0 = (sq[0][3] + sq[0][4] + (lo ? 0.f : sq[0][2])) * r0, o1 = (sq[1][3] + sq[1][4] + (lo ? 0.f : sq[1][2])) * r1;
          const float k0 = (lo ? e0 : o0) + __shfl_xor_sync(~0u, lo ? o0 : e0, 2);
          const float k1 = (lo ? e1 : o1) + __shfl_xor_sync(~0u, lo ? o1 : e1, 2);
          const float z = ((c & 1) ? k1 : k0) + __shfl_xor_sync(~0u, (c & 1) ? k0 : k1, 1);
          const uint32_t em = __reduce_max_sync(~0u, lo ? __float_as_uint(z) : 0u), om = __reduce_max_sync(~0u, lo ? 0u : __float_as_uint(z));
          if ((lane >> 1) == hp) nm = __uint_as_float((lane & 1) ? om : em);
        }
        if (lane < 8) g_nrm[(n * 8 + lane) * 128 + (row0 >> 4)] = nm;
      }
    }
    if (tid == 0) STAMP(0, 4);
  }
  cluster_wait();
  if (tid == 0) STAMP(0, 6);
}

constexpr int K2_SMEM = 2 * HEAD_IMG + 2 * 6144 + 2 * 10240 + 256;

__device__ __forceinline__ uint64_t desc64(uint32_t lo, uint32_t hi) {
  uint64_t d;
  asm("mov.b64 %0, {%1, %2};" : "=l"(d) : "r"(lo), "r"(hi));
  return d;
}
__device__ __forceinline__ uint32_t exp_pair(bool poly, float a, float b, uint32_t mk) {
  if (poly) {
    const uint32_t pk = __byte_perm(__float_as_uint(a), __float_as_uint(b), 0x6521);
    uint32_t m, q;
    asm("lop3.b32 %0, %1, %2, 0x3f803f80, 0xEA;" : "=r"(m) : "r"(pk), "r"(mk));
    asm("fma.rn.bf16x2 %0, %1, %1, %2;" : "=r"(q) : "r"(m), "r"(0x40014001u));
    return pk - m + q;
  }
  return pack_bf16(ex2(a), ex2(b));
}
#define PV_GR 4
__device__ __forceinline__ void exp_pv(const float (&s)[64], float (&o)[12], uint64_t dv, uint32_t mk) {
#pragma unroll
  for (int k0 = 0; k0 < 8; k0 += PV_GR) {
    uint32_t p[4 * PV_GR];
#pragma unroll
    for (int i = 0; i < 4 * PV_GR; i++)
      p[i] = exp_pair((POLY_MASK >> (k0 * 2 + i / 2)) & 1, s[k0 * 8 + 2 * i], s[k0 * 8 + 2 * i + 1], mk);
    WG_FENCE();
#pragma unroll
    for (int k = 0; k < PV_GR; k++)
      wgmma_rs_n24(o, p[4 * k], p[4 * k + 1], p[4 * k + 2], p[4 * k + 3], dv + (k0 + k) * 48, 1);
  }
}
__device__ __forceinline__ void load_q(uint32_t (&q)[6], const uint8_t* p) {
  q[0] = __ldcg((const uint32_t*)p);         q[1] = __ldcg((const uint32_t*)(p + 384));
  q[2] = __ldcg((const uint32_t*)(p + 128)); q[3] = __ldcg((const uint32_t*)(p + 512));
  q[4] = __ldcg((const uint32_t*)(p + 256)); q[5] = __ldcg((const uint32_t*)(p + 640));
}
__device__ __forceinline__ float rcp(float x) {
  float y;
  asm("rcp.approx.ftz.f32 %0, %1;" : "=f"(y) : "f"(x));
  return y;
}
__device__ __forceinline__ int img_off(int chunk) { return chunk * 2048; }
__device__ __forceinline__ void store_o(const float (&o)[12], int tile) {
  int tid, bid;
  asm volatile("mov.u32 %0, %%tid.x;" : "=r"(tid));
  asm volatile("mov.u32 %0, %%ctaid.x;" : "=r"(bid));
  const int head = bid >> 2;
  uint8_t* dst = (uint8_t*)g_o + ((bid & 3) * 4 + (tile >> 1)) * 163840 + (tile & 1) * 1024 + ((tid >> 5) & 3) * 256 + (tid & 31) * 4;
  const int oc = (head >> 1) * 5 + (head & 1) * 2;
  const int o0 = img_off(oc), o1 = img_off(oc + 1), o2 = img_off((head >> 1) * 5 + 4) + (head & 1) * 8;
  const float i0 = rcp(__shfl_sync(~0u, o[8], 2, 4)), i1 = rcp(__shfl_sync(~0u, o[10], 2, 4));
  *(uint32_t*)(dst + o0) = pack_bf16(o[0] * i0, o[1] * i0); *(uint32_t*)(dst + o0 + 128) = pack_bf16(o[2] * i1, o[3] * i1);
  *(uint32_t*)(dst + o1) = pack_bf16(o[4] * i0, o[5] * i0); *(uint32_t*)(dst + o1 + 128) = pack_bf16(o[6] * i1, o[7] * i1);
  if ((tid & 3) < 2) {
    *(uint32_t*)(dst + o2) = pack_bf16(o[8] * i0, o[9] * i0);
    *(uint32_t*)(dst + o2 + 128) = pack_bf16(o[10] * i1, o[11] * i1);
  }
}

struct Maps5 { CUtensorMap m[5]; };

__global__ void __launch_bounds__(512, 1)
k2_attn(const __grid_constant__ Maps5 maps, uint32_t mk) {
  const CUtensorMap* tmw = maps.m;
  extern __shared__ __align__(1024) uint8_t sm[];
  const uint32_t sbase = smem_u32(sm);
  float* part = (float*)(sm + 2 * HEAD_IMG);
  const uint32_t rbuf = sbase + 2 * HEAD_IMG + 2 * 6144;
  const uint32_t kvb = rbuf + 2 * 10240;
  const uint32_t partb = kvb + 128, rbar = kvb + 144;
  const int tid = threadIdx.x, lane = tid & 31;
  const int warp = __shfl_sync(~0u, tid >> 5, 0);
  const int head = blockIdx.x >> 2, qb = blockIdx.x & 3;

  if (tid == 0) STAMP(1, 0);
  if (tid == 0) {
    for (int i = 0; i < 16; i++) mbar_init(kvb + 8 * i, 1);
    mbar_init(partb, 128); mbar_init(partb + 8, 128); mbar_init(rbar, 1); mbar_init(rbar + 8, 1);
    asm volatile("fence.mbarrier_init.release.cluster;" ::: "memory");
  }
  __syncthreads();

  if (warp >= 12) {
    asm volatile("setmaxnreg.dec.sync.aligned.u32 32;");
    if (tid == 384) {
      pdl_wait();
      pdl_trigger();
      const uint8_t* kimg = (const uint8_t*)g_qkv + (size_t)(32 + head) * HEAD_IMG;
#pragma unroll 1
      for (int b = 0; b < 16; b++) {
        mbar_expect(kvb + 8 * b, 12288);
        bulk_ld(sbase + b * 6144, kimg + b * 6144, 6144, kvb + 8 * b);
        bulk_ld(sbase + HEAD_IMG + b * 6144, kimg + 32 * HEAD_IMG + b * 6144, 6144, kvb + 8 * b);
        if (b >= 2) mbar_wait(kvb + 8 * (b - 1), 0);

      }
      if (blockIdx.x == 0) g_epoch = g_epoch + 1;
      mbar_wait(kvb + 8 * 15, 0);
      STAMP(1, 2);
      uint8_t* pdst = nullptr;
      uint32_t pbytes = 0;
#pragma unroll 1
      for (int i = 0; i < 8; i++) {
        const int p = blockIdx.x + 128 * i;
        uint8_t* dst = nullptr;
        uint32_t bytes = 0;
        if (i < 7 && p < 856) {
          asm volatile("cp.async.bulk.wait_group.read 0;" ::: "memory");
          const CUtensorMap* tm;
          int c1, c2;
          if (p < 640) {
            const int nt = p / 80, r = p - nt * 80, ph = r / 40, st = (r - ph * 40) >> 1, up = r & 1;
            bytes = ph ? 6656 : 7168;
            dst = (uint8_t*)g_wgu + nt * 552960 + ph * 286720 + st * 2 * bytes + up * (bytes >> 1);
            tm = &tmw[ph * 2 + up]; c1 = ph ? 112 + nt * 13 : nt * 14; c2 = st * 2;
          } else {
            const int nk = p - 640, nt = nk / 27;
            bytes = 10240;
            dst = (uint8_t*)g_wd + (size_t)nk * 10240;
            tm = &tmw[4]; c1 = nt * 10; c2 = nk - nt * 27;
          }
          mbar_expect(rbar + 8 * (i & 1), bytes);
          tma4d(rbuf + (i & 1) * 10240, tm, c1, c2, rbar + 8 * (i & 1));
        }
        if (pbytes) {
          mbar_wait(rbar + 8 * ((i - 1) & 1), ((i - 1) >> 1) & 1);
          if (pbytes == 10240) {
            bulk_st(pdst, rbuf + ((i - 1) & 1) * 10240, pbytes);
          } else {
            bulk_st(pdst, rbuf + ((i - 1) & 1) * 10240, pbytes >> 1);
            bulk_st(pdst + pbytes, rbuf + ((i - 1) & 1) * 10240 + (pbytes >> 1), pbytes >> 1);
          }
          asm volatile("cp.async.bulk.commit_group;" ::: "memory");
        }
        pdst = dst; pbytes = bytes;
      }
      asm volatile("cp.async.bulk.wait_group.read 0;" ::: "memory");
      STAMP(1, 6);
    }
  } else {
    asm volatile("setmaxnreg.inc.sync.aligned.u32 160;");
    const int wg = warp >> 2;
    const uint8_t* qthr = (const uint8_t*)g_qkv + (size_t)head * HEAD_IMG + qb * 64 * 384 + (warp & 3) * 768 + lane * 4;
    const uint32_t klo0 = ((sbase & 0x3FFFF) >> 4) | (128u << 16), vlo0 = (((sbase + HEAD_IMG) & 0x3FFFF) >> 4) | (24u << 16);
    constexpr uint64_t KSTEP2 = (uint64_t)(int64_t)(256 - (128 << 16));
    constexpr uint64_t KV2K = 384 - (HEAD_IMG >> 4) + (104 << 16);
    const int nun = wg == 1 ? 4 : 3;
    uint32_t utile = wg == 0 ? 0x210u : (wg == 1 ? 0x4235u : 0x576u);
    uint32_t ubeg = wg == 0 ? 0u : (wg == 1 ? 0x0b00u : 0x600u);
    uint32_t ulen = wg == 0 ? 0x0b1010u : (wg == 1 ? 0x10051006u : 0x0a1010u);
    pdl_wait();
    if (tid == 0) STAMP(1, 1);
    uint32_t q[6];
    load_q(q, qthr + (utile & 15) * 3072);
    bool fast;
    {
      const float4 kn = __ldcg((const float4*)&g_nrm[(32 + head) * 128 + lane * 4]);
      const float qv = __ldcg(&g_nrm[head * 128 + qb * 32 + lane]);
      const uint32_t km = max(max(__float_as_uint(kn.x), __float_as_uint(kn.y)), max(__float_as_uint(kn.z), __float_as_uint(kn.w)));
      const float k2 = __uint_as_float(__reduce_max_sync(~0u, km)), q2 = __uint_as_float(__reduce_max_sync(~0u, __float_as_uint(qv)));
      fast = q2 * k2 <= 3400.f;
    }
    if (fast) {
#pragma unroll 1
      for (int u = 0; u < nun; u++) {
        const uint32_t b0 = ubeg & 15;
        const bool wt = u == 0 || (wg == 1 && u == 1);
        float s[64], o[12];
#pragma unroll
        for (int i = 0; i < 12; i++) o[i] = 0.f;
        uint32_t vlo = vlo0 + b0 * 384, kb = kvb + b0 * 8;
        const uint32_t vend = vlo + ((ulen & 255) - 1) * 384;
        if (wt) mbar_wait(kb, 0);
        if (tid == 0) STAMP(5, 4 + u);
        fence_regs(o);
        WG_FENCE();
        wgmma_rs_n128(s, q[0], q[1], q[2], q[3], desc64(klo0 + b0 * 384, 8), 0);
        wgmma_rs_n128(s, q[4], q[5], 0, 0, desc64(klo0 + b0 * 384, 8) + KSTEP2, 1);
        WG_COMMIT();
#define K2UNR 1
        constexpr int kUnr = K2UNR;
#pragma unroll kUnr
        for (; vlo != vend; vlo += 384) {
          if (wt) { kb += 8; mbar_wait(kb, 0); }
          WG_WAIT(0);
          fence_regs(s); fence_regs(o);
          const uint64_t dv = desc64(vlo, 8);
          exp_pv(s, o, dv, mk);
          wgmma_rs_n128(s, q[0], q[1], q[2], q[3], dv + KV2K, 0);
          wgmma_rs_n128(s, q[4], q[5], 0, 0, dv + (KV2K + KSTEP2), 1);
          WG_COMMIT();
        }
        WG_WAIT(0);
        fence_regs(s); fence_regs(o);
        if (u + 1 < nun) load_q(q, qthr + ((utile >> 4) & 15) * 3072);
        exp_pv(s, o, desc64(vlo, 8), mk);
        WG_COMMIT();
        WG_WAIT(0);
        fence_regs(o);
        if (wg == 1 && !(u & 1)) {
          float4* pp = (float4*)(part + u * 768) + (tid & 127);
          pp[0] = make_float4(o[0], o[1], o[2], o[3]);
          pp[128] = make_float4(o[4], o[5], o[6], o[7]);
          pp[256] = make_float4(o[8], o[9], o[10], o[11]);
          mbar_arrive(partb + 4 * u);
        } else {
          if (wg != 1 && u == 2) {
            const int pi = wg == 0 ? 1 : 0;
            mbar_wait(partb + 8 * pi, 0);
            const float4* pp = (const float4*)(part + pi * 1536) + (tid & 127);
            const float4 x0 = pp[0], x1 = pp[128], x2 = pp[256];
            o[0] += x0.x; o[1] += x0.y; o[2] += x0.z; o[3] += x0.w; o[4] += x1.x; o[5] += x1.y;
            o[6] += x1.z; o[7] += x1.w; o[8] += x2.x; o[9] += x2.y; o[10] += x2.z; o[11] += x2.w;
          }
          store_o(o, utile & 15);
        }
        utile >>= 4; ubeg >>= 4; ulen >>= 8;
      }
      if ((tid & 127) == 0) STAMP(1, 3 + wg);
    } else {
#pragma unroll 1
      for (int tile = wg; tile < 8; tile += 3) {
        load_q(q, qthr + tile * 3072);
        if ((lane & 3) >= 2) { q[4] = 0; q[5] = 0; }
        float o[12], m0 = -INFINITY, m1 = -INFINITY;
#pragma unroll
        for (int i = 0; i < 12; i++) o[i] = 0.f;
#pragma unroll 1
        for (int b = 0; b < 16; b++) {
          float s[64];
          mbar_wait(kvb + 8 * b, 0);
          WG_FENCE();
          wgmma_rs_n128(s, q[0], q[1], q[2], q[3], desc64(klo0 + b * 384, 8), 0);
          wgmma_rs_n128(s, q[4], q[5], 0, 0, desc64(klo0 + b * 384, 8) + KSTEP2, 1);
          WG_COMMIT();
          WG_WAIT(0);
          fence_regs(s);
          float x0 = m0, x1 = m1;
#pragma unroll
          for (int j = 0; j < 16; j++) {
            if ((POLY_MASK >> j) & 1) {
#pragma unroll
              for (int i = 0; i < 4; i++) s[4 * j + i] *= (1.f / 32768.f);
            }
            x0 = fmaxf(x0, fmaxf(s[4 * j], s[4 * j + 1]));
            x1 = fmaxf(x1, fmaxf(s[4 * j + 2], s[4 * j + 3]));
          }
          x0 = fmaxf(x0, __shfl_xor_sync(~0u, x0, 1)); x0 = fmaxf(x0, __shfl_xor_sync(~0u, x0, 2));
          x1 = fmaxf(x1, __shfl_xor_sync(~0u, x1, 1)); x1 = fmaxf(x1, __shfl_xor_sync(~0u, x1, 2));
          const float al0 = ex2(m0 - x0), al1 = ex2(m1 - x1);
          m0 = x0; m1 = x1;
#pragma unroll
          for (int i = 0; i < 12; i++) o[i] *= (i & 2) ? al1 : al0;
          uint32_t p[32];
#pragma unroll
          for (int i = 0; i < 32; i++) {
            const float mm = (i & 1) ? m1 : m0;
            p[i] = pack_bf16(ex2(s[2 * i] - mm), ex2(s[2 * i + 1] - mm));
          }
          fence_regs(o);
          WG_FENCE();
#pragma unroll
          for (int k = 0; k < 8; k++)
            wgmma_rs_n24(o, p[4 * k], p[4 * k + 1], p[4 * k + 2], p[4 * k + 3], desc64(vlo0 + b * 384 + k * 48, 8), 1);
          WG_COMMIT();
          WG_WAIT(0);
          fence_regs(o);
        }
        store_o(o, tile);
      }
    }
  }
}

#define K3S 4
#define K3NB 4
#define K3P 1
constexpr int K3_ST = K3S, K3_STAGE = 37888, K3_PRE = K3P;
constexpr int K3_SMEM = K3_ST * K3_STAGE + 24576 + 20480 + 256;

template <int N> struct Acc { float v[N]; };

template <int NB, int NK, bool FIRST>
__global__ void __cluster_dims__(2, 1, 1) __launch_bounds__(384, 1)
k3_proj(const __grid_constant__ CUtensorMap tmr, const uint4* __restrict__ aimg, const uint4* __restrict__ wimg) {
  constexpr int KT = 2 * NB + NK, EX = FIRST ? 1 : 0;
  extern __shared__ __align__(1024) uint8_t sm[];
  const uint32_t sbase = smem_u32(sm);
  uint8_t* xch = sm + K3_ST * K3_STAGE;
  uint8_t* stg = sm + K3_ST * K3_STAGE + 24576;
  const uint32_t fullb = smem_u32(stg) + 20480, emptyb = fullb + 8 * K3_ST, resb = emptyb + 8 * K3_ST, xchb = resb + 8;
  const int tid = threadIdx.x, lane = tid & 31;
  const int warp = __shfl_sync(~0u, tid >> 5, 0);
  const int rank = blockIdx.x & 1;
  const int n = blockIdx.x & 7, m = blockIdx.x >> 3;
  if (tid == 0) STAMP(FIRST ? 2 : 4, 0);
  if (warp == 0) {
    if (lane == 0) {
      prefetch_map(&tmr);
      for (int i = 0; i < K3_ST; i++) { mbar_init(fullb + 8 * i, 1); mbar_init(emptyb + 8 * i, 4); }
      mbar_init(resb, 1); mbar_init(xchb, 1);
      mbar_expect(xchb, 4096 * (5 + EX));
      asm volatile("fence.mbarrier_init.release.cluster;" ::: "memory");
    }
    __syncwarp();
    cluster_arrive();
    bar_arrive(4, 256 + 32);
    const uint8_t* wk = (const uint8_t*)wimg + (size_t)n * KT * 10240;
    const uint8_t* ws = (const uint8_t*)wimg + (size_t)(n ^ 1) * KT * 10240;
    const uint8_t* ab = (const uint8_t*)aimg + (size_t)m * KT * 16384;
    auto load_w = [&](int i) {
      const int s = i % K3_ST, kt = i < NB ? i + rank * (NB + NK) : i;
      const uint32_t sa = sbase + s * K3_STAGE;
      mbar_expect(fullb + 8 * s, 26624 + EX * 1024 + (i < NB ? 10240 : 0));
      bulk_ld(sa + 16384, wk + kt * 10240, 10240, fullb + 8 * s);
      if (FIRST) bulk_ld(sa + 26624, (const uint8_t*)g_wm + kt * 1024, 1024, fullb + 8 * s);
      if (i < NB) bulk_ld(sa + 26624 + EX * 1024, ws + kt * 10240, 10240, fullb + 8 * s);
    };
    if (elect_one()) {
#pragma unroll 1
      for (int i = 0; i < K3_PRE; i++) load_w(i);
    }
    cluster_wait();
    pdl_wait();
    pdl_trigger();
    if (lane == 0) STAMP(2, 6);
#pragma unroll 1
    for (int i = 0; i < NB + NK; i++) {
      const int s = i % K3_ST;
      const uint32_t sa = sbase + s * K3_STAGE;
      if (i >= K3_ST) mbar_wait(emptyb + 8 * s, ((i / K3_ST) - 1) & 1);
      if (elect_one()) {
        if (i < NB) bulk_ld(sa, ab + (i + rank * (NB + NK)) * 16384, 16384, fullb + 8 * s);
        else bulk_ld_mc(sa + rank * 8192, ab + i * 16384 + rank * 8192, 8192, fullb + 8 * s);
        if (i >= K3_PRE) load_w(i);
        if (FIRST && i == K3_ST - 1) {
          mbar_expect(resb, 20480);
          tma2d(smem_u32(stg), &tmr, n * 80, m * 128, resb);
          tma2d(smem_u32(stg) + 10240, &tmr, n * 80, m * 128 + 64, resb);
        }
      }
    }
    __syncwarp();
    cluster_arrive();
  } else if (warp >= 4) {
    cluster_arrive();
    const int cw = warp - 4, wg = cw >> 2;
    const int g = lane >> 2, c = lane & 3;
    const int row = m * 128 + cw * 16 + g;
    uint8_t* himg = (uint8_t*)g_h + (size_t)m * 163840 + cw * 256 + lane * 4;
    uint32_t rv[20];
    float mu0, mu1;
    if (FIRST) {
      mu0 = __uint_as_float(__ldcg(&g_rowstat[row].z)); mu1 = __uint_as_float(__ldcg(&g_rowstat[row + 8].z));
    } else {
      mu0 = __ldcg(&g_hmean[row]); mu1 = __ldcg(&g_hmean[row + 8]);
#pragma unroll
      for (int j = 0; j < 10; j++) {
        rv[2 * j] = __ldcg((const uint32_t*)(himg + img_off(n * 10 + j)));
        rv[2 * j + 1] = __ldcg((const uint32_t*)(himg + img_off(n * 10 + j) + 128));
      }
    }
    float acc[80 + 4 * EX];
    float (&keep)[40 + 4 * EX] = ((Acc<40 + 4 * EX>*)acc)->v;
    const uint64_t da0 = mkdesc(sbase + wg * 1024, 2048, 128, 0);
    const uint64_t db0 = mkdesc(sbase + 16384, 128, 1024, 0);
    bar_sync(4, 256 + 32);
    cluster_wait();
#pragma unroll 1
    for (int i = 0; i < NB; i++) {
      const int s = i % K3_ST;
      mbar_wait(fullb + 8 * s, (i / K3_ST) & 1);
      if (i == 0 && tid == 128) STAMP(FIRST ? 2 : 4, 2);
      const uint64_t da = da0 + s * (K3_STAGE >> 4), db = db0 + s * (K3_STAGE >> 4);
      WG_FENCE();
#pragma unroll
      for (int k = 0; k < 4; k++) {
        if constexpr (FIRST) wgmma_ss_n168(acc, da + k * 256, db + k * 16, (i | k) != 0);
        else wgmma_ss_n160(acc, da + k * 256, db + k * 16, (i | k) != 0);
      }
      WG_COMMIT();
      if (i > 0) {
        WG_WAIT(1);
        if ((tid & 127) < 2) mbar_arrive_cta(emptyb + 8 * ((i - 1) % K3_ST), tid & 1);
      }
    }
    const uint32_t rx = mapa(smem_u32(xch) + (tid - 128) * 16, rank ^ 1), rb = mapa(xchb, rank ^ 1);
    WG_WAIT(0);
    fence_regs(acc);
    if ((tid & 127) < 2) mbar_arrive_cta(emptyb + 8 * ((NB - 1) % K3_ST), tid & 1);
    if (FIRST) st_async4(rx, acc[40], acc[41], acc[42], acc[43], rb);
    if (tid == 128) STAMP(FIRST ? 2 : 4, 1);
#pragma unroll
    for (int i = NB; i < NB + NK; i++) {
      const int s = i % K3_ST;
      mbar_wait(fullb + 8 * s, (i / K3_ST) & 1);
      const uint64_t da = da0 + s * (K3_STAGE >> 4), db = db0 + s * (K3_STAGE >> 4);
      WG_FENCE();
#pragma unroll
      for (int k = 0; k < 4; k++) {
        if constexpr (FIRST) wgmma_ss_n88(keep, da + k * 256, db + k * 16, 1);
        else wgmma_ss_n80(keep, da + k * 256, db + k * 16, 1);
      }
      WG_COMMIT();
      if (i > NB && i - 1 + K3_ST < NB + NK) {
        WG_WAIT(1);
        if ((tid & 127) < 2) mbar_arrive_cta(emptyb + 8 * ((i - 1) % K3_ST), tid & 1);
      }
#pragma unroll
      for (int j = (i - NB) * 3; j < (i - NB) * 3 + 3; j++)
        if (j < 5) SEND8(rx + (j + EX) * 4096, acc, 40 + 4 * EX + 8 * j, rb);
    }
    cluster_arrive();
    uint8_t* sp = stg + (cw * 16 + g) * 160 + c * 4;
    if (FIRST) {
      mbar_wait(resb, 0);
#pragma unroll
      for (int j = 0; j < 10; j++) {
        rv[2 * j] = *(const uint32_t*)(sp + j * 16);
        rv[2 * j + 1] = *(const uint32_t*)(sp + 1280 + j * 16);
      }
    }
    WG_WAIT(0);
    fence_regs(keep);
    if (tid == 128) STAMP(FIRST ? 2 : 4, 3);
    mbar_wait(xchb, 0);
    if (tid == 128) STAMP(FIRST ? 2 : 4, 5);
    const uint8_t* xp = xch + (tid - 128) * 16;
    if (FIRST) {
      const float4 p = *(const float4*)xp;
      mu0 += __shfl_sync(~0u, (keep[40] + p.x) + (keep[41] + p.y), 0, 4);
      mu1 += __shfl_sync(~0u, (keep[42] + p.z) + (keep[43] + p.w), 0, 4);
      if (n == 0 && c == 0) { g_hmean[row] = mu0; g_hmean[row + 8] = mu1; }
      mu0 = -mu0; mu1 = -mu1;
    }
    float q0 = 0.f, q1 = 0.f;
#pragma unroll
    for (int j = 0; j < 10; j++) {
      const uint2 p = *(const uint2*)(xp + ((j >> 1) + EX) * 4096 + (j & 1) * 8);
      const float x0 = (keep[4 * j] + bf_lo(p.x)) + (bf_lo(rv[2 * j]) + mu0), x1 = (keep[4 * j + 1] + bf_hi(p.x)) + (bf_hi(rv[2 * j]) + mu0);
      const float y0 = (keep[4 * j + 2] + bf_lo(p.y)) + (bf_lo(rv[2 * j + 1]) + mu1), y1 = (keep[4 * j + 3] + bf_hi(p.y)) + (bf_hi(rv[2 * j + 1]) + mu1);
      if (FIRST) {
        *(uint32_t*)(himg + img_off(n * 10 + j)) = pack_bf16(x0, x1);
        *(uint32_t*)(himg + img_off(n * 10 + j) + 128) = pack_bf16(y0, y1);
        q0 = fmaf(x0, x0, fmaf(x1, x1, q0)); q1 = fmaf(y0, y0, fmaf(y1, y1, q1));
      } else {
        *(uint32_t*)(sp + j * 16) = pack_bf16(x0, x1);
        *(uint32_t*)(sp + 1280 + j * 16) = pack_bf16(y0, y1);
      }
    }
    if (FIRST) {
      q0 += __shfl_xor_sync(~0u, q0, 1); q0 += __shfl_xor_sync(~0u, q0, 2);
      q1 += __shfl_xor_sync(~0u, q1, 1); q1 += __shfl_xor_sync(~0u, q1, 2);
      if (c < 2) g_hpart[n * S_ + row + c * 8] = c ? q1 : q0;
    } else {
      fence_async();
      bar_sync(1 + wg, 128);
      if ((tid & 127) == 0) {
        tma2d_st(&tmr, n * 80, m * 128 + wg * 64, smem_u32(stg) + wg * 10240);
        bulk_commit_wait();
      }
      __syncwarp();
    }
    if (tid == 128) STAMP(FIRST ? 2 : 4, 4);
  } else {
    cluster_arrive();
    cluster_wait();
    cluster_arrive();
  }
  cluster_wait();
}

#define NB3 12
constexpr int P3_NB = NB3, P3_NT = 27 - NB3;
constexpr int K4_G = 2, K4_NS = 4, K4_NJ = 20;
constexpr int K4_RB = 163840, K4_BST = 7168 * K4_G, K4_XCH = 147456, K4_STG = K4_XCH + 40960, K4_BAR = K4_RB + K4_NS * K4_BST;
constexpr int K4_SMEM = K4_BAR + 384;

__device__ __forceinline__ void wait_flags(const uint4* f, uint32_t tag, uint32_t need, uint32_t& seen) {
  if ((seen & need) == need) return;
  for (uint32_t it = 0; (seen & need) != need; it++) {
    if (it > (1u << 20)) wait_timeout();
#define PSLEEP 150
    if (it) __nanosleep(PSLEEP);
    uint32_t v = 0;
    if ((threadIdx.x & 31) < 8) asm volatile("ld.acquire.gpu.global.u32 %0, [%1];" : "=r"(v) : "l"((const uint32_t*)f + (threadIdx.x & 7)) : "memory");
    seen = __ballot_sync(~0u, v == tag) & 255;
  }
  asm volatile("fence.proxy.async.global;" ::: "memory");
}

__global__ void __cluster_dims__(2, 1, 1) __launch_bounds__(384, 1)
k45_ffn(const __grid_constant__ CUtensorMap tmo) {
  extern __shared__ __align__(1024) uint8_t sm[];
  const uint32_t sbase = smem_u32(sm);
  const uint32_t afull = sbase + K4_BAR, bfull = afull + 80, bempty = bfull + 8 * K4_NS, full3 = bempty + 8 * K4_NS;
  const uint32_t empty3 = full3 + 32, afree = empty3 + 32, xchb = afree + 32;
  const int tid = threadIdx.x, lane = tid & 31;
  const int warp = __shfl_sync(~0u, tid >> 5, 0);
  const int rank = blockIdx.x & 1;
  const int n1 = (blockIdx.x >> 1) & 7, m1 = (blockIdx.x >> 4) * 2 + rank;
  const int n3 = blockIdx.x & 7, m3 = blockIdx.x >> 3;
  if (tid == 0) STAMP(3, 0);
  if (warp == 8) {
    if (elect_one()) {
#pragma unroll
      for (int i = 0; i < 10; i++) mbar_init(afull + 8 * i, 1);
#pragma unroll
      for (int i = 0; i < 4; i++) {
        mbar_init(bfull + 8 * i, 1); mbar_init(bempty + 8 * i, 4); mbar_init(full3 + 8 * i, 1); mbar_init(empty3 + 8 * i, 4);
        mbar_init(afree + 8 * i, 2);
      }
      mbar_init(xchb, 1);
      mbar_expect(xchb, 20480);
      asm volatile("fence.mbarrier_init.release.cluster;" ::: "memory");
    }
    __syncwarp();
  }
  cluster_arrive();
  if (warp >= 8) {
    cluster_wait();
    if (warp == 8) {
      if (lane == 0) STAMP(3, 7);
      const uint8_t* src = (const uint8_t*)g_wgu + n1 * 552960;
      const uint8_t* hb = (const uint8_t*)g_h + (size_t)m1 * 163840;
#pragma unroll 1
      for (int j = 0; j < 40; j++) {
        const uint32_t s8 = (j & 3) * 8, sz = j < 20 ? 14336 : 13312;
#define K4PRE 2
        if (j == K4PRE) {
          pdl_wait();
          if (lane == 0) STAMP(3, 1);
          if (elect_one()) {
#pragma unroll
            for (int kt = 0; kt < K4PRE / 2 + 1; kt++) { mbar_expect(afull + 8 * kt, 16384); bulk_ld(sbase + kt * 16384, hb + kt * 16384, 16384, afull + 8 * kt); }
          }
        }
        if (j >= 4) mbar_wait(bempty + s8, ((j >> 2) - 1) & 1);
        if (elect_one()) {
          mbar_expect(bfull + s8, sz);
          if ((j & 1) == rank) bulk_ld_mc(sbase + K4_RB + s8 * (K4_BST / 8), src, sz, bfull + s8);
          if (j > K4PRE && j < 18 && (j & 1)) {
            mbar_expect(afull + 4 + j * 4, 16384);
            bulk_ld(sbase + 8192 + j * 8192, hb + 8192 + j * 8192, 16384, afull + 4 + j * 4);
          }
        }
        src += sz;
      }
    } else if (warp == 9) {
      prefetch_map(&tmo);
      const uint32_t tag = __ldcg(&g_epoch);
#pragma unroll 1
      for (int ph = 0; ph < 2; ph++) {
        bar_sync(5 + ph, 256 + 32);
        if (lane == 0) {
          asm volatile("st.release.gpu.global.u32 [%0], %1;" ::"l"((uint32_t*)&g_flag[ph * 32 + m1 * 2] + n1), "r"(tag) : "memory");
          STAMP(3, 5 + ph);
        }
        __syncwarp();
      }
    } else {
      const uint8_t* wk = (const uint8_t*)g_wd + n3 * 276480;
      const uint8_t* ws = (const uint8_t*)g_wd + (n3 ^ 1) * 276480;
      const uint8_t* ab = (const uint8_t*)g_hh + (size_t)m3 * 442368;
      const uint32_t tag = __ldcg(&g_epoch);
      uint32_t seen = 0;
#pragma unroll 1
      for (int i = 0; i < P3_NT; i++) {
        const int kt = i < 7 ? rank * 7 + i : (i < P3_NB ? rank * (P3_NB - 7) + 7 + i : P3_NB + i);
        const uint32_t sa = sbase + (i & 3) * 36864, fb = full3 + 8 * (i & 3);
        if (warp == 11) {
          const int q = kt * 8 - (i < 7 ? 0 : 112), w = i < 7 ? 14 : 13;
          if (i == 0) mbar_wait(afull + 72, 0);
          if (i == 7) seen = 0;
          wait_flags(&g_flag[(i < 7 ? 0 : 32) + m3 * 2], tag, 1u << (q / w) | 1u << ((q + 7) / w), seen);
          if (lane == 0 && (i == 0 || i == 7)) STAMP(4, i ? 7 : 6);
        }
        if (i < 4) mbar_wait(afree + 8 * i, 0);
        else mbar_wait(empty3 + 8 * (i & 3), ((i >> 2) - 1) & 1);
        if (warp == 10) {
          if (elect_one()) {
            mbar_expect(fb, i < P3_NB ? 36864 : 26624);
            bulk_ld(sa + 16384, wk + kt * 10240, 10240, fb);
            if (i < P3_NB) bulk_ld(sa + 26624, ws + kt * 10240, 10240, fb);
          }
        } else {
          if (elect_one()) {
            if (i < P3_NB) bulk_ld(sa, ab + kt * 16384, 16384, fb);
            else bulk_ld_mc(sa + rank * 8192, ab + kt * 16384 + rank * 8192, 8192, fb);
          }
        }
      }
    }
    __syncwarp();
    cluster_arrive();
    asm volatile("barrier.cluster.wait.aligned; // producers" ::: "memory");
  } else {
    const int wg = warp >> 2;
    const uint64_t da0 = mkdesc(sbase + wg * 1024, 2048, 128, 0);
    const uint64_t db0 = mkdesc(sbase + K4_RB, 128, 256, 0);
    cluster_wait();
    float a1[112], a2[104];
    int s = 0, ph = 0, sprev = 0;
#pragma unroll 1
    for (int j = 0; j < K4_NJ; j++) {
      if ((j * K4_G) % 4 == 0) mbar_wait(afull + 2 * K4_G * j, 0);
      mbar_wait(bfull + 8 * s, ph);
      if (j == 0 && tid == 0) STAMP(3, 2);
      const uint64_t da = da0 + j * K4_G * 256, db = db0 + s * (K4_BST >> 4);
      WG_FENCE();
#pragma unroll
      for (int k = 0; k < K4_G; k++) wgmma_ss_n224(a1, da + k * 256, db + k * 448, (j | k) != 0);
      WG_COMMIT();
      if (j > 0) {
        WG_WAIT(1);
        if ((tid & 127) < 2) mbar_arrive_cta(bempty + 8 * sprev, tid & 1);
      }
      sprev = s;
      if (++s == K4_NS) { s = 0; ph ^= 1; }
    }
    float acc[80];
    uint8_t* hd = (uint8_t*)g_hh + (size_t)m1 * 442368 + warp * 256 + lane * 4;
    WG_WAIT(0);
    fence_regs(a1);
    if ((tid & 127) < 2) mbar_arrive_cta(bempty + 8 * ((K4_NJ - 1) % K4_NS), tid & 1);
    if (tid == 0) STAMP(3, 3);
#define STORE_H(a, off, ptr, c) do { uint8_t* p_ = ptr; \
      *(uint32_t*)p_ = pack_bf16(a[4 * (c)] * a[off + 4 * (c)], a[4 * (c) + 1] * a[off + 1 + 4 * (c)]); \
      *(uint32_t*)(p_ + 128) = pack_bf16(a[4 * (c) + 2] * a[off + 2 + 4 * (c)], a[4 * (c) + 3] * a[off + 3 + 4 * (c)]); } while (0)
#pragma unroll
    for (int c = 0; c < 14; c++) STORE_H(a1, 56, hd + img_off(n1 * 14 + c), c);
    bar_arrive(5, 256 + 32);
#pragma unroll 1
    for (int j = 0; j < K4_NJ; j++) {
      mbar_wait(bfull + 8 * s, ph);
      const uint64_t da = da0 + j * K4_G * 256, db = db0 + s * (K4_BST >> 4);
      WG_FENCE();
#pragma unroll
      for (int k = 0; k < K4_G; k++) wgmma_ss_n208(a2, da + k * 256, db + k * 416, (j | k) != 0);
      WG_COMMIT();
      if (j > 0) {
        WG_WAIT(1);
        if (j <= K4_NJ - K4_NS && (tid & 127) < 2) mbar_arrive_cta(bempty + 8 * sprev, tid & 1);
        if (j * K4_G >= 12 && ((j * K4_G) & 7) == 4 && (tid & 127) == 0) mbar_arrive(afree + (j * K4_G - 12));
      }
      sprev = s;
      if (++s == K4_NS) { s = 0; ph ^= 1; }
    }
    WG_WAIT(0);
    fence_regs(a2);
    if (tid == 0) STAMP(3, 4);
#pragma unroll
    for (int c = 0; c < 13; c++) STORE_H(a2, 52, hd + img_off(112 + n1 * 13 + c), c);
    bar_arrive(6, 256 + 32);
    float (&keep)[40] = ((Acc<40>*)acc)->v;
    const uint64_t db3 = mkdesc(sbase + 16384, 128, 1024, 0);
#pragma unroll 1
    for (int i = 0; i < P3_NB; i++) {
      mbar_wait(full3 + 8 * (i & 3), (i >> 2) & 1);
      if (i == 0 && tid == 0) STAMP(4, 2);
      const uint64_t da = da0 + (i & 3) * 2304, db = db3 + (i & 3) * 2304;
      WG_FENCE();
#pragma unroll
      for (int k = 0; k < 4; k++) wgmma_ss_n160(acc, da + k * 256, db + k * 16, (i | k) != 0);
      WG_COMMIT();
      if (i > 0) {
        WG_WAIT(1);
        if (i + 3 < P3_NT && (tid & 127) < 2) mbar_arrive_cta(empty3 + 8 * ((i - 1) & 3), tid & 1);
      }
    }
    const int g = lane >> 2, c = lane & 3, row = m3 * 128 + warp * 16 + g;
    const uint8_t* himg = (const uint8_t*)g_h + (size_t)m3 * 163840 + warp * 256 + lane * 4;
    uint32_t rv[20];
    const float mu0 = __ldcg(&g_hmean[row]), mu1 = __ldcg(&g_hmean[row + 8]);
    float r0 = __ldcg(&g_hpart[c * 2 * S_ + row]) + __ldcg(&g_hpart[(c * 2 + 1) * S_ + row]);
    float r1 = __ldcg(&g_hpart[c * 2 * S_ + row + 8]) + __ldcg(&g_hpart[(c * 2 + 1) * S_ + row + 8]);
#pragma unroll
    for (int j = 0; j < 10; j++) {
      rv[2 * j] = __ldcg((const uint32_t*)(himg + img_off(n3 * 10 + j)));
      rv[2 * j + 1] = __ldcg((const uint32_t*)(himg + img_off(n3 * 10 + j) + 128));
    }
    const uint32_t rx = mapa(sbase + K4_XCH + tid * 16, rank ^ 1), rb = mapa(xchb, rank ^ 1);
    WG_WAIT(0);
    fence_regs(acc);
    if (P3_NB + 3 < P3_NT && (tid & 127) < 2) mbar_arrive_cta(empty3 + 8 * ((P3_NB - 1) & 3), tid & 1);
    if (tid == 0) STAMP(4, 1);
#pragma unroll
    for (int i = P3_NB; i < P3_NT; i++) {
      mbar_wait(full3 + 8 * (i & 3), (i >> 2) & 1);
      const uint64_t da = da0 + (i & 3) * 2304, db = db3 + (i & 3) * 2304;
      WG_FENCE();
#pragma unroll
      for (int k = 0; k < 4; k++) wgmma_ss_n80(keep, da + k * 256, db + k * 16, 1);
      WG_COMMIT();
      if (i > P3_NB && i + 3 < P3_NT) {
        WG_WAIT(1);
        if ((tid & 127) < 2) mbar_arrive_cta(empty3 + 8 * ((i - 1) & 3), tid & 1);
      }
#pragma unroll
      for (int j = (i - P3_NB) * 3; j < (i - P3_NB) * 3 + 3; j++)
        if (j < 5) SEND8(rx + j * 4096, acc, 40 + 8 * j, rb);
    }
    cluster_arrive();
    r0 += __shfl_xor_sync(~0u, r0, 1); r1 += __shfl_xor_sync(~0u, r1, 1);
    r0 += __shfl_xor_sync(~0u, r0, 2); r1 += __shfl_xor_sync(~0u, r1, 2);
    r0 = rcp(r0 * (1.f / D_) + 1e-5f); r1 = rcp(r1 * (1.f / D_) + 1e-5f);
    asm volatile("" : "+f"(r0), "+f"(r1)::"memory");
    WG_WAIT(0);
    fence_regs(keep);
    if (tid == 0) STAMP(4, 3);
    mbar_wait(xchb, 0);
    if (tid == 0) STAMP(4, 5);
    uint8_t* sp = sm + K4_STG + (warp * 16 + g) * 160 + c * 4;
#pragma unroll
    for (int j = 0; j < 10; j++) {
      const uint2 p = *(const uint2*)(sm + K4_XCH + tid * 16 + (j >> 1) * 4096 + (j & 1) * 8);
      *(uint32_t*)(sp + j * 16) = pack_bf16(fmaf(keep[4 * j] + bf_lo(p.x), r0, bf_lo(rv[2 * j]) + mu0), fmaf(keep[4 * j + 1] + bf_hi(p.x), r0, bf_hi(rv[2 * j]) + mu0));
      *(uint32_t*)(sp + 1280 + j * 16) = pack_bf16(fmaf(keep[4 * j + 2] + bf_lo(p.y), r1, bf_lo(rv[2 * j + 1]) + mu1), fmaf(keep[4 * j + 3] + bf_hi(p.y), r1, bf_hi(rv[2 * j + 1]) + mu1));
    }
    fence_async();
    bar_sync(1 + wg, 128);
    if ((tid & 127) == 0) {
      tma2d_st(&tmo, n3 * 80, m3 * 128 + wg * 64, sbase + K4_STG + wg * 10240);
      bulk_commit_wait();
    }
    __syncwarp();
    if (tid == 0) STAMP(4, 4);
    asm volatile("barrier.cluster.wait.aligned; // consumers" ::: "memory");
  }
}

typedef CUresult (*EncodeFn)(CUtensorMap*, CUtensorMapDataType, cuuint32_t, void*, const cuuint64_t*, const cuuint64_t*,
                             const cuuint32_t*, const cuuint32_t*, CUtensorMapInterleave, CUtensorMapSwizzle,
                             CUtensorMapL2promotion, CUtensorMapFloatOOBfill);

static CUtensorMap make_map(EncodeFn enc, const void* p, uint64_t inner, uint64_t outer, uint32_t box_inner,
                            uint32_t box_outer, CUtensorMapSwizzle swz) {
  CUtensorMap m;
  cuuint64_t gd[2] = {inner, outer};
  cuuint64_t gs[1] = {inner * 2};
  cuuint32_t bd[2] = {box_inner, box_outer};
  cuuint32_t es[2] = {1, 1};
  enc(&m, CU_TENSOR_MAP_DATA_TYPE_BFLOAT16, 2, (void*)p, gd, gs, bd, es, CU_TENSOR_MAP_INTERLEAVE_NONE, swz,
      CU_TENSOR_MAP_L2_PROMOTION_L2_256B, CU_TENSOR_MAP_FLOAT_OOB_FILL_NONE);
  return m;
}

static CUtensorMap make_map_img(EncodeFn enc, const void* p, uint64_t k, uint64_t n, uint32_t rows, uint32_t chunks,
                                uint32_t groups) {
  CUtensorMap m;
  cuuint64_t gd[4] = {8, rows, n / 8, k / rows};
  cuuint64_t gs[3] = {n * 2, 16, n * 2 * rows};
  cuuint32_t bd[4] = {8, rows, chunks, groups};
  cuuint32_t es[4] = {1, 1, 1, 1};
  enc(&m, CU_TENSOR_MAP_DATA_TYPE_BFLOAT16, 4, (void*)p, gd, gs, bd, es, CU_TENSOR_MAP_INTERLEAVE_NONE,
      CU_TENSOR_MAP_SWIZZLE_NONE, CU_TENSOR_MAP_L2_PROMOTION_L2_128B, CU_TENSOR_MAP_FLOAT_OOB_FILL_NONE);
  return m;
}

template <typename... KArgs, typename... Args>
static void launch(void (*k)(KArgs...), int grid, int threads, int smem, bool pdl, Args... args) {
  cudaLaunchConfig_t cfg = {};
  cfg.gridDim = dim3(grid);
  cfg.blockDim = dim3(threads);
  cfg.dynamicSmemBytes = smem;
  cfg.stream = cudaStreamPerThread;
  cudaLaunchAttribute at[1];
  at[0].id = cudaLaunchAttributeProgrammaticStreamSerialization;
  at[0].val.programmaticStreamSerializationAllowed = 1;
  cfg.attrs = at;
  cfg.numAttrs = pdl ? 1 : 0;
  cudaLaunchKernelEx(&cfg, k, KArgs(args)...);
}

extern "C" void kernel_launch(void* const* d_in, const int* in_sizes, int n_in, void* d_out, int out_size) {
  const bf16* x = (const bf16*)d_in[0];
  const bf16* wqkv = (const bf16*)d_in[1];
  const bf16* wo = (const bf16*)d_in[2];
  const bf16* wg = (const bf16*)d_in[4];
  const bf16* wu = (const bf16*)d_in[5];
  const bf16* wd = (const bf16*)d_in[6];

  static EncodeFn enc = nullptr;
  static void *p_o, *p_wo;
  if (!enc) {
    void* fn = nullptr;
    cudaDriverEntryPointQueryResult qr;
    cudaGetDriverEntryPoint("cuTensorMapEncodeTiled", &fn, cudaEnableDefault, &qr);
    enc = (EncodeFn)fn;
    cudaGetSymbolAddress(&p_o, g_o);
    cudaGetSymbolAddress(&p_wo, g_wo);
    cudaFuncSetAttribute(k1_qkv, cudaFuncAttributeMaxDynamicSharedMemorySize, K1_SMEM);
    cudaFuncSetAttribute(k2_attn, cudaFuncAttributeMaxDynamicSharedMemorySize, K2_SMEM);
    cudaFuncSetAttribute(k3_proj<K3NB, 10 - 2 * K3NB, true>, cudaFuncAttributeMaxDynamicSharedMemorySize, K3_SMEM);
    cudaFuncSetAttribute(k45_ffn, cudaFuncAttributeMaxDynamicSharedMemorySize, K4_SMEM);
  }
  const CUtensorMap tmx = make_map(enc, x, D_, S_, 64, 96, CU_TENSOR_MAP_SWIZZLE_128B);
  const CUtensorMap tmw = make_map(enc, wqkv, 3 * D_, D_, 32, 64, CU_TENSOR_MAP_SWIZZLE_64B);
  const CUtensorMap tmxr = make_map(enc, x, D_, S_, 80, 64, CU_TENSOR_MAP_SWIZZLE_NONE);
  Maps5 maps;
  maps.m[0] = make_map_img(enc, wg, D_, F_, 16, 14, 2); maps.m[1] = make_map_img(enc, wu, D_, F_, 16, 14, 2);
  maps.m[2] = make_map_img(enc, wg, D_, F_, 16, 13, 2); maps.m[3] = make_map_img(enc, wu, D_, F_, 16, 13, 2);
  maps.m[4] = make_map_img(enc, wd, F_, D_, 64, 10, 1);
  const CUtensorMap tmout = make_map(enc, d_out, D_, S_, 80, 64, CU_TENSOR_MAP_SWIZZLE_NONE);

  launch(k1_qkv, 132, 512, K1_SMEM, false, tmx, tmw, x, wqkv, wo);
  launch(k2_attn, 128, 512, K2_SMEM, true, maps, 0x007f007fu);
  launch(k3_proj<K3NB, 10 - 2 * K3NB, true>, 128, 384, K3_SMEM, true, tmxr, (const uint4*)p_o, (const uint4*)p_wo);
  launch(k45_ffn, 128, 384, K4_SMEM, true, tmout);
}
```

```cpp
#include <cuda_runtime.h>
#include <cuda_bf16.h>
#include <cuda.h>
#include <stdint.h>

typedef __nv_bfloat16 bf16;

constexpr int S_ = 2048, D_ = 640, F_ = 1728;
constexpr int HEAD_IMG = 98304;
constexpr uint32_t POLY_MASK = 0xDB6D;
constexpr float QSCALE = 0.22360679774997896f * 1.4426950408889634f;

__device__ __align__(1024) uint4 g_qkv[96 * HEAD_IMG / 16];
__device__ __align__(1024) uint4 g_o[S_ * D_ / 8];
__device__ __align__(1024) uint4 g_h[S_ * D_ / 8];
__device__ __align__(1024) uint4 g_hh[S_ * F_ / 8];
__device__ __align__(1024) uint4 g_wo[D_ * D_ / 8];
__device__ __align__(1024) uint4 g_wgu[2 * D_ * F_ / 8];
__device__ __align__(1024) uint4 g_wd[F_ * D_ / 8];
__device__ uint4 g_rowstat[S_];
__device__ uint4 g_cpart[10 * 12 * 80];
__device__ float g_nrm[96 * 128];
__device__ uint4 g_wm[D_];
__device__ float g_hmean[S_];
__device__ float g_hpart[8 * S_];
__device__ uint4 g_flag[2 * 16 * 2];
__device__ unsigned g_epoch;

#define STAMP(k, i)
__device__ __forceinline__ uint32_t smem_u32(const void* p) { return (uint32_t)__cvta_generic_to_shared(p); }
__device__ __forceinline__ void mbar_init(uint32_t a, uint32_t c) {
  asm volatile("mbarrier.init.shared::cta.b64 [%0], %1;" ::"r"(a), "r"(c) : "memory");
}
__device__ __forceinline__ void mbar_expect(uint32_t a, uint32_t bytes) {
  asm volatile("mbarrier.arrive.expect_tx.shared::cta.b64 _, [%0], %1;" ::"r"(a), "r"(bytes) : "memory");
}
__device__ __forceinline__ void mbar_arrive(uint32_t a) {
  asm volatile("mbarrier.arrive.shared::cta.b64 _, [%0];" ::"r"(a) : "memory");
}
__device__ __forceinline__ void mbar_arrive_cta(uint32_t a, uint32_t cta) {
  asm volatile("{\n.reg .b32 r;\nmapa.shared::cluster.u32 r, %0, %1;\n"
               "mbarrier.arrive.shared::cluster.b64 _, [r];\n}" ::"r"(a), "r"(cta) : "memory");
}
__device__ __forceinline__ bool mbar_try(uint32_t a, uint32_t ph) {
  uint32_t ok;
  asm volatile("{\n.reg .pred p;\nmbarrier.try_wait.parity.shared::cta.b64 p, [%1], %2;\nselp.u32 %0, 1, 0, p;\n}"
               : "=r"(ok) : "r"(a), "r"(ph) : "memory");
  return ok;
}
__device__ __noinline__ void wait_timeout() { __trap(); }
__device__ __forceinline__ void mbar_wait(uint32_t a, uint32_t ph) {
  if (mbar_try(a, ph)) return;
  uint32_t it = 0;
  while (!mbar_try(a, ph)) if (++it > (1u << 22)) wait_timeout();
}
__device__ __forceinline__ void tma2d(uint32_t dst, const CUtensorMap* m, int c0, int c1, uint32_t bar) {
  asm volatile("cp.async.bulk.tensor.2d.shared::cluster.global.mbarrier::complete_tx::bytes [%0], [%1, {%3, %4}], [%2];"
               ::"r"(dst), "l"(m), "r"(bar), "r"(c0), "r"(c1) : "memory");
}
__device__ __forceinline__ void tma2d_mc(uint32_t dst, const CUtensorMap* m, int c0, int c1, uint32_t bar) {
  asm volatile("cp.async.bulk.tensor.2d.shared::cluster.global.mbarrier::complete_tx::bytes.multicast::cluster "
               "[%0], [%1, {%3, %4}], [%2], %5;"
               ::"r"(dst), "l"(m), "r"(bar), "r"(c0), "r"(c1), "h"((uint16_t)3) : "memory");
}
__device__ __forceinline__ void bulk_ld(uint32_t dst, const void* src, uint32_t bytes, uint32_t bar) {
  asm volatile("cp.async.bulk.shared::cluster.global.mbarrier::complete_tx::bytes [%0], [%1], %2, [%3];"
               ::"r"(dst), "l"(src), "r"(bytes), "r"(bar) : "memory");
}
__device__ __forceinline__ void bulk_ld_mc(uint32_t dst, const void* src, uint32_t bytes, uint32_t bar) {
  asm volatile("cp.async.bulk.shared::cluster.global.mbarrier::complete_tx::bytes.multicast::cluster "
               "[%0], [%1], %2, [%3], %4;"
               ::"r"(dst), "l"(src), "r"(bytes), "r"(bar), "h"((uint16_t)3) : "memory");
}
__device__ __forceinline__ void cluster_arrive() { asm volatile("barrier.cluster.arrive.relaxed.aligned;" ::: "memory"); }
__device__ __forceinline__ void cluster_wait() { asm volatile("barrier.cluster.wait.aligned;" ::: "memory"); }
__device__ __forceinline__ void bulk_st(void* dst, uint32_t src, uint32_t bytes) {
  asm volatile("cp.async.bulk.global.shared::cta.bulk_group [%0], [%1], %2;" ::"l"(dst), "r"(src), "r"(bytes) : "memory");
}
__device__ __forceinline__ void tma2d_st(const CUtensorMap* m, int c0, int c1, uint32_t src) {
  asm volatile("cp.async.bulk.tensor.2d.global.shared::cta.bulk_group [%0, {%2, %3}], [%1];"
               ::"l"(m), "r"(src), "r"(c0), "r"(c1) : "memory");
}
__device__ __forceinline__ void bulk_commit_wait() {
  asm volatile("cp.async.bulk.commit_group;\ncp.async.bulk.wait_group.read 0;" ::: "memory");
}
__device__ __forceinline__ uint32_t mapa(uint32_t a, uint32_t cta) {
  uint32_t r;
  asm("mapa.shared::cluster.u32 %0, %1, %2;" : "=r"(r) : "r"(a), "r"(cta));
  return r;
}
__device__ __forceinline__ void st_async4(uint32_t dst, float a, float b, float c, float d, uint32_t bar) {
  asm volatile("st.async.shared::cluster.mbarrier::complete_tx::bytes.v4.f32 [%0], {%1, %2, %3, %4}, [%5];"
               ::"r"(dst), "f"(a), "f"(b), "f"(c), "f"(d), "r"(bar) : "memory");
}
__device__ __forceinline__ void st_async4u(uint32_t dst, uint32_t a, uint32_t b, uint32_t c, uint32_t d, uint32_t bar) {
  asm volatile("st.async.shared::cluster.mbarrier::complete_tx::bytes.v4.b32 [%0], {%1, %2, %3, %4}, [%5];"
               ::"r"(dst), "r"(a), "r"(b), "r"(c), "r"(d), "r"(bar) : "memory");
}
#define SEND8(dst, a, o, bar) st_async4u(dst, pack_bf16(a[o], a[(o) + 1]), pack_bf16(a[(o) + 2], a[(o) + 3]), \
                                         pack_bf16(a[(o) + 4], a[(o) + 5]), pack_bf16(a[(o) + 6], a[(o) + 7]), bar)
__device__ __forceinline__ void fence_async() { asm volatile("fence.proxy.async.shared::cta;" ::: "memory"); }
__device__ __forceinline__ void prefetch_map(const CUtensorMap* m) {
  asm volatile("prefetch.tensormap [%0];" ::"l"(m) : "memory");
}
__device__ __forceinline__ bool elect_one() {
  uint32_t p;
  asm volatile("{\n.reg .pred q;\nelect.sync _|q, 0xffffffff;\nselp.u32 %0, 1, 0, q;\n}" : "=r"(p));
  return p;
}
__device__ __forceinline__ void pdl_wait() { asm volatile("griddepcontrol.wait;" ::: "memory"); }
__device__ __forceinline__ void pdl_trigger() { asm volatile("griddepcontrol.launch_dependents;" ::: "memory"); }
__device__ __forceinline__ void bar_sync(int id, int n) { asm volatile("bar.sync %0, %1;" ::"r"(id), "r"(n) : "memory"); }
__device__ __forceinline__ void bar_arrive(int id, int n) { asm volatile("bar.arrive %0, %1;" ::"r"(id), "r"(n) : "memory"); }
#define WG_FENCE() asm volatile("wgmma.fence.sync.aligned;" ::: "memory")
#define WG_COMMIT() asm volatile("wgmma.commit_group.sync.aligned;" ::: "memory")
#define WG_WAIT(n) asm volatile("wgmma.wait_group.sync.aligned %0;" ::"n"(n) : "memory")
__device__ __forceinline__ uint64_t mkdesc(uint32_t addr, uint32_t lbo, uint32_t sbo, uint32_t sw) {
  return (uint64_t)((addr & 0x3FFFF) >> 4) | ((uint64_t)(lbo >> 4) << 16) | ((uint64_t)(sbo >> 4) << 32) |
         ((uint64_t)sw << 62);
}
template <int N> __device__ __forceinline__ void fence_regs(float (&r)[N]) {
#pragma unroll
  for (int i = 0; i < N; i++) asm volatile("" : "+f"(r[i])::"memory");
}
__device__ __forceinline__ uint32_t pack_bf16(float lo, float hi) {
  uint32_t r;
  asm("cvt.rn.bf16x2.f32 %0, %1, %2;" : "=r"(r) : "f"(hi), "f"(lo));
  return r;
}
__device__ __forceinline__ float bf_lo(uint32_t v) { return __uint_as_float(v << 16); }
__device__ __forceinline__ float bf_hi(uint32_t v) { return __uint_as_float(v & 0xffff0000u); }
__device__ __forceinline__ float ex2(float x) {
  float y;
  asm("ex2.approx.ftz.f32 %0, %1;" : "=f"(y) : "f"(x));
  return y;
}
__device__ __forceinline__ uint4 ldg_nc(const void* p) {
  uint4 v;
  asm volatile("ld.global.nc.L1::no_allocate.v4.u32 {%0, %1, %2, %3}, [%4];"
               : "=r"(v.x), "=r"(v.y), "=r"(v.z), "=r"(v.w) : "l"(p));
  return v;
}

__device__ __forceinline__ uint4 ld_relaxed(const uint4* p) {
  uint64_t a, b;
  asm volatile("ld.relaxed.gpu.global.v2.u64 {%0, %1}, [%2];" : "=l"(a), "=l"(b) : "l"(p) : "memory");
  return make_uint4((uint32_t)a, (uint32_t)(a >> 32), (uint32_t)b, (uint32_t)(b >> 32));
}
__device__ __forceinline__ void st_relaxed(uint4* p, float x, float y, uint32_t tag) {
  const uint64_t a = ((uint64_t)tag << 32) | __float_as_uint(x), b = ((uint64_t)tag << 32) | __float_as_uint(y);
  asm volatile("st.relaxed.gpu.global.v2.u64 [%0], {%1, %2};" ::"l"(p), "l"(a), "l"(b) : "memory");
}
__device__ __forceinline__ void tma4d(uint32_t dst, const CUtensorMap* m, int c2, int c3, uint32_t bar) {
  asm volatile("cp.async.bulk.tensor.4d.shared::cluster.global.mbarrier::complete_tx::bytes [%0], [%1, {%3, %3, %4, %5}], [%2];"
               ::"r"(dst), "l"(m), "r"(bar), "r"(0), "r"(c2), "r"(c3) : "memory");
}
#define ACC8(a, v) do { a[0] += bf_lo(v.x); a[1] += bf_hi(v.x); a[2] += bf_lo(v.y); a[3] += bf_hi(v.y); \
                        a[4] += bf_lo(v.z); a[5] += bf_hi(v.z); a[6] += bf_lo(v.w); a[7] += bf_hi(v.w); } while (0)

__device__ __forceinline__ void wgmma_ss_n224(float (&d)[112], uint64_t da, uint64_t db, int sd) {
  asm volatile("{\n.reg .pred p;\nsetp.ne.b32 p, %114, 0;\n"
      "wgmma.mma_async.sync.aligned.m64n224k16.f32.bf16.bf16 {"
      "%0, %1, %2, %3, %4, %5, %6, %7, %8, %9, %10, %11, %12, %13, %14, %15, "
      "%16, %17, %18, %19, %20, %21, %22, %23, %24, %25, %26, %27, %28, %29, %30, %31, "
      "%32, %33, %34, %35, %36, %37, %38, %39, %40, %41, %42, %43, %44, %45, %46, %47, "
      "%48, %49, %50, %51, %52, %53, %54, %55, %56, %57, %58, %59, %60, %61, %62, %63, "
      "%64, %65, %66, %67, %68, %69, %70, %71, %72, %73, %74, %75, %76, %77, %78, %79, "
      "%80, %81, %82, %83, %84, %85, %86, %87, %88, %89, %90, %91, %92, %93, %94, %95, "
      "%96, %97, %98, %99, %100, %101, %102, %103, %104, %105, %106, %107, %108, %109, %110, %111"
      "}, %112, %113, p, 1, 1, 0, 1;\n}\n"
    : "+f"(d[0]), "+f"(d[1]), "+f"(d[2]), "+f"(d[3]), "+f"(d[4]), "+f"(d[5]), "+f"(d[6]), "+f"(d[7]),
      "+f"(d[8]), "+f"(d[9]), "+f"(d[10]), "+f"(d[11]), "+f"(d[12]), "+f"(d[13]), "+f"(d[14]), "+f"(d[15]),
      "+f"(d[16]), "+f"(d[17]), "+f"(d[18]), "+f"(d[19]), "+f"(d[20]), "+f"(d[21]), "+f"(d[22]), "+f"(d[23]),
      "+f"(d[24]), "+f"(d[25]), "+f"(d[26]), "+f"(d[27]), "+f"(d[28]), "+f"(d[29]), "+f"(d[30]), "+f"(d[31]),
      "+f"(d[32]), "+f"(d[33]), "+f"(d[34]), "+f"(d[35]), "+f"(d[36]), "+f"(d[37]), "+f"(d[38]), "+f"(d[39]),
      "+f"(d[40]), "+f"(d[41]), "+f"(d[42]), "+f"(d[43]), "+f"(d[44]), "+f"(d[45]), "+f"(d[46]), "+f"(d[47]),
      "+f"(d[48]), "+f"(d[49]), "+f"(d[50]), "+f"(d[51]), "+f"(d[52]), "+f"(d[53]), "+f"(d[54]), "+f"(d[55]),
      "+f"(d[56]), "+f"(d[57]), "+f"(d[58]), "+f"(d[59]), "+f"(d[60]), "+f"(d[61]), "+f"(d[62]), "+f"(d[63]),
      "+f"(d[64]), "+f"(d[65]), "+f"(d[66]), "+f"(d[67]), "+f"(d[68]), "+f"(d[69]), "+f"(d[70]), "+f"(d[71]),
      "+f"(d[72]), "+f"(d[73]), "+f"(d[74]), "+f"(d[75]), "+f"(d[76]), "+f"(d[77]), "+f"(d[78]), "+f"(d[79]),
      "+f"(d[80]), "+f"(d[81]), "+f"(d[82]), "+f"(d[83]), "+f"(d[84]), "+f"(d[85]), "+f"(d[86]), "+f"(d[87]),
      "+f"(d[88]), "+f"(d[89]), "+f"(d[90]), "+f"(d[91]), "+f"(d[92]), "+f"(d[93]), "+f"(d[94]), "+f"(d[95]),
      "+f"(d[96]), "+f"(d[97]), "+f"(d[98]), "+f"(d[99]), "+f"(d[100]), "+f"(d[101]), "+f"(d[102]), "+f"(d[103]),
      "+f"(d[104]), "+f"(d[105]), "+f"(d[106]), "+f"(d[107]), "+f"(d[108]), "+f"(d[109]), "+f"(d[110]), "+f"(d[111])
    : "l"(da), "l"(db), "r"(sd));
}
__device__ __forceinline__ void wgmma_ss_n208(float (&d)[104], uint64_t da, uint64_t db, int sd) {
  asm volatile("{\n.reg .pred p;\nsetp.ne.b32 p, %106, 0;\n"
      "wgmma.mma_async.sync.aligned.m64n208k16.f32.bf16.bf16 {"
      "%0, %1, %2, %3, %4, %5, %6, %7, %8, %9, %10, %11, %12, %13, %14, %15, "
      "%16, %17, %18, %19, %20, %21, %22, %23, %24, %25, %26, %27, %28, %29, %30, %31, "
      "%32, %33, %34, %35, %36, %37, %38, %39, %40, %41, %42, %43, %44, %45, %46, %47, "
      "%48, %49, %50, %51, %52, %53, %54, %55, %56, %57, %58, %59, %60, %61, %62, %63, "
      "%64, %65, %66, %67, %68, %69, %70, %71, %72, %73, %74, %75, %76, %77, %78, %79, "
      "%80, %81, %82, %83, %84, %85, %86, %87, %88, %89, %90, %91, %92, %93, %94, %95, "
      "%96, %97, %98, %99, %100, %101, %102, %103"
      "}, %104, %105, p, 1, 1, 0, 1;\n}\n"
    : "+f"(d[0]), "+f"(d[1]), "+f"(d[2]), "+f"(d[3]), "+f"(d[4]), "+f"(d[5]), "+f"(d[6]), "+f"(d[7]),
      "+f"(d[8]), "+f"(d[9]), "+f"(d[10]), "+f"(d[11]), "+f"(d[12]), "+f"(d[13]), "+f"(d[14]), "+f"(d[15]),
      "+f"(d[16]), "+f"(d[17]), "+f"(d[18]), "+f"(d[19]), "+f"(d[20]), "+f"(d[21]), "+f"(d[22]), "+f"(d[23]),
      "+f"(d[24]), "+f"(d[25]), "+f"(d[26]), "+f"(d[27]), "+f"(d[28]), "+f"(d[29]), "+f"(d[30]), "+f"(d[31]),
      "+f"(d[32]), "+f"(d[33]), "+f"(d[34]), "+f"(d[35]), "+f"(d[36]), "+f"(d[37]), "+f"(d[38]), "+f"(d[39]),
      "+f"(d[40]), "+f"(d[41]), "+f"(d[42]), "+f"(d[43]), "+f"(d[44]), "+f"(d[45]), "+f"(d[46]), "+f"(d[47]),
      "+f"(d[48]), "+f"(d[49]), "+f"(d[50]), "+f"(d[51]), "+f"(d[52]), "+f"(d[53]), "+f"(d[54]), "+f"(d[55]),
      "+f"(d[56]), "+f"(d[57]), "+f"(d[58]), "+f"(d[59]), "+f"(d[60]), "+f"(d[61]), "+f"(d[62]), "+f"(d[63]),
      "+f"(d[64]), "+f"(d[65]), "+f"(d[66]), "+f"(d[67]), "+f"(d[68]), "+f"(d[69]), "+f"(d[70]), "+f"(d[71]),
      "+f"(d[72]), "+f"(d[73]), "+f"(d[74]), "+f"(d[75]), "+f"(d[76]), "+f"(d[77]), "+f"(d[78]), "+f"(d[79]),
      "+f"(d[80]), "+f"(d[81]), "+f"(d[82]), "+f"(d[83]), "+f"(d[84]), "+f"(d[85]), "+f"(d[86]), "+f"(d[87]),
      "+f"(d[88]), "+f"(d[89]), "+f"(d[90]), "+f"(d[91]), "+f"(d[92]), "+f"(d[93]), "+f"(d[94]), "+f"(d[95]),
      "+f"(d[96]), "+f"(d[97]), "+f"(d[98]), "+f"(d[99]), "+f"(d[100]), "+f"(d[101]), "+f"(d[102]), "+f"(d[103])
    : "l"(da), "l"(db), "r"(sd));
}
__device__ __forceinline__ void wgmma_ss_n168(float (&d)[84], uint64_t da, uint64_t db, int sd) {
  asm volatile("{\n.reg .pred p;\nsetp.ne.b32 p, %86, 0;\n"
      "wgmma.mma_async.sync.aligned.m64n168k16.f32.bf16.bf16 {"
      "%0, %1, %2, %3, %4, %5, %6, %7, %8, %9, %10, %11, %12, %13, %14, %15, "
      "%16, %17, %18, %19, %20, %21, %22, %23, %24, %25, %26, %27, %28, %29, %30, %31, "
      "%32, %33, %34, %35, %36, %37, %38, %39, %40, %41, %42, %43, %44, %45, %46, %47, "
      "%48, %49, %50, %51, %52, %53, %54, %55, %56, %57, %58, %59, %60, %61, %62, %63, "
      "%64, %65, %66, %67, %68, %69, %70, %71, %72, %73, %74, %75, %76, %77, %78, %79, "
      "%80, %81, %82, %83"
      "}, %84, %85, p, 1, 1, 0, 1;\n}\n"
    : "+f"(d[0]), "+f"(d[1]), "+f"(d[2]), "+f"(d[3]), "+f"(d[4]), "+f"(d[5]), "+f"(d[6]), "+f"(d[7]),
      "+f"(d[8]), "+f"(d[9]), "+f"(d[10]), "+f"(d[11]), "+f"(d[12]), "+f"(d[13]), "+f"(d[14]), "+f"(d[15]),
      "+f"(d[16]), "+f"(d[17]), "+f"(d[18]), "+f"(d[19]), "+f"(d[20]), "+f"(d[21]), "+f"(d[22]), "+f"(d[23]),
      "+f"(d[24]), "+f"(d[25]), "+f"(d[26]), "+f"(d[27]), "+f"(d[28]), "+f"(d[29]), "+f"(d[30]), "+f"(d[31]),
      "+f"(d[32]), "+f"(d[33]), "+f"(d[34]), "+f"(d[35]), "+f"(d[36]), "+f"(d[37]), "+f"(d[38]), "+f"(d[39]),
      "+f"(d[40]), "+f"(d[41]), "+f"(d[42]), "+f"(d[43]), "+f"(d[44]), "+f"(d[45]), "+f"(d[46]), "+f"(d[47]),
      "+f"(d[48]), "+f"(d[49]), "+f"(d[50]), "+f"(d[51]), "+f"(d[52]), "+f"(d[53]), "+f"(d[54]), "+f"(d[55]),
      "+f"(d[56]), "+f"(d[57]), "+f"(d[58]), "+f"(d[59]), "+f"(d[60]), "+f"(d[61]), "+f"(d[62]), "+f"(d[63]),
      "+f"(d[64]), "+f"(d[65]), "+f"(d[66]), "+f"(d[67]), "+f"(d[68]), "+f"(d[69]), "+f"(d[70]), "+f"(d[71]),
      "+f"(d[72]), "+f"(d[73]), "+f"(d[74]), "+f"(d[75]), "+f"(d[76]), "+f"(d[77]), "+f"(d[78]), "+f"(d[79]),
      "+f"(d[80]), "+f"(d[81]), "+f"(d[82]), "+f"(d[83])
    : "l"(da), "l"(db), "r"(sd));
}
__device__ __forceinline__ void wgmma_ss_n160(float (&d)[80], uint64_t da, uint64_t db, int sd) {
  asm volatile("{\n.reg .pred p;\nsetp.ne.b32 p, %82, 0;\n"
      "wgmma.mma_async.sync.aligned.m64n160k16.f32.bf16.bf16 {"
      "%0, %1, %2, %3, %4, %5, %6, %7, %8, %9, %10, %11, %12, %13, %14, %15, "
      "%16, %17, %18, %19, %20, %21, %22, %23, %24, %25, %26, %27, %28, %29, %30, %31, "
      "%32, %33, %34, %35, %36, %37, %38, %39, %40, %41, %42, %43, %44, %45, %46, %47, "
      "%48, %49, %50, %51, %52, %53, %54, %55, %56, %57, %58, %59, %60, %61, %62, %63, "
      "%64, %65, %66, %67, %68, %69, %70, %71, %72, %73, %74, %75, %76, %77, %78, %79"
      "}, %80, %81, p, 1, 1, 0, 1;\n}\n"
    : "+f"(d[0]), "+f"(d[1]), "+f"(d[2]), "+f"(d[3]), "+f"(d[4]), "+f"(d[5]), "+f"(d[6]), "+f"(d[7]),
      "+f"(d[8]), "+f"(d[9]), "+f"(d[10]), "+f"(d[11]), "+f"(d[12]), "+f"(d[13]), "+f"(d[14]), "+f"(d[15]),
      "+f"(d[16]), "+f"(d[17]), "+f"(d[18]), "+f"(d[19]), "+f"(d[20]), "+f"(d[21]), "+f"(d[22]), "+f"(d[23]),
      "+f"(d[24]), "+f"(d[25]), "+f"(d[26]), "+f"(d[27]), "+f"(d[28]), "+f"(d[29]), "+f"(d[30]), "+f"(d[31]),
      "+f"(d[32]), "+f"(d[33]), "+f"(d[34]), "+f"(d[35]), "+f"(d[36]), "+f"(d[37]), "+f"(d[38]), "+f"(d[39]),
      "+f"(d[40]), "+f"(d[41]), "+f"(d[42]), "+f"(d[43]), "+f"(d[44]), "+f"(d[45]), "+f"(d[46]), "+f"(d[47]),
      "+f"(d[48]), "+f"(d[49]), "+f"(d[50]), "+f"(d[51]), "+f"(d[52]), "+f"(d[53]), "+f"(d[54]), "+f"(d[55]),
      "+f"(d[56]), "+f"(d[57]), "+f"(d[58]), "+f"(d[59]), "+f"(d[60]), "+f"(d[61]), "+f"(d[62]), "+f"(d[63]),
      "+f"(d[64]), "+f"(d[65]), "+f"(d[66]), "+f"(d[67]), "+f"(d[68]), "+f"(d[69]), "+f"(d[70]), "+f"(d[71]),
      "+f"(d[72]), "+f"(d[73]), "+f"(d[74]), "+f"(d[75]), "+f"(d[76]), "+f"(d[77]), "+f"(d[78]), "+f"(d[79])
    : "l"(da), "l"(db), "r"(sd));
}
__device__ __forceinline__ void wgmma_ss_n88(float (&d)[44], uint64_t da, uint64_t db, int sd) {
  asm volatile("{\n.reg .pred p;\nsetp.ne.b32 p, %46, 0;\n"
      "wgmma.mma_async.sync.aligned.m64n88k16.f32.bf16.bf16 {"
      "%0, %1, %2, %3, %4, %5, %6, %7, %8, %9, %10, %11, %12, %13, %14, %15, "
      "%16, %17, %18, %19, %20, %21, %22, %23, %24, %25, %26, %27, %28, %29, %30, %31, "
      "%32, %33, %34, %35, %36, %37, %38, %39, %40, %41, %42, %43"
      "}, %44, %45, p, 1, 1, 0, 1;\n}\n"
    : "+f"(d[0]), "+f"(d[1]), "+f"(d[2]), "+f"(d[3]), "+f"(d[4]), "+f"(d[5]), "+f"(d[6]), "+f"(d[7]),
      "+f"(d[8]), "+f"(d[9]), "+f"(d[10]), "+f"(d[11]), "+f"(d[12]), "+f"(d[13]), "+f"(d[14]), "+f"(d[15]),
      "+f"(d[16]), "+f"(d[17]), "+f"(d[18]), "+f"(d[19]), "+f"(d[20]), "+f"(d[21]), "+f"(d[22]), "+f"(d[23]),
      "+f"(d[24]), "+f"(d[25]), "+f"(d[26]), "+f"(d[27]), "+f"(d[28]), "+f"(d[29]), "+f"(d[30]), "+f"(d[31]),
      "+f"(d[32]), "+f"(d[33]), "+f"(d[34]), "+f"(d[35]), "+f"(d[36]), "+f"(d[37]), "+f"(d[38]), "+f"(d[39]),
      "+f"(d[40]), "+f"(d[41]), "+f"(d[42]), "+f"(d[43])
    : "l"(da), "l"(db), "r"(sd));
}
__device__ __forceinline__ void wgmma_ss_n80(float (&d)[40], uint64_t da, uint64_t db, int sd) {
  asm volatile("{\n.reg .pred p;\nsetp.ne.b32 p, %42, 0;\n"
      "wgmma.mma_async.sync.aligned.m64n80k16.f32.bf16.bf16 {"
      "%0, %1, %2, %3, %4, %5, %6, %7, %8, %9, %10, %11, %12, %13, %14, %15, "
      "%16, %17, %18, %19, %20, %21, %22, %23, %24, %25, %26, %27, %28, %29, %30, %31, "
      "%32, %33, %34, %35, %36, %37, %38, %39"
      "}, %40, %41, p, 1, 1, 0, 1;\n}\n"
    : "+f"(d[0]), "+f"(d[1]), "+f"(d[2]), "+f"(d[3]), "+f"(d[4]), "+f"(d[5]), "+f"(d[6]), "+f"(d[7]),
      "+f"(d[8]), "+f"(d[9]), "+f"(d[10]), "+f"(d[11]), "+f"(d[12]), "+f"(d[13]), "+f"(d[14]), "+f"(d[15]),
      "+f"(d[16]), "+f"(d[17]), "+f"(d[18]), "+f"(d[19]), "+f"(d[20]), "+f"(d[21]), "+f"(d[22]), "+f"(d[23]),
      "+f"(d[24]), "+f"(d[25]), "+f"(d[26]), "+f"(d[27]), "+f"(d[28]), "+f"(d[29]), "+f"(d[30]), "+f"(d[31]),
      "+f"(d[32]), "+f"(d[33]), "+f"(d[34]), "+f"(d[35]), "+f"(d[36]), "+f"(d[37]), "+f"(d[38]), "+f"(d[39])
    : "l"(da), "l"(db), "r"(sd));
}
__device__ __forceinline__ void wgmma_rs_n128(float (&d)[64], uint32_t a0, uint32_t a1, uint32_t a2, uint32_t a3,
                                  uint64_t db, int sd) {
  asm volatile("{\n.reg .pred p;\nsetp.ne.b32 p, %69, 0;\n"
      "wgmma.mma_async.sync.aligned.m64n128k16.f32.bf16.bf16 {"
      "%0, %1, %2, %3, %4, %5, %6, %7, %8, %9, %10, %11, %12, %13, %14, %15, "
      "%16, %17, %18, %19, %20, %21, %22, %23, %24, %25, %26, %27, %28, %29, %30, %31, "
      "%32, %33, %34, %35, %36, %37, %38, %39, %40, %41, %42, %43, %44, %45, %46, %47, "
      "%48, %49, %50, %51, %52, %53, %54, %55, %56, %57, %58, %59, %60, %61, %62, %63"
      "}, {%64, %65, %66, %67}, %68, p, 1, 1, 0;\n}\n"
    : "+f"(d[0]), "+f"(d[1]), "+f"(d[2]), "+f"(d[3]), "+f"(d[4]), "+f"(d[5]), "+f"(d[6]), "+f"(d[7]),
      "+f"(d[8]), "+f"(d[9]), "+f"(d[10]), "+f"(d[11]), "+f"(d[12]), "+f"(d[13]), "+f"(d[14]), "+f"(d[15]),
      "+f"(d[16]), "+f"(d[17]), "+f"(d[18]), "+f"(d[19]), "+f"(d[20]), "+f"(d[21]), "+f"(d[22]), "+f"(d[23]),
      "+f"(d[24]), "+f"(d[25]), "+f"(d[26]), "+f"(d[27]), "+f"(d[28]), "+f"(d[29]), "+f"(d[30]), "+f"(d[31]),
      "+f"(d[32]), "+f"(d[33]), "+f"(d[34]), "+f"(d[35]), "+f"(d[36]), "+f"(d[37]), "+f"(d[38]), "+f"(d[39]),
      "+f"(d[40]), "+f"(d[41]), "+f"(d[42]), "+f"(d[43]), "+f"(d[44]), "+f"(d[45]), "+f"(d[46]), "+f"(d[47]),
      "+f"(d[48]), "+f"(d[49]), "+f"(d[50]), "+f"(d[51]), "+f"(d[52]), "+f"(d[53]), "+f"(d[54]), "+f"(d[55]),
      "+f"(d[56]), "+f"(d[57]), "+f"(d[58]), "+f"(d[59]), "+f"(d[60]), "+f"(d[61]), "+f"(d[62]), "+f"(d[63])
    : "r"(a0), "r"(a1), "r"(a2), "r"(a3), "l"(db), "r"(sd));
}
__device__ __forceinline__ void wgmma_rs_n24(float (&d)[12], uint32_t a0, uint32_t a1, uint32_t a2, uint32_t a3,
                                  uint64_t db, int sd) {
  asm volatile("{\n.reg .pred p;\nsetp.ne.b32 p, %17, 0;\n"
      "wgmma.mma_async.sync.aligned.m64n24k16.f32.bf16.bf16 {"
      "%0, %1, %2, %3, %4, %5, %6, %7, %8, %9, %10, %11"
      "}, {%12, %13, %14, %15}, %16, p, 1, 1, 1;\n}\n"
    : "+f"(d[0]), "+f"(d[1]), "+f"(d[2]), "+f"(d[3]), "+f"(d[4]), "+f"(d[5]), "+f"(d[6]), "+f"(d[7]),
      "+f"(d[8]), "+f"(d[9]), "+f"(d[10]), "+f"(d[11])
    : "r"(a0), "r"(a1), "r"(a2), "r"(a3), "l"(db), "r"(sd));
}

constexpr int KST = 4;
constexpr int K1_ST = 4, K1_STAGE = 45056;
constexpr int K1_SMEM = K1_ST * K1_STAGE + 640   + 1536   + 2560   + 128;

__device__ __forceinline__ float2 row_stats(uint4 v0, uint4 v1, uint4 v2) {
  const uint32_t wd[12] = {v0.x, v0.y, v0.z, v0.w, v1.x, v1.y, v1.z, v1.w, v2.x, v2.y, v2.z, v2.w};
  float sx = 0.f, sq = 0.f;
#pragma unroll
  for (int e = 0; e < 12; e++) {
    const float lo = bf_lo(wd[e]), hi = bf_hi(wd[e]);
    sx += lo + hi; sq = fmaf(lo, lo, fmaf(hi, hi, sq));
  }
#pragma unroll
  for (int o = 16; o; o >>= 1) { sx += __shfl_xor_sync(~0u, sx, o); sq += __shfl_xor_sync(~0u, sq, o); }
  const float mean = sx * (1.f / D_);
  return make_float2(rsqrtf(fmaxf(sq * (1.f / D_) - mean * mean, 0.f) + 1e-5f), mean);
}

__global__ void __cluster_dims__(2, 1, 1) __launch_bounds__(512, 1)
k1_qkv(const __grid_constant__ CUtensorMap tmx, const __grid_constant__ CUtensorMap tmw,
       const bf16* __restrict__ x, const bf16* __restrict__ w) {
  extern __shared__ __align__(1024) uint8_t sm[];
  float* cs = (float*)(sm + K1_ST * K1_STAGE);
  float2* rowab = (float2*)(sm + K1_ST * K1_STAGE + 640);
  float* red = (float*)(sm + K1_ST * K1_STAGE + 2176);
  const uint32_t sbase = smem_u32(sm);
  const uint32_t fullb = sbase + K1_ST * K1_STAGE + 4736, emptyb = fullb + 8 * K1_ST;
  const int tid = threadIdx.x, lane = tid & 31;
  const int warp = __shfl_sync(~0u, tid >> 5, 0);
  const int rank = blockIdx.x & 1, cl = blockIdx.x >> 1;
  const int m = cl / 6, n = (cl - m * 6) * 2 + rank;
  if (tid == 0) STAMP(0, 0);

  if (warp == 12) {
    if (lane == 0) {
      prefetch_map(&tmx); prefetch_map(&tmw);
      for (int i = 0; i < K1_ST; i++) { mbar_init(fullb + 8 * i, 1); mbar_init(emptyb + 8 * i, 6); }
      asm volatile("fence.mbarrier_init.release.cluster;" ::: "memory");
    }
    __syncwarp();
    cluster_arrive();
    bar_arrive(4, 512);
    if (elect_one()) {
#pragma unroll
      for (int kt = 0; kt < K1_ST; kt++) mbar_expect(fullb + 8 * kt, K1_STAGE);
      tma2d(sbase, &tmx, 0, m * 192, fullb);
      tma2d(sbase + 12288, &tmx, 0, m * 192 + 96, fullb);
#pragma unroll
      for (int j = 0; j < 5; j++) tma2d(sbase + 24576 + j * 4096, &tmw, n * 160 + j * 32, 0, fullb);
    }
    cluster_wait();
#pragma unroll 1
    for (int kt = 1; kt < 10; kt++) {
      const int s = kt % K1_ST;
      const uint32_t sa = sbase + s * K1_STAGE;
      if (kt >= K1_ST) mbar_wait(emptyb + 8 * s, ((kt / K1_ST) - 1) & 1);
      if (elect_one()) {
        if (kt >= K1_ST) mbar_expect(fullb + 8 * s, K1_STAGE);
        tma2d_mc(sa + rank * 12288, &tmx, kt * 64, m * 192 + rank * 96, fullb + 8 * s);
#pragma unroll
        for (int j = 0; j < 5; j++) tma2d(sa + 24576 + j * 4096, &tmw, n * 160 + j * 32, kt * 64, fullb + 8 * s);
      }
      if (kt == K1_ST - 1) pdl_trigger();
    }
    __syncwarp();
    cluster_arrive();
  } else if (warp > 12) {
    cluster_arrive();
    const int t96 = tid - 416;
    const uint32_t tag = __ldcg(&g_epoch) + 1;
    bar_sync(4, 512);
    mbar_wait(fullb, 0);
    if (m < 10) {
      const int ck = t96 % 20, rg = min(t96 / 20, 3);
      uint4 wv[16];
#pragma unroll
      for (int i = 0; i < 16; i++) wv[i] = ldg_nc(w + (size_t)(m * 64 + rg * 16 + i) * 1920 + n * 160 + ck * 8);
      float acc8[8];
#pragma unroll
      for (int i = 0; i < 8; i++) acc8[i] = 0.f;
#pragma unroll
      for (int i = 0; i < 16; i++) ACC8(acc8, wv[i]);
      *(float4*)&red[rg * 160 + ck * 8] = make_float4(acc8[0], acc8[1], acc8[2], acc8[3]);
      *(float4*)&red[rg * 160 + ck * 8 + 4] = make_float4(acc8[4], acc8[5], acc8[6], acc8[7]);
      bar_sync(1, 96);
      if (t96 < 80) {
        const float2 p0 = *(const float2*)&red[t96 * 2], p1 = *(const float2*)&red[160 + t96 * 2];
        const float2 p2 = *(const float2*)&red[320 + t96 * 2], p3 = *(const float2*)&red[480 + t96 * 2];
        st_relaxed(&g_cpart[(m * 12 + n) * 80 + t96], (p0.x + p1.x) + (p2.x + p3.x), (p0.y + p1.y) + (p2.y + p3.y), tag);
      }
    }
    if (tid == 416) STAMP(5, 7);
    bool ok = false;
    for (int it = 0; it < 64 && !ok; it++) {
      uint4 p[10], st[2];
#pragma unroll
      for (int k = 0; k < 10; k++) p[k] = ld_relaxed(&g_cpart[(k * 12 + n) * 80 + min(t96, 79)]);
#pragma unroll
      for (int k = 0; k < 2; k++) st[k] = ld_relaxed(&g_rowstat[min(m * 192 + k * 96 + t96, S_ - 1)]);
      ok = true;
      float s0 = 0.f, s1 = 0.f;
#pragma unroll
      for (int k = 0; k < 10; k++) {
        ok = ok && p[k].y == tag && p[k].w == tag;
        s0 += __uint_as_float(p[k].x); s1 += __uint_as_float(p[k].z);
      }
      if (t96 < 80) *(float2*)&cs[t96 * 2] = make_float2(s0, s1);
#pragma unroll
      for (int k = 0; k < 2; k++) {
        ok = ok && st[k].y == tag && st[k].w == tag;
        rowab[k * 96 + t96] = make_float2(__uint_as_float(st[k].x), -__uint_as_float(st[k].x) * __uint_as_float(st[k].z));
      }
      ok = __all_sync(~0u, ok);
      if (!ok) __nanosleep(300);
    }
    if (!ok) {
      const int c2 = min(t96, 79);
      float s0 = 0.f, s1 = 0.f;
#pragma unroll 1
      for (int k = 0; k < D_; k++) {
        const uint32_t v = *(const uint32_t*)(w + (size_t)k * 1920 + n * 160 + c2 * 2);
        s0 += bf_lo(v); s1 += bf_hi(v);
      }
      if (t96 < 80) *(float2*)&cs[t96 * 2] = make_float2(s0, s1);
#pragma unroll 1
      for (int i = 0; i < 64; i++) {
        const int r = (i >> 5) * 96 + (t96 & ~31) + (i & 31);
        const bf16* xr = x + (size_t)min(m * 192 + r, S_ - 1) * D_ + lane * 8;
        const float2 st = row_stats(ldg_nc(xr), ldg_nc(xr + 256), lane < 16 ? ldg_nc(xr + 512) : make_uint4(0u, 0u, 0u, 0u));
        if (lane == 0) rowab[r] = make_float2(st.x, -st.x * st.y);
      }
    }
    __syncwarp();
    bar_arrive(2, 96 + 384);
    if (tid == 416) STAMP(0, 5);
    if (tid == 416) STAMP(0, 7);
    __syncwarp();
    cluster_wait();
    cluster_arrive();
  } else {
    cluster_arrive();
    float acc[80];
    const uint64_t da0 = mkdesc(sbase + (warp >> 2) * 8192, 16, 1024, 1);
    const uint64_t db0 = mkdesc(sbase + 24576, 4096, 512, 2);
    const uint32_t tag = __ldcg(&g_epoch) + 1;
    const int srow = m * 192 + n * 16 + warp * 2;
    const bool dostat = warp < 8 && srow < S_;
    uint4 xv[2][3];
    bar_sync(4, 512);
    cluster_wait();
#pragma unroll
    for (int kt = 0; kt < 10; kt++) {
      const int s = kt % K1_ST;
      mbar_wait(fullb + 8 * s, (kt / K1_ST) & 1);
      if (kt == 0 && tid == 0) STAMP(0, 1);
      if (kt == 2 && tid == 0) STAMP(5, 0);
      if (kt == 4 && tid == 0) STAMP(5, 1);
      if (kt == 7 && tid == 0) STAMP(5, 2);
      const uint64_t da = da0 + s * (K1_STAGE >> 4), db = db0 + s * (K1_STAGE >> 4);
      WG_FENCE();
#pragma unroll
      for (int k = 0; k < 4; k++) wgmma_ss_n160(acc, da + k * 2, db + k * 64, (kt | k) != 0);
      WG_COMMIT();
      if (kt > 0) {
        WG_WAIT(1);
        if (kt - 1 + K1_ST < 10 && (tid & 127) < 2) mbar_arrive_cta(emptyb + 8 * ((kt - 1) % K1_ST), tid & 1);
      }
      if (kt == 0) {
#pragma unroll
        for (int i = 0; i < 2; i++) {
          const bf16* xr = x + (size_t)min(srow + i, S_ - 1) * D_ + lane * 8;
          xv[i][0] = xv[i][1] = xv[i][2] = make_uint4(0u, 0u, 0u, 0u);
          if (dostat) { xv[i][0] = ldg_nc(xr); xv[i][1] = ldg_nc(xr + 256); }
          if (dostat && lane < 16) xv[i][2] = ldg_nc(xr + 512);
        }
      }
      if ((kt == KST || kt == KST + 1) && dostat) {
        const float2 st = row_stats(xv[kt - KST][0], xv[kt - KST][1], xv[kt - KST][2]);
        if (lane == 0) st_relaxed(&g_rowstat[srow + kt - KST], st.x, st.y, tag);
      }
      __syncwarp();
    }
    cluster_arrive();
    WG_WAIT(0);
    fence_regs(acc);
    if (tid == 0) STAMP(0, 2);
    bar_sync(2, 96 + 384);
    if (tid == 0) STAMP(0, 3);
    const int row0 = m * 192 + warp * 16;
    if (row0 < S_) {
      const int g = lane >> 2, c = lane & 3, sec = n >> 2, grp = (row0 & 127) >> 3;
      const bool lo = c < 2;
      const float2 ab0 = rowab[warp * 16 + g], ab1 = rowab[warp * 16 + g + 8];
      const bool p0 = sec == 1 && ((POLY_MASK >> grp) & 1), p1 = sec == 1 && ((POLY_MASK >> (grp + 1)) & 1);
      const uint32_t padqv = sec == 0 ? (c == 2 ? 0x3F803F80u : 0x00003F80u) : (sec == 2 && c == 2 ? 0x00003F80u : 0u);
      const uint32_t padk = c == 2 ? 0x4A7A4B00u : 0x00004653u;
      const uint32_t pad0 = p0 ? padk : padqv, pad1 = p1 ? padk : padqv;
      const float f0 = sec == 0 ? QSCALE : (p0 ? 32768.f : 1.f), f1 = sec == 0 ? QSCALE : (p1 ? 32768.f : 1.f);
      const float a0 = ab0.x * f0, b0 = ab0.y * f0, a1 = ab1.x * f1, b1 = ab1.y * f1;
      const float r0 = p0 ? 9.313225746154785e-10f : 1.f, r1 = p1 ? 9.313225746154785e-10f : 1.f;
      const int cst = sec == 1 ? 2048 : 128, gst = sec == 1 ? 128 : 384;
      uint8_t* pe = (uint8_t*)g_qkv + (size_t)(n * 8) * HEAD_IMG + (row0 >> 7) * 6144 + grp * gst + lane * 4;
      uint8_t* pe1 = pe + cst;
      uint8_t* pe2 = pe1 + cst;
      uint8_t* pf = pe + gst;
      uint8_t* pf1 = pf + cst;
      uint8_t* pf2 = pf1 + cst;
      uint32_t u[20], v[20];
#pragma unroll
      for (int hp = 0; hp < 4; hp++) {
#pragma unroll
        for (int j = hp * 5; j < hp * 5 + 5; j++) {
          const float2 t = *(const float2*)&cs[j * 8 + c * 2];
          u[j] = pack_bf16(fmaf(acc[4 * j], a0, b0 * t.x), fmaf(acc[4 * j + 1], a0, b0 * t.y));
          v[j] = pack_bf16(fmaf(acc[4 * j + 2], a1, b1 * t.x), fmaf(acc[4 * j + 3], a1, b1 * t.y));
        }
        constexpr int HE = HEAD_IMG;
        const int oe = hp * 2 * HE, oo = oe + HE, j = hp * 5;
        *(uint32_t*)(pe + oe) = u[j];      *(uint32_t*)(pf + oe) = v[j];
        *(uint32_t*)(pe1 + oe) = u[j + 1]; *(uint32_t*)(pf1 + oe) = v[j + 1];
        *(uint32_t*)(pe2 + oe) = lo ? u[j + 2] : pad0; *(uint32_t*)(pf2 + oe) = lo ? v[j + 2] : pad1;
        *(uint32_t*)(pe + oo) = __shfl_xor_sync(~0u, lo ? u[j + 3] : u[j + 2], 2);
        *(uint32_t*)(pf + oo) = __shfl_xor_sync(~0u, lo ? v[j + 3] : v[j + 2], 2);
        *(uint32_t*)(pe1 + oo) = __shfl_xor_sync(~0u, lo ? u[j + 4] : u[j + 3], 2);
        *(uint32_t*)(pf1 + oo) = __shfl_xor_sync(~0u, lo ? v[j + 4] : v[j + 3], 2);
        const uint32_t tu = __shfl_xor_sync(~0u, u[j + 4], 2), tv = __shfl_xor_sync(~0u, v[j + 4], 2);
        *(uint32_t*)(pe2 + oo) = lo ? tu : pad0; *(uint32_t*)(pf2 + oo) = lo ? tv : pad1;
      }
      if (tid == 0) STAMP(5, 3);
      {
        float nm = 0.f;
#pragma unroll
        for (int hp = 0; hp < 4; hp++) {
          float sq[2][5];
#pragma unroll
          for (int i = 0; i < 5; i++) {
            const uint32_t x = u[hp * 5 + i], y = v[hp * 5 + i];
            sq[0][i] = fmaf(bf_lo(x), bf_lo(x), bf_hi(x) * bf_hi(x));
            sq[1][i] = fmaf(bf_lo(y), bf_lo(y), bf_hi(y) * bf_hi(y));
          }
          const float e0 = (sq[0][0] + sq[0][1] + (lo ? sq[0][2] : 0.f)) * r0, e1 = (sq[1][0] + sq[1][1] + (lo ? sq[1][2] : 0.f)) * r1;
          const float o0 = (sq[0][3] + sq[0][4] + (lo ? 0.f : sq[0][2])) * r0, o1 = (sq[1][3] + sq[1][4] + (lo ? 0.f : sq[1][2])) * r1;
          const float k0 = (lo ? e0 : o0) + __shfl_xor_sync(~0u, lo ? o0 : e0, 2);
          const float k1 = (lo ? e1 : o1) + __shfl_xor_sync(~0u, lo ? o1 : e1, 2);
          const float z = ((c & 1) ? k1 : k0) + __shfl_xor_sync(~0u, (c & 1) ? k0 : k1, 1);
          const uint32_t em = __reduce_max_sync(~0u, lo ? __float_as_uint(z) : 0u), om = __reduce_max_sync(~0u, lo ? 0u : __float_as_uint(z));
          if ((lane >> 1) == hp) nm = __uint_as_float((lane & 1) ? om : em);
        }
        if (lane < 8) g_nrm[(n * 8 + lane) * 128 + (row0 >> 4)] = nm;
      }
    }
    if (tid == 0) STAMP(0, 4);
  }
  cluster_wait();
  if (tid == 0) STAMP(0, 6);
}

constexpr int K2_SMEM = 2 * HEAD_IMG + 2 * 6144 + 2 * 10240 + 160 + 96;

__device__ __forceinline__ uint64_t desc64(uint32_t lo, uint32_t hi) {
  uint64_t d;
  asm("mov.b64 %0, {%1, %2};" : "=l"(d) : "r"(lo), "r"(hi));
  return d;
}
__device__ __forceinline__ uint32_t exp_pair(bool poly, float a, float b, uint32_t mk) {
  if (poly) {
    const uint32_t pk = __byte_perm(__float_as_uint(a), __float_as_uint(b), 0x6521);
    uint32_t m, q;
    asm("lop3.b32 %0, %1, %2, 0x3f803f80, 0xEA;" : "=r"(m) : "r"(pk), "r"(mk));
    asm("fma.rn.bf16x2 %0, %1, %1, %2;" : "=r"(q) : "r"(m), "r"(0x40014001u));
    return pk - m + q;
  }
  return pack_bf16(ex2(a), ex2(b));
}
constexpr int PV_GR = 4;
__device__ __forceinline__ void exp_pv(const float (&s)[64], float (&o)[12], uint64_t dv, uint32_t mk) {
#pragma unroll
  for (int k0 = 0; k0 < 8; k0 += PV_GR) {
    uint32_t p[4 * PV_GR];
#pragma unroll
    for (int i = 0; i < 4 * PV_GR; i++)
      p[i] = exp_pair((POLY_MASK >> (k0 * 2 + i / 2)) & 1, s[k0 * 8 + 2 * i], s[k0 * 8 + 2 * i + 1], mk);
    WG_FENCE();
#pragma unroll
    for (int k = 0; k < PV_GR; k++)
      wgmma_rs_n24(o, p[4 * k], p[4 * k + 1], p[4 * k + 2], p[4 * k + 3], dv + (k0 + k) * 48, 1);
  }
}
__device__ __forceinline__ void load_q(uint32_t (&q)[6], const uint8_t* p) {
  q[0] = __ldcg((const uint32_t*)p);         q[1] = __ldcg((const uint32_t*)(p + 384));
  q[2] = __ldcg((const uint32_t*)(p + 128)); q[3] = __ldcg((const uint32_t*)(p + 512));
  q[4] = __ldcg((const uint32_t*)(p + 256)); q[5] = __ldcg((const uint32_t*)(p + 640));
}
__device__ __forceinline__ float rcp(float x) {
  float y;
  asm("rcp.approx.ftz.f32 %0, %1;" : "=f"(y) : "f"(x));
  return y;
}
__device__ __forceinline__ int img_off(int chunk) { return chunk * 2048; }
__device__ __forceinline__ void store_o(const float (&o)[12], int tile) {
  int tid, bid;
  asm volatile("mov.u32 %0, %%tid.x;" : "=r"(tid));
  asm volatile("mov.u32 %0, %%ctaid.x;" : "=r"(bid));
  const int head = bid >> 2;
  uint8_t* dst = (uint8_t*)g_o + ((bid & 3) * 4 + (tile >> 1)) * 163840 + (tile & 1) * 1024 + ((tid >> 5) & 3) * 256 + (tid & 31) * 4;
  const int oc = (head >> 1) * 5 + (head & 1) * 2;
  const int o0 = img_off(oc), o1 = img_off(oc + 1), o2 = img_off((head >> 1) * 5 + 4) + (head & 1) * 8;
  const float i0 = rcp(__shfl_sync(~0u, o[8], 2, 4)), i1 = rcp(__shfl_sync(~0u, o[10], 2, 4));
  *(uint32_t*)(dst + o0) = pack_bf16(o[0] * i0, o[1] * i0); *(uint32_t*)(dst + o0 + 128) = pack_bf16(o[2] * i1, o[3] * i1);
  *(uint32_t*)(dst + o1) = pack_bf16(o[4] * i0, o[5] * i0); *(uint32_t*)(dst + o1 + 128) = pack_bf16(o[6] * i1, o[7] * i1);
  if ((tid & 3) < 2) {
    *(uint32_t*)(dst + o2) = pack_bf16(o[8] * i0, o[9] * i0);
    *(uint32_t*)(dst + o2 + 128) = pack_bf16(o[10] * i1, o[11] * i1);
  }
}

struct Maps5 { CUtensorMap m[5]; };

__global__ void __launch_bounds__(512, 1)
k2_attn(const __grid_constant__ Maps5 maps, const bf16* __restrict__ wo, uint32_t mk) {
  const CUtensorMap* tmw = maps.m;
  extern __shared__ __align__(1024) uint8_t sm[];
  const uint32_t sbase = smem_u32(sm);
  float* part = (float*)(sm + 2 * HEAD_IMG);
  const uint32_t rbuf = sbase + 2 * HEAD_IMG + 2 * 6144;
  const uint32_t kvb = rbuf + 2 * 10240;
  const uint32_t partb = kvb + 128, rbar = kvb + 144;
  const int tid = threadIdx.x, lane = tid & 31;
  const int warp = __shfl_sync(~0u, tid >> 5, 0);
  const int head = blockIdx.x >> 2, qb = blockIdx.x & 3;

  if (tid == 0) STAMP(1, 0);
  if (tid == 0) {
    for (int i = 0; i < 16; i++) mbar_init(kvb + 8 * i, 1);
    mbar_init(partb, 128); mbar_init(partb + 8, 128); mbar_init(rbar, 1); mbar_init(rbar + 8, 1);
    asm volatile("fence.mbarrier_init.release.cluster;" ::: "memory");
  }
  __syncthreads();

  if (warp >= 12) {
    asm volatile("setmaxnreg.dec.sync.aligned.u32 32;");
    if (warp == 12) {
      const uint8_t* kimg = (const uint8_t*)g_qkv + (size_t)(32 + head) * HEAD_IMG;
      if (elect_one()) {
#pragma unroll
        for (int b = 0; b < 16; b++) mbar_expect(kvb + 8 * b, 12288);
      }
      pdl_wait();
#pragma unroll 1
      for (int b = 0; b < 16; b++) {
        if (elect_one()) {
          bulk_ld(sbase + b * 6144, kimg + b * 6144, 6144, kvb + 8 * b);
          bulk_ld(sbase + HEAD_IMG + b * 6144, kimg + 32 * HEAD_IMG + b * 6144, 6144, kvb + 8 * b);
        }
        if (b >= 2) mbar_wait(kvb + 8 * (b - 1), 0);
      }
      pdl_trigger();
    }
    if (warp > 12) {
      const int t96 = tid - 416, ck = min(t96, 79), nt = ck / 10;
      float* red = (float*)(sm + K2_SMEM - 96);
#pragma unroll 1
      for (int i = 0; i < 5; i++) {
        const int k = blockIdx.x * 5 + i, pr = k / 40, r = k - pr * 40;
        const uint4 v = ldg_nc(wo + (pr * 40 + (r < 16 ? r : (r < 32 ? r + 4 : (r < 36 ? r - 16 : r)))) * D_ + ck * 8);
        g_wo[((nt * 10 + (k >> 6)) * 10 + ck - nt * 10) * 64 + (k & 63)] = v;
        float t = ((bf_lo(v.x) + bf_hi(v.x)) + (bf_lo(v.y) + bf_hi(v.y))) + ((bf_lo(v.z) + bf_hi(v.z)) + (bf_lo(v.w) + bf_hi(v.w)));
        if (t96 >= 80) t = 0.f;
#pragma unroll
        for (int o = 16; o; o >>= 1) t += __shfl_xor_sync(~0u, t, o);
        if (lane == 0) red[(t96 >> 5) * 8 + i] = t;
      }
      bar_sync(1, 96);
      if (t96 < 5) {
        const float mu = (red[t96] + red[8 + t96] + red[16 + t96]) * (1.f / D_);
        const float hi = bf_lo(pack_bf16(mu, 0.f));
        g_wm[blockIdx.x * 5 + t96] = make_uint4(pack_bf16(hi, mu - hi), 0u, 0u, 0u);
      }
    }
    if (tid == 384) {
      if (blockIdx.x == 0) g_epoch = g_epoch + 1;
      mbar_wait(kvb + 8 * 15, 0);
      STAMP(1, 2);
      uint8_t* pdst = nullptr;
      uint32_t pbytes = 0;
#pragma unroll 1
      for (int i = 0; i < 8; i++) {
        const int p = blockIdx.x + 128 * i;
        uint8_t* dst = nullptr;
        uint32_t bytes = 0;
        if (i < 7 && p < 856) {
          asm volatile("cp.async.bulk.wait_group.read 0;" ::: "memory");
          const CUtensorMap* tm;
          int c1, c2;
          if (p < 640) {
            const int nt = p / 80, r = p - nt * 80, ph = r / 40, st = (r - ph * 40) >> 1, up = r & 1;
            bytes = ph ? 6656 : 7168;
            dst = (uint8_t*)g_wgu + nt * 552960 + ph * 286720 + st * 2 * bytes + up * (bytes >> 1);
            tm = &tmw[ph * 2 + up]; c1 = ph ? 112 + nt * 13 : nt * 14; c2 = st * 2;
          } else {
            const int nk = p - 640, nt = nk / 27;
            bytes = 10240;
            dst = (uint8_t*)g_wd + (size_t)nk * 10240;
            tm = &tmw[4]; c1 = nt * 10; c2 = nk - nt * 27;
          }
          mbar_expect(rbar + 8 * (i & 1), bytes);
          tma4d(rbuf + (i & 1) * 10240, tm, c1, c2, rbar + 8 * (i & 1));
        }
        if (pbytes) {
          mbar_wait(rbar + 8 * ((i - 1) & 1), ((i - 1) >> 1) & 1);
          if (pbytes == 10240) {
            bulk_st(pdst, rbuf + ((i - 1) & 1) * 10240, pbytes);
          } else {
            bulk_st(pdst, rbuf + ((i - 1) & 1) * 10240, pbytes >> 1);
            bulk_st(pdst + pbytes, rbuf + ((i - 1) & 1) * 10240 + (pbytes >> 1), pbytes >> 1);
          }
          asm volatile("cp.async.bulk.commit_group;" ::: "memory");
        }
        pdst = dst; pbytes = bytes;
      }
      asm volatile("cp.async.bulk.wait_group.read 0;" ::: "memory");
      STAMP(1, 6);
    }
  } else {
    asm volatile("setmaxnreg.inc.sync.aligned.u32 160;");
    const int wg = warp >> 2;
    const uint8_t* qthr = (const uint8_t*)g_qkv + (size_t)head * HEAD_IMG + qb * 64 * 384 + (warp & 3) * 768 + lane * 4;
    const uint32_t klo0 = ((sbase & 0x3FFFF) >> 4) | (128u << 16), vlo0 = (((sbase + HEAD_IMG) & 0x3FFFF) >> 4) | (24u << 16);
    constexpr uint64_t KSTEP2 = (uint64_t)(int64_t)(256 - (128 << 16));
    constexpr uint64_t KV2K = 384 - (HEAD_IMG >> 4) + (104 << 16);
    const int nun = wg == 1 ? 4 : 3;
    uint32_t utile = wg == 0 ? 0x210u : (wg == 1 ? 0x4235u : 0x576u);
    uint32_t ubeg = wg == 0 ? 0u : (wg == 1 ? 0x0b00u : 0x600u);
    uint32_t ulen = wg == 0 ? 0x0b1010u : (wg == 1 ? 0x10051006u : 0x0a1010u);
    pdl_wait();
    if (tid == 0) STAMP(1, 1);
    uint32_t q[6];
    load_q(q, qthr + (utile & 15) * 3072);
    bool fast;
    {
      const uint4 kn = __ldcg((const uint4*)&g_nrm[(32 + head) * 128 + lane * 4]);
      const uint4 vn = __ldcg((const uint4*)&g_nrm[(64 + head) * 128 + lane * 4]);
      const float qv = __ldcg(&g_nrm[head * 128 + qb * 32 + lane]);
      const float k2 = __uint_as_float(__reduce_max_sync(~0u, max(max(kn.x, kn.y), max(kn.z, kn.w))));
      const float v2 = __uint_as_float(__reduce_max_sync(~0u, max(max(vn.x, vn.y), max(vn.z, vn.w))));
      const float q2 = __uint_as_float(__reduce_max_sync(~0u, __float_as_uint(qv)));
      fast = q2 * k2 <= 3400.f && v2 < 1e24f && v2 > 1e-24f;
    }
    if (fast) {
#pragma unroll 1
      for (int u = 0; u < nun; u++) {
        const uint32_t b0 = ubeg & 15;
        const bool wt = u == 0 || (wg == 1 && u == 1);
        float s[64], o[12];
#pragma unroll
        for (int i = 0; i < 12; i++) o[i] = 0.f;
        uint32_t vlo = vlo0 + b0 * 384, kb = kvb + b0 * 8;
        const uint32_t vend = vlo + ((ulen & 255) - 1) * 384;
        if (wt) mbar_wait(kb, 0);
        if (tid == 0) STAMP(5, 4 + u);
        fence_regs(o);
        WG_FENCE();
        wgmma_rs_n128(s, q[0], q[1], q[2], q[3], desc64(klo0 + b0 * 384, 8), 0);
        wgmma_rs_n128(s, q[4], q[5], 0, 0, desc64(klo0 + b0 * 384, 8) + KSTEP2, 1);
        WG_COMMIT();
#pragma unroll 1
        for (; vlo != vend; vlo += 384) {
          if (wt) { kb += 8; mbar_wait(kb, 0); }
          WG_WAIT(0);
          fence_regs(s); fence_regs(o);
          const uint64_t dv = desc64(vlo, 8);
          exp_pv(s, o, dv, mk);
          wgmma_rs_n128(s, q[0], q[1], q[2], q[3], dv + KV2K, 0);
          wgmma_rs_n128(s, q[4], q[5], 0, 0, dv + (KV2K + KSTEP2), 1);
          WG_COMMIT();
        }
        WG_WAIT(0);
        fence_regs(s); fence_regs(o);
        if (u + 1 < nun) load_q(q, qthr + ((utile >> 4) & 15) * 3072);
        exp_pv(s, o, desc64(vlo, 8), mk);
        WG_COMMIT();
        WG_WAIT(0);
        fence_regs(o);
        if (wg == 1 && !(u & 1)) {
          float4* pp = (float4*)(part + u * 768) + (tid & 127);
          pp[0] = make_float4(o[0], o[1], o[2], o[3]);
          pp[128] = make_float4(o[4], o[5], o[6], o[7]);
          pp[256] = make_float4(o[8], o[9], o[10], o[11]);
          mbar_arrive(partb + 4 * u);
        } else {
          if (wg != 1 && u == 2) {
            const int pi = wg == 0 ? 1 : 0;
            mbar_wait(partb + 8 * pi, 0);
            const float4* pp = (const float4*)(part + pi * 1536) + (tid & 127);
            const float4 x0 = pp[0], x1 = pp[128], x2 = pp[256];
            o[0] += x0.x; o[1] += x0.y; o[2] += x0.z; o[3] += x0.w; o[4] += x1.x; o[5] += x1.y;
            o[6] += x1.z; o[7] += x1.w; o[8] += x2.x; o[9] += x2.y; o[10] += x2.z; o[11] += x2.w;
          }
          store_o(o, utile & 15);
        }
        utile >>= 4; ubeg >>= 4; ulen >>= 8;
      }
      if ((tid & 127) == 0) STAMP(1, 3 + wg);
    } else {
#pragma unroll 1
      for (int tile = wg; tile < 8; tile += 3) {
        load_q(q, qthr + tile * 3072);
        if ((lane & 3) >= 2) { q[4] = 0; q[5] = 0; }
        float o[12], m0 = -INFINITY, m1 = -INFINITY;
#pragma unroll
        for (int i = 0; i < 12; i++) o[i] = 0.f;
#pragma unroll 1
        for (int b = 0; b < 16; b++) {
          float s[64];
          mbar_wait(kvb + 8 * b, 0);
          WG_FENCE();
          wgmma_rs_n128(s, q[0], q[1], q[2], q[3], desc64(klo0 + b * 384, 8), 0);
          wgmma_rs_n128(s, q[4], q[5], 0, 0, desc64(klo0 + b * 384, 8) + KSTEP2, 1);
          WG_COMMIT();
          WG_WAIT(0);
          fence_regs(s);
          float x0 = m0, x1 = m1;
#pragma unroll
          for (int j = 0; j < 16; j++) {
            if ((POLY_MASK >> j) & 1) {
#pragma unroll
              for (int i = 0; i < 4; i++) s[4 * j + i] *= (1.f / 32768.f);
            }
            x0 = fmaxf(x0, fmaxf(s[4 * j], s[4 * j + 1]));
            x1 = fmaxf(x1, fmaxf(s[4 * j + 2], s[4 * j + 3]));
          }
          x0 = fmaxf(x0, __shfl_xor_sync(~0u, x0, 1)); x0 = fmaxf(x0, __shfl_xor_sync(~0u, x0, 2));
          x1 = fmaxf(x1, __shfl_xor_sync(~0u, x1, 1)); x1 = fmaxf(x1, __shfl_xor_sync(~0u, x1, 2));
          const float al0 = ex2(m0 - x0), al1 = ex2(m1 - x1);
          m0 = x0; m1 = x1;
#pragma unroll
          for (int i = 0; i < 12; i++) o[i] *= (i & 2) ? al1 : al0;
          uint32_t p[32];
#pragma unroll
          for (int i = 0; i < 32; i++) {
            const float mm = (i & 1) ? m1 : m0;
            p[i] = pack_bf16(ex2(s[2 * i] - mm), ex2(s[2 * i + 1] - mm));
          }
          fence_regs(o);
          WG_FENCE();
#pragma unroll
          for (int k = 0; k < 8; k++)
            wgmma_rs_n24(o, p[4 * k], p[4 * k + 1], p[4 * k + 2], p[4 * k + 3], desc64(vlo0 + b * 384 + k * 48, 8), 1);
          WG_COMMIT();
          WG_WAIT(0);
          fence_regs(o);
        }
        store_o(o, tile);
      }
    }
  }
}

constexpr int K3_ST = 4, K3_STAGE = 37888, K3_NB = 4, K3_NT = 6;
constexpr int K3_SMEM = K3_ST * K3_STAGE + 24576 + 20480 + 256;

template <int N> struct Acc { float v[N]; };

__global__ void __cluster_dims__(2, 1, 1) __launch_bounds__(288, 1)
k3_proj(const __grid_constant__ CUtensorMap tmx) {
  extern __shared__ __align__(1024) uint8_t sm[];
  const uint32_t sbase = smem_u32(sm);
  const uint8_t* xch = sm + K3_ST * K3_STAGE;
  const uint8_t* res = sm + K3_ST * K3_STAGE + 24576;
  const uint32_t fullb = smem_u32(res) + 20480, emptyb = fullb + 8 * K3_ST, resb = emptyb + 8 * K3_ST, xchb = resb + 8;
  const int tid = threadIdx.x, lane = tid & 31;
  const int warp = __shfl_sync(~0u, tid >> 5, 0);
  const int rank = blockIdx.x & 1;
  const int n = blockIdx.x & 7, m = blockIdx.x >> 3;
  if (tid == 0) STAMP(2, 0);
  if (warp == 8) {
    if (elect_one()) {
#pragma unroll
      for (int i = 0; i < K3_ST; i++) { mbar_init(fullb + 8 * i, 1); mbar_init(emptyb + 8 * i, 4); }
      mbar_init(resb, 1); mbar_init(xchb, 1);
      mbar_expect(xchb, 24576);
      asm volatile("fence.mbarrier_init.release.cluster;" ::: "memory");
    }
    __syncwarp();
  }
  cluster_arrive();
  if (warp == 8) {
    const uint8_t* wk = (const uint8_t*)g_wo + n * 102400;
    const uint8_t* ws = (const uint8_t*)g_wo + (n ^ 1) * 102400;
    const uint8_t* ab = (const uint8_t*)g_o + m * 163840;
    prefetch_map(&tmx);
    cluster_wait();
    pdl_wait();
    if (lane == 0) STAMP(2, 6);
#pragma unroll 1
    for (int i = 0; i < K3_NT; i++) {
      const int s = i % K3_ST, kt = i < K3_NB ? i + rank * K3_NT : i;
      const uint32_t sa = sbase + s * K3_STAGE, fb = fullb + 8 * s;
      if (i >= K3_ST) mbar_wait(emptyb + 8 * s, 0);
      if (elect_one()) {
        mbar_expect(fb, i < K3_NB ? 37888 : 27648);
        if (i < K3_NB) bulk_ld(sa, ab + kt * 16384, 16384, fb);
        else bulk_ld_mc(sa + rank * 8192, ab + kt * 16384 + rank * 8192, 8192, fb);
        bulk_ld(sa + 16384, wk + kt * 10240, 10240, fb);
        bulk_ld(sa + 26624, (const uint8_t*)g_wm + kt * 1024, 1024, fb);
        if (i < K3_NB) bulk_ld(sa + 27648, ws + kt * 10240, 10240, fb);
        if (i == K3_ST - 1) {
          mbar_expect(resb, 20480);
          tma2d(smem_u32(res), &tmx, n * 80, m * 128, resb);
          tma2d(smem_u32(res) + 10240, &tmx, n * 80, m * 128 + 64, resb);
        }
      }
      if (i == 0) pdl_trigger();
    }
    cluster_arrive();
  } else {
    const int g = lane >> 2, c = lane & 3;
    const int row = m * 128 + warp * 16 + g;
    float mu0 = __uint_as_float(__ldcg(&g_rowstat[row].z)), mu1 = __uint_as_float(__ldcg(&g_rowstat[row + 8].z));
    float acc[84];
    float (&keep)[44] = ((Acc<44>*)acc)->v;
    const uint64_t da0 = mkdesc(sbase + (warp >> 2) * 1024, 2048, 128, 0);
    const uint64_t db0 = mkdesc(sbase + 16384, 128, 1024, 0);
    cluster_wait();
#pragma unroll 1
    for (int i = 0; i < K3_NB; i++) {
      mbar_wait(fullb + 8 * i, 0);
      if (i == 0 && tid == 0) STAMP(2, 2);
      const uint64_t da = da0 + i * (K3_STAGE >> 4), db = db0 + i * (K3_STAGE >> 4);
      WG_FENCE();
#pragma unroll
      for (int k = 0; k < 4; k++) wgmma_ss_n168(acc, da + k * 256, db + k * 16, (i | k) != 0);
      WG_COMMIT();
      if (i > 0) {
        WG_WAIT(1);
        if (i - 1 + K3_ST < K3_NT && (tid & 127) < 2) mbar_arrive_cta(emptyb + 8 * (i - 1), tid & 1);
      }
    }
    const uint32_t rx = mapa(smem_u32(xch) + tid * 16, rank ^ 1), rb = mapa(xchb, rank ^ 1);
    WG_WAIT(0);
    fence_regs(acc);
    st_async4(rx, acc[40], acc[41], acc[42], acc[43], rb);
    if (tid == 0) STAMP(2, 1);
#pragma unroll
    for (int i = K3_NB; i < K3_NT; i++) {
      const int s = i % K3_ST;
      mbar_wait(fullb + 8 * s, 1);
      const uint64_t da = da0 + s * (K3_STAGE >> 4), db = db0 + s * (K3_STAGE >> 4);
      WG_FENCE();
#pragma unroll
      for (int k = 0; k < 4; k++) wgmma_ss_n88(keep, da + k * 256, db + k * 16, 1);
      WG_COMMIT();
#pragma unroll
      for (int j = (i - K3_NB) * 3; j < (i - K3_NB) * 3 + 3; j++)
        if (j < 5) SEND8(rx + (j + 1) * 4096, acc, 44 + 8 * j, rb);
    }
    cluster_arrive();
    const uint8_t* sp = res + (warp * 16 + g) * 160 + c * 4;
    uint32_t rv[20];
    mbar_wait(resb, 0);
#pragma unroll
    for (int j = 0; j < 10; j++) {
      rv[2 * j] = *(const uint32_t*)(sp + j * 16);
      rv[2 * j + 1] = *(const uint32_t*)(sp + 1280 + j * 16);
    }
    WG_WAIT(0);
    fence_regs(keep);
    if (tid == 0) STAMP(2, 3);
    mbar_wait(xchb, 0);
    if (tid == 0) STAMP(2, 5);
    const uint8_t* xp = xch + tid * 16;
    {
      const float4 p = *(const float4*)xp;
      mu0 += __shfl_sync(~0u, (keep[40] + p.x) + (keep[41] + p.y), 0, 4);
      mu1 += __shfl_sync(~0u, (keep[42] + p.z) + (keep[43] + p.w), 0, 4);
    }
    uint8_t* himg = (uint8_t*)g_h + m * 163840 + img_off(n * 10) + warp * 256 + lane * 4;
    float q0 = 0.f, q1 = 0.f;
#pragma unroll
    for (int j = 0; j < 10; j++) {
      const uint2 p = *(const uint2*)(xp + ((j >> 1) + 1) * 4096 + (j & 1) * 8);
      const float x0 = (keep[4 * j] + bf_lo(p.x)) + (bf_lo(rv[2 * j]) - mu0), x1 = (keep[4 * j + 1] + bf_hi(p.x)) + (bf_hi(rv[2 * j]) - mu0);
      const float y0 = (keep[4 * j + 2] + bf_lo(p.y)) + (bf_lo(rv[2 * j + 1]) - mu1), y1 = (keep[4 * j + 3] + bf_hi(p.y)) + (bf_hi(rv[2 * j + 1]) - mu1);
      *(uint32_t*)(himg + img_off(j)) = pack_bf16(x0, x1);
      *(uint32_t*)(himg + img_off(j) + 128) = pack_bf16(y0, y1);
      q0 = fmaf(x0, x0, fmaf(x1, x1, q0)); q1 = fmaf(y0, y0, fmaf(y1, y1, q1));
    }
    q0 += __shfl_xor_sync(~0u, q0, 1); q0 += __shfl_xor_sync(~0u, q0, 2);
    q1 += __shfl_xor_sync(~0u, q1, 1); q1 += __shfl_xor_sync(~0u, q1, 2);
    if (c < 2) g_hpart[n * S_ + row + c * 8] = c ? q1 : q0;
    if (n == 0 && c < 2) g_hmean[row + c * 8] = c ? mu1 : mu0;
    if (tid == 0) STAMP(2, 4);
  }
  cluster_wait();
}

constexpr int P3_NB = 12, P3_NT = 15;
constexpr int K4_G = 2, K4_NS = 4, K4_NJ = 20;
constexpr int K4_RB = 163840, K4_BST = 7168 * K4_G, K4_XCH = 147456, K4_STG = K4_XCH + 40960, K4_BAR = K4_RB + K4_NS * K4_BST;
constexpr int K4_SMEM = K4_BAR + 384;

__device__ __forceinline__ void wait_flags(const uint4* f, uint32_t tag, uint32_t need, uint32_t& seen) {
  if ((seen & need) == need) return;
  for (uint32_t it = 0; (seen & need) != need; it++) {
    if (it > (1u << 20)) wait_timeout();
    if (it) __nanosleep(150);
    uint32_t v = 0;
    if ((threadIdx.x & 31) < 8) asm volatile("ld.acquire.gpu.global.u32 %0, [%1];" : "=r"(v) : "l"((const uint32_t*)f + (threadIdx.x & 7)) : "memory");
    seen = __ballot_sync(~0u, v == tag) & 255;
  }
  asm volatile("fence.proxy.async.global;" ::: "memory");
}

template <int MODE>
__global__ void __cluster_dims__(2, 1, 1) __launch_bounds__(384, 1)
k45_ffn(const __grid_constant__ CUtensorMap tmo) {
  extern __shared__ __align__(1024) uint8_t sm[];
  const uint32_t sbase = smem_u32(sm);
  const uint32_t afull = sbase + K4_BAR, bfull = afull + 80, bempty = bfull + 8 * K4_NS, full3 = bempty + 8 * K4_NS;
  const uint32_t empty3 = full3 + 32, afree = empty3 + 32, xchb = afree + 32;
  const int tid = threadIdx.x, lane = tid & 31;
  const int warp = __shfl_sync(~0u, tid >> 5, 0);
  const int rank = blockIdx.x & 1;
  const int n1 = (blockIdx.x >> 1) & 7, m1 = (blockIdx.x >> 4) * 2 + rank;
  const int n3 = blockIdx.x & 7, m3 = blockIdx.x >> 3;
  if (tid == 0) STAMP(3, 0);
  if (warp == 8) {
    if (elect_one()) {
#pragma unroll
      for (int i = 0; i < 10; i++) mbar_init(afull + 8 * i, 1);
#pragma unroll
      for (int i = 0; i < 4; i++) {
        mbar_init(bfull + 8 * i, 1); mbar_init(bempty + 8 * i, 4); mbar_init(full3 + 8 * i, 1); mbar_init(empty3 + 8 * i, 4);
        mbar_init(afree + 8 * i, 2);
      }
      mbar_init(xchb, 1);
      mbar_expect(xchb, 20480);
      asm volatile("fence.mbarrier_init.release.cluster;" ::: "memory");
    }
    __syncwarp();
  }
  cluster_arrive();
  if (warp >= 8) {
    cluster_wait();
    if (warp == 8) {
      if (lane == 0) STAMP(3, 7);
      const uint8_t* src = (const uint8_t*)g_wgu + n1 * 552960;
      const uint8_t* hb = (const uint8_t*)g_h + (size_t)m1 * 163840;
#pragma unroll 1
      for (int j = 0; j < (MODE == 2 ? 0 : 40); j++) {
        const uint32_t s8 = (j & 3) * 8, sz = j < 20 ? 14336 : 13312;
        if (j == 2) {
          pdl_wait();
          if (lane == 0) STAMP(3, 1);
          if (elect_one()) {
#pragma unroll
            for (int kt = 0; kt < 2 / 2 + 1; kt++) { mbar_expect(afull + 8 * kt, 16384); bulk_ld(sbase + kt * 16384, hb + kt * 16384, 16384, afull + 8 * kt); }
          }
        }
        if (j >= 4) mbar_wait(bempty + s8, ((j >> 2) - 1) & 1);
        if (elect_one()) {
          mbar_expect(bfull + s8, sz);
          if ((j & 1) == rank) bulk_ld_mc(sbase + K4_RB + s8 * (K4_BST / 8), src, sz, bfull + s8);
          if (j > 2 && j < 18 && (j & 1)) {
            mbar_expect(afull + 4 + j * 4, 16384);
            bulk_ld(sbase + 8192 + j * 8192, hb + 8192 + j * 8192, 16384, afull + 4 + j * 4);
          }
        }
        src += sz;
      }
    } else if (warp == 9) {
      prefetch_map(&tmo);
      const uint32_t tag = __ldcg(&g_epoch);
#pragma unroll 1
      for (int ph = 0; ph < (MODE == 2 ? 0 : 2); ph++) {
        bar_sync(5 + ph, 256 + 32);
        if (lane == 0) {
          asm volatile("st.release.gpu.global.u32 [%0], %1;" ::"l"((uint32_t*)&g_flag[ph * 32 + m1 * 2] + n1), "r"(tag) : "memory");
          STAMP(3, 5 + ph);
        }
        __syncwarp();
      }
    } else {
      const uint8_t* wk = (const uint8_t*)g_wd + n3 * 276480;
      const uint8_t* ws = (const uint8_t*)g_wd + (n3 ^ 1) * 276480;
      const uint8_t* ab = (const uint8_t*)g_hh + (size_t)m3 * 442368;
      const uint32_t tag = __ldcg(&g_epoch);
      uint32_t seen = 0;
#pragma unroll 1
      for (int i = 0; i < (MODE == 1 ? 0 : P3_NT); i++) {
        const int kt = i < 7 ? rank * 7 + i : (i < P3_NB ? rank * (P3_NB - 7) + 7 + i : P3_NB + i);
        const uint32_t sa = sbase + (i & 3) * 36864, fb = full3 + 8 * (i & 3);
        if (warp == 11) {
          const int q = kt * 8 - (i < 7 ? 0 : 112), w = i < 7 ? 14 : 13;
          if (MODE == 0 && i == 0) mbar_wait(afull + 72, 0);
          if (i == 7) seen = 0;
          wait_flags(&g_flag[(i < 7 ? 0 : 32) + m3 * 2], tag, 1u << (q / w) | 1u << ((q + 7) / w), seen);
          if (lane == 0 && (i == 0 || i == 7)) STAMP(4, i ? 7 : 6);
        }
        if (i < 4) { if (MODE == 0) mbar_wait(afree + 8 * i, 0); }
        else mbar_wait(empty3 + 8 * (i & 3), ((i >> 2) - 1) & 1);
        if (warp == 10) {
          if (elect_one()) {
            mbar_expect(fb, i < P3_NB ? 36864 : 26624);
            bulk_ld(sa + 16384, wk + kt * 10240, 10240, fb);
            if (i < P3_NB) bulk_ld(sa + 26624, ws + kt * 10240, 10240, fb);
          }
        } else {
          if (elect_one()) {
            if (i < P3_NB) bulk_ld(sa, ab + kt * 16384, 16384, fb);
            else bulk_ld_mc(sa + rank * 8192, ab + kt * 16384 + rank * 8192, 8192, fb);
          }
        }
      }
    }
    __syncwarp();
    cluster_arrive();
    asm volatile("barrier.cluster.wait.aligned; // producers" ::: "memory");
  } else {
    const int wg = warp >> 2;
    const uint64_t da0 = mkdesc(sbase + wg * 1024, 2048, 128, 0);
    const uint64_t db0 = mkdesc(sbase + K4_RB, 128, 256, 0);
    cluster_wait();
    float acc[80];
    if constexpr (MODE != 2) {
    float a1[112], a2[104];
    int s = 0, ph = 0, sprev = 0;
#pragma unroll 1
    for (int j = 0; j < K4_NJ; j++) {
      if ((j * K4_G) % 4 == 0) mbar_wait(afull + 2 * K4_G * j, 0);
      mbar_wait(bfull + 8 * s, ph);
      if (j == 0 && tid == 0) STAMP(3, 2);
      const uint64_t da = da0 + j * K4_G * 256, db = db0 + s * (K4_BST >> 4);
      WG_FENCE();
#pragma unroll
      for (int k = 0; k < K4_G; k++) wgmma_ss_n224(a1, da + k * 256, db + k * 448, (j | k) != 0);
      WG_COMMIT();
      if (j > 0) {
        WG_WAIT(1);
        if ((tid & 127) < 2) mbar_arrive_cta(bempty + 8 * sprev, tid & 1);
      }
      sprev = s;
      if (++s == K4_NS) { s = 0; ph ^= 1; }
    }
    uint8_t* hd = (uint8_t*)g_hh + (size_t)m1 * 442368 + warp * 256 + lane * 4;
    WG_WAIT(0);
    fence_regs(a1);
    if ((tid & 127) < 2) mbar_arrive_cta(bempty + 8 * ((K4_NJ - 1) % K4_NS), tid & 1);
    if (tid == 0) STAMP(3, 3);
#define STORE_H(a, off, ptr, c) do { uint8_t* p_ = ptr; \
      *(uint32_t*)p_ = pack_bf16(a[4 * (c)] * a[off + 4 * (c)], a[4 * (c) + 1] * a[off + 1 + 4 * (c)]); \
      *(uint32_t*)(p_ + 128) = pack_bf16(a[4 * (c) + 2] * a[off + 2 + 4 * (c)], a[4 * (c) + 3] * a[off + 3 + 4 * (c)]); } while (0)
#pragma unroll
    for (int c = 0; c < 14; c++) STORE_H(a1, 56, hd + img_off(n1 * 14 + c), c);
    bar_arrive(5, 256 + 32);
#pragma unroll 1
    for (int j = 0; j < K4_NJ; j++) {
      mbar_wait(bfull + 8 * s, ph);
      const uint64_t da = da0 + j * K4_G * 256, db = db0 + s * (K4_BST >> 4);
      WG_FENCE();
#pragma unroll
      for (int k = 0; k < K4_G; k++) wgmma_ss_n208(a2, da + k * 256, db + k * 416, (j | k) != 0);
      WG_COMMIT();
      if (j > 0) {
        WG_WAIT(1);
        if (j <= K4_NJ - K4_NS && (tid & 127) < 2) mbar_arrive_cta(bempty + 8 * sprev, tid & 1);
        if (j * K4_G >= 12 && ((j * K4_G) & 7) == 4 && (tid & 127) == 0) mbar_arrive(afree + (j * K4_G - 12));
      }
      sprev = s;
      if (++s == K4_NS) { s = 0; ph ^= 1; }
    }
    WG_WAIT(0);
    fence_regs(a2);
    if (tid == 0) STAMP(3, 4);
#pragma unroll
    for (int c = 0; c < 13; c++) STORE_H(a2, 52, hd + img_off(112 + n1 * 13 + c), c);
    bar_arrive(6, 256 + 32);
    }
    if constexpr (MODE == 1) cluster_arrive();
    if constexpr (MODE != 1) {
    float (&keep)[40] = ((Acc<40>*)acc)->v;
    const uint64_t db3 = mkdesc(sbase + 16384, 128, 1024, 0);
#pragma unroll 1
    for (int i = 0; i < P3_NB; i++) {
      mbar_wait(full3 + 8 * (i & 3), (i >> 2) & 1);
      if (i == 0 && tid == 0) STAMP(4, 2);
      const uint64_t da = da0 + (i & 3) * 2304, db = db3 + (i & 3) * 2304;
      WG_FENCE();
#pragma unroll
      for (int k = 0; k < 4; k++) wgmma_ss_n160(acc, da + k * 256, db + k * 16, (i | k) != 0);
      WG_COMMIT();
      if (i > 0) {
        WG_WAIT(1);
        if (i + 3 < P3_NT && (tid & 127) < 2) mbar_arrive_cta(empty3 + 8 * ((i - 1) & 3), tid & 1);
      }
    }
    const int g = lane >> 2, c = lane & 3, row = m3 * 128 + warp * 16 + g;
    const uint8_t* himg = (const uint8_t*)g_h + (size_t)m3 * 163840 + warp * 256 + lane * 4;
    uint32_t rv[20];
    const float mu0 = __ldcg(&g_hmean[row]), mu1 = __ldcg(&g_hmean[row + 8]);
    float r0 = __ldcg(&g_hpart[c * 2 * S_ + row]) + __ldcg(&g_hpart[(c * 2 + 1) * S_ + row]);
    float r1 = __ldcg(&g_hpart[c * 2 * S_ + row + 8]) + __ldcg(&g_hpart[(c * 2 + 1) * S_ + row + 8]);
#pragma unroll
    for (int j = 0; j < 10; j++) {
      rv[2 * j] = __ldcg((const uint32_t*)(himg + img_off(n3 * 10 + j)));
      rv[2 * j + 1] = __ldcg((const uint32_t*)(himg + img_off(n3 * 10 + j) + 128));
    }
    const uint32_t rx = mapa(sbase + K4_XCH + tid * 16, rank ^ 1), rb = mapa(xchb, rank ^ 1);
    WG_WAIT(0);
    fence_regs(acc);
    if (P3_NB + 3 < P3_NT && (tid & 127) < 2) mbar_arrive_cta(empty3 + 8 * ((P3_NB - 1) & 3), tid & 1);
    if (tid == 0) STAMP(4, 1);
#pragma unroll
    for (int i = P3_NB; i < P3_NT; i++) {
      mbar_wait(full3 + 8 * (i & 3), (i >> 2) & 1);
      const uint64_t da = da0 + (i & 3) * 2304, db = db3 + (i & 3) * 2304;
      WG_FENCE();
#pragma unroll
      for (int k = 0; k < 4; k++) wgmma_ss_n80(keep, da + k * 256, db + k * 16, 1);
      WG_COMMIT();
      if (i > P3_NB && i + 3 < P3_NT) {
        WG_WAIT(1);
        if ((tid & 127) < 2) mbar_arrive_cta(empty3 + 8 * ((i - 1) & 3), tid & 1);
      }
#pragma unroll
      for (int j = (i - P3_NB) * 3; j < (i - P3_NB) * 3 + 3; j++)
        if (j < 5) SEND8(rx + j * 4096, acc, 40 + 8 * j, rb);
    }
    cluster_arrive();
    r0 += __shfl_xor_sync(~0u, r0, 1); r1 += __shfl_xor_sync(~0u, r1, 1);
    r0 += __shfl_xor_sync(~0u, r0, 2); r1 += __shfl_xor_sync(~0u, r1, 2);
    r0 = rcp(r0 * (1.f / D_) + 1e-5f); r1 = rcp(r1 * (1.f / D_) + 1e-5f);
    asm volatile("" : "+f"(r0), "+f"(r1)::"memory");
    WG_WAIT(0);
    fence_regs(keep);
    if (tid == 0) STAMP(4, 3);
    mbar_wait(xchb, 0);
    if (tid == 0) STAMP(4, 5);
    uint8_t* sp = sm + K4_STG + (warp * 16 + g) * 160 + c * 4;
#pragma unroll
    for (int j = 0; j < 10; j++) {
      const uint2 p = *(const uint2*)(sm + K4_XCH + tid * 16 + (j >> 1) * 4096 + (j & 1) * 8);
      *(uint32_t*)(sp + j * 16) = pack_bf16(fmaf(keep[4 * j] + bf_lo(p.x), r0, bf_lo(rv[2 * j]) + mu0), fmaf(keep[4 * j + 1] + bf_hi(p.x), r0, bf_hi(rv[2 * j]) + mu0));
      *(uint32_t*)(sp + 1280 + j * 16) = pack_bf16(fmaf(keep[4 * j + 2] + bf_lo(p.y), r1, bf_lo(rv[2 * j + 1]) + mu1), fmaf(keep[4 * j + 3] + bf_hi(p.y), r1, bf_hi(rv[2 * j + 1]) + mu1));
    }
    fence_async();
    bar_sync(1 + wg, 128);
    if ((tid & 127) == 0) {
      tma2d_st(&tmo, n3 * 80, m3 * 128 + wg * 64, sbase + K4_STG + wg * 10240);
      bulk_commit_wait();
    }
    __syncwarp();
    if (tid == 0) STAMP(4, 4);
    }
    asm volatile("barrier.cluster.wait.aligned; // consumers" ::: "memory");
  }
}

typedef CUresult (*EncodeFn)(CUtensorMap*, CUtensorMapDataType, cuuint32_t, void*, const cuuint64_t*, const cuuint64_t*,
                             const cuuint32_t*, const cuuint32_t*, CUtensorMapInterleave, CUtensorMapSwizzle,
                             CUtensorMapL2promotion, CUtensorMapFloatOOBfill);

static CUtensorMap make_map(EncodeFn enc, const void* p, uint64_t inner, uint64_t outer, uint32_t box_inner,
                            uint32_t box_outer, CUtensorMapSwizzle swz) {
  CUtensorMap m;
  cuuint64_t gd[2] = {inner, outer};
  cuuint64_t gs[1] = {inner * 2};
  cuuint32_t bd[2] = {box_inner, box_outer};
  cuuint32_t es[2] = {1, 1};
  enc(&m, CU_TENSOR_MAP_DATA_TYPE_BFLOAT16, 2, (void*)p, gd, gs, bd, es, CU_TENSOR_MAP_INTERLEAVE_NONE, swz,
      CU_TENSOR_MAP_L2_PROMOTION_L2_256B, CU_TENSOR_MAP_FLOAT_OOB_FILL_NONE);
  return m;
}

static CUtensorMap make_map_img(EncodeFn enc, const void* p, uint64_t k, uint64_t n, uint32_t rows, uint32_t chunks,
                                uint32_t groups) {
  CUtensorMap m;
  cuuint64_t gd[4] = {8, rows, n / 8, k / rows};
  cuuint64_t gs[3] = {n * 2, 16, n * 2 * rows};
  cuuint32_t bd[4] = {8, rows, chunks, groups};
  cuuint32_t es[4] = {1, 1, 1, 1};
  enc(&m, CU_TENSOR_MAP_DATA_TYPE_BFLOAT16, 4, (void*)p, gd, gs, bd, es, CU_TENSOR_MAP_INTERLEAVE_NONE,
      CU_TENSOR_MAP_SWIZZLE_NONE, CU_TENSOR_MAP_L2_PROMOTION_L2_128B, CU_TENSOR_MAP_FLOAT_OOB_FILL_NONE);
  return m;
}

template <typename... KArgs, typename... Args>
static void launch(void (*k)(KArgs...), int grid, int threads, int smem, bool pdl, Args... args) {
  cudaLaunchConfig_t cfg = {};
  cfg.gridDim = dim3(grid);
  cfg.blockDim = dim3(threads);
  cfg.dynamicSmemBytes = smem;
  cfg.stream = cudaStreamPerThread;
  cudaLaunchAttribute at[1];
  at[0].id = cudaLaunchAttributeProgrammaticStreamSerialization;
  at[0].val.programmaticStreamSerializationAllowed = 1;
  cfg.attrs = at;
  cfg.numAttrs = pdl ? 1 : 0;
  cudaLaunchKernelEx(&cfg, k, KArgs(args)...);
}

extern "C" void kernel_launch(void* const* d_in, const int* in_sizes, int n_in, void* d_out, int out_size) {
  const bf16* x = (const bf16*)d_in[0];
  const bf16* wqkv = (const bf16*)d_in[1];
  const bf16* wo = (const bf16*)d_in[2];
  const bf16* wg = (const bf16*)d_in[4];
  const bf16* wu = (const bf16*)d_in[5];
  const bf16* wd = (const bf16*)d_in[6];

  static EncodeFn enc = nullptr;
  static bool fused = true;
  if (!enc) {
    void* fn = nullptr;
    cudaDriverEntryPointQueryResult qr;
    cudaGetDriverEntryPoint("cuTensorMapEncodeTiled", &fn, cudaEnableDefault, &qr);
    enc = (EncodeFn)fn;
    cudaFuncSetAttribute(k1_qkv, cudaFuncAttributeMaxDynamicSharedMemorySize, K1_SMEM);
    cudaFuncSetAttribute(k2_attn, cudaFuncAttributeMaxDynamicSharedMemorySize, K2_SMEM);
    cudaFuncSetAttribute(k3_proj, cudaFuncAttributeMaxDynamicSharedMemorySize, K3_SMEM);
    cudaFuncSetAttribute(k45_ffn<0>, cudaFuncAttributeMaxDynamicSharedMemorySize, K4_SMEM);
    cudaFuncSetAttribute(k45_ffn<1>, cudaFuncAttributeMaxDynamicSharedMemorySize, K4_SMEM);
    cudaFuncSetAttribute(k45_ffn<2>, cudaFuncAttributeMaxDynamicSharedMemorySize, K4_SMEM);
    cudaLaunchConfig_t cfg = {};
    cfg.gridDim = dim3(128); cfg.blockDim = dim3(384); cfg.dynamicSmemBytes = K4_SMEM;
    int clusters = 0;
    cudaOccupancyMaxActiveClusters(&clusters, k45_ffn<0>, &cfg);
    fused = clusters >= 64;
  }
  const CUtensorMap tmx = make_map(enc, x, D_, S_, 64, 96, CU_TENSOR_MAP_SWIZZLE_128B);
  const CUtensorMap tmw = make_map(enc, wqkv, 3 * D_, D_, 32, 64, CU_TENSOR_MAP_SWIZZLE_64B);
  const CUtensorMap tmxr = make_map(enc, x, D_, S_, 80, 64, CU_TENSOR_MAP_SWIZZLE_NONE);
  Maps5 maps;
  maps.m[0] = make_map_img(enc, wg, D_, F_, 16, 14, 2); maps.m[1] = make_map_img(enc, wu, D_, F_, 16, 14, 2);
  maps.m[2] = make_map_img(enc, wg, D_, F_, 16, 13, 2); maps.m[3] = make_map_img(enc, wu, D_, F_, 16, 13, 2);
  maps.m[4] = make_map_img(enc, wd, F_, D_, 64, 10, 1);
  const CUtensorMap tmout = make_map(enc, d_out, D_, S_, 80, 64, CU_TENSOR_MAP_SWIZZLE_NONE);

  launch(k1_qkv, 132, 512, K1_SMEM, false, tmx, tmw, x, wqkv);
  launch(k2_attn, 128, 512, K2_SMEM, true, maps, wo, 0x007f007fu);
  launch(k3_proj, 128, 288, K3_SMEM, true, tmxr);
  if (fused) {
    launch(k45_ffn<0>, 128, 384, K4_SMEM, true, tmout);
  } else {
    launch(k45_ffn<1>, 128, 384, K4_SMEM, true, tmout);
    launch(k45_ffn<2>, 128, 384, K4_SMEM, false, tmout);
  }
}
```

```cpp
#include <cuda_runtime.h>
#include <cuda_bf16.h>
#include <cuda.h>
#include <stdint.h>

typedef __nv_bfloat16 bf16;

constexpr int S_ = 2048, D_ = 640, F_ = 1728;
constexpr int HEAD_IMG = 98304;
constexpr uint32_t POLY_MASK = 0xFAAB;
constexpr float QSCALE = 0.22360679774997896f * 1.4426950408889634f;

__device__ __align__(1024) uint4 g_qkv[96 * HEAD_IMG / 16];
__device__ __align__(1024) uint4 g_o[S_ * D_ / 8];
__device__ __align__(1024) uint4 g_h[S_ * D_ / 8];
__device__ __align__(1024) uint4 g_hh[S_ * F_ / 8];
__device__ __align__(1024) uint4 g_wo[D_ * D_ / 8];
__device__ __align__(1024) uint4 g_wgu[2 * D_ * F_ / 8];
__device__ __align__(1024) uint4 g_wd[F_ * D_ / 8];
__device__ uint4 g_rowstat[S_];
__device__ uint4 g_cpart[10 * 12 * 80];
__device__ float g_nrm[96 * 128];
__device__ uint4 g_wm[D_];
__device__ float g_hmean[S_];
__device__ float g_hpart[8 * S_];
__device__ uint4 g_flag[2 * 16 * 2];
__device__ unsigned g_wflag[128];
__device__ unsigned g_epoch;

#define STAMP(k, i)
__device__ __forceinline__ uint32_t smem_u32(const void* p) { return (uint32_t)__cvta_generic_to_shared(p); }
__device__ __forceinline__ void mbar_init(uint32_t a, uint32_t c) {
  asm volatile("mbarrier.init.shared::cta.b64 [%0], %1;" ::"r"(a), "r"(c) : "memory");
}
__device__ __forceinline__ void mbar_expect(uint32_t a, uint32_t bytes) {
  asm volatile("mbarrier.arrive.expect_tx.shared::cta.b64 _, [%0], %1;" ::"r"(a), "r"(bytes) : "memory");
}
__device__ __forceinline__ void mbar_arrive(uint32_t a) {
  asm volatile("mbarrier.arrive.shared::cta.b64 _, [%0];" ::"r"(a) : "memory");
}
__device__ __forceinline__ void mbar_arrive_cta(uint32_t a, uint32_t cta) {
  asm volatile("{\n.reg .b32 r;\nmapa.shared::cluster.u32 r, %0, %1;\n"
               "mbarrier.arrive.shared::cluster.b64 _, [r];\n}" ::"r"(a), "r"(cta) : "memory");
}
__device__ __forceinline__ bool mbar_try(uint32_t a, uint32_t ph) {
  uint32_t ok;
  asm volatile("{\n.reg .pred p;\nmbarrier.try_wait.parity.shared::cta.b64 p, [%1], %2;\nselp.u32 %0, 1, 0, p;\n}"
               : "=r"(ok) : "r"(a), "r"(ph) : "memory");
  return ok;
}
__device__ __noinline__ void wait_timeout() { __trap(); }
__device__ __forceinline__ void mbar_wait(uint32_t a, uint32_t ph) {
  if (mbar_try(a, ph)) return;
  uint32_t it = 0;
  while (!mbar_try(a, ph)) if (++it > (1u << 22)) wait_timeout();
}
__device__ __forceinline__ void tma2d(uint32_t dst, const CUtensorMap* m, int c0, int c1, uint32_t bar) {
  asm volatile("cp.async.bulk.tensor.2d.shared::cluster.global.mbarrier::complete_tx::bytes [%0], [%1, {%3, %4}], [%2];"
               ::"r"(dst), "l"(m), "r"(bar), "r"(c0), "r"(c1) : "memory");
}
__device__ __forceinline__ void tma2d_mc(uint32_t dst, const CUtensorMap* m, int c0, int c1, uint32_t bar) {
  asm volatile("cp.async.bulk.tensor.2d.shared::cluster.global.mbarrier::complete_tx::bytes.multicast::cluster "
               "[%0], [%1, {%3, %4}], [%2], %5;"
               ::"r"(dst), "l"(m), "r"(bar), "r"(c0), "r"(c1), "h"((uint16_t)3) : "memory");
}
__device__ __forceinline__ void bulk_ld(uint32_t dst, const void* src, uint32_t bytes, uint32_t bar) {
  asm volatile("cp.async.bulk.shared::cluster.global.mbarrier::complete_tx::bytes [%0], [%1], %2, [%3];"
               ::"r"(dst), "l"(src), "r"(bytes), "r"(bar) : "memory");
}
__device__ __forceinline__ void bulk_ld_mc(uint32_t dst, const void* src, uint32_t bytes, uint32_t bar) {
  asm volatile("cp.async.bulk.shared::cluster.global.mbarrier::complete_tx::bytes.multicast::cluster "
               "[%0], [%1], %2, [%3], %4;"
               ::"r"(dst), "l"(src), "r"(bytes), "r"(bar), "h"((uint16_t)3) : "memory");
}
__device__ __forceinline__ void cluster_arrive() { asm volatile("barrier.cluster.arrive.relaxed.aligned;" ::: "memory"); }
__device__ __forceinline__ void cluster_wait() { asm volatile("barrier.cluster.wait.aligned;" ::: "memory"); }
__device__ __forceinline__ void bulk_st(void* dst, uint32_t src, uint32_t bytes) {
  asm volatile("cp.async.bulk.global.shared::cta.bulk_group [%0], [%1], %2;" ::"l"(dst), "r"(src), "r"(bytes) : "memory");
}
__device__ __forceinline__ void tma2d_st(const CUtensorMap* m, int c0, int c1, uint32_t src) {
  asm volatile("cp.async.bulk.tensor.2d.global.shared::cta.bulk_group [%0, {%2, %3}], [%1];"
               ::"l"(m), "r"(src), "r"(c0), "r"(c1) : "memory");
}
__device__ __forceinline__ void bulk_commit_wait() {
  asm volatile("cp.async.bulk.commit_group;\ncp.async.bulk.wait_group.read 0;" ::: "memory");
}
__device__ __forceinline__ uint32_t mapa(uint32_t a, uint32_t cta) {
  uint32_t r;
  asm("mapa.shared::cluster.u32 %0, %1, %2;" : "=r"(r) : "r"(a), "r"(cta));
  return r;
}
__device__ __forceinline__ void st_async4(uint32_t dst, float a, float b, float c, float d, uint32_t bar) {
  asm volatile("st.async.shared::cluster.mbarrier::complete_tx::bytes.v4.f32 [%0], {%1, %2, %3, %4}, [%5];"
               ::"r"(dst), "f"(a), "f"(b), "f"(c), "f"(d), "r"(bar) : "memory");
}
__device__ __forceinline__ void st_async4u(uint32_t dst, uint32_t a, uint32_t b, uint32_t c, uint32_t d, uint32_t bar) {
  asm volatile("st.async.shared::cluster.mbarrier::complete_tx::bytes.v4.b32 [%0], {%1, %2, %3, %4}, [%5];"
               ::"r"(dst), "r"(a), "r"(b), "r"(c), "r"(d), "r"(bar) : "memory");
}
#define SEND8(dst, a, o, bar) st_async4u(dst, pack_bf16(a[o], a[(o) + 1]), pack_bf16(a[(o) + 2], a[(o) + 3]), \
                                         pack_bf16(a[(o) + 4], a[(o) + 5]), pack_bf16(a[(o) + 6], a[(o) + 7]), bar)
__device__ __forceinline__ void fence_async() { asm volatile("fence.proxy.async.shared::cta;" ::: "memory"); }
__device__ __forceinline__ void prefetch_map(const CUtensorMap* m) {
  asm volatile("prefetch.tensormap [%0];" ::"l"(m) : "memory");
}
__device__ __forceinline__ bool elect_one() {
  uint32_t p;
  asm volatile("{\n.reg .pred q;\nelect.sync _|q, 0xffffffff;\nselp.u32 %0, 1, 0, q;\n}" : "=r"(p));
  return p;
}
__device__ __forceinline__ void pdl_wait() { asm volatile("griddepcontrol.wait;" ::: "memory"); }
__device__ __forceinline__ void pdl_trigger() { asm volatile("griddepcontrol.launch_dependents;" ::: "memory"); }
__device__ __forceinline__ void bar_sync(int id, int n) { asm volatile("bar.sync %0, %1;" ::"r"(id), "r"(n) : "memory"); }
__device__ __forceinline__ void bar_arrive(int id, int n) { asm volatile("bar.arrive %0, %1;" ::"r"(id), "r"(n) : "memory"); }
#define WG_FENCE() asm volatile("wgmma.fence.sync.aligned;" ::: "memory")
#define WG_COMMIT() asm volatile("wgmma.commit_group.sync.aligned;" ::: "memory")
#define WG_WAIT(n) asm volatile("wgmma.wait_group.sync.aligned %0;" ::"n"(n) : "memory")
__device__ __forceinline__ uint64_t mkdesc(uint32_t addr, uint32_t lbo, uint32_t sbo, uint32_t sw) {
  return (uint64_t)((addr & 0x3FFFF) >> 4) | ((uint64_t)(lbo >> 4) << 16) | ((uint64_t)(sbo >> 4) << 32) |
         ((uint64_t)sw << 62);
}
template <int N> __device__ __forceinline__ void fence_regs(float (&r)[N]) {
#pragma unroll
  for (int i = 0; i < N; i++) asm volatile("" : "+f"(r[i])::"memory");
}
__device__ __forceinline__ uint32_t pack_bf16(float lo, float hi) {
  uint32_t r;
  asm("cvt.rn.bf16x2.f32 %0, %1, %2;" : "=r"(r) : "f"(hi), "f"(lo));
  return r;
}
__device__ __forceinline__ float bf_lo(uint32_t v) { return __uint_as_float(v << 16); }
__device__ __forceinline__ float bf_hi(uint32_t v) { return __uint_as_float(v & 0xffff0000u); }
__device__ __forceinline__ float ex2(float x) {
  float y;
  asm("ex2.approx.ftz.f32 %0, %1;" : "=f"(y) : "f"(x));
  return y;
}
__device__ __forceinline__ uint4 ldg_nc(const void* p) {
  uint4 v;
  asm volatile("ld.global.nc.L1::no_allocate.v4.u32 {%0, %1, %2, %3}, [%4];"
               : "=r"(v.x), "=r"(v.y), "=r"(v.z), "=r"(v.w) : "l"(p));
  return v;
}

__device__ __forceinline__ uint4 ld_relaxed(const uint4* p) {
  uint64_t a, b;
  asm volatile("ld.relaxed.gpu.global.v2.u64 {%0, %1}, [%2];" : "=l"(a), "=l"(b) : "l"(p) : "memory");
  return make_uint4((uint32_t)a, (uint32_t)(a >> 32), (uint32_t)b, (uint32_t)(b >> 32));
}
__device__ __forceinline__ void st_relaxed(uint4* p, float x, float y, uint32_t tag) {
  const uint64_t a = ((uint64_t)tag << 32) | __float_as_uint(x), b = ((uint64_t)tag << 32) | __float_as_uint(y);
  asm volatile("st.relaxed.gpu.global.v2.u64 [%0], {%1, %2};" ::"l"(p), "l"(a), "l"(b) : "memory");
}
__device__ __forceinline__ void tma4d(uint32_t dst, const CUtensorMap* m, int c2, int c3, uint32_t bar) {
  asm volatile("cp.async.bulk.tensor.4d.shared::cluster.global.mbarrier::complete_tx::bytes [%0], [%1, {%3, %3, %4, %5}], [%2];"
               ::"r"(dst), "l"(m), "r"(bar), "r"(0), "r"(c2), "r"(c3) : "memory");
}
#define ACC8(a, v) do { a[0] += bf_lo(v.x); a[1] += bf_hi(v.x); a[2] += bf_lo(v.y); a[3] += bf_hi(v.y); \
                        a[4] += bf_lo(v.z); a[5] += bf_hi(v.z); a[6] += bf_lo(v.w); a[7] += bf_hi(v.w); } while (0)

__device__ __forceinline__ void wgmma_ss_n224(float (&d)[112], uint64_t da, uint64_t db, int sd) {
  asm volatile("{\n.reg .pred p;\nsetp.ne.b32 p, %114, 0;\n"
      "wgmma.mma_async.sync.aligned.m64n224k16.f32.bf16.bf16 {"
      "%0, %1, %2, %3, %4, %5, %6, %7, %8, %9, %10, %11, %12, %13, %14, %15, "
      "%16, %17, %18, %19, %20, %21, %22, %23, %24, %25, %26, %27, %28, %29, %30, %31, "
      "%32, %33, %34, %35, %36, %37, %38, %39, %40, %41, %42, %43, %44, %45, %46, %47, "
      "%48, %49, %50, %51, %52, %53, %54, %55, %56, %57, %58, %59, %60, %61, %62, %63, "
      "%64, %65, %66, %67, %68, %69, %70, %71, %72, %73, %74, %75, %76, %77, %78, %79, "
      "%80, %81, %82, %83, %84, %85, %86, %87, %88, %89, %90, %91, %92, %93, %94, %95, "
      "%96, %97, %98, %99, %100, %101, %102, %103, %104, %105, %106, %107, %108, %109, %110, %111"
      "}, %112, %113, p, 1, 1, 0, 1;\n}\n"
    : "+f"(d[0]), "+f"(d[1]), "+f"(d[2]), "+f"(d[3]), "+f"(d[4]), "+f"(d[5]), "+f"(d[6]), "+f"(d[7]),
      "+f"(d[8]), "+f"(d[9]), "+f"(d[10]), "+f"(d[11]), "+f"(d[12]), "+f"(d[13]), "+f"(d[14]), "+f"(d[15]),
      "+f"(d[16]), "+f"(d[17]), "+f"(d[18]), "+f"(d[19]), "+f"(d[20]), "+f"(d[21]), "+f"(d[22]), "+f"(d[23]),
      "+f"(d[24]), "+f"(d[25]), "+f"(d[26]), "+f"(d[27]), "+f"(d[28]), "+f"(d[29]), "+f"(d[30]), "+f"(d[31]),
      "+f"(d[32]), "+f"(d[33]), "+f"(d[34]), "+f"(d[35]), "+f"(d[36]), "+f"(d[37]), "+f"(d[38]), "+f"(d[39]),
      "+f"(d[40]), "+f"(d[41]), "+f"(d[42]), "+f"(d[43]), "+f"(d[44]), "+f"(d[45]), "+f"(d[46]), "+f"(d[47]),
      "+f"(d[48]), "+f"(d[49]), "+f"(d[50]), "+f"(d[51]), "+f"(d[52]), "+f"(d[53]), "+f"(d[54]), "+f"(d[55]),
      "+f"(d[56]), "+f"(d[57]), "+f"(d[58]), "+f"(d[59]), "+f"(d[60]), "+f"(d[61]), "+f"(d[62]), "+f"(d[63]),
      "+f"(d[64]), "+f"(d[65]), "+f"(d[66]), "+f"(d[67]), "+f"(d[68]), "+f"(d[69]), "+f"(d[70]), "+f"(d[71]),
      "+f"(d[72]), "+f"(d[73]), "+f"(d[74]), "+f"(d[75]), "+f"(d[76]), "+f"(d[77]), "+f"(d[78]), "+f"(d[79]),
      "+f"(d[80]), "+f"(d[81]), "+f"(d[82]), "+f"(d[83]), "+f"(d[84]), "+f"(d[85]), "+f"(d[86]), "+f"(d[87]),
      "+f"(d[88]), "+f"(d[89]), "+f"(d[90]), "+f"(d[91]), "+f"(d[92]), "+f"(d[93]), "+f"(d[94]), "+f"(d[95]),
      "+f"(d[96]), "+f"(d[97]), "+f"(d[98]), "+f"(d[99]), "+f"(d[100]), "+f"(d[101]), "+f"(d[102]), "+f"(d[103]),
      "+f"(d[104]), "+f"(d[105]), "+f"(d[106]), "+f"(d[107]), "+f"(d[108]), "+f"(d[109]), "+f"(d[110]), "+f"(d[111])
    : "l"(da), "l"(db), "r"(sd));
}
__device__ __forceinline__ void wgmma_ss_n208(float (&d)[104], uint64_t da, uint64_t db, int sd) {
  asm volatile("{\n.reg .pred p;\nsetp.ne.b32 p, %106, 0;\n"
      "wgmma.mma_async.sync.aligned.m64n208k16.f32.bf16.bf16 {"
      "%0, %1, %2, %3, %4, %5, %6, %7, %8, %9, %10, %11, %12, %13, %14, %15, "
      "%16, %17, %18, %19, %20, %21, %22, %23, %24, %25, %26, %27, %28, %29, %30, %31, "
      "%32, %33, %34, %35, %36, %37, %38, %39, %40, %41, %42, %43, %44, %45, %46, %47, "
      "%48, %49, %50, %51, %52, %53, %54, %55, %56, %57, %58, %59, %60, %61, %62, %63, "
      "%64, %65, %66, %67, %68, %69, %70, %71, %72, %73, %74, %75, %76, %77, %78, %79, "
      "%80, %81, %82, %83, %84, %85, %86, %87, %88, %89, %90, %91, %92, %93, %94, %95, "
      "%96, %97, %98, %99, %100, %101, %102, %103"
      "}, %104, %105, p, 1, 1, 0, 1;\n}\n"
    : "+f"(d[0]), "+f"(d[1]), "+f"(d[2]), "+f"(d[3]), "+f"(d[4]), "+f"(d[5]), "+f"(d[6]), "+f"(d[7]),
      "+f"(d[8]), "+f"(d[9]), "+f"(d[10]), "+f"(d[11]), "+f"(d[12]), "+f"(d[13]), "+f"(d[14]), "+f"(d[15]),
      "+f"(d[16]), "+f"(d[17]), "+f"(d[18]), "+f"(d[19]), "+f"(d[20]), "+f"(d[21]), "+f"(d[22]), "+f"(d[23]),
      "+f"(d[24]), "+f"(d[25]), "+f"(d[26]), "+f"(d[27]), "+f"(d[28]), "+f"(d[29]), "+f"(d[30]), "+f"(d[31]),
      "+f"(d[32]), "+f"(d[33]), "+f"(d[34]), "+f"(d[35]), "+f"(d[36]), "+f"(d[37]), "+f"(d[38]), "+f"(d[39]),
      "+f"(d[40]), "+f"(d[41]), "+f"(d[42]), "+f"(d[43]), "+f"(d[44]), "+f"(d[45]), "+f"(d[46]), "+f"(d[47]),
      "+f"(d[48]), "+f"(d[49]), "+f"(d[50]), "+f"(d[51]), "+f"(d[52]), "+f"(d[53]), "+f"(d[54]), "+f"(d[55]),
      "+f"(d[56]), "+f"(d[57]), "+f"(d[58]), "+f"(d[59]), "+f"(d[60]), "+f"(d[61]), "+f"(d[62]), "+f"(d[63]),
      "+f"(d[64]), "+f"(d[65]), "+f"(d[66]), "+f"(d[67]), "+f"(d[68]), "+f"(d[69]), "+f"(d[70]), "+f"(d[71]),
      "+f"(d[72]), "+f"(d[73]), "+f"(d[74]), "+f"(d[75]), "+f"(d[76]), "+f"(d[77]), "+f"(d[78]), "+f"(d[79]),
      "+f"(d[80]), "+f"(d[81]), "+f"(d[82]), "+f"(d[83]), "+f"(d[84]), "+f"(d[85]), "+f"(d[86]), "+f"(d[87]),
      "+f"(d[88]), "+f"(d[89]), "+f"(d[90]), "+f"(d[91]), "+f"(d[92]), "+f"(d[93]), "+f"(d[94]), "+f"(d[95]),
      "+f"(d[96]), "+f"(d[97]), "+f"(d[98]), "+f"(d[99]), "+f"(d[100]), "+f"(d[101]), "+f"(d[102]), "+f"(d[103])
    : "l"(da), "l"(db), "r"(sd));
}
__device__ __forceinline__ void wgmma_ss_n168(float (&d)[84], uint64_t da, uint64_t db, int sd) {
  asm volatile("{\n.reg .pred p;\nsetp.ne.b32 p, %86, 0;\n"
      "wgmma.mma_async.sync.aligned.m64n168k16.f32.bf16.bf16 {"
      "%0, %1, %2, %3, %4, %5, %6, %7, %8, %9, %10, %11, %12, %13, %14, %15, "
      "%16, %17, %18, %19, %20, %21, %22, %23, %24, %25, %26, %27, %28, %29, %30, %31, "
      "%32, %33, %34, %35, %36, %37, %38, %39, %40, %41, %42, %43, %44, %45, %46, %47, "
      "%48, %49, %50, %51, %52, %53, %54, %55, %56, %57, %58, %59, %60, %61, %62, %63, "
      "%64, %65, %66, %67, %68, %69, %70, %71, %72, %73, %74, %75, %76, %77, %78, %79, "
      "%80, %81, %82, %83"
      "}, %84, %85, p, 1, 1, 0, 1;\n}\n"
    : "+f"(d[0]), "+f"(d[1]), "+f"(d[2]), "+f"(d[3]), "+f"(d[4]), "+f"(d[5]), "+f"(d[6]), "+f"(d[7]),
      "+f"(d[8]), "+f"(d[9]), "+f"(d[10]), "+f"(d[11]), "+f"(d[12]), "+f"(d[13]), "+f"(d[14]), "+f"(d[15]),
      "+f"(d[16]), "+f"(d[17]), "+f"(d[18]), "+f"(d[19]), "+f"(d[20]), "+f"(d[21]), "+f"(d[22]), "+f"(d[23]),
      "+f"(d[24]), "+f"(d[25]), "+f"(d[26]), "+f"(d[27]), "+f"(d[28]), "+f"(d[29]), "+f"(d[30]), "+f"(d[31]),
      "+f"(d[32]), "+f"(d[33]), "+f"(d[34]), "+f"(d[35]), "+f"(d[36]), "+f"(d[37]), "+f"(d[38]), "+f"(d[39]),
      "+f"(d[40]), "+f"(d[41]), "+f"(d[42]), "+f"(d[43]), "+f"(d[44]), "+f"(d[45]), "+f"(d[46]), "+f"(d[47]),
      "+f"(d[48]), "+f"(d[49]), "+f"(d[50]), "+f"(d[51]), "+f"(d[52]), "+f"(d[53]), "+f"(d[54]), "+f"(d[55]),
      "+f"(d[56]), "+f"(d[57]), "+f"(d[58]), "+f"(d[59]), "+f"(d[60]), "+f"(d[61]), "+f"(d[62]), "+f"(d[63]),
      "+f"(d[64]), "+f"(d[65]), "+f"(d[66]), "+f"(d[67]), "+f"(d[68]), "+f"(d[69]), "+f"(d[70]), "+f"(d[71]),
      "+f"(d[72]), "+f"(d[73]), "+f"(d[74]), "+f"(d[75]), "+f"(d[76]), "+f"(d[77]), "+f"(d[78]), "+f"(d[79]),
      "+f"(d[80]), "+f"(d[81]), "+f"(d[82]), "+f"(d[83])
    : "l"(da), "l"(db), "r"(sd));
}
__device__ __forceinline__ void wgmma_ss_n160(float (&d)[80], uint64_t da, uint64_t db, int sd) {
  asm volatile("{\n.reg .pred p;\nsetp.ne.b32 p, %82, 0;\n"
      "wgmma.mma_async.sync.aligned.m64n160k16.f32.bf16.bf16 {"
      "%0, %1, %2, %3, %4, %5, %6, %7, %8, %9, %10, %11, %12, %13, %14, %15, "
      "%16, %17, %18, %19, %20, %21, %22, %23, %24, %25, %26, %27, %28, %29, %30, %31, "
      "%32, %33, %34, %35, %36, %37, %38, %39, %40, %41, %42, %43, %44, %45, %46, %47, "
      "%48, %49, %50, %51, %52, %53, %54, %55, %56, %57, %58, %59, %60, %61, %62, %63, "
      "%64, %65, %66, %67, %68, %69, %70, %71, %72, %73, %74, %75, %76, %77, %78, %79"
      "}, %80, %81, p, 1, 1, 0, 1;\n}\n"
    : "+f"(d[0]), "+f"(d[1]), "+f"(d[2]), "+f"(d[3]), "+f"(d[4]), "+f"(d[5]), "+f"(d[6]), "+f"(d[7]),
      "+f"(d[8]), "+f"(d[9]), "+f"(d[10]), "+f"(d[11]), "+f"(d[12]), "+f"(d[13]), "+f"(d[14]), "+f"(d[15]),
      "+f"(d[16]), "+f"(d[17]), "+f"(d[18]), "+f"(d[19]), "+f"(d[20]), "+f"(d[21]), "+f"(d[22]), "+f"(d[23]),
      "+f"(d[24]), "+f"(d[25]), "+f"(d[26]), "+f"(d[27]), "+f"(d[28]), "+f"(d[29]), "+f"(d[30]), "+f"(d[31]),
      "+f"(d[32]), "+f"(d[33]), "+f"(d[34]), "+f"(d[35]), "+f"(d[36]), "+f"(d[37]), "+f"(d[38]), "+f"(d[39]),
      "+f"(d[40]), "+f"(d[41]), "+f"(d[42]), "+f"(d[43]), "+f"(d[44]), "+f"(d[45]), "+f"(d[46]), "+f"(d[47]),
      "+f"(d[48]), "+f"(d[49]), "+f"(d[50]), "+f"(d[51]), "+f"(d[52]), "+f"(d[53]), "+f"(d[54]), "+f"(d[55]),
      "+f"(d[56]), "+f"(d[57]), "+f"(d[58]), "+f"(d[59]), "+f"(d[60]), "+f"(d[61]), "+f"(d[62]), "+f"(d[63]),
      "+f"(d[64]), "+f"(d[65]), "+f"(d[66]), "+f"(d[67]), "+f"(d[68]), "+f"(d[69]), "+f"(d[70]), "+f"(d[71]),
      "+f"(d[72]), "+f"(d[73]), "+f"(d[74]), "+f"(d[75]), "+f"(d[76]), "+f"(d[77]), "+f"(d[78]), "+f"(d[79])
    : "l"(da), "l"(db), "r"(sd));
}
__device__ __forceinline__ void wgmma_ss_n88(float (&d)[44], uint64_t da, uint64_t db, int sd) {
  asm volatile("{\n.reg .pred p;\nsetp.ne.b32 p, %46, 0;\n"
      "wgmma.mma_async.sync.aligned.m64n88k16.f32.bf16.bf16 {"
      "%0, %1, %2, %3, %4, %5, %6, %7, %8, %9, %10, %11, %12, %13, %14, %15, "
      "%16, %17, %18, %19, %20, %21, %22, %23, %24, %25, %26, %27, %28, %29, %30, %31, "
      "%32, %33, %34, %35, %36, %37, %38, %39, %40, %41, %42, %43"
      "}, %44, %45, p, 1, 1, 0, 1;\n}\n"
    : "+f"(d[0]), "+f"(d[1]), "+f"(d[2]), "+f"(d[3]), "+f"(d[4]), "+f"(d[5]), "+f"(d[6]), "+f"(d[7]),
      "+f"(d[8]), "+f"(d[9]), "+f"(d[10]), "+f"(d[11]), "+f"(d[12]), "+f"(d[13]), "+f"(d[14]), "+f"(d[15]),
      "+f"(d[16]), "+f"(d[17]), "+f"(d[18]), "+f"(d[19]), "+f"(d[20]), "+f"(d[21]), "+f"(d[22]), "+f"(d[23]),
      "+f"(d[24]), "+f"(d[25]), "+f"(d[26]), "+f"(d[27]), "+f"(d[28]), "+f"(d[29]), "+f"(d[30]), "+f"(d[31]),
      "+f"(d[32]), "+f"(d[33]), "+f"(d[34]), "+f"(d[35]), "+f"(d[36]), "+f"(d[37]), "+f"(d[38]), "+f"(d[39]),
      "+f"(d[40]), "+f"(d[41]), "+f"(d[42]), "+f"(d[43])
    : "l"(da), "l"(db), "r"(sd));
}
__device__ __forceinline__ void wgmma_ss_n80(float (&d)[40], uint64_t da, uint64_t db, int sd) {
  asm volatile("{\n.reg .pred p;\nsetp.ne.b32 p, %42, 0;\n"
      "wgmma.mma_async.sync.aligned.m64n80k16.f32.bf16.bf16 {"
      "%0, %1, %2, %3, %4, %5, %6, %7, %8, %9, %10, %11, %12, %13, %14, %15, "
      "%16, %17, %18, %19, %20, %21, %22, %23, %24, %25, %26, %27, %28, %29, %30, %31, "
      "%32, %33, %34, %35, %36, %37, %38, %39"
      "}, %40, %41, p, 1, 1, 0, 1;\n}\n"
    : "+f"(d[0]), "+f"(d[1]), "+f"(d[2]), "+f"(d[3]), "+f"(d[4]), "+f"(d[5]), "+f"(d[6]), "+f"(d[7]),
      "+f"(d[8]), "+f"(d[9]), "+f"(d[10]), "+f"(d[11]), "+f"(d[12]), "+f"(d[13]), "+f"(d[14]), "+f"(d[15]),
      "+f"(d[16]), "+f"(d[17]), "+f"(d[18]), "+f"(d[19]), "+f"(d[20]), "+f"(d[21]), "+f"(d[22]), "+f"(d[23]),
      "+f"(d[24]), "+f"(d[25]), "+f"(d[26]), "+f"(d[27]), "+f"(d[28]), "+f"(d[29]), "+f"(d[30]), "+f"(d[31]),
      "+f"(d[32]), "+f"(d[33]), "+f"(d[34]), "+f"(d[35]), "+f"(d[36]), "+f"(d[37]), "+f"(d[38]), "+f"(d[39])
    : "l"(da), "l"(db), "r"(sd));
}
__device__ __forceinline__ void wgmma_rs_n128(float (&d)[64], uint32_t a0, uint32_t a1, uint32_t a2, uint32_t a3,
                                  uint64_t db, int sd) {
  asm volatile("{\n.reg .pred p;\nsetp.ne.b32 p, %69, 0;\n"
      "wgmma.mma_async.sync.aligned.m64n128k16.f32.bf16.bf16 {"
      "%0, %1, %2, %3, %4, %5, %6, %7, %8, %9, %10, %11, %12, %13, %14, %15, "
      "%16, %17, %18, %19, %20, %21, %22, %23, %24, %25, %26, %27, %28, %29, %30, %31, "
      "%32, %33, %34, %35, %36, %37, %38, %39, %40, %41, %42, %43, %44, %45, %46, %47, "
      "%48, %49, %50, %51, %52, %53, %54, %55, %56, %57, %58, %59, %60, %61, %62, %63"
      "}, {%64, %65, %66, %67}, %68, p, 1, 1, 0;\n}\n"
    : "+f"(d[0]), "+f"(d[1]), "+f"(d[2]), "+f"(d[3]), "+f"(d[4]), "+f"(d[5]), "+f"(d[6]), "+f"(d[7]),
      "+f"(d[8]), "+f"(d[9]), "+f"(d[10]), "+f"(d[11]), "+f"(d[12]), "+f"(d[13]), "+f"(d[14]), "+f"(d[15]),
      "+f"(d[16]), "+f"(d[17]), "+f"(d[18]), "+f"(d[19]), "+f"(d[20]), "+f"(d[21]), "+f"(d[22]), "+f"(d[23]),
      "+f"(d[24]), "+f"(d[25]), "+f"(d[26]), "+f"(d[27]), "+f"(d[28]), "+f"(d[29]), "+f"(d[30]), "+f"(d[31]),
      "+f"(d[32]), "+f"(d[33]), "+f"(d[34]), "+f"(d[35]), "+f"(d[36]), "+f"(d[37]), "+f"(d[38]), "+f"(d[39]),
      "+f"(d[40]), "+f"(d[41]), "+f"(d[42]), "+f"(d[43]), "+f"(d[44]), "+f"(d[45]), "+f"(d[46]), "+f"(d[47]),
      "+f"(d[48]), "+f"(d[49]), "+f"(d[50]), "+f"(d[51]), "+f"(d[52]), "+f"(d[53]), "+f"(d[54]), "+f"(d[55]),
      "+f"(d[56]), "+f"(d[57]), "+f"(d[58]), "+f"(d[59]), "+f"(d[60]), "+f"(d[61]), "+f"(d[62]), "+f"(d[63])
    : "r"(a0), "r"(a1), "r"(a2), "r"(a3), "l"(db), "r"(sd));
}
__device__ __forceinline__ void wgmma_rs_n24(float (&d)[12], uint32_t a0, uint32_t a1, uint32_t a2, uint32_t a3,
                                  uint64_t db, int sd) {
  asm volatile("{\n.reg .pred p;\nsetp.ne.b32 p, %17, 0;\n"
      "wgmma.mma_async.sync.aligned.m64n24k16.f32.bf16.bf16 {"
      "%0, %1, %2, %3, %4, %5, %6, %7, %8, %9, %10, %11"
      "}, {%12, %13, %14, %15}, %16, p, 1, 1, 1;\n}\n"
    : "+f"(d[0]), "+f"(d[1]), "+f"(d[2]), "+f"(d[3]), "+f"(d[4]), "+f"(d[5]), "+f"(d[6]), "+f"(d[7]),
      "+f"(d[8]), "+f"(d[9]), "+f"(d[10]), "+f"(d[11])
    : "r"(a0), "r"(a1), "r"(a2), "r"(a3), "l"(db), "r"(sd));
}

constexpr int KST = 4;
constexpr int K1_ST = 4, K1_STAGE = 45056;
constexpr int K1_SMEM = K1_ST * K1_STAGE + 640   + 1536   + 2560   + 128;

__device__ __forceinline__ float2 row_stats(uint4 v0, uint4 v1, uint4 v2) {
  const uint32_t wd[12] = {v0.x, v0.y, v0.z, v0.w, v1.x, v1.y, v1.z, v1.w, v2.x, v2.y, v2.z, v2.w};
  float sx = 0.f, sq = 0.f;
#pragma unroll
  for (int e = 0; e < 12; e++) {
    const float lo = bf_lo(wd[e]), hi = bf_hi(wd[e]);
    sx += lo + hi; sq = fmaf(lo, lo, fmaf(hi, hi, sq));
  }
#pragma unroll
  for (int o = 16; o; o >>= 1) { sx += __shfl_xor_sync(~0u, sx, o); sq += __shfl_xor_sync(~0u, sq, o); }
  const float mean = sx * (1.f / D_);
  return make_float2(rsqrtf(fmaxf(sq * (1.f / D_) - mean * mean, 0.f) + 1e-5f), mean);
}

__global__ void __cluster_dims__(2, 1, 1) __launch_bounds__(512, 1)
k1_qkv(const __grid_constant__ CUtensorMap tmx, const __grid_constant__ CUtensorMap tmw,
       const bf16* __restrict__ x, const bf16* __restrict__ w) {
  extern __shared__ __align__(1024) uint8_t sm[];
  float* cs = (float*)(sm + K1_ST * K1_STAGE);
  float2* rowab = (float2*)(sm + K1_ST * K1_STAGE + 640);
  float* red = (float*)(sm + K1_ST * K1_STAGE + 2176);
  const uint32_t sbase = smem_u32(sm);
  const uint32_t fullb = sbase + K1_ST * K1_STAGE + 4736, emptyb = fullb + 8 * K1_ST;
  const int tid = threadIdx.x, lane = tid & 31;
  const int warp = __shfl_sync(~0u, tid >> 5, 0);
  const int rank = blockIdx.x & 1, cl = blockIdx.x >> 1;
  const int m = cl / 6, n = (cl - m * 6) * 2 + rank;
  if (tid == 0) STAMP(0, 0);

  if (warp == 12) {
    if (lane == 0) {
      prefetch_map(&tmx); prefetch_map(&tmw);
      for (int i = 0; i < K1_ST; i++) { mbar_init(fullb + 8 * i, 1); mbar_init(emptyb + 8 * i, 6); }
      asm volatile("fence.mbarrier_init.release.cluster;" ::: "memory");
    }
    __syncwarp();
    cluster_arrive();
    bar_arrive(4, 512);
    if (elect_one()) {
#pragma unroll
      for (int kt = 0; kt < K1_ST; kt++) mbar_expect(fullb + 8 * kt, K1_STAGE);
      tma2d(sbase, &tmx, 0, m * 192, fullb);
      tma2d(sbase + 12288, &tmx, 0, m * 192 + 96, fullb);
#pragma unroll
      for (int j = 0; j < 5; j++) tma2d(sbase + 24576 + j * 4096, &tmw, n * 160 + j * 32, 0, fullb);
    }
    cluster_wait();
#pragma unroll 1
    for (int kt = 1; kt < 10; kt++) {
      const int s = kt % K1_ST;
      const uint32_t sa = sbase + s * K1_STAGE;
      if (kt >= K1_ST) mbar_wait(emptyb + 8 * s, ((kt / K1_ST) - 1) & 1);
      if (elect_one()) {
        if (kt >= K1_ST) mbar_expect(fullb + 8 * s, K1_STAGE);
        tma2d_mc(sa + rank * 12288, &tmx, kt * 64, m * 192 + rank * 96, fullb + 8 * s);
#pragma unroll
        for (int j = 0; j < 5; j++) tma2d(sa + 24576 + j * 4096, &tmw, n * 160 + j * 32, kt * 64, fullb + 8 * s);
      }
      if (kt == K1_ST - 1) pdl_trigger();
    }
    __syncwarp();
    cluster_arrive();
  } else if (warp > 12) {
    cluster_arrive();
    const int t96 = tid - 416;
    const uint32_t tag = __ldcg(&g_epoch) + 1;
    bar_sync(4, 512);
    mbar_wait(fullb, 0);
    if (m < 10) {
      const int ck = t96 % 20, rg = min(t96 / 20, 3);
      uint4 wv[16];
#pragma unroll
      for (int i = 0; i < 16; i++) wv[i] = ldg_nc(w + (size_t)(m * 64 + rg * 16 + i) * 1920 + n * 160 + ck * 8);
      float acc8[8];
#pragma unroll
      for (int i = 0; i < 8; i++) acc8[i] = 0.f;
#pragma unroll
      for (int i = 0; i < 16; i++) ACC8(acc8, wv[i]);
      *(float4*)&red[rg * 160 + ck * 8] = make_float4(acc8[0], acc8[1], acc8[2], acc8[3]);
      *(float4*)&red[rg * 160 + ck * 8 + 4] = make_float4(acc8[4], acc8[5], acc8[6], acc8[7]);
      bar_sync(1, 96);
      if (t96 < 80) {
        const float2 p0 = *(const float2*)&red[t96 * 2], p1 = *(const float2*)&red[160 + t96 * 2];
        const float2 p2 = *(const float2*)&red[320 + t96 * 2], p3 = *(const float2*)&red[480 + t96 * 2];
        st_relaxed(&g_cpart[(m * 12 + n) * 80 + t96], (p0.x + p1.x) + (p2.x + p3.x), (p0.y + p1.y) + (p2.y + p3.y), tag);
      }
    }
    if (tid == 416) STAMP(5, 7);
    bool ok = false;
    for (int it = 0; it < 64 && !ok; it++) {
      uint4 p[10], st[2];
#pragma unroll
      for (int k = 0; k < 10; k++) p[k] = ld_relaxed(&g_cpart[(k * 12 + n) * 80 + min(t96, 79)]);
#pragma unroll
      for (int k = 0; k < 2; k++) st[k] = ld_relaxed(&g_rowstat[min(m * 192 + k * 96 + t96, S_ - 1)]);
      ok = true;
      float s0 = 0.f, s1 = 0.f;
#pragma unroll
      for (int k = 0; k < 10; k++) {
        ok = ok && p[k].y == tag && p[k].w == tag;
        s0 += __uint_as_float(p[k].x); s1 += __uint_as_float(p[k].z);
      }
      if (t96 < 80) *(float2*)&cs[t96 * 2] = make_float2(s0, s1);
#pragma unroll
      for (int k = 0; k < 2; k++) {
        ok = ok && st[k].y == tag && st[k].w == tag;
        rowab[k * 96 + t96] = make_float2(__uint_as_float(st[k].x), -__uint_as_float(st[k].x) * __uint_as_float(st[k].z));
      }
      ok = __all_sync(~0u, ok);
      if (!ok) __nanosleep(300);
    }
    if (!ok) {
      const int c2 = min(t96, 79);
      float s0 = 0.f, s1 = 0.f;
#pragma unroll 1
      for (int k = 0; k < D_; k++) {
        const uint32_t v = *(const uint32_t*)(w + (size_t)k * 1920 + n * 160 + c2 * 2);
        s0 += bf_lo(v); s1 += bf_hi(v);
      }
      if (t96 < 80) *(float2*)&cs[t96 * 2] = make_float2(s0, s1);
#pragma unroll 1
      for (int i = 0; i < 64; i++) {
        const int r = (i >> 5) * 96 + (t96 & ~31) + (i & 31);
        const bf16* xr = x + (size_t)min(m * 192 + r, S_ - 1) * D_ + lane * 8;
        const float2 st = row_stats(ldg_nc(xr), ldg_nc(xr + 256), lane < 16 ? ldg_nc(xr + 512) : make_uint4(0u, 0u, 0u, 0u));
        if (lane == 0) rowab[r] = make_float2(st.x, -st.x * st.y);
      }
    }
    __syncwarp();
    bar_arrive(2, 96 + 384);
    if (tid == 416) STAMP(0, 5);
    if (tid == 416) STAMP(0, 7);
    __syncwarp();
    cluster_wait();
    cluster_arrive();
  } else {
    cluster_arrive();
    float acc[80];
    const uint64_t da0 = mkdesc(sbase + (warp >> 2) * 8192, 16, 1024, 1);
    const uint64_t db0 = mkdesc(sbase + 24576, 4096, 512, 2);
    const uint32_t tag = __ldcg(&g_epoch) + 1;
    const int srow = m * 192 + n * 16 + warp * 2;
    const bool dostat = warp < 8 && srow < S_;
    uint4 xv[2][3];
    bar_sync(4, 512);
    cluster_wait();
#pragma unroll
    for (int kt = 0; kt < 10; kt++) {
      const int s = kt % K1_ST;
      mbar_wait(fullb + 8 * s, (kt / K1_ST) & 1);
      if (kt == 0 && tid == 0) STAMP(0, 1);
      if (kt == 2 && tid == 0) STAMP(5, 0);
      if (kt == 4 && tid == 0) STAMP(5, 1);
      if (kt == 7 && tid == 0) STAMP(5, 2);
      const uint64_t da = da0 + s * (K1_STAGE >> 4), db = db0 + s * (K1_STAGE >> 4);
      WG_FENCE();
#pragma unroll
      for (int k = 0; k < 4; k++) wgmma_ss_n160(acc, da + k * 2, db + k * 64, (kt | k) != 0);
      WG_COMMIT();
      if (kt > 0) {
        WG_WAIT(1);
        if (kt - 1 + K1_ST < 10 && (tid & 127) < 2) mbar_arrive_cta(emptyb + 8 * ((kt - 1) % K1_ST), tid & 1);
      }
      if (kt == 0) {
#pragma unroll
        for (int i = 0; i < 2; i++) {
          const bf16* xr = x + (size_t)min(srow + i, S_ - 1) * D_ + lane * 8;
          xv[i][0] = xv[i][1] = xv[i][2] = make_uint4(0u, 0u, 0u, 0u);
          if (dostat) { xv[i][0] = ldg_nc(xr); xv[i][1] = ldg_nc(xr + 256); }
          if (dostat && lane < 16) xv[i][2] = ldg_nc(xr + 512);
        }
      }
      if ((kt == KST || kt == KST + 1) && dostat) {
        const float2 st = row_stats(xv[kt - KST][0], xv[kt - KST][1], xv[kt - KST][2]);
        if (lane == 0) st_relaxed(&g_rowstat[srow + kt - KST], st.x, st.y, tag);
      }
      __syncwarp();
    }
    cluster_arrive();
    WG_WAIT(0);
    fence_regs(acc);
    if (tid == 0) STAMP(0, 2);
    bar_sync(2, 96 + 384);
    if (tid == 0) STAMP(0, 3);
    const int row0 = m * 192 + warp * 16;
    if (row0 < S_) {
      const int g = lane >> 2, c = lane & 3, sec = n >> 2, grp = (row0 & 127) >> 3;
      const bool lo = c < 2;
      const float2 ab0 = rowab[warp * 16 + g], ab1 = rowab[warp * 16 + g + 8];
      const bool p0 = sec == 1 && ((POLY_MASK >> grp) & 1), p1 = sec == 1 && ((POLY_MASK >> (grp + 1)) & 1);
      const uint32_t padqv = sec == 0 ? (c == 2 ? 0x3F803F80u : 0x00003F80u) : (sec == 2 && c == 2 ? 0x00003F80u : 0u);
      const uint32_t padk = c == 2 ? 0x4A7A4B00u : 0x00004653u;
      const uint32_t pad0 = p0 ? padk : padqv, pad1 = p1 ? padk : padqv;
      const float f0 = sec == 0 ? QSCALE : (p0 ? 32768.f : 1.f), f1 = sec == 0 ? QSCALE : (p1 ? 32768.f : 1.f);
      const float a0 = ab0.x * f0, b0 = ab0.y * f0, a1 = ab1.x * f1, b1 = ab1.y * f1;
      const float r0 = p0 ? 9.313225746154785e-10f : 1.f, r1 = p1 ? 9.313225746154785e-10f : 1.f;
      const int cst = sec == 1 ? 2048 : 128, gst = sec == 1 ? 128 : 384;
      uint8_t* pe = (uint8_t*)g_qkv + (size_t)(n * 8) * HEAD_IMG + (row0 >> 7) * 6144 + grp * gst + lane * 4;
      uint8_t* pe1 = pe + cst;
      uint8_t* pe2 = pe1 + cst;
      uint8_t* pf = pe + gst;
      uint8_t* pf1 = pf + cst;
      uint8_t* pf2 = pf1 + cst;
      uint32_t u[20], v[20];
#pragma unroll
      for (int hp = 0; hp < 4; hp++) {
#pragma unroll
        for (int j = hp * 5; j < hp * 5 + 5; j++) {
          const float2 t = *(const float2*)&cs[j * 8 + c * 2];
          u[j] = pack_bf16(fmaf(acc[4 * j], a0, b0 * t.x), fmaf(acc[4 * j + 1], a0, b0 * t.y));
          v[j] = pack_bf16(fmaf(acc[4 * j + 2], a1, b1 * t.x), fmaf(acc[4 * j + 3], a1, b1 * t.y));
        }
        constexpr int HE = HEAD_IMG;
        const int oe = hp * 2 * HE, oo = oe + HE, j = hp * 5;
        *(uint32_t*)(pe + oe) = u[j];      *(uint32_t*)(pf + oe) = v[j];
        *(uint32_t*)(pe1 + oe) = u[j + 1]; *(uint32_t*)(pf1 + oe) = v[j + 1];
        *(uint32_t*)(pe2 + oe) = lo ? u[j + 2] : pad0; *(uint32_t*)(pf2 + oe) = lo ? v[j + 2] : pad1;
        *(uint32_t*)(pe + oo) = __shfl_xor_sync(~0u, lo ? u[j + 3] : u[j + 2], 2);
        *(uint32_t*)(pf + oo) = __shfl_xor_sync(~0u, lo ? v[j + 3] : v[j + 2], 2);
        *(uint32_t*)(pe1 + oo) = __shfl_xor_sync(~0u, lo ? u[j + 4] : u[j + 3], 2);
        *(uint32_t*)(pf1 + oo) = __shfl_xor_sync(~0u, lo ? v[j + 4] : v[j + 3], 2);
        const uint32_t tu = __shfl_xor_sync(~0u, u[j + 4], 2), tv = __shfl_xor_sync(~0u, v[j + 4], 2);
        *(uint32_t*)(pe2 + oo) = lo ? tu : pad0; *(uint32_t*)(pf2 + oo) = lo ? tv : pad1;
      }
      if (tid == 0) STAMP(5, 3);
      {
        float nm = 0.f;
#pragma unroll
        for (int hp = 0; hp < 4; hp++) {
          float sq[2][5];
#pragma unroll
          for (int i = 0; i < 5; i++) {
            const uint32_t x = u[hp * 5 + i], y = v[hp * 5 + i];
            sq[0][i] = fmaf(bf_lo(x), bf_lo(x), bf_hi(x) * bf_hi(x));
            sq[1][i] = fmaf(bf_lo(y), bf_lo(y), bf_hi(y) * bf_hi(y));
          }
          const float e0 = (sq[0][0] + sq[0][1] + (lo ? sq[0][2] : 0.f)) * r0, e1 = (sq[1][0] + sq[1][1] + (lo ? sq[1][2] : 0.f)) * r1;
          const float o0 = (sq[0][3] + sq[0][4] + (lo ? 0.f : sq[0][2])) * r0, o1 = (sq[1][3] + sq[1][4] + (lo ? 0.f : sq[1][2])) * r1;
          const float k0 = (lo ? e0 : o0) + __shfl_xor_sync(~0u, lo ? o0 : e0, 2);
          const float k1 = (lo ? e1 : o1) + __shfl_xor_sync(~0u, lo ? o1 : e1, 2);
          const float z = ((c & 1) ? k1 : k0) + __shfl_xor_sync(~0u, (c & 1) ? k0 : k1, 1);
          const uint32_t em = __reduce_max_sync(~0u, lo ? __float_as_uint(z) : 0u), om = __reduce_max_sync(~0u, lo ? 0u : __float_as_uint(z));
          if ((lane >> 1) == hp) nm = __uint_as_float((lane & 1) ? om : em);
        }
        if (lane < 8) g_nrm[(n * 8 + lane) * 128 + (row0 >> 4)] = nm;
      }
    }
    if (tid == 0) STAMP(0, 4);
  }
  cluster_wait();
  if (tid == 0) STAMP(0, 6);
}

constexpr int K2_SMEM = 2 * HEAD_IMG + 2 * 6144 + 2 * 10240 + 160 + 96;

__device__ __forceinline__ uint64_t desc64(uint32_t lo, uint32_t hi) {
  uint64_t d;
  asm("mov.b64 %0, {%1, %2};" : "=l"(d) : "r"(lo), "r"(hi));
  return d;
}
__device__ __forceinline__ uint32_t exp_pair(bool poly, float a, float b, uint32_t mk) {
  if (poly) {
    const uint32_t pk = __byte_perm(__float_as_uint(a), __float_as_uint(b), 0x6521);
    uint32_t m, q;
    asm("lop3.b32 %0, %1, %2, 0x3f803f80, 0xEA;" : "=r"(m) : "r"(pk), "r"(mk));
    asm("fma.rn.bf16x2 %0, %1, %1, %2;" : "=r"(q) : "r"(m), "r"(0x40014001u));
    return pk - m + q;
  }
  return pack_bf16(ex2(a), ex2(b));
}
constexpr int PV_GRP = 4;
__device__ __forceinline__ void exp_pv(const float (&s)[64], float (&o)[12], uint64_t dv, uint32_t mk) {
#pragma unroll
  for (int k0 = 0; k0 < 8; k0 += PV_GRP) {
    uint32_t p[4 * PV_GRP];
#pragma unroll
    for (int i = 0; i < 4 * PV_GRP; i++)
      p[i] = exp_pair((POLY_MASK >> (k0 * 2 + i / 2)) & 1, s[k0 * 8 + 2 * i], s[k0 * 8 + 2 * i + 1], mk);
    WG_FENCE();
#pragma unroll
    for (int k = 0; k < PV_GRP; k++)
      wgmma_rs_n24(o, p[4 * k], p[4 * k + 1], p[4 * k + 2], p[4 * k + 3], dv + (k0 + k) * 48, 1);
  }
}
__device__ __forceinline__ void load_q(uint32_t (&q)[6], const uint8_t* p) {
  q[0] = __ldcg((const uint32_t*)p);         q[1] = __ldcg((const uint32_t*)(p + 384));
  q[2] = __ldcg((const uint32_t*)(p + 128)); q[3] = __ldcg((const uint32_t*)(p + 512));
  q[4] = __ldcg((const uint32_t*)(p + 256)); q[5] = __ldcg((const uint32_t*)(p + 640));
}
__device__ __forceinline__ float rcp(float x) {
  float y;
  asm("rcp.approx.ftz.f32 %0, %1;" : "=f"(y) : "f"(x));
  return y;
}
__device__ __forceinline__ int img_off(int chunk) { return chunk * 2048; }
__device__ __forceinline__ void store_o(const float (&o)[12], int tile) {
  int tid, bid;
  asm volatile("mov.u32 %0, %%tid.x;" : "=r"(tid));
  asm volatile("mov.u32 %0, %%ctaid.x;" : "=r"(bid));
  const int head = bid >> 2;
  uint8_t* dst = (uint8_t*)g_o + ((bid & 3) * 4 + (tile >> 1)) * 163840 + (tile & 1) * 1024 + ((tid >> 5) & 3) * 256 + (tid & 31) * 4;
  const int oc = (head >> 1) * 5 + (head & 1) * 2;
  const int o0 = img_off(oc), o1 = img_off(oc + 1), o2 = img_off((head >> 1) * 5 + 4) + (head & 1) * 8;
  const float i0 = rcp(__shfl_sync(~0u, o[8], 2, 4)), i1 = rcp(__shfl_sync(~0u, o[10], 2, 4));
  *(uint32_t*)(dst + o0) = pack_bf16(o[0] * i0, o[1] * i0); *(uint32_t*)(dst + o0 + 128) = pack_bf16(o[2] * i1, o[3] * i1);
  *(uint32_t*)(dst + o1) = pack_bf16(o[4] * i0, o[5] * i0); *(uint32_t*)(dst + o1 + 128) = pack_bf16(o[6] * i1, o[7] * i1);
  if ((tid & 3) < 2) {
    *(uint32_t*)(dst + o2) = pack_bf16(o[8] * i0, o[9] * i0);
    *(uint32_t*)(dst + o2 + 128) = pack_bf16(o[10] * i1, o[11] * i1);
  }
}

struct Maps5 { CUtensorMap m[5]; };

__global__ void __launch_bounds__(512, 1)
k2_attn(const __grid_constant__ Maps5 maps, const bf16* __restrict__ wo, uint32_t mk) {
  const CUtensorMap* tmw = maps.m;
  extern __shared__ __align__(1024) uint8_t sm[];
  const uint32_t sbase = smem_u32(sm);
  float* part = (float*)(sm + 2 * HEAD_IMG);
  const uint32_t rbuf = sbase + 2 * HEAD_IMG + 2 * 6144;
  const uint32_t kvb = rbuf + 2 * 10240;
  const uint32_t partb = kvb + 128, rbar = kvb + 144;
  const int tid = threadIdx.x, lane = tid & 31;
  const int warp = __shfl_sync(~0u, tid >> 5, 0);
  const int head = blockIdx.x >> 2, qb = blockIdx.x & 3;

  if (tid == 0) STAMP(1, 0);
  if (tid == 0) {
    for (int i = 0; i < 16; i++) mbar_init(kvb + 8 * i, 1);
    mbar_init(partb, 128); mbar_init(partb + 8, 128); mbar_init(rbar, 1); mbar_init(rbar + 8, 1);
    asm volatile("fence.mbarrier_init.release.cluster;" ::: "memory");
  }
  __syncthreads();

  if (warp >= 12) {
    asm volatile("setmaxnreg.dec.sync.aligned.u32 32;");
    if (warp == 12) {
      const uint8_t* kimg = (const uint8_t*)g_qkv + (size_t)(32 + head) * HEAD_IMG;
      if (elect_one()) {
#pragma unroll
        for (int b = 0; b < 16; b++) mbar_expect(kvb + 8 * b, 12288);
      }
      pdl_wait();
#pragma unroll 1
      for (int b = 0; b < 16; b++) {
        if (elect_one()) {
          bulk_ld(sbase + b * 6144, kimg + b * 6144, 6144, kvb + 8 * b);
          bulk_ld(sbase + HEAD_IMG + b * 6144, kimg + 32 * HEAD_IMG + b * 6144, 6144, kvb + 8 * b);
        }
        if (b >= 2) mbar_wait(kvb + 8 * (b - 1), 0);
      }
      pdl_trigger();
    }
    if (warp > 12) {
      const int t96 = tid - 416, ck = min(t96, 79), nt = ck / 10;
      float* red = (float*)(sm + K2_SMEM - 96);
#pragma unroll 1
      for (int i = 0; i < 5; i++) {
        const int k = blockIdx.x * 5 + i, pr = k / 40, r = k - pr * 40;
        const uint4 v = ldg_nc(wo + (pr * 40 + (r < 16 ? r : (r < 32 ? r + 4 : (r < 36 ? r - 16 : r)))) * D_ + ck * 8);
        g_wo[((nt * 10 + (k >> 6)) * 10 + ck - nt * 10) * 64 + (k & 63)] = v;
        float t = ((bf_lo(v.x) + bf_hi(v.x)) + (bf_lo(v.y) + bf_hi(v.y))) + ((bf_lo(v.z) + bf_hi(v.z)) + (bf_lo(v.w) + bf_hi(v.w)));
        if (t96 >= 80) t = 0.f;
#pragma unroll
        for (int o = 16; o; o >>= 1) t += __shfl_xor_sync(~0u, t, o);
        if (lane == 0) red[(t96 >> 5) * 8 + i] = t;
      }
      bar_sync(1, 96);
      if (t96 < 5) {
        const float mu = (red[t96] + red[8 + t96] + red[16 + t96]) * (1.f / D_);
        const float hi = bf_lo(pack_bf16(mu, 0.f));
        g_wm[blockIdx.x * 5 + t96] = make_uint4(pack_bf16(hi, mu - hi), 0u, 0u, 0u);
      }
      __syncwarp();
      if (t96 == 0) asm volatile("st.release.gpu.global.u32 [%0], %1;" ::"l"(&g_wflag[blockIdx.x]), "r"(__ldcg(&g_epoch) + 1) : "memory");
    }
    if (tid == 384) {
      mbar_wait(kvb + 8 * 15, 0);
      STAMP(1, 2);
      uint8_t* pdst = nullptr;
      uint32_t pbytes = 0;
#pragma unroll 1
      for (int i = 0; i < 8; i++) {
        const int p = blockIdx.x + 128 * i;
        uint8_t* dst = nullptr;
        uint32_t bytes = 0;
        if (i < 7 && p < 856) {
          asm volatile("cp.async.bulk.wait_group.read 0;" ::: "memory");
          const CUtensorMap* tm;
          int c1, c2;
          if (p < 640) {
            const int nt = p / 80, r = p - nt * 80, ph = r / 40, st = (r - ph * 40) >> 1, up = r & 1;
            bytes = ph ? 6656 : 7168;
            dst = (uint8_t*)g_wgu + nt * 552960 + ph * 286720 + st * 2 * bytes + up * (bytes >> 1);
            tm = &tmw[ph * 2 + up]; c1 = ph ? 112 + nt * 13 : nt * 14; c2 = st * 2;
          } else {
            const int nk = p - 640, nt = nk / 27;
            bytes = 10240;
            dst = (uint8_t*)g_wd + (size_t)nk * 10240;
            tm = &tmw[4]; c1 = nt * 10; c2 = nk - nt * 27;
          }
          mbar_expect(rbar + 8 * (i & 1), bytes);
          tma4d(rbuf + (i & 1) * 10240, tm, c1, c2, rbar + 8 * (i & 1));
        }
        if (pbytes) {
          mbar_wait(rbar + 8 * ((i - 1) & 1), ((i - 1) >> 1) & 1);
          if (pbytes == 10240) {
            bulk_st(pdst, rbuf + ((i - 1) & 1) * 10240, pbytes);
          } else {
            bulk_st(pdst, rbuf + ((i - 1) & 1) * 10240, pbytes >> 1);
            bulk_st(pdst + pbytes, rbuf + ((i - 1) & 1) * 10240 + (pbytes >> 1), pbytes >> 1);
          }
          asm volatile("cp.async.bulk.commit_group;" ::: "memory");
        }
        pdst = dst; pbytes = bytes;
      }
      asm volatile("cp.async.bulk.wait_group.read 0;" ::: "memory");
      STAMP(1, 6);
    }
  } else {
    asm volatile("setmaxnreg.inc.sync.aligned.u32 160;");
    const int wg = warp >> 2;
    const uint8_t* qthr = (const uint8_t*)g_qkv + (size_t)head * HEAD_IMG + qb * 64 * 384 + (warp & 3) * 768 + lane * 4;
    const uint32_t klo0 = ((sbase & 0x3FFFF) >> 4) | (128u << 16), vlo0 = (((sbase + HEAD_IMG) & 0x3FFFF) >> 4) | (24u << 16);
    constexpr uint64_t KSTEP2 = (uint64_t)(int64_t)(256 - (128 << 16));
    constexpr uint64_t KV2K = 384 - (HEAD_IMG >> 4) + (104 << 16);
    const int nun = wg == 1 ? 4 : 3;
    uint32_t utile = wg == 0 ? 0x210u : (wg == 1 ? 0x4235u : 0x576u);
    uint32_t ubeg = wg == 0 ? 0u : (wg == 1 ? 0x0b00u : 0x600u);
    uint32_t ulen = wg == 0 ? 0x0b1010u : (wg == 1 ? 0x10051006u : 0x0a1010u);
    pdl_wait();
    if (tid == 0) STAMP(1, 1);
    uint32_t q[6];
    load_q(q, qthr + (utile & 15) * 3072);
    bool fast;
    {
      const uint4 kn = __ldcg((const uint4*)&g_nrm[(32 + head) * 128 + lane * 4]);
      const uint4 vn = __ldcg((const uint4*)&g_nrm[(64 + head) * 128 + lane * 4]);
      const float qv = __ldcg(&g_nrm[head * 128 + qb * 32 + lane]);
      const float k2 = __uint_as_float(__reduce_max_sync(~0u, max(max(kn.x, kn.y), max(kn.z, kn.w))));
      const float v2 = __uint_as_float(__reduce_max_sync(~0u, max(max(vn.x, vn.y), max(vn.z, vn.w))));
      const float q2 = __uint_as_float(__reduce_max_sync(~0u, __float_as_uint(qv)));
      fast = q2 * k2 <= 3400.f && v2 < 1e24f && v2 > 1e-24f;
    }
    if (fast) {
#pragma unroll 1
      for (int u = 0; u < nun; u++) {
        const uint32_t b0 = ubeg & 15;
        const bool wt = u == 0 || (wg == 1 && u == 1);
        float s[64], o[12];
#pragma unroll
        for (int i = 0; i < 12; i++) o[i] = 0.f;
        uint32_t vlo = vlo0 + b0 * 384, kb = kvb + b0 * 8;
        const uint32_t vend = vlo + ((ulen & 255) - 1) * 384;
        if (wt) mbar_wait(kb, 0);
        if (tid == 0) STAMP(5, 4 + u);
        fence_regs(o);
        WG_FENCE();
        wgmma_rs_n128(s, q[0], q[1], q[2], q[3], desc64(klo0 + b0 * 384, 8), 0);
        wgmma_rs_n128(s, q[4], q[5], 0, 0, desc64(klo0 + b0 * 384, 8) + KSTEP2, 1);
        WG_COMMIT();
#pragma unroll 1
        for (; vlo != vend; vlo += 384) {
          if (wt) { kb += 8; mbar_wait(kb, 0); }
          WG_WAIT(0);
          fence_regs(s); fence_regs(o);
          const uint64_t dv = desc64(vlo, 8);
          exp_pv(s, o, dv, mk);
          wgmma_rs_n128(s, q[0], q[1], q[2], q[3], dv + KV2K, 0);
          wgmma_rs_n128(s, q[4], q[5], 0, 0, dv + (KV2K + KSTEP2), 1);
          WG_COMMIT();
        }
        WG_WAIT(0);
        fence_regs(s); fence_regs(o);
        if (u + 1 < nun) load_q(q, qthr + ((utile >> 4) & 15) * 3072);
        exp_pv(s, o, desc64(vlo, 8), mk);
        WG_COMMIT();
        WG_WAIT(0);
        fence_regs(o);
        if (wg == 1 && !(u & 1)) {
          float4* pp = (float4*)(part + u * 768) + (tid & 127);
          pp[0] = make_float4(o[0], o[1], o[2], o[3]);
          pp[128] = make_float4(o[4], o[5], o[6], o[7]);
          pp[256] = make_float4(o[8], o[9], o[10], o[11]);
          mbar_arrive(partb + 4 * u);
        } else {
          if (wg != 1 && u == 2) {
            const int pi = wg == 0 ? 1 : 0;
            mbar_wait(partb + 8 * pi, 0);
            const float4* pp = (const float4*)(part + pi * 1536) + (tid & 127);
            const float4 x0 = pp[0], x1 = pp[128], x2 = pp[256];
            o[0] += x0.x; o[1] += x0.y; o[2] += x0.z; o[3] += x0.w; o[4] += x1.x; o[5] += x1.y;
            o[6] += x1.z; o[7] += x1.w; o[8] += x2.x; o[9] += x2.y; o[10] += x2.z; o[11] += x2.w;
          }
          store_o(o, utile & 15);
        }
        utile >>= 4; ubeg >>= 4; ulen >>= 8;
      }
      if ((tid & 127) == 0) STAMP(1, 3 + wg);
    } else {
#pragma unroll 1
      for (int tile = wg; tile < 8; tile += 3) {
        load_q(q, qthr + tile * 3072);
        if ((lane & 3) >= 2) { q[4] = 0; q[5] = 0; }
        float o[12], m0 = -INFINITY, m1 = -INFINITY;
#pragma unroll
        for (int i = 0; i < 12; i++) o[i] = 0.f;
#pragma unroll 1
        for (int b = 0; b < 16; b++) {
          float s[64];
          mbar_wait(kvb + 8 * b, 0);
          WG_FENCE();
          wgmma_rs_n128(s, q[0], q[1], q[2], q[3], desc64(klo0 + b * 384, 8), 0);
          wgmma_rs_n128(s, q[4], q[5], 0, 0, desc64(klo0 + b * 384, 8) + KSTEP2, 1);
          WG_COMMIT();
          WG_WAIT(0);
          fence_regs(s);
          float x0 = m0, x1 = m1;
#pragma unroll
          for (int j = 0; j < 16; j++) {
            if ((POLY_MASK >> j) & 1) {
#pragma unroll
              for (int i = 0; i < 4; i++) s[4 * j + i] *= (1.f / 32768.f);
            }
            x0 = fmaxf(x0, fmaxf(s[4 * j], s[4 * j + 1]));
            x1 = fmaxf(x1, fmaxf(s[4 * j + 2], s[4 * j + 3]));
          }
          x0 = fmaxf(x0, __shfl_xor_sync(~0u, x0, 1)); x0 = fmaxf(x0, __shfl_xor_sync(~0u, x0, 2));
          x1 = fmaxf(x1, __shfl_xor_sync(~0u, x1, 1)); x1 = fmaxf(x1, __shfl_xor_sync(~0u, x1, 2));
          const float al0 = ex2(m0 - x0), al1 = ex2(m1 - x1);
          m0 = x0; m1 = x1;
#pragma unroll
          for (int i = 0; i < 12; i++) o[i] *= (i & 2) ? al1 : al0;
          uint32_t p[32];
#pragma unroll
          for (int i = 0; i < 32; i++) {
            const float mm = (i & 1) ? m1 : m0;
            p[i] = pack_bf16(ex2(s[2 * i] - mm), ex2(s[2 * i + 1] - mm));
          }
          fence_regs(o);
          WG_FENCE();
#pragma unroll
          for (int k = 0; k < 8; k++)
            wgmma_rs_n24(o, p[4 * k], p[4 * k + 1], p[4 * k + 2], p[4 * k + 3], desc64(vlo0 + b * 384 + k * 48, 8), 1);
          WG_COMMIT();
          WG_WAIT(0);
          fence_regs(o);
        }
        store_o(o, tile);
      }
    }
  }
}

constexpr int K3_ST = 4, K3_STAGE = 37888, K3_NB = 4, K3_NT = 6;
constexpr int K3_SMEM = K3_ST * K3_STAGE + 24576 + 20480 + 256;

template <int N> struct Acc { float v[N]; };

__global__ void __cluster_dims__(2, 1, 1) __launch_bounds__(288, 1)
k3_proj(const __grid_constant__ CUtensorMap tmx) {
  extern __shared__ __align__(1024) uint8_t sm[];
  const uint32_t sbase = smem_u32(sm);
  const uint8_t* xch = sm + K3_ST * K3_STAGE;
  const uint8_t* res = sm + K3_ST * K3_STAGE + 24576;
  const uint32_t fullb = smem_u32(res) + 20480, emptyb = fullb + 8 * K3_ST, resb = emptyb + 8 * K3_ST, xchb = resb + 8;
  const int tid = threadIdx.x, lane = tid & 31;
  const int warp = __shfl_sync(~0u, tid >> 5, 0);
  const int rank = blockIdx.x & 1;
  const int n = blockIdx.x & 7, m = blockIdx.x >> 3;
  if (tid == 0) STAMP(2, 0);
  if (warp == 8) {
    if (elect_one()) {
#pragma unroll
      for (int i = 0; i < K3_ST; i++) { mbar_init(fullb + 8 * i, 1); mbar_init(emptyb + 8 * i, 4); }
      mbar_init(resb, 1); mbar_init(xchb, 1);
      mbar_expect(xchb, 24576);
      asm volatile("fence.mbarrier_init.release.cluster;" ::: "memory");
    }
    __syncwarp();
  }
  cluster_arrive();
  if (warp == 8) {
    const uint8_t* wk = (const uint8_t*)g_wo + n * 102400;
    const uint8_t* ws = (const uint8_t*)g_wo + (n ^ 1) * 102400;
    const uint8_t* ab = (const uint8_t*)g_o + m * 163840;
    prefetch_map(&tmx);
    uint32_t wf;
    asm volatile("ld.acquire.gpu.global.u32 %0, [%1];" : "=r"(wf) : "l"(&g_wflag[(rank * K3_NT * 64) / 5 + min(lane, 13)]) : "memory");
    const bool early = __all_sync(~0u, wf == __ldcg(&g_epoch) + 1);
#pragma unroll 1
    for (int i = -1; i < K3_NT; i++) {
      const int ii = max(i, 0), s = ii % K3_ST, kt = ii < K3_NB ? ii + rank * K3_NT : ii;
      const uint32_t sa = sbase + s * K3_STAGE, fb = fullb + 8 * s;
      if (i == 0) {
        cluster_wait();
        pdl_wait();
        if (lane == 0) STAMP(2, 6);
      }
      if (i >= K3_ST) mbar_wait(emptyb + 8 * s, 0);
      if (elect_one()) {
        if (i < 0) asm volatile("fence.proxy.async.global;" ::: "memory");
        if (i != 0) mbar_expect(fb, i < K3_NB ? 37888 : 27648);
        if (i >= K3_NB) bulk_ld_mc(sa + rank * 8192, ab + kt * 16384 + rank * 8192, 8192, fb);
        else if (i >= 0) bulk_ld(sa, ab + kt * 16384, 16384, fb);
        if (i > 0 || (i < 0) == early) {
          bulk_ld(sa + 16384, wk + kt * 10240, 10240, fb);
          bulk_ld(sa + 26624, (const uint8_t*)g_wm + kt * 1024, 1024, fb);
          if (i < K3_NB) bulk_ld(sa + 27648, ws + kt * 10240, 10240, fb);
        }
        if (i == K3_ST - 1) {
          mbar_expect(resb, 20480);
          tma2d(smem_u32(res), &tmx, n * 80, m * 128, resb);
          tma2d(smem_u32(res) + 10240, &tmx, n * 80, m * 128 + 64, resb);
        }
      }
      if (i == 0) {
        pdl_trigger();
        if (blockIdx.x == 0 && lane == 0) g_epoch = g_epoch + 1;
      }
    }
    cluster_arrive();
  } else {
    const int g = lane >> 2, c = lane & 3;
    const int row = m * 128 + warp * 16 + g;
    float mu0 = __uint_as_float(__ldcg(&g_rowstat[row].z)), mu1 = __uint_as_float(__ldcg(&g_rowstat[row + 8].z));
    float acc[84];
    float (&keep)[44] = ((Acc<44>*)acc)->v;
    const uint64_t da0 = mkdesc(sbase + (warp >> 2) * 1024, 2048, 128, 0);
    const uint64_t db0 = mkdesc(sbase + 16384, 128, 1024, 0);
    cluster_wait();
#pragma unroll 1
    for (int i = 0; i < K3_NB; i++) {
      mbar_wait(fullb + 8 * i, 0);
      if (i == 0 && tid == 0) STAMP(2, 2);
      const uint64_t da = da0 + i * (K3_STAGE >> 4), db = db0 + i * (K3_STAGE >> 4);
      WG_FENCE();
#pragma unroll
      for (int k = 0; k < 4; k++) wgmma_ss_n168(acc, da + k * 256, db + k * 16, (i | k) != 0);
      WG_COMMIT();
      if (i > 0) {
        WG_WAIT(1);
        if (i - 1 + K3_ST < K3_NT && (tid & 127) < 2) mbar_arrive_cta(emptyb + 8 * (i - 1), tid & 1);
      }
    }
    const uint32_t rx = mapa(smem_u32(xch) + tid * 16, rank ^ 1), rb = mapa(xchb, rank ^ 1);
    WG_WAIT(0);
    fence_regs(acc);
    st_async4(rx, acc[40], acc[41], acc[42], acc[43], rb);
    if (tid == 0) STAMP(2, 1);
#pragma unroll
    for (int i = K3_NB; i < K3_NT; i++) {
      const int s = i % K3_ST;
      mbar_wait(fullb + 8 * s, 1);
      const uint64_t da = da0 + s * (K3_STAGE >> 4), db = db0 + s * (K3_STAGE >> 4);
      WG_FENCE();
#pragma unroll
      for (int k = 0; k < 4; k++) wgmma_ss_n88(keep, da + k * 256, db + k * 16, 1);
      WG_COMMIT();
#pragma unroll
      for (int j = (i - K3_NB) * 3; j < (i - K3_NB) * 3 + 3; j++)
        if (j < 5) SEND8(rx + (j + 1) * 4096, acc, 44 + 8 * j, rb);
    }
    cluster_arrive();
    const uint8_t* sp = res + (warp * 16 + g) * 160 + c * 4;
    uint32_t rv[20];
    mbar_wait(resb, 0);
#pragma unroll
    for (int j = 0; j < 10; j++) {
      rv[2 * j] = *(const uint32_t*)(sp + j * 16);
      rv[2 * j + 1] = *(const uint32_t*)(sp + 1280 + j * 16);
    }
    WG_WAIT(0);
    fence_regs(keep);
    if (tid == 0) STAMP(2, 3);
    mbar_wait(xchb, 0);
    if (tid == 0) STAMP(2, 5);
    const uint8_t* xp = xch + tid * 16;
    {
      const float4 p = *(const float4*)xp;
      mu0 += __shfl_sync(~0u, (keep[40] + p.x) + (keep[41] + p.y), 0, 4);
      mu1 += __shfl_sync(~0u, (keep[42] + p.z) + (keep[43] + p.w), 0, 4);
    }
    uint8_t* himg = (uint8_t*)g_h + m * 163840 + img_off(n * 10) + warp * 256 + lane * 4;
    float q0 = 0.f, q1 = 0.f;
#pragma unroll
    for (int j = 0; j < 10; j++) {
      const uint2 p = *(const uint2*)(xp + ((j >> 1) + 1) * 4096 + (j & 1) * 8);
      const float x0 = (keep[4 * j] + bf_lo(p.x)) + (bf_lo(rv[2 * j]) - mu0), x1 = (keep[4 * j + 1] + bf_hi(p.x)) + (bf_hi(rv[2 * j]) - mu0);
      const float y0 = (keep[4 * j + 2] + bf_lo(p.y)) + (bf_lo(rv[2 * j + 1]) - mu1), y1 = (keep[4 * j + 3] + bf_hi(p.y)) + (bf_hi(rv[2 * j + 1]) - mu1);
      *(uint32_t*)(himg + img_off(j)) = pack_bf16(x0, x1);
      *(uint32_t*)(himg + img_off(j) + 128) = pack_bf16(y0, y1);
      q0 = fmaf(x0, x0, fmaf(x1, x1, q0)); q1 = fmaf(y0, y0, fmaf(y1, y1, q1));
    }
    q0 += __shfl_xor_sync(~0u, q0, 1); q0 += __shfl_xor_sync(~0u, q0, 2);
    q1 += __shfl_xor_sync(~0u, q1, 1); q1 += __shfl_xor_sync(~0u, q1, 2);
    if (c < 2) g_hpart[n * S_ + row + c * 8] = c ? q1 : q0;
    if (n == 0 && c < 2) g_hmean[row + c * 8] = c ? mu1 : mu0;
    if (tid == 0) STAMP(2, 4);
  }
  cluster_wait();
}

constexpr int P3_NB = 12, P3_NT = 15;
constexpr int K4_G = 2, K4_NS = 4, K4_NJ = 20;
constexpr int K4_RB = 163840, K4_BST = 7168 * K4_G, K4_XCH = 147456, K4_STG = K4_XCH + 40960, K4_BAR = K4_RB + K4_NS * K4_BST;
constexpr int K4_SMEM = K4_BAR + 384;

__device__ __forceinline__ void wait_flags(const uint4* f, uint32_t tag, uint32_t need, uint32_t& seen) {
  if ((seen & need) == need) return;
  for (uint32_t it = 0; (seen & need) != need; it++) {
    if (it > (1u << 20)) wait_timeout();
    if (it) __nanosleep(150);
    uint32_t v = 0;
    if ((threadIdx.x & 31) < 8) asm volatile("ld.acquire.gpu.global.u32 %0, [%1];" : "=r"(v) : "l"((const uint32_t*)f + (threadIdx.x & 7)) : "memory");
    seen = __ballot_sync(~0u, v == tag) & 255;
  }
  asm volatile("fence.proxy.async.global;" ::: "memory");
}

template <int MODE>
__global__ void __cluster_dims__(2, 1, 1) __launch_bounds__(384, 1)
k45_ffn(const __grid_constant__ CUtensorMap tmo) {
  extern __shared__ __align__(1024) uint8_t sm[];
  const uint32_t sbase = smem_u32(sm);
  const uint32_t afull = sbase + K4_BAR, bfull = afull + 80, bempty = bfull + 8 * K4_NS, full3 = bempty + 8 * K4_NS;
  const uint32_t empty3 = full3 + 32, afree = empty3 + 32, xchb = afree + 32;
  const int tid = threadIdx.x, lane = tid & 31;
  const int warp = __shfl_sync(~0u, tid >> 5, 0);
  const int rank = blockIdx.x & 1;
  const int n1 = (blockIdx.x >> 1) & 7, m1 = (blockIdx.x >> 4) * 2 + rank;
  const int n3 = blockIdx.x & 7, m3 = blockIdx.x >> 3;
  if (tid == 0) STAMP(3, 0);
  if (warp == 8) {
    if (elect_one()) {
#pragma unroll
      for (int i = 0; i < 10; i++) mbar_init(afull + 8 * i, 1);
#pragma unroll
      for (int i = 0; i < 4; i++) {
        mbar_init(bfull + 8 * i, 1); mbar_init(bempty + 8 * i, 4); mbar_init(full3 + 8 * i, 1); mbar_init(empty3 + 8 * i, 4);
        mbar_init(afree + 8 * i, 2);
      }
      mbar_init(xchb, 1);
      mbar_expect(xchb, 20480);
      asm volatile("fence.mbarrier_init.release.cluster;" ::: "memory");
    }
    __syncwarp();
  }
  cluster_arrive();
  if (warp >= 8) {
    cluster_wait();
    if (warp == 8) {
      if (lane == 0) STAMP(3, 7);
      const uint8_t* src = (const uint8_t*)g_wgu + n1 * 552960;
      const uint8_t* hb = (const uint8_t*)g_h + (size_t)m1 * 163840;
#pragma unroll 1
      for (int j = 0; j < (MODE == 2 ? 0 : 40); j++) {
        const uint32_t s8 = (j & 3) * 8, sz = j < 20 ? 14336 : 13312;
        if (j == 2) {
          pdl_wait();
          if (lane == 0) STAMP(3, 1);
          if (elect_one()) {
#pragma unroll
            for (int kt = 0; kt < 2 / 2 + 1; kt++) { mbar_expect(afull + 8 * kt, 16384); bulk_ld(sbase + kt * 16384, hb + kt * 16384, 16384, afull + 8 * kt); }
          }
        }
        if (j >= 4) mbar_wait(bempty + s8, ((j >> 2) - 1) & 1);
        if (elect_one()) {
          mbar_expect(bfull + s8, sz);
          if ((j & 1) == rank) bulk_ld_mc(sbase + K4_RB + s8 * (K4_BST / 8), src, sz, bfull + s8);
          if (j > 2 && j < 18 && (j & 1)) {
            mbar_expect(afull + 4 + j * 4, 16384);
            bulk_ld(sbase + 8192 + j * 8192, hb + 8192 + j * 8192, 16384, afull + 4 + j * 4);
          }
        }
        src += sz;
      }
    } else if (warp == 9) {
      prefetch_map(&tmo);
      if (MODE != 2) mbar_wait(afull, 0);
      const uint32_t tag = __ldcg(&g_epoch);
#pragma unroll 1
      for (int ph = 0; ph < (MODE == 2 ? 0 : 2); ph++) {
        bar_sync(5 + ph, 256 + 32);
        if (lane == 0) {
          asm volatile("st.release.gpu.global.u32 [%0], %1;" ::"l"((uint32_t*)&g_flag[ph * 32 + m1 * 2] + n1), "r"(tag) : "memory");
          STAMP(3, 5 + ph);
        }
        __syncwarp();
      }
    } else {
      const uint8_t* wk = (const uint8_t*)g_wd + n3 * 276480;
      const uint8_t* ws = (const uint8_t*)g_wd + (n3 ^ 1) * 276480;
      const uint8_t* ab = (const uint8_t*)g_hh + (size_t)m3 * 442368;
      if (MODE != 2) mbar_wait(afull + 72, 0);
      const uint32_t tag = __ldcg(&g_epoch);
      uint32_t seen = 0;
#pragma unroll 1
      for (int i = 0; i < (MODE == 1 ? 0 : P3_NT); i++) {
        const int kt = i < 7 ? rank * 7 + i : (i < P3_NB ? rank * (P3_NB - 7) + 7 + i : P3_NB + i);
        const uint32_t sa = sbase + (i & 3) * 36864, fb = full3 + 8 * (i & 3);
        if (warp == 11) {
          const int q = kt * 8 - (i < 7 ? 0 : 112), w = i < 7 ? 14 : 13;
          if (i == 7) seen = 0;
          wait_flags(&g_flag[(i < 7 ? 0 : 32) + m3 * 2], tag, 1u << (q / w) | 1u << ((q + 7) / w), seen);
          if (lane == 0 && (i == 0 || i == 7)) STAMP(4, i ? 7 : 6);
        }
        if (i < 4) { if (MODE == 0) mbar_wait(afree + 8 * i, 0); }
        else mbar_wait(empty3 + 8 * (i & 3), ((i >> 2) - 1) & 1);
        if (warp == 10) {
          if (elect_one()) {
            mbar_expect(fb, i < P3_NB ? 36864 : 26624);
            bulk_ld(sa + 16384, wk + kt * 10240, 10240, fb);
            if (i < P3_NB) bulk_ld(sa + 26624, ws + kt * 10240, 10240, fb);
          }
        } else {
          if (elect_one()) {
            if (i < P3_NB) bulk_ld(sa, ab + kt * 16384, 16384, fb);
            else bulk_ld_mc(sa + rank * 8192, ab + kt * 16384 + rank * 8192, 8192, fb);
          }
        }
      }
    }
    __syncwarp();
    cluster_arrive();
    asm volatile("barrier.cluster.wait.aligned; // producers" ::: "memory");
  } else {
    const int wg = warp >> 2;
    const uint64_t da0 = mkdesc(sbase + wg * 1024, 2048, 128, 0);
    const uint64_t db0 = mkdesc(sbase + K4_RB, 128, 256, 0);
    cluster_wait();
    float acc[80];
    if constexpr (MODE != 2) {
    float a1[112], a2[104];
    int s = 0, ph = 0, sprev = 0;
#pragma unroll 1
    for (int j = 0; j < K4_NJ; j++) {
      if ((j * K4_G) % 4 == 0) mbar_wait(afull + 2 * K4_G * j, 0);
      mbar_wait(bfull + 8 * s, ph);
      if (j == 0 && tid == 0) STAMP(3, 2);
      const uint64_t da = da0 + j * K4_G * 256, db = db0 + s * (K4_BST >> 4);
      WG_FENCE();
#pragma unroll
      for (int k = 0; k < K4_G; k++) wgmma_ss_n224(a1, da + k * 256, db + k * 448, (j | k) != 0);
      WG_COMMIT();
      if (j > 0) {
        WG_WAIT(1);
        if ((tid & 127) < 2) mbar_arrive_cta(bempty + 8 * sprev, tid & 1);
      }
      sprev = s;
      if (++s == K4_NS) { s = 0; ph ^= 1; }
    }
    uint8_t* hd = (uint8_t*)g_hh + (size_t)m1 * 442368 + warp * 256 + lane * 4;
    WG_WAIT(0);
    fence_regs(a1);
    if ((tid & 127) < 2) mbar_arrive_cta(bempty + 8 * ((K4_NJ - 1) % K4_NS), tid & 1);
    if (tid == 0) STAMP(3, 3);
#define STORE_H(a, off, ptr, c) do { uint8_t* p_ = ptr; \
      *(uint32_t*)p_ = pack_bf16(a[4 * (c)] * a[off + 4 * (c)], a[4 * (c) + 1] * a[off + 1 + 4 * (c)]); \
      *(uint32_t*)(p_ + 128) = pack_bf16(a[4 * (c) + 2] * a[off + 2 + 4 * (c)], a[4 * (c) + 3] * a[off + 3 + 4 * (c)]); } while (0)
#pragma unroll
    for (int c = 0; c < 14; c++) STORE_H(a1, 56, hd + img_off(n1 * 14 + c), c);
    bar_arrive(5, 256 + 32);
#pragma unroll 1
    for (int j = 0; j < K4_NJ; j++) {
      mbar_wait(bfull + 8 * s, ph);
      const uint64_t da = da0 + j * K4_G * 256, db = db0 + s * (K4_BST >> 4);
      WG_FENCE();
#pragma unroll
      for (int k = 0; k < K4_G; k++) wgmma_ss_n208(a2, da + k * 256, db + k * 416, (j | k) != 0);
      WG_COMMIT();
      if (j > 0) {
        WG_WAIT(1);
        if (j <= K4_NJ - K4_NS && (tid & 127) < 2) mbar_arrive_cta(bempty + 8 * sprev, tid & 1);
        if (j * K4_G >= 12 && ((j * K4_G) & 7) == 4 && (tid & 127) == 0) mbar_arrive(afree + (j * K4_G - 12));
      }
      sprev = s;
      if (++s == K4_NS) { s = 0; ph ^= 1; }
    }
    WG_WAIT(0);
    fence_regs(a2);
    if (tid == 0) STAMP(3, 4);
#pragma unroll
    for (int c = 0; c < 13; c++) STORE_H(a2, 52, hd + img_off(112 + n1 * 13 + c), c);
    bar_arrive(6, 256 + 32);
    }
    if constexpr (MODE == 1) cluster_arrive();
    if constexpr (MODE != 1) {
    float (&keep)[40] = ((Acc<40>*)acc)->v;
    const uint64_t db3 = mkdesc(sbase + 16384, 128, 1024, 0);
#pragma unroll 1
    for (int i = 0; i < P3_NB; i++) {
      mbar_wait(full3 + 8 * (i & 3), (i >> 2) & 1);
      if (i == 0 && tid == 0) STAMP(4, 2);
      const uint64_t da = da0 + (i & 3) * 2304, db = db3 + (i & 3) * 2304;
      WG_FENCE();
#pragma unroll
      for (int k = 0; k < 4; k++) wgmma_ss_n160(acc, da + k * 256, db + k * 16, (i | k) != 0);
      WG_COMMIT();
      if (i > 0) {
        WG_WAIT(1);
        if (i + 3 < P3_NT && (tid & 127) < 2) mbar_arrive_cta(empty3 + 8 * ((i - 1) & 3), tid & 1);
      }
    }
    const int g = lane >> 2, c = lane & 3, row = m3 * 128 + warp * 16 + g;
    const uint8_t* himg = (const uint8_t*)g_h + (size_t)m3 * 163840 + warp * 256 + lane * 4;
    uint32_t rv[20];
    const float mu0 = __ldcg(&g_hmean[row]), mu1 = __ldcg(&g_hmean[row + 8]);
    float r0 = __ldcg(&g_hpart[c * 2 * S_ + row]) + __ldcg(&g_hpart[(c * 2 + 1) * S_ + row]);
    float r1 = __ldcg(&g_hpart[c * 2 * S_ + row + 8]) + __ldcg(&g_hpart[(c * 2 + 1) * S_ + row + 8]);
#pragma unroll
    for (int j = 0; j < 10; j++) {
      rv[2 * j] = __ldcg((const uint32_t*)(himg + img_off(n3 * 10 + j)));
      rv[2 * j + 1] = __ldcg((const uint32_t*)(himg + img_off(n3 * 10 + j) + 128));
    }
    const uint32_t rx = mapa(sbase + K4_XCH + tid * 16, rank ^ 1), rb = mapa(xchb, rank ^ 1);
    WG_WAIT(0);
    fence_regs(acc);
    if (P3_NB + 3 < P3_NT && (tid & 127) < 2) mbar_arrive_cta(empty3 + 8 * ((P3_NB - 1) & 3), tid & 1);
    if (tid == 0) STAMP(4, 1);
#pragma unroll
    for (int i = P3_NB; i < P3_NT; i++) {
      mbar_wait(full3 + 8 * (i & 3), (i >> 2) & 1);
      const uint64_t da = da0 + (i & 3) * 2304, db = db3 + (i & 3) * 2304;
      WG_FENCE();
#pragma unroll
      for (int k = 0; k < 4; k++) wgmma_ss_n80(keep, da + k * 256, db + k * 16, 1);
      WG_COMMIT();
      if (i > P3_NB && i + 3 < P3_NT) {
        WG_WAIT(1);
        if ((tid & 127) < 2) mbar_arrive_cta(empty3 + 8 * ((i - 1) & 3), tid & 1);
      }
#pragma unroll
      for (int j = (i - P3_NB) * 3; j < (i - P3_NB) * 3 + 3; j++)
        if (j < 5) SEND8(rx + j * 4096, acc, 40 + 8 * j, rb);
    }
    cluster_arrive();
    r0 += __shfl_xor_sync(~0u, r0, 1); r1 += __shfl_xor_sync(~0u, r1, 1);
    r0 += __shfl_xor_sync(~0u, r0, 2); r1 += __shfl_xor_sync(~0u, r1, 2);
    r0 = rcp(r0 * (1.f / D_) + 1e-5f); r1 = rcp(r1 * (1.f / D_) + 1e-5f);
    asm volatile("" : "+f"(r0), "+f"(r1)::"memory");
    WG_WAIT(0);
    fence_regs(keep);
    if (tid == 0) STAMP(4, 3);
    mbar_wait(xchb, 0);
    if (tid == 0) STAMP(4, 5);
    uint8_t* sp = sm + K4_STG + (warp * 16 + g) * 160 + c * 4;
#pragma unroll
    for (int j = 0; j < 10; j++) {
      const uint2 p = *(const uint2*)(sm + K4_XCH + tid * 16 + (j >> 1) * 4096 + (j & 1) * 8);
      *(uint32_t*)(sp + j * 16) = pack_bf16(fmaf(keep[4 * j] + bf_lo(p.x), r0, bf_lo(rv[2 * j]) + mu0), fmaf(keep[4 * j + 1] + bf_hi(p.x), r0, bf_hi(rv[2 * j]) + mu0));
      *(uint32_t*)(sp + 1280 + j * 16) = pack_bf16(fmaf(keep[4 * j + 2] + bf_lo(p.y), r1, bf_lo(rv[2 * j + 1]) + mu1), fmaf(keep[4 * j + 3] + bf_hi(p.y), r1, bf_hi(rv[2 * j + 1]) + mu1));
    }
    fence_async();
    bar_sync(1 + wg, 128);
    if ((tid & 127) == 0) {
      tma2d_st(&tmo, n3 * 80, m3 * 128 + wg * 64, sbase + K4_STG + wg * 10240);
      bulk_commit_wait();
    }
    __syncwarp();
    if (tid == 0) STAMP(4, 4);
    }
    asm volatile("barrier.cluster.wait.aligned; // consumers" ::: "memory");
  }
}

typedef CUresult (*EncodeFn)(CUtensorMap*, CUtensorMapDataType, cuuint32_t, void*, const cuuint64_t*, const cuuint64_t*,
                             const cuuint32_t*, const cuuint32_t*, CUtensorMapInterleave, CUtensorMapSwizzle,
                             CUtensorMapL2promotion, CUtensorMapFloatOOBfill);

static CUtensorMap make_map(EncodeFn enc, const void* p, uint64_t inner, uint64_t outer, uint32_t box_inner,
                            uint32_t box_outer, CUtensorMapSwizzle swz) {
  CUtensorMap m;
  cuuint64_t gd[2] = {inner, outer};
  cuuint64_t gs[1] = {inner * 2};
  cuuint32_t bd[2] = {box_inner, box_outer};
  cuuint32_t es[2] = {1, 1};
  enc(&m, CU_TENSOR_MAP_DATA_TYPE_BFLOAT16, 2, (void*)p, gd, gs, bd, es, CU_TENSOR_MAP_INTERLEAVE_NONE, swz,
      CU_TENSOR_MAP_L2_PROMOTION_L2_256B, CU_TENSOR_MAP_FLOAT_OOB_FILL_NONE);
  return m;
}

static CUtensorMap make_map_img(EncodeFn enc, const void* p, uint64_t k, uint64_t n, uint32_t rows, uint32_t chunks,
                                uint32_t groups) {
  CUtensorMap m;
  cuuint64_t gd[4] = {8, rows, n / 8, k / rows};
  cuuint64_t gs[3] = {n * 2, 16, n * 2 * rows};
  cuuint32_t bd[4] = {8, rows, chunks, groups};
  cuuint32_t es[4] = {1, 1, 1, 1};
  enc(&m, CU_TENSOR_MAP_DATA_TYPE_BFLOAT16, 4, (void*)p, gd, gs, bd, es, CU_TENSOR_MAP_INTERLEAVE_NONE,
      CU_TENSOR_MAP_SWIZZLE_NONE, CU_TENSOR_MAP_L2_PROMOTION_L2_128B, CU_TENSOR_MAP_FLOAT_OOB_FILL_NONE);
  return m;
}

template <typename... KArgs, typename... Args>
static void launch(void (*k)(KArgs...), int grid, int threads, int smem, bool pdl, Args... args) {
  cudaLaunchConfig_t cfg = {};
  cfg.gridDim = dim3(grid);
  cfg.blockDim = dim3(threads);
  cfg.dynamicSmemBytes = smem;
  cfg.stream = cudaStreamPerThread;
  cudaLaunchAttribute at[1];
  at[0].id = cudaLaunchAttributeProgrammaticStreamSerialization;
  at[0].val.programmaticStreamSerializationAllowed = 1;
  cfg.attrs = at;
  cfg.numAttrs = pdl ? 1 : 0;
  cudaLaunchKernelEx(&cfg, k, KArgs(args)...);
}

extern "C" void kernel_launch(void* const* d_in, const int* in_sizes, int n_in, void* d_out, int out_size) {
  const bf16* x = (const bf16*)d_in[0];
  const bf16* wqkv = (const bf16*)d_in[1];
  const bf16* wo = (const bf16*)d_in[2];
  const bf16* wg = (const bf16*)d_in[4];
  const bf16* wu = (const bf16*)d_in[5];
  const bf16* wd = (const bf16*)d_in[6];

  static EncodeFn enc = nullptr;
  static bool fused = true;
  if (!enc) {
    void* fn = nullptr;
    cudaDriverEntryPointQueryResult qr;
    cudaGetDriverEntryPoint("cuTensorMapEncodeTiled", &fn, cudaEnableDefault, &qr);
    enc = (EncodeFn)fn;
    cudaFuncSetAttribute(k1_qkv, cudaFuncAttributeMaxDynamicSharedMemorySize, K1_SMEM);
    cudaFuncSetAttribute(k2_attn, cudaFuncAttributeMaxDynamicSharedMemorySize, K2_SMEM);
    cudaFuncSetAttribute(k3_proj, cudaFuncAttributeMaxDynamicSharedMemorySize, K3_SMEM);
    cudaFuncSetAttribute(k45_ffn<0>, cudaFuncAttributeMaxDynamicSharedMemorySize, K4_SMEM);
    cudaFuncSetAttribute(k45_ffn<1>, cudaFuncAttributeMaxDynamicSharedMemorySize, K4_SMEM);
    cudaFuncSetAttribute(k45_ffn<2>, cudaFuncAttributeMaxDynamicSharedMemorySize, K4_SMEM);
    cudaLaunchConfig_t cfg = {};
    cfg.gridDim = dim3(128); cfg.blockDim = dim3(384); cfg.dynamicSmemBytes = K4_SMEM;
    int clusters = 0;
    cudaOccupancyMaxActiveClusters(&clusters, k45_ffn<0>, &cfg);
    fused = clusters >= 64;
  }
  const CUtensorMap tmx = make_map(enc, x, D_, S_, 64, 96, CU_TENSOR_MAP_SWIZZLE_128B);
  const CUtensorMap tmw = make_map(enc, wqkv, 3 * D_, D_, 32, 64, CU_TENSOR_MAP_SWIZZLE_64B);
  const CUtensorMap tmxr = make_map(enc, x, D_, S_, 80, 64, CU_TENSOR_MAP_SWIZZLE_NONE);
  Maps5 maps;
  maps.m[0] = make_map_img(enc, wg, D_, F_, 16, 14, 2); maps.m[1] = make_map_img(enc, wu, D_, F_, 16, 14, 2);
  maps.m[2] = make_map_img(enc, wg, D_, F_, 16, 13, 2); maps.m[3] = make_map_img(enc, wu, D_, F_, 16, 13, 2);
  maps.m[4] = make_map_img(enc, wd, F_, D_, 64, 10, 1);
  const CUtensorMap tmout = make_map(enc, d_out, D_, S_, 80, 64, CU_TENSOR_MAP_SWIZZLE_NONE);

  launch(k1_qkv, 132, 512, K1_SMEM, false, tmx, tmw, x, wqkv);
  launch(k2_attn, 128, 512, K2_SMEM, true, maps, wo, 0x007f007fu);
  launch(k3_proj, 128, 288, K3_SMEM, true, tmxr);
  if (fused) {
    launch(k45_ffn<0>, 128, 384, K4_SMEM, true, tmout);
  } else {
    launch(k45_ffn<1>, 128, 384, K4_SMEM, true, tmout);
    launch(k45_ffn<2>, 128, 384, K4_SMEM, false, tmout);
  }
}
```

```cpp
#include <cuda_runtime.h>
#include <cuda_bf16.h>
#include <cuda.h>
#include <stdint.h>

typedef __nv_bfloat16 bf16;

constexpr int S_ = 2048, D_ = 640, F_ = 1728;
constexpr int HEAD_IMG = 98304;
constexpr uint32_t POLY_MASK = 0xFAAB;
constexpr float QSCALE = 0.22360679774997896f * 1.4426950408889634f;

__device__ __align__(1024) uint4 g_qkv[96 * HEAD_IMG / 16];
__device__ __align__(1024) uint4 g_o[S_ * D_ / 8];
__device__ __align__(1024) uint4 g_h[S_ * D_ / 8];
__device__ __align__(1024) uint4 g_hh[S_ * F_ / 8];
__device__ __align__(1024) uint4 g_wo[D_ * D_ / 8];
__device__ __align__(1024) uint4 g_wgu[2 * D_ * F_ / 8];
__device__ __align__(1024) uint4 g_wd[F_ * D_ / 8];
__device__ uint4 g_rowstat[S_];
__device__ uint4 g_cpart[10 * 12 * 80];
__device__ float g_nrm[96 * 128];
__device__ uint4 g_wm[D_];
__device__ float g_hmean[S_];
__device__ float g_hpart[8 * S_];
__device__ uint4 g_flag[2 * 16 * 2];
__device__ unsigned g_epoch;

__device__ __forceinline__ uint32_t smem_u32(const void* p) { return (uint32_t)__cvta_generic_to_shared(p); }
__device__ __forceinline__ void mbar_init(uint32_t a, uint32_t c) {
  asm volatile("mbarrier.init.shared::cta.b64 [%0], %1;" ::"r"(a), "r"(c) : "memory");
}
__device__ __forceinline__ void mbar_expect(uint32_t a, uint32_t bytes) {
  asm volatile("mbarrier.arrive.expect_tx.shared::cta.b64 _, [%0], %1;" ::"r"(a), "r"(bytes) : "memory");
}
__device__ __forceinline__ void mbar_arrive(uint32_t a) {
  asm volatile("mbarrier.arrive.shared::cta.b64 _, [%0];" ::"r"(a) : "memory");
}
__device__ __forceinline__ void mbar_arrive_cta(uint32_t a, uint32_t cta) {
  asm volatile("{\n.reg .b32 r;\nmapa.shared::cluster.u32 r, %0, %1;\n"
               "mbarrier.arrive.shared::cluster.b64 _, [r];\n}" ::"r"(a), "r"(cta) : "memory");
}
__device__ __forceinline__ bool mbar_try(uint32_t a, uint32_t ph) {
  uint32_t ok;
  asm volatile("{\n.reg .pred p;\nmbarrier.try_wait.parity.shared::cta.b64 p, [%1], %2;\nselp.u32 %0, 1, 0, p;\n}"
               : "=r"(ok) : "r"(a), "r"(ph) : "memory");
  return ok;
}
__device__ __noinline__ void wait_timeout() { __trap(); }
__device__ __forceinline__ void mbar_wait(uint32_t a, uint32_t ph) {
  if (mbar_try(a, ph)) return;
  uint32_t it = 0;
  while (!mbar_try(a, ph)) if (++it > (1u << 22)) wait_timeout();
}
__device__ __forceinline__ void tma2d(uint32_t dst, const CUtensorMap* m, int c0, int c1, uint32_t bar) {
  asm volatile("cp.async.bulk.tensor.2d.shared::cluster.global.mbarrier::complete_tx::bytes [%0], [%1, {%3, %4}], [%2];"
               ::"r"(dst), "l"(m), "r"(bar), "r"(c0), "r"(c1) : "memory");
}
__device__ __forceinline__ void tma2d_mc(uint32_t dst, const CUtensorMap* m, int c0, int c1, uint32_t bar) {
  asm volatile("cp.async.bulk.tensor.2d.shared::cluster.global.mbarrier::complete_tx::bytes.multicast::cluster "
               "[%0], [%1, {%3, %4}], [%2], %5;"
               ::"r"(dst), "l"(m), "r"(bar), "r"(c0), "r"(c1), "h"((uint16_t)3) : "memory");
}
__device__ __forceinline__ void bulk_ld(uint32_t dst, const void* src, uint32_t bytes, uint32_t bar) {
  asm volatile("cp.async.bulk.shared::cluster.global.mbarrier::complete_tx::bytes [%0], [%1], %2, [%3];"
               ::"r"(dst), "l"(src), "r"(bytes), "r"(bar) : "memory");
}
__device__ __forceinline__ void bulk_ld_mc(uint32_t dst, const void* src, uint32_t bytes, uint32_t bar) {
  asm volatile("cp.async.bulk.shared::cluster.global.mbarrier::complete_tx::bytes.multicast::cluster "
               "[%0], [%1], %2, [%3], %4;"
               ::"r"(dst), "l"(src), "r"(bytes), "r"(bar), "h"((uint16_t)3) : "memory");
}
__device__ __forceinline__ void cluster_arrive() { asm volatile("barrier.cluster.arrive.relaxed.aligned;" ::: "memory"); }
__device__ __forceinline__ void cluster_wait() { asm volatile("barrier.cluster.wait.aligned;" ::: "memory"); }
__device__ __forceinline__ void bulk_st(void* dst, uint32_t src, uint32_t bytes) {
  asm volatile("cp.async.bulk.global.shared::cta.bulk_group [%0], [%1], %2;" ::"l"(dst), "r"(src), "r"(bytes) : "memory");
}
__device__ __forceinline__ void tma2d_st(const CUtensorMap* m, int c0, int c1, uint32_t src) {
  asm volatile("cp.async.bulk.tensor.2d.global.shared::cta.bulk_group [%0, {%2, %3}], [%1];"
               ::"l"(m), "r"(src), "r"(c0), "r"(c1) : "memory");
}
__device__ __forceinline__ void bulk_commit_wait() {
  asm volatile("cp.async.bulk.commit_group;\ncp.async.bulk.wait_group.read 0;" ::: "memory");
}
__device__ __forceinline__ uint32_t mapa(uint32_t a, uint32_t cta) {
  uint32_t r;
  asm("mapa.shared::cluster.u32 %0, %1, %2;" : "=r"(r) : "r"(a), "r"(cta));
  return r;
}
__device__ __forceinline__ void st_async4(uint32_t dst, float a, float b, float c, float d, uint32_t bar) {
  asm volatile("st.async.shared::cluster.mbarrier::complete_tx::bytes.v4.f32 [%0], {%1, %2, %3, %4}, [%5];"
               ::"r"(dst), "f"(a), "f"(b), "f"(c), "f"(d), "r"(bar) : "memory");
}
__device__ __forceinline__ void st_async4u(uint32_t dst, uint32_t a, uint32_t b, uint32_t c, uint32_t d, uint32_t bar) {
  asm volatile("st.async.shared::cluster.mbarrier::complete_tx::bytes.v4.b32 [%0], {%1, %2, %3, %4}, [%5];"
               ::"r"(dst), "r"(a), "r"(b), "r"(c), "r"(d), "r"(bar) : "memory");
}
#define SEND8(dst, a, o, bar) st_async4u(dst, pack_bf16(a[o], a[(o) + 1]), pack_bf16(a[(o) + 2], a[(o) + 3]), \
                                         pack_bf16(a[(o) + 4], a[(o) + 5]), pack_bf16(a[(o) + 6], a[(o) + 7]), bar)
__device__ __forceinline__ void fence_async() { asm volatile("fence.proxy.async.shared::cta;" ::: "memory"); }
__device__ __forceinline__ void prefetch_map(const CUtensorMap* m) {
  asm volatile("prefetch.tensormap [%0];" ::"l"(m) : "memory");
}
__device__ __forceinline__ bool elect_one() {
  uint32_t p;
  asm volatile("{\n.reg .pred q;\nelect.sync _|q, 0xffffffff;\nselp.u32 %0, 1, 0, q;\n}" : "=r"(p));
  return p;
}
__device__ __forceinline__ void pdl_wait() { asm volatile("griddepcontrol.wait;" ::: "memory"); }
__device__ __forceinline__ void pdl_trigger() { asm volatile("griddepcontrol.launch_dependents;" ::: "memory"); }
__device__ __forceinline__ void bar_sync(int id, int n) { asm volatile("bar.sync %0, %1;" ::"r"(id), "r"(n) : "memory"); }
__device__ __forceinline__ void bar_arrive(int id, int n) { asm volatile("bar.arrive %0, %1;" ::"r"(id), "r"(n) : "memory"); }
#define WG_FENCE() asm volatile("wgmma.fence.sync.aligned;" ::: "memory")
#define WG_COMMIT() asm volatile("wgmma.commit_group.sync.aligned;" ::: "memory")
#define WG_WAIT(n) asm volatile("wgmma.wait_group.sync.aligned %0;" ::"n"(n) : "memory")
__device__ __forceinline__ uint64_t mkdesc(uint32_t addr, uint32_t lbo, uint32_t sbo, uint32_t sw) {
  return (uint64_t)((addr & 0x3FFFF) >> 4) | ((uint64_t)(lbo >> 4) << 16) | ((uint64_t)(sbo >> 4) << 32) |
         ((uint64_t)sw << 62);
}
template <int N> __device__ __forceinline__ void fence_regs(float (&r)[N]) {
#pragma unroll
  for (int i = 0; i < N; i++) asm volatile("" : "+f"(r[i])::"memory");
}
__device__ __forceinline__ uint32_t pack_bf16(float lo, float hi) {
  uint32_t r;
  asm("cvt.rn.bf16x2.f32 %0, %1, %2;" : "=r"(r) : "f"(hi), "f"(lo));
  return r;
}
__device__ __forceinline__ float bf_lo(uint32_t v) { return __uint_as_float(v << 16); }
__device__ __forceinline__ float bf_hi(uint32_t v) { return __uint_as_float(v & 0xffff0000u); }
__device__ __forceinline__ float ex2(float x) {
  float y;
  asm("ex2.approx.ftz.f32 %0, %1;" : "=f"(y) : "f"(x));
  return y;
}
__device__ __forceinline__ uint4 ldg_nc(const void* p) {
  uint4 v;
  asm volatile("ld.global.nc.L1::no_allocate.v4.u32 {%0, %1, %2, %3}, [%4];"
               : "=r"(v.x), "=r"(v.y), "=r"(v.z), "=r"(v.w) : "l"(p));
  return v;
}

__device__ __forceinline__ uint4 ld_relaxed(const uint4* p) {
  uint64_t a, b;
  asm volatile("ld.relaxed.gpu.global.v2.u64 {%0, %1}, [%2];" : "=l"(a), "=l"(b) : "l"(p) : "memory");
  return make_uint4((uint32_t)a, (uint32_t)(a >> 32), (uint32_t)b, (uint32_t)(b >> 32));
}
__device__ __forceinline__ void st_relaxed(uint4* p, float x, float y, uint32_t tag) {
  const uint64_t a = ((uint64_t)tag << 32) | __float_as_uint(x), b = ((uint64_t)tag << 32) | __float_as_uint(y);
  asm volatile("st.relaxed.gpu.global.v2.u64 [%0], {%1, %2};" ::"l"(p), "l"(a), "l"(b) : "memory");
}
__device__ __forceinline__ void tma4d(uint32_t dst, const CUtensorMap* m, int c2, int c3, uint32_t bar) {
  asm volatile("cp.async.bulk.tensor.4d.shared::cluster.global.mbarrier::complete_tx::bytes [%0], [%1, {%3, %3, %4, %5}], [%2];"
               ::"r"(dst), "l"(m), "r"(bar), "r"(0), "r"(c2), "r"(c3) : "memory");
}
#define ACC8(a, v) do { a[0] += bf_lo(v.x); a[1] += bf_hi(v.x); a[2] += bf_lo(v.y); a[3] += bf_hi(v.y); \
                        a[4] += bf_lo(v.z); a[5] += bf_hi(v.z); a[6] += bf_lo(v.w); a[7] += bf_hi(v.w); } while (0)

__device__ __forceinline__ void wgmma_ss_n224(float (&d)[112], uint64_t da, uint64_t db, int sd) {
  asm volatile("{\n.reg .pred p;\nsetp.ne.b32 p, %114, 0;\n"
      "wgmma.mma_async.sync.aligned.m64n224k16.f32.bf16.bf16 {"
      "%0, %1, %2, %3, %4, %5, %6, %7, %8, %9, %10, %11, %12, %13, %14, %15, "
      "%16, %17, %18, %19, %20, %21, %22, %23, %24, %25, %26, %27, %28, %29, %30, %31, "
      "%32, %33, %34, %35, %36, %37, %38, %39, %40, %41, %42, %43, %44, %45, %46, %47, "
      "%48, %49, %50, %51, %52, %53, %54, %55, %56, %57, %58, %59, %60, %61, %62, %63, "
      "%64, %65, %66, %67, %68, %69, %70, %71, %72, %73, %74, %75, %76, %77, %78, %79, "
      "%80, %81, %82, %83, %84, %85, %86, %87, %88, %89, %90, %91, %92, %93, %94, %95, "
      "%96, %97, %98, %99, %100, %101, %102, %103, %104, %105, %106, %107, %108, %109, %110, %111"
      "}, %112, %113, p, 1, 1, 0, 1;\n}\n"
    : "+f"(d[0]), "+f"(d[1]), "+f"(d[2]), "+f"(d[3]), "+f"(d[4]), "+f"(d[5]), "+f"(d[6]), "+f"(d[7]),
      "+f"(d[8]), "+f"(d[9]), "+f"(d[10]), "+f"(d[11]), "+f"(d[12]), "+f"(d[13]), "+f"(d[14]), "+f"(d[15]),
      "+f"(d[16]), "+f"(d[17]), "+f"(d[18]), "+f"(d[19]), "+f"(d[20]), "+f"(d[21]), "+f"(d[22]), "+f"(d[23]),
      "+f"(d[24]), "+f"(d[25]), "+f"(d[26]), "+f"(d[27]), "+f"(d[28]), "+f"(d[29]), "+f"(d[30]), "+f"(d[31]),
      "+f"(d[32]), "+f"(d[33]), "+f"(d[34]), "+f"(d[35]), "+f"(d[36]), "+f"(d[37]), "+f"(d[38]), "+f"(d[39]),
      "+f"(d[40]), "+f"(d[41]), "+f"(d[42]), "+f"(d[43]), "+f"(d[44]), "+f"(d[45]), "+f"(d[46]), "+f"(d[47]),
      "+f"(d[48]), "+f"(d[49]), "+f"(d[50]), "+f"(d[51]), "+f"(d[52]), "+f"(d[53]), "+f"(d[54]), "+f"(d[55]),
      "+f"(d[56]), "+f"(d[57]), "+f"(d[58]), "+f"(d[59]), "+f"(d[60]), "+f"(d[61]), "+f"(d[62]), "+f"(d[63]),
      "+f"(d[64]), "+f"(d[65]), "+f"(d[66]), "+f"(d[67]), "+f"(d[68]), "+f"(d[69]), "+f"(d[70]), "+f"(d[71]),
      "+f"(d[72]), "+f"(d[73]), "+f"(d[74]), "+f"(d[75]), "+f"(d[76]), "+f"(d[77]), "+f"(d[78]), "+f"(d[79]),
      "+f"(d[80]), "+f"(d[81]), "+f"(d[82]), "+f"(d[83]), "+f"(d[84]), "+f"(d[85]), "+f"(d[86]), "+f"(d[87]),
      "+f"(d[88]), "+f"(d[89]), "+f"(d[90]), "+f"(d[91]), "+f"(d[92]), "+f"(d[93]), "+f"(d[94]), "+f"(d[95]),
      "+f"(d[96]), "+f"(d[97]), "+f"(d[98]), "+f"(d[99]), "+f"(d[100]), "+f"(d[101]), "+f"(d[102]), "+f"(d[103]),
      "+f"(d[104]), "+f"(d[105]), "+f"(d[106]), "+f"(d[107]), "+f"(d[108]), "+f"(d[109]), "+f"(d[110]), "+f"(d[111])
    : "l"(da), "l"(db), "r"(sd));
}
__device__ __forceinline__ void wgmma_ss_n208(float (&d)[104], uint64_t da, uint64_t db, int sd) {
  asm volatile("{\n.reg .pred p;\nsetp.ne.b32 p, %106, 0;\n"
      "wgmma.mma_async.sync.aligned.m64n208k16.f32.bf16.bf16 {"
      "%0, %1, %2, %3, %4, %5, %6, %7, %8, %9, %10, %11, %12, %13, %14, %15, "
      "%16, %17, %18, %19, %20, %21, %22, %23, %24, %25, %26, %27, %28, %29, %30, %31, "
      "%32, %33, %34, %35, %36, %37, %38, %39, %40, %41, %42, %43, %44, %45, %46, %47, "
      "%48, %49, %50, %51, %52, %53, %54, %55, %56, %57, %58, %59, %60, %61, %62, %63, "
      "%64, %65, %66, %67, %68, %69, %70, %71, %72, %73, %74, %75, %76, %77, %78, %79, "
      "%80, %81, %82, %83, %84, %85, %86, %87, %88, %89, %90, %91, %92, %93, %94, %95, "
      "%96, %97, %98, %99, %100, %101, %102, %103"
      "}, %104, %105, p, 1, 1, 0, 1;\n}\n"
    : "+f"(d[0]), "+f"(d[1]), "+f"(d[2]), "+f"(d[3]), "+f"(d[4]), "+f"(d[5]), "+f"(d[6]), "+f"(d[7]),
      "+f"(d[8]), "+f"(d[9]), "+f"(d[10]), "+f"(d[11]), "+f"(d[12]), "+f"(d[13]), "+f"(d[14]), "+f"(d[15]),
      "+f"(d[16]), "+f"(d[17]), "+f"(d[18]), "+f"(d[19]), "+f"(d[20]), "+f"(d[21]), "+f"(d[22]), "+f"(d[23]),
      "+f"(d[24]), "+f"(d[25]), "+f"(d[26]), "+f"(d[27]), "+f"(d[28]), "+f"(d[29]), "+f"(d[30]), "+f"(d[31]),
      "+f"(d[32]), "+f"(d[33]), "+f"(d[34]), "+f"(d[35]), "+f"(d[36]), "+f"(d[37]), "+f"(d[38]), "+f"(d[39]),
      "+f"(d[40]), "+f"(d[41]), "+f"(d[42]), "+f"(d[43]), "+f"(d[44]), "+f"(d[45]), "+f"(d[46]), "+f"(d[47]),
      "+f"(d[48]), "+f"(d[49]), "+f"(d[50]), "+f"(d[51]), "+f"(d[52]), "+f"(d[53]), "+f"(d[54]), "+f"(d[55]),
      "+f"(d[56]), "+f"(d[57]), "+f"(d[58]), "+f"(d[59]), "+f"(d[60]), "+f"(d[61]), "+f"(d[62]), "+f"(d[63]),
      "+f"(d[64]), "+f"(d[65]), "+f"(d[66]), "+f"(d[67]), "+f"(d[68]), "+f"(d[69]), "+f"(d[70]), "+f"(d[71]),
      "+f"(d[72]), "+f"(d[73]), "+f"(d[74]), "+f"(d[75]), "+f"(d[76]), "+f"(d[77]), "+f"(d[78]), "+f"(d[79]),
      "+f"(d[80]), "+f"(d[81]), "+f"(d[82]), "+f"(d[83]), "+f"(d[84]), "+f"(d[85]), "+f"(d[86]), "+f"(d[87]),
      "+f"(d[88]), "+f"(d[89]), "+f"(d[90]), "+f"(d[91]), "+f"(d[92]), "+f"(d[93]), "+f"(d[94]), "+f"(d[95]),
      "+f"(d[96]), "+f"(d[97]), "+f"(d[98]), "+f"(d[99]), "+f"(d[100]), "+f"(d[101]), "+f"(d[102]), "+f"(d[103])
    : "l"(da), "l"(db), "r"(sd));
}
__device__ __forceinline__ void wgmma_ss_n168(float (&d)[84], uint64_t da, uint64_t db, int sd) {
  asm volatile("{\n.reg .pred p;\nsetp.ne.b32 p, %86, 0;\n"
      "wgmma.mma_async.sync.aligned.m64n168k16.f32.bf16.bf16 {"
      "%0, %1, %2, %3, %4, %5, %6, %7, %8, %9, %10, %11, %12, %13, %14, %15, "
      "%16, %17, %18, %19, %20, %21, %22, %23, %24, %25, %26, %27, %28, %29, %30, %31, "
      "%32, %33, %34, %35, %36, %37, %38, %39, %40, %41, %42, %43, %44, %45, %46, %47, "
      "%48, %49, %50, %51, %52, %53, %54, %55, %56, %57, %58, %59, %60, %61, %62, %63, "
      "%64, %65, %66, %67, %68, %69, %70, %71, %72, %73, %74, %75, %76, %77, %78, %79, "
      "%80, %81, %82, %83"
      "}, %84, %85, p, 1, 1, 0, 1;\n}\n"
    : "+f"(d[0]), "+f"(d[1]), "+f"(d[2]), "+f"(d[3]), "+f"(d[4]), "+f"(d[5]), "+f"(d[6]), "+f"(d[7]),
      "+f"(d[8]), "+f"(d[9]), "+f"(d[10]), "+f"(d[11]), "+f"(d[12]), "+f"(d[13]), "+f"(d[14]), "+f"(d[15]),
      "+f"(d[16]), "+f"(d[17]), "+f"(d[18]), "+f"(d[19]), "+f"(d[20]), "+f"(d[21]), "+f"(d[22]), "+f"(d[23]),
      "+f"(d[24]), "+f"(d[25]), "+f"(d[26]), "+f"(d[27]), "+f"(d[28]), "+f"(d[29]), "+f"(d[30]), "+f"(d[31]),
      "+f"(d[32]), "+f"(d[33]), "+f"(d[34]), "+f"(d[35]), "+f"(d[36]), "+f"(d[37]), "+f"(d[38]), "+f"(d[39]),
      "+f"(d[40]), "+f"(d[41]), "+f"(d[42]), "+f"(d[43]), "+f"(d[44]), "+f"(d[45]), "+f"(d[46]), "+f"(d[47]),
      "+f"(d[48]), "+f"(d[49]), "+f"(d[50]), "+f"(d[51]), "+f"(d[52]), "+f"(d[53]), "+f"(d[54]), "+f"(d[55]),
      "+f"(d[56]), "+f"(d[57]), "+f"(d[58]), "+f"(d[59]), "+f"(d[60]), "+f"(d[61]), "+f"(d[62]), "+f"(d[63]),
      "+f"(d[64]), "+f"(d[65]), "+f"(d[66]), "+f"(d[67]), "+f"(d[68]), "+f"(d[69]), "+f"(d[70]), "+f"(d[71]),
      "+f"(d[72]), "+f"(d[73]), "+f"(d[74]), "+f"(d[75]), "+f"(d[76]), "+f"(d[77]), "+f"(d[78]), "+f"(d[79]),
      "+f"(d[80]), "+f"(d[81]), "+f"(d[82]), "+f"(d[83])
    : "l"(da), "l"(db), "r"(sd));
}
__device__ __forceinline__ void wgmma_ss_n160(float (&d)[80], uint64_t da, uint64_t db, int sd) {
  asm volatile("{\n.reg .pred p;\nsetp.ne.b32 p, %82, 0;\n"
      "wgmma.mma_async.sync.aligned.m64n160k16.f32.bf16.bf16 {"
      "%0, %1, %2, %3, %4, %5, %6, %7, %8, %9, %10, %11, %12, %13, %14, %15, "
      "%16, %17, %18, %19, %20, %21, %22, %23, %24, %25, %26, %27, %28, %29, %30, %31, "
      "%32, %33, %34, %35, %36, %37, %38, %39, %40, %41, %42, %43, %44, %45, %46, %47, "
      "%48, %49, %50, %51, %52, %53, %54, %55, %56, %57, %58, %59, %60, %61, %62, %63, "
      "%64, %65, %66, %67, %68, %69, %70, %71, %72, %73, %74, %75, %76, %77, %78, %79"
      "}, %80, %81, p, 1, 1, 0, 1;\n}\n"
    : "+f"(d[0]), "+f"(d[1]), "+f"(d[2]), "+f"(d[3]), "+f"(d[4]), "+f"(d[5]), "+f"(d[6]), "+f"(d[7]),
      "+f"(d[8]), "+f"(d[9]), "+f"(d[10]), "+f"(d[11]), "+f"(d[12]), "+f"(d[13]), "+f"(d[14]), "+f"(d[15]),
      "+f"(d[16]), "+f"(d[17]), "+f"(d[18]), "+f"(d[19]), "+f"(d[20]), "+f"(d[21]), "+f"(d[22]), "+f"(d[23]),
      "+f"(d[24]), "+f"(d[25]), "+f"(d[26]), "+f"(d[27]), "+f"(d[28]), "+f"(d[29]), "+f"(d[30]), "+f"(d[31]),
      "+f"(d[32]), "+f"(d[33]), "+f"(d[34]), "+f"(d[35]), "+f"(d[36]), "+f"(d[37]), "+f"(d[38]), "+f"(d[39]),
      "+f"(d[40]), "+f"(d[41]), "+f"(d[42]), "+f"(d[43]), "+f"(d[44]), "+f"(d[45]), "+f"(d[46]), "+f"(d[47]),
      "+f"(d[48]), "+f"(d[49]), "+f"(d[50]), "+f"(d[51]), "+f"(d[52]), "+f"(d[53]), "+f"(d[54]), "+f"(d[55]),
      "+f"(d[56]), "+f"(d[57]), "+f"(d[58]), "+f"(d[59]), "+f"(d[60]), "+f"(d[61]), "+f"(d[62]), "+f"(d[63]),
      "+f"(d[64]), "+f"(d[65]), "+f"(d[66]), "+f"(d[67]), "+f"(d[68]), "+f"(d[69]), "+f"(d[70]), "+f"(d[71]),
      "+f"(d[72]), "+f"(d[73]), "+f"(d[74]), "+f"(d[75]), "+f"(d[76]), "+f"(d[77]), "+f"(d[78]), "+f"(d[79])
    : "l"(da), "l"(db), "r"(sd));
}
__device__ __forceinline__ void wgmma_ss_n88(float (&d)[44], uint64_t da, uint64_t db, int sd) {
  asm volatile("{\n.reg .pred p;\nsetp.ne.b32 p, %46, 0;\n"
      "wgmma.mma_async.sync.aligned.m64n88k16.f32.bf16.bf16 {"
      "%0, %1, %2, %3, %4, %5, %6, %7, %8, %9, %10, %11, %12, %13, %14, %15, "
      "%16, %17, %18, %19, %20, %21, %22, %23, %24, %25, %26, %27, %28, %29, %30, %31, "
      "%32, %33, %34, %35, %36, %37, %38, %39, %40, %41, %42, %43"
      "}, %44, %45, p, 1, 1, 0, 1;\n}\n"
    : "+f"(d[0]), "+f"(d[1]), "+f"(d[2]), "+f"(d[3]), "+f"(d[4]), "+f"(d[5]), "+f"(d[6]), "+f"(d[7]),
      "+f"(d[8]), "+f"(d[9]), "+f"(d[10]), "+f"(d[11]), "+f"(d[12]), "+f"(d[13]), "+f"(d[14]), "+f"(d[15]),
      "+f"(d[16]), "+f"(d[17]), "+f"(d[18]), "+f"(d[19]), "+f"(d[20]), "+f"(d[21]), "+f"(d[22]), "+f"(d[23]),
      "+f"(d[24]), "+f"(d[25]), "+f"(d[26]), "+f"(d[27]), "+f"(d[28]), "+f"(d[29]), "+f"(d[30]), "+f"(d[31]),
      "+f"(d[32]), "+f"(d[33]), "+f"(d[34]), "+f"(d[35]), "+f"(d[36]), "+f"(d[37]), "+f"(d[38]), "+f"(d[39]),
      "+f"(d[40]), "+f"(d[41]), "+f"(d[42]), "+f"(d[43])
    : "l"(da), "l"(db), "r"(sd));
}
__device__ __forceinline__ void wgmma_ss_n80(float (&d)[40], uint64_t da, uint64_t db, int sd) {
  asm volatile("{\n.reg .pred p;\nsetp.ne.b32 p, %42, 0;\n"
      "wgmma.mma_async.sync.aligned.m64n80k16.f32.bf16.bf16 {"
      "%0, %1, %2, %3, %4, %5, %6, %7, %8, %9, %10, %11, %12, %13, %14, %15, "
      "%16, %17, %18, %19, %20, %21, %22, %23, %24, %25, %26, %27, %28, %29, %30, %31, "
      "%32, %33, %34, %35, %36, %37, %38, %39"
      "}, %40, %41, p, 1, 1, 0, 1;\n}\n"
    : "+f"(d[0]), "+f"(d[1]), "+f"(d[2]), "+f"(d[3]), "+f"(d[4]), "+f"(d[5]), "+f"(d[6]), "+f"(d[7]),
      "+f"(d[8]), "+f"(d[9]), "+f"(d[10]), "+f"(d[11]), "+f"(d[12]), "+f"(d[13]), "+f"(d[14]), "+f"(d[15]),
      "+f"(d[16]), "+f"(d[17]), "+f"(d[18]), "+f"(d[19]), "+f"(d[20]), "+f"(d[21]), "+f"(d[22]), "+f"(d[23]),
      "+f"(d[24]), "+f"(d[25]), "+f"(d[26]), "+f"(d[27]), "+f"(d[28]), "+f"(d[29]), "+f"(d[30]), "+f"(d[31]),
      "+f"(d[32]), "+f"(d[33]), "+f"(d[34]), "+f"(d[35]), "+f"(d[36]), "+f"(d[37]), "+f"(d[38]), "+f"(d[39])
    : "l"(da), "l"(db), "r"(sd));
}
__device__ __forceinline__ void wgmma_rs_n128(float (&d)[64], uint32_t a0, uint32_t a1, uint32_t a2, uint32_t a3,
                                  uint64_t db, int sd) {
  asm volatile("{\n.reg .pred p;\nsetp.ne.b32 p, %69, 0;\n"
      "wgmma.mma_async.sync.aligned.m64n128k16.f32.bf16.bf16 {"
      "%0, %1, %2, %3, %4, %5, %6, %7, %8, %9, %10, %11, %12, %13, %14, %15, "
      "%16, %17, %18, %19, %20, %21, %22, %23, %24, %25, %26, %27, %28, %29, %30, %31, "
      "%32, %33, %34, %35, %36, %37, %38, %39, %40, %41, %42, %43, %44, %45, %46, %47, "
      "%48, %49, %50, %51, %52, %53, %54, %55, %56, %57, %58, %59, %60, %61, %62, %63"
      "}, {%64, %65, %66, %67}, %68, p, 1, 1, 0;\n}\n"
    : "+f"(d[0]), "+f"(d[1]), "+f"(d[2]), "+f"(d[3]), "+f"(d[4]), "+f"(d[5]), "+f"(d[6]), "+f"(d[7]),
      "+f"(d[8]), "+f"(d[9]), "+f"(d[10]), "+f"(d[11]), "+f"(d[12]), "+f"(d[13]), "+f"(d[14]), "+f"(d[15]),
      "+f"(d[16]), "+f"(d[17]), "+f"(d[18]), "+f"(d[19]), "+f"(d[20]), "+f"(d[21]), "+f"(d[22]), "+f"(d[23]),
      "+f"(d[24]), "+f"(d[25]), "+f"(d[26]), "+f"(d[27]), "+f"(d[28]), "+f"(d[29]), "+f"(d[30]), "+f"(d[31]),
      "+f"(d[32]), "+f"(d[33]), "+f"(d[34]), "+f"(d[35]), "+f"(d[36]), "+f"(d[37]), "+f"(d[38]), "+f"(d[39]),
      "+f"(d[40]), "+f"(d[41]), "+f"(d[42]), "+f"(d[43]), "+f"(d[44]), "+f"(d[45]), "+f"(d[46]), "+f"(d[47]),
      "+f"(d[48]), "+f"(d[49]), "+f"(d[50]), "+f"(d[51]), "+f"(d[52]), "+f"(d[53]), "+f"(d[54]), "+f"(d[55]),
      "+f"(d[56]), "+f"(d[57]), "+f"(d[58]), "+f"(d[59]), "+f"(d[60]), "+f"(d[61]), "+f"(d[62]), "+f"(d[63])
    : "r"(a0), "r"(a1), "r"(a2), "r"(a3), "l"(db), "r"(sd));
}
__device__ __forceinline__ void wgmma_rs_n24(float (&d)[12], uint32_t a0, uint32_t a1, uint32_t a2, uint32_t a3,
                                  uint64_t db, int sd) {
  asm volatile("{\n.reg .pred p;\nsetp.ne.b32 p, %17, 0;\n"
      "wgmma.mma_async.sync.aligned.m64n24k16.f32.bf16.bf16 {"
      "%0, %1, %2, %3, %4, %5, %6, %7, %8, %9, %10, %11"
      "}, {%12, %13, %14, %15}, %16, p, 1, 1, 1;\n}\n"
    : "+f"(d[0]), "+f"(d[1]), "+f"(d[2]), "+f"(d[3]), "+f"(d[4]), "+f"(d[5]), "+f"(d[6]), "+f"(d[7]),
      "+f"(d[8]), "+f"(d[9]), "+f"(d[10]), "+f"(d[11])
    : "r"(a0), "r"(a1), "r"(a2), "r"(a3), "l"(db), "r"(sd));
}

constexpr int KST = 4;
constexpr int K1_ST = 4, K1_STAGE = 45056;
constexpr int K1_SMEM = K1_ST * K1_STAGE + 640   + 1536   + 2560   + 128;

__device__ __forceinline__ float2 row_stats(uint4 v0, uint4 v1, uint4 v2) {
  const uint32_t wd[12] = {v0.x, v0.y, v0.z, v0.w, v1.x, v1.y, v1.z, v1.w, v2.x, v2.y, v2.z, v2.w};
  float sx = 0.f, sq = 0.f;
#pragma unroll
  for (int e = 0; e < 12; e++) {
    const float lo = bf_lo(wd[e]), hi = bf_hi(wd[e]);
    sx += lo + hi; sq = fmaf(lo, lo, fmaf(hi, hi, sq));
  }
#pragma unroll
  for (int o = 16; o; o >>= 1) { sx += __shfl_xor_sync(~0u, sx, o); sq += __shfl_xor_sync(~0u, sq, o); }
  const float mean = sx * (1.f / D_);
  return make_float2(rsqrtf(fmaxf(sq * (1.f / D_) - mean * mean, 0.f) + 1e-5f), mean);
}

__global__ void __cluster_dims__(2, 1, 1) __launch_bounds__(512, 1)
k1_qkv(const __grid_constant__ CUtensorMap tmx, const __grid_constant__ CUtensorMap tmw,
       const bf16* __restrict__ x, const bf16* __restrict__ w) {
  extern __shared__ __align__(1024) uint8_t sm[];
  float* cs = (float*)(sm + K1_ST * K1_STAGE);
  float2* rowab = (float2*)(sm + K1_ST * K1_STAGE + 640);
  float* red = (float*)(sm + K1_ST * K1_STAGE + 2176);
  const uint32_t sbase = smem_u32(sm);
  const uint32_t fullb = sbase + K1_ST * K1_STAGE + 4736, emptyb = fullb + 8 * K1_ST;
  const int tid = threadIdx.x, lane = tid & 31;
  const int warp = __shfl_sync(~0u, tid >> 5, 0);
  const int rank = blockIdx.x & 1, cl = blockIdx.x >> 1;
  const int m = cl / 6, n = (cl - m * 6) * 2 + rank;

  if (warp == 12) {
    if (lane == 0) {
      prefetch_map(&tmx); prefetch_map(&tmw);
      for (int i = 0; i < K1_ST; i++) { mbar_init(fullb + 8 * i, 1); mbar_init(emptyb + 8 * i, 6); }
      asm volatile("fence.mbarrier_init.release.cluster;" ::: "memory");
    }
    __syncwarp();
    cluster_arrive();
    bar_arrive(4, 512);
    if (elect_one()) {
#pragma unroll
      for (int kt = 1; kt < K1_ST; kt++) mbar_expect(fullb + 8 * kt, K1_STAGE);
      tma2d(sbase + K1_STAGE, &tmx, 64, m * 192, fullb + 8);
      tma2d(sbase + K1_STAGE + 12288, &tmx, 64, m * 192 + 96, fullb + 8);
#pragma unroll
      for (int j = 0; j < 5; j++) tma2d(sbase + K1_STAGE + 24576 + j * 4096, &tmw, n * 160 + j * 32, 64, fullb + 8);
    }
    cluster_wait();
#pragma unroll 1
    for (int kt = 2; kt < 10; kt++) {
      const int s = kt % K1_ST;
      const uint32_t sa = sbase + s * K1_STAGE;
      if (kt >= K1_ST) mbar_wait(emptyb + 8 * s, ((kt / K1_ST) - 1) & 1);
      if (elect_one()) {
        if (kt >= K1_ST) mbar_expect(fullb + 8 * s, K1_STAGE);
        tma2d_mc(sa + rank * 12288, &tmx, kt * 64, m * 192 + rank * 96, fullb + 8 * s);
#pragma unroll
        for (int j = 0; j < 5; j++) tma2d(sa + 24576 + j * 4096, &tmw, n * 160 + j * 32, kt * 64, fullb + 8 * s);
      }
      if (kt == K1_ST - 1) pdl_trigger();
    }
    __syncwarp();
    cluster_arrive();
  } else if (warp > 12) {
    cluster_arrive();
    const int t96 = tid - 416;
    const uint32_t tag = __ldcg(&g_epoch) + 1;
    bar_sync(4, 512);
    mbar_wait(fullb + 8, 0);
    if (m < 10) {
      const int ck = t96 % 20, rg = min(t96 / 20, 3);
      uint4 wv[16];
#pragma unroll
      for (int i = 0; i < 16; i++) wv[i] = ldg_nc(w + (size_t)(m * 64 + rg * 16 + i) * 1920 + n * 160 + ck * 8);
      float acc8[8];
#pragma unroll
      for (int i = 0; i < 8; i++) acc8[i] = 0.f;
#pragma unroll
      for (int i = 0; i < 16; i++) ACC8(acc8, wv[i]);
      *(float4*)&red[rg * 160 + ck * 8] = make_float4(acc8[0], acc8[1], acc8[2], acc8[3]);
      *(float4*)&red[rg * 160 + ck * 8 + 4] = make_float4(acc8[4], acc8[5], acc8[6], acc8[7]);
      bar_sync(1, 96);
      if (t96 < 80) {
        const float2 p0 = *(const float2*)&red[t96 * 2], p1 = *(const float2*)&red[160 + t96 * 2];
        const float2 p2 = *(const float2*)&red[320 + t96 * 2], p3 = *(const float2*)&red[480 + t96 * 2];
        st_relaxed(&g_cpart[(m * 12 + n) * 80 + t96], (p0.x + p1.x) + (p2.x + p3.x), (p0.y + p1.y) + (p2.y + p3.y), tag);
      }
    }
    bool ok = false;
    for (int it = 0; it < 64 && !ok; it++) {
      uint4 p[10], st[2];
#pragma unroll
      for (int k = 0; k < 10; k++) p[k] = ld_relaxed(&g_cpart[(k * 12 + n) * 80 + min(t96, 79)]);
#pragma unroll
      for (int k = 0; k < 2; k++) st[k] = ld_relaxed(&g_rowstat[min(m * 192 + k * 96 + t96, S_ - 1)]);
      ok = true;
      float s0 = 0.f, s1 = 0.f;
#pragma unroll
      for (int k = 0; k < 10; k++) {
        ok = ok && p[k].y == tag && p[k].w == tag;
        s0 += __uint_as_float(p[k].x); s1 += __uint_as_float(p[k].z);
      }
      if (t96 < 80) *(float2*)&cs[t96 * 2] = make_float2(s0, s1);
#pragma unroll
      for (int k = 0; k < 2; k++) {
        ok = ok && st[k].y == tag && st[k].w == tag;
        rowab[k * 96 + t96] = make_float2(__uint_as_float(st[k].x), -__uint_as_float(st[k].x) * __uint_as_float(st[k].z));
      }
      ok = __all_sync(~0u, ok);
      if (!ok) __nanosleep(300);
    }
    if (!ok) {
      const int c2 = min(t96, 79);
      float s0 = 0.f, s1 = 0.f;
#pragma unroll 1
      for (int k = 0; k < D_; k++) {
        const uint32_t v = *(const uint32_t*)(w + (size_t)k * 1920 + n * 160 + c2 * 2);
        s0 += bf_lo(v); s1 += bf_hi(v);
      }
      if (t96 < 80) *(float2*)&cs[t96 * 2] = make_float2(s0, s1);
#pragma unroll 1
      for (int i = 0; i < 64; i++) {
        const int r = (i >> 5) * 96 + (t96 & ~31) + (i & 31);
        const bf16* xr = x + (size_t)min(m * 192 + r, S_ - 1) * D_ + lane * 8;
        const float2 st = row_stats(ldg_nc(xr), ldg_nc(xr + 256), lane < 16 ? ldg_nc(xr + 512) : make_uint4(0u, 0u, 0u, 0u));
        if (lane == 0) rowab[r] = make_float2(st.x, -st.x * st.y);
      }
    }
    __syncwarp();
    bar_arrive(2, 96 + 384);
    __syncwarp();
    cluster_wait();
    cluster_arrive();
  } else {
    cluster_arrive();
    {
      uint4 va[4], vb[4];
#pragma unroll
      for (int j = 0; j < 4; j++) {
        const int i = tid + 384 * j, ib = min(i, 1279);
        va[j] = ldg_nc(x + (size_t)min(m * 192 + (i >> 3), S_ - 1) * D_ + (i & 7) * 8);
        vb[j] = ldg_nc(w + (ib / 20) * 1920 + n * 160 + (ib % 20) * 8);
      }
#pragma unroll
      for (int j = 0; j < 4; j++) {
        const int i = tid + 384 * j, ib = min(i, 1279), r = ib / 20, ch = ib % 20;
        *(uint4*)(sm + (i >> 3) * 128 + (((i & 7) ^ ((i >> 3) & 7)) << 4)) = va[j];
        *(uint4*)(sm + 24576 + (ch >> 2) * 4096 + r * 64 + (((ch & 3) ^ ((r >> 1) & 3)) << 4)) = vb[j];
      }
      fence_async();
      bar_sync(3, 384);
    }
    float acc[80];
    const uint64_t da0 = mkdesc(sbase + (warp >> 2) * 8192, 16, 1024, 1);
    const uint64_t db0 = mkdesc(sbase + 24576, 4096, 512, 2);
    const uint32_t tag = __ldcg(&g_epoch) + 1;
    const int srow = m * 192 + n * 16 + warp * 2;
    const bool dostat = warp < 8 && srow < S_;
    uint4 xv[2][3];
    bar_sync(4, 512);
    cluster_wait();
#pragma unroll
    for (int kt = 0; kt < 10; kt++) {
      const int s = kt % K1_ST;
      if (kt > 0) mbar_wait(fullb + 8 * s, s == 0 ? ((kt / K1_ST) - 1) & 1 : (kt / K1_ST) & 1);
      const uint64_t da = da0 + s * (K1_STAGE >> 4), db = db0 + s * (K1_STAGE >> 4);
      WG_FENCE();
#pragma unroll
      for (int k = 0; k < 4; k++) wgmma_ss_n160(acc, da + k * 2, db + k * 64, (kt | k) != 0);
      WG_COMMIT();
      if (kt > 0) {
        WG_WAIT(1);
        if (kt - 1 + K1_ST < 10 && (tid & 127) < 2) mbar_arrive_cta(emptyb + 8 * ((kt - 1) % K1_ST), tid & 1);
      }
      if (kt == 1) {
#pragma unroll
        for (int i = 0; i < 2; i++) {
          const bf16* xr = x + (size_t)min(srow + i, S_ - 1) * D_ + lane * 8;
          xv[i][0] = xv[i][1] = xv[i][2] = make_uint4(0u, 0u, 0u, 0u);
          if (dostat) { xv[i][0] = ldg_nc(xr); xv[i][1] = ldg_nc(xr + 256); }
          if (dostat && lane < 16) xv[i][2] = ldg_nc(xr + 512);
        }
      }
      if ((kt == KST || kt == KST + 1) && dostat) {
        const float2 st = row_stats(xv[kt - KST][0], xv[kt - KST][1], xv[kt - KST][2]);
        if (lane == 0) st_relaxed(&g_rowstat[srow + kt - KST], st.x, st.y, tag);
      }
      __syncwarp();
    }
    cluster_arrive();
    WG_WAIT(0);
    fence_regs(acc);
    bar_sync(2, 96 + 384);
    const int row0 = m * 192 + warp * 16;
    if (row0 < S_) {
      const int g = lane >> 2, c = lane & 3, sec = n >> 2, grp = (row0 & 127) >> 3;
      const bool lo = c < 2;
      const float2 ab0 = rowab[warp * 16 + g], ab1 = rowab[warp * 16 + g + 8];
      const bool p0 = sec == 1 && ((POLY_MASK >> grp) & 1), p1 = sec == 1 && ((POLY_MASK >> (grp + 1)) & 1);
      const uint32_t padqv = sec == 0 ? (c == 2 ? 0x3F803F80u : 0x00003F80u) : (sec == 2 && c == 2 ? 0x00003F80u : 0u);
      const uint32_t padk = c == 2 ? 0x4A7A4B00u : 0x00004653u;
      const uint32_t pad0 = p0 ? padk : padqv, pad1 = p1 ? padk : padqv;
      const float f0 = sec == 0 ? QSCALE : (p0 ? 32768.f : 1.f), f1 = sec == 0 ? QSCALE : (p1 ? 32768.f : 1.f);
      const float a0 = ab0.x * f0, b0 = ab0.y * f0, a1 = ab1.x * f1, b1 = ab1.y * f1;
      const float r0 = p0 ? 9.313225746154785e-10f : 1.f, r1 = p1 ? 9.313225746154785e-10f : 1.f;
      const int cst = sec == 1 ? 2048 : 128, gst = sec == 1 ? 128 : 384;
      uint8_t* pe = (uint8_t*)g_qkv + (size_t)(n * 8) * HEAD_IMG + (row0 >> 7) * 6144 + grp * gst + lane * 4;
      uint8_t* pe1 = pe + cst;
      uint8_t* pe2 = pe1 + cst;
      uint8_t* pf = pe + gst;
      uint8_t* pf1 = pf + cst;
      uint8_t* pf2 = pf1 + cst;
      uint32_t u[20], v[20];
#pragma unroll
      for (int hp = 0; hp < 4; hp++) {
#pragma unroll
        for (int j = hp * 5; j < hp * 5 + 5; j++) {
          const float2 t = *(const float2*)&cs[j * 8 + c * 2];
          u[j] = pack_bf16(fmaf(acc[4 * j], a0, b0 * t.x), fmaf(acc[4 * j + 1], a0, b0 * t.y));
          v[j] = pack_bf16(fmaf(acc[4 * j + 2], a1, b1 * t.x), fmaf(acc[4 * j + 3], a1, b1 * t.y));
        }
        constexpr int HE = HEAD_IMG;
        const int oe = hp * 2 * HE, oo = oe + HE, j = hp * 5;
        *(uint32_t*)(pe + oe) = u[j];      *(uint32_t*)(pf + oe) = v[j];
        *(uint32_t*)(pe1 + oe) = u[j + 1]; *(uint32_t*)(pf1 + oe) = v[j + 1];
        *(uint32_t*)(pe2 + oe) = lo ? u[j + 2] : pad0; *(uint32_t*)(pf2 + oe) = lo ? v[j + 2] : pad1;
        *(uint32_t*)(pe + oo) = __shfl_xor_sync(~0u, lo ? u[j + 3] : u[j + 2], 2);
        *(uint32_t*)(pf + oo) = __shfl_xor_sync(~0u, lo ? v[j + 3] : v[j + 2], 2);
        *(uint32_t*)(pe1 + oo) = __shfl_xor_sync(~0u, lo ? u[j + 4] : u[j + 3], 2);
        *(uint32_t*)(pf1 + oo) = __shfl_xor_sync(~0u, lo ? v[j + 4] : v[j + 3], 2);
        const uint32_t tu = __shfl_xor_sync(~0u, u[j + 4], 2), tv = __shfl_xor_sync(~0u, v[j + 4], 2);
        *(uint32_t*)(pe2 + oo) = lo ? tu : pad0; *(uint32_t*)(pf2 + oo) = lo ? tv : pad1;
      }
      {
        float nm = 0.f;
#pragma unroll
        for (int hp = 0; hp < 4; hp++) {
          float sq[2][5];
#pragma unroll
          for (int i = 0; i < 5; i++) {
            const uint32_t x = u[hp * 5 + i], y = v[hp * 5 + i];
            sq[0][i] = fmaf(bf_lo(x), bf_lo(x), bf_hi(x) * bf_hi(x));
            sq[1][i] = fmaf(bf_lo(y), bf_lo(y), bf_hi(y) * bf_hi(y));
          }
          const float e0 = (sq[0][0] + sq[0][1] + (lo ? sq[0][2] : 0.f)) * r0, e1 = (sq[1][0] + sq[1][1] + (lo ? sq[1][2] : 0.f)) * r1;
          const float o0 = (sq[0][3] + sq[0][4] + (lo ? 0.f : sq[0][2])) * r0, o1 = (sq[1][3] + sq[1][4] + (lo ? 0.f : sq[1][2])) * r1;
          const float k0 = (lo ? e0 : o0) + __shfl_xor_sync(~0u, lo ? o0 : e0, 2);
          const float k1 = (lo ? e1 : o1) + __shfl_xor_sync(~0u, lo ? o1 : e1, 2);
          const float z = ((c & 1) ? k1 : k0) + __shfl_xor_sync(~0u, (c & 1) ? k0 : k1, 1);
          const uint32_t em = __reduce_max_sync(~0u, lo ? __float_as_uint(z) : 0u), om = __reduce_max_sync(~0u, lo ? 0u : __float_as_uint(z));
          if ((lane >> 1) == hp) nm = __uint_as_float((lane & 1) ? om : em);
        }
        if (lane < 8) g_nrm[(n * 8 + lane) * 128 + (row0 >> 4)] = nm;
      }
    }
  }
  cluster_wait();
}

constexpr int K2_SMEM = 2 * HEAD_IMG + 2 * 6144 + 2 * 10240 + 160 + 96;

__device__ __forceinline__ uint64_t desc64(uint32_t lo, uint32_t hi) {
  uint64_t d;
  asm("mov.b64 %0, {%1, %2};" : "=l"(d) : "r"(lo), "r"(hi));
  return d;
}
__device__ __forceinline__ uint32_t exp_pair(bool poly, float a, float b, uint32_t mk) {
  if (poly) {
    const uint32_t pk = __byte_perm(__float_as_uint(a), __float_as_uint(b), 0x6521);
    uint32_t m, q;
    asm("lop3.b32 %0, %1, %2, 0x3f803f80, 0xEA;" : "=r"(m) : "r"(pk), "r"(mk));
    asm("fma.rn.bf16x2 %0, %1, %1, %2;" : "=r"(q) : "r"(m), "r"(0x40014001u));
    return pk - m + q;
  }
  return pack_bf16(ex2(a), ex2(b));
}
constexpr int PV_GR = 4;
__device__ __forceinline__ void exp_pv(const float (&s)[64], float (&o)[12], uint64_t dv, uint32_t mk) {
#pragma unroll
  for (int k0 = 0; k0 < 8; k0 += PV_GR) {
    uint32_t p[4 * PV_GR];
#pragma unroll
    for (int i = 0; i < 4 * PV_GR; i++)
      p[i] = exp_pair((POLY_MASK >> (k0 * 2 + i / 2)) & 1, s[k0 * 8 + 2 * i], s[k0 * 8 + 2 * i + 1], mk);
    WG_FENCE();
#pragma unroll
    for (int k = 0; k < PV_GR; k++)
      wgmma_rs_n24(o, p[4 * k], p[4 * k + 1], p[4 * k + 2], p[4 * k + 3], dv + (k0 + k) * 48, 1);
  }
}
__device__ __forceinline__ void load_q(uint32_t (&q)[6], const uint8_t* p) {
  q[0] = __ldcg((const uint32_t*)p);         q[1] = __ldcg((const uint32_t*)(p + 384));
  q[2] = __ldcg((const uint32_t*)(p + 128)); q[3] = __ldcg((const uint32_t*)(p + 512));
  q[4] = __ldcg((const uint32_t*)(p + 256)); q[5] = __ldcg((const uint32_t*)(p + 640));
}
__device__ __forceinline__ float rcp(float x) {
  float y;
  asm("rcp.approx.ftz.f32 %0, %1;" : "=f"(y) : "f"(x));
  return y;
}
__device__ __forceinline__ int img_off(int chunk) { return chunk * 2048; }
__device__ __forceinline__ void store_o(const float (&o)[12], int tile) {
  int tid, bid;
  asm volatile("mov.u32 %0, %%tid.x;" : "=r"(tid));
  asm volatile("mov.u32 %0, %%ctaid.x;" : "=r"(bid));
  const int head = bid >> 2;
  uint8_t* dst = (uint8_t*)g_o + ((bid & 3) * 4 + (tile >> 1)) * 163840 + (tile & 1) * 1024 + ((tid >> 5) & 3) * 256 + (tid & 31) * 4;
  const int oc = (head >> 1) * 5 + (head & 1) * 2;
  const int o0 = img_off(oc), o1 = img_off(oc + 1), o2 = img_off((head >> 1) * 5 + 4) + (head & 1) * 8;
  const float i0 = rcp(__shfl_sync(~0u, o[8], 2, 4)), i1 = rcp(__shfl_sync(~0u, o[10], 2, 4));
  *(uint32_t*)(dst + o0) = pack_bf16(o[0] * i0, o[1] * i0); *(uint32_t*)(dst + o0 + 128) = pack_bf16(o[2] * i1, o[3] * i1);
  *(uint32_t*)(dst + o1) = pack_bf16(o[4] * i0, o[5] * i0); *(uint32_t*)(dst + o1 + 128) = pack_bf16(o[6] * i1, o[7] * i1);
  if ((tid & 3) < 2) {
    *(uint32_t*)(dst + o2) = pack_bf16(o[8] * i0, o[9] * i0);
    *(uint32_t*)(dst + o2 + 128) = pack_bf16(o[10] * i1, o[11] * i1);
  }
}

struct Maps5 { CUtensorMap m[5]; };

__global__ void __launch_bounds__(512, 1)
k2_attn(const __grid_constant__ Maps5 maps, const bf16* __restrict__ wo, uint32_t mk) {
  const CUtensorMap* tmw = maps.m;
  extern __shared__ __align__(1024) uint8_t sm[];
  const uint32_t sbase = smem_u32(sm);
  float* part = (float*)(sm + 2 * HEAD_IMG);
  const uint32_t rbuf = sbase + 2 * HEAD_IMG + 2 * 6144;
  const uint32_t kvb = rbuf + 2 * 10240;
  const uint32_t partb = kvb + 128, rbar = kvb + 144;
  const int tid = threadIdx.x, lane = tid & 31;
  const int warp = __shfl_sync(~0u, tid >> 5, 0);
  const int head = blockIdx.x >> 2, qb = blockIdx.x & 3;

  if (tid == 0) {
    for (int i = 0; i < 16; i++) mbar_init(kvb + 8 * i, 1);
    mbar_init(partb, 128); mbar_init(partb + 8, 128); mbar_init(rbar, 1); mbar_init(rbar + 8, 1);
    asm volatile("fence.mbarrier_init.release.cluster;" ::: "memory");
  }
  __syncthreads();

  if (warp >= 12) {
    asm volatile("setmaxnreg.dec.sync.aligned.u32 32;");
    if (warp == 12) {
      const uint8_t* kimg = (const uint8_t*)g_qkv + (size_t)(32 + head) * HEAD_IMG;
      if (elect_one()) {
#pragma unroll
        for (int b = 0; b < 16; b++) mbar_expect(kvb + 8 * b, 12288);
      }
      pdl_wait();
#pragma unroll 1
      for (int b = 0; b < 16; b++) {
        if (elect_one()) {
          bulk_ld(sbase + b * 6144, kimg + b * 6144, 6144, kvb + 8 * b);
          bulk_ld(sbase + HEAD_IMG + b * 6144, kimg + 32 * HEAD_IMG + b * 6144, 6144, kvb + 8 * b);
        }
        if (b >= 2) mbar_wait(kvb + 8 * (b - 1), 0);
      }
      pdl_trigger();
    }
    if (warp > 12) {
      const int t96 = tid - 416, ck = min(t96, 79), nt = ck / 10;
      float* red = (float*)(sm + K2_SMEM - 96);
#pragma unroll 1
      for (int i = 0; i < 5; i++) {
        const int k = blockIdx.x * 5 + i, pr = k / 40, r = k - pr * 40;
        const uint4 v = ldg_nc(wo + (pr * 40 + (r < 16 ? r : (r < 32 ? r + 4 : (r < 36 ? r - 16 : r)))) * D_ + ck * 8);
        g_wo[((nt * 10 + (k >> 6)) * 10 + ck - nt * 10) * 64 + (k & 63)] = v;
        float t = ((bf_lo(v.x) + bf_hi(v.x)) + (bf_lo(v.y) + bf_hi(v.y))) + ((bf_lo(v.z) + bf_hi(v.z)) + (bf_lo(v.w) + bf_hi(v.w)));
        if (t96 >= 80) t = 0.f;
#pragma unroll
        for (int o = 16; o; o >>= 1) t += __shfl_xor_sync(~0u, t, o);
        if (lane == 0) red[(t96 >> 5) * 8 + i] = t;
      }
      bar_sync(1, 96);
      if (t96 < 5) {
        const float mu = (red[t96] + red[8 + t96] + red[16 + t96]) * (1.f / D_);
        const float hi = bf_lo(pack_bf16(mu, 0.f));
        g_wm[blockIdx.x * 5 + t96] = make_uint4(pack_bf16(hi, mu - hi), 0u, 0u, 0u);
      }
    }
    if (tid == 384) {
      if (blockIdx.x == 0) g_epoch = g_epoch + 1;
      mbar_wait(kvb + 8 * 15, 0);
      uint8_t* pdst = nullptr;
      uint32_t pbytes = 0;
#pragma unroll 1
      for (int i = 0; i < 8; i++) {
        const int p = blockIdx.x + 128 * i;
        uint8_t* dst = nullptr;
        uint32_t bytes = 0;
        if (i < 7 && p < 856) {
          asm volatile("cp.async.bulk.wait_group.read 0;" ::: "memory");
          const CUtensorMap* tm;
          int c1, c2;
          if (p < 640) {
            const int nt = p / 80, r = p - nt * 80, ph = r / 40, st = (r - ph * 40) >> 1, up = r & 1;
            bytes = ph ? 6656 : 7168;
            dst = (uint8_t*)g_wgu + nt * 552960 + ph * 286720 + st * 2 * bytes + up * (bytes >> 1);
            tm = &tmw[ph * 2 + up]; c1 = ph ? 112 + nt * 13 : nt * 14; c2 = st * 2;
          } else {
            const int nk = p - 640, nt = nk / 27;
            bytes = 10240;
            dst = (uint8_t*)g_wd + (size_t)nk * 10240;
            tm = &tmw[4]; c1 = nt * 10; c2 = nk - nt * 27;
          }
          mbar_expect(rbar + 8 * (i & 1), bytes);
          tma4d(rbuf + (i & 1) * 10240, tm, c1, c2, rbar + 8 * (i & 1));
        }
        if (pbytes) {
          mbar_wait(rbar + 8 * ((i - 1) & 1), ((i - 1) >> 1) & 1);
          if (pbytes == 10240) {
            bulk_st(pdst, rbuf + ((i - 1) & 1) * 10240, pbytes);
          } else {
            bulk_st(pdst, rbuf + ((i - 1) & 1) * 10240, pbytes >> 1);
            bulk_st(pdst + pbytes, rbuf + ((i - 1) & 1) * 10240 + (pbytes >> 1), pbytes >> 1);
          }
          asm volatile("cp.async.bulk.commit_group;" ::: "memory");
        }
        pdst = dst; pbytes = bytes;
      }
      asm volatile("cp.async.bulk.wait_group.read 0;" ::: "memory");
    }
  } else {
    asm volatile("setmaxnreg.inc.sync.aligned.u32 160;");
    const int wg = warp >> 2;
    const uint8_t* qthr = (const uint8_t*)g_qkv + (size_t)head * HEAD_IMG + qb * 64 * 384 + (warp & 3) * 768 + lane * 4;
    const uint32_t klo0 = ((sbase & 0x3FFFF) >> 4) | (128u << 16), vlo0 = (((sbase + HEAD_IMG) & 0x3FFFF) >> 4) | (24u << 16);
    constexpr uint64_t KSTEP2 = (uint64_t)(int64_t)(256 - (128 << 16));
    constexpr uint64_t KV2K = 384 - (HEAD_IMG >> 4) + (104 << 16);
    const int nun = wg == 1 ? 4 : 3;
    uint32_t utile = wg == 0 ? 0x210u : (wg == 1 ? 0x4235u : 0x576u);
    uint32_t ubeg = wg == 0 ? 0u : (wg == 1 ? 0x0b00u : 0x600u);
    uint32_t ulen = wg == 0 ? 0x0b1010u : (wg == 1 ? 0x10051006u : 0x0a1010u);
    pdl_wait();
    uint32_t q[6];
    load_q(q, qthr + (utile & 15) * 3072);
    bool fast;
    {
      const uint4 kn = __ldcg((const uint4*)&g_nrm[(32 + head) * 128 + lane * 4]);
      const uint4 vn = __ldcg((const uint4*)&g_nrm[(64 + head) * 128 + lane * 4]);
      const float qv = __ldcg(&g_nrm[head * 128 + qb * 32 + lane]);
      const float k2 = __uint_as_float(__reduce_max_sync(~0u, max(max(kn.x, kn.y), max(kn.z, kn.w))));
      const float v2 = __uint_as_float(__reduce_max_sync(~0u, max(max(vn.x, vn.y), max(vn.z, vn.w))));
      const float q2 = __uint_as_float(__reduce_max_sync(~0u, __float_as_uint(qv)));
      fast = q2 * k2 <= 3400.f && v2 < 1e24f && v2 > 1e-24f;
    }
    if (fast) {
#pragma unroll 1
      for (int u = 0; u < nun; u++) {
        const uint32_t b0 = ubeg & 15;
        const bool wt = u == 0 || (wg == 1 && u == 1);
        float s[64], o[12];
#pragma unroll
        for (int i = 0; i < 12; i++) o[i] = 0.f;
        uint32_t vlo = vlo0 + b0 * 384, kb = kvb + b0 * 8;
        const uint32_t vend = vlo + ((ulen & 255) - 1) * 384;
        if (wt) mbar_wait(kb, 0);
        fence_regs(o);
        WG_FENCE();
        wgmma_rs_n128(s, q[0], q[1], q[2], q[3], desc64(klo0 + b0 * 384, 8), 0);
        wgmma_rs_n128(s, q[4], q[5], 0, 0, desc64(klo0 + b0 * 384, 8) + KSTEP2, 1);
        WG_COMMIT();
#pragma unroll 1
        for (; vlo != vend; vlo += 384) {
          if (wt) { kb += 8; mbar_wait(kb, 0); }
          WG_WAIT(0);
          fence_regs(s); fence_regs(o);
          const uint64_t dv = desc64(vlo, 8);
          exp_pv(s, o, dv, mk);
          wgmma_rs_n128(s, q[0], q[1], q[2], q[3], dv + KV2K, 0);
          wgmma_rs_n128(s, q[4], q[5], 0, 0, dv + (KV2K + KSTEP2), 1);
          WG_COMMIT();
        }
        WG_WAIT(0);
        fence_regs(s); fence_regs(o);
        if (u + 1 < nun) load_q(q, qthr + ((utile >> 4) & 15) * 3072);
        exp_pv(s, o, desc64(vlo, 8), mk);
        WG_COMMIT();
        WG_WAIT(0);
        fence_regs(o);
        if (wg == 1 && !(u & 1)) {
          float4* pp = (float4*)(part + u * 768) + (tid & 127);
          pp[0] = make_float4(o[0], o[1], o[2], o[3]);
          pp[128] = make_float4(o[4], o[5], o[6], o[7]);
          pp[256] = make_float4(o[8], o[9], o[10], o[11]);
          mbar_arrive(partb + 4 * u);
        } else {
          if (wg != 1 && u == 2) {
            const int pi = wg == 0 ? 1 : 0;
            mbar_wait(partb + 8 * pi, 0);
            const float4* pp = (const float4*)(part + pi * 1536) + (tid & 127);
            const float4 x0 = pp[0], x1 = pp[128], x2 = pp[256];
            o[0] += x0.x; o[1] += x0.y; o[2] += x0.z; o[3] += x0.w; o[4] += x1.x; o[5] += x1.y;
            o[6] += x1.z; o[7] += x1.w; o[8] += x2.x; o[9] += x2.y; o[10] += x2.z; o[11] += x2.w;
          }
          store_o(o, utile & 15);
        }
        utile >>= 4; ubeg >>= 4; ulen >>= 8;
      }
    } else {
#pragma unroll 1
      for (int tile = wg; tile < 8; tile += 3) {
        load_q(q, qthr + tile * 3072);
        if ((lane & 3) >= 2) { q[4] = 0; q[5] = 0; }
        float o[12], m0 = -INFINITY, m1 = -INFINITY;
#pragma unroll
        for (int i = 0; i < 12; i++) o[i] = 0.f;
#pragma unroll 1
        for (int b = 0; b < 16; b++) {
          float s[64];
          mbar_wait(kvb + 8 * b, 0);
          WG_FENCE();
          wgmma_rs_n128(s, q[0], q[1], q[2], q[3], desc64(klo0 + b * 384, 8), 0);
          wgmma_rs_n128(s, q[4], q[5], 0, 0, desc64(klo0 + b * 384, 8) + KSTEP2, 1);
          WG_COMMIT();
          WG_WAIT(0);
          fence_regs(s);
          float x0 = m0, x1 = m1;
#pragma unroll
          for (int j = 0; j < 16; j++) {
            if ((POLY_MASK >> j) & 1) {
#pragma unroll
              for (int i = 0; i < 4; i++) s[4 * j + i] *= (1.f / 32768.f);
            }
            x0 = fmaxf(x0, fmaxf(s[4 * j], s[4 * j + 1]));
            x1 = fmaxf(x1, fmaxf(s[4 * j + 2], s[4 * j + 3]));
          }
          x0 = fmaxf(x0, __shfl_xor_sync(~0u, x0, 1)); x0 = fmaxf(x0, __shfl_xor_sync(~0u, x0, 2));
          x1 = fmaxf(x1, __shfl_xor_sync(~0u, x1, 1)); x1 = fmaxf(x1, __shfl_xor_sync(~0u, x1, 2));
          const float al0 = ex2(m0 - x0), al1 = ex2(m1 - x1);
          m0 = x0; m1 = x1;
#pragma unroll
          for (int i = 0; i < 12; i++) o[i] *= (i & 2) ? al1 : al0;
          uint32_t p[32];
#pragma unroll
          for (int i = 0; i < 32; i++) {
            const float mm = (i & 1) ? m1 : m0;
            p[i] = pack_bf16(ex2(s[2 * i] - mm), ex2(s[2 * i + 1] - mm));
          }
          fence_regs(o);
          WG_FENCE();
#pragma unroll
          for (int k = 0; k < 8; k++)
            wgmma_rs_n24(o, p[4 * k], p[4 * k + 1], p[4 * k + 2], p[4 * k + 3], desc64(vlo0 + b * 384 + k * 48, 8), 1);
          WG_COMMIT();
          WG_WAIT(0);
          fence_regs(o);
        }
        store_o(o, tile);
      }
    }
  }
}

constexpr int K3_ST = 4, K3_STAGE = 37888, K3_NB = 4, K3_NT = 6;
constexpr int K3_SMEM = K3_ST * K3_STAGE + 24576 + 20480 + 256;

template <int N> struct Acc { float v[N]; };

__global__ void __cluster_dims__(2, 1, 1) __launch_bounds__(288, 1)
k3_proj(const __grid_constant__ CUtensorMap tmx) {
  extern __shared__ __align__(1024) uint8_t sm[];
  const uint32_t sbase = smem_u32(sm);
  const uint8_t* xch = sm + K3_ST * K3_STAGE;
  const uint8_t* res = sm + K3_ST * K3_STAGE + 24576;
  const uint32_t fullb = smem_u32(res) + 20480, emptyb = fullb + 8 * K3_ST, resb = emptyb + 8 * K3_ST, xchb = resb + 8;
  const int tid = threadIdx.x, lane = tid & 31;
  const int warp = __shfl_sync(~0u, tid >> 5, 0);
  const int rank = blockIdx.x & 1;
  const int n = blockIdx.x & 7, m = blockIdx.x >> 3;
  if (warp == 8) {
    if (elect_one()) {
#pragma unroll
      for (int i = 0; i < K3_ST; i++) { mbar_init(fullb + 8 * i, 1); mbar_init(emptyb + 8 * i, 4); }
      mbar_init(resb, 1); mbar_init(xchb, 1);
      mbar_expect(xchb, 24576);
      asm volatile("fence.mbarrier_init.release.cluster;" ::: "memory");
    }
    __syncwarp();
  }
  cluster_arrive();
  if (warp == 8) {
    const uint8_t* wk = (const uint8_t*)g_wo + n * 102400;
    const uint8_t* ws = (const uint8_t*)g_wo + (n ^ 1) * 102400;
    const uint8_t* ab = (const uint8_t*)g_o + m * 163840;
    prefetch_map(&tmx);
    cluster_wait();
    pdl_wait();
#pragma unroll 1
    for (int i = 0; i < K3_NT; i++) {
      const int s = i % K3_ST, kt = i < K3_NB ? i + rank * K3_NT : i;
      const uint32_t sa = sbase + s * K3_STAGE, fb = fullb + 8 * s;
      if (i >= K3_ST) mbar_wait(emptyb + 8 * s, 0);
      if (elect_one()) {
        mbar_expect(fb, i < K3_NB ? 37888 : 27648);
        if (i < K3_NB) bulk_ld(sa, ab + kt * 16384, 16384, fb);
        else bulk_ld_mc(sa + rank * 8192, ab + kt * 16384 + rank * 8192, 8192, fb);
        bulk_ld(sa + 16384, wk + kt * 10240, 10240, fb);
        bulk_ld(sa + 26624, (const uint8_t*)g_wm + kt * 1024, 1024, fb);
        if (i < K3_NB) bulk_ld(sa + 27648, ws + kt * 10240, 10240, fb);
        if (i == K3_ST - 1) {
          mbar_expect(resb, 20480);
          tma2d(smem_u32(res), &tmx, n * 80, m * 128, resb);
          tma2d(smem_u32(res) + 10240, &tmx, n * 80, m * 128 + 64, resb);
        }
      }
      if (i == 0) pdl_trigger();
    }
    cluster_arrive();
  } else {
    const int g = lane >> 2, c = lane & 3;
    const int row = m * 128 + warp * 16 + g;
    float mu0 = __uint_as_float(__ldcg(&g_rowstat[row].z)), mu1 = __uint_as_float(__ldcg(&g_rowstat[row + 8].z));
    float acc[84];
    float (&keep)[44] = ((Acc<44>*)acc)->v;
    const uint64_t da0 = mkdesc(sbase + (warp >> 2) * 1024, 2048, 128, 0);
    const uint64_t db0 = mkdesc(sbase + 16384, 128, 1024, 0);
    cluster_wait();
#pragma unroll 1
    for (int i = 0; i < K3_NB; i++) {
      mbar_wait(fullb + 8 * i, 0);
      const uint64_t da = da0 + i * (K3_STAGE >> 4), db = db0 + i * (K3_STAGE >> 4);
      WG_FENCE();
#pragma unroll
      for (int k = 0; k < 4; k++) wgmma_ss_n168(acc, da + k * 256, db + k * 16, (i | k) != 0);
      WG_COMMIT();
      if (i > 0) {
        WG_WAIT(1);
        if (i - 1 + K3_ST < K3_NT && (tid & 127) < 2) mbar_arrive_cta(emptyb + 8 * (i - 1), tid & 1);
      }
    }
    const uint32_t rx = mapa(smem_u32(xch) + tid * 16, rank ^ 1), rb = mapa(xchb, rank ^ 1);
    WG_WAIT(0);
    fence_regs(acc);
    st_async4(rx, acc[40], acc[41], acc[42], acc[43], rb);
#pragma unroll
    for (int i = K3_NB; i < K3_NT; i++) {
      const int s = i % K3_ST;
      mbar_wait(fullb + 8 * s, 1);
      const uint64_t da = da0 + s * (K3_STAGE >> 4), db = db0 + s * (K3_STAGE >> 4);
      WG_FENCE();
#pragma unroll
      for (int k = 0; k < 4; k++) wgmma_ss_n88(keep, da + k * 256, db + k * 16, 1);
      WG_COMMIT();
#pragma unroll
      for (int j = (i - K3_NB) * 3; j < (i - K3_NB) * 3 + 3; j++)
        if (j < 5) SEND8(rx + (j + 1) * 4096, acc, 44 + 8 * j, rb);
    }
    cluster_arrive();
    const uint8_t* sp = res + (warp * 16 + g) * 160 + c * 4;
    uint32_t rv[20];
    mbar_wait(resb, 0);
#pragma unroll
    for (int j = 0; j < 10; j++) {
      rv[2 * j] = *(const uint32_t*)(sp + j * 16);
      rv[2 * j + 1] = *(const uint32_t*)(sp + 1280 + j * 16);
    }
    WG_WAIT(0);
    fence_regs(keep);
    mbar_wait(xchb, 0);
    const uint8_t* xp = xch + tid * 16;
    {
      const float4 p = *(const float4*)xp;
      mu0 += __shfl_sync(~0u, (keep[40] + p.x) + (keep[41] + p.y), 0, 4);
      mu1 += __shfl_sync(~0u, (keep[42] + p.z) + (keep[43] + p.w), 0, 4);
    }
    uint8_t* himg = (uint8_t*)g_h + m * 163840 + img_off(n * 10) + warp * 256 + lane * 4;
    float q0 = 0.f, q1 = 0.f;
#pragma unroll
    for (int j = 0; j < 10; j++) {
      const uint2 p = *(const uint2*)(xp + ((j >> 1) + 1) * 4096 + (j & 1) * 8);
      const float x0 = (keep[4 * j] + bf_lo(p.x)) + (bf_lo(rv[2 * j]) - mu0), x1 = (keep[4 * j + 1] + bf_hi(p.x)) + (bf_hi(rv[2 * j]) - mu0);
      const float y0 = (keep[4 * j + 2] + bf_lo(p.y)) + (bf_lo(rv[2 * j + 1]) - mu1), y1 = (keep[4 * j + 3] + bf_hi(p.y)) + (bf_hi(rv[2 * j + 1]) - mu1);
      *(uint32_t*)(himg + img_off(j)) = pack_bf16(x0, x1);
      *(uint32_t*)(himg + img_off(j) + 128) = pack_bf16(y0, y1);
      q0 = fmaf(x0, x0, fmaf(x1, x1, q0)); q1 = fmaf(y0, y0, fmaf(y1, y1, q1));
    }
    q0 += __shfl_xor_sync(~0u, q0, 1); q0 += __shfl_xor_sync(~0u, q0, 2);
    q1 += __shfl_xor_sync(~0u, q1, 1); q1 += __shfl_xor_sync(~0u, q1, 2);
    if (c < 2) g_hpart[n * S_ + row + c * 8] = c ? q1 : q0;
    if (n == 0 && c < 2) g_hmean[row + c * 8] = c ? mu1 : mu0;
  }
  cluster_wait();
}

constexpr int P3_NB = 12, P3_NT = 15;
constexpr int K4_G = 2, K4_NS = 4, K4_NJ = 20;
constexpr int K4_RB = 163840, K4_BST = 7168 * K4_G, K4_XCH = 147456, K4_STG = K4_XCH + 40960, K4_BAR = K4_RB + K4_NS * K4_BST;
constexpr int K4_SMEM = K4_BAR + 384;

__device__ __forceinline__ void wait_flags(const uint4* f, uint32_t tag, uint32_t need, uint32_t& seen) {
  if ((seen & need) == need) return;
  for (uint32_t it = 0; (seen & need) != need; it++) {
    if (it > (1u << 20)) wait_timeout();
    if (it) __nanosleep(150);
    uint32_t v = 0;
    if ((threadIdx.x & 31) < 8) asm volatile("ld.acquire.gpu.global.u32 %0, [%1];" : "=r"(v) : "l"((const uint32_t*)f + (threadIdx.x & 7)) : "memory");
    seen = __ballot_sync(~0u, v == tag) & 255;
  }
  asm volatile("fence.proxy.async.global;" ::: "memory");
}

template <int MODE>
__global__ void __cluster_dims__(2, 1, 1) __launch_bounds__(384, 1)
k45_ffn(const __grid_constant__ CUtensorMap tmo) {
  extern __shared__ __align__(1024) uint8_t sm[];
  const uint32_t sbase = smem_u32(sm);
  const uint32_t afull = sbase + K4_BAR, bfull = afull + 80, bempty = bfull + 8 * K4_NS, full3 = bempty + 8 * K4_NS;
  const uint32_t empty3 = full3 + 32, afree = empty3 + 32, xchb = afree + 32;
  const int tid = threadIdx.x, lane = tid & 31;
  const int warp = __shfl_sync(~0u, tid >> 5, 0);
  const int rank = blockIdx.x & 1;
  const int n1 = (blockIdx.x >> 1) & 7, m1 = (blockIdx.x >> 4) * 2 + rank;
  const int n3 = blockIdx.x & 7, m3 = blockIdx.x >> 3;
  if (warp == 8) {
    if (elect_one()) {
#pragma unroll
      for (int i = 0; i < 10; i++) mbar_init(afull + 8 * i, 1);
#pragma unroll
      for (int i = 0; i < 4; i++) {
        mbar_init(bfull + 8 * i, 1); mbar_init(bempty + 8 * i, 4); mbar_init(full3 + 8 * i, 1); mbar_init(empty3 + 8 * i, 4);
        mbar_init(afree + 8 * i, 2);
      }
      mbar_init(xchb, 1);
      mbar_expect(xchb, 20480);
      asm volatile("fence.mbarrier_init.release.cluster;" ::: "memory");
    }
    __syncwarp();
  }
  cluster_arrive();
  if (warp >= 8) {
    cluster_wait();
    if (warp == 8) {
      const uint8_t* src = (const uint8_t*)g_wgu + n1 * 552960;
      const uint8_t* hb = (const uint8_t*)g_h + (size_t)m1 * 163840;
#pragma unroll 1
      for (int j = 0; j < (MODE == 2 ? 0 : 40); j++) {
        const uint32_t s8 = (j & 3) * 8, sz = j < 20 ? 14336 : 13312;
        if (j == 2) {
          pdl_wait();
          if (elect_one()) {
#pragma unroll
            for (int kt = 0; kt < 2 / 2 + 1; kt++) { mbar_expect(afull + 8 * kt, 16384); bulk_ld(sbase + kt * 16384, hb + kt * 16384, 16384, afull + 8 * kt); }
          }
        }
        if (j >= 4) mbar_wait(bempty + s8, ((j >> 2) - 1) & 1);
        if (elect_one()) {
          mbar_expect(bfull + s8, sz);
          if ((j & 1) == rank) bulk_ld_mc(sbase + K4_RB + s8 * (K4_BST / 8), src, sz, bfull + s8);
          if (j > 2 && j < 18 && (j & 1)) {
            mbar_expect(afull + 4 + j * 4, 16384);
            bulk_ld(sbase + 8192 + j * 8192, hb + 8192 + j * 8192, 16384, afull + 4 + j * 4);
          }
        }
        src += sz;
      }
    } else if (warp == 9) {
      prefetch_map(&tmo);
      const uint32_t tag = __ldcg(&g_epoch);
#pragma unroll 1
      for (int ph = 0; ph < (MODE == 2 ? 0 : 2); ph++) {
        bar_sync(5 + ph, 256 + 32);
        if (lane == 0) {
          asm volatile("st.release.gpu.global.u32 [%0], %1;" ::"l"((uint32_t*)&g_flag[ph * 32 + m1 * 2] + n1), "r"(tag) : "memory");
        }
        __syncwarp();
      }
    } else {
      const uint8_t* wk = (const uint8_t*)g_wd + n3 * 276480;
      const uint8_t* ws = (const uint8_t*)g_wd + (n3 ^ 1) * 276480;
      const uint8_t* ab = (const uint8_t*)g_hh + (size_t)m3 * 442368;
      const uint32_t tag = __ldcg(&g_epoch);
      uint32_t seen = 0;
#pragma unroll 1
      for (int i = 0; i < (MODE == 1 ? 0 : P3_NT); i++) {
        const int kt = i < 7 ? rank * 7 + i : (i < P3_NB ? rank * (P3_NB - 7) + 7 + i : P3_NB + i);
        const uint32_t sa = sbase + (i & 3) * 36864, fb = full3 + 8 * (i & 3);
        if (warp == 11) {
          const int q = kt * 8 - (i < 7 ? 0 : 112), w = i < 7 ? 14 : 13;
          if (MODE == 0 && i == 0) mbar_wait(afull + 72, 0);
          if (i == 7) seen = 0;
          wait_flags(&g_flag[(i < 7 ? 0 : 32) + m3 * 2], tag, 1u << (q / w) | 1u << ((q + 7) / w), seen);
        }
        if (i < 4) { if (MODE == 0) mbar_wait(afree + 8 * i, 0); }
        else mbar_wait(empty3 + 8 * (i & 3), ((i >> 2) - 1) & 1);
        if (warp == 10) {
          if (elect_one()) {
            mbar_expect(fb, i < P3_NB ? 36864 : 26624);
            bulk_ld(sa + 16384, wk + kt * 10240, 10240, fb);
            if (i < P3_NB) bulk_ld(sa + 26624, ws + kt * 10240, 10240, fb);
          }
        } else {
          if (elect_one()) {
            if (i < P3_NB) bulk_ld(sa, ab + kt * 16384, 16384, fb);
            else bulk_ld_mc(sa + rank * 8192, ab + kt * 16384 + rank * 8192, 8192, fb);
          }
        }
      }
    }
    __syncwarp();
    cluster_arrive();
    asm volatile("barrier.cluster.wait.aligned; // producers" ::: "memory");
  } else {
    const int wg = warp >> 2;
    const uint64_t da0 = mkdesc(sbase + wg * 1024, 2048, 128, 0);
    const uint64_t db0 = mkdesc(sbase + K4_RB, 128, 256, 0);
    cluster_wait();
    float acc[80];
    if constexpr (MODE != 2) {
    float a1[112], a2[104];
    int s = 0, ph = 0, sprev = 0;
#pragma unroll 1
    for (int j = 0; j < K4_NJ; j++) {
      if ((j * K4_G) % 4 == 0) mbar_wait(afull + 2 * K4_G * j, 0);
      mbar_wait(bfull + 8 * s, ph);
      const uint64_t da = da0 + j * K4_G * 256, db = db0 + s * (K4_BST >> 4);
      WG_FENCE();
#pragma unroll
      for (int k = 0; k < K4_G; k++) wgmma_ss_n224(a1, da + k * 256, db + k * 448, (j | k) != 0);
      WG_COMMIT();
      if (j > 0) {
        WG_WAIT(1);
        if ((tid & 127) < 2) mbar_arrive_cta(bempty + 8 * sprev, tid & 1);
      }
      sprev = s;
      if (++s == K4_NS) { s = 0; ph ^= 1; }
    }
    uint8_t* hd = (uint8_t*)g_hh + (size_t)m1 * 442368 + warp * 256 + lane * 4;
    WG_WAIT(0);
    fence_regs(a1);
    if ((tid & 127) < 2) mbar_arrive_cta(bempty + 8 * ((K4_NJ - 1) % K4_NS), tid & 1);
#define STORE_H(a, off, ptr, c) do { uint8_t* p_ = ptr; \
      *(uint32_t*)p_ = pack_bf16(a[4 * (c)] * a[off + 4 * (c)], a[4 * (c) + 1] * a[off + 1 + 4 * (c)]); \
      *(uint32_t*)(p_ + 128) = pack_bf16(a[4 * (c) + 2] * a[off + 2 + 4 * (c)], a[4 * (c) + 3] * a[off + 3 + 4 * (c)]); } while (0)
#pragma unroll
    for (int c = 0; c < 14; c++) STORE_H(a1, 56, hd + img_off(n1 * 14 + c), c);
    bar_arrive(5, 256 + 32);
#pragma unroll 1
    for (int j = 0; j < K4_NJ; j++) {
      mbar_wait(bfull + 8 * s, ph);
      const uint64_t da = da0 + j * K4_G * 256, db = db0 + s * (K4_BST >> 4);
      WG_FENCE();
#pragma unroll
      for (int k = 0; k < K4_G; k++) wgmma_ss_n208(a2, da + k * 256, db + k * 416, (j | k) != 0);
      WG_COMMIT();
      if (j > 0) {
        WG_WAIT(1);
        if (j <= K4_NJ - K4_NS && (tid & 127) < 2) mbar_arrive_cta(bempty + 8 * sprev, tid & 1);
        if (j * K4_G >= 12 && ((j * K4_G) & 7) == 4 && (tid & 127) == 0) mbar_arrive(afree + (j * K4_G - 12));
      }
      sprev = s;
      if (++s == K4_NS) { s = 0; ph ^= 1; }
    }
    WG_WAIT(0);
    fence_regs(a2);
#pragma unroll
    for (int c = 0; c < 13; c++) STORE_H(a2, 52, hd + img_off(112 + n1 * 13 + c), c);
    bar_arrive(6, 256 + 32);
    }
    if constexpr (MODE == 1) cluster_arrive();
    if constexpr (MODE != 1) {
    float (&keep)[40] = ((Acc<40>*)acc)->v;
    const uint64_t db3 = mkdesc(sbase + 16384, 128, 1024, 0);
#pragma unroll 1
    for (int i = 0; i < P3_NB; i++) {
      mbar_wait(full3 + 8 * (i & 3), (i >> 2) & 1);
      const uint64_t da = da0 + (i & 3) * 2304, db = db3 + (i & 3) * 2304;
      WG_FENCE();
#pragma unroll
      for (int k = 0; k < 4; k++) wgmma_ss_n160(acc, da + k * 256, db + k * 16, (i | k) != 0);
      WG_COMMIT();
      if (i > 0) {
        WG_WAIT(1);
        if (i + 3 < P3_NT && (tid & 127) < 2) mbar_arrive_cta(empty3 + 8 * ((i - 1) & 3), tid & 1);
      }
    }
    const int g = lane >> 2, c = lane & 3, row = m3 * 128 + warp * 16 + g;
    const uint8_t* himg = (const uint8_t*)g_h + (size_t)m3 * 163840 + warp * 256 + lane * 4;
    uint32_t rv[20];
    const float mu0 = __ldcg(&g_hmean[row]), mu1 = __ldcg(&g_hmean[row + 8]);
    float r0 = __ldcg(&g_hpart[c * 2 * S_ + row]) + __ldcg(&g_hpart[(c * 2 + 1) * S_ + row]);
    float r1 = __ldcg(&g_hpart[c * 2 * S_ + row + 8]) + __ldcg(&g_hpart[(c * 2 + 1) * S_ + row + 8]);
#pragma unroll
    for (int j = 0; j < 10; j++) {
      rv[2 * j] = __ldcg((const uint32_t*)(himg + img_off(n3 * 10 + j)));
      rv[2 * j + 1] = __ldcg((const uint32_t*)(himg + img_off(n3 * 10 + j) + 128));
    }
    const uint32_t rx = mapa(sbase + K4_XCH + tid * 16, rank ^ 1), rb = mapa(xchb, rank ^ 1);
    WG_WAIT(0);
    fence_regs(acc);
    if (P3_NB + 3 < P3_NT && (tid & 127) < 2) mbar_arrive_cta(empty3 + 8 * ((P3_NB - 1) & 3), tid & 1);
#pragma unroll
    for (int i = P3_NB; i < P3_NT; i++) {
      mbar_wait(full3 + 8 * (i & 3), (i >> 2) & 1);
      const uint64_t da = da0 + (i & 3) * 2304, db = db3 + (i & 3) * 2304;
      WG_FENCE();
#pragma unroll
      for (int k = 0; k < 4; k++) wgmma_ss_n80(keep, da + k * 256, db + k * 16, 1);
      WG_COMMIT();
      if (i > P3_NB && i + 3 < P3_NT) {
        WG_WAIT(1);
        if ((tid & 127) < 2) mbar_arrive_cta(empty3 + 8 * ((i - 1) & 3), tid & 1);
      }
#pragma unroll
      for (int j = (i - P3_NB) * 3; j < (i - P3_NB) * 3 + 3; j++)
        if (j < 5) SEND8(rx + j * 4096, acc, 40 + 8 * j, rb);
    }
    cluster_arrive();
    r0 += __shfl_xor_sync(~0u, r0, 1); r1 += __shfl_xor_sync(~0u, r1, 1);
    r0 += __shfl_xor_sync(~0u, r0, 2); r1 += __shfl_xor_sync(~0u, r1, 2);
    r0 = rcp(r0 * (1.f / D_) + 1e-5f); r1 = rcp(r1 * (1.f / D_) + 1e-5f);
    asm volatile("" : "+f"(r0), "+f"(r1)::"memory");
    WG_WAIT(0);
    fence_regs(keep);
    mbar_wait(xchb, 0);
    uint8_t* sp = sm + K4_STG + (warp * 16 + g) * 160 + c * 4;
#pragma unroll
    for (int j = 0; j < 10; j++) {
      const uint2 p = *(const uint2*)(sm + K4_XCH + tid * 16 + (j >> 1) * 4096 + (j & 1) * 8);
      *(uint32_t*)(sp + j * 16) = pack_bf16(fmaf(keep[4 * j] + bf_lo(p.x), r0, bf_lo(rv[2 * j]) + mu0), fmaf(keep[4 * j + 1] + bf_hi(p.x), r0, bf_hi(rv[2 * j]) + mu0));
      *(uint32_t*)(sp + 1280 + j * 16) = pack_bf16(fmaf(keep[4 * j + 2] + bf_lo(p.y), r1, bf_lo(rv[2 * j + 1]) + mu1), fmaf(keep[4 * j + 3] + bf_hi(p.y), r1, bf_hi(rv[2 * j + 1]) + mu1));
    }
    fence_async();
    bar_sync(1 + wg, 128);
    if ((tid & 127) == 0) {
      tma2d_st(&tmo, n3 * 80, m3 * 128 + wg * 64, sbase + K4_STG + wg * 10240);
      bulk_commit_wait();
    }
    __syncwarp();
    }
    asm volatile("barrier.cluster.wait.aligned; // consumers" ::: "memory");
  }
}

typedef CUresult (*EncodeFn)(CUtensorMap*, CUtensorMapDataType, cuuint32_t, void*, const cuuint64_t*, const cuuint64_t*,
                             const cuuint32_t*, const cuuint32_t*, CUtensorMapInterleave, CUtensorMapSwizzle,
                             CUtensorMapL2promotion, CUtensorMapFloatOOBfill);

static CUtensorMap make_map(EncodeFn enc, const void* p, uint64_t inner, uint64_t outer, uint32_t box_inner,
                            uint32_t box_outer, CUtensorMapSwizzle swz) {
  CUtensorMap m;
  cuuint64_t gd[2] = {inner, outer};
  cuuint64_t gs[1] = {inner * 2};
  cuuint32_t bd[2] = {box_inner, box_outer};
  cuuint32_t es[2] = {1, 1};
  enc(&m, CU_TENSOR_MAP_DATA_TYPE_BFLOAT16, 2, (void*)p, gd, gs, bd, es, CU_TENSOR_MAP_INTERLEAVE_NONE, swz,
      CU_TENSOR_MAP_L2_PROMOTION_L2_256B, CU_TENSOR_MAP_FLOAT_OOB_FILL_NONE);
  return m;
}

static CUtensorMap make_map_img(EncodeFn enc, const void* p, uint64_t k, uint64_t n, uint32_t rows, uint32_t chunks,
                                uint32_t groups) {
  CUtensorMap m;
  cuuint64_t gd[4] = {8, rows, n / 8, k / rows};
  cuuint64_t gs[3] = {n * 2, 16, n * 2 * rows};
  cuuint32_t bd[4] = {8, rows, chunks, groups};
  cuuint32_t es[4] = {1, 1, 1, 1};
  enc(&m, CU_TENSOR_MAP_DATA_TYPE_BFLOAT16, 4, (void*)p, gd, gs, bd, es, CU_TENSOR_MAP_INTERLEAVE_NONE,
      CU_TENSOR_MAP_SWIZZLE_NONE, CU_TENSOR_MAP_L2_PROMOTION_L2_128B, CU_TENSOR_MAP_FLOAT_OOB_FILL_NONE);
  return m;
}

template <typename... KArgs, typename... Args>
static void launch(void (*k)(KArgs...), int grid, int threads, int smem, bool pdl, Args... args) {
  cudaLaunchConfig_t cfg = {};
  cfg.gridDim = dim3(grid);
  cfg.blockDim = dim3(threads);
  cfg.dynamicSmemBytes = smem;
  cfg.stream = cudaStreamPerThread;
  cudaLaunchAttribute at[1];
  at[0].id = cudaLaunchAttributeProgrammaticStreamSerialization;
  at[0].val.programmaticStreamSerializationAllowed = 1;
  cfg.attrs = at;
  cfg.numAttrs = pdl ? 1 : 0;
  cudaLaunchKernelEx(&cfg, k, KArgs(args)...);
}

extern "C" void kernel_launch(void* const* d_in, const int* in_sizes, int n_in, void* d_out, int out_size) {
  const bf16* x = (const bf16*)d_in[0];
  const bf16* wqkv = (const bf16*)d_in[1];
  const bf16* wo = (const bf16*)d_in[2];
  const bf16* wg = (const bf16*)d_in[4];
  const bf16* wu = (const bf16*)d_in[5];
  const bf16* wd = (const bf16*)d_in[6];

  static EncodeFn enc = nullptr;
  static bool fused = true;
  if (!enc) {
    void* fn = nullptr;
    cudaDriverEntryPointQueryResult qr;
    cudaGetDriverEntryPoint("cuTensorMapEncodeTiled", &fn, cudaEnableDefault, &qr);
    enc = (EncodeFn)fn;
    cudaFuncSetAttribute(k1_qkv, cudaFuncAttributeMaxDynamicSharedMemorySize, K1_SMEM);
    cudaFuncSetAttribute(k2_attn, cudaFuncAttributeMaxDynamicSharedMemorySize, K2_SMEM);
    cudaFuncSetAttribute(k3_proj, cudaFuncAttributeMaxDynamicSharedMemorySize, K3_SMEM);
    cudaFuncSetAttribute(k45_ffn<0>, cudaFuncAttributeMaxDynamicSharedMemorySize, K4_SMEM);
    cudaFuncSetAttribute(k45_ffn<1>, cudaFuncAttributeMaxDynamicSharedMemorySize, K4_SMEM);
    cudaFuncSetAttribute(k45_ffn<2>, cudaFuncAttributeMaxDynamicSharedMemorySize, K4_SMEM);
    cudaLaunchConfig_t cfg = {};
    cfg.gridDim = dim3(128); cfg.blockDim = dim3(384); cfg.dynamicSmemBytes = K4_SMEM;
    int clusters = 0;
    cudaOccupancyMaxActiveClusters(&clusters, k45_ffn<0>, &cfg);
    fused = clusters >= 64;
  }
  const CUtensorMap tmx = make_map(enc, x, D_, S_, 64, 96, CU_TENSOR_MAP_SWIZZLE_128B);
  const CUtensorMap tmw = make_map(enc, wqkv, 3 * D_, D_, 32, 64, CU_TENSOR_MAP_SWIZZLE_64B);
  const CUtensorMap tmxr = make_map(enc, x, D_, S_, 80, 64, CU_TENSOR_MAP_SWIZZLE_NONE);
  Maps5 maps;
  maps.m[0] = make_map_img(enc, wg, D_, F_, 16, 14, 2); maps.m[1] = make_map_img(enc, wu, D_, F_, 16, 14, 2);
  maps.m[2] = make_map_img(enc, wg, D_, F_, 16, 13, 2); maps.m[3] = make_map_img(enc, wu, D_, F_, 16, 13, 2);
  maps.m[4] = make_map_img(enc, wd, F_, D_, 64, 10, 1);
  const CUtensorMap tmout = make_map(enc, d_out, D_, S_, 80, 64, CU_TENSOR_MAP_SWIZZLE_NONE);

  launch(k1_qkv, 132, 512, K1_SMEM, false, tmx, tmw, x, wqkv);
  launch(k2_attn, 128, 512, K2_SMEM, true, maps, wo, 0x007f007fu);
  launch(k3_proj, 128, 288, K3_SMEM, true, tmxr);
  if (fused) {
    launch(k45_ffn<0>, 128, 384, K4_SMEM, true, tmout);
  } else {
    launch(k45_ffn<1>, 128, 384, K4_SMEM, true, tmout);
    launch(k45_ffn<2>, 128, 384, K4_SMEM, false, tmout);
  }
}
```

```cpp
#include <cuda_runtime.h>
#include <cuda_bf16.h>
#include <cuda.h>
#include <stdint.h>

typedef __nv_bfloat16 bf16;

constexpr int S_ = 2048, D_ = 640, F_ = 1728;
constexpr int HEAD_IMG = 98304;
constexpr uint32_t POLY_MASK = 0xFAAB;
constexpr float QSCALE = 0.22360679774997896f * 1.4426950408889634f;

__device__ __align__(1024) uint4 g_qkv[96 * HEAD_IMG / 16];
__device__ __align__(1024) uint4 g_o[S_ * D_ / 8];
__device__ __align__(1024) uint4 g_h[S_ * D_ / 8];
__device__ __align__(1024) uint4 g_hh[S_ * F_ / 8];
__device__ __align__(1024) uint4 g_wo[D_ * D_ / 8];
__device__ __align__(1024) uint4 g_wgu[2 * D_ * F_ / 8];
__device__ __align__(1024) uint4 g_wd[F_ * D_ / 8];
__device__ uint4 g_rowstat[S_];
__device__ uint4 g_cpart[10 * 12 * 80];
__device__ float g_nrm[96 * 128];
__device__ uint4 g_wm[D_];
__device__ float g_hmean[S_];
__device__ float g_hpart[8 * S_];
__device__ uint4 g_flag[2 * 16 * 2];
__device__ unsigned g_epoch;

__device__ __forceinline__ uint32_t smem_u32(const void* p) { return (uint32_t)__cvta_generic_to_shared(p); }
__device__ __forceinline__ void mbar_init(uint32_t a, uint32_t c) {
  asm volatile("mbarrier.init.shared::cta.b64 [%0], %1;" ::"r"(a), "r"(c) : "memory");
}
__device__ __forceinline__ void mbar_expect(uint32_t a, uint32_t bytes) {
  asm volatile("mbarrier.arrive.expect_tx.shared::cta.b64 _, [%0], %1;" ::"r"(a), "r"(bytes) : "memory");
}
__device__ __forceinline__ void mbar_arrive(uint32_t a) {
  asm volatile("mbarrier.arrive.shared::cta.b64 _, [%0];" ::"r"(a) : "memory");
}
__device__ __forceinline__ void mbar_arrive_cta(uint32_t a, uint32_t cta) {
  asm volatile("{\n.reg .b32 r;\nmapa.shared::cluster.u32 r, %0, %1;\n"
               "mbarrier.arrive.shared::cluster.b64 _, [r];\n}" ::"r"(a), "r"(cta) : "memory");
}
__device__ __forceinline__ bool mbar_try(uint32_t a, uint32_t ph) {
  uint32_t ok;
  asm volatile("{\n.reg .pred p;\nmbarrier.try_wait.parity.shared::cta.b64 p, [%1], %2;\nselp.u32 %0, 1, 0, p;\n}"
               : "=r"(ok) : "r"(a), "r"(ph) : "memory");
  return ok;
}
__device__ __noinline__ void wait_timeout() { __trap(); }
__device__ __forceinline__ void mbar_wait(uint32_t a, uint32_t ph) {
  if (mbar_try(a, ph)) return;
  uint32_t it = 0;
  while (!mbar_try(a, ph)) if (++it > (1u << 22)) wait_timeout();
}
__device__ __forceinline__ void tma2d(uint32_t dst, const CUtensorMap* m, int c0, int c1, uint32_t bar) {
  asm volatile("cp.async.bulk.tensor.2d.shared::cluster.global.mbarrier::complete_tx::bytes [%0], [%1, {%3, %4}], [%2];"
               ::"r"(dst), "l"(m), "r"(bar), "r"(c0), "r"(c1) : "memory");
}
__device__ __forceinline__ void bulk_ld(uint32_t dst, const void* src, uint32_t bytes, uint32_t bar) {
  asm volatile("cp.async.bulk.shared::cluster.global.mbarrier::complete_tx::bytes [%0], [%1], %2, [%3];"
               ::"r"(dst), "l"(src), "r"(bytes), "r"(bar) : "memory");
}
__device__ __forceinline__ void cluster_arrive() { asm volatile("barrier.cluster.arrive.relaxed.aligned;" ::: "memory"); }
__device__ __forceinline__ void cluster_wait() { asm volatile("barrier.cluster.wait.aligned;" ::: "memory"); }
__device__ __forceinline__ void bulk_st(void* dst, uint32_t src, uint32_t bytes) {
  asm volatile("cp.async.bulk.global.shared::cta.bulk_group [%0], [%1], %2;" ::"l"(dst), "r"(src), "r"(bytes) : "memory");
}
__device__ __forceinline__ void tma2d_st(const CUtensorMap* m, int c0, int c1, uint32_t src) {
  asm volatile("cp.async.bulk.tensor.2d.global.shared::cta.bulk_group [%0, {%2, %3}], [%1];"
               ::"l"(m), "r"(src), "r"(c0), "r"(c1) : "memory");
}
__device__ __forceinline__ void bulk_commit_wait() {
  asm volatile("cp.async.bulk.commit_group;\ncp.async.bulk.wait_group.read 0;" ::: "memory");
}
__device__ __forceinline__ uint32_t mapa(uint32_t a, uint32_t cta) {
  uint32_t r;
  asm("mapa.shared::cluster.u32 %0, %1, %2;" : "=r"(r) : "r"(a), "r"(cta));
  return r;
}
__device__ __forceinline__ void st_async4(uint32_t dst, float a, float b, float c, float d, uint32_t bar) {
  asm volatile("st.async.shared::cluster.mbarrier::complete_tx::bytes.v4.f32 [%0], {%1, %2, %3, %4}, [%5];"
               ::"r"(dst), "f"(a), "f"(b), "f"(c), "f"(d), "r"(bar) : "memory");
}
__device__ __forceinline__ void st_async4u(uint32_t dst, uint32_t a, uint32_t b, uint32_t c, uint32_t d, uint32_t bar) {
  asm volatile("st.async.shared::cluster.mbarrier::complete_tx::bytes.v4.b32 [%0], {%1, %2, %3, %4}, [%5];"
               ::"r"(dst), "r"(a), "r"(b), "r"(c), "r"(d), "r"(bar) : "memory");
}
#define SEND8(dst, a, o, bar) st_async4u(dst, pack_bf16(a[o], a[(o) + 1]), pack_bf16(a[(o) + 2], a[(o) + 3]), \
                                         pack_bf16(a[(o) + 4], a[(o) + 5]), pack_bf16(a[(o) + 6], a[(o) + 7]), bar)
__device__ __forceinline__ void fence_async() { asm volatile("fence.proxy.async.shared::cta;" ::: "memory"); }
__device__ __forceinline__ void prefetch_map(const CUtensorMap* m) {
  asm volatile("prefetch.tensormap [%0];" ::"l"(m) : "memory");
}
__device__ __forceinline__ bool elect_one() {
  uint32_t p;
  asm volatile("{\n.reg .pred q;\nelect.sync _|q, 0xffffffff;\nselp.u32 %0, 1, 0, q;\n}" : "=r"(p));
  return p;
}
__device__ __forceinline__ void pdl_wait() { asm volatile("griddepcontrol.wait;" ::: "memory"); }
__device__ __forceinline__ void pdl_trigger() { asm volatile("griddepcontrol.launch_dependents;" ::: "memory"); }
__device__ __forceinline__ void bar_sync(int id, int n) { asm volatile("bar.sync %0, %1;" ::"r"(id), "r"(n) : "memory"); }
__device__ __forceinline__ void bar_arrive(int id, int n) { asm volatile("bar.arrive %0, %1;" ::"r"(id), "r"(n) : "memory"); }
#define WG_FENCE() asm volatile("wgmma.fence.sync.aligned;" ::: "memory")
#define WG_COMMIT() asm volatile("wgmma.commit_group.sync.aligned;" ::: "memory")
#define WG_WAIT(n) asm volatile("wgmma.wait_group.sync.aligned %0;" ::"n"(n) : "memory")
__device__ __forceinline__ uint64_t mkdesc(uint32_t addr, uint32_t lbo, uint32_t sbo, uint32_t sw) {
  return (uint64_t)((addr & 0x3FFFF) >> 4) | ((uint64_t)(lbo >> 4) << 16) | ((uint64_t)(sbo >> 4) << 32) |
         ((uint64_t)sw << 62);
}
template <int N> __device__ __forceinline__ void fence_regs(float (&r)[N]) {
#pragma unroll
  for (int i = 0; i < N; i++) asm volatile("" : "+f"(r[i])::"memory");
}
__device__ __forceinline__ uint32_t pack_bf16(float lo, float hi) {
  uint32_t r;
  asm("cvt.rn.bf16x2.f32 %0, %1, %2;" : "=r"(r) : "f"(hi), "f"(lo));
  return r;
}
__device__ __forceinline__ float bf_lo(uint32_t v) { return __uint_as_float(v << 16); }
__device__ __forceinline__ float bf_hi(uint32_t v) { return __uint_as_float(v & 0xffff0000u); }
__device__ __forceinline__ float ex2(float x) {
  float y;
  asm("ex2.approx.ftz.f32 %0, %1;" : "=f"(y) : "f"(x));
  return y;
}
__device__ __forceinline__ uint4 ldg_nc(const void* p) {
  uint4 v;
  asm volatile("ld.global.nc.L1::no_allocate.v4.u32 {%0, %1, %2, %3}, [%4];"
               : "=r"(v.x), "=r"(v.y), "=r"(v.z), "=r"(v.w) : "l"(p));
  return v;
}

__device__ __forceinline__ uint4 ld_relaxed(const uint4* p) {
  uint64_t a, b;
  asm volatile("ld.relaxed.gpu.global.v2.u64 {%0, %1}, [%2];" : "=l"(a), "=l"(b) : "l"(p) : "memory");
  return make_uint4((uint32_t)a, (uint32_t)(a >> 32), (uint32_t)b, (uint32_t)(b >> 32));
}
__device__ __forceinline__ void st_relaxed(uint4* p, float x, float y, uint32_t tag) {
  const uint64_t a = ((uint64_t)tag << 32) | __float_as_uint(x), b = ((uint64_t)tag << 32) | __float_as_uint(y);
  asm volatile("st.relaxed.gpu.global.v2.u64 [%0], {%1, %2};" ::"l"(p), "l"(a), "l"(b) : "memory");
}
__device__ __forceinline__ void tma4d(uint32_t dst, const CUtensorMap* m, int c2, int c3, uint32_t bar) {
  asm volatile("cp.async.bulk.tensor.4d.shared::cluster.global.mbarrier::complete_tx::bytes [%0], [%1, {%3, %3, %4, %5}], [%2];"
               ::"r"(dst), "l"(m), "r"(bar), "r"(0), "r"(c2), "r"(c3) : "memory");
}
#define ACC8(a, v) do { a[0] += bf_lo(v.x); a[1] += bf_hi(v.x); a[2] += bf_lo(v.y); a[3] += bf_hi(v.y); \
                        a[4] += bf_lo(v.z); a[5] += bf_hi(v.z); a[6] += bf_lo(v.w); a[7] += bf_hi(v.w); } while (0)

__device__ __forceinline__ void wgmma_ss_n224(float (&d)[112], uint64_t da, uint64_t db, int sd) {
  asm volatile("{\n.reg .pred p;\nsetp.ne.b32 p, %114, 0;\n"
      "wgmma.mma_async.sync.aligned.m64n224k16.f32.bf16.bf16 {"
      "%0, %1, %2, %3, %4, %5, %6, %7, %8, %9, %10, %11, %12, %13, %14, %15, "
      "%16, %17, %18, %19, %20, %21, %22, %23, %24, %25, %26, %27, %28, %29, %30, %31, "
      "%32, %33, %34, %35, %36, %37, %38, %39, %40, %41, %42, %43, %44, %45, %46, %47, "
      "%48, %49, %50, %51, %52, %53, %54, %55, %56, %57, %58, %59, %60, %61, %62, %63, "
      "%64, %65, %66, %67, %68, %69, %70, %71, %72, %73, %74, %75, %76, %77, %78, %79, "
      "%80, %81, %82, %83, %84, %85, %86, %87, %88, %89, %90, %91, %92, %93, %94, %95, "
      "%96, %97, %98, %99, %100, %101, %102, %103, %104, %105, %106, %107, %108, %109, %110, %111"
      "}, %112, %113, p, 1, 1, 0, 1;\n}\n"
    : "+f"(d[0]), "+f"(d[1]), "+f"(d[2]), "+f"(d[3]), "+f"(d[4]), "+f"(d[5]), "+f"(d[6]), "+f"(d[7]),
      "+f"(d[8]), "+f"(d[9]), "+f"(d[10]), "+f"(d[11]), "+f"(d[12]), "+f"(d[13]), "+f"(d[14]), "+f"(d[15]),
      "+f"(d[16]), "+f"(d[17]), "+f"(d[18]), "+f"(d[19]), "+f"(d[20]), "+f"(d[21]), "+f"(d[22]), "+f"(d[23]),
      "+f"(d[24]), "+f"(d[25]), "+f"(d[26]), "+f"(d[27]), "+f"(d[28]), "+f"(d[29]), "+f"(d[30]), "+f"(d[31]),
      "+f"(d[32]), "+f"(d[33]), "+f"(d[34]), "+f"(d[35]), "+f"(d[36]), "+f"(d[37]), "+f"(d[38]), "+f"(d[39]),
      "+f"(d[40]), "+f"(d[41]), "+f"(d[42]), "+f"(d[43]), "+f"(d[44]), "+f"(d[45]), "+f"(d[46]), "+f"(d[47]),
      "+f"(d[48]), "+f"(d[49]), "+f"(d[50]), "+f"(d[51]), "+f"(d[52]), "+f"(d[53]), "+f"(d[54]), "+f"(d[55]),
      "+f"(d[56]), "+f"(d[57]), "+f"(d[58]), "+f"(d[59]), "+f"(d[60]), "+f"(d[61]), "+f"(d[62]), "+f"(d[63]),
      "+f"(d[64]), "+f"(d[65]), "+f"(d[66]), "+f"(d[67]), "+f"(d[68]), "+f"(d[69]), "+f"(d[70]), "+f"(d[71]),
      "+f"(d[72]), "+f"(d[73]), "+f"(d[74]), "+f"(d[75]), "+f"(d[76]), "+f"(d[77]), "+f"(d[78]), "+f"(d[79]),
      "+f"(d[80]), "+f"(d[81]), "+f"(d[82]), "+f"(d[83]), "+f"(d[84]), "+f"(d[85]), "+f"(d[86]), "+f"(d[87]),
      "+f"(d[88]), "+f"(d[89]), "+f"(d[90]), "+f"(d[91]), "+f"(d[92]), "+f"(d[93]), "+f"(d[94]), "+f"(d[95]),
      "+f"(d[96]), "+f"(d[97]), "+f"(d[98]), "+f"(d[99]), "+f"(d[100]), "+f"(d[101]), "+f"(d[102]), "+f"(d[103]),
      "+f"(d[104]), "+f"(d[105]), "+f"(d[106]), "+f"(d[107]), "+f"(d[108]), "+f"(d[109]), "+f"(d[110]), "+f"(d[111])
    : "l"(da), "l"(db), "r"(sd));
}
__device__ __forceinline__ void wgmma_ss_n208(float (&d)[104], uint64_t da, uint64_t db, int sd) {
  asm volatile("{\n.reg .pred p;\nsetp.ne.b32 p, %106, 0;\n"
      "wgmma.mma_async.sync.aligned.m64n208k16.f32.bf16.bf16 {"
      "%0, %1, %2, %3, %4, %5, %6, %7, %8, %9, %10, %11, %12, %13, %14, %15, "
      "%16, %17, %18, %19, %20, %21, %22, %23, %24, %25, %26, %27, %28, %29, %30, %31, "
      "%32, %33, %34, %35, %36, %37, %38, %39, %40, %41, %42, %43, %44, %45, %46, %47, "
      "%48, %49, %50, %51, %52, %53, %54, %55, %56, %57, %58, %59, %60, %61, %62, %63, "
      "%64, %65, %66, %67, %68, %69, %70, %71, %72, %73, %74, %75, %76, %77, %78, %79, "
      "%80, %81, %82, %83, %84, %85, %86, %87, %88, %89, %90, %91, %92, %93, %94, %95, "
      "%96, %97, %98, %99, %100, %101, %102, %103"
      "}, %104, %105, p, 1, 1, 0, 1;\n}\n"
    : "+f"(d[0]), "+f"(d[1]), "+f"(d[2]), "+f"(d[3]), "+f"(d[4]), "+f"(d[5]), "+f"(d[6]), "+f"(d[7]),
      "+f"(d[8]), "+f"(d[9]), "+f"(d[10]), "+f"(d[11]), "+f"(d[12]), "+f"(d[13]), "+f"(d[14]), "+f"(d[15]),
      "+f"(d[16]), "+f"(d[17]), "+f"(d[18]), "+f"(d[19]), "+f"(d[20]), "+f"(d[21]), "+f"(d[22]), "+f"(d[23]),
      "+f"(d[24]), "+f"(d[25]), "+f"(d[26]), "+f"(d[27]), "+f"(d[28]), "+f"(d[29]), "+f"(d[30]), "+f"(d[31]),
      "+f"(d[32]), "+f"(d[33]), "+f"(d[34]), "+f"(d[35]), "+f"(d[36]), "+f"(d[37]), "+f"(d[38]), "+f"(d[39]),
      "+f"(d[40]), "+f"(d[41]), "+f"(d[42]), "+f"(d[43]), "+f"(d[44]), "+f"(d[45]), "+f"(d[46]), "+f"(d[47]),
      "+f"(d[48]), "+f"(d[49]), "+f"(d[50]), "+f"(d[51]), "+f"(d[52]), "+f"(d[53]), "+f"(d[54]), "+f"(d[55]),
      "+f"(d[56]), "+f"(d[57]), "+f"(d[58]), "+f"(d[59]), "+f"(d[60]), "+f"(d[61]), "+f"(d[62]), "+f"(d[63]),
      "+f"(d[64]), "+f"(d[65]), "+f"(d[66]), "+f"(d[67]), "+f"(d[68]), "+f"(d[69]), "+f"(d[70]), "+f"(d[71]),
      "+f"(d[72]), "+f"(d[73]), "+f"(d[74]), "+f"(d[75]), "+f"(d[76]), "+f"(d[77]), "+f"(d[78]), "+f"(d[79]),
      "+f"(d[80]), "+f"(d[81]), "+f"(d[82]), "+f"(d[83]), "+f"(d[84]), "+f"(d[85]), "+f"(d[86]), "+f"(d[87]),
      "+f"(d[88]), "+f"(d[89]), "+f"(d[90]), "+f"(d[91]), "+f"(d[92]), "+f"(d[93]), "+f"(d[94]), "+f"(d[95]),
      "+f"(d[96]), "+f"(d[97]), "+f"(d[98]), "+f"(d[99]), "+f"(d[100]), "+f"(d[101]), "+f"(d[102]), "+f"(d[103])
    : "l"(da), "l"(db), "r"(sd));
}
__device__ __forceinline__ void wgmma_ss_n168(float (&d)[84], uint64_t da, uint64_t db, int sd) {
  asm volatile("{\n.reg .pred p;\nsetp.ne.b32 p, %86, 0;\n"
      "wgmma.mma_async.sync.aligned.m64n168k16.f32.bf16.bf16 {"
      "%0, %1, %2, %3, %4, %5, %6, %7, %8, %9, %10, %11, %12, %13, %14, %15, "
      "%16, %17, %18, %19, %20, %21, %22, %23, %24, %25, %26, %27, %28, %29, %30, %31, "
      "%32, %33, %34, %35, %36, %37, %38, %39, %40, %41, %42, %43, %44, %45, %46, %47, "
      "%48, %49, %50, %51, %52, %53, %54, %55, %56, %57, %58, %59, %60, %61, %62, %63, "
      "%64, %65, %66, %67, %68, %69, %70, %71, %72, %73, %74, %75, %76, %77, %78, %79, "
      "%80, %81, %82, %83"
      "}, %84, %85, p, 1, 1, 0, 1;\n}\n"
    : "+f"(d[0]), "+f"(d[1]), "+f"(d[2]), "+f"(d[3]), "+f"(d[4]), "+f"(d[5]), "+f"(d[6]), "+f"(d[7]),
      "+f"(d[8]), "+f"(d[9]), "+f"(d[10]), "+f"(d[11]), "+f"(d[12]), "+f"(d[13]), "+f"(d[14]), "+f"(d[15]),
      "+f"(d[16]), "+f"(d[17]), "+f"(d[18]), "+f"(d[19]), "+f"(d[20]), "+f"(d[21]), "+f"(d[22]), "+f"(d[23]),
      "+f"(d[24]), "+f"(d[25]), "+f"(d[26]), "+f"(d[27]), "+f"(d[28]), "+f"(d[29]), "+f"(d[30]), "+f"(d[31]),
      "+f"(d[32]), "+f"(d[33]), "+f"(d[34]), "+f"(d[35]), "+f"(d[36]), "+f"(d[37]), "+f"(d[38]), "+f"(d[39]),
      "+f"(d[40]), "+f"(d[41]), "+f"(d[42]), "+f"(d[43]), "+f"(d[44]), "+f"(d[45]), "+f"(d[46]), "+f"(d[47]),
      "+f"(d[48]), "+f"(d[49]), "+f"(d[50]), "+f"(d[51]), "+f"(d[52]), "+f"(d[53]), "+f"(d[54]), "+f"(d[55]),
      "+f"(d[56]), "+f"(d[57]), "+f"(d[58]), "+f"(d[59]), "+f"(d[60]), "+f"(d[61]), "+f"(d[62]), "+f"(d[63]),
      "+f"(d[64]), "+f"(d[65]), "+f"(d[66]), "+f"(d[67]), "+f"(d[68]), "+f"(d[69]), "+f"(d[70]), "+f"(d[71]),
      "+f"(d[72]), "+f"(d[73]), "+f"(d[74]), "+f"(d[75]), "+f"(d[76]), "+f"(d[77]), "+f"(d[78]), "+f"(d[79]),
      "+f"(d[80]), "+f"(d[81]), "+f"(d[82]), "+f"(d[83])
    : "l"(da), "l"(db), "r"(sd));
}
__device__ __forceinline__ void wgmma_ss_n160(float (&d)[80], uint64_t da, uint64_t db, int sd) {
  asm volatile("{\n.reg .pred p;\nsetp.ne.b32 p, %82, 0;\n"
      "wgmma.mma_async.sync.aligned.m64n160k16.f32.bf16.bf16 {"
      "%0, %1, %2, %3, %4, %5, %6, %7, %8, %9, %10, %11, %12, %13, %14, %15, "
      "%16, %17, %18, %19, %20, %21, %22, %23, %24, %25, %26, %27, %28, %29, %30, %31, "
      "%32, %33, %34, %35, %36, %37, %38, %39, %40, %41, %42, %43, %44, %45, %46, %47, "
      "%48, %49, %50, %51, %52, %53, %54, %55, %56, %57, %58, %59, %60, %61, %62, %63, "
      "%64, %65, %66, %67, %68, %69, %70, %71, %72, %73, %74, %75, %76, %77, %78, %79"
      "}, %80, %81, p, 1, 1, 0, 1;\n}\n"
    : "+f"(d[0]), "+f"(d[1]), "+f"(d[2]), "+f"(d[3]), "+f"(d[4]), "+f"(d[5]), "+f"(d[6]), "+f"(d[7]),
      "+f"(d[8]), "+f"(d[9]), "+f"(d[10]), "+f"(d[11]), "+f"(d[12]), "+f"(d[13]), "+f"(d[14]), "+f"(d[15]),
      "+f"(d[16]), "+f"(d[17]), "+f"(d[18]), "+f"(d[19]), "+f"(d[20]), "+f"(d[21]), "+f"(d[22]), "+f"(d[23]),
      "+f"(d[24]), "+f"(d[25]), "+f"(d[26]), "+f"(d[27]), "+f"(d[28]), "+f"(d[29]), "+f"(d[30]), "+f"(d[31]),
      "+f"(d[32]), "+f"(d[33]), "+f"(d[34]), "+f"(d[35]), "+f"(d[36]), "+f"(d[37]), "+f"(d[38]), "+f"(d[39]),
      "+f"(d[40]), "+f"(d[41]), "+f"(d[42]), "+f"(d[43]), "+f"(d[44]), "+f"(d[45]), "+f"(d[46]), "+f"(d[47]),
      "+f"(d[48]), "+f"(d[49]), "+f"(d[50]), "+f"(d[51]), "+f"(d[52]), "+f"(d[53]), "+f"(d[54]), "+f"(d[55]),
      "+f"(d[56]), "+f"(d[57]), "+f"(d[58]), "+f"(d[59]), "+f"(d[60]), "+f"(d[61]), "+f"(d[62]), "+f"(d[63]),
      "+f"(d[64]), "+f"(d[65]), "+f"(d[66]), "+f"(d[67]), "+f"(d[68]), "+f"(d[69]), "+f"(d[70]), "+f"(d[71]),
      "+f"(d[72]), "+f"(d[73]), "+f"(d[74]), "+f"(d[75]), "+f"(d[76]), "+f"(d[77]), "+f"(d[78]), "+f"(d[79])
    : "l"(da), "l"(db), "r"(sd));
}
__device__ __forceinline__ void wgmma_ss_n88(float (&d)[44], uint64_t da, uint64_t db, int sd) {
  asm volatile("{\n.reg .pred p;\nsetp.ne.b32 p, %46, 0;\n"
      "wgmma.mma_async.sync.aligned.m64n88k16.f32.bf16.bf16 {"
      "%0, %1, %2, %3, %4, %5, %6, %7, %8, %9, %10, %11, %12, %13, %14, %15, "
      "%16, %17, %18, %19, %20, %21, %22, %23, %24, %25, %26, %27, %28, %29, %30, %31, "
      "%32, %33, %34, %35, %36, %37, %38, %39, %40, %41, %42, %43"
      "}, %44, %45, p, 1, 1, 0, 1;\n}\n"
    : "+f"(d[0]), "+f"(d[1]), "+f"(d[2]), "+f"(d[3]), "+f"(d[4]), "+f"(d[5]), "+f"(d[6]), "+f"(d[7]),
      "+f"(d[8]), "+f"(d[9]), "+f"(d[10]), "+f"(d[11]), "+f"(d[12]), "+f"(d[13]), "+f"(d[14]), "+f"(d[15]),
      "+f"(d[16]), "+f"(d[17]), "+f"(d[18]), "+f"(d[19]), "+f"(d[20]), "+f"(d[21]), "+f"(d[22]), "+f"(d[23]),
      "+f"(d[24]), "+f"(d[25]), "+f"(d[26]), "+f"(d[27]), "+f"(d[28]), "+f"(d[29]), "+f"(d[30]), "+f"(d[31]),
      "+f"(d[32]), "+f"(d[33]), "+f"(d[34]), "+f"(d[35]), "+f"(d[36]), "+f"(d[37]), "+f"(d[38]), "+f"(d[39]),
      "+f"(d[40]), "+f"(d[41]), "+f"(d[42]), "+f"(d[43])
    : "l"(da), "l"(db), "r"(sd));
}
__device__ __forceinline__ void wgmma_ss_n80(float (&d)[40], uint64_t da, uint64_t db, int sd) {
  asm volatile("{\n.reg .pred p;\nsetp.ne.b32 p, %42, 0;\n"
      "wgmma.mma_async.sync.aligned.m64n80k16.f32.bf16.bf16 {"
      "%0, %1, %2, %3, %4, %5, %6, %7, %8, %9, %10, %11, %12, %13, %14, %15, "
      "%16, %17, %18, %19, %20, %21, %22, %23, %24, %25, %26, %27, %28, %29, %30, %31, "
      "%32, %33, %34, %35, %36, %37, %38, %39"
      "}, %40, %41, p, 1, 1, 0, 1;\n}\n"
    : "+f"(d[0]), "+f"(d[1]), "+f"(d[2]), "+f"(d[3]), "+f"(d[4]), "+f"(d[5]), "+f"(d[6]), "+f"(d[7]),
      "+f"(d[8]), "+f"(d[9]), "+f"(d[10]), "+f"(d[11]), "+f"(d[12]), "+f"(d[13]), "+f"(d[14]), "+f"(d[15]),
      "+f"(d[16]), "+f"(d[17]), "+f"(d[18]), "+f"(d[19]), "+f"(d[20]), "+f"(d[21]), "+f"(d[22]), "+f"(d[23]),
      "+f"(d[24]), "+f"(d[25]), "+f"(d[26]), "+f"(d[27]), "+f"(d[28]), "+f"(d[29]), "+f"(d[30]), "+f"(d[31]),
      "+f"(d[32]), "+f"(d[33]), "+f"(d[34]), "+f"(d[35]), "+f"(d[36]), "+f"(d[37]), "+f"(d[38]), "+f"(d[39])
    : "l"(da), "l"(db), "r"(sd));
}
__device__ __forceinline__ void wgmma_rs_n128(float (&d)[64], uint32_t a0, uint32_t a1, uint32_t a2, uint32_t a3,
                                  uint64_t db, int sd) {
  asm volatile("{\n.reg .pred p;\nsetp.ne.b32 p, %69, 0;\n"
      "wgmma.mma_async.sync.aligned.m64n128k16.f32.bf16.bf16 {"
      "%0, %1, %2, %3, %4, %5, %6, %7, %8, %9, %10, %11, %12, %13, %14, %15, "
      "%16, %17, %18, %19, %20, %21, %22, %23, %24, %25, %26, %27, %28, %29, %30, %31, "
      "%32, %33, %34, %35, %36, %37, %38, %39, %40, %41, %42, %43, %44, %45, %46, %47, "
      "%48, %49, %50, %51, %52, %53, %54, %55, %56, %57, %58, %59, %60, %61, %62, %63"
      "}, {%64, %65, %66, %67}, %68, p, 1, 1, 0;\n}\n"
    : "+f"(d[0]), "+f"(d[1]), "+f"(d[2]), "+f"(d[3]), "+f"(d[4]), "+f"(d[5]), "+f"(d[6]), "+f"(d[7]),
      "+f"(d[8]), "+f"(d[9]), "+f"(d[10]), "+f"(d[11]), "+f"(d[12]), "+f"(d[13]), "+f"(d[14]), "+f"(d[15]),
      "+f"(d[16]), "+f"(d[17]), "+f"(d[18]), "+f"(d[19]), "+f"(d[20]), "+f"(d[21]), "+f"(d[22]), "+f"(d[23]),
      "+f"(d[24]), "+f"(d[25]), "+f"(d[26]), "+f"(d[27]), "+f"(d[28]), "+f"(d[29]), "+f"(d[30]), "+f"(d[31]),
      "+f"(d[32]), "+f"(d[33]), "+f"(d[34]), "+f"(d[35]), "+f"(d[36]), "+f"(d[37]), "+f"(d[38]), "+f"(d[39]),
      "+f"(d[40]), "+f"(d[41]), "+f"(d[42]), "+f"(d[43]), "+f"(d[44]), "+f"(d[45]), "+f"(d[46]), "+f"(d[47]),
      "+f"(d[48]), "+f"(d[49]), "+f"(d[50]), "+f"(d[51]), "+f"(d[52]), "+f"(d[53]), "+f"(d[54]), "+f"(d[55]),
      "+f"(d[56]), "+f"(d[57]), "+f"(d[58]), "+f"(d[59]), "+f"(d[60]), "+f"(d[61]), "+f"(d[62]), "+f"(d[63])
    : "r"(a0), "r"(a1), "r"(a2), "r"(a3), "l"(db), "r"(sd));
}
__device__ __forceinline__ void wgmma_rs_n24(float (&d)[12], uint32_t a0, uint32_t a1, uint32_t a2, uint32_t a3,
                                  uint64_t db, int sd) {
  asm volatile("{\n.reg .pred p;\nsetp.ne.b32 p, %17, 0;\n"
      "wgmma.mma_async.sync.aligned.m64n24k16.f32.bf16.bf16 {"
      "%0, %1, %2, %3, %4, %5, %6, %7, %8, %9, %10, %11"
      "}, {%12, %13, %14, %15}, %16, p, 1, 1, 1;\n}\n"
    : "+f"(d[0]), "+f"(d[1]), "+f"(d[2]), "+f"(d[3]), "+f"(d[4]), "+f"(d[5]), "+f"(d[6]), "+f"(d[7]),
      "+f"(d[8]), "+f"(d[9]), "+f"(d[10]), "+f"(d[11])
    : "r"(a0), "r"(a1), "r"(a2), "r"(a3), "l"(db), "r"(sd));
}

constexpr int KST = 4;
constexpr int K1_ST = 4, K1_STAGE = 45056;
constexpr int K1_SMEM = K1_ST * K1_STAGE + 640   + 1536   + 2560   + 128;

__device__ __forceinline__ float2 row_stats(uint4 v0, uint4 v1, uint4 v2) {
  const uint32_t wd[12] = {v0.x, v0.y, v0.z, v0.w, v1.x, v1.y, v1.z, v1.w, v2.x, v2.y, v2.z, v2.w};
  float sx = 0.f, sq = 0.f;
#pragma unroll
  for (int e = 0; e < 12; e++) {
    const float lo = bf_lo(wd[e]), hi = bf_hi(wd[e]);
    sx += lo + hi; sq = fmaf(lo, lo, fmaf(hi, hi, sq));
  }
#pragma unroll
  for (int o = 16; o; o >>= 1) { sx += __shfl_xor_sync(~0u, sx, o); sq += __shfl_xor_sync(~0u, sq, o); }
  const float mean = sx * (1.f / D_);
  return make_float2(rsqrtf(fmaxf(sq * (1.f / D_) - mean * mean, 0.f) + 1e-5f), mean);
}

__global__ void __launch_bounds__(512, 1)
k1_qkv(const __grid_constant__ CUtensorMap tmx, const __grid_constant__ CUtensorMap tmw,
       const bf16* __restrict__ x, const bf16* __restrict__ w) {
  extern __shared__ __align__(1024) uint8_t sm[];
  float* cs = (float*)(sm + K1_ST * K1_STAGE);
  float2* rowab = (float2*)(sm + K1_ST * K1_STAGE + 640);
  float* red = (float*)(sm + K1_ST * K1_STAGE + 2176);
  const uint32_t sbase = smem_u32(sm);
  const uint32_t fullb = sbase + K1_ST * K1_STAGE + 4736, emptyb = fullb + 8 * K1_ST;
  const int tid = threadIdx.x, lane = tid & 31;
  const int warp = __shfl_sync(~0u, tid >> 5, 0);
  const int m = blockIdx.x / 12, n = blockIdx.x - m * 12;

  if (warp == 12) {
    if (lane == 0) {
      prefetch_map(&tmx); prefetch_map(&tmw);
      for (int i = 0; i < K1_ST; i++) { mbar_init(fullb + 8 * i, 1); mbar_init(emptyb + 8 * i, 3); }
      asm volatile("fence.mbarrier_init.release.cluster;" ::: "memory");
    }
    __syncwarp();
    bar_arrive(4, 512);
#pragma unroll 1
    for (int kt = 0; kt < 10; kt++) {
      const int s = kt % K1_ST;
      const uint32_t sa = sbase + s * K1_STAGE;
      if (kt >= K1_ST) mbar_wait(emptyb + 8 * s, ((kt / K1_ST) - 1) & 1);
      if (elect_one()) {
        mbar_expect(fullb + 8 * s, K1_STAGE);
        tma2d(sa, &tmx, kt * 64, m * 192, fullb + 8 * s);
#pragma unroll
        for (int j = 0; j < 5; j++) tma2d(sa + 24576 + j * 4096, &tmw, n * 160 + j * 32, kt * 64, fullb + 8 * s);
      }
      if (kt == K1_ST - 1) pdl_trigger();
    }
    __syncwarp();
  } else if (warp > 12) {
    const int t96 = tid - 416;
    const uint32_t tag = __ldcg(&g_epoch) + 1;
    bar_sync(4, 512);
    mbar_wait(fullb, 0);
    if (m < 10) {
      const int ck = t96 % 20, rg = min(t96 / 20, 3);
      uint4 wv[16];
#pragma unroll
      for (int i = 0; i < 16; i++) wv[i] = ldg_nc(w + (size_t)(m * 64 + rg * 16 + i) * 1920 + n * 160 + ck * 8);
      float acc8[8];
#pragma unroll
      for (int i = 0; i < 8; i++) acc8[i] = 0.f;
#pragma unroll
      for (int i = 0; i < 16; i++) ACC8(acc8, wv[i]);
      *(float4*)&red[rg * 160 + ck * 8] = make_float4(acc8[0], acc8[1], acc8[2], acc8[3]);
      *(float4*)&red[rg * 160 + ck * 8 + 4] = make_float4(acc8[4], acc8[5], acc8[6], acc8[7]);
      bar_sync(1, 96);
      if (t96 < 80) {
        const float2 p0 = *(const float2*)&red[t96 * 2], p1 = *(const float2*)&red[160 + t96 * 2];
        const float2 p2 = *(const float2*)&red[320 + t96 * 2], p3 = *(const float2*)&red[480 + t96 * 2];
        st_relaxed(&g_cpart[(m * 12 + n) * 80 + t96], (p0.x + p1.x) + (p2.x + p3.x), (p0.y + p1.y) + (p2.y + p3.y), tag);
      }
    }
    bool ok = false;
    for (int it = 0; it < 64 && !ok; it++) {
      uint4 p[10], st[2];
#pragma unroll
      for (int k = 0; k < 10; k++) p[k] = ld_relaxed(&g_cpart[(k * 12 + n) * 80 + min(t96, 79)]);
#pragma unroll
      for (int k = 0; k < 2; k++) st[k] = ld_relaxed(&g_rowstat[min(m * 192 + k * 96 + t96, S_ - 1)]);
      ok = true;
      float s0 = 0.f, s1 = 0.f;
#pragma unroll
      for (int k = 0; k < 10; k++) {
        ok = ok && p[k].y == tag && p[k].w == tag;
        s0 += __uint_as_float(p[k].x); s1 += __uint_as_float(p[k].z);
      }
      if (t96 < 80) *(float2*)&cs[t96 * 2] = make_float2(s0, s1);
#pragma unroll
      for (int k = 0; k < 2; k++) {
        ok = ok && st[k].y == tag && st[k].w == tag;
        rowab[k * 96 + t96] = make_float2(__uint_as_float(st[k].x), -__uint_as_float(st[k].x) * __uint_as_float(st[k].z));
      }
      ok = __all_sync(~0u, ok);
      if (!ok) __nanosleep(300);
    }
    if (!ok) {
      const int c2 = min(t96, 79);
      float s0 = 0.f, s1 = 0.f;
#pragma unroll 1
      for (int k = 0; k < D_; k++) {
        const uint32_t v = *(const uint32_t*)(w + (size_t)k * 1920 + n * 160 + c2 * 2);
        s0 += bf_lo(v); s1 += bf_hi(v);
      }
      if (t96 < 80) *(float2*)&cs[t96 * 2] = make_float2(s0, s1);
#pragma unroll 1
      for (int i = 0; i < 64; i++) {
        const int r = (i >> 5) * 96 + (t96 & ~31) + (i & 31);
        const bf16* xr = x + (size_t)min(m * 192 + r, S_ - 1) * D_ + lane * 8;
        const float2 st = row_stats(ldg_nc(xr), ldg_nc(xr + 256), lane < 16 ? ldg_nc(xr + 512) : make_uint4(0u, 0u, 0u, 0u));
        if (lane == 0) rowab[r] = make_float2(st.x, -st.x * st.y);
      }
    }
    __syncwarp();
    bar_arrive(2, 96 + 384);
    __syncwarp();
  } else {
    float acc[80];
    const uint64_t da0 = mkdesc(sbase + (warp >> 2) * 8192, 16, 1024, 1);
    const uint64_t db0 = mkdesc(sbase + 24576, 4096, 512, 2);
    const uint32_t tag = __ldcg(&g_epoch) + 1;
    const int srow = m * 192 + n * 16 + warp * 2;
    const bool dostat = warp < 8 && srow < S_;
    uint4 xv[2][3];
    bar_sync(4, 512);
#pragma unroll
    for (int kt = 0; kt < 10; kt++) {
      const int s = kt % K1_ST;
      mbar_wait(fullb + 8 * s, (kt / K1_ST) & 1);
      const uint64_t da = da0 + s * (K1_STAGE >> 4), db = db0 + s * (K1_STAGE >> 4);
      WG_FENCE();
#pragma unroll
      for (int k = 0; k < 4; k++) wgmma_ss_n160(acc, da + k * 2, db + k * 64, (kt | k) != 0);
      WG_COMMIT();
      if (kt > 0) {
        WG_WAIT(1);
        if (kt - 1 + K1_ST < 10 && (tid & 127) == 0) mbar_arrive(emptyb + 8 * ((kt - 1) % K1_ST));
      }
      if (kt == 0) {
#pragma unroll
        for (int i = 0; i < 2; i++) {
          const bf16* xr = x + (size_t)min(srow + i, S_ - 1) * D_ + lane * 8;
          xv[i][0] = xv[i][1] = xv[i][2] = make_uint4(0u, 0u, 0u, 0u);
          if (dostat) { xv[i][0] = ldg_nc(xr); xv[i][1] = ldg_nc(xr + 256); }
          if (dostat && lane < 16) xv[i][2] = ldg_nc(xr + 512);
        }
      }
      if ((kt == KST || kt == KST + 1) && dostat) {
        const float2 st = row_stats(xv[kt - KST][0], xv[kt - KST][1], xv[kt - KST][2]);
        if (lane == 0) st_relaxed(&g_rowstat[srow + kt - KST], st.x, st.y, tag);
      }
      __syncwarp();
    }
    WG_WAIT(0);
    fence_regs(acc);
    bar_sync(2, 96 + 384);
    const int row0 = m * 192 + warp * 16;
    if (row0 < S_) {
      const int g = lane >> 2, c = lane & 3, sec = n >> 2, grp = (row0 & 127) >> 3;
      const bool lo = c < 2;
      const float2 ab0 = rowab[warp * 16 + g], ab1 = rowab[warp * 16 + g + 8];
      const bool p0 = sec == 1 && ((POLY_MASK >> grp) & 1), p1 = sec == 1 && ((POLY_MASK >> (grp + 1)) & 1);
      const uint32_t padqv = sec == 0 ? (c == 2 ? 0x3F803F80u : 0x00003F80u) : (sec == 2 && c == 2 ? 0x00003F80u : 0u);
      const uint32_t padk = c == 2 ? 0x4A7A4B00u : 0x00004653u;
      const uint32_t pad0 = p0 ? padk : padqv, pad1 = p1 ? padk : padqv;
      const float f0 = sec == 0 ? QSCALE : (p0 ? 32768.f : 1.f), f1 = sec == 0 ? QSCALE : (p1 ? 32768.f : 1.f);
      const float a0 = ab0.x * f0, b0 = ab0.y * f0, a1 = ab1.x * f1, b1 = ab1.y * f1;
      const float r0 = p0 ? 9.313225746154785e-10f : 1.f, r1 = p1 ? 9.313225746154785e-10f : 1.f;
      const int cst = sec == 1 ? 2048 : 128, gst = sec == 1 ? 128 : 384;
      uint8_t* pe = (uint8_t*)g_qkv + (size_t)(n * 8) * HEAD_IMG + (row0 >> 7) * 6144 + grp * gst + lane * 4;
      uint8_t* pe1 = pe + cst;
      uint8_t* pe2 = pe1 + cst;
      uint8_t* pf = pe + gst;
      uint8_t* pf1 = pf + cst;
      uint8_t* pf2 = pf1 + cst;
      uint32_t u[20], v[20];
#pragma unroll
      for (int hp = 0; hp < 4; hp++) {
#pragma unroll
        for (int j = hp * 5; j < hp * 5 + 5; j++) {
          const float2 t = *(const float2*)&cs[j * 8 + c * 2];
          u[j] = pack_bf16(fmaf(acc[4 * j], a0, b0 * t.x), fmaf(acc[4 * j + 1], a0, b0 * t.y));
          v[j] = pack_bf16(fmaf(acc[4 * j + 2], a1, b1 * t.x), fmaf(acc[4 * j + 3], a1, b1 * t.y));
        }
        constexpr int HE = HEAD_IMG;
        const int oe = hp * 2 * HE, oo = oe + HE, j = hp * 5;
        *(uint32_t*)(pe + oe) = u[j];      *(uint32_t*)(pf + oe) = v[j];
        *(uint32_t*)(pe1 + oe) = u[j + 1]; *(uint32_t*)(pf1 + oe) = v[j + 1];
        *(uint32_t*)(pe2 + oe) = lo ? u[j + 2] : pad0; *(uint32_t*)(pf2 + oe) = lo ? v[j + 2] : pad1;
        *(uint32_t*)(pe + oo) = __shfl_xor_sync(~0u, lo ? u[j + 3] : u[j + 2], 2);
        *(uint32_t*)(pf + oo) = __shfl_xor_sync(~0u, lo ? v[j + 3] : v[j + 2], 2);
        *(uint32_t*)(pe1 + oo) = __shfl_xor_sync(~0u, lo ? u[j + 4] : u[j + 3], 2);
        *(uint32_t*)(pf1 + oo) = __shfl_xor_sync(~0u, lo ? v[j + 4] : v[j + 3], 2);
        const uint32_t tu = __shfl_xor_sync(~0u, u[j + 4], 2), tv = __shfl_xor_sync(~0u, v[j + 4], 2);
        *(uint32_t*)(pe2 + oo) = lo ? tu : pad0; *(uint32_t*)(pf2 + oo) = lo ? tv : pad1;
      }
      {
        float nm = 0.f;
#pragma unroll
        for (int hp = 0; hp < 4; hp++) {
          float sq[2][5];
#pragma unroll
          for (int i = 0; i < 5; i++) {
            const uint32_t x = u[hp * 5 + i], y = v[hp * 5 + i];
            sq[0][i] = fmaf(bf_lo(x), bf_lo(x), bf_hi(x) * bf_hi(x));
            sq[1][i] = fmaf(bf_lo(y), bf_lo(y), bf_hi(y) * bf_hi(y));
          }
          const float e0 = (sq[0][0] + sq[0][1] + (lo ? sq[0][2] : 0.f)) * r0, e1 = (sq[1][0] + sq[1][1] + (lo ? sq[1][2] : 0.f)) * r1;
          const float o0 = (sq[0][3] + sq[0][4] + (lo ? 0.f : sq[0][2])) * r0, o1 = (sq[1][3] + sq[1][4] + (lo ? 0.f : sq[1][2])) * r1;
          const float k0 = (lo ? e0 : o0) + __shfl_xor_sync(~0u, lo ? o0 : e0, 2);
          const float k1 = (lo ? e1 : o1) + __shfl_xor_sync(~0u, lo ? o1 : e1, 2);
          const float z = ((c & 1) ? k1 : k0) + __shfl_xor_sync(~0u, (c & 1) ? k0 : k1, 1);
          const uint32_t em = __reduce_max_sync(~0u, lo ? __float_as_uint(z) : 0u), om = __reduce_max_sync(~0u, lo ? 0u : __float_as_uint(z));
          if ((lane >> 1) == hp) nm = __uint_as_float((lane & 1) ? om : em);
        }
        if (lane < 8) g_nrm[(n * 8 + lane) * 128 + (row0 >> 4)] = nm;
      }
    }
  }
}

constexpr int K2_SMEM = 2 * HEAD_IMG + 2 * 6144 + 2 * 10240 + 160 + 96;

__device__ __forceinline__ uint64_t desc64(uint32_t lo, uint32_t hi) {
  uint64_t d;
  asm("mov.b64 %0, {%1, %2};" : "=l"(d) : "r"(lo), "r"(hi));
  return d;
}
__device__ __forceinline__ uint32_t exp_pair(bool poly, float a, float b, uint32_t mk) {
  if (poly) {
    const uint32_t pk = __byte_perm(__float_as_uint(a), __float_as_uint(b), 0x6521);
    uint32_t m, q;
    asm("lop3.b32 %0, %1, %2, 0x3f803f80, 0xEA;" : "=r"(m) : "r"(pk), "r"(mk));
    asm("fma.rn.bf16x2 %0, %1, %1, %2;" : "=r"(q) : "r"(m), "r"(0x40014001u));
    return pk - m + q;
  }
  return pack_bf16(ex2(a), ex2(b));
}
constexpr int PV_GR = 4;
__device__ __forceinline__ void exp_pv(const float (&s)[64], float (&o)[12], uint64_t dv, uint32_t mk) {
#pragma unroll
  for (int k0 = 0; k0 < 8; k0 += PV_GR) {
    uint32_t p[4 * PV_GR];
#pragma unroll
    for (int i = 0; i < 4 * PV_GR; i++)
      p[i] = exp_pair((POLY_MASK >> (k0 * 2 + i / 2)) & 1, s[k0 * 8 + 2 * i], s[k0 * 8 + 2 * i + 1], mk);
    WG_FENCE();
#pragma unroll
    for (int k = 0; k < PV_GR; k++)
      wgmma_rs_n24(o, p[4 * k], p[4 * k + 1], p[4 * k + 2], p[4 * k + 3], dv + (k0 + k) * 48, 1);
  }
}
__device__ __forceinline__ void load_q(uint32_t (&q)[6], const uint8_t* p) {
  q[0] = __ldcg((const uint32_t*)p);         q[1] = __ldcg((const uint32_t*)(p + 384));
  q[2] = __ldcg((const uint32_t*)(p + 128)); q[3] = __ldcg((const uint32_t*)(p + 512));
  q[4] = __ldcg((const uint32_t*)(p + 256)); q[5] = __ldcg((const uint32_t*)(p + 640));
}
__device__ __forceinline__ float rcp(float x) {
  float y;
  asm("rcp.approx.ftz.f32 %0, %1;" : "=f"(y) : "f"(x));
  return y;
}
__device__ __forceinline__ int img_off(int chunk) { return chunk * 2048; }
__device__ __forceinline__ void store_o(const float (&o)[12], int tile) {
  int tid, bid;
  asm volatile("mov.u32 %0, %%tid.x;" : "=r"(tid));
  asm volatile("mov.u32 %0, %%ctaid.x;" : "=r"(bid));
  const int head = bid >> 2;
  uint8_t* dst = (uint8_t*)g_o + ((bid & 3) * 4 + (tile >> 1)) * 163840 + (tile & 1) * 1024 + ((tid >> 5) & 3) * 256 + (tid & 31) * 4;
  const int oc = (head >> 1) * 5 + (head & 1) * 2;
  const int o0 = img_off(oc), o1 = img_off(oc + 1), o2 = img_off((head >> 1) * 5 + 4) + (head & 1) * 8;
  const float i0 = rcp(__shfl_sync(~0u, o[8], 2, 4)), i1 = rcp(__shfl_sync(~0u, o[10], 2, 4));
  *(uint32_t*)(dst + o0) = pack_bf16(o[0] * i0, o[1] * i0); *(uint32_t*)(dst + o0 + 128) = pack_bf16(o[2] * i1, o[3] * i1);
  *(uint32_t*)(dst + o1) = pack_bf16(o[4] * i0, o[5] * i0); *(uint32_t*)(dst + o1 + 128) = pack_bf16(o[6] * i1, o[7] * i1);
  if ((tid & 3) < 2) {
    *(uint32_t*)(dst + o2) = pack_bf16(o[8] * i0, o[9] * i0);
    *(uint32_t*)(dst + o2 + 128) = pack_bf16(o[10] * i1, o[11] * i1);
  }
}

struct Maps5 { CUtensorMap m[5]; };

__global__ void __launch_bounds__(512, 1)
k2_attn(const __grid_constant__ Maps5 maps, const bf16* __restrict__ wo, uint32_t mk) {
  const CUtensorMap* tmw = maps.m;
  extern __shared__ __align__(1024) uint8_t sm[];
  const uint32_t sbase = smem_u32(sm);
  float* part = (float*)(sm + 2 * HEAD_IMG);
  const uint32_t rbuf = sbase + 2 * HEAD_IMG + 2 * 6144;
  const uint32_t kvb = rbuf + 2 * 10240;
  const uint32_t partb = kvb + 128, rbar = kvb + 144;
  const int tid = threadIdx.x, lane = tid & 31;
  const int warp = __shfl_sync(~0u, tid >> 5, 0);
  const int head = blockIdx.x >> 2, qb = blockIdx.x & 3;

  if (tid == 0) {
    for (int i = 0; i < 16; i++) mbar_init(kvb + 8 * i, 1);
    mbar_init(partb, 128); mbar_init(partb + 8, 128); mbar_init(rbar, 1); mbar_init(rbar + 8, 1);
    asm volatile("fence.mbarrier_init.release.cluster;" ::: "memory");
  }
  __syncthreads();

  if (warp >= 12) {
    asm volatile("setmaxnreg.dec.sync.aligned.u32 32;");
    if (warp == 12) {
      const uint8_t* kimg = (const uint8_t*)g_qkv + (size_t)(32 + head) * HEAD_IMG;
      if (elect_one()) {
#pragma unroll
        for (int b = 0; b < 16; b++) mbar_expect(kvb + 8 * b, 12288);
      }
      pdl_wait();
#pragma unroll 1
      for (int b = 0; b < 16; b++) {
        if (elect_one()) {
          bulk_ld(sbase + b * 6144, kimg + b * 6144, 6144, kvb + 8 * b);
          bulk_ld(sbase + HEAD_IMG + b * 6144, kimg + 32 * HEAD_IMG + b * 6144, 6144, kvb + 8 * b);
        }
        if (b >= 2) mbar_wait(kvb + 8 * (b - 1), 0);
      }
      pdl_trigger();
    }
    if (warp > 12) {
      const int t96 = tid - 416, ck = min(t96, 79), nt = ck / 10;
      float* red = (float*)(sm + K2_SMEM - 96);
#pragma unroll 1
      for (int i = 0; i < 5; i++) {
        const int k = blockIdx.x * 5 + i, pr = k / 40, r = k - pr * 40;
        const uint4 v = ldg_nc(wo + (pr * 40 + (r < 16 ? r : (r < 32 ? r + 4 : (r < 36 ? r - 16 : r)))) * D_ + ck * 8);
        g_wo[((nt * 10 + (k >> 6)) * 10 + ck - nt * 10) * 64 + (k & 63)] = v;
        float t = ((bf_lo(v.x) + bf_hi(v.x)) + (bf_lo(v.y) + bf_hi(v.y))) + ((bf_lo(v.z) + bf_hi(v.z)) + (bf_lo(v.w) + bf_hi(v.w)));
        if (t96 >= 80) t = 0.f;
#pragma unroll
        for (int o = 16; o; o >>= 1) t += __shfl_xor_sync(~0u, t, o);
        if (lane == 0) red[(t96 >> 5) * 8 + i] = t;
      }
      bar_sync(1, 96);
      if (t96 < 5) {
        const float mu = (red[t96] + red[8 + t96] + red[16 + t96]) * (1.f / D_);
        const float hi = bf_lo(pack_bf16(mu, 0.f));
        g_wm[blockIdx.x * 5 + t96] = make_uint4(pack_bf16(hi, mu - hi), 0u, 0u, 0u);
      }
    }
    if (tid == 384) {
      if (blockIdx.x == 0) g_epoch = g_epoch + 1;
      mbar_wait(kvb + 8 * 15, 0);
      uint8_t* pdst = nullptr;
      uint32_t pbytes = 0;
#pragma unroll 1
      for (int i = 0; i < 8; i++) {
        const int p = blockIdx.x + 128 * i;
        uint8_t* dst = nullptr;
        uint32_t bytes = 0;
        if (i < 7 && p < 856) {
          asm volatile("cp.async.bulk.wait_group.read 0;" ::: "memory");
          const CUtensorMap* tm;
          int c1, c2;
          if (p < 640) {
            const int nt = p / 80, r = p - nt * 80, ph = r / 40, st = (r - ph * 40) >> 1, up = r & 1;
            bytes = ph ? 6656 : 7168;
            dst = (uint8_t*)g_wgu + nt * 552960 + ph * 286720 + st * 2 * bytes + up * (bytes >> 1);
            tm = &tmw[ph * 2 + up]; c1 = ph ? 112 + nt * 13 : nt * 14; c2 = st * 2;
          } else {
            const int nk = p - 640, nt = nk / 27;
            bytes = 10240;
            dst = (uint8_t*)g_wd + (size_t)nk * 10240;
            tm = &tmw[4]; c1 = nt * 10; c2 = nk - nt * 27;
          }
          mbar_expect(rbar + 8 * (i & 1), bytes);
          tma4d(rbuf + (i & 1) * 10240, tm, c1, c2, rbar + 8 * (i & 1));
        }
        if (pbytes) {
          mbar_wait(rbar + 8 * ((i - 1) & 1), ((i - 1) >> 1) & 1);
          if (pbytes == 10240) {
            bulk_st(pdst, rbuf + ((i - 1) & 1) * 10240, pbytes);
          } else {
            bulk_st(pdst, rbuf + ((i - 1) & 1) * 10240, pbytes >> 1);
            bulk_st(pdst + pbytes, rbuf + ((i - 1) & 1) * 10240 + (pbytes >> 1), pbytes >> 1);
          }
          asm volatile("cp.async.bulk.commit_group;" ::: "memory");
        }
        pdst = dst; pbytes = bytes;
      }
      asm volatile("cp.async.bulk.wait_group.read 0;" ::: "memory");
    }
  } else {
    asm volatile("setmaxnreg.inc.sync.aligned.u32 160;");
    const int wg = warp >> 2;
    const uint8_t* qthr = (const uint8_t*)g_qkv + (size_t)head * HEAD_IMG + qb * 64 * 384 + (warp & 3) * 768 + lane * 4;
    const uint32_t klo0 = ((sbase & 0x3FFFF) >> 4) | (128u << 16), vlo0 = (((sbase + HEAD_IMG) & 0x3FFFF) >> 4) | (24u << 16);
    constexpr uint64_t KSTEP2 = (uint64_t)(int64_t)(256 - (128 << 16));
    constexpr uint64_t KV2K = 384 - (HEAD_IMG >> 4) + (104 << 16);
    const int nun = wg == 1 ? 4 : 3;
    uint32_t utile = wg == 0 ? 0x210u : (wg == 1 ? 0x4235u : 0x576u);
    uint32_t ubeg = wg == 0 ? 0u : (wg == 1 ? 0x0b00u : 0x600u);
    uint32_t ulen = wg == 0 ? 0x0b1010u : (wg == 1 ? 0x10051006u : 0x0a1010u);
    pdl_wait();
    uint32_t q[6];
    load_q(q, qthr + (utile & 15) * 3072);
    bool fast;
    {
      const uint4 kn = __ldcg((const uint4*)&g_nrm[(32 + head) * 128 + lane * 4]);
      const uint4 vn = __ldcg((const uint4*)&g_nrm[(64 + head) * 128 + lane * 4]);
      const float qv = __ldcg(&g_nrm[head * 128 + qb * 32 + lane]);
      const float k2 = __uint_as_float(__reduce_max_sync(~0u, max(max(kn.x, kn.y), max(kn.z, kn.w))));
      const float v2 = __uint_as_float(__reduce_max_sync(~0u, max(max(vn.x, vn.y), max(vn.z, vn.w))));
      const float q2 = __uint_as_float(__reduce_max_sync(~0u, __float_as_uint(qv)));
      fast = q2 * k2 <= 3400.f && v2 < 1e24f && v2 > 1e-24f;
    }
    if (fast) {
#pragma unroll 1
      for (int u = 0; u < nun; u++) {
        const uint32_t b0 = ubeg & 15;
        const bool wt = u == 0 || (wg == 1 && u == 1);
        float s[64], o[12];
#pragma unroll
        for (int i = 0; i < 12; i++) o[i] = 0.f;
        uint32_t vlo = vlo0 + b0 * 384, kb = kvb + b0 * 8;
        const uint32_t vend = vlo + ((ulen & 255) - 1) * 384;
        if (wt) mbar_wait(kb, 0);
        fence_regs(o);
        WG_FENCE();
        wgmma_rs_n128(s, q[0], q[1], q[2], q[3], desc64(klo0 + b0 * 384, 8), 0);
        wgmma_rs_n128(s, q[4], q[5], 0, 0, desc64(klo0 + b0 * 384, 8) + KSTEP2, 1);
        WG_COMMIT();
#pragma unroll 1
        for (; vlo != vend; vlo += 384) {
          if (wt) { kb += 8; mbar_wait(kb, 0); }
          WG_WAIT(0);
          fence_regs(s); fence_regs(o);
          const uint64_t dv = desc64(vlo, 8);
          exp_pv(s, o, dv, mk);
          wgmma_rs_n128(s, q[0], q[1], q[2], q[3], dv + KV2K, 0);
          wgmma_rs_n128(s, q[4], q[5], 0, 0, dv + (KV2K + KSTEP2), 1);
          WG_COMMIT();
        }
        WG_WAIT(0);
        fence_regs(s); fence_regs(o);
        if (u + 1 < nun) load_q(q, qthr + ((utile >> 4) & 15) * 3072);
        exp_pv(s, o, desc64(vlo, 8), mk);
        WG_COMMIT();
        WG_WAIT(0);
        fence_regs(o);
        if (wg == 1 && !(u & 1)) {
          float4* pp = (float4*)(part + u * 768) + (tid & 127);
          pp[0] = make_float4(o[0], o[1], o[2], o[3]);
          pp[128] = make_float4(o[4], o[5], o[6], o[7]);
          pp[256] = make_float4(o[8], o[9], o[10], o[11]);
          mbar_arrive(partb + 4 * u);
        } else {
          if (wg != 1 && u == 2) {
            const int pi = wg == 0 ? 1 : 0;
            mbar_wait(partb + 8 * pi, 0);
            const float4* pp = (const float4*)(part + pi * 1536) + (tid & 127);
            const float4 x0 = pp[0], x1 = pp[128], x2 = pp[256];
            o[0] += x0.x; o[1] += x0.y; o[2] += x0.z; o[3] += x0.w; o[4] += x1.x; o[5] += x1.y;
            o[6] += x1.z; o[7] += x1.w; o[8] += x2.x; o[9] += x2.y; o[10] += x2.z; o[11] += x2.w;
          }
          store_o(o, utile & 15);
        }
        utile >>= 4; ubeg >>= 4; ulen >>= 8;
      }
    } else {
#pragma unroll 1
      for (int tile = wg; tile < 8; tile += 3) {
        load_q(q, qthr + tile * 3072);
        if ((lane & 3) >= 2) { q[4] = 0; q[5] = 0; }
        float o[12], m0 = -INFINITY, m1 = -INFINITY;
#pragma unroll
        for (int i = 0; i < 12; i++) o[i] = 0.f;
#pragma unroll 1
        for (int b = 0; b < 16; b++) {
          float s[64];
          mbar_wait(kvb + 8 * b, 0);
          WG_FENCE();
          wgmma_rs_n128(s, q[0], q[1], q[2], q[3], desc64(klo0 + b * 384, 8), 0);
          wgmma_rs_n128(s, q[4], q[5], 0, 0, desc64(klo0 + b * 384, 8) + KSTEP2, 1);
          WG_COMMIT();
          WG_WAIT(0);
          fence_regs(s);
          float x0 = m0, x1 = m1;
#pragma unroll
          for (int j = 0; j < 16; j++) {
            if ((POLY_MASK >> j) & 1) {
#pragma unroll
              for (int i = 0; i < 4; i++) s[4 * j + i] *= (1.f / 32768.f);
            }
            x0 = fmaxf(x0, fmaxf(s[4 * j], s[4 * j + 1]));
            x1 = fmaxf(x1, fmaxf(s[4 * j + 2], s[4 * j + 3]));
          }
          x0 = fmaxf(x0, __shfl_xor_sync(~0u, x0, 1)); x0 = fmaxf(x0, __shfl_xor_sync(~0u, x0, 2));
          x1 = fmaxf(x1, __shfl_xor_sync(~0u, x1, 1)); x1 = fmaxf(x1, __shfl_xor_sync(~0u, x1, 2));
          const float al0 = ex2(m0 - x0), al1 = ex2(m1 - x1);
          m0 = x0; m1 = x1;
#pragma unroll
          for (int i = 0; i < 12; i++) o[i] *= (i & 2) ? al1 : al0;
          uint32_t p[32];
#pragma unroll
          for (int i = 0; i < 32; i++) {
            const float mm = (i & 1) ? m1 : m0;
            p[i] = pack_bf16(ex2(s[2 * i] - mm), ex2(s[2 * i + 1] - mm));
          }
          fence_regs(o);
          WG_FENCE();
#pragma unroll
          for (int k = 0; k < 8; k++)
            wgmma_rs_n24(o, p[4 * k], p[4 * k + 1], p[4 * k + 2], p[4 * k + 3], desc64(vlo0 + b * 384 + k * 48, 8), 1);
          WG_COMMIT();
          WG_WAIT(0);
          fence_regs(o);
        }
        store_o(o, tile);
      }
    }
  }
}

constexpr int K3_ST = 4, K3_STAGE = 37888, K3_NB = 4, K3_NT = 6;
constexpr int K3_SMEM = K3_ST * K3_STAGE + 24576 + 20480 + 256;

template <int N> struct Acc { float v[N]; };

__global__ void __cluster_dims__(2, 1, 1) __launch_bounds__(288, 1)
k3_proj(const __grid_constant__ CUtensorMap tmx) {
  extern __shared__ __align__(1024) uint8_t sm[];
  const uint32_t sbase = smem_u32(sm);
  const uint8_t* xch = sm + K3_ST * K3_STAGE;
  const uint8_t* res = sm + K3_ST * K3_STAGE + 24576;
  const uint32_t fullb = smem_u32(res) + 20480, emptyb = fullb + 8 * K3_ST, resb = emptyb + 8 * K3_ST, xchb = resb + 8;
  const int tid = threadIdx.x, lane = tid & 31;
  const int warp = __shfl_sync(~0u, tid >> 5, 0);
  const int rank = blockIdx.x & 1;
  const int n = blockIdx.x & 7, m = blockIdx.x >> 3;
  if (warp == 8) {
    if (elect_one()) {
#pragma unroll
      for (int i = 0; i < K3_ST; i++) { mbar_init(fullb + 8 * i, 1); mbar_init(emptyb + 8 * i, 2); }
      mbar_init(resb, 1); mbar_init(xchb, 1);
      mbar_expect(xchb, 24576);
      asm volatile("fence.mbarrier_init.release.cluster;" ::: "memory");
    }
    __syncwarp();
  }
  cluster_arrive();
  if (warp == 8) {
    const uint8_t* wk = (const uint8_t*)g_wo + n * 102400;
    const uint8_t* ws = (const uint8_t*)g_wo + (n ^ 1) * 102400;
    const uint8_t* ab = (const uint8_t*)g_o + m * 163840;
    prefetch_map(&tmx);
    cluster_wait();
    pdl_wait();
#pragma unroll 1
    for (int i = 0; i < K3_NT; i++) {
      const int s = i % K3_ST, kt = i < K3_NB ? i + rank * K3_NT : i;
      const uint32_t sa = sbase + s * K3_STAGE, fb = fullb + 8 * s;
      if (i >= K3_ST) mbar_wait(emptyb + 8 * s, 0);
      if (elect_one()) {
        mbar_expect(fb, i < K3_NB ? 37888 : 27648);
        bulk_ld(sa, ab + kt * 16384, 16384, fb);
        bulk_ld(sa + 16384, wk + kt * 10240, 10240, fb);
        bulk_ld(sa + 26624, (const uint8_t*)g_wm + kt * 1024, 1024, fb);
        if (i < K3_NB) bulk_ld(sa + 27648, ws + kt * 10240, 10240, fb);
        if (i == K3_ST - 1) {
          mbar_expect(resb, 20480);
          tma2d(smem_u32(res), &tmx, n * 80, m * 128, resb);
          tma2d(smem_u32(res) + 10240, &tmx, n * 80, m * 128 + 64, resb);
        }
      }
      if (i == 0) pdl_trigger();
    }
  } else {
    const int g = lane >> 2, c = lane & 3;
    const int row = m * 128 + warp * 16 + g;
    float mu0 = __uint_as_float(__ldcg(&g_rowstat[row].z)), mu1 = __uint_as_float(__ldcg(&g_rowstat[row + 8].z));
    float acc[84];
    float (&keep)[44] = ((Acc<44>*)acc)->v;
    const uint64_t da0 = mkdesc(sbase + (warp >> 2) * 1024, 2048, 128, 0);
    const uint64_t db0 = mkdesc(sbase + 16384, 128, 1024, 0);
    cluster_wait();
#pragma unroll 1
    for (int i = 0; i < K3_NB; i++) {
      mbar_wait(fullb + 8 * i, 0);
      const uint64_t da = da0 + i * (K3_STAGE >> 4), db = db0 + i * (K3_STAGE >> 4);
      WG_FENCE();
#pragma unroll
      for (int k = 0; k < 4; k++) wgmma_ss_n168(acc, da + k * 256, db + k * 16, (i | k) != 0);
      WG_COMMIT();
      if (i > 0) {
        WG_WAIT(1);
        if (i - 1 + K3_ST < K3_NT && (tid & 127) == 0) mbar_arrive(emptyb + 8 * (i - 1));
      }
    }
    const uint32_t rx = mapa(smem_u32(xch) + tid * 16, rank ^ 1), rb = mapa(xchb, rank ^ 1);
    WG_WAIT(0);
    fence_regs(acc);
    st_async4(rx, acc[40], acc[41], acc[42], acc[43], rb);
#pragma unroll
    for (int i = K3_NB; i < K3_NT; i++) {
      const int s = i % K3_ST;
      mbar_wait(fullb + 8 * s, 1);
      const uint64_t da = da0 + s * (K3_STAGE >> 4), db = db0 + s * (K3_STAGE >> 4);
      WG_FENCE();
#pragma unroll
      for (int k = 0; k < 4; k++) wgmma_ss_n88(keep, da + k * 256, db + k * 16, 1);
      WG_COMMIT();
#pragma unroll
      for (int j = (i - K3_NB) * 3; j < (i - K3_NB) * 3 + 3; j++)
        if (j < 5) SEND8(rx + (j + 1) * 4096, acc, 44 + 8 * j, rb);
    }
    const uint8_t* sp = res + (warp * 16 + g) * 160 + c * 4;
    uint32_t rv[20];
    mbar_wait(resb, 0);
#pragma unroll
    for (int j = 0; j < 10; j++) {
      rv[2 * j] = *(const uint32_t*)(sp + j * 16);
      rv[2 * j + 1] = *(const uint32_t*)(sp + 1280 + j * 16);
    }
    WG_WAIT(0);
    fence_regs(keep);
    mbar_wait(xchb, 0);
    const uint8_t* xp = xch + tid * 16;
    {
      const float4 p = *(const float4*)xp;
      mu0 += __shfl_sync(~0u, (keep[40] + p.x) + (keep[41] + p.y), 0, 4);
      mu1 += __shfl_sync(~0u, (keep[42] + p.z) + (keep[43] + p.w), 0, 4);
    }
    uint8_t* himg = (uint8_t*)g_h + m * 163840 + img_off(n * 10) + warp * 256 + lane * 4;
    float q0 = 0.f, q1 = 0.f;
#pragma unroll
    for (int j = 0; j < 10; j++) {
      const uint2 p = *(const uint2*)(xp + ((j >> 1) + 1) * 4096 + (j & 1) * 8);
      const float x0 = (keep[4 * j] + bf_lo(p.x)) + (bf_lo(rv[2 * j]) - mu0), x1 = (keep[4 * j + 1] + bf_hi(p.x)) + (bf_hi(rv[2 * j]) - mu0);
      const float y0 = (keep[4 * j + 2] + bf_lo(p.y)) + (bf_lo(rv[2 * j + 1]) - mu1), y1 = (keep[4 * j + 3] + bf_hi(p.y)) + (bf_hi(rv[2 * j + 1]) - mu1);
      *(uint32_t*)(himg + img_off(j)) = pack_bf16(x0, x1);
      *(uint32_t*)(himg + img_off(j) + 128) = pack_bf16(y0, y1);
      q0 = fmaf(x0, x0, fmaf(x1, x1, q0)); q1 = fmaf(y0, y0, fmaf(y1, y1, q1));
    }
    q0 += __shfl_xor_sync(~0u, q0, 1); q0 += __shfl_xor_sync(~0u, q0, 2);
    q1 += __shfl_xor_sync(~0u, q1, 1); q1 += __shfl_xor_sync(~0u, q1, 2);
    if (c < 2) g_hpart[n * S_ + row + c * 8] = c ? q1 : q0;
    if (n == 0 && c < 2) g_hmean[row + c * 8] = c ? mu1 : mu0;
  }
}

constexpr int P3_NB = 12, P3_NT = 15;
constexpr int K4_G = 2, K4_NS = 4, K4_NJ = 20;
constexpr int K4_RB = 163840, K4_BST = 7168 * K4_G, K4_XCH = 147456, K4_STG = K4_XCH + 20480, K4_BAR = K4_RB + K4_NS * K4_BST;
constexpr int K4_SMEM = K4_BAR + 384;

__device__ __forceinline__ void wait_flags(const uint4* f, uint32_t tag, uint32_t need, uint32_t& seen) {
  if ((seen & need) == need) return;
  for (uint32_t it = 0; (seen & need) != need; it++) {
    if (it > (1u << 20)) wait_timeout();
    if (it) __nanosleep(150);
    uint32_t v = 0;
    if ((threadIdx.x & 31) < 8) asm volatile("ld.acquire.gpu.global.u32 %0, [%1];" : "=r"(v) : "l"((const uint32_t*)f + (threadIdx.x & 7)) : "memory");
    seen = __ballot_sync(~0u, v == tag) & 255;
  }
  asm volatile("fence.proxy.async.global;" ::: "memory");
}

template <int MODE>
__global__ void __cluster_dims__(2, 1, 1) __launch_bounds__(384, 1)
k45_ffn(const __grid_constant__ CUtensorMap tmo) {
  extern __shared__ __align__(1024) uint8_t sm[];
  const uint32_t sbase = smem_u32(sm);
  const uint32_t afull = sbase + K4_BAR, bfull = afull + 80, bempty = bfull + 8 * K4_NS, full3 = bempty + 8 * K4_NS;
  const uint32_t empty3 = full3 + 32, afree = empty3 + 32, xchb = afree + 32, rdyb = xchb + 8;
  const int tid = threadIdx.x, lane = tid & 31;
  const int warp = __shfl_sync(~0u, tid >> 5, 0);
  const int rank = blockIdx.x & 1;
  const int n = blockIdx.x & 7, m = blockIdx.x >> 3;
  if (warp == 8) {
    if (elect_one()) {
#pragma unroll
      for (int i = 0; i < 10; i++) mbar_init(afull + 8 * i, 1);
#pragma unroll
      for (int i = 0; i < 4; i++) {
        mbar_init(bfull + 8 * i, 1); mbar_init(bempty + 8 * i, 2); mbar_init(full3 + 8 * i, 1); mbar_init(empty3 + 8 * i, 2);
        mbar_init(afree + 8 * i, 2);
      }
      mbar_init(xchb, 1); mbar_init(rdyb, 2);
      mbar_expect(xchb, 20480);
      asm volatile("fence.mbarrier_init.release.cluster;" ::: "memory");
    }
    __syncwarp();
  }
  cluster_arrive();
  if (warp >= 8) {
    if (warp != 8) cluster_wait();
    if (warp == 8) {
      const uint8_t* src = (const uint8_t*)g_wgu + n * 552960;
      const uint8_t* hb = (const uint8_t*)g_h + (size_t)m * 163840;
#pragma unroll 1
      for (int j = 0; j < (MODE == 2 ? 0 : 40); j++) {
        const uint32_t s8 = (j & 3) * 8, sz = j < 20 ? 14336 : 13312;
        if (j == 2) {
          pdl_wait();
          if (elect_one()) {
#pragma unroll
            for (int kt = 0; kt < 2; kt++) { mbar_expect(afull + 8 * kt, 16384); bulk_ld(sbase + kt * 16384, hb + kt * 16384, 16384, afull + 8 * kt); }
          }
        }
        if (j >= 4) mbar_wait(bempty + s8, ((j >> 2) - 1) & 1);
        if (elect_one()) {
          mbar_expect(bfull + s8, sz);
          bulk_ld(sbase + K4_RB + s8 * (K4_BST / 8), src, sz, bfull + s8);
          if (j > 2 && j < 18 && (j & 1)) {
            mbar_expect(afull + 4 + j * 4, 16384);
            bulk_ld(sbase + 8192 + j * 8192, hb + 8192 + j * 8192, 16384, afull + 4 + j * 4);
          }
        }
        src += sz;
      }
      cluster_wait();
    } else if (warp == 9) {
      prefetch_map(&tmo);
      const uint32_t tag = __ldcg(&g_epoch);
#pragma unroll 1
      for (int ph = 0; ph < (MODE == 2 ? 0 : 2); ph++) {
        bar_sync(5 + ph, 256 + 32);
        if (lane == 0) {
          asm volatile("st.release.gpu.global.u32 [%0], %1;" ::"l"((uint32_t*)&g_flag[ph * 32 + m * 2] + n), "r"(tag) : "memory");
        }
        __syncwarp();
      }
    } else {
      const uint8_t* wk = (const uint8_t*)g_wd + n * 276480;
      const uint8_t* ws = (const uint8_t*)g_wd + (n ^ 1) * 276480;
      const uint8_t* ab = (const uint8_t*)g_hh + (size_t)m * 442368;
      const uint32_t tag = __ldcg(&g_epoch);
      uint32_t seen = 0;
#pragma unroll 1
      for (int i = 0; i < (MODE == 1 ? 0 : P3_NT); i++) {
        const int kt = i < 7 ? rank * 7 + i : (i < P3_NB ? rank * (P3_NB - 7) + 7 + i : P3_NB + i);
        const uint32_t sa = sbase + (i & 3) * 36864, fb = full3 + 8 * (i & 3);
        if (warp == 11) {
          const int q = kt * 8 - (i < 7 ? 0 : 112), w = i < 7 ? 14 : 13;
          if (MODE == 0 && i == 0) mbar_wait(afull + 72, 0);
          if (i == 7) seen = 0;
          wait_flags(&g_flag[(i < 7 ? 0 : 32) + m * 2], tag, 1u << (q / w) | 1u << ((q + 7) / w), seen);
        }
        if (i < 4) { if (MODE == 0) mbar_wait(afree + 8 * i, 0); }
        else mbar_wait(empty3 + 8 * (i & 3), ((i >> 2) - 1) & 1);
        if (warp == 10) {
          if (elect_one()) {
            mbar_expect(fb, i < P3_NB ? 36864 : 26624);
            bulk_ld(sa + 16384, wk + kt * 10240, 10240, fb);
            if (i < P3_NB) bulk_ld(sa + 26624, ws + kt * 10240, 10240, fb);
          }
        } else {
          if (elect_one()) {
            bulk_ld(sa, ab + kt * 16384, 16384, fb);
          }
        }
      }
    }
  } else {
    const int wg = warp >> 2;
    const uint64_t da0 = mkdesc(sbase + wg * 1024, 2048, 128, 0);
    const uint64_t db0 = mkdesc(sbase + K4_RB, 128, 256, 0);
    cluster_wait();
    float acc[80];
    if constexpr (MODE != 2) {
    float a1[112], a2[104];
    int s = 0, ph = 0, sprev = 0;
#pragma unroll 1
    for (int j = 0; j < K4_NJ; j++) {
      if ((j * K4_G) % 4 == 0) mbar_wait(afull + 2 * K4_G * j, 0);
      mbar_wait(bfull + 8 * s, ph);
      const uint64_t da = da0 + j * K4_G * 256, db = db0 + s * (K4_BST >> 4);
      WG_FENCE();
#pragma unroll
      for (int k = 0; k < K4_G; k++) wgmma_ss_n224(a1, da + k * 256, db + k * 448, (j | k) != 0);
      WG_COMMIT();
      if (j > 0) {
        WG_WAIT(1);
        if ((tid & 127) == 0) mbar_arrive(bempty + 8 * sprev);
      }
      sprev = s;
      if (++s == K4_NS) { s = 0; ph ^= 1; }
    }
    uint8_t* hd = (uint8_t*)g_hh + (size_t)m * 442368 + warp * 256 + lane * 4;
    WG_WAIT(0);
    fence_regs(a1);
    if ((tid & 127) == 0) mbar_arrive(bempty + 8 * ((K4_NJ - 1) % K4_NS));
#define STORE_H(a, off, ptr, c) do { uint8_t* p_ = ptr; \
      *(uint32_t*)p_ = pack_bf16(a[4 * (c)] * a[off + 4 * (c)], a[4 * (c) + 1] * a[off + 1 + 4 * (c)]); \
      *(uint32_t*)(p_ + 128) = pack_bf16(a[4 * (c) + 2] * a[off + 2 + 4 * (c)], a[4 * (c) + 3] * a[off + 3 + 4 * (c)]); } while (0)
#pragma unroll
    for (int c = 0; c < 14; c++) STORE_H(a1, 56, hd + img_off(n * 14 + c), c);
    bar_arrive(5, 256 + 32);
#pragma unroll 1
    for (int j = 0; j < K4_NJ; j++) {
      mbar_wait(bfull + 8 * s, ph);
      const uint64_t da = da0 + j * K4_G * 256, db = db0 + s * (K4_BST >> 4);
      WG_FENCE();
#pragma unroll
      for (int k = 0; k < K4_G; k++) wgmma_ss_n208(a2, da + k * 256, db + k * 416, (j | k) != 0);
      WG_COMMIT();
      if (j > 0) {
        WG_WAIT(1);
        if (j <= K4_NJ - K4_NS && (tid & 127) == 0) mbar_arrive(bempty + 8 * sprev);
        if (j * K4_G >= 12 && ((j * K4_G) & 7) == 4 && (tid & 127) == 0) mbar_arrive(afree + (j * K4_G - 12));
      }
      sprev = s;
      if (++s == K4_NS) { s = 0; ph ^= 1; }
    }
    WG_WAIT(0);
    fence_regs(a2);
#pragma unroll
    for (int c = 0; c < 13; c++) STORE_H(a2, 52, hd + img_off(112 + n * 13 + c), c);
    bar_arrive(6, 256 + 32);
    }
    if constexpr (MODE != 1) {
    if ((tid & 127) == 0) mbar_arrive_cta(rdyb, rank ^ 1);
    float (&keep)[40] = ((Acc<40>*)acc)->v;
    const uint64_t db3 = mkdesc(sbase + 16384, 128, 1024, 0);
#pragma unroll 1
    for (int i = 0; i < P3_NB; i++) {
      mbar_wait(full3 + 8 * (i & 3), (i >> 2) & 1);
      const uint64_t da = da0 + (i & 3) * 2304, db = db3 + (i & 3) * 2304;
      WG_FENCE();
#pragma unroll
      for (int k = 0; k < 4; k++) wgmma_ss_n160(acc, da + k * 256, db + k * 16, (i | k) != 0);
      WG_COMMIT();
      if (i > 0) {
        WG_WAIT(1);
        if (i + 3 < P3_NT && (tid & 127) == 0) mbar_arrive(empty3 + 8 * ((i - 1) & 3));
      }
    }
    const int g = lane >> 2, c = lane & 3, row = m * 128 + warp * 16 + g;
    const uint8_t* himg = (const uint8_t*)g_h + (size_t)m * 163840 + warp * 256 + lane * 4;
    uint32_t rv[20];
    const float mu0 = __ldcg(&g_hmean[row]), mu1 = __ldcg(&g_hmean[row + 8]);
    float r0 = __ldcg(&g_hpart[c * 2 * S_ + row]) + __ldcg(&g_hpart[(c * 2 + 1) * S_ + row]);
    float r1 = __ldcg(&g_hpart[c * 2 * S_ + row + 8]) + __ldcg(&g_hpart[(c * 2 + 1) * S_ + row + 8]);
#pragma unroll
    for (int j = 0; j < 10; j++) {
      rv[2 * j] = __ldcg((const uint32_t*)(himg + img_off(n * 10 + j)));
      rv[2 * j + 1] = __ldcg((const uint32_t*)(himg + img_off(n * 10 + j) + 128));
    }
    const uint32_t rx = mapa(sbase + K4_XCH + tid * 16, rank ^ 1), rb = mapa(xchb, rank ^ 1);
    WG_WAIT(0);
    fence_regs(acc);
    mbar_wait(rdyb, 0);
#pragma unroll
    for (int i = P3_NB; i < P3_NT; i++) {
      mbar_wait(full3 + 8 * (i & 3), (i >> 2) & 1);
      const uint64_t da = da0 + (i & 3) * 2304, db = db3 + (i & 3) * 2304;
      WG_FENCE();
#pragma unroll
      for (int k = 0; k < 4; k++) wgmma_ss_n80(keep, da + k * 256, db + k * 16, 1);
      WG_COMMIT();
#pragma unroll
      for (int j = (i - P3_NB) * 3; j < (i - P3_NB) * 3 + 3; j++)
        if (j < 5) SEND8(rx + j * 4096, acc, 40 + 8 * j, rb);
    }
    r0 += __shfl_xor_sync(~0u, r0, 1); r1 += __shfl_xor_sync(~0u, r1, 1);
    r0 += __shfl_xor_sync(~0u, r0, 2); r1 += __shfl_xor_sync(~0u, r1, 2);
    r0 = rcp(r0 * (1.f / D_) + 1e-5f); r1 = rcp(r1 * (1.f / D_) + 1e-5f);
    asm volatile("" : "+f"(r0), "+f"(r1)::"memory");
    WG_WAIT(0);
    fence_regs(keep);
    mbar_wait(xchb, 0);
    uint8_t* sp = sm + K4_STG + (warp * 16 + g) * 160 + c * 4;
#pragma unroll
    for (int j = 0; j < 10; j++) {
      const uint2 p = *(const uint2*)(sm + K4_XCH + tid * 16 + (j >> 1) * 4096 + (j & 1) * 8);
      *(uint32_t*)(sp + j * 16) = pack_bf16(fmaf(keep[4 * j] + bf_lo(p.x), r0, bf_lo(rv[2 * j]) + mu0), fmaf(keep[4 * j + 1] + bf_hi(p.x), r0, bf_hi(rv[2 * j]) + mu0));
      *(uint32_t*)(sp + 1280 + j * 16) = pack_bf16(fmaf(keep[4 * j + 2] + bf_lo(p.y), r1, bf_lo(rv[2 * j + 1]) + mu1), fmaf(keep[4 * j + 3] + bf_hi(p.y), r1, bf_hi(rv[2 * j + 1]) + mu1));
    }
    fence_async();
    bar_sync(1 + wg, 128);
    if ((tid & 127) == 0) {
      tma2d_st(&tmo, n * 80, m * 128 + wg * 64, sbase + K4_STG + wg * 10240);
      bulk_commit_wait();
    }
    __syncwarp();
    }
  }
}

typedef CUresult (*EncodeFn)(CUtensorMap*, CUtensorMapDataType, cuuint32_t, void*, const cuuint64_t*, const cuuint64_t*,
                             const cuuint32_t*, const cuuint32_t*, CUtensorMapInterleave, CUtensorMapSwizzle,
                             CUtensorMapL2promotion, CUtensorMapFloatOOBfill);

static CUtensorMap make_map(EncodeFn enc, const void* p, uint64_t inner, uint64_t outer, uint32_t box_inner,
                            uint32_t box_outer, CUtensorMapSwizzle swz) {
  CUtensorMap m;
  cuuint64_t gd[2] = {inner, outer};
  cuuint64_t gs[1] = {inner * 2};
  cuuint32_t bd[2] = {box_inner, box_outer};
  cuuint32_t es[2] = {1, 1};
  enc(&m, CU_TENSOR_MAP_DATA_TYPE_BFLOAT16, 2, (void*)p, gd, gs, bd, es, CU_TENSOR_MAP_INTERLEAVE_NONE, swz,
      CU_TENSOR_MAP_L2_PROMOTION_L2_256B, CU_TENSOR_MAP_FLOAT_OOB_FILL_NONE);
  return m;
}

static CUtensorMap make_map_img(EncodeFn enc, const void* p, uint64_t k, uint64_t n, uint32_t rows, uint32_t chunks,
                                uint32_t groups) {
  CUtensorMap m;
  cuuint64_t gd[4] = {8, rows, n / 8, k / rows};
  cuuint64_t gs[3] = {n * 2, 16, n * 2 * rows};
  cuuint32_t bd[4] = {8, rows, chunks, groups};
  cuuint32_t es[4] = {1, 1, 1, 1};
  enc(&m, CU_TENSOR_MAP_DATA_TYPE_BFLOAT16, 4, (void*)p, gd, gs, bd, es, CU_TENSOR_MAP_INTERLEAVE_NONE,
      CU_TENSOR_MAP_SWIZZLE_NONE, CU_TENSOR_MAP_L2_PROMOTION_L2_128B, CU_TENSOR_MAP_FLOAT_OOB_FILL_NONE);
  return m;
}

template <typename... KArgs, typename... Args>
static void launch(void (*k)(KArgs...), int grid, int threads, int smem, bool pdl, Args... args) {
  cudaLaunchConfig_t cfg = {};
  cfg.gridDim = dim3(grid);
  cfg.blockDim = dim3(threads);
  cfg.dynamicSmemBytes = smem;
  cfg.stream = cudaStreamPerThread;
  cudaLaunchAttribute at[1];
  at[0].id = cudaLaunchAttributeProgrammaticStreamSerialization;
  at[0].val.programmaticStreamSerializationAllowed = 1;
  cfg.attrs = at;
  cfg.numAttrs = pdl ? 1 : 0;
  cudaLaunchKernelEx(&cfg, k, KArgs(args)...);
}

extern "C" void kernel_launch(void* const* d_in, const int* in_sizes, int n_in, void* d_out, int out_size) {
  const bf16* x = (const bf16*)d_in[0];
  const bf16* wqkv = (const bf16*)d_in[1];
  const bf16* wo = (const bf16*)d_in[2];
  const bf16* wg = (const bf16*)d_in[4];
  const bf16* wu = (const bf16*)d_in[5];
  const bf16* wd = (const bf16*)d_in[6];

  static EncodeFn enc = nullptr;
  static bool fused = true;
  if (!enc) {
    void* fn = nullptr;
    cudaDriverEntryPointQueryResult qr;
    cudaGetDriverEntryPoint("cuTensorMapEncodeTiled", &fn, cudaEnableDefault, &qr);
    enc = (EncodeFn)fn;
    cudaFuncSetAttribute(k1_qkv, cudaFuncAttributeMaxDynamicSharedMemorySize, K1_SMEM);
    cudaFuncSetAttribute(k2_attn, cudaFuncAttributeMaxDynamicSharedMemorySize, K2_SMEM);
    cudaFuncSetAttribute(k3_proj, cudaFuncAttributeMaxDynamicSharedMemorySize, K3_SMEM);
    cudaFuncSetAttribute(k45_ffn<0>, cudaFuncAttributeMaxDynamicSharedMemorySize, K4_SMEM);
    cudaFuncSetAttribute(k45_ffn<1>, cudaFuncAttributeMaxDynamicSharedMemorySize, K4_SMEM);
    cudaFuncSetAttribute(k45_ffn<2>, cudaFuncAttributeMaxDynamicSharedMemorySize, K4_SMEM);
    cudaLaunchConfig_t cfg = {};
    cfg.gridDim = dim3(128); cfg.blockDim = dim3(384); cfg.dynamicSmemBytes = K4_SMEM;
    int clusters = 0;
    cudaOccupancyMaxActiveClusters(&clusters, k45_ffn<0>, &cfg);
    fused = clusters >= 64;
  }
  const CUtensorMap tmx = make_map(enc, x, D_, S_, 64, 192, CU_TENSOR_MAP_SWIZZLE_128B);
  const CUtensorMap tmw = make_map(enc, wqkv, 3 * D_, D_, 32, 64, CU_TENSOR_MAP_SWIZZLE_64B);
  const CUtensorMap tmxr = make_map(enc, x, D_, S_, 80, 64, CU_TENSOR_MAP_SWIZZLE_NONE);
  Maps5 maps;
  maps.m[0] = make_map_img(enc, wg, D_, F_, 16, 14, 2); maps.m[1] = make_map_img(enc, wu, D_, F_, 16, 14, 2);
  maps.m[2] = make_map_img(enc, wg, D_, F_, 16, 13, 2); maps.m[3] = make_map_img(enc, wu, D_, F_, 16, 13, 2);
  maps.m[4] = make_map_img(enc, wd, F_, D_, 64, 10, 1);
  const CUtensorMap tmout = make_map(enc, d_out, D_, S_, 80, 64, CU_TENSOR_MAP_SWIZZLE_NONE);

  launch(k1_qkv, 132, 512, K1_SMEM, false, tmx, tmw, x, wqkv);
  launch(k2_attn, 128, 512, K2_SMEM, true, maps, wo, 0x007f007fu);
  launch(k3_proj, 128, 288, K3_SMEM, true, tmxr);
  if (fused) {
    launch(k45_ffn<0>, 128, 384, K4_SMEM, true, tmout);
  } else {
    launch(k45_ffn<1>, 128, 384, K4_SMEM, true, tmout);
    launch(k45_ffn<2>, 128, 384, K4_SMEM, false, tmout);
  }
}
```

```cpp
#include <cuda_runtime.h>
#include <cuda_bf16.h>
#include <cuda.h>
#include <stdint.h>

typedef __nv_bfloat16 bf16;

constexpr int S_ = 2048, D_ = 640, F_ = 1728;
constexpr int HEAD_IMG = 98304;
constexpr uint32_t POLY_MASK = 0xFAAB;
constexpr float QSCALE = 0.22360679774997896f * 1.4426950408889634f;

__device__ __align__(1024) uint4 g_qkv[96 * HEAD_IMG / 16];
__device__ __align__(1024) uint4 g_o[S_ * D_ / 8];
__device__ __align__(1024) uint4 g_h[S_ * D_ / 8];
__device__ __align__(1024) uint4 g_hh[S_ * F_ / 8];
__device__ __align__(1024) uint4 g_wo[D_ * D_ / 8];
__device__ __align__(1024) uint4 g_wgu[2 * D_ * F_ / 8];
__device__ __align__(1024) uint4 g_wd[F_ * D_ / 8];
__device__ uint4 g_rowstat[S_];
__device__ uint4 g_cpart[10 * 12 * 80];
__device__ float g_nrm[96 * 128];
__device__ uint4 g_wm[D_];
__device__ float g_hmean[S_];
__device__ float g_hpart[8 * S_];
__device__ uint4 g_flag[2 * 16 * 2];
__device__ unsigned g_epoch;

__device__ __forceinline__ uint32_t smem_u32(const void* p) { return (uint32_t)__cvta_generic_to_shared(p); }
__device__ __forceinline__ void mbar_init(uint32_t a, uint32_t c) {
  asm volatile("mbarrier.init.shared::cta.b64 [%0], %1;" ::"r"(a), "r"(c) : "memory");
}
__device__ __forceinline__ void mbar_expect(uint32_t a, uint32_t bytes) {
  asm volatile("mbarrier.arrive.expect_tx.shared::cta.b64 _, [%0], %1;" ::"r"(a), "r"(bytes) : "memory");
}
__device__ __forceinline__ void mbar_arrive(uint32_t a) {
  asm volatile("mbarrier.arrive.shared::cta.b64 _, [%0];" ::"r"(a) : "memory");
}
__device__ __forceinline__ void mbar_arrive_cta(uint32_t a, uint32_t cta) {
  asm volatile("{\n.reg .b32 r;\nmapa.shared::cluster.u32 r, %0, %1;\n"
               "mbarrier.arrive.shared::cluster.b64 _, [r];\n}" ::"r"(a), "r"(cta) : "memory");
}
__device__ __forceinline__ bool mbar_try(uint32_t a, uint32_t ph) {
  uint32_t ok;
  asm volatile("{\n.reg .pred p;\nmbarrier.try_wait.parity.shared::cta.b64 p, [%1], %2;\nselp.u32 %0, 1, 0, p;\n}"
               : "=r"(ok) : "r"(a), "r"(ph) : "memory");
  return ok;
}
__device__ __noinline__ void wait_timeout() { __trap(); }
__device__ __forceinline__ void mbar_wait(uint32_t a, uint32_t ph) {
  if (mbar_try(a, ph)) return;
  uint32_t it = 0;
  while (!mbar_try(a, ph)) if (++it > (1u << 22)) wait_timeout();
}
__device__ __forceinline__ void tma2d(uint32_t dst, const CUtensorMap* m, int c0, int c1, uint32_t bar) {
  asm volatile("cp.async.bulk.tensor.2d.shared::cluster.global.mbarrier::complete_tx::bytes [%0], [%1, {%3, %4}], [%2];"
               ::"r"(dst), "l"(m), "r"(bar), "r"(c0), "r"(c1) : "memory");
}
__device__ __forceinline__ void bulk_ld(uint32_t dst, const void* src, uint32_t bytes, uint32_t bar) {
  asm volatile("cp.async.bulk.shared::cluster.global.mbarrier::complete_tx::bytes [%0], [%1], %2, [%3];"
               ::"r"(dst), "l"(src), "r"(bytes), "r"(bar) : "memory");
}
__device__ __forceinline__ void cluster_arrive() { asm volatile("barrier.cluster.arrive.relaxed.aligned;" ::: "memory"); }
__device__ __forceinline__ void cluster_wait() { asm volatile("barrier.cluster.wait.aligned;" ::: "memory"); }
__device__ __forceinline__ void bulk_st(void* dst, uint32_t src, uint32_t bytes) {
  asm volatile("cp.async.bulk.global.shared::cta.bulk_group [%0], [%1], %2;" ::"l"(dst), "r"(src), "r"(bytes) : "memory");
}
__device__ __forceinline__ void tma2d_st(const CUtensorMap* m, int c0, int c1, uint32_t src) {
  asm volatile("cp.async.bulk.tensor.2d.global.shared::cta.bulk_group [%0, {%2, %3}], [%1];"
               ::"l"(m), "r"(src), "r"(c0), "r"(c1) : "memory");
}
__device__ __forceinline__ void bulk_commit_wait() {
  asm volatile("cp.async.bulk.commit_group;\ncp.async.bulk.wait_group.read 0;" ::: "memory");
}
__device__ __forceinline__ uint32_t mapa(uint32_t a, uint32_t cta) {
  uint32_t r;
  asm("mapa.shared::cluster.u32 %0, %1, %2;" : "=r"(r) : "r"(a), "r"(cta));
  return r;
}
__device__ __forceinline__ void st_async4(uint32_t dst, float a, float b, float c, float d, uint32_t bar) {
  asm volatile("st.async.shared::cluster.mbarrier::complete_tx::bytes.v4.f32 [%0], {%1, %2, %3, %4}, [%5];"
               ::"r"(dst), "f"(a), "f"(b), "f"(c), "f"(d), "r"(bar) : "memory");
}
__device__ __forceinline__ void st_async4u(uint32_t dst, uint32_t a, uint32_t b, uint32_t c, uint32_t d, uint32_t bar) {
  asm volatile("st.async.shared::cluster.mbarrier::complete_tx::bytes.v4.b32 [%0], {%1, %2, %3, %4}, [%5];"
               ::"r"(dst), "r"(a), "r"(b), "r"(c), "r"(d), "r"(bar) : "memory");
}
#define SEND8(dst, a, o, bar) st_async4u(dst, pack_bf16(a[o], a[(o) + 1]), pack_bf16(a[(o) + 2], a[(o) + 3]), \
                                         pack_bf16(a[(o) + 4], a[(o) + 5]), pack_bf16(a[(o) + 6], a[(o) + 7]), bar)
__device__ __forceinline__ void fence_async() { asm volatile("fence.proxy.async.shared::cta;" ::: "memory"); }
__device__ __forceinline__ void prefetch_map(const CUtensorMap* m) {
  asm volatile("prefetch.tensormap [%0];" ::"l"(m) : "memory");
}
__device__ __forceinline__ bool elect_one() {
  uint32_t p;
  asm volatile("{\n.reg .pred q;\nelect.sync _|q, 0xffffffff;\nselp.u32 %0, 1, 0, q;\n}" : "=r"(p));
  return p;
}
__device__ __forceinline__ void pdl_wait() { asm volatile("griddepcontrol.wait;" ::: "memory"); }
__device__ __forceinline__ void pdl_trigger() { asm volatile("griddepcontrol.launch_dependents;" ::: "memory"); }
__device__ __forceinline__ void bar_sync(int id, int n) { asm volatile("bar.sync %0, %1;" ::"r"(id), "r"(n) : "memory"); }
__device__ __forceinline__ void bar_arrive(int id, int n) { asm volatile("bar.arrive %0, %1;" ::"r"(id), "r"(n) : "memory"); }
#define WG_FENCE() asm volatile("wgmma.fence.sync.aligned;" ::: "memory")
#define WG_COMMIT() asm volatile("wgmma.commit_group.sync.aligned;" ::: "memory")
#define WG_WAIT(n) asm volatile("wgmma.wait_group.sync.aligned %0;" ::"n"(n) : "memory")
__device__ __forceinline__ uint64_t mkdesc(uint32_t addr, uint32_t lbo, uint32_t sbo, uint32_t sw) {
  return (uint64_t)((addr & 0x3FFFF) >> 4) | ((uint64_t)(lbo >> 4) << 16) | ((uint64_t)(sbo >> 4) << 32) |
         ((uint64_t)sw << 62);
}
template <int N> __device__ __forceinline__ void fence_regs(float (&r)[N]) {
#pragma unroll
  for (int i = 0; i < N; i++) asm volatile("" : "+f"(r[i])::"memory");
}
__device__ __forceinline__ uint32_t pack_bf16(float lo, float hi) {
  uint32_t r;
  asm("cvt.rn.bf16x2.f32 %0, %1, %2;" : "=r"(r) : "f"(hi), "f"(lo));
  return r;
}
__device__ __forceinline__ float bf_lo(uint32_t v) { return __uint_as_float(v << 16); }
__device__ __forceinline__ float bf_hi(uint32_t v) { return __uint_as_float(v & 0xffff0000u); }
__device__ __forceinline__ float ex2(float x) {
  float y;
  asm("ex2.approx.ftz.f32 %0, %1;" : "=f"(y) : "f"(x));
  return y;
}
__device__ __forceinline__ uint4 ldg_nc(const void* p) {
  uint4 v;
  asm volatile("ld.global.nc.L1::no_allocate.v4.u32 {%0, %1, %2, %3}, [%4];"
               : "=r"(v.x), "=r"(v.y), "=r"(v.z), "=r"(v.w) : "l"(p));
  return v;
}

__device__ __forceinline__ uint4 ld_relaxed(const uint4* p) {
  uint64_t a, b;
  asm volatile("ld.relaxed.gpu.global.v2.u64 {%0, %1}, [%2];" : "=l"(a), "=l"(b) : "l"(p) : "memory");
  return make_uint4((uint32_t)a, (uint32_t)(a >> 32), (uint32_t)b, (uint32_t)(b >> 32));
}
__device__ __forceinline__ void st_relaxed(uint4* p, float x, float y, uint32_t tag) {
  const uint64_t a = ((uint64_t)tag << 32) | __float_as_uint(x), b = ((uint64_t)tag << 32) | __float_as_uint(y);
  asm volatile("st.relaxed.gpu.global.v2.u64 [%0], {%1, %2};" ::"l"(p), "l"(a), "l"(b) : "memory");
}
__device__ __forceinline__ void tma4d(uint32_t dst, const CUtensorMap* m, int c2, int c3, uint32_t bar) {
  asm volatile("cp.async.bulk.tensor.4d.shared::cluster.global.mbarrier::complete_tx::bytes [%0], [%1, {%3, %3, %4, %5}], [%2];"
               ::"r"(dst), "l"(m), "r"(bar), "r"(0), "r"(c2), "r"(c3) : "memory");
}
#define ACC8(a, v) do { a[0] += bf_lo(v.x); a[1] += bf_hi(v.x); a[2] += bf_lo(v.y); a[3] += bf_hi(v.y); \
                        a[4] += bf_lo(v.z); a[5] += bf_hi(v.z); a[6] += bf_lo(v.w); a[7] += bf_hi(v.w); } while (0)

__device__ __forceinline__ void wgmma_ss_n224(float (&d)[112], uint64_t da, uint64_t db, int sd) {
  asm volatile("{\n.reg .pred p;\nsetp.ne.b32 p, %114, 0;\n"
      "wgmma.mma_async.sync.aligned.m64n224k16.f32.bf16.bf16 {"
      "%0, %1, %2, %3, %4, %5, %6, %7, %8, %9, %10, %11, %12, %13, %14, %15, "
      "%16, %17, %18, %19, %20, %21, %22, %23, %24, %25, %26, %27, %28, %29, %30, %31, "
      "%32, %33, %34, %35, %36, %37, %38, %39, %40, %41, %42, %43, %44, %45, %46, %47, "
      "%48, %49, %50, %51, %52, %53, %54, %55, %56, %57, %58, %59, %60, %61, %62, %63, "
      "%64, %65, %66, %67, %68, %69, %70, %71, %72, %73, %74, %75, %76, %77, %78, %79, "
      "%80, %81, %82, %83, %84, %85, %86, %87, %88, %89, %90, %91, %92, %93, %94, %95, "
      "%96, %97, %98, %99, %100, %101, %102, %103, %104, %105, %106, %107, %108, %109, %110, %111"
      "}, %112, %113, p, 1, 1, 0, 1;\n}\n"
    : "+f"(d[0]), "+f"(d[1]), "+f"(d[2]), "+f"(d[3]), "+f"(d[4]), "+f"(d[5]), "+f"(d[6]), "+f"(d[7]),
      "+f"(d[8]), "+f"(d[9]), "+f"(d[10]), "+f"(d[11]), "+f"(d[12]), "+f"(d[13]), "+f"(d[14]), "+f"(d[15]),
      "+f"(d[16]), "+f"(d[17]), "+f"(d[18]), "+f"(d[19]), "+f"(d[20]), "+f"(d[21]), "+f"(d[22]), "+f"(d[23]),
      "+f"(d[24]), "+f"(d[25]), "+f"(d[26]), "+f"(d[27]), "+f"(d[28]), "+f"(d[29]), "+f"(d[30]), "+f"(d[31]),
      "+f"(d[32]), "+f"(d[33]), "+f"(d[34]), "+f"(d[35]), "+f"(d[36]), "+f"(d[37]), "+f"(d[38]), "+f"(d[39]),
      "+f"(d[40]), "+f"(d[41]), "+f"(d[42]), "+f"(d[43]), "+f"(d[44]), "+f"(d[45]), "+f"(d[46]), "+f"(d[47]),
      "+f"(d[48]), "+f"(d[49]), "+f"(d[50]), "+f"(d[51]), "+f"(d[52]), "+f"(d[53]), "+f"(d[54]), "+f"(d[55]),
      "+f"(d[56]), "+f"(d[57]), "+f"(d[58]), "+f"(d[59]), "+f"(d[60]), "+f"(d[61]), "+f"(d[62]), "+f"(d[63]),
      "+f"(d[64]), "+f"(d[65]), "+f"(d[66]), "+f"(d[67]), "+f"(d[68]), "+f"(d[69]), "+f"(d[70]), "+f"(d[71]),
      "+f"(d[72]), "+f"(d[73]), "+f"(d[74]), "+f"(d[75]), "+f"(d[76]), "+f"(d[77]), "+f"(d[78]), "+f"(d[79]),
      "+f"(d[80]), "+f"(d[81]), "+f"(d[82]), "+f"(d[83]), "+f"(d[84]), "+f"(d[85]), "+f"(d[86]), "+f"(d[87]),
      "+f"(d[88]), "+f"(d[89]), "+f"(d[90]), "+f"(d[91]), "+f"(d[92]), "+f"(d[93]), "+f"(d[94]), "+f"(d[95]),
      "+f"(d[96]), "+f"(d[97]), "+f"(d[98]), "+f"(d[99]), "+f"(d[100]), "+f"(d[101]), "+f"(d[102]), "+f"(d[103]),
      "+f"(d[104]), "+f"(d[105]), "+f"(d[106]), "+f"(d[107]), "+f"(d[108]), "+f"(d[109]), "+f"(d[110]), "+f"(d[111])
    : "l"(da), "l"(db), "r"(sd));
}
__device__ __forceinline__ void wgmma_ss_n208(float (&d)[104], uint64_t da, uint64_t db, int sd) {
  asm volatile("{\n.reg .pred p;\nsetp.ne.b32 p, %106, 0;\n"
      "wgmma.mma_async.sync.aligned.m64n208k16.f32.bf16.bf16 {"
      "%0, %1, %2, %3, %4, %5, %6, %7, %8, %9, %10, %11, %12, %13, %14, %15, "
      "%16, %17, %18, %19, %20, %21, %22, %23, %24, %25, %26, %27, %28, %29, %30, %31, "
      "%32, %33, %34, %35, %36, %37, %38, %39, %40, %41, %42, %43, %44, %45, %46, %47, "
      "%48, %49, %50, %51, %52, %53, %54, %55, %56, %57, %58, %59, %60, %61, %62, %63, "
      "%64, %65, %66, %67, %68, %69, %70, %71, %72, %73, %74, %75, %76, %77, %78, %79, "
      "%80, %81, %82, %83, %84, %85, %86, %87, %88, %89, %90, %91, %92, %93, %94, %95, "
      "%96, %97, %98, %99, %100, %101, %102, %103"
      "}, %104, %105, p, 1, 1, 0, 1;\n}\n"
    : "+f"(d[0]), "+f"(d[1]), "+f"(d[2]), "+f"(d[3]), "+f"(d[4]), "+f"(d[5]), "+f"(d[6]), "+f"(d[7]),
      "+f"(d[8]), "+f"(d[9]), "+f"(d[10]), "+f"(d[11]), "+f"(d[12]), "+f"(d[13]), "+f"(d[14]), "+f"(d[15]),
      "+f"(d[16]), "+f"(d[17]), "+f"(d[18]), "+f"(d[19]), "+f"(d[20]), "+f"(d[21]), "+f"(d[22]), "+f"(d[23]),
      "+f"(d[24]), "+f"(d[25]), "+f"(d[26]), "+f"(d[27]), "+f"(d[28]), "+f"(d[29]), "+f"(d[30]), "+f"(d[31]),
      "+f"(d[32]), "+f"(d[33]), "+f"(d[34]), "+f"(d[35]), "+f"(d[36]), "+f"(d[37]), "+f"(d[38]), "+f"(d[39]),
      "+f"(d[40]), "+f"(d[41]), "+f"(d[42]), "+f"(d[43]), "+f"(d[44]), "+f"(d[45]), "+f"(d[46]), "+f"(d[47]),
      "+f"(d[48]), "+f"(d[49]), "+f"(d[50]), "+f"(d[51]), "+f"(d[52]), "+f"(d[53]), "+f"(d[54]), "+f"(d[55]),
      "+f"(d[56]), "+f"(d[57]), "+f"(d[58]), "+f"(d[59]), "+f"(d[60]), "+f"(d[61]), "+f"(d[62]), "+f"(d[63]),
      "+f"(d[64]), "+f"(d[65]), "+f"(d[66]), "+f"(d[67]), "+f"(d[68]), "+f"(d[69]), "+f"(d[70]), "+f"(d[71]),
      "+f"(d[72]), "+f"(d[73]), "+f"(d[74]), "+f"(d[75]), "+f"(d[76]), "+f"(d[77]), "+f"(d[78]), "+f"(d[79]),
      "+f"(d[80]), "+f"(d[81]), "+f"(d[82]), "+f"(d[83]), "+f"(d[84]), "+f"(d[85]), "+f"(d[86]), "+f"(d[87]),
      "+f"(d[88]), "+f"(d[89]), "+f"(d[90]), "+f"(d[91]), "+f"(d[92]), "+f"(d[93]), "+f"(d[94]), "+f"(d[95]),
      "+f"(d[96]), "+f"(d[97]), "+f"(d[98]), "+f"(d[99]), "+f"(d[100]), "+f"(d[101]), "+f"(d[102]), "+f"(d[103])
    : "l"(da), "l"(db), "r"(sd));
}
__device__ __forceinline__ void wgmma_ss_n168(float (&d)[84], uint64_t da, uint64_t db, int sd) {
  asm volatile("{\n.reg .pred p;\nsetp.ne.b32 p, %86, 0;\n"
      "wgmma.mma_async.sync.aligned.m64n168k16.f32.bf16.bf16 {"
      "%0, %1, %2, %3, %4, %5, %6, %7, %8, %9, %10, %11, %12, %13, %14, %15, "
      "%16, %17, %18, %19, %20, %21, %22, %23, %24, %25, %26, %27, %28, %29, %30, %31, "
      "%32, %33, %34, %35, %36, %37, %38, %39, %40, %41, %42, %43, %44, %45, %46, %47, "
      "%48, %49, %50, %51, %52, %53, %54, %55, %56, %57, %58, %59, %60, %61, %62, %63, "
      "%64, %65, %66, %67, %68, %69, %70, %71, %72, %73, %74, %75, %76, %77, %78, %79, "
      "%80, %81, %82, %83"
      "}, %84, %85, p, 1, 1, 0, 1;\n}\n"
    : "+f"(d[0]), "+f"(d[1]), "+f"(d[2]), "+f"(d[3]), "+f"(d[4]), "+f"(d[5]), "+f"(d[6]), "+f"(d[7]),
      "+f"(d[8]), "+f"(d[9]), "+f"(d[10]), "+f"(d[11]), "+f"(d[12]), "+f"(d[13]), "+f"(d[14]), "+f"(d[15]),
      "+f"(d[16]), "+f"(d[17]), "+f"(d[18]), "+f"(d[19]), "+f"(d[20]), "+f"(d[21]), "+f"(d[22]), "+f"(d[23]),
      "+f"(d[24]), "+f"(d[25]), "+f"(d[26]), "+f"(d[27]), "+f"(d[28]), "+f"(d[29]), "+f"(d[30]), "+f"(d[31]),
      "+f"(d[32]), "+f"(d[33]), "+f"(d[34]), "+f"(d[35]), "+f"(d[36]), "+f"(d[37]), "+f"(d[38]), "+f"(d[39]),
      "+f"(d[40]), "+f"(d[41]), "+f"(d[42]), "+f"(d[43]), "+f"(d[44]), "+f"(d[45]), "+f"(d[46]), "+f"(d[47]),
      "+f"(d[48]), "+f"(d[49]), "+f"(d[50]), "+f"(d[51]), "+f"(d[52]), "+f"(d[53]), "+f"(d[54]), "+f"(d[55]),
      "+f"(d[56]), "+f"(d[57]), "+f"(d[58]), "+f"(d[59]), "+f"(d[60]), "+f"(d[61]), "+f"(d[62]), "+f"(d[63]),
      "+f"(d[64]), "+f"(d[65]), "+f"(d[66]), "+f"(d[67]), "+f"(d[68]), "+f"(d[69]), "+f"(d[70]), "+f"(d[71]),
      "+f"(d[72]), "+f"(d[73]), "+f"(d[74]), "+f"(d[75]), "+f"(d[76]), "+f"(d[77]), "+f"(d[78]), "+f"(d[79]),
      "+f"(d[80]), "+f"(d[81]), "+f"(d[82]), "+f"(d[83])
    : "l"(da), "l"(db), "r"(sd));
}
__device__ __forceinline__ void wgmma_ss_n160(float (&d)[80], uint64_t da, uint64_t db, int sd) {
  asm volatile("{\n.reg .pred p;\nsetp.ne.b32 p, %82, 0;\n"
      "wgmma.mma_async.sync.aligned.m64n160k16.f32.bf16.bf16 {"
      "%0, %1, %2, %3, %4, %5, %6, %7, %8, %9, %10, %11, %12, %13, %14, %15, "
      "%16, %17, %18, %19, %20, %21, %22, %23, %24, %25, %26, %27, %28, %29, %30, %31, "
      "%32, %33, %34, %35, %36, %37, %38, %39, %40, %41, %42, %43, %44, %45, %46, %47, "
      "%48, %49, %50, %51, %52, %53, %54, %55, %56, %57, %58, %59, %60, %61, %62, %63, "
      "%64, %65, %66, %67, %68, %69, %70, %71, %72, %73, %74, %75, %76, %77, %78, %79"
      "}, %80, %81, p, 1, 1, 0, 1;\n}\n"
    : "+f"(d[0]), "+f"(d[1]), "+f"(d[2]), "+f"(d[3]), "+f"(d[4]), "+f"(d[5]), "+f"(d[6]), "+f"(d[7]),
      "+f"(d[8]), "+f"(d[9]), "+f"(d[10]), "+f"(d[11]), "+f"(d[12]), "+f"(d[13]), "+f"(d[14]), "+f"(d[15]),
      "+f"(d[16]), "+f"(d[17]), "+f"(d[18]), "+f"(d[19]), "+f"(d[20]), "+f"(d[21]), "+f"(d[22]), "+f"(d[23]),
      "+f"(d[24]), "+f"(d[25]), "+f"(d[26]), "+f"(d[27]), "+f"(d[28]), "+f"(d[29]), "+f"(d[30]), "+f"(d[31]),
      "+f"(d[32]), "+f"(d[33]), "+f"(d[34]), "+f"(d[35]), "+f"(d[36]), "+f"(d[37]), "+f"(d[38]), "+f"(d[39]),
      "+f"(d[40]), "+f"(d[41]), "+f"(d[42]), "+f"(d[43]), "+f"(d[44]), "+f"(d[45]), "+f"(d[46]), "+f"(d[47]),
      "+f"(d[48]), "+f"(d[49]), "+f"(d[50]), "+f"(d[51]), "+f"(d[52]), "+f"(d[53]), "+f"(d[54]), "+f"(d[55]),
      "+f"(d[56]), "+f"(d[57]), "+f"(d[58]), "+f"(d[59]), "+f"(d[60]), "+f"(d[61]), "+f"(d[62]), "+f"(d[63]),
      "+f"(d[64]), "+f"(d[65]), "+f"(d[66]), "+f"(d[67]), "+f"(d[68]), "+f"(d[69]), "+f"(d[70]), "+f"(d[71]),
      "+f"(d[72]), "+f"(d[73]), "+f"(d[74]), "+f"(d[75]), "+f"(d[76]), "+f"(d[77]), "+f"(d[78]), "+f"(d[79])
    : "l"(da), "l"(db), "r"(sd));
}
__device__ __forceinline__ void wgmma_ss_n88(float (&d)[44], uint64_t da, uint64_t db, int sd) {
  asm volatile("{\n.reg .pred p;\nsetp.ne.b32 p, %46, 0;\n"
      "wgmma.mma_async.sync.aligned.m64n88k16.f32.bf16.bf16 {"
      "%0, %1, %2, %3, %4, %5, %6, %7, %8, %9, %10, %11, %12, %13, %14, %15, "
      "%16, %17, %18, %19, %20, %21, %22, %23, %24, %25, %26, %27, %28, %29, %30, %31, "
      "%32, %33, %34, %35, %36, %37, %38, %39, %40, %41, %42, %43"
      "}, %44, %45, p, 1, 1, 0, 1;\n}\n"
    : "+f"(d[0]), "+f"(d[1]), "+f"(d[2]), "+f"(d[3]), "+f"(d[4]), "+f"(d[5]), "+f"(d[6]), "+f"(d[7]),
      "+f"(d[8]), "+f"(d[9]), "+f"(d[10]), "+f"(d[11]), "+f"(d[12]), "+f"(d[13]), "+f"(d[14]), "+f"(d[15]),
      "+f"(d[16]), "+f"(d[17]), "+f"(d[18]), "+f"(d[19]), "+f"(d[20]), "+f"(d[21]), "+f"(d[22]), "+f"(d[23]),
      "+f"(d[24]), "+f"(d[25]), "+f"(d[26]), "+f"(d[27]), "+f"(d[28]), "+f"(d[29]), "+f"(d[30]), "+f"(d[31]),
      "+f"(d[32]), "+f"(d[33]), "+f"(d[34]), "+f"(d[35]), "+f"(d[36]), "+f"(d[37]), "+f"(d[38]), "+f"(d[39]),
      "+f"(d[40]), "+f"(d[41]), "+f"(d[42]), "+f"(d[43])
    : "l"(da), "l"(db), "r"(sd));
}
__device__ __forceinline__ void wgmma_ss_n80(float (&d)[40], uint64_t da, uint64_t db, int sd) {
  asm volatile("{\n.reg .pred p;\nsetp.ne.b32 p, %42, 0;\n"
      "wgmma.mma_async.sync.aligned.m64n80k16.f32.bf16.bf16 {"
      "%0, %1, %2, %3, %4, %5, %6, %7, %8, %9, %10, %11, %12, %13, %14, %15, "
      "%16, %17, %18, %19, %20, %21, %22, %23, %24, %25, %26, %27, %28, %29, %30, %31, "
      "%32, %33, %34, %35, %36, %37, %38, %39"
      "}, %40, %41, p, 1, 1, 0, 1;\n}\n"
    : "+f"(d[0]), "+f"(d[1]), "+f"(d[2]), "+f"(d[3]), "+f"(d[4]), "+f"(d[5]), "+f"(d[6]), "+f"(d[7]),
      "+f"(d[8]), "+f"(d[9]), "+f"(d[10]), "+f"(d[11]), "+f"(d[12]), "+f"(d[13]), "+f"(d[14]), "+f"(d[15]),
      "+f"(d[16]), "+f"(d[17]), "+f"(d[18]), "+f"(d[19]), "+f"(d[20]), "+f"(d[21]), "+f"(d[22]), "+f"(d[23]),
      "+f"(d[24]), "+f"(d[25]), "+f"(d[26]), "+f"(d[27]), "+f"(d[28]), "+f"(d[29]), "+f"(d[30]), "+f"(d[31]),
      "+f"(d[32]), "+f"(d[33]), "+f"(d[34]), "+f"(d[35]), "+f"(d[36]), "+f"(d[37]), "+f"(d[38]), "+f"(d[39])
    : "l"(da), "l"(db), "r"(sd));
}
__device__ __forceinline__ void wgmma_rs_n128(float (&d)[64], uint32_t a0, uint32_t a1, uint32_t a2, uint32_t a3,
                                  uint64_t db, int sd) {
  asm volatile("{\n.reg .pred p;\nsetp.ne.b32 p, %69, 0;\n"
      "wgmma.mma_async.sync.aligned.m64n128k16.f32.bf16.bf16 {"
      "%0, %1, %2, %3, %4, %5, %6, %7, %8, %9, %10, %11, %12, %13, %14, %15, "
      "%16, %17, %18, %19, %20, %21, %22, %23, %24, %25, %26, %27, %28, %29, %30, %31, "
      "%32, %33, %34, %35, %36, %37, %38, %39, %40, %41, %42, %43, %44, %45, %46, %47, "
      "%48, %49, %50, %51, %52, %53, %54, %55, %56, %57, %58, %59, %60, %61, %62, %63"
      "}, {%64, %65, %66, %67}, %68, p, 1, 1, 0;\n}\n"
    : "+f"(d[0]), "+f"(d[1]), "+f"(d[2]), "+f"(d[3]), "+f"(d[4]), "+f"(d[5]), "+f"(d[6]), "+f"(d[7]),
      "+f"(d[8]), "+f"(d[9]), "+f"(d[10]), "+f"(d[11]), "+f"(d[12]), "+f"(d[13]), "+f"(d[14]), "+f"(d[15]),
      "+f"(d[16]), "+f"(d[17]), "+f"(d[18]), "+f"(d[19]), "+f"(d[20]), "+f"(d[21]), "+f"(d[22]), "+f"(d[23]),
      "+f"(d[24]), "+f"(d[25]), "+f"(d[26]), "+f"(d[27]), "+f"(d[28]), "+f"(d[29]), "+f"(d[30]), "+f"(d[31]),
      "+f"(d[32]), "+f"(d[33]), "+f"(d[34]), "+f"(d[35]), "+f"(d[36]), "+f"(d[37]), "+f"(d[38]), "+f"(d[39]),
      "+f"(d[40]), "+f"(d[41]), "+f"(d[42]), "+f"(d[43]), "+f"(d[44]), "+f"(d[45]), "+f"(d[46]), "+f"(d[47]),
      "+f"(d[48]), "+f"(d[49]), "+f"(d[50]), "+f"(d[51]), "+f"(d[52]), "+f"(d[53]), "+f"(d[54]), "+f"(d[55]),
      "+f"(d[56]), "+f"(d[57]), "+f"(d[58]), "+f"(d[59]), "+f"(d[60]), "+f"(d[61]), "+f"(d[62]), "+f"(d[63])
    : "r"(a0), "r"(a1), "r"(a2), "r"(a3), "l"(db), "r"(sd));
}
__device__ __forceinline__ void wgmma_rs_n24(float (&d)[12], uint32_t a0, uint32_t a1, uint32_t a2, uint32_t a3,
                                  uint64_t db, int sd) {
  asm volatile("{\n.reg .pred p;\nsetp.ne.b32 p, %17, 0;\n"
      "wgmma.mma_async.sync.aligned.m64n24k16.f32.bf16.bf16 {"
      "%0, %1, %2, %3, %4, %5, %6, %7, %8, %9, %10, %11"
      "}, {%12, %13, %14, %15}, %16, p, 1, 1, 1;\n}\n"
    : "+f"(d[0]), "+f"(d[1]), "+f"(d[2]), "+f"(d[3]), "+f"(d[4]), "+f"(d[5]), "+f"(d[6]), "+f"(d[7]),
      "+f"(d[8]), "+f"(d[9]), "+f"(d[10]), "+f"(d[11])
    : "r"(a0), "r"(a1), "r"(a2), "r"(a3), "l"(db), "r"(sd));
}

constexpr int KST = 4;
constexpr int K1_ST = 4, K1_STAGE = 45056;
constexpr int K1_SMEM = K1_ST * K1_STAGE + 640   + 1536   + 2560   + 128;

__device__ __forceinline__ float2 row_stats(uint4 v0, uint4 v1, uint4 v2) {
  const uint32_t wd[12] = {v0.x, v0.y, v0.z, v0.w, v1.x, v1.y, v1.z, v1.w, v2.x, v2.y, v2.z, v2.w};
  float sx = 0.f, sq = 0.f;
#pragma unroll
  for (int e = 0; e < 12; e++) {
    const float lo = bf_lo(wd[e]), hi = bf_hi(wd[e]);
    sx += lo + hi; sq = fmaf(lo, lo, fmaf(hi, hi, sq));
  }
#pragma unroll
  for (int o = 16; o; o >>= 1) { sx += __shfl_xor_sync(~0u, sx, o); sq += __shfl_xor_sync(~0u, sq, o); }
  const float mean = sx * (1.f / D_);
  return make_float2(rsqrtf(fmaxf(sq * (1.f / D_) - mean * mean, 0.f) + 1e-5f), mean);
}

__global__ void __launch_bounds__(512, 1)
k1_qkv(const __grid_constant__ CUtensorMap tmx, const __grid_constant__ CUtensorMap tmw,
       const bf16* __restrict__ x, const bf16* __restrict__ w) {
  extern __shared__ __align__(1024) uint8_t sm[];
  float* cs = (float*)(sm + K1_ST * K1_STAGE);
  float2* rowab = (float2*)(sm + K1_ST * K1_STAGE + 640);
  float* red = (float*)(sm + K1_ST * K1_STAGE + 2176);
  const uint32_t sbase = smem_u32(sm);
  const uint32_t fullb = sbase + K1_ST * K1_STAGE + 4736, emptyb = fullb + 8 * K1_ST;
  const int tid = threadIdx.x, lane = tid & 31;
  const int warp = __shfl_sync(~0u, tid >> 5, 0);
  const int m = blockIdx.x / 12, n = blockIdx.x - m * 12;

  if (warp == 12) {
    if (lane == 0) {
      prefetch_map(&tmx); prefetch_map(&tmw);
      for (int i = 0; i < K1_ST; i++) { mbar_init(fullb + 8 * i, 1); mbar_init(emptyb + 8 * i, 3); }
      asm volatile("fence.mbarrier_init.release.cluster;" ::: "memory");
    }
    __syncwarp();
    bar_arrive(4, 512);
#pragma unroll 1
    for (int kt = 0; kt < 10; kt++) {
      const int s = kt % K1_ST;
      const uint32_t sa = sbase + s * K1_STAGE;
      if (kt >= K1_ST) mbar_wait(emptyb + 8 * s, ((kt / K1_ST) - 1) & 1);
      if (elect_one()) {
        mbar_expect(fullb + 8 * s, K1_STAGE);
        tma2d(sa, &tmx, kt * 64, m * 192, fullb + 8 * s);
#pragma unroll
        for (int j = 0; j < 5; j++) tma2d(sa + 24576 + j * 4096, &tmw, n * 160 + j * 32, kt * 64, fullb + 8 * s);
      }
      if (kt == K1_ST - 1) pdl_trigger();
    }
    __syncwarp();
  } else if (warp > 12) {
    const int t96 = tid - 416;
    const uint32_t tag = __ldcg(&g_epoch) + 1;
    bar_sync(4, 512);
    mbar_wait(fullb, 0);
    if (m < 10) {
      const int ck = t96 % 20, rg = min(t96 / 20, 3);
      uint4 wv[16];
#pragma unroll
      for (int i = 0; i < 16; i++) wv[i] = ldg_nc(w + (size_t)(m * 64 + rg * 16 + i) * 1920 + n * 160 + ck * 8);
      float acc8[8];
#pragma unroll
      for (int i = 0; i < 8; i++) acc8[i] = 0.f;
#pragma unroll
      for (int i = 0; i < 16; i++) ACC8(acc8, wv[i]);
      *(float4*)&red[rg * 160 + ck * 8] = make_float4(acc8[0], acc8[1], acc8[2], acc8[3]);
      *(float4*)&red[rg * 160 + ck * 8 + 4] = make_float4(acc8[4], acc8[5], acc8[6], acc8[7]);
      bar_sync(1, 96);
      if (t96 < 80) {
        const float2 p0 = *(const float2*)&red[t96 * 2], p1 = *(const float2*)&red[160 + t96 * 2];
        const float2 p2 = *(const float2*)&red[320 + t96 * 2], p3 = *(const float2*)&red[480 + t96 * 2];
        st_relaxed(&g_cpart[(m * 12 + n) * 80 + t96], (p0.x + p1.x) + (p2.x + p3.x), (p0.y + p1.y) + (p2.y + p3.y), tag);
      }
    }
    bool ok = false;
    for (int it = 0; it < 64 && !ok; it++) {
      uint4 p[10], st[2];
#pragma unroll
      for (int k = 0; k < 10; k++) p[k] = ld_relaxed(&g_cpart[(k * 12 + n) * 80 + min(t96, 79)]);
#pragma unroll
      for (int k = 0; k < 2; k++) st[k] = ld_relaxed(&g_rowstat[min(m * 192 + k * 96 + t96, S_ - 1)]);
      ok = true;
      float s0 = 0.f, s1 = 0.f;
#pragma unroll
      for (int k = 0; k < 10; k++) {
        ok = ok && p[k].y == tag && p[k].w == tag;
        s0 += __uint_as_float(p[k].x); s1 += __uint_as_float(p[k].z);
      }
      if (t96 < 80) *(float2*)&cs[t96 * 2] = make_float2(s0, s1);
#pragma unroll
      for (int k = 0; k < 2; k++) {
        ok = ok && st[k].y == tag && st[k].w == tag;
        rowab[k * 96 + t96] = make_float2(__uint_as_float(st[k].x), -__uint_as_float(st[k].x) * __uint_as_float(st[k].z));
      }
      ok = __all_sync(~0u, ok);
      if (!ok) __nanosleep(300);
    }
    if (!ok) {
      const int c2 = min(t96, 79);
      float s0 = 0.f, s1 = 0.f;
#pragma unroll 1
      for (int k = 0; k < D_; k++) {
        const uint32_t v = *(const uint32_t*)(w + (size_t)k * 1920 + n * 160 + c2 * 2);
        s0 += bf_lo(v); s1 += bf_hi(v);
      }
      if (t96 < 80) *(float2*)&cs[t96 * 2] = make_float2(s0, s1);
#pragma unroll 1
      for (int i = 0; i < 64; i++) {
        const int r = (i >> 5) * 96 + (t96 & ~31) + (i & 31);
        const bf16* xr = x + (size_t)min(m * 192 + r, S_ - 1) * D_ + lane * 8;
        const float2 st = row_stats(ldg_nc(xr), ldg_nc(xr + 256), lane < 16 ? ldg_nc(xr + 512) : make_uint4(0u, 0u, 0u, 0u));
        if (lane == 0) rowab[r] = make_float2(st.x, -st.x * st.y);
      }
    }
    __syncwarp();
    bar_arrive(2, 96 + 384);
    __syncwarp();
  } else {
    float acc[80];
    const uint64_t da0 = mkdesc(sbase + (warp >> 2) * 8192, 16, 1024, 1);
    const uint64_t db0 = mkdesc(sbase + 24576, 4096, 512, 2);
    const uint32_t tag = __ldcg(&g_epoch) + 1;
    const int srow = m * 192 + n * 16 + warp * 2;
    const bool dostat = warp < 8 && srow < S_;
    uint4 xv[2][3];
    bar_sync(4, 512);
#pragma unroll
    for (int kt = 0; kt < 10; kt++) {
      const int s = kt % K1_ST;
      mbar_wait(fullb + 8 * s, (kt / K1_ST) & 1);
      const uint64_t da = da0 + s * (K1_STAGE >> 4), db = db0 + s * (K1_STAGE >> 4);
      WG_FENCE();
#pragma unroll
      for (int k = 0; k < 4; k++) wgmma_ss_n160(acc, da + k * 2, db + k * 64, (kt | k) != 0);
      WG_COMMIT();
      if (kt > 0) {
        WG_WAIT(1);
        if (kt - 1 + K1_ST < 10 && (tid & 127) == 0) mbar_arrive(emptyb + 8 * ((kt - 1) % K1_ST));
      }
      if (kt == 0) {
#pragma unroll
        for (int i = 0; i < 2; i++) {
          const bf16* xr = x + (size_t)min(srow + i, S_ - 1) * D_ + lane * 8;
          xv[i][0] = xv[i][1] = xv[i][2] = make_uint4(0u, 0u, 0u, 0u);
          if (dostat) { xv[i][0] = ldg_nc(xr); xv[i][1] = ldg_nc(xr + 256); }
          if (dostat && lane < 16) xv[i][2] = ldg_nc(xr + 512);
        }
      }
      if ((kt == KST || kt == KST + 1) && dostat) {
        const float2 st = row_stats(xv[kt - KST][0], xv[kt - KST][1], xv[kt - KST][2]);
        if (lane == 0) st_relaxed(&g_rowstat[srow + kt - KST], st.x, st.y, tag);
      }
      __syncwarp();
    }
    WG_WAIT(0);
    fence_regs(acc);
    bar_sync(2, 96 + 384);
    const int row0 = m * 192 + warp * 16;
    if (row0 < S_) {
      const int g = lane >> 2, c = lane & 3, sec = n >> 2, grp = (row0 & 127) >> 3;
      const bool lo = c < 2;
      const float2 ab0 = rowab[warp * 16 + g], ab1 = rowab[warp * 16 + g + 8];
      const bool p0 = sec == 1 && ((POLY_MASK >> grp) & 1), p1 = sec == 1 && ((POLY_MASK >> (grp + 1)) & 1);
      const uint32_t padqv = sec == 0 ? (c == 2 ? 0x3F803F80u : 0x00003F80u) : (sec == 2 && c == 2 ? 0x00003F80u : 0u);
      const uint32_t padk = c == 2 ? 0x4A7A4B00u : 0x00004653u;
      const uint32_t pad0 = p0 ? padk : padqv, pad1 = p1 ? padk : padqv;
      const float f0 = sec == 0 ? QSCALE : (p0 ? 32768.f : 1.f), f1 = sec == 0 ? QSCALE : (p1 ? 32768.f : 1.f);
      const float a0 = ab0.x * f0, b0 = ab0.y * f0, a1 = ab1.x * f1, b1 = ab1.y * f1;
      const float r0 = p0 ? 9.313225746154785e-10f : 1.f, r1 = p1 ? 9.313225746154785e-10f : 1.f;
      const int cst = sec == 1 ? 2048 : 128, gst = sec == 1 ? 128 : 384;
      uint8_t* pe = (uint8_t*)g_qkv + (size_t)(n * 8) * HEAD_IMG + (row0 >> 7) * 6144 + grp * gst + lane * 4;
      uint8_t* pe1 = pe + cst;
      uint8_t* pe2 = pe1 + cst;
      uint8_t* pf = pe + gst;
      uint8_t* pf1 = pf + cst;
      uint8_t* pf2 = pf1 + cst;
      uint32_t u[20], v[20];
#pragma unroll
      for (int hp = 0; hp < 4; hp++) {
#pragma unroll
        for (int j = hp * 5; j < hp * 5 + 5; j++) {
          const float2 t = *(const float2*)&cs[j * 8 + c * 2];
          u[j] = pack_bf16(fmaf(acc[4 * j], a0, b0 * t.x), fmaf(acc[4 * j + 1], a0, b0 * t.y));
          v[j] = pack_bf16(fmaf(acc[4 * j + 2], a1, b1 * t.x), fmaf(acc[4 * j + 3], a1, b1 * t.y));
        }
        constexpr int HE = HEAD_IMG;
        const int oe = hp * 2 * HE, oo = oe + HE, j = hp * 5;
        *(uint32_t*)(pe + oe) = u[j];      *(uint32_t*)(pf + oe) = v[j];
        *(uint32_t*)(pe1 + oe) = u[j + 1]; *(uint32_t*)(pf1 + oe) = v[j + 1];
        *(uint32_t*)(pe2 + oe) = lo ? u[j + 2] : pad0; *(uint32_t*)(pf2 + oe) = lo ? v[j + 2] : pad1;
        *(uint32_t*)(pe + oo) = __shfl_xor_sync(~0u, lo ? u[j + 3] : u[j + 2], 2);
        *(uint32_t*)(pf + oo) = __shfl_xor_sync(~0u, lo ? v[j + 3] : v[j + 2], 2);
        *(uint32_t*)(pe1 + oo) = __shfl_xor_sync(~0u, lo ? u[j + 4] : u[j + 3], 2);
        *(uint32_t*)(pf1 + oo) = __shfl_xor_sync(~0u, lo ? v[j + 4] : v[j + 3], 2);
        const uint32_t tu = __shfl_xor_sync(~0u, u[j + 4], 2), tv = __shfl_xor_sync(~0u, v[j + 4], 2);
        *(uint32_t*)(pe2 + oo) = lo ? tu : pad0; *(uint32_t*)(pf2 + oo) = lo ? tv : pad1;
      }
      {
        float nm = 0.f;
#pragma unroll
        for (int hp = 0; hp < 4; hp++) {
          float sq[2][5];
#pragma unroll
          for (int i = 0; i < 5; i++) {
            const uint32_t x = u[hp * 5 + i], y = v[hp * 5 + i];
            sq[0][i] = fmaf(bf_lo(x), bf_lo(x), bf_hi(x) * bf_hi(x));
            sq[1][i] = fmaf(bf_lo(y), bf_lo(y), bf_hi(y) * bf_hi(y));
          }
          const float e0 = (sq[0][0] + sq[0][1] + (lo ? sq[0][2] : 0.f)) * r0, e1 = (sq[1][0] + sq[1][1] + (lo ? sq[1][2] : 0.f)) * r1;
          const float o0 = (sq[0][3] + sq[0][4] + (lo ? 0.f : sq[0][2])) * r0, o1 = (sq[1][3] + sq[1][4] + (lo ? 0.f : sq[1][2])) * r1;
          const float k0 = (lo ? e0 : o0) + __shfl_xor_sync(~0u, lo ? o0 : e0, 2);
          const float k1 = (lo ? e1 : o1) + __shfl_xor_sync(~0u, lo ? o1 : e1, 2);
          const float z = ((c & 1) ? k1 : k0) + __shfl_xor_sync(~0u, (c & 1) ? k0 : k1, 1);
          const uint32_t em = __reduce_max_sync(~0u, lo ? __float_as_uint(z) : 0u), om = __reduce_max_sync(~0u, lo ? 0u : __float_as_uint(z));
          if ((lane >> 1) == hp) nm = __uint_as_float((lane & 1) ? om : em);
        }
        if (lane < 8) g_nrm[(n * 8 + lane) * 128 + (row0 >> 4)] = nm;
      }
    }
  }
}

constexpr int K2_SMEM = 2 * HEAD_IMG + 2 * 6144 + 2 * 10240 + 160 + 96;

__device__ __forceinline__ uint64_t desc64(uint32_t lo, uint32_t hi) {
  uint64_t d;
  asm("mov.b64 %0, {%1, %2};" : "=l"(d) : "r"(lo), "r"(hi));
  return d;
}
__device__ __forceinline__ uint32_t exp_pair(bool poly, float a, float b, uint32_t mk) {
  if (poly) {
    const uint32_t pk = __byte_perm(__float_as_uint(a), __float_as_uint(b), 0x6521);
    uint32_t m, q;
    asm("lop3.b32 %0, %1, %2, 0x3f803f80, 0xEA;" : "=r"(m) : "r"(pk), "r"(mk));
    asm("fma.rn.bf16x2 %0, %1, %1, %2;" : "=r"(q) : "r"(m), "r"(0x40014001u));
    return pk - m + q;
  }
  return pack_bf16(ex2(a), ex2(b));
}
constexpr int PV_GR = 4;
__device__ __forceinline__ void exp_pv(const float (&s)[64], float (&o)[12], uint64_t dv, uint32_t mk) {
#pragma unroll
  for (int k0 = 0; k0 < 8; k0 += PV_GR) {
    uint32_t p[4 * PV_GR];
#pragma unroll
    for (int i = 0; i < 4 * PV_GR; i++)
      p[i] = exp_pair((POLY_MASK >> (k0 * 2 + i / 2)) & 1, s[k0 * 8 + 2 * i], s[k0 * 8 + 2 * i + 1], mk);
    WG_FENCE();
#pragma unroll
    for (int k = 0; k < PV_GR; k++)
      wgmma_rs_n24(o, p[4 * k], p[4 * k + 1], p[4 * k + 2], p[4 * k + 3], dv + (k0 + k) * 48, 1);
  }
}
__device__ __forceinline__ void load_q(uint32_t (&q)[6], const uint8_t* p) {
  q[0] = __ldcg((const uint32_t*)p);         q[1] = __ldcg((const uint32_t*)(p + 384));
  q[2] = __ldcg((const uint32_t*)(p + 128)); q[3] = __ldcg((const uint32_t*)(p + 512));
  q[4] = __ldcg((const uint32_t*)(p + 256)); q[5] = __ldcg((const uint32_t*)(p + 640));
}
__device__ __forceinline__ float rcp(float x) {
  float y;
  asm("rcp.approx.ftz.f32 %0, %1;" : "=f"(y) : "f"(x));
  return y;
}
__device__ __forceinline__ int img_off(int chunk) { return chunk * 2048; }
__device__ __forceinline__ void store_o(const float (&o)[12], int tile) {
  int tid, bid;
  asm volatile("mov.u32 %0, %%tid.x;" : "=r"(tid));
  asm volatile("mov.u32 %0, %%ctaid.x;" : "=r"(bid));
  const int head = bid >> 2;
  uint8_t* dst = (uint8_t*)g_o + ((bid & 3) * 4 + (tile >> 1)) * 163840 + (tile & 1) * 1024 + ((tid >> 5) & 3) * 256 + (tid & 31) * 4;
  const int oc = (head >> 1) * 5 + (head & 1) * 2;
  const int o0 = img_off(oc), o1 = img_off(oc + 1), o2 = img_off((head >> 1) * 5 + 4) + (head & 1) * 8;
  const float i0 = rcp(__shfl_sync(~0u, o[8], 2, 4)), i1 = rcp(__shfl_sync(~0u, o[10], 2, 4));
  *(uint32_t*)(dst + o0) = pack_bf16(o[0] * i0, o[1] * i0); *(uint32_t*)(dst + o0 + 128) = pack_bf16(o[2] * i1, o[3] * i1);
  *(uint32_t*)(dst + o1) = pack_bf16(o[4] * i0, o[5] * i0); *(uint32_t*)(dst + o1 + 128) = pack_bf16(o[6] * i1, o[7] * i1);
  if ((tid & 3) < 2) {
    *(uint32_t*)(dst + o2) = pack_bf16(o[8] * i0, o[9] * i0);
    *(uint32_t*)(dst + o2 + 128) = pack_bf16(o[10] * i1, o[11] * i1);
  }
}

struct Maps5 { CUtensorMap m[5]; };

__global__ void __launch_bounds__(512, 1)
k2_attn(const __grid_constant__ Maps5 maps, const bf16* __restrict__ wo, uint32_t mk) {
  const CUtensorMap* tmw = maps.m;
  extern __shared__ __align__(1024) uint8_t sm[];
  const uint32_t sbase = smem_u32(sm);
  float* part = (float*)(sm + 2 * HEAD_IMG);
  const uint32_t rbuf = sbase + 2 * HEAD_IMG + 2 * 6144;
  const uint32_t kvb = rbuf + 2 * 10240;
  const uint32_t partb = kvb + 128, rbar = kvb + 144;
  const int tid = threadIdx.x, lane = tid & 31;
  const int warp = __shfl_sync(~0u, tid >> 5, 0);
  const int head = blockIdx.x >> 2, qb = blockIdx.x & 3;

  if (tid == 0) {
    for (int i = 0; i < 16; i++) mbar_init(kvb + 8 * i, 1);
    mbar_init(partb, 128); mbar_init(partb + 8, 128); mbar_init(rbar, 1); mbar_init(rbar + 8, 1);
    asm volatile("fence.mbarrier_init.release.cluster;" ::: "memory");
  }
  __syncthreads();

  if (warp >= 12) {
    asm volatile("setmaxnreg.dec.sync.aligned.u32 32;");
    if (warp == 12) {
      const uint8_t* kimg = (const uint8_t*)g_qkv + (size_t)(32 + head) * HEAD_IMG;
      if (elect_one()) {
#pragma unroll
        for (int b = 0; b < 16; b++) mbar_expect(kvb + 8 * b, 12288);
      }
      pdl_wait();
#pragma unroll 1
      for (int b = 0; b < 16; b++) {
        if (elect_one()) {
          bulk_ld(sbase + b * 6144, kimg + b * 6144, 6144, kvb + 8 * b);
          bulk_ld(sbase + HEAD_IMG + b * 6144, kimg + 32 * HEAD_IMG + b * 6144, 6144, kvb + 8 * b);
        }
        if (b >= 2) mbar_wait(kvb + 8 * (b - 1), 0);
      }
      pdl_trigger();
    }
    if (warp > 12) {
      const int t96 = tid - 416, ck = min(t96, 79), nt = ck / 10;
      float* red = (float*)(sm + K2_SMEM - 96);
#pragma unroll 1
      for (int i = 0; i < 5; i++) {
        const int k = blockIdx.x * 5 + i, pr = k / 40, r = k - pr * 40;
        const uint4 v = ldg_nc(wo + (pr * 40 + (r < 16 ? r : (r < 32 ? r + 4 : (r < 36 ? r - 16 : r)))) * D_ + ck * 8);
        g_wo[((nt * 10 + (k >> 6)) * 10 + ck - nt * 10) * 64 + (k & 63)] = v;
        float t = ((bf_lo(v.x) + bf_hi(v.x)) + (bf_lo(v.y) + bf_hi(v.y))) + ((bf_lo(v.z) + bf_hi(v.z)) + (bf_lo(v.w) + bf_hi(v.w)));
        if (t96 >= 80) t = 0.f;
#pragma unroll
        for (int o = 16; o; o >>= 1) t += __shfl_xor_sync(~0u, t, o);
        if (lane == 0) red[(t96 >> 5) * 8 + i] = t;
      }
      bar_sync(1, 96);
      if (t96 < 5) {
        const float mu = (red[t96] + red[8 + t96] + red[16 + t96]) * (1.f / D_);
        const float hi = bf_lo(pack_bf16(mu, 0.f));
        g_wm[blockIdx.x * 5 + t96] = make_uint4(pack_bf16(hi, mu - hi), 0u, 0u, 0u);
      }
    }
    if (tid == 384) {
      if (blockIdx.x == 0) g_epoch = g_epoch + 1;
      mbar_wait(kvb + 8 * 15, 0);
      uint8_t* pdst = nullptr;
      uint32_t pbytes = 0;
#pragma unroll 1
      for (int i = 0; i < 8; i++) {
        const int p = blockIdx.x + 128 * i;
        uint8_t* dst = nullptr;
        uint32_t bytes = 0;
        if (i < 7 && p < 856) {
          asm volatile("cp.async.bulk.wait_group.read 0;" ::: "memory");
          const CUtensorMap* tm;
          int c1, c2;
          if (p < 640) {
            const int nt = p / 80, r = p - nt * 80, ph = r / 40, st = (r - ph * 40) >> 1, up = r & 1;
            bytes = ph ? 6656 : 7168;
            dst = (uint8_t*)g_wgu + nt * 552960 + ph * 286720 + st * 2 * bytes + up * (bytes >> 1);
            tm = &tmw[ph * 2 + up]; c1 = ph ? 112 + nt * 13 : nt * 14; c2 = st * 2;
          } else {
            const int nk = p - 640, nt = nk / 27;
            bytes = 10240;
            dst = (uint8_t*)g_wd + (size_t)nk * 10240;
            tm = &tmw[4]; c1 = nt * 10; c2 = nk - nt * 27;
          }
          mbar_expect(rbar + 8 * (i & 1), bytes);
          tma4d(rbuf + (i & 1) * 10240, tm, c1, c2, rbar + 8 * (i & 1));
        }
        if (pbytes) {
          mbar_wait(rbar + 8 * ((i - 1) & 1), ((i - 1) >> 1) & 1);
          if (pbytes == 10240) {
            bulk_st(pdst, rbuf + ((i - 1) & 1) * 10240, pbytes);
          } else {
            bulk_st(pdst, rbuf + ((i - 1) & 1) * 10240, pbytes >> 1);
            bulk_st(pdst + pbytes, rbuf + ((i - 1) & 1) * 10240 + (pbytes >> 1), pbytes >> 1);
          }
          asm volatile("cp.async.bulk.commit_group;" ::: "memory");
        }
        pdst = dst; pbytes = bytes;
      }
      asm volatile("cp.async.bulk.wait_group.read 0;" ::: "memory");
    }
  } else {
    asm volatile("setmaxnreg.inc.sync.aligned.u32 160;");
    const int wg = warp >> 2;
    const uint8_t* qthr = (const uint8_t*)g_qkv + (size_t)head * HEAD_IMG + qb * 64 * 384 + (warp & 3) * 768 + lane * 4;
    const uint32_t klo0 = ((sbase & 0x3FFFF) >> 4) | (128u << 16), vlo0 = (((sbase + HEAD_IMG) & 0x3FFFF) >> 4) | (24u << 16);
    constexpr uint64_t KSTEP2 = (uint64_t)(int64_t)(256 - (128 << 16));
    constexpr uint64_t KV2K = 384 - (HEAD_IMG >> 4) + (104 << 16);
    const int nun = wg == 1 ? 4 : 3;
    uint32_t utile = wg == 0 ? 0x210u : (wg == 1 ? 0x4235u : 0x576u);
    uint32_t ubeg = wg == 0 ? 0u : (wg == 1 ? 0x0b00u : 0x600u);
    uint32_t ulen = wg == 0 ? 0x0b1010u : (wg == 1 ? 0x10051006u : 0x0a1010u);
    pdl_wait();
    uint32_t q[6];
    load_q(q, qthr + (utile & 15) * 3072);
    bool fast;
    {
      const uint4 kn = __ldcg((const uint4*)&g_nrm[(32 + head) * 128 + lane * 4]);
      const uint4 vn = __ldcg((const uint4*)&g_nrm[(64 + head) * 128 + lane * 4]);
      const float qv = __ldcg(&g_nrm[head * 128 + qb * 32 + lane]);
      const float k2 = __uint_as_float(__reduce_max_sync(~0u, max(max(kn.x, kn.y), max(kn.z, kn.w))));
      const float v2 = __uint_as_float(__reduce_max_sync(~0u, max(max(vn.x, vn.y), max(vn.z, vn.w))));
      const float q2 = __uint_as_float(__reduce_max_sync(~0u, __float_as_uint(qv)));
      fast = q2 * k2 <= 3400.f && v2 < 1e24f && v2 > 1e-24f;
    }
    if (fast) {
#pragma unroll 1
      for (int u = 0; u < nun; u++) {
        const uint32_t b0 = ubeg & 15;
        const bool wt = u == 0 || (wg == 1 && u == 1);
        float s[64], o[12];
#pragma unroll
        for (int i = 0; i < 12; i++) o[i] = 0.f;
        uint32_t vlo = vlo0 + b0 * 384, kb = kvb + b0 * 8;
        const uint32_t vend = vlo + ((ulen & 255) - 1) * 384;
        if (wt) mbar_wait(kb, 0);
        fence_regs(o);
        WG_FENCE();
        wgmma_rs_n128(s, q[0], q[1], q[2], q[3], desc64(klo0 + b0 * 384, 8), 0);
        wgmma_rs_n128(s, q[4], q[5], 0, 0, desc64(klo0 + b0 * 384, 8) + KSTEP2, 1);
        WG_COMMIT();
#pragma unroll 1
        for (; vlo != vend; vlo += 384) {
          if (wt) { kb += 8; mbar_wait(kb, 0); }
          WG_WAIT(0);
          fence_regs(s); fence_regs(o);
          const uint64_t dv = desc64(vlo, 8);
          exp_pv(s, o, dv, mk);
          wgmma_rs_n128(s, q[0], q[1], q[2], q[3], dv + KV2K, 0);
          wgmma_rs_n128(s, q[4], q[5], 0, 0, dv + (KV2K + KSTEP2), 1);
          WG_COMMIT();
        }
        WG_WAIT(0);
        fence_regs(s); fence_regs(o);
        if (u + 1 < nun) load_q(q, qthr + ((utile >> 4) & 15) * 3072);
        exp_pv(s, o, desc64(vlo, 8), mk);
        WG_COMMIT();
        WG_WAIT(0);
        fence_regs(o);
        if (wg == 1 && !(u & 1)) {
          float4* pp = (float4*)(part + u * 768) + (tid & 127);
          pp[0] = make_float4(o[0], o[1], o[2], o[3]);
          pp[128] = make_float4(o[4], o[5], o[6], o[7]);
          pp[256] = make_float4(o[8], o[9], o[10], o[11]);
          mbar_arrive(partb + 4 * u);
        } else {
          if (wg != 1 && u == 2) {
            const int pi = wg == 0 ? 1 : 0;
            mbar_wait(partb + 8 * pi, 0);
            const float4* pp = (const float4*)(part + pi * 1536) + (tid & 127);
            const float4 x0 = pp[0], x1 = pp[128], x2 = pp[256];
            o[0] += x0.x; o[1] += x0.y; o[2] += x0.z; o[3] += x0.w; o[4] += x1.x; o[5] += x1.y;
            o[6] += x1.z; o[7] += x1.w; o[8] += x2.x; o[9] += x2.y; o[10] += x2.z; o[11] += x2.w;
          }
          store_o(o, utile & 15);
        }
        utile >>= 4; ubeg >>= 4; ulen >>= 8;
      }
    } else {
#pragma unroll 1
      for (int tile = wg; tile < 8; tile += 3) {
        load_q(q, qthr + tile * 3072);
        if ((lane & 3) >= 2) { q[4] = 0; q[5] = 0; }
        float o[12], m0 = -INFINITY, m1 = -INFINITY;
#pragma unroll
        for (int i = 0; i < 12; i++) o[i] = 0.f;
#pragma unroll 1
        for (int b = 0; b < 16; b++) {
          float s[64];
          mbar_wait(kvb + 8 * b, 0);
          WG_FENCE();
          wgmma_rs_n128(s, q[0], q[1], q[2], q[3], desc64(klo0 + b * 384, 8), 0);
          wgmma_rs_n128(s, q[4], q[5], 0, 0, desc64(klo0 + b * 384, 8) + KSTEP2, 1);
          WG_COMMIT();
          WG_WAIT(0);
          fence_regs(s);
          float x0 = m0, x1 = m1;
#pragma unroll
          for (int j = 0; j < 16; j++) {
            if ((POLY_MASK >> j) & 1) {
#pragma unroll
              for (int i = 0; i < 4; i++) s[4 * j + i] *= (1.f / 32768.f);
            }
            x0 = fmaxf(x0, fmaxf(s[4 * j], s[4 * j + 1]));
            x1 = fmaxf(x1, fmaxf(s[4 * j + 2], s[4 * j + 3]));
          }
          x0 = fmaxf(x0, __shfl_xor_sync(~0u, x0, 1)); x0 = fmaxf(x0, __shfl_xor_sync(~0u, x0, 2));
          x1 = fmaxf(x1, __shfl_xor_sync(~0u, x1, 1)); x1 = fmaxf(x1, __shfl_xor_sync(~0u, x1, 2));
          const float al0 = ex2(m0 - x0), al1 = ex2(m1 - x1);
          m0 = x0; m1 = x1;
#pragma unroll
          for (int i = 0; i < 12; i++) o[i] *= (i & 2) ? al1 : al0;
          uint32_t p[32];
#pragma unroll
          for (int i = 0; i < 32; i++) {
            const float mm = (i & 1) ? m1 : m0;
            p[i] = pack_bf16(ex2(s[2 * i] - mm), ex2(s[2 * i + 1] - mm));
          }
          fence_regs(o);
          WG_FENCE();
#pragma unroll
          for (int k = 0; k < 8; k++)
            wgmma_rs_n24(o, p[4 * k], p[4 * k + 1], p[4 * k + 2], p[4 * k + 3], desc64(vlo0 + b * 384 + k * 48, 8), 1);
          WG_COMMIT();
          WG_WAIT(0);
          fence_regs(o);
        }
        store_o(o, tile);
      }
    }
  }
}

constexpr int K3_ST = 4, K3_STAGE = 37888, K3_NB = 4, K3_NT = 6;
constexpr int K3_SMEM = K3_ST * K3_STAGE + 24576 + 20480 + 256;

template <int N> struct Acc { float v[N]; };

__global__ void __cluster_dims__(2, 1, 1) __launch_bounds__(288, 1)
k3_proj(const __grid_constant__ CUtensorMap tmx) {
  extern __shared__ __align__(1024) uint8_t sm[];
  const uint32_t sbase = smem_u32(sm);
  const uint8_t* xch = sm + K3_ST * K3_STAGE;
  const uint8_t* res = sm + K3_ST * K3_STAGE + 24576;
  const uint32_t fullb = smem_u32(res) + 20480, emptyb = fullb + 8 * K3_ST, resb = emptyb + 8 * K3_ST, xchb = resb + 8;
  const int tid = threadIdx.x, lane = tid & 31;
  const int warp = __shfl_sync(~0u, tid >> 5, 0);
  const int rank = blockIdx.x & 1;
  const int n = blockIdx.x & 7, m = blockIdx.x >> 3;
  if (warp == 8) {
    if (elect_one()) {
#pragma unroll
      for (int i = 0; i < K3_ST; i++) { mbar_init(fullb + 8 * i, 1); mbar_init(emptyb + 8 * i, 2); }
      mbar_init(resb, 1); mbar_init(xchb, 1);
      mbar_expect(xchb, 24576);
      asm volatile("fence.mbarrier_init.release.cluster;" ::: "memory");
    }
    __syncwarp();
  }
  cluster_arrive();
  if (warp == 8) {
    const uint8_t* wk = (const uint8_t*)g_wo + n * 102400;
    const uint8_t* ws = (const uint8_t*)g_wo + (n ^ 1) * 102400;
    const uint8_t* ab = (const uint8_t*)g_o + m * 163840;
    prefetch_map(&tmx);
    pdl_wait();
#pragma unroll 1
    for (int i = 0; i < K3_NT; i++) {
      const int s = i % K3_ST, kt = i < K3_NB ? i + rank * K3_NT : i;
      const uint32_t sa = sbase + s * K3_STAGE, fb = fullb + 8 * s;
      if (i >= K3_ST) mbar_wait(emptyb + 8 * s, 0);
      if (elect_one()) {
        mbar_expect(fb, i < K3_NB ? 37888 : 27648);
        bulk_ld(sa, ab + kt * 16384, 16384, fb);
        bulk_ld(sa + 16384, wk + kt * 10240, 10240, fb);
        bulk_ld(sa + 26624, (const uint8_t*)g_wm + kt * 1024, 1024, fb);
        if (i < K3_NB) bulk_ld(sa + 27648, ws + kt * 10240, 10240, fb);
        if (i == K3_ST - 1) {
          mbar_expect(resb, 20480);
          tma2d(smem_u32(res), &tmx, n * 80, m * 128, resb);
          tma2d(smem_u32(res) + 10240, &tmx, n * 80, m * 128 + 64, resb);
        }
      }
      if (i == 0) pdl_trigger();
    }
    cluster_wait();
  } else {
    const int g = lane >> 2, c = lane & 3;
    const int row = m * 128 + warp * 16 + g;
    float mu0 = __uint_as_float(__ldcg(&g_rowstat[row].z)), mu1 = __uint_as_float(__ldcg(&g_rowstat[row + 8].z));
    float acc[84];
    float (&keep)[44] = ((Acc<44>*)acc)->v;
    const uint64_t da0 = mkdesc(sbase + (warp >> 2) * 1024, 2048, 128, 0);
    const uint64_t db0 = mkdesc(sbase + 16384, 128, 1024, 0);
    cluster_wait();
#pragma unroll 1
    for (int i = 0; i < K3_NB; i++) {
      mbar_wait(fullb + 8 * i, 0);
      const uint64_t da = da0 + i * (K3_STAGE >> 4), db = db0 + i * (K3_STAGE >> 4);
      WG_FENCE();
#pragma unroll
      for (int k = 0; k < 4; k++) wgmma_ss_n168(acc, da + k * 256, db + k * 16, (i | k) != 0);
      WG_COMMIT();
      if (i > 0) {
        WG_WAIT(1);
        if (i - 1 + K3_ST < K3_NT && (tid & 127) == 0) mbar_arrive(emptyb + 8 * (i - 1));
      }
    }
    const uint32_t rx = mapa(smem_u32(xch) + tid * 16, rank ^ 1), rb = mapa(xchb, rank ^ 1);
    WG_WAIT(0);
    fence_regs(acc);
    st_async4(rx, acc[40], acc[41], acc[42], acc[43], rb);
#pragma unroll
    for (int i = K3_NB; i < K3_NT; i++) {
      const int s = i % K3_ST;
      mbar_wait(fullb + 8 * s, 1);
      const uint64_t da = da0 + s * (K3_STAGE >> 4), db = db0 + s * (K3_STAGE >> 4);
      WG_FENCE();
#pragma unroll
      for (int k = 0; k < 4; k++) wgmma_ss_n88(keep, da + k * 256, db + k * 16, 1);
      WG_COMMIT();
#pragma unroll
      for (int j = (i - K3_NB) * 3; j < (i - K3_NB) * 3 + 3; j++)
        if (j < 5) SEND8(rx + (j + 1) * 4096, acc, 44 + 8 * j, rb);
    }
    const uint8_t* sp = res + (warp * 16 + g) * 160 + c * 4;
    uint32_t rv[20];
    mbar_wait(resb, 0);
#pragma unroll
    for (int j = 0; j < 10; j++) {
      rv[2 * j] = *(const uint32_t*)(sp + j * 16);
      rv[2 * j + 1] = *(const uint32_t*)(sp + 1280 + j * 16);
    }
    WG_WAIT(0);
    fence_regs(keep);
    mbar_wait(xchb, 0);
    const uint8_t* xp = xch + tid * 16;
    {
      const float4 p = *(const float4*)xp;
      mu0 += __shfl_sync(~0u, (keep[40] + p.x) + (keep[41] + p.y), 0, 4);
      mu1 += __shfl_sync(~0u, (keep[42] + p.z) + (keep[43] + p.w), 0, 4);
    }
    uint8_t* himg = (uint8_t*)g_h + m * 163840 + img_off(n * 10) + warp * 256 + lane * 4;
    float q0 = 0.f, q1 = 0.f;
#pragma unroll
    for (int j = 0; j < 10; j++) {
      const uint2 p = *(const uint2*)(xp + ((j >> 1) + 1) * 4096 + (j & 1) * 8);
      const float x0 = (keep[4 * j] + bf_lo(p.x)) + (bf_lo(rv[2 * j]) - mu0), x1 = (keep[4 * j + 1] + bf_hi(p.x)) + (bf_hi(rv[2 * j]) - mu0);
      const float y0 = (keep[4 * j + 2] + bf_lo(p.y)) + (bf_lo(rv[2 * j + 1]) - mu1), y1 = (keep[4 * j + 3] + bf_hi(p.y)) + (bf_hi(rv[2 * j + 1]) - mu1);
      *(uint32_t*)(himg + img_off(j)) = pack_bf16(x0, x1);
      *(uint32_t*)(himg + img_off(j) + 128) = pack_bf16(y0, y1);
      q0 = fmaf(x0, x0, fmaf(x1, x1, q0)); q1 = fmaf(y0, y0, fmaf(y1, y1, q1));
    }
    q0 += __shfl_xor_sync(~0u, q0, 1); q0 += __shfl_xor_sync(~0u, q0, 2);
    q1 += __shfl_xor_sync(~0u, q1, 1); q1 += __shfl_xor_sync(~0u, q1, 2);
    if (c < 2) g_hpart[n * S_ + row + c * 8] = c ? q1 : q0;
    if (n == 0 && c < 2) g_hmean[row + c * 8] = c ? mu1 : mu0;
  }
}

constexpr int P3_NB = 12, P3_NT = 15;
constexpr int K4_G = 2, K4_NS = 4, K4_NJ = 20;
constexpr int K4_RB = 163840, K4_BST = 7168 * K4_G, K4_XCH = 147456, K4_STG = K4_XCH + 20480, K4_BAR = K4_RB + K4_NS * K4_BST;
constexpr int K4_SMEM = K4_BAR + 384;

__device__ __forceinline__ void wait_flags(const uint4* f, uint32_t tag, uint32_t need, uint32_t& seen) {
  if ((seen & need) == need) return;
  for (uint32_t it = 0; (seen & need) != need; it++) {
    if (it > (1u << 20)) wait_timeout();
    if (it) __nanosleep(150);
    uint32_t v = 0;
    if ((threadIdx.x & 31) < 8) asm volatile("ld.acquire.gpu.global.u32 %0, [%1];" : "=r"(v) : "l"((const uint32_t*)f + (threadIdx.x & 7)) : "memory");
    seen = __ballot_sync(~0u, v == tag) & 255;
  }
  asm volatile("fence.proxy.async.global;" ::: "memory");
}

template <int MODE>
__global__ void __cluster_dims__(2, 1, 1) __launch_bounds__(384, 1)
k45_ffn(const __grid_constant__ CUtensorMap tmo) {
  extern __shared__ __align__(1024) uint8_t sm[];
  const uint32_t sbase = smem_u32(sm);
  const uint32_t afull = sbase + K4_BAR, bfull = afull + 80, bempty = bfull + 8 * K4_NS, full3 = bempty + 8 * K4_NS;
  const uint32_t empty3 = full3 + 32, afree = empty3 + 32, xchb = afree + 32, rdyb = xchb + 8;
  const int tid = threadIdx.x, lane = tid & 31;
  const int warp = __shfl_sync(~0u, tid >> 5, 0);
  const int rank = blockIdx.x & 1;
  const int n = blockIdx.x & 7, m = blockIdx.x >> 3;
  if (warp == 8) {
    if (elect_one()) {
#pragma unroll
      for (int i = 0; i < 10; i++) mbar_init(afull + 8 * i, 1);
#pragma unroll
      for (int i = 0; i < 4; i++) {
        mbar_init(bfull + 8 * i, 1); mbar_init(bempty + 8 * i, 2); mbar_init(full3 + 8 * i, 1); mbar_init(empty3 + 8 * i, 2);
        mbar_init(afree + 8 * i, 2);
      }
      mbar_init(xchb, 1); mbar_init(rdyb, 2);
      mbar_expect(xchb, 20480);
      asm volatile("fence.mbarrier_init.release.cluster;" ::: "memory");
    }
    __syncwarp();
  }
  cluster_arrive();
  if (warp >= 8) {
    if (warp != 8) cluster_wait();
    if (warp == 8) {
      const uint8_t* src = (const uint8_t*)g_wgu + n * 552960;
      const uint8_t* hb = (const uint8_t*)g_h + (size_t)m * 163840;
      int ka = 1;
#pragma unroll 1
      for (int j = 0; j < (MODE == 2 ? 0 : 40); j++) {
        const uint32_t s8 = (j & 3) * 8, sz = j < 20 ? 14336 : 13312;
        if (j == 1) {
          pdl_wait();
          if (elect_one()) { mbar_expect(afull, 16384); bulk_ld(sbase, hb, 16384, afull); }
        }
        if (j >= 4) mbar_wait(bempty + s8, ((j >> 2) - 1) & 1);
        if (elect_one()) {
          mbar_expect(bfull + s8, sz);
          bulk_ld(sbase + K4_RB + s8 * (K4_BST / 8), src, sz, bfull + s8);
          if (j >= 1 && ka < 10 && (j < 4 || (j & 1))) {
            mbar_expect(afull + 8 * ka, 16384);
            bulk_ld(sbase + ka * 16384, hb + ka * 16384, 16384, afull + 8 * ka);
          }
        }
        if (j >= 1 && (j < 4 || (j & 1))) ka++;
        src += sz;
      }
      cluster_wait();
    } else if (warp == 9) {
      prefetch_map(&tmo);
      const uint32_t tag = __ldcg(&g_epoch);
#pragma unroll 1
      for (int ph = 0; ph < (MODE == 2 ? 0 : 2); ph++) {
        bar_sync(5 + ph, 256 + 32);
        if (lane == 0) {
          asm volatile("st.release.gpu.global.u32 [%0], %1;" ::"l"((uint32_t*)&g_flag[ph * 32 + m * 2] + n), "r"(tag) : "memory");
        }
        __syncwarp();
      }
    } else {
      const uint8_t* wk = (const uint8_t*)g_wd + n * 276480;
      const uint8_t* ws = (const uint8_t*)g_wd + (n ^ 1) * 276480;
      const uint8_t* ab = (const uint8_t*)g_hh + (size_t)m * 442368;
      const uint32_t tag = __ldcg(&g_epoch);
      uint32_t seen = 0;
#pragma unroll 1
      for (int i = 0; i < (MODE == 1 ? 0 : P3_NT); i++) {
        const int kt = i < 7 ? rank * 7 + i : (i < P3_NB ? rank * (P3_NB - 7) + 7 + i : P3_NB + i);
        const uint32_t sa = sbase + (i & 3) * 36864, fb = full3 + 8 * (i & 3);
        if (warp == 11) {
          const int q = kt * 8 - (i < 7 ? 0 : 112), w = i < 7 ? 14 : 13;
          if (MODE == 0 && i == 0) mbar_wait(afull + 72, 0);
          if (i == 7) seen = 0;
          wait_flags(&g_flag[(i < 7 ? 0 : 32) + m * 2], tag, 1u << (q / w) | 1u << ((q + 7) / w), seen);
        }
        if (i < 4) { if (MODE == 0) mbar_wait(afree + 8 * i, 0); }
        else mbar_wait(empty3 + 8 * (i & 3), ((i >> 2) - 1) & 1);
        if (warp == 10) {
          if (elect_one()) {
            mbar_expect(fb, i < P3_NB ? 36864 : 26624);
            bulk_ld(sa + 16384, wk + kt * 10240, 10240, fb);
            if (i < P3_NB) bulk_ld(sa + 26624, ws + kt * 10240, 10240, fb);
          }
        } else {
          if (elect_one()) {
            bulk_ld(sa, ab + kt * 16384, 16384, fb);
          }
        }
      }
    }
  } else {
    const int wg = warp >> 2;
    const uint64_t da0 = mkdesc(sbase + wg * 1024, 2048, 128, 0);
    const uint64_t db0 = mkdesc(sbase + K4_RB, 128, 256, 0);
    cluster_wait();
    float acc[80];
    if constexpr (MODE != 2) {
    float a1[112], a2[104];
    int s = 0, ph = 0, sprev = 0;
#pragma unroll 1
    for (int j = 0; j < K4_NJ; j++) {
      if ((j * K4_G) % 4 == 0) mbar_wait(afull + 2 * K4_G * j, 0);
      mbar_wait(bfull + 8 * s, ph);
      const uint64_t da = da0 + j * K4_G * 256, db = db0 + s * (K4_BST >> 4);
      WG_FENCE();
#pragma unroll
      for (int k = 0; k < K4_G; k++) wgmma_ss_n224(a1, da + k * 256, db + k * 448, (j | k) != 0);
      WG_COMMIT();
      if (j > 0) {
        WG_WAIT(1);
        if ((tid & 127) == 0) mbar_arrive(bempty + 8 * sprev);
      }
      sprev = s;
      if (++s == K4_NS) { s = 0; ph ^= 1; }
    }
    uint8_t* hd = (uint8_t*)g_hh + (size_t)m * 442368 + warp * 256 + lane * 4;
    WG_WAIT(0);
    fence_regs(a1);
    if ((tid & 127) == 0) mbar_arrive(bempty + 8 * ((K4_NJ - 1) % K4_NS));
#define STORE_H(a, off, ptr, c) do { uint8_t* p_ = ptr; \
      *(uint32_t*)p_ = pack_bf16(a[4 * (c)] * a[off + 4 * (c)], a[4 * (c) + 1] * a[off + 1 + 4 * (c)]); \
      *(uint32_t*)(p_ + 128) = pack_bf16(a[4 * (c) + 2] * a[off + 2 + 4 * (c)], a[4 * (c) + 3] * a[off + 3 + 4 * (c)]); } while (0)
#pragma unroll
    for (int c = 0; c < 14; c++) STORE_H(a1, 56, hd + img_off(n * 14 + c), c);
    bar_arrive(5, 256 + 32);
#pragma unroll 1
    for (int j = 0; j < K4_NJ; j++) {
      mbar_wait(bfull + 8 * s, ph);
      const uint64_t da = da0 + j * K4_G * 256, db = db0 + s * (K4_BST >> 4);
      WG_FENCE();
#pragma unroll
      for (int k = 0; k < K4_G; k++) wgmma_ss_n208(a2, da + k * 256, db + k * 416, (j | k) != 0);
      WG_COMMIT();
      if (j > 0) {
        WG_WAIT(1);
        if (j <= K4_NJ - K4_NS && (tid & 127) == 0) mbar_arrive(bempty + 8 * sprev);
        if (j * K4_G >= 12 && ((j * K4_G) & 7) == 4 && (tid & 127) == 0) mbar_arrive(afree + (j * K4_G - 12));
      }
      sprev = s;
      if (++s == K4_NS) { s = 0; ph ^= 1; }
    }
    WG_WAIT(0);
    fence_regs(a2);
#pragma unroll
    for (int c = 0; c < 13; c++) STORE_H(a2, 52, hd + img_off(112 + n * 13 + c), c);
    bar_arrive(6, 256 + 32);
    }
    if constexpr (MODE != 1) {
    if ((tid & 127) == 0) mbar_arrive_cta(rdyb, rank ^ 1);
    float (&keep)[40] = ((Acc<40>*)acc)->v;
    const uint64_t db3 = mkdesc(sbase + 16384, 128, 1024, 0);
#pragma unroll 1
    for (int i = 0; i < P3_NB; i++) {
      mbar_wait(full3 + 8 * (i & 3), (i >> 2) & 1);
      const uint64_t da = da0 + (i & 3) * 2304, db = db3 + (i & 3) * 2304;
      WG_FENCE();
#pragma unroll
      for (int k = 0; k < 4; k++) wgmma_ss_n160(acc, da + k * 256, db + k * 16, (i | k) != 0);
      WG_COMMIT();
      if (i > 0) {
        WG_WAIT(1);
        if (i + 3 < P3_NT && (tid & 127) == 0) mbar_arrive(empty3 + 8 * ((i - 1) & 3));
      }
    }
    const int g = lane >> 2, c = lane & 3, row = m * 128 + warp * 16 + g;
    const uint8_t* himg = (const uint8_t*)g_h + (size_t)m * 163840 + warp * 256 + lane * 4;
    uint32_t rv[20];
    const float mu0 = __ldcg(&g_hmean[row]), mu1 = __ldcg(&g_hmean[row + 8]);
    float r0 = __ldcg(&g_hpart[c * 2 * S_ + row]) + __ldcg(&g_hpart[(c * 2 + 1) * S_ + row]);
    float r1 = __ldcg(&g_hpart[c * 2 * S_ + row + 8]) + __ldcg(&g_hpart[(c * 2 + 1) * S_ + row + 8]);
#pragma unroll
    for (int j = 0; j < 10; j++) {
      rv[2 * j] = __ldcg((const uint32_t*)(himg + img_off(n * 10 + j)));
      rv[2 * j + 1] = __ldcg((const uint32_t*)(himg + img_off(n * 10 + j) + 128));
    }
    const uint32_t rx = mapa(sbase + K4_XCH + tid * 16, rank ^ 1), rb = mapa(xchb, rank ^ 1);
    WG_WAIT(0);
    fence_regs(acc);
    mbar_wait(rdyb, 0);
#pragma unroll
    for (int i = P3_NB; i < P3_NT; i++) {
      mbar_wait(full3 + 8 * (i & 3), (i >> 2) & 1);
      const uint64_t da = da0 + (i & 3) * 2304, db = db3 + (i & 3) * 2304;
      WG_FENCE();
#pragma unroll
      for (int k = 0; k < 4; k++) wgmma_ss_n80(keep, da + k * 256, db + k * 16, 1);
      WG_COMMIT();
#pragma unroll
      for (int j = (i - P3_NB) * 3; j < (i - P3_NB) * 3 + 3; j++)
        if (j < 5) SEND8(rx + j * 4096, acc, 40 + 8 * j, rb);
    }
    r0 += __shfl_xor_sync(~0u, r0, 1); r1 += __shfl_xor_sync(~0u, r1, 1);
    r0 += __shfl_xor_sync(~0u, r0, 2); r1 += __shfl_xor_sync(~0u, r1, 2);
    r0 = rcp(r0 * (1.f / D_) + 1e-5f); r1 = rcp(r1 * (1.f / D_) + 1e-5f);
    asm volatile("" : "+f"(r0), "+f"(r1)::"memory");
    WG_WAIT(0);
    fence_regs(keep);
    mbar_wait(xchb, 0);
    uint8_t* sp = sm + K4_STG + (warp * 16 + g) * 160 + c * 4;
#pragma unroll
    for (int j = 0; j < 10; j++) {
      const uint2 p = *(const uint2*)(sm + K4_XCH + tid * 16 + (j >> 1) * 4096 + (j & 1) * 8);
      *(uint32_t*)(sp + j * 16) = pack_bf16(fmaf(keep[4 * j] + bf_lo(p.x), r0, bf_lo(rv[2 * j]) + mu0), fmaf(keep[4 * j + 1] + bf_hi(p.x), r0, bf_hi(rv[2 * j]) + mu0));
      *(uint32_t*)(sp + 1280 + j * 16) = pack_bf16(fmaf(keep[4 * j + 2] + bf_lo(p.y), r1, bf_lo(rv[2 * j + 1]) + mu1), fmaf(keep[4 * j + 3] + bf_hi(p.y), r1, bf_hi(rv[2 * j + 1]) + mu1));
    }
    fence_async();
    bar_sync(1 + wg, 128);
    if ((tid & 127) == 0) {
      tma2d_st(&tmo, n * 80, m * 128 + wg * 64, sbase + K4_STG + wg * 10240);
      bulk_commit_wait();
    }
    __syncwarp();
    }
  }
}

typedef CUresult (*EncodeFn)(CUtensorMap*, CUtensorMapDataType, cuuint32_t, void*, const cuuint64_t*, const cuuint64_t*,
                             const cuuint32_t*, const cuuint32_t*, CUtensorMapInterleave, CUtensorMapSwizzle,
                             CUtensorMapL2promotion, CUtensorMapFloatOOBfill);

static CUtensorMap make_map(EncodeFn enc, const void* p, uint64_t inner, uint64_t outer, uint32_t box_inner,
                            uint32_t box_outer, CUtensorMapSwizzle swz) {
  CUtensorMap m;
  cuuint64_t gd[2] = {inner, outer};
  cuuint64_t gs[1] = {inner * 2};
  cuuint32_t bd[2] = {box_inner, box_outer};
  cuuint32_t es[2] = {1, 1};
  enc(&m, CU_TENSOR_MAP_DATA_TYPE_BFLOAT16, 2, (void*)p, gd, gs, bd, es, CU_TENSOR_MAP_INTERLEAVE_NONE, swz,
      CU_TENSOR_MAP_L2_PROMOTION_L2_256B, CU_TENSOR_MAP_FLOAT_OOB_FILL_NONE);
  return m;
}

static CUtensorMap make_map_img(EncodeFn enc, const void* p, uint64_t k, uint64_t n, uint32_t rows, uint32_t chunks,
                                uint32_t groups) {
  CUtensorMap m;
  cuuint64_t gd[4] = {8, rows, n / 8, k / rows};
  cuuint64_t gs[3] = {n * 2, 16, n * 2 * rows};
  cuuint32_t bd[4] = {8, rows, chunks, groups};
  cuuint32_t es[4] = {1, 1, 1, 1};
  enc(&m, CU_TENSOR_MAP_DATA_TYPE_BFLOAT16, 4, (void*)p, gd, gs, bd, es, CU_TENSOR_MAP_INTERLEAVE_NONE,
      CU_TENSOR_MAP_SWIZZLE_NONE, CU_TENSOR_MAP_L2_PROMOTION_L2_128B, CU_TENSOR_MAP_FLOAT_OOB_FILL_NONE);
  return m;
}

template <typename... KArgs, typename... Args>
static void launch(void (*k)(KArgs...), int grid, int threads, int smem, bool pdl, Args... args) {
  cudaLaunchConfig_t cfg = {};
  cfg.gridDim = dim3(grid);
  cfg.blockDim = dim3(threads);
  cfg.dynamicSmemBytes = smem;
  cfg.stream = cudaStreamPerThread;
  cudaLaunchAttribute at[1];
  at[0].id = cudaLaunchAttributeProgrammaticStreamSerialization;
  at[0].val.programmaticStreamSerializationAllowed = 1;
  cfg.attrs = at;
  cfg.numAttrs = pdl ? 1 : 0;
  cudaLaunchKernelEx(&cfg, k, KArgs(args)...);
}

extern "C" void kernel_launch(void* const* d_in, const int* in_sizes, int n_in, void* d_out, int out_size) {
  const bf16* x = (const bf16*)d_in[0];
  const bf16* wqkv = (const bf16*)d_in[1];
  const bf16* wo = (const bf16*)d_in[2];
  const bf16* wg = (const bf16*)d_in[4];
  const bf16* wu = (const bf16*)d_in[5];
  const bf16* wd = (const bf16*)d_in[6];

  static EncodeFn enc = nullptr;
  static bool fused = true;
  if (!enc) {
    void* fn = nullptr;
    cudaDriverEntryPointQueryResult qr;
    cudaGetDriverEntryPoint("cuTensorMapEncodeTiled", &fn, cudaEnableDefault, &qr);
    enc = (EncodeFn)fn;
    cudaFuncSetAttribute(k1_qkv, cudaFuncAttributeMaxDynamicSharedMemorySize, K1_SMEM);
    cudaFuncSetAttribute(k2_attn, cudaFuncAttributeMaxDynamicSharedMemorySize, K2_SMEM);
    cudaFuncSetAttribute(k3_proj, cudaFuncAttributeMaxDynamicSharedMemorySize, K3_SMEM);
    cudaFuncSetAttribute(k45_ffn<0>, cudaFuncAttributeMaxDynamicSharedMemorySize, K4_SMEM);
    cudaFuncSetAttribute(k45_ffn<1>, cudaFuncAttributeMaxDynamicSharedMemorySize, K4_SMEM);
    cudaFuncSetAttribute(k45_ffn<2>, cudaFuncAttributeMaxDynamicSharedMemorySize, K4_SMEM);
    cudaLaunchConfig_t cfg = {};
    cfg.gridDim = dim3(128); cfg.blockDim = dim3(384); cfg.dynamicSmemBytes = K4_SMEM;
    int clusters = 0;
    cudaOccupancyMaxActiveClusters(&clusters, k45_ffn<0>, &cfg);
    fused = clusters >= 64;
  }
  const CUtensorMap tmx = make_map(enc, x, D_, S_, 64, 192, CU_TENSOR_MAP_SWIZZLE_128B);
  const CUtensorMap tmw = make_map(enc, wqkv, 3 * D_, D_, 32, 64, CU_TENSOR_MAP_SWIZZLE_64B);
  const CUtensorMap tmxr = make_map(enc, x, D_, S_, 80, 64, CU_TENSOR_MAP_SWIZZLE_NONE);
  Maps5 maps;
  maps.m[0] = make_map_img(enc, wg, D_, F_, 16, 14, 2); maps.m[1] = make_map_img(enc, wu, D_, F_, 16, 14, 2);
  maps.m[2] = make_map_img(enc, wg, D_, F_, 16, 13, 2); maps.m[3] = make_map_img(enc, wu, D_, F_, 16, 13, 2);
  maps.m[4] = make_map_img(enc, wd, F_, D_, 64, 10, 1);
  const CUtensorMap tmout = make_map(enc, d_out, D_, S_, 80, 64, CU_TENSOR_MAP_SWIZZLE_NONE);

  launch(k1_qkv, 132, 512, K1_SMEM, false, tmx, tmw, x, wqkv);
  launch(k2_attn, 128, 512, K2_SMEM, true, maps, wo, 0x007f007fu);
  launch(k3_proj, 128, 288, K3_SMEM, true, tmxr);
  if (fused) {
    launch(k45_ffn<0>, 128, 384, K4_SMEM, true, tmout);
  } else {
    launch(k45_ffn<1>, 128, 384, K4_SMEM, true, tmout);
    launch(k45_ffn<2>, 128, 384, K4_SMEM, false, tmout);
  }
}
```

```cpp
#include <cuda_runtime.h>
#include <cuda_bf16.h>
#include <cuda.h>
#include <stdint.h>

typedef __nv_bfloat16 bf16;

constexpr int S_ = 2048, D_ = 640, F_ = 1728;
constexpr int HEAD_IMG = 98304;
constexpr uint32_t POLY_MASK = 0xFAAB;
constexpr float QSCALE = 0.22360679774997896f * 1.4426950408889634f;

__device__ __align__(1024) uint4 g_qkv[96 * HEAD_IMG / 16];
__device__ __align__(1024) uint4 g_o[S_ * D_ / 8];
__device__ __align__(1024) uint4 g_h[S_ * D_ / 8];
__device__ __align__(1024) uint4 g_hh[S_ * F_ / 8];
__device__ __align__(1024) uint4 g_wo[D_ * D_ / 8];
__device__ __align__(1024) uint4 g_wgu[2 * D_ * F_ / 8];
__device__ __align__(1024) uint4 g_wd[F_ * D_ / 8];
__device__ uint4 g_rowstat[S_];
__device__ uint4 g_cpart[10 * 12 * 80];
__device__ float g_nrm[96 * 128];
__device__ uint4 g_wm[D_];
__device__ float g_hmean[S_];
__device__ float g_hpart[8 * S_];
__device__ uint4 g_flag[2 * 16 * 2];
__device__ unsigned g_epoch;

__device__ __forceinline__ uint32_t smem_u32(const void* p) { return (uint32_t)__cvta_generic_to_shared(p); }
__device__ __forceinline__ void mbar_init(uint32_t a, uint32_t c) {
  asm volatile("mbarrier.init.shared::cta.b64 [%0], %1;" ::"r"(a), "r"(c) : "memory");
}
__device__ __forceinline__ void mbar_expect(uint32_t a, uint32_t bytes) {
  asm volatile("mbarrier.arrive.expect_tx.shared::cta.b64 _, [%0], %1;" ::"r"(a), "r"(bytes) : "memory");
}
__device__ __forceinline__ void mbar_arrive(uint32_t a) {
  asm volatile("mbarrier.arrive.shared::cta.b64 _, [%0];" ::"r"(a) : "memory");
}
__device__ __forceinline__ void mbar_arrive_cta(uint32_t a, uint32_t cta) {
  asm volatile("{\n.reg .b32 r;\nmapa.shared::cluster.u32 r, %0, %1;\n"
               "mbarrier.arrive.shared::cluster.b64 _, [r];\n}" ::"r"(a), "r"(cta) : "memory");
}
__device__ __forceinline__ bool mbar_try(uint32_t a, uint32_t ph) {
  uint32_t ok;
  asm volatile("{\n.reg .pred p;\nmbarrier.try_wait.parity.shared::cta.b64 p, [%1], %2;\nselp.u32 %0, 1, 0, p;\n}"
               : "=r"(ok) : "r"(a), "r"(ph) : "memory");
  return ok;
}
__device__ __noinline__ void wait_timeout() { __trap(); }
__device__ __forceinline__ void mbar_wait(uint32_t a, uint32_t ph) {
  if (mbar_try(a, ph)) return;
  uint32_t it = 0;
  while (!mbar_try(a, ph)) if (++it > (1u << 22)) wait_timeout();
}
__device__ __forceinline__ void tma2d(uint32_t dst, const CUtensorMap* m, int c0, int c1, uint32_t bar) {
  asm volatile("cp.async.bulk.tensor.2d.shared::cluster.global.mbarrier::complete_tx::bytes [%0], [%1, {%3, %4}], [%2];"
               ::"r"(dst), "l"(m), "r"(bar), "r"(c0), "r"(c1) : "memory");
}
__device__ __forceinline__ void bulk_ld(uint32_t dst, const void* src, uint32_t bytes, uint32_t bar) {
  asm volatile("cp.async.bulk.shared::cluster.global.mbarrier::complete_tx::bytes [%0], [%1], %2, [%3];"
               ::"r"(dst), "l"(src), "r"(bytes), "r"(bar) : "memory");
}
__device__ __forceinline__ void cluster_arrive() { asm volatile("barrier.cluster.arrive.relaxed.aligned;" ::: "memory"); }
__device__ __forceinline__ void cluster_wait() { asm volatile("barrier.cluster.wait.aligned;" ::: "memory"); }
__device__ __forceinline__ void bulk_st(void* dst, uint32_t src, uint32_t bytes) {
  asm volatile("cp.async.bulk.global.shared::cta.bulk_group [%0], [%1], %2;" ::"l"(dst), "r"(src), "r"(bytes) : "memory");
}
__device__ __forceinline__ void tma2d_st(const CUtensorMap* m, int c0, int c1, uint32_t src) {
  asm volatile("cp.async.bulk.tensor.2d.global.shared::cta.bulk_group [%0, {%2, %3}], [%1];"
               ::"l"(m), "r"(src), "r"(c0), "r"(c1) : "memory");
}
__device__ __forceinline__ void bulk_commit_wait() {
  asm volatile("cp.async.bulk.commit_group;\ncp.async.bulk.wait_group.read 0;" ::: "memory");
}
__device__ __forceinline__ uint32_t mapa(uint32_t a, uint32_t cta) {
  uint32_t r;
  asm("mapa.shared::cluster.u32 %0, %1, %2;" : "=r"(r) : "r"(a), "r"(cta));
  return r;
}
__device__ __forceinline__ void st_async4(uint32_t dst, float a, float b, float c, float d, uint32_t bar) {
  asm volatile("st.async.shared::cluster.mbarrier::complete_tx::bytes.v4.f32 [%0], {%1, %2, %3, %4}, [%5];"
               ::"r"(dst), "f"(a), "f"(b), "f"(c), "f"(d), "r"(bar) : "memory");
}
__device__ __forceinline__ void st_async4u(uint32_t dst, uint32_t a, uint32_t b, uint32_t c, uint32_t d, uint32_t bar) {
  asm volatile("st.async.shared::cluster.mbarrier::complete_tx::bytes.v4.b32 [%0], {%1, %2, %3, %4}, [%5];"
               ::"r"(dst), "r"(a), "r"(b), "r"(c), "r"(d), "r"(bar) : "memory");
}
#define SEND8(dst, a, o, bar) st_async4u(dst, pack_bf16(a[o], a[(o) + 1]), pack_bf16(a[(o) + 2], a[(o) + 3]), \
                                         pack_bf16(a[(o) + 4], a[(o) + 5]), pack_bf16(a[(o) + 6], a[(o) + 7]), bar)
__device__ __forceinline__ void fence_async() { asm volatile("fence.proxy.async.shared::cta;" ::: "memory"); }
__device__ __forceinline__ void prefetch_map(const CUtensorMap* m) {
  asm volatile("prefetch.tensormap [%0];" ::"l"(m) : "memory");
}
__device__ __forceinline__ bool elect_one() {
  uint32_t p;
  asm volatile("{\n.reg .pred q;\nelect.sync _|q, 0xffffffff;\nselp.u32 %0, 1, 0, q;\n}" : "=r"(p));
  return p;
}
__device__ __forceinline__ void pdl_wait() { asm volatile("griddepcontrol.wait;" ::: "memory"); }
__device__ __forceinline__ void pdl_trigger() { asm volatile("griddepcontrol.launch_dependents;" ::: "memory"); }
__device__ __forceinline__ void bar_sync(int id, int n) { asm volatile("bar.sync %0, %1;" ::"r"(id), "r"(n) : "memory"); }
__device__ __forceinline__ void bar_arrive(int id, int n) { asm volatile("bar.arrive %0, %1;" ::"r"(id), "r"(n) : "memory"); }
#define WG_FENCE() asm volatile("wgmma.fence.sync.aligned;" ::: "memory")
#define WG_COMMIT() asm volatile("wgmma.commit_group.sync.aligned;" ::: "memory")
#define WG_WAIT(n) asm volatile("wgmma.wait_group.sync.aligned %0;" ::"n"(n) : "memory")
__device__ __forceinline__ uint64_t mkdesc(uint32_t addr, uint32_t lbo, uint32_t sbo, uint32_t sw) {
  return (uint64_t)((addr & 0x3FFFF) >> 4) | ((uint64_t)(lbo >> 4) << 16) | ((uint64_t)(sbo >> 4) << 32) |
         ((uint64_t)sw << 62);
}
template <int N> __device__ __forceinline__ void fence_regs(float (&r)[N]) {
#pragma unroll
  for (int i = 0; i < N; i++) asm volatile("" : "+f"(r[i])::"memory");
}
__device__ __forceinline__ uint32_t pack_bf16(float lo, float hi) {
  uint32_t r;
  asm("cvt.rn.bf16x2.f32 %0, %1, %2;" : "=r"(r) : "f"(hi), "f"(lo));
  return r;
}
__device__ __forceinline__ float bf_lo(uint32_t v) { return __uint_as_float(v << 16); }
__device__ __forceinline__ float bf_hi(uint32_t v) { return __uint_as_float(v & 0xffff0000u); }
__device__ __forceinline__ float ex2(float x) {
  float y;
  asm("ex2.approx.ftz.f32 %0, %1;" : "=f"(y) : "f"(x));
  return y;
}
__device__ __forceinline__ uint4 ldg_nc(const void* p) {
  uint4 v;
  asm volatile("ld.global.nc.L1::no_allocate.v4.u32 {%0, %1, %2, %3}, [%4];"
               : "=r"(v.x), "=r"(v.y), "=r"(v.z), "=r"(v.w) : "l"(p));
  return v;
}

__device__ __forceinline__ uint4 ld_relaxed(const uint4* p) {
  uint64_t a, b;
  asm volatile("ld.relaxed.gpu.global.v2.u64 {%0, %1}, [%2];" : "=l"(a), "=l"(b) : "l"(p) : "memory");
  return make_uint4((uint32_t)a, (uint32_t)(a >> 32), (uint32_t)b, (uint32_t)(b >> 32));
}
__device__ __forceinline__ void st_relaxed(uint4* p, float x, float y, uint32_t tag) {
  const uint64_t a = ((uint64_t)tag << 32) | __float_as_uint(x), b = ((uint64_t)tag << 32) | __float_as_uint(y);
  asm volatile("st.relaxed.gpu.global.v2.u64 [%0], {%1, %2};" ::"l"(p), "l"(a), "l"(b) : "memory");
}
__device__ __forceinline__ void tma4d(uint32_t dst, const CUtensorMap* m, int c2, int c3, uint32_t bar) {
  asm volatile("cp.async.bulk.tensor.4d.shared::cluster.global.mbarrier::complete_tx::bytes [%0], [%1, {%3, %3, %4, %5}], [%2];"
               ::"r"(dst), "l"(m), "r"(bar), "r"(0), "r"(c2), "r"(c3) : "memory");
}
#define ACC8(a, v) do { a[0] += bf_lo(v.x); a[1] += bf_hi(v.x); a[2] += bf_lo(v.y); a[3] += bf_hi(v.y); \
                        a[4] += bf_lo(v.z); a[5] += bf_hi(v.z); a[6] += bf_lo(v.w); a[7] += bf_hi(v.w); } while (0)

__device__ __forceinline__ void wgmma_ss_n224(float (&d)[112], uint64_t da, uint64_t db, int sd) {
  asm volatile("{\n.reg .pred p;\nsetp.ne.b32 p, %114, 0;\n"
      "wgmma.mma_async.sync.aligned.m64n224k16.f32.bf16.bf16 {"
      "%0, %1, %2, %3, %4, %5, %6, %7, %8, %9, %10, %11, %12, %13, %14, %15, "
      "%16, %17, %18, %19, %20, %21, %22, %23, %24, %25, %26, %27, %28, %29, %30, %31, "
      "%32, %33, %34, %35, %36, %37, %38, %39, %40, %41, %42, %43, %44, %45, %46, %47, "
      "%48, %49, %50, %51, %52, %53, %54, %55, %56, %57, %58, %59, %60, %61, %62, %63, "
      "%64, %65, %66, %67, %68, %69, %70, %71, %72, %73, %74, %75, %76, %77, %78, %79, "
      "%80, %81, %82, %83, %84, %85, %86, %87, %88, %89, %90, %91, %92, %93, %94, %95, "
      "%96, %97, %98, %99, %100, %101, %102, %103, %104, %105, %106, %107, %108, %109, %110, %111"
      "}, %112, %113, p, 1, 1, 0, 1;\n}\n"
    : "+f"(d[0]), "+f"(d[1]), "+f"(d[2]), "+f"(d[3]), "+f"(d[4]), "+f"(d[5]), "+f"(d[6]), "+f"(d[7]),
      "+f"(d[8]), "+f"(d[9]), "+f"(d[10]), "+f"(d[11]), "+f"(d[12]), "+f"(d[13]), "+f"(d[14]), "+f"(d[15]),
      "+f"(d[16]), "+f"(d[17]), "+f"(d[18]), "+f"(d[19]), "+f"(d[20]), "+f"(d[21]), "+f"(d[22]), "+f"(d[23]),
      "+f"(d[24]), "+f"(d[25]), "+f"(d[26]), "+f"(d[27]), "+f"(d[28]), "+f"(d[29]), "+f"(d[30]), "+f"(d[31]),
      "+f"(d[32]), "+f"(d[33]), "+f"(d[34]), "+f"(d[35]), "+f"(d[36]), "+f"(d[37]), "+f"(d[38]), "+f"(d[39]),
      "+f"(d[40]), "+f"(d[41]), "+f"(d[42]), "+f"(d[43]), "+f"(d[44]), "+f"(d[45]), "+f"(d[46]), "+f"(d[47]),
      "+f"(d[48]), "+f"(d[49]), "+f"(d[50]), "+f"(d[51]), "+f"(d[52]), "+f"(d[53]), "+f"(d[54]), "+f"(d[55]),
      "+f"(d[56]), "+f"(d[57]), "+f"(d[58]), "+f"(d[59]), "+f"(d[60]), "+f"(d[61]), "+f"(d[62]), "+f"(d[63]),
      "+f"(d[64]), "+f"(d[65]), "+f"(d[66]), "+f"(d[67]), "+f"(d[68]), "+f"(d[69]), "+f"(d[70]), "+f"(d[71]),
      "+f"(d[72]), "+f"(d[73]), "+f"(d[74]), "+f"(d[75]), "+f"(d[76]), "+f"(d[77]), "+f"(d[78]), "+f"(d[79]),
      "+f"(d[80]), "+f"(d[81]), "+f"(d[82]), "+f"(d[83]), "+f"(d[84]), "+f"(d[85]), "+f"(d[86]), "+f"(d[87]),
      "+f"(d[88]), "+f"(d[89]), "+f"(d[90]), "+f"(d[91]), "+f"(d[92]), "+f"(d[93]), "+f"(d[94]), "+f"(d[95]),
      "+f"(d[96]), "+f"(d[97]), "+f"(d[98]), "+f"(d[99]), "+f"(d[100]), "+f"(d[101]), "+f"(d[102]), "+f"(d[103]),
      "+f"(d[104]), "+f"(d[105]), "+f"(d[106]), "+f"(d[107]), "+f"(d[108]), "+f"(d[109]), "+f"(d[110]), "+f"(d[111])
    : "l"(da), "l"(db), "r"(sd));
}
__device__ __forceinline__ void wgmma_ss_n208(float (&d)[104], uint64_t da, uint64_t db, int sd) {
  asm volatile("{\n.reg .pred p;\nsetp.ne.b32 p, %106, 0;\n"
      "wgmma.mma_async.sync.aligned.m64n208k16.f32.bf16.bf16 {"
      "%0, %1, %2, %3, %4, %5, %6, %7, %8, %9, %10, %11, %12, %13, %14, %15, "
      "%16, %17, %18, %19, %20, %21, %22, %23, %24, %25, %26, %27, %28, %29, %30, %31, "
      "%32, %33, %34, %35, %36, %37, %38, %39, %40, %41, %42, %43, %44, %45, %46, %47, "
      "%48, %49, %50, %51, %52, %53, %54, %55, %56, %57, %58, %59, %60, %61, %62, %63, "
      "%64, %65, %66, %67, %68, %69, %70, %71, %72, %73, %74, %75, %76, %77, %78, %79, "
      "%80, %81, %82, %83, %84, %85, %86, %87, %88, %89, %90, %91, %92, %93, %94, %95, "
      "%96, %97, %98, %99, %100, %101, %102, %103"
      "}, %104, %105, p, 1, 1, 0, 1;\n}\n"
    : "+f"(d[0]), "+f"(d[1]), "+f"(d[2]), "+f"(d[3]), "+f"(d[4]), "+f"(d[5]), "+f"(d[6]), "+f"(d[7]),
      "+f"(d[8]), "+f"(d[9]), "+f"(d[10]), "+f"(d[11]), "+f"(d[12]), "+f"(d[13]), "+f"(d[14]), "+f"(d[15]),
      "+f"(d[16]), "+f"(d[17]), "+f"(d[18]), "+f"(d[19]), "+f"(d[20]), "+f"(d[21]), "+f"(d[22]), "+f"(d[23]),
      "+f"(d[24]), "+f"(d[25]), "+f"(d[26]), "+f"(d[27]), "+f"(d[28]), "+f"(d[29]), "+f"(d[30]), "+f"(d[31]),
      "+f"(d[32]), "+f"(d[33]), "+f"(d[34]), "+f"(d[35]), "+f"(d[36]), "+f"(d[37]), "+f"(d[38]), "+f"(d[39]),
      "+f"(d[40]), "+f"(d[41]), "+f"(d[42]), "+f"(d[43]), "+f"(d[44]), "+f"(d[45]), "+f"(d[46]), "+f"(d[47]),
      "+f"(d[48]), "+f"(d[49]), "+f"(d[50]), "+f"(d[51]), "+f"(d[52]), "+f"(d[53]), "+f"(d[54]), "+f"(d[55]),
      "+f"(d[56]), "+f"(d[57]), "+f"(d[58]), "+f"(d[59]), "+f"(d[60]), "+f"(d[61]), "+f"(d[62]), "+f"(d[63]),
      "+f"(d[64]), "+f"(d[65]), "+f"(d[66]), "+f"(d[67]), "+f"(d[68]), "+f"(d[69]), "+f"(d[70]), "+f"(d[71]),
      "+f"(d[72]), "+f"(d[73]), "+f"(d[74]), "+f"(d[75]), "+f"(d[76]), "+f"(d[77]), "+f"(d[78]), "+f"(d[79]),
      "+f"(d[80]), "+f"(d[81]), "+f"(d[82]), "+f"(d[83]), "+f"(d[84]), "+f"(d[85]), "+f"(d[86]), "+f"(d[87]),
      "+f"(d[88]), "+f"(d[89]), "+f"(d[90]), "+f"(d[91]), "+f"(d[92]), "+f"(d[93]), "+f"(d[94]), "+f"(d[95]),
      "+f"(d[96]), "+f"(d[97]), "+f"(d[98]), "+f"(d[99]), "+f"(d[100]), "+f"(d[101]), "+f"(d[102]), "+f"(d[103])
    : "l"(da), "l"(db), "r"(sd));
}
__device__ __forceinline__ void wgmma_ss_n168(float (&d)[84], uint64_t da, uint64_t db, int sd) {
  asm volatile("{\n.reg .pred p;\nsetp.ne.b32 p, %86, 0;\n"
      "wgmma.mma_async.sync.aligned.m64n168k16.f32.bf16.bf16 {"
      "%0, %1, %2, %3, %4, %5, %6, %7, %8, %9, %10, %11, %12, %13, %14, %15, "
      "%16, %17, %18, %19, %20, %21, %22, %23, %24, %25, %26, %27, %28, %29, %30, %31, "
      "%32, %33, %34, %35, %36, %37, %38, %39, %40, %41, %42, %43, %44, %45, %46, %47, "
      "%48, %49, %50, %51, %52, %53, %54, %55, %56, %57, %58, %59, %60, %61, %62, %63, "
      "%64, %65, %66, %67, %68, %69, %70, %71, %72, %73, %74, %75, %76, %77, %78, %79, "
      "%80, %81, %82, %83"
      "}, %84, %85, p, 1, 1, 0, 1;\n}\n"
    : "+f"(d[0]), "+f"(d[1]), "+f"(d[2]), "+f"(d[3]), "+f"(d[4]), "+f"(d[5]), "+f"(d[6]), "+f"(d[7]),
      "+f"(d[8]), "+f"(d[9]), "+f"(d[10]), "+f"(d[11]), "+f"(d[12]), "+f"(d[13]), "+f"(d[14]), "+f"(d[15]),
      "+f"(d[16]), "+f"(d[17]), "+f"(d[18]), "+f"(d[19]), "+f"(d[20]), "+f"(d[21]), "+f"(d[22]), "+f"(d[23]),
      "+f"(d[24]), "+f"(d[25]), "+f"(d[26]), "+f"(d[27]), "+f"(d[28]), "+f"(d[29]), "+f"(d[30]), "+f"(d[31]),
      "+f"(d[32]), "+f"(d[33]), "+f"(d[34]), "+f"(d[35]), "+f"(d[36]), "+f"(d[37]), "+f"(d[38]), "+f"(d[39]),
      "+f"(d[40]), "+f"(d[41]), "+f"(d[42]), "+f"(d[43]), "+f"(d[44]), "+f"(d[45]), "+f"(d[46]), "+f"(d[47]),
      "+f"(d[48]), "+f"(d[49]), "+f"(d[50]), "+f"(d[51]), "+f"(d[52]), "+f"(d[53]), "+f"(d[54]), "+f"(d[55]),
      "+f"(d[56]), "+f"(d[57]), "+f"(d[58]), "+f"(d[59]), "+f"(d[60]), "+f"(d[61]), "+f"(d[62]), "+f"(d[63]),
      "+f"(d[64]), "+f"(d[65]), "+f"(d[66]), "+f"(d[67]), "+f"(d[68]), "+f"(d[69]), "+f"(d[70]), "+f"(d[71]),
      "+f"(d[72]), "+f"(d[73]), "+f"(d[74]), "+f"(d[75]), "+f"(d[76]), "+f"(d[77]), "+f"(d[78]), "+f"(d[79]),
      "+f"(d[80]), "+f"(d[81]), "+f"(d[82]), "+f"(d[83])
    : "l"(da), "l"(db), "r"(sd));
}
__device__ __forceinline__ void wgmma_ss_n160(float (&d)[80], uint64_t da, uint64_t db, int sd) {
  asm volatile("{\n.reg .pred p;\nsetp.ne.b32 p, %82, 0;\n"
      "wgmma.mma_async.sync.aligned.m64n160k16.f32.bf16.bf16 {"
      "%0, %1, %2, %3, %4, %5, %6, %7, %8, %9, %10, %11, %12, %13, %14, %15, "
      "%16, %17, %18, %19, %20, %21, %22, %23, %24, %25, %26, %27, %28, %29, %30, %31, "
      "%32, %33, %34, %35, %36, %37, %38, %39, %40, %41, %42, %43, %44, %45, %46, %47, "
      "%48, %49, %50, %51, %52, %53, %54, %55, %56, %57, %58, %59, %60, %61, %62, %63, "
      "%64, %65, %66, %67, %68, %69, %70, %71, %72, %73, %74, %75, %76, %77, %78, %79"
      "}, %80, %81, p, 1, 1, 0, 1;\n}\n"
    : "+f"(d[0]), "+f"(d[1]), "+f"(d[2]), "+f"(d[3]), "+f"(d[4]), "+f"(d[5]), "+f"(d[6]), "+f"(d[7]),
      "+f"(d[8]), "+f"(d[9]), "+f"(d[10]), "+f"(d[11]), "+f"(d[12]), "+f"(d[13]), "+f"(d[14]), "+f"(d[15]),
      "+f"(d[16]), "+f"(d[17]), "+f"(d[18]), "+f"(d[19]), "+f"(d[20]), "+f"(d[21]), "+f"(d[22]), "+f"(d[23]),
      "+f"(d[24]), "+f"(d[25]), "+f"(d[26]), "+f"(d[27]), "+f"(d[28]), "+f"(d[29]), "+f"(d[30]), "+f"(d[31]),
      "+f"(d[32]), "+f"(d[33]), "+f"(d[34]), "+f"(d[35]), "+f"(d[36]), "+f"(d[37]), "+f"(d[38]), "+f"(d[39]),
      "+f"(d[40]), "+f"(d[41]), "+f"(d[42]), "+f"(d[43]), "+f"(d[44]), "+f"(d[45]), "+f"(d[46]), "+f"(d[47]),
      "+f"(d[48]), "+f"(d[49]), "+f"(d[50]), "+f"(d[51]), "+f"(d[52]), "+f"(d[53]), "+f"(d[54]), "+f"(d[55]),
      "+f"(d[56]), "+f"(d[57]), "+f"(d[58]), "+f"(d[59]), "+f"(d[60]), "+f"(d[61]), "+f"(d[62]), "+f"(d[63]),
      "+f"(d[64]), "+f"(d[65]), "+f"(d[66]), "+f"(d[67]), "+f"(d[68]), "+f"(d[69]), "+f"(d[70]), "+f"(d[71]),
      "+f"(d[72]), "+f"(d[73]), "+f"(d[74]), "+f"(d[75]), "+f"(d[76]), "+f"(d[77]), "+f"(d[78]), "+f"(d[79])
    : "l"(da), "l"(db), "r"(sd));
}
__device__ __forceinline__ void wgmma_ss_n88(float (&d)[44], uint64_t da, uint64_t db, int sd) {
  asm volatile("{\n.reg .pred p;\nsetp.ne.b32 p, %46, 0;\n"
      "wgmma.mma_async.sync.aligned.m64n88k16.f32.bf16.bf16 {"
      "%0, %1, %2, %3, %4, %5, %6, %7, %8, %9, %10, %11, %12, %13, %14, %15, "
      "%16, %17, %18, %19, %20, %21, %22, %23, %24, %25, %26, %27, %28, %29, %30, %31, "
      "%32, %33, %34, %35, %36, %37, %38, %39, %40, %41, %42, %43"
      "}, %44, %45, p, 1, 1, 0, 1;\n}\n"
    : "+f"(d[0]), "+f"(d[1]), "+f"(d[2]), "+f"(d[3]), "+f"(d[4]), "+f"(d[5]), "+f"(d[6]), "+f"(d[7]),
      "+f"(d[8]), "+f"(d[9]), "+f"(d[10]), "+f"(d[11]), "+f"(d[12]), "+f"(d[13]), "+f"(d[14]), "+f"(d[15]),
      "+f"(d[16]), "+f"(d[17]), "+f"(d[18]), "+f"(d[19]), "+f"(d[20]), "+f"(d[21]), "+f"(d[22]), "+f"(d[23]),
      "+f"(d[24]), "+f"(d[25]), "+f"(d[26]), "+f"(d[27]), "+f"(d[28]), "+f"(d[29]), "+f"(d[30]), "+f"(d[31]),
      "+f"(d[32]), "+f"(d[33]), "+f"(d[34]), "+f"(d[35]), "+f"(d[36]), "+f"(d[37]), "+f"(d[38]), "+f"(d[39]),
      "+f"(d[40]), "+f"(d[41]), "+f"(d[42]), "+f"(d[43])
    : "l"(da), "l"(db), "r"(sd));
}
__device__ __forceinline__ void wgmma_ss_n80(float (&d)[40], uint64_t da, uint64_t db, int sd) {
  asm volatile("{\n.reg .pred p;\nsetp.ne.b32 p, %42, 0;\n"
      "wgmma.mma_async.sync.aligned.m64n80k16.f32.bf16.bf16 {"
      "%0, %1, %2, %3, %4, %5, %6, %7, %8, %9, %10, %11, %12, %13, %14, %15, "
      "%16, %17, %18, %19, %20, %21, %22, %23, %24, %25, %26, %27, %28, %29, %30, %31, "
      "%32, %33, %34, %35, %36, %37, %38, %39"
      "}, %40, %41, p, 1, 1, 0, 1;\n}\n"
    : "+f"(d[0]), "+f"(d[1]), "+f"(d[2]), "+f"(d[3]), "+f"(d[4]), "+f"(d[5]), "+f"(d[6]), "+f"(d[7]),
      "+f"(d[8]), "+f"(d[9]), "+f"(d[10]), "+f"(d[11]), "+f"(d[12]), "+f"(d[13]), "+f"(d[14]), "+f"(d[15]),
      "+f"(d[16]), "+f"(d[17]), "+f"(d[18]), "+f"(d[19]), "+f"(d[20]), "+f"(d[21]), "+f"(d[22]), "+f"(d[23]),
      "+f"(d[24]), "+f"(d[25]), "+f"(d[26]), "+f"(d[27]), "+f"(d[28]), "+f"(d[29]), "+f"(d[30]), "+f"(d[31]),
      "+f"(d[32]), "+f"(d[33]), "+f"(d[34]), "+f"(d[35]), "+f"(d[36]), "+f"(d[37]), "+f"(d[38]), "+f"(d[39])
    : "l"(da), "l"(db), "r"(sd));
}
__device__ __forceinline__ void wgmma_rs_n128(float (&d)[64], uint32_t a0, uint32_t a1, uint32_t a2, uint32_t a3,
                                  uint64_t db, int sd) {
  asm volatile("{\n.reg .pred p;\nsetp.ne.b32 p, %69, 0;\n"
      "wgmma.mma_async.sync.aligned.m64n128k16.f32.bf16.bf16 {"
      "%0, %1, %2, %3, %4, %5, %6, %7, %8, %9, %10, %11, %12, %13, %14, %15, "
      "%16, %17, %18, %19, %20, %21, %22, %23, %24, %25, %26, %27, %28, %29, %30, %31, "
      "%32, %33, %34, %35, %36, %37, %38, %39, %40, %41, %42, %43, %44, %45, %46, %47, "
      "%48, %49, %50, %51, %52, %53, %54, %55, %56, %57, %58, %59, %60, %61, %62, %63"
      "}, {%64, %65, %66, %67}, %68, p, 1, 1, 0;\n}\n"
    : "+f"(d[0]), "+f"(d[1]), "+f"(d[2]), "+f"(d[3]), "+f"(d[4]), "+f"(d[5]), "+f"(d[6]), "+f"(d[7]),
      "+f"(d[8]), "+f"(d[9]), "+f"(d[10]), "+f"(d[11]), "+f"(d[12]), "+f"(d[13]), "+f"(d[14]), "+f"(d[15]),
      "+f"(d[16]), "+f"(d[17]), "+f"(d[18]), "+f"(d[19]), "+f"(d[20]), "+f"(d[21]), "+f"(d[22]), "+f"(d[23]),
      "+f"(d[24]), "+f"(d[25]), "+f"(d[26]), "+f"(d[27]), "+f"(d[28]), "+f"(d[29]), "+f"(d[30]), "+f"(d[31]),
      "+f"(d[32]), "+f"(d[33]), "+f"(d[34]), "+f"(d[35]), "+f"(d[36]), "+f"(d[37]), "+f"(d[38]), "+f"(d[39]),
      "+f"(d[40]), "+f"(d[41]), "+f"(d[42]), "+f"(d[43]), "+f"(d[44]), "+f"(d[45]), "+f"(d[46]), "+f"(d[47]),
      "+f"(d[48]), "+f"(d[49]), "+f"(d[50]), "+f"(d[51]), "+f"(d[52]), "+f"(d[53]), "+f"(d[54]), "+f"(d[55]),
      "+f"(d[56]), "+f"(d[57]), "+f"(d[58]), "+f"(d[59]), "+f"(d[60]), "+f"(d[61]), "+f"(d[62]), "+f"(d[63])
    : "r"(a0), "r"(a1), "r"(a2), "r"(a3), "l"(db), "r"(sd));
}
__device__ __forceinline__ void wgmma_rs_n24(float (&d)[12], uint32_t a0, uint32_t a1, uint32_t a2, uint32_t a3,
                                  uint64_t db, int sd) {
  asm volatile("{\n.reg .pred p;\nsetp.ne.b32 p, %17, 0;\n"
      "wgmma.mma_async.sync.aligned.m64n24k16.f32.bf16.bf16 {"
      "%0, %1, %2, %3, %4, %5, %6, %7, %8, %9, %10, %11"
      "}, {%12, %13, %14, %15}, %16, p, 1, 1, 1;\n}\n"
    : "+f"(d[0]), "+f"(d[1]), "+f"(d[2]), "+f"(d[3]), "+f"(d[4]), "+f"(d[5]), "+f"(d[6]), "+f"(d[7]),
      "+f"(d[8]), "+f"(d[9]), "+f"(d[10]), "+f"(d[11])
    : "r"(a0), "r"(a1), "r"(a2), "r"(a3), "l"(db), "r"(sd));
}

constexpr int KST = 4;
constexpr int K1_ST = 4, K1_STAGE = 45056;
constexpr int K1_SMEM = K1_ST * K1_STAGE + 640   + 1536   + 2560   + 128;

__device__ __forceinline__ float2 row_stats(uint4 v0, uint4 v1, uint4 v2) {
  const uint32_t wd[12] = {v0.x, v0.y, v0.z, v0.w, v1.x, v1.y, v1.z, v1.w, v2.x, v2.y, v2.z, v2.w};
  float sx = 0.f, sq = 0.f;
#pragma unroll
  for (int e = 0; e < 12; e++) {
    const float lo = bf_lo(wd[e]), hi = bf_hi(wd[e]);
    sx += lo + hi; sq = fmaf(lo, lo, fmaf(hi, hi, sq));
  }
#pragma unroll
  for (int o = 16; o; o >>= 1) { sx += __shfl_xor_sync(~0u, sx, o); sq += __shfl_xor_sync(~0u, sq, o); }
  const float mean = sx * (1.f / D_);
  return make_float2(rsqrtf(fmaxf(sq * (1.f / D_) - mean * mean, 0.f) + 1e-5f), mean);
}

__global__ void __launch_bounds__(512, 1)
k1_qkv(const __grid_constant__ CUtensorMap tmx, const __grid_constant__ CUtensorMap tmw,
       const bf16* __restrict__ x, const bf16* __restrict__ w) {
  extern __shared__ __align__(1024) uint8_t sm[];
  float* cs = (float*)(sm + K1_ST * K1_STAGE);
  float2* rowab = (float2*)(sm + K1_ST * K1_STAGE + 640);
  float* red = (float*)(sm + K1_ST * K1_STAGE + 2176);
  const uint32_t sbase = smem_u32(sm);
  const uint32_t fullb = sbase + K1_ST * K1_STAGE + 4736, emptyb = fullb + 8 * K1_ST;
  const int tid = threadIdx.x, lane = tid & 31;
  const int warp = __shfl_sync(~0u, tid >> 5, 0);
  const int m = blockIdx.x / 12, n = blockIdx.x - m * 12;

  if (warp == 12) {
    if (lane == 0) {
      prefetch_map(&tmx); prefetch_map(&tmw);
      for (int i = 0; i < K1_ST; i++) { mbar_init(fullb + 8 * i, 1); mbar_init(emptyb + 8 * i, 3); }
      asm volatile("fence.mbarrier_init.release.cluster;" ::: "memory");
    }
    __syncwarp();
    bar_arrive(4, 512);
#pragma unroll 1
    for (int kt = 0; kt < 10; kt++) {
      const int s = kt % K1_ST;
      const uint32_t sa = sbase + s * K1_STAGE;
      if (kt >= K1_ST) mbar_wait(emptyb + 8 * s, ((kt / K1_ST) - 1) & 1);
      if (elect_one()) {
        mbar_expect(fullb + 8 * s, K1_STAGE);
        tma2d(sa, &tmx, kt * 64, m * 192, fullb + 8 * s);
#pragma unroll
        for (int j = 0; j < 5; j++) tma2d(sa + 24576 + j * 4096, &tmw, n * 160 + j * 32, kt * 64, fullb + 8 * s);
      }
      if (kt == K1_ST - 1) pdl_trigger();
    }
    __syncwarp();
  } else if (warp > 12) {
    const int t96 = tid - 416;
    const uint32_t tag = __ldcg(&g_epoch) + 1;
    bar_sync(4, 512);
    mbar_wait(fullb, 0);
    if (m < 10) {
      const int ck = t96 % 20, rg = min(t96 / 20, 3);
      uint4 wv[16];
#pragma unroll
      for (int i = 0; i < 16; i++) wv[i] = ldg_nc(w + (size_t)(m * 64 + rg * 16 + i) * 1920 + n * 160 + ck * 8);
      float acc8[8];
#pragma unroll
      for (int i = 0; i < 8; i++) acc8[i] = 0.f;
#pragma unroll
      for (int i = 0; i < 16; i++) ACC8(acc8, wv[i]);
      *(float4*)&red[rg * 160 + ck * 8] = make_float4(acc8[0], acc8[1], acc8[2], acc8[3]);
      *(float4*)&red[rg * 160 + ck * 8 + 4] = make_float4(acc8[4], acc8[5], acc8[6], acc8[7]);
      bar_sync(1, 96);
      if (t96 < 80) {
        const float2 p0 = *(const float2*)&red[t96 * 2], p1 = *(const float2*)&red[160 + t96 * 2];
        const float2 p2 = *(const float2*)&red[320 + t96 * 2], p3 = *(const float2*)&red[480 + t96 * 2];
        st_relaxed(&g_cpart[(m * 12 + n) * 80 + t96], (p0.x + p1.x) + (p2.x + p3.x), (p0.y + p1.y) + (p2.y + p3.y), tag);
      }
    }
    bool ok = false;
    for (int it = 0; it < 64 && !ok; it++) {
      uint4 p[10], st[2];
#pragma unroll
      for (int k = 0; k < 10; k++) p[k] = ld_relaxed(&g_cpart[(k * 12 + n) * 80 + min(t96, 79)]);
#pragma unroll
      for (int k = 0; k < 2; k++) st[k] = ld_relaxed(&g_rowstat[min(m * 192 + k * 96 + t96, S_ - 1)]);
      ok = true;
      float s0 = 0.f, s1 = 0.f;
#pragma unroll
      for (int k = 0; k < 10; k++) {
        ok = ok && p[k].y == tag && p[k].w == tag;
        s0 += __uint_as_float(p[k].x); s1 += __uint_as_float(p[k].z);
      }
      if (t96 < 80) *(float2*)&cs[t96 * 2] = make_float2(s0, s1);
#pragma unroll
      for (int k = 0; k < 2; k++) {
        ok = ok && st[k].y == tag && st[k].w == tag;
        rowab[k * 96 + t96] = make_float2(__uint_as_float(st[k].x), -__uint_as_float(st[k].x) * __uint_as_float(st[k].z));
      }
      ok = __all_sync(~0u, ok);
      if (!ok) __nanosleep(300);
    }
    if (!ok) {
      const int c2 = min(t96, 79);
      float s0 = 0.f, s1 = 0.f;
#pragma unroll 1
      for (int k = 0; k < D_; k++) {
        const uint32_t v = *(const uint32_t*)(w + (size_t)k * 1920 + n * 160 + c2 * 2);
        s0 += bf_lo(v); s1 += bf_hi(v);
      }
      if (t96 < 80) *(float2*)&cs[t96 * 2] = make_float2(s0, s1);
#pragma unroll 1
      for (int i = 0; i < 64; i++) {
        const int r = (i >> 5) * 96 + (t96 & ~31) + (i & 31);
        const bf16* xr = x + (size_t)min(m * 192 + r, S_ - 1) * D_ + lane * 8;
        const float2 st = row_stats(ldg_nc(xr), ldg_nc(xr + 256), lane < 16 ? ldg_nc(xr + 512) : make_uint4(0u, 0u, 0u, 0u));
        if (lane == 0) rowab[r] = make_float2(st.x, -st.x * st.y);
      }
    }
    __syncwarp();
    bar_arrive(2, 96 + 384);
    __syncwarp();
  } else {
    float acc[80];
    const uint64_t da0 = mkdesc(sbase + (warp >> 2) * 8192, 16, 1024, 1);
    const uint64_t db0 = mkdesc(sbase + 24576, 4096, 512, 2);
    const uint32_t tag = __ldcg(&g_epoch) + 1;
    const int srow = m * 192 + n * 16 + warp * 2;
    const bool dostat = warp < 8 && srow < S_;
    uint4 xv[2][3];
    bar_sync(4, 512);
#pragma unroll
    for (int kt = 0; kt < 10; kt++) {
      const int s = kt % K1_ST;
      mbar_wait(fullb + 8 * s, (kt / K1_ST) & 1);
      const uint64_t da = da0 + s * (K1_STAGE >> 4), db = db0 + s * (K1_STAGE >> 4);
      WG_FENCE();
#pragma unroll
      for (int k = 0; k < 4; k++) wgmma_ss_n160(acc, da + k * 2, db + k * 64, (kt | k) != 0);
      WG_COMMIT();
      if (kt > 0) {
        WG_WAIT(1);
        if (kt - 1 + K1_ST < 10 && (tid & 127) == 0) mbar_arrive(emptyb + 8 * ((kt - 1) % K1_ST));
      }
      if (kt == 0) {
#pragma unroll
        for (int i = 0; i < 2; i++) {
          const bf16* xr = x + (size_t)min(srow + i, S_ - 1) * D_ + lane * 8;
          xv[i][0] = xv[i][1] = xv[i][2] = make_uint4(0u, 0u, 0u, 0u);
          if (dostat) { xv[i][0] = ldg_nc(xr); xv[i][1] = ldg_nc(xr + 256); }
          if (dostat && lane < 16) xv[i][2] = ldg_nc(xr + 512);
        }
      }
      if ((kt == KST || kt == KST + 1) && dostat) {
        const float2 st = row_stats(xv[kt - KST][0], xv[kt - KST][1], xv[kt - KST][2]);
        if (lane == 0) st_relaxed(&g_rowstat[srow + kt - KST], st.x, st.y, tag);
      }
      __syncwarp();
    }
    WG_WAIT(0);
    fence_regs(acc);
    bar_sync(2, 96 + 384);
    const int row0 = m * 192 + warp * 16;
    if (row0 < S_) {
      const int g = lane >> 2, c = lane & 3, sec = n >> 2, grp = (row0 & 127) >> 3;
      const bool lo = c < 2;
      const float2 ab0 = rowab[warp * 16 + g], ab1 = rowab[warp * 16 + g + 8];
      const bool p0 = sec == 1 && ((POLY_MASK >> grp) & 1), p1 = sec == 1 && ((POLY_MASK >> (grp + 1)) & 1);
      const uint32_t padqv = sec == 0 ? (c == 2 ? 0x3F803F80u : 0x00003F80u) : (sec == 2 && c == 2 ? 0x00003F80u : 0u);
      const uint32_t padk = c == 2 ? 0x4A7A4B00u : 0x00004653u;
      const uint32_t pad0 = p0 ? padk : padqv, pad1 = p1 ? padk : padqv;
      const float f0 = sec == 0 ? QSCALE : (p0 ? 32768.f : 1.f), f1 = sec == 0 ? QSCALE : (p1 ? 32768.f : 1.f);
      const float a0 = ab0.x * f0, b0 = ab0.y * f0, a1 = ab1.x * f1, b1 = ab1.y * f1;
      const float r0 = p0 ? 9.313225746154785e-10f : 1.f, r1 = p1 ? 9.313225746154785e-10f : 1.f;
      const int cst = sec == 1 ? 2048 : 128, gst = sec == 1 ? 128 : 384;
      uint8_t* pe = (uint8_t*)g_qkv + (size_t)(n * 8) * HEAD_IMG + (row0 >> 7) * 6144 + grp * gst + lane * 4;
      uint8_t* pe1 = pe + cst;
      uint8_t* pe2 = pe1 + cst;
      uint8_t* pf = pe + gst;
      uint8_t* pf1 = pf + cst;
      uint8_t* pf2 = pf1 + cst;
      uint32_t u[20], v[20];
#pragma unroll
      for (int hp = 0; hp < 4; hp++) {
#pragma unroll
        for (int j = hp * 5; j < hp * 5 + 5; j++) {
          const float2 t = *(const float2*)&cs[j * 8 + c * 2];
          u[j] = pack_bf16(fmaf(acc[4 * j], a0, b0 * t.x), fmaf(acc[4 * j + 1], a0, b0 * t.y));
          v[j] = pack_bf16(fmaf(acc[4 * j + 2], a1, b1 * t.x), fmaf(acc[4 * j + 3], a1, b1 * t.y));
        }
        constexpr int HE = HEAD_IMG;
        const int oe = hp * 2 * HE, oo = oe + HE, j = hp * 5;
        *(uint32_t*)(pe + oe) = u[j];      *(uint32_t*)(pf + oe) = v[j];
        *(uint32_t*)(pe1 + oe) = u[j + 1]; *(uint32_t*)(pf1 + oe) = v[j + 1];
        *(uint32_t*)(pe2 + oe) = lo ? u[j + 2] : pad0; *(uint32_t*)(pf2 + oe) = lo ? v[j + 2] : pad1;
        *(uint32_t*)(pe + oo) = __shfl_xor_sync(~0u, lo ? u[j + 3] : u[j + 2], 2);
        *(uint32_t*)(pf + oo) = __shfl_xor_sync(~0u, lo ? v[j + 3] : v[j + 2], 2);
        *(uint32_t*)(pe1 + oo) = __shfl_xor_sync(~0u, lo ? u[j + 4] : u[j + 3], 2);
        *(uint32_t*)(pf1 + oo) = __shfl_xor_sync(~0u, lo ? v[j + 4] : v[j + 3], 2);
        const uint32_t tu = __shfl_xor_sync(~0u, u[j + 4], 2), tv = __shfl_xor_sync(~0u, v[j + 4], 2);
        *(uint32_t*)(pe2 + oo) = lo ? tu : pad0; *(uint32_t*)(pf2 + oo) = lo ? tv : pad1;
      }
      {
        float nm = 0.f;
#pragma unroll
        for (int hp = 0; hp < 4; hp++) {
          float sq[2][5];
#pragma unroll
          for (int i = 0; i < 5; i++) {
            const uint32_t x = u[hp * 5 + i], y = v[hp * 5 + i];
            sq[0][i] = fmaf(bf_lo(x), bf_lo(x), bf_hi(x) * bf_hi(x));
            sq[1][i] = fmaf(bf_lo(y), bf_lo(y), bf_hi(y) * bf_hi(y));
          }
          const float e0 = (sq[0][0] + sq[0][1] + (lo ? sq[0][2] : 0.f)) * r0, e1 = (sq[1][0] + sq[1][1] + (lo ? sq[1][2] : 0.f)) * r1;
          const float o0 = (sq[0][3] + sq[0][4] + (lo ? 0.f : sq[0][2])) * r0, o1 = (sq[1][3] + sq[1][4] + (lo ? 0.f : sq[1][2])) * r1;
          const float k0 = (lo ? e0 : o0) + __shfl_xor_sync(~0u, lo ? o0 : e0, 2);
          const float k1 = (lo ? e1 : o1) + __shfl_xor_sync(~0u, lo ? o1 : e1, 2);
          const float z = ((c & 1) ? k1 : k0) + __shfl_xor_sync(~0u, (c & 1) ? k0 : k1, 1);
          const uint32_t em = __reduce_max_sync(~0u, lo ? __float_as_uint(z) : 0u), om = __reduce_max_sync(~0u, lo ? 0u : __float_as_uint(z));
          if ((lane >> 1) == hp) nm = __uint_as_float((lane & 1) ? om : em);
        }
        if (lane < 8) g_nrm[(n * 8 + lane) * 128 + (row0 >> 4)] = nm;
      }
    }
  }
}

constexpr int K2_SMEM = 2 * HEAD_IMG + 2 * 6144 + 2 * 10240 + 160 + 96;

__device__ __forceinline__ uint64_t desc64(uint32_t lo, uint32_t hi) {
  uint64_t d;
  asm("mov.b64 %0, {%1, %2};" : "=l"(d) : "r"(lo), "r"(hi));
  return d;
}
__device__ __forceinline__ uint32_t exp_pair(bool poly, float a, float b, uint32_t mk) {
  if (poly) {
    const uint32_t pk = __byte_perm(__float_as_uint(a), __float_as_uint(b), 0x6521);
    uint32_t m, q;
    asm("lop3.b32 %0, %1, %2, 0x3f803f80, 0xEA;" : "=r"(m) : "r"(pk), "r"(mk));
    asm("fma.rn.bf16x2 %0, %1, %1, %2;" : "=r"(q) : "r"(m), "r"(0x40014001u));
    return pk - m + q;
  }
  return pack_bf16(ex2(a), ex2(b));
}
constexpr int PV_GR = 4;
__device__ __forceinline__ void exp_pv(const float (&s)[64], float (&o)[12], uint64_t dv, uint32_t mk) {
#pragma unroll
  for (int k0 = 0; k0 < 8; k0 += PV_GR) {
    uint32_t p[4 * PV_GR];
#pragma unroll
    for (int i = 0; i < 4 * PV_GR; i++)
      p[i] = exp_pair((POLY_MASK >> (k0 * 2 + i / 2)) & 1, s[k0 * 8 + 2 * i], s[k0 * 8 + 2 * i + 1], mk);
    WG_FENCE();
#pragma unroll
    for (int k = 0; k < PV_GR; k++)
      wgmma_rs_n24(o, p[4 * k], p[4 * k + 1], p[4 * k + 2], p[4 * k + 3], dv + (k0 + k) * 48, 1);
  }
}
__device__ __forceinline__ void load_q(uint32_t (&q)[6], const uint8_t* p) {
  q[0] = __ldcg((const uint32_t*)p);         q[1] = __ldcg((const uint32_t*)(p + 384));
  q[2] = __ldcg((const uint32_t*)(p + 128)); q[3] = __ldcg((const uint32_t*)(p + 512));
  q[4] = __ldcg((const uint32_t*)(p + 256)); q[5] = __ldcg((const uint32_t*)(p + 640));
}
__device__ __forceinline__ float rcp(float x) {
  float y;
  asm("rcp.approx.ftz.f32 %0, %1;" : "=f"(y) : "f"(x));
  return y;
}
__device__ __forceinline__ int img_off(int chunk) { return chunk * 2048; }
__device__ __forceinline__ void store_o(const float (&o)[12], int tile) {
  int tid, bid;
  asm volatile("mov.u32 %0, %%tid.x;" : "=r"(tid));
  asm volatile("mov.u32 %0, %%ctaid.x;" : "=r"(bid));
  const int head = bid >> 2;
  uint8_t* dst = (uint8_t*)g_o + ((bid & 3) * 4 + (tile >> 1)) * 163840 + (tile & 1) * 1024 + ((tid >> 5) & 3) * 256 + (tid & 31) * 4;
  const int oc = (head >> 1) * 5 + (head & 1) * 2;
  const int o0 = img_off(oc), o1 = img_off(oc + 1), o2 = img_off((head >> 1) * 5 + 4) + (head & 1) * 8;
  const float i0 = rcp(__shfl_sync(~0u, o[8], 2, 4)), i1 = rcp(__shfl_sync(~0u, o[10], 2, 4));
  *(uint32_t*)(dst + o0) = pack_bf16(o[0] * i0, o[1] * i0); *(uint32_t*)(dst + o0 + 128) = pack_bf16(o[2] * i1, o[3] * i1);
  *(uint32_t*)(dst + o1) = pack_bf16(o[4] * i0, o[5] * i0); *(uint32_t*)(dst + o1 + 128) = pack_bf16(o[6] * i1, o[7] * i1);
  if ((tid & 3) < 2) {
    *(uint32_t*)(dst + o2) = pack_bf16(o[8] * i0, o[9] * i0);
    *(uint32_t*)(dst + o2 + 128) = pack_bf16(o[10] * i1, o[11] * i1);
  }
}

struct Maps5 { CUtensorMap m[5]; };

__global__ void __launch_bounds__(512, 1)
k2_attn(const __grid_constant__ Maps5 maps, const bf16* __restrict__ wo, uint32_t mk) {
  const CUtensorMap* tmw = maps.m;
  extern __shared__ __align__(1024) uint8_t sm[];
  const uint32_t sbase = smem_u32(sm);
  float* part = (float*)(sm + 2 * HEAD_IMG);
  const uint32_t rbuf = sbase + 2 * HEAD_IMG + 2 * 6144;
  const uint32_t kvb = rbuf + 2 * 10240;
  const uint32_t partb = kvb + 128, rbar = kvb + 144;
  const int tid = threadIdx.x, lane = tid & 31;
  const int warp = __shfl_sync(~0u, tid >> 5, 0);
  const int head = blockIdx.x >> 2, qb = blockIdx.x & 3;

  if (tid == 0) {
    for (int i = 0; i < 16; i++) mbar_init(kvb + 8 * i, 1);
    mbar_init(partb, 128); mbar_init(partb + 8, 128); mbar_init(rbar, 1); mbar_init(rbar + 8, 1);
    asm volatile("fence.mbarrier_init.release.cluster;" ::: "memory");
  }
  __syncthreads();

  if (warp >= 12) {
    asm volatile("setmaxnreg.dec.sync.aligned.u32 32;");
    if (warp == 12) {
      const uint8_t* kimg = (const uint8_t*)g_qkv + (size_t)(32 + head) * HEAD_IMG;
      if (elect_one()) {
#pragma unroll
        for (int b = 0; b < 16; b++) mbar_expect(kvb + 8 * b, 12288);
      }
      pdl_wait();
#pragma unroll 1
      for (int b = 0; b < 16; b++) {
        if (elect_one()) {
          bulk_ld(sbase + b * 6144, kimg + b * 6144, 6144, kvb + 8 * b);
          bulk_ld(sbase + HEAD_IMG + b * 6144, kimg + 32 * HEAD_IMG + b * 6144, 6144, kvb + 8 * b);
        }
        if (b >= 2) mbar_wait(kvb + 8 * (b - 1), 0);
      }
      pdl_trigger();
    }
    if (warp > 12) {
      const int t96 = tid - 416, ck = min(t96, 79), nt = ck / 10;
      float* red = (float*)(sm + K2_SMEM - 96);
#pragma unroll 1
      for (int i = 0; i < 5; i++) {
        const int k = blockIdx.x * 5 + i, pr = k / 40, r = k - pr * 40;
        const uint4 v = ldg_nc(wo + (pr * 40 + (r < 16 ? r : (r < 32 ? r + 4 : (r < 36 ? r - 16 : r)))) * D_ + ck * 8);
        g_wo[((nt * 10 + (k >> 6)) * 10 + ck - nt * 10) * 64 + (k & 63)] = v;
        float t = ((bf_lo(v.x) + bf_hi(v.x)) + (bf_lo(v.y) + bf_hi(v.y))) + ((bf_lo(v.z) + bf_hi(v.z)) + (bf_lo(v.w) + bf_hi(v.w)));
        if (t96 >= 80) t = 0.f;
#pragma unroll
        for (int o = 16; o; o >>= 1) t += __shfl_xor_sync(~0u, t, o);
        if (lane == 0) red[(t96 >> 5) * 8 + i] = t;
      }
      bar_sync(1, 96);
      if (t96 < 5) {
        const float mu = (red[t96] + red[8 + t96] + red[16 + t96]) * (1.f / D_);
        const float hi = bf_lo(pack_bf16(mu, 0.f));
        g_wm[blockIdx.x * 5 + t96] = make_uint4(pack_bf16(hi, mu - hi), 0u, 0u, 0u);
      }
    }
    if (tid == 384) {
      if (blockIdx.x == 0) g_epoch = g_epoch + 1;
      mbar_wait(kvb + 8 * 15, 0);
      uint8_t* pdst = nullptr;
      uint32_t pbytes = 0;
#pragma unroll 1
      for (int i = 0; i < 8; i++) {
        const int p = blockIdx.x + 128 * i;
        uint8_t* dst = nullptr;
        uint32_t bytes = 0;
        if (i < 7 && p < 856) {
          asm volatile("cp.async.bulk.wait_group.read 0;" ::: "memory");
          const CUtensorMap* tm;
          int c1, c2;
          if (p < 640) {
            const int nt = p / 80, r = p - nt * 80, ph = r / 40, st = (r - ph * 40) >> 1, up = r & 1;
            bytes = ph ? 6656 : 7168;
            dst = (uint8_t*)g_wgu + nt * 552960 + ph * 286720 + st * 2 * bytes + up * (bytes >> 1);
            tm = &tmw[ph * 2 + up]; c1 = ph ? 112 + nt * 13 : nt * 14; c2 = st * 2;
          } else {
            const int nk = p - 640, nt = nk / 27;
            bytes = 10240;
            dst = (uint8_t*)g_wd + (size_t)nk * 10240;
            tm = &tmw[4]; c1 = nt * 10; c2 = nk - nt * 27;
          }
          mbar_expect(rbar + 8 * (i & 1), bytes);
          tma4d(rbuf + (i & 1) * 10240, tm, c1, c2, rbar + 8 * (i & 1));
        }
        if (pbytes) {
          mbar_wait(rbar + 8 * ((i - 1) & 1), ((i - 1) >> 1) & 1);
          if (pbytes == 10240) {
            bulk_st(pdst, rbuf + ((i - 1) & 1) * 10240, pbytes);
          } else {
            bulk_st(pdst, rbuf + ((i - 1) & 1) * 10240, pbytes >> 1);
            bulk_st(pdst + pbytes, rbuf + ((i - 1) & 1) * 10240 + (pbytes >> 1), pbytes >> 1);
          }
          asm volatile("cp.async.bulk.commit_group;" ::: "memory");
        }
        pdst = dst; pbytes = bytes;
      }
      asm volatile("cp.async.bulk.wait_group.read 0;" ::: "memory");
    }
  } else {
    asm volatile("setmaxnreg.inc.sync.aligned.u32 160;");
    const int wg = warp >> 2;
    const uint8_t* qthr = (const uint8_t*)g_qkv + (size_t)head * HEAD_IMG + qb * 64 * 384 + (warp & 3) * 768 + lane * 4;
    const uint32_t klo0 = ((sbase & 0x3FFFF) >> 4) | (128u << 16), vlo0 = (((sbase + HEAD_IMG) & 0x3FFFF) >> 4) | (24u << 16);
    constexpr uint64_t KSTEP2 = (uint64_t)(int64_t)(256 - (128 << 16));
    constexpr uint64_t KV2K = 384 - (HEAD_IMG >> 4) + (104 << 16);
    const int nun = wg == 1 ? 4 : 3;
    uint32_t utile = wg == 0 ? 0x210u : (wg == 1 ? 0x4235u : 0x576u);
    uint32_t ubeg = wg == 0 ? 0u : (wg == 1 ? 0x0b00u : 0x600u);
    uint32_t ulen = wg == 0 ? 0x0b1010u : (wg == 1 ? 0x10051006u : 0x0a1010u);
    pdl_wait();
    uint32_t q[6];
    load_q(q, qthr + (utile & 15) * 3072);
    bool fast;
    {
      const uint4 kn = __ldcg((const uint4*)&g_nrm[(32 + head) * 128 + lane * 4]);
      const uint4 vn = __ldcg((const uint4*)&g_nrm[(64 + head) * 128 + lane * 4]);
      const float qv = __ldcg(&g_nrm[head * 128 + qb * 32 + lane]);
      const float k2 = __uint_as_float(__reduce_max_sync(~0u, max(max(kn.x, kn.y), max(kn.z, kn.w))));
      const float v2 = __uint_as_float(__reduce_max_sync(~0u, max(max(vn.x, vn.y), max(vn.z, vn.w))));
      const float q2 = __uint_as_float(__reduce_max_sync(~0u, __float_as_uint(qv)));
      fast = q2 * k2 <= 3400.f && v2 < 1e24f && v2 > 1e-24f;
    }
    if (fast) {
#pragma unroll 1
      for (int u = 0; u < nun; u++) {
        const uint32_t b0 = ubeg & 15;
        const bool wt = u == 0 || (wg == 1 && u == 1);
        float s[64], o[12];
#pragma unroll
        for (int i = 0; i < 12; i++) o[i] = 0.f;
        uint32_t vlo = vlo0 + b0 * 384, kb = kvb + b0 * 8;
        const uint32_t vend = vlo + ((ulen & 255) - 1) * 384;
        if (wt) mbar_wait(kb, 0);
        fence_regs(o);
        WG_FENCE();
        wgmma_rs_n128(s, q[0], q[1], q[2], q[3], desc64(klo0 + b0 * 384, 8), 0);
        wgmma_rs_n128(s, q[4], q[5], 0, 0, desc64(klo0 + b0 * 384, 8) + KSTEP2, 1);
        WG_COMMIT();
#pragma unroll 1
        for (; vlo != vend; vlo += 384) {
          if (wt) { kb += 8; mbar_wait(kb, 0); }
          WG_WAIT(0);
          fence_regs(s); fence_regs(o);
          const uint64_t dv = desc64(vlo, 8);
          exp_pv(s, o, dv, mk);
          wgmma_rs_n128(s, q[0], q[1], q[2], q[3], dv + KV2K, 0);
          wgmma_rs_n128(s, q[4], q[5], 0, 0, dv + (KV2K + KSTEP2), 1);
          WG_COMMIT();
        }
        WG_WAIT(0);
        fence_regs(s); fence_regs(o);
        if (u + 1 < nun) load_q(q, qthr + ((utile >> 4) & 15) * 3072);
        exp_pv(s, o, desc64(vlo, 8), mk);
        WG_COMMIT();
        WG_WAIT(0);
        fence_regs(o);
        if (wg == 1 && !(u & 1)) {
          float4* pp = (float4*)(part + u * 768) + (tid & 127);
          pp[0] = make_float4(o[0], o[1], o[2], o[3]);
          pp[128] = make_float4(o[4], o[5], o[6], o[7]);
          pp[256] = make_float4(o[8], o[9], o[10], o[11]);
          mbar_arrive(partb + 4 * u);
        } else {
          if (wg != 1 && u == 2) {
            const int pi = wg == 0 ? 1 : 0;
            mbar_wait(partb + 8 * pi, 0);
            const float4* pp = (const float4*)(part + pi * 1536) + (tid & 127);
            const float4 x0 = pp[0], x1 = pp[128], x2 = pp[256];
            o[0] += x0.x; o[1] += x0.y; o[2] += x0.z; o[3] += x0.w; o[4] += x1.x; o[5] += x1.y;
            o[6] += x1.z; o[7] += x1.w; o[8] += x2.x; o[9] += x2.y; o[10] += x2.z; o[11] += x2.w;
          }
          store_o(o, utile & 15);
        }
        utile >>= 4; ubeg >>= 4; ulen >>= 8;
      }
    } else {
#pragma unroll 1
      for (int tile = wg; tile < 8; tile += 3) {
        load_q(q, qthr + tile * 3072);
        if ((lane & 3) >= 2) { q[4] = 0; q[5] = 0; }
        float o[12], m0 = -INFINITY, m1 = -INFINITY;
#pragma unroll
        for (int i = 0; i < 12; i++) o[i] = 0.f;
#pragma unroll 1
        for (int b = 0; b < 16; b++) {
          float s[64];
          mbar_wait(kvb + 8 * b, 0);
          WG_FENCE();
          wgmma_rs_n128(s, q[0], q[1], q[2], q[3], desc64(klo0 + b * 384, 8), 0);
          wgmma_rs_n128(s, q[4], q[5], 0, 0, desc64(klo0 + b * 384, 8) + KSTEP2, 1);
          WG_COMMIT();
          WG_WAIT(0);
          fence_regs(s);
          float x0 = m0, x1 = m1;
#pragma unroll
          for (int j = 0; j < 16; j++) {
            if ((POLY_MASK >> j) & 1) {
#pragma unroll
              for (int i = 0; i < 4; i++) s[4 * j + i] *= (1.f / 32768.f);
            }
            x0 = fmaxf(x0, fmaxf(s[4 * j], s[4 * j + 1]));
            x1 = fmaxf(x1, fmaxf(s[4 * j + 2], s[4 * j + 3]));
          }
          x0 = fmaxf(x0, __shfl_xor_sync(~0u, x0, 1)); x0 = fmaxf(x0, __shfl_xor_sync(~0u, x0, 2));
          x1 = fmaxf(x1, __shfl_xor_sync(~0u, x1, 1)); x1 = fmaxf(x1, __shfl_xor_sync(~0u, x1, 2));
          const float al0 = ex2(m0 - x0), al1 = ex2(m1 - x1);
          m0 = x0; m1 = x1;
#pragma unroll
          for (int i = 0; i < 12; i++) o[i] *= (i & 2) ? al1 : al0;
          uint32_t p[32];
#pragma unroll
          for (int i = 0; i < 32; i++) {
            const float mm = (i & 1) ? m1 : m0;
            p[i] = pack_bf16(ex2(s[2 * i] - mm), ex2(s[2 * i + 1] - mm));
          }
          fence_regs(o);
          WG_FENCE();
#pragma unroll
          for (int k = 0; k < 8; k++)
            wgmma_rs_n24(o, p[4 * k], p[4 * k + 1], p[4 * k + 2], p[4 * k + 3], desc64(vlo0 + b * 384 + k * 48, 8), 1);
          WG_COMMIT();
          WG_WAIT(0);
          fence_regs(o);
        }
        store_o(o, tile);
      }
    }
  }
}

constexpr int K3_ST = 4, K3_STAGE = 37888, K3_NB = 4, K3_NT = 6;
constexpr int K3_SMEM = K3_ST * K3_STAGE + 24576 + 20480 + 256;

template <int N> struct Acc { float v[N]; };

__global__ void __cluster_dims__(2, 1, 1) __launch_bounds__(288, 1)
k3_proj(const __grid_constant__ CUtensorMap tmx) {
  extern __shared__ __align__(1024) uint8_t sm[];
  const uint32_t sbase = smem_u32(sm);
  const uint8_t* xch = sm + K3_ST * K3_STAGE;
  const uint8_t* res = sm + K3_ST * K3_STAGE + 24576;
  const uint32_t fullb = smem_u32(res) + 20480, emptyb = fullb + 8 * K3_ST, resb = emptyb + 8 * K3_ST, xchb = resb + 8;
  const int tid = threadIdx.x, lane = tid & 31;
  const int warp = __shfl_sync(~0u, tid >> 5, 0);
  const int rank = blockIdx.x & 1;
  const int n = blockIdx.x & 7, m = blockIdx.x >> 3;
  if (warp == 8) {
    if (elect_one()) {
#pragma unroll
      for (int i = 0; i < K3_ST; i++) { mbar_init(fullb + 8 * i, 1); mbar_init(emptyb + 8 * i, 2); }
      mbar_init(resb, 1); mbar_init(xchb, 1);
      mbar_expect(xchb, 24576);
      asm volatile("fence.mbarrier_init.release.cluster;" ::: "memory");
    }
    __syncwarp();
  }
  cluster_arrive();
  if (warp == 8) {
    const uint8_t* wk = (const uint8_t*)g_wo + n * 102400;
    const uint8_t* ws = (const uint8_t*)g_wo + (n ^ 1) * 102400;
    const uint8_t* ab = (const uint8_t*)g_o + m * 163840;
    prefetch_map(&tmx);
    pdl_wait();
#pragma unroll 1
    for (int i = 0; i < K3_NT; i++) {
      const int s = i % K3_ST, kt = i < K3_NB ? i + rank * K3_NT : i;
      const uint32_t sa = sbase + s * K3_STAGE, fb = fullb + 8 * s;
      if (i >= K3_ST) mbar_wait(emptyb + 8 * s, 0);
      if (elect_one()) {
        mbar_expect(fb, i < K3_NB ? 37888 : 27648);
        bulk_ld(sa, ab + kt * 16384, 16384, fb);
        bulk_ld(sa + 16384, wk + kt * 10240, 10240, fb);
        bulk_ld(sa + 26624, (const uint8_t*)g_wm + kt * 1024, 1024, fb);
        if (i < K3_NB) bulk_ld(sa + 27648, ws + kt * 10240, 10240, fb);
        if (i == K3_ST - 1) {
          mbar_expect(resb, 20480);
          tma2d(smem_u32(res), &tmx, n * 80, m * 128, resb);
          tma2d(smem_u32(res) + 10240, &tmx, n * 80, m * 128 + 64, resb);
        }
      }
      if (i == 0) pdl_trigger();
    }
    cluster_wait();
  } else {
    const int g = lane >> 2, c = lane & 3;
    const int row = m * 128 + warp * 16 + g;
    float mu0 = __uint_as_float(__ldcg(&g_rowstat[row].z)), mu1 = __uint_as_float(__ldcg(&g_rowstat[row + 8].z));
    float acc[84];
    float (&keep)[44] = ((Acc<44>*)acc)->v;
    const uint64_t da0 = mkdesc(sbase + (warp >> 2) * 1024, 2048, 128, 0);
    const uint64_t db0 = mkdesc(sbase + 16384, 128, 1024, 0);
    cluster_wait();
#pragma unroll 1
    for (int i = 0; i < K3_NB; i++) {
      mbar_wait(fullb + 8 * i, 0);
      const uint64_t da = da0 + i * (K3_STAGE >> 4), db = db0 + i * (K3_STAGE >> 4);
      WG_FENCE();
#pragma unroll
      for (int k = 0; k < 4; k++) wgmma_ss_n168(acc, da + k * 256, db + k * 16, (i | k) != 0);
      WG_COMMIT();
      if (i > 0) {
        WG_WAIT(1);
        if (i - 1 + K3_ST < K3_NT && (tid & 127) == 0) mbar_arrive(emptyb + 8 * (i - 1));
      }
    }
    const uint32_t rx = mapa(smem_u32(xch) + tid * 16, rank ^ 1), rb = mapa(xchb, rank ^ 1);
    WG_WAIT(0);
    fence_regs(acc);
    st_async4(rx, acc[40], acc[41], acc[42], acc[43], rb);
#pragma unroll
    for (int i = K3_NB; i < K3_NT; i++) {
      const int s = i % K3_ST;
      mbar_wait(fullb + 8 * s, 1);
      const uint64_t da = da0 + s * (K3_STAGE >> 4), db = db0 + s * (K3_STAGE >> 4);
      WG_FENCE();
#pragma unroll
      for (int k = 0; k < 4; k++) wgmma_ss_n88(keep, da + k * 256, db + k * 16, 1);
      WG_COMMIT();
#pragma unroll
      for (int j = (i - K3_NB) * 3; j < (i - K3_NB) * 3 + 3; j++)
        if (j < 5) SEND8(rx + (j + 1) * 4096, acc, 44 + 8 * j, rb);
    }
    const uint8_t* sp = res + (warp * 16 + g) * 160 + c * 4;
    uint32_t rv[20];
    mbar_wait(resb, 0);
#pragma unroll
    for (int j = 0; j < 10; j++) {
      rv[2 * j] = *(const uint32_t*)(sp + j * 16);
      rv[2 * j + 1] = *(const uint32_t*)(sp + 1280 + j * 16);
    }
    WG_WAIT(0);
    fence_regs(keep);
    mbar_wait(xchb, 0);
    const uint8_t* xp = xch + tid * 16;
    {
      const float4 p = *(const float4*)xp;
      mu0 += __shfl_sync(~0u, (keep[40] + p.x) + (keep[41] + p.y), 0, 4);
      mu1 += __shfl_sync(~0u, (keep[42] + p.z) + (keep[43] + p.w), 0, 4);
    }
    uint8_t* himg = (uint8_t*)g_h + m * 163840 + img_off(n * 10) + warp * 256 + lane * 4;
    float q0 = 0.f, q1 = 0.f;
#pragma unroll
    for (int j = 0; j < 10; j++) {
      const uint2 p = *(const uint2*)(xp + ((j >> 1) + 1) * 4096 + (j & 1) * 8);
      const float x0 = (keep[4 * j] + bf_lo(p.x)) + (bf_lo(rv[2 * j]) - mu0), x1 = (keep[4 * j + 1] + bf_hi(p.x)) + (bf_hi(rv[2 * j]) - mu0);
      const float y0 = (keep[4 * j + 2] + bf_lo(p.y)) + (bf_lo(rv[2 * j + 1]) - mu1), y1 = (keep[4 * j + 3] + bf_hi(p.y)) + (bf_hi(rv[2 * j + 1]) - mu1);
      *(uint32_t*)(himg + img_off(j)) = pack_bf16(x0, x1);
      *(uint32_t*)(himg + img_off(j) + 128) = pack_bf16(y0, y1);
      q0 = fmaf(x0, x0, fmaf(x1, x1, q0)); q1 = fmaf(y0, y0, fmaf(y1, y1, q1));
    }
    q0 += __shfl_xor_sync(~0u, q0, 1); q0 += __shfl_xor_sync(~0u, q0, 2);
    q1 += __shfl_xor_sync(~0u, q1, 1); q1 += __shfl_xor_sync(~0u, q1, 2);
    if (c < 2) g_hpart[n * S_ + row + c * 8] = c ? q1 : q0;
    if (n == 0 && c < 2) g_hmean[row + c * 8] = c ? mu1 : mu0;
  }
}

constexpr int P3_NB = 12, P3_NT = 15;
constexpr int K4_G = 2, K4_NS = 4, K4_NJ = 20;
constexpr int K4_RB = 163840, K4_BST = 7168 * K4_G, K4_XCH = 147456, K4_STG = K4_XCH + 20480, K4_BAR = K4_RB + K4_NS * K4_BST;
constexpr int K4_SMEM = K4_BAR + 384;

__device__ __forceinline__ void wait_flags(const uint4* f, uint32_t tag, uint32_t need, uint32_t& seen) {
  if ((seen & need) == need) return;
  for (uint32_t it = 0; (seen & need) != need; it++) {
    if (it > (1u << 20)) wait_timeout();
    if (it) __nanosleep(150);
    uint32_t v = 0;
    if ((threadIdx.x & 31) < 8) asm volatile("ld.acquire.gpu.global.u32 %0, [%1];" : "=r"(v) : "l"((const uint32_t*)f + (threadIdx.x & 7)) : "memory");
    seen = __ballot_sync(~0u, v == tag) & 255;
  }
  asm volatile("fence.proxy.async.global;" ::: "memory");
}

template <int MODE>
__global__ void __cluster_dims__(2, 1, 1) __launch_bounds__(384, 1)
k45_ffn(const __grid_constant__ CUtensorMap tmo) {
  extern __shared__ __align__(1024) uint8_t sm[];
  const uint32_t sbase = smem_u32(sm);
  const uint32_t afull = sbase + K4_BAR, bfull = afull + 80, bempty = bfull + 8 * K4_NS, full3 = bempty + 8 * K4_NS;
  const uint32_t empty3 = full3 + 32, afree = empty3 + 32, xchb = afree + 32, rdyb = xchb + 8;
  const int tid = threadIdx.x, lane = tid & 31;
  const int warp = __shfl_sync(~0u, tid >> 5, 0);
  const int rank = blockIdx.x & 1;
  const int n = blockIdx.x & 7, m = blockIdx.x >> 3;
  if (warp == 8) {
    if (elect_one()) {
#pragma unroll
      for (int i = 0; i < 10; i++) mbar_init(afull + 8 * i, 1);
#pragma unroll
      for (int i = 0; i < 4; i++) {
        mbar_init(bfull + 8 * i, 1); mbar_init(bempty + 8 * i, 2); mbar_init(full3 + 8 * i, 1); mbar_init(empty3 + 8 * i, 2);
        mbar_init(afree + 8 * i, 2);
      }
      mbar_init(xchb, 1); mbar_init(rdyb, 2);
      mbar_expect(xchb, 20480);
      asm volatile("fence.mbarrier_init.release.cluster;" ::: "memory");
    }
    __syncwarp();
  }
  cluster_arrive();
  if (warp >= 8) {
    if (warp != 8) cluster_wait();
    if (warp == 8) {
      const uint8_t* src = (const uint8_t*)g_wgu + n * 552960;
      const uint8_t* hb = (const uint8_t*)g_h + (size_t)m * 163840;
      int ka = 1;
#pragma unroll 1
      for (int j = 0; j < (MODE == 2 ? 0 : 40); j++) {
        const uint32_t s8 = (j & 3) * 8, sz = j < 20 ? 14336 : 13312;
        if (j == 1) {
          pdl_wait();
          if (elect_one()) { mbar_expect(afull, 16384); bulk_ld(sbase, hb, 16384, afull); }
        }
        if (j >= 4) mbar_wait(bempty + s8, ((j >> 2) - 1) & 1);
        if (elect_one()) {
          mbar_expect(bfull + s8, sz);
          bulk_ld(sbase + K4_RB + s8 * (K4_BST / 8), src, sz, bfull + s8);
          if (j >= 1 && ka < 10 && (j < 4 || (j & 1))) {
            mbar_expect(afull + 8 * ka, 16384);
            bulk_ld(sbase + ka * 16384, hb + ka * 16384, 16384, afull + 8 * ka);
          }
        }
        if (j >= 1 && (j < 4 || (j & 1))) ka++;
        src += sz;
      }
      cluster_wait();
    } else if (warp == 9) {
      prefetch_map(&tmo);
      const uint32_t tag = __ldcg(&g_epoch);
#pragma unroll 1
      for (int ph = 0; ph < (MODE == 2 ? 0 : 2); ph++) {
        bar_sync(5 + ph, 256 + 32);
        if (lane == 0) {
          asm volatile("st.release.gpu.global.u32 [%0], %1;" ::"l"((uint32_t*)&g_flag[ph * 32 + m * 2] + n), "r"(tag) : "memory");
        }
        __syncwarp();
      }
    } else {
      const uint8_t* wk = (const uint8_t*)g_wd + n * 276480;
      const uint8_t* ws = (const uint8_t*)g_wd + (n ^ 1) * 276480;
      const uint8_t* ab = (const uint8_t*)g_hh + (size_t)m * 442368;
      const uint32_t tag = __ldcg(&g_epoch);
      uint32_t seen = 0;
#pragma unroll 1
      for (int i = 0; i < (MODE == 1 ? 0 : P3_NT); i++) {
        const int kt = i < 7 ? rank * 7 + i : (i < P3_NB ? rank * (P3_NB - 7) + 7 + i : P3_NB + i);
        const uint32_t sa = sbase + (i & 3) * 36864, fb = full3 + 8 * (i & 3);
        if (warp == 11) {
          const int q = kt * 8 - (i < 7 ? 0 : 112), w = i < 7 ? 14 : 13;
          if (MODE == 0 && i == 0) mbar_wait(afull + 72, 0);
          if (i == 7) seen = 0;
          wait_flags(&g_flag[(i < 7 ? 0 : 32) + m * 2], tag, 1u << (q / w) | 1u << ((q + 7) / w), seen);
        }
        if (i < 4) { if (MODE == 0) mbar_wait(afree + 8 * i, 0); }
        else mbar_wait(empty3 + 8 * (i & 3), ((i >> 2) - 1) & 1);
        if (warp == 10) {
          if (elect_one()) {
            mbar_expect(fb, i < P3_NB ? 36864 : 26624);
            bulk_ld(sa + 16384, wk + kt * 10240, 10240, fb);
            if (i < P3_NB) bulk_ld(sa + 26624, ws + kt * 10240, 10240, fb);
          }
        } else {
          if (elect_one()) {
            bulk_ld(sa, ab + kt * 16384, 16384, fb);
          }
        }
      }
    }
  } else {
    const int wg = warp >> 2;
    const uint64_t da0 = mkdesc(sbase + wg * 1024, 2048, 128, 0);
    const uint64_t db0 = mkdesc(sbase + K4_RB, 128, 256, 0);
    cluster_wait();
    float acc[80];
    if constexpr (MODE != 2) {
    float a1[112], a2[104];
    int s = 0, ph = 0, sprev = 0;
#pragma unroll 1
    for (int j = 0; j < K4_NJ; j++) {
      if ((j * K4_G) % 4 == 0) mbar_wait(afull + 2 * K4_G * j, 0);
      mbar_wait(bfull + 8 * s, ph);
      const uint64_t da = da0 + j * K4_G * 256, db = db0 + s * (K4_BST >> 4);
      WG_FENCE();
#pragma unroll
      for (int k = 0; k < K4_G; k++) wgmma_ss_n224(a1, da + k * 256, db + k * 448, (j | k) != 0);
      WG_COMMIT();
      if (j > 0) {
        WG_WAIT(1);
        if ((tid & 127) == 0) mbar_arrive(bempty + 8 * sprev);
      }
      sprev = s;
      if (++s == K4_NS) { s = 0; ph ^= 1; }
    }
    uint8_t* hd = (uint8_t*)g_hh + (size_t)m * 442368 + warp * 256 + lane * 4;
    WG_WAIT(0);
    fence_regs(a1);
    if ((tid & 127) == 0) mbar_arrive(bempty + 8 * ((K4_NJ - 1) % K4_NS));
#define STORE_H(a, off, ptr, c) do { uint8_t* p_ = ptr; \
      *(uint32_t*)p_ = pack_bf16(a[4 * (c)] * a[off + 4 * (c)], a[4 * (c) + 1] * a[off + 1 + 4 * (c)]); \
      *(uint32_t*)(p_ + 128) = pack_bf16(a[4 * (c) + 2] * a[off + 2 + 4 * (c)], a[4 * (c) + 3] * a[off + 3 + 4 * (c)]); } while (0)
#pragma unroll
    for (int c = 0; c < 14; c++) STORE_H(a1, 56, hd + img_off(n * 14 + c), c);
    bar_arrive(5, 256 + 32);
#pragma unroll 1
    for (int j = 0; j < K4_NJ; j++) {
      mbar_wait(bfull + 8 * s, ph);
      const uint64_t da = da0 + j * K4_G * 256, db = db0 + s * (K4_BST >> 4);
      WG_FENCE();
#pragma unroll
      for (int k = 0; k < K4_G; k++) wgmma_ss_n208(a2, da + k * 256, db + k * 416, (j | k) != 0);
      WG_COMMIT();
      if (j > 0) {
        WG_WAIT(1);
        if (j <= K4_NJ - K4_NS && (tid & 127) == 0) mbar_arrive(bempty + 8 * sprev);
        if (j * K4_G >= 12 && ((j * K4_G) & 7) == 4 && (tid & 127) == 0) mbar_arrive(afree + (j * K4_G - 12));
      }
      sprev = s;
      if (++s == K4_NS) { s = 0; ph ^= 1; }
    }
    WG_WAIT(0);
    fence_regs(a2);
#pragma unroll
    for (int c = 0; c < 13; c++) STORE_H(a2, 52, hd + img_off(112 + n * 13 + c), c);
    bar_arrive(6, 256 + 32);
    }
    if constexpr (MODE != 1) {
    if ((tid & 127) == 0) mbar_arrive_cta(rdyb, rank ^ 1);
    float (&keep)[40] = ((Acc<40>*)acc)->v;
    const uint64_t db3 = mkdesc(sbase + 16384, 128, 1024, 0);
#pragma unroll 1
    for (int i = 0; i < P3_NB; i++) {
      mbar_wait(full3 + 8 * (i & 3), (i >> 2) & 1);
      const uint64_t da = da0 + (i & 3) * 2304, db = db3 + (i & 3) * 2304;
      WG_FENCE();
#pragma unroll
      for (int k = 0; k < 4; k++) wgmma_ss_n160(acc, da + k * 256, db + k * 16, (i | k) != 0);
      WG_COMMIT();
      if (i > 0) {
        WG_WAIT(1);
        if (i + 3 < P3_NT && (tid & 127) == 0) mbar_arrive(empty3 + 8 * ((i - 1) & 3));
      }
    }
    const int g = lane >> 2, c = lane & 3, row = m * 128 + warp * 16 + g;
    const uint8_t* himg = (const uint8_t*)g_h + (size_t)m * 163840 + warp * 256 + lane * 4;
    uint32_t rv[20];
    const float mu0 = __ldcg(&g_hmean[row]), mu1 = __ldcg(&g_hmean[row + 8]);
    float r0 = __ldcg(&g_hpart[c * 2 * S_ + row]) + __ldcg(&g_hpart[(c * 2 + 1) * S_ + row]);
    float r1 = __ldcg(&g_hpart[c * 2 * S_ + row + 8]) + __ldcg(&g_hpart[(c * 2 + 1) * S_ + row + 8]);
#pragma unroll
    for (int j = 0; j < 10; j++) {
      rv[2 * j] = __ldcg((const uint32_t*)(himg + img_off(n * 10 + j)));
      rv[2 * j + 1] = __ldcg((const uint32_t*)(himg + img_off(n * 10 + j) + 128));
    }
    const uint32_t rx = mapa(sbase + K4_XCH + tid * 16, rank ^ 1), rb = mapa(xchb, rank ^ 1);
    WG_WAIT(0);
    fence_regs(acc);
    mbar_wait(rdyb, 0);
#pragma unroll
    for (int i = P3_NB; i < P3_NT; i++) {
      mbar_wait(full3 + 8 * (i & 3), (i >> 2) & 1);
      const uint64_t da = da0 + (i & 3) * 2304, db = db3 + (i & 3) * 2304;
      WG_FENCE();
#pragma unroll
      for (int k = 0; k < 4; k++) wgmma_ss_n80(keep, da + k * 256, db + k * 16, 1);
      WG_COMMIT();
#pragma unroll
      for (int j = (i - P3_NB) * 3; j < (i - P3_NB) * 3 + 3; j++)
        if (j < 5) SEND8(rx + j * 4096, acc, 40 + 8 * j, rb);
    }
    r0 += __shfl_xor_sync(~0u, r0, 1); r1 += __shfl_xor_sync(~0u, r1, 1);
    r0 += __shfl_xor_sync(~0u, r0, 2); r1 += __shfl_xor_sync(~0u, r1, 2);
    r0 = rcp(r0 * (1.f / D_) + 1e-5f); r1 = rcp(r1 * (1.f / D_) + 1e-5f);
    asm volatile("" : "+f"(r0), "+f"(r1)::"memory");
    WG_WAIT(0);
    fence_regs(keep);
    mbar_wait(xchb, 0);
    uint8_t* sp = sm + K4_STG + (warp * 16 + g) * 160 + c * 4;
#pragma unroll
    for (int j = 0; j < 10; j++) {
      const uint2 p = *(const uint2*)(sm + K4_XCH + tid * 16 + (j >> 1) * 4096 + (j & 1) * 8);
      *(uint32_t*)(sp + j * 16) = pack_bf16(fmaf(keep[4 * j] + bf_lo(p.x), r0, bf_lo(rv[2 * j]) + mu0), fmaf(keep[4 * j + 1] + bf_hi(p.x), r0, bf_hi(rv[2 * j]) + mu0));
      *(uint32_t*)(sp + 1280 + j * 16) = pack_bf16(fmaf(keep[4 * j + 2] + bf_lo(p.y), r1, bf_lo(rv[2 * j + 1]) + mu1), fmaf(keep[4 * j + 3] + bf_hi(p.y), r1, bf_hi(rv[2 * j + 1]) + mu1));
    }
    fence_async();
    __syncwarp();
    if (elect_one()) {
      tma2d_st(&tmo, n * 80, m * 128 + warp * 16, sbase + K4_STG + warp * 2560);
      bulk_commit_wait();
    }
    __syncwarp();
    }
  }
}

typedef CUresult (*EncodeFn)(CUtensorMap*, CUtensorMapDataType, cuuint32_t, void*, const cuuint64_t*, const cuuint64_t*,
                             const cuuint32_t*, const cuuint32_t*, CUtensorMapInterleave, CUtensorMapSwizzle,
                             CUtensorMapL2promotion, CUtensorMapFloatOOBfill);

static CUtensorMap make_map(EncodeFn enc, const void* p, uint64_t inner, uint64_t outer, uint32_t box_inner,
                            uint32_t box_outer, CUtensorMapSwizzle swz) {
  CUtensorMap m;
  cuuint64_t gd[2] = {inner, outer};
  cuuint64_t gs[1] = {inner * 2};
  cuuint32_t bd[2] = {box_inner, box_outer};
  cuuint32_t es[2] = {1, 1};
  enc(&m, CU_TENSOR_MAP_DATA_TYPE_BFLOAT16, 2, (void*)p, gd, gs, bd, es, CU_TENSOR_MAP_INTERLEAVE_NONE, swz,
      CU_TENSOR_MAP_L2_PROMOTION_L2_256B, CU_TENSOR_MAP_FLOAT_OOB_FILL_NONE);
  return m;
}

static CUtensorMap make_map_img(EncodeFn enc, const void* p, uint64_t k, uint64_t n, uint32_t rows, uint32_t chunks,
                                uint32_t groups) {
  CUtensorMap m;
  cuuint64_t gd[4] = {8, rows, n / 8, k / rows};
  cuuint64_t gs[3] = {n * 2, 16, n * 2 * rows};
  cuuint32_t bd[4] = {8, rows, chunks, groups};
  cuuint32_t es[4] = {1, 1, 1, 1};
  enc(&m, CU_TENSOR_MAP_DATA_TYPE_BFLOAT16, 4, (void*)p, gd, gs, bd, es, CU_TENSOR_MAP_INTERLEAVE_NONE,
      CU_TENSOR_MAP_SWIZZLE_NONE, CU_TENSOR_MAP_L2_PROMOTION_L2_128B, CU_TENSOR_MAP_FLOAT_OOB_FILL_NONE);
  return m;
}

template <typename... KArgs, typename... Args>
static void launch(void (*k)(KArgs...), int grid, int threads, int smem, bool pdl, Args... args) {
  cudaLaunchConfig_t cfg = {};
  cfg.gridDim = dim3(grid);
  cfg.blockDim = dim3(threads);
  cfg.dynamicSmemBytes = smem;
  cfg.stream = cudaStreamPerThread;
  cudaLaunchAttribute at[1];
  at[0].id = cudaLaunchAttributeProgrammaticStreamSerialization;
  at[0].val.programmaticStreamSerializationAllowed = 1;
  cfg.attrs = at;
  cfg.numAttrs = pdl ? 1 : 0;
  cudaLaunchKernelEx(&cfg, k, KArgs(args)...);
}

extern "C" void kernel_launch(void* const* d_in, const int* in_sizes, int n_in, void* d_out, int out_size) {
  const bf16* x = (const bf16*)d_in[0];
  const bf16* wqkv = (const bf16*)d_in[1];
  const bf16* wo = (const bf16*)d_in[2];
  const bf16* wg = (const bf16*)d_in[4];
  const bf16* wu = (const bf16*)d_in[5];
  const bf16* wd = (const bf16*)d_in[6];

  static EncodeFn enc = nullptr;
  static bool fused = true;
  if (!enc) {
    void* fn = nullptr;
    cudaDriverEntryPointQueryResult qr;
    cudaGetDriverEntryPoint("cuTensorMapEncodeTiled", &fn, cudaEnableDefault, &qr);
    enc = (EncodeFn)fn;
    cudaFuncSetAttribute(k1_qkv, cudaFuncAttributeMaxDynamicSharedMemorySize, K1_SMEM);
    cudaFuncSetAttribute(k2_attn, cudaFuncAttributeMaxDynamicSharedMemorySize, K2_SMEM);
    cudaFuncSetAttribute(k3_proj, cudaFuncAttributeMaxDynamicSharedMemorySize, K3_SMEM);
    cudaFuncSetAttribute(k45_ffn<0>, cudaFuncAttributeMaxDynamicSharedMemorySize, K4_SMEM);
    cudaFuncSetAttribute(k45_ffn<1>, cudaFuncAttributeMaxDynamicSharedMemorySize, K4_SMEM);
    cudaFuncSetAttribute(k45_ffn<2>, cudaFuncAttributeMaxDynamicSharedMemorySize, K4_SMEM);
    cudaLaunchConfig_t cfg = {};
    cfg.gridDim = dim3(128); cfg.blockDim = dim3(384); cfg.dynamicSmemBytes = K4_SMEM;
    int clusters = 0;
    cudaOccupancyMaxActiveClusters(&clusters, k45_ffn<0>, &cfg);
    fused = clusters >= 64;
  }
  const CUtensorMap tmx = make_map(enc, x, D_, S_, 64, 192, CU_TENSOR_MAP_SWIZZLE_128B);
  const CUtensorMap tmw = make_map(enc, wqkv, 3 * D_, D_, 32, 64, CU_TENSOR_MAP_SWIZZLE_64B);
  const CUtensorMap tmxr = make_map(enc, x, D_, S_, 80, 64, CU_TENSOR_MAP_SWIZZLE_NONE);
  Maps5 maps;
  maps.m[0] = make_map_img(enc, wg, D_, F_, 16, 14, 2); maps.m[1] = make_map_img(enc, wu, D_, F_, 16, 14, 2);
  maps.m[2] = make_map_img(enc, wg, D_, F_, 16, 13, 2); maps.m[3] = make_map_img(enc, wu, D_, F_, 16, 13, 2);
  maps.m[4] = make_map_img(enc, wd, F_, D_, 64, 10, 1);
  const CUtensorMap tmout = make_map(enc, d_out, D_, S_, 80, 16, CU_TENSOR_MAP_SWIZZLE_NONE);

  launch(k1_qkv, 132, 512, K1_SMEM, false, tmx, tmw, x, wqkv);
  launch(k2_attn, 128, 512, K2_SMEM, true, maps, wo, 0x007f007fu);
  launch(k3_proj, 128, 288, K3_SMEM, true, tmxr);
  if (fused) {
    launch(k45_ffn<0>, 128, 384, K4_SMEM, true, tmout);
  } else {
    launch(k45_ffn<1>, 128, 384, K4_SMEM, true, tmout);
    launch(k45_ffn<2>, 128, 384, K4_SMEM, false, tmout);
  }
}
```
